```python
import torch

def _softmax(x, axis=-1):
    return torch.softmax(x, dim=axis)
def _gelu(x):
    return torch.nn.functional.gelu(x, approximate="tanh")
def _silu(x):
    return torch.nn.functional.silu(x)
def _sigmoid(x):
    return torch.sigmoid(x)
def _layernorm(x, axis=-1, eps=1e-5):
    m = x.mean(dim=axis, keepdim=True)
    v = x.var(dim=axis, keepdim=True, unbiased=False)
    return (x - m) / torch.sqrt(v + eps)
def _scatter_add(tgt, idx, src, axis=0):
    return tgt.clone().index_add_(axis, idx, src)
def _segment_sum(src, seg, n):
    out = torch.zeros((n,) + src.shape[1:], dtype=src.dtype)
    return out.index_add_(0, seg, src)
def _pad(x, pw):
    flat = tuple(v for pair in reversed(pw) for v in pair)
    return torch.nn.functional.pad(x, flat)

kernel_name = 'concat_heads__gqa_block_cached__mha_block_cached__near_ridge'

def setup_inputs():

    _w = (lambda a: (lambda t: t.to(torch.bfloat16) if t.is_floating_point() else t)(torch.as_tensor(a)))
    def _A_setup():
        B, Sq, D = 16, 160, 640
        Hq, Hkv, Sk, Dh = 32, 32, 512, 192
        assert Hq % Hkv == 0, (Hq, Hkv)
        return {
            "x": _w((lambda *s: torch.randn(*s, dtype=torch.bfloat16) * 0.8)(B, Sq, D)),
            "k_cache": _w((lambda *s: torch.randn(*s, dtype=torch.bfloat16) * 0.8)(B, Hkv, Sk, Dh)),
            "v_cache": _w((lambda *s: torch.randn(*s, dtype=torch.bfloat16) * 0.05)(B, Hkv, Sk, Dh)),
            "wq": _w((lambda *s: torch.randn(*s, dtype=torch.bfloat16) * 0.8)(D, Hq * Dh) * (D ** -0.5)),
            "wo": _w((lambda *s: torch.randn(*s, dtype=torch.bfloat16) * 0.05)(Hq * Dh, D) * ((Hq * Dh) ** -0.5)),
        }
    _A_in = _A_setup()

    def _B_setup():
        B, Sq, D = 16, 160, 640
        H, Sk, Dh = 32, 512, 192
        return {
            "x": _w((lambda *s: torch.randn(*s, dtype=torch.bfloat16) * 0.8)(B, Sq, D)),
            "k_cache": _w((lambda *s: torch.randn(*s, dtype=torch.bfloat16) * 0.8)(B, H, Sk, Dh)),
            "v_cache": _w((lambda *s: torch.randn(*s, dtype=torch.bfloat16) * 0.05)(B, H, Sk, Dh)),
            "wq": _w((lambda *s: torch.randn(*s, dtype=torch.bfloat16) * 0.8)(D, H * Dh) * (D ** -0.5)),
            "wo": _w((lambda *s: torch.randn(*s, dtype=torch.bfloat16) * 0.05)(H * Dh, D) * ((H * Dh) ** -0.5)),
        }
    _B_in = _B_setup()

    return {
        "A_x": _A_in["x"],
        "A_k_cache": _A_in["k_cache"],
        "A_v_cache": _A_in["v_cache"],
        "A_wq": _A_in["wq"],
        "A_wo": _A_in["wo"],
        "B_x": _B_in["x"],
        "B_k_cache": _B_in["k_cache"],
        "B_v_cache": _B_in["v_cache"],
        "B_wq": _B_in["wq"],
        "B_wo": _B_in["wo"],
    }

def reference(A_x, A_k_cache, A_v_cache, A_wq, A_wo, B_x, B_k_cache, B_v_cache, B_wq, B_wo):
    def _A_ref(x, k_cache, v_cache, wq, wo):
        B, Sq, D = x.shape
        Hq, Dh = 32, 192
        Hkv = k_cache.shape[1]
        rep = Hq // Hkv
        q = (lambda x, *d: x.permute(*d))((x @ wq).reshape(B, Sq, Hq, Dh), 0, 2, 1, 3)
        k = (lambda x, n, axis: torch.repeat_interleave(x, n, dim=axis))(k_cache, rep, axis=1)
        v = (lambda x, n, axis: torch.repeat_interleave(x, n, dim=axis))(v_cache, rep, axis=1)
        scores = torch.einsum("bhqd,bhkd->bhqk", q, k) * (Dh ** -0.5)
        p = _softmax(scores, axis=-1)
        o = torch.einsum("bhqk,bhkd->bhqd", p, v)
        return (lambda x, *d: x.permute(*d))(o, 0, 2, 1, 3).reshape(B, Sq, Hq * Dh) @ wo

    def _B_ref(x, k_cache, v_cache, wq, wo):
        B, Sq, D = x.shape
        H, Dh = 32, 192
        q = (lambda x, *d: x.permute(*d))((x @ wq).reshape(B, Sq, H, Dh), 0, 2, 1, 3)
        scores = torch.einsum("bhqd,bhkd->bhqk", q, k_cache) * (Dh ** -0.5)
        p = _softmax(scores, axis=-1)
        o = torch.einsum("bhqk,bhkd->bhqd", p, v_cache)
        return (lambda x, *d: x.permute(*d))(o, 0, 2, 1, 3).reshape(B, Sq, H * Dh) @ wo

    a = _A_ref(A_x, A_k_cache, A_v_cache, A_wq, A_wo)
    b = _B_ref(B_x, B_k_cache, B_v_cache, B_wq, B_wo)
    return torch.concatenate([a, b], axis=-1)
```

```cpp
#include <cuda_runtime.h>
#include <cuda.h>
#include <cuda_bf16.h>
#include <stdint.h>

namespace {

constexpr int NCTA = 132;
constexpr int MAXI = 16;
constexpr int SLOT = 24576;
constexpr int NSLOT = 5;
constexpr int XS = 20480;
constexpr int OFF_R = 0;
constexpr int OFF_RING = 5 * XS;
constexpr int OFF_MISC = OFF_RING + NSLOT * SLOT;
constexpr int OFF_LX = OFF_MISC;
constexpr int OFF_LINV = OFF_LX + 2560;
constexpr int OFF_FB = OFF_LINV + 640;
constexpr int OFF_GM = OFF_FB + 16;
constexpr int OFF_BAR = OFF_GM + 16;
constexpr int BAR_RFULL = OFF_BAR;
constexpr int BAR_REMPTY = BAR_RFULL + 40;
constexpr int BAR_XFULL = BAR_REMPTY + 40;
constexpr int BAR_XEMPTY = BAR_XFULL + 40;
constexpr int SMEM_BYTES = BAR_XEMPTY + 40;
static_assert(SMEM_BYTES <= 232448, "smem");

constexpr int NB_S = 1, NB_VOTE = 2, NB_PFULL = 3, NB_PEMPTY = 5, NB_Q2 = 7, NB_SDONE = 8, NB_PDONE = 9,
              NB_L = 10, NB_OPST = 11, NB_ODONE = 12, NB_OPEND = 13;

constexpr uint32_t IT_QA = 1, IT_OP = 2;
__host__ __device__ constexpr uint32_t mk_item(uint32_t type, uint32_t br, uint32_t b, uint32_t h0, uint32_t h1, uint32_t half) {
    return type | (br << 2) | (b << 3) | (h0 << 7) | (h1 << 13) | (half << 19);
}
#define IT_TYPE(e) ((e) & 3u)
#define IT_BR(e) (((e) >> 2) & 1u)
#define IT_B(e) (((e) >> 3) & 15u)
#define IT_H0(e) (((e) >> 7) & 63u)
#define IT_H1(e) (((e) >> 13) & 63u)
#define IT_HALF(e) (((e) >> 19) & 1u)

struct Params {
    CUtensorMap x[2], wq[2], k[2], v[2], wo[2], out;
    const __nv_bfloat16 *px[2], *pwq[2], *pk[2], *pv[2];
    uint32_t items[NCTA][MAXI];
};

constexpr int OUNIT = 61440;
__device__ __align__(1024) unsigned char g_ostash[(size_t)1024 * OUNIT];
__device__ unsigned int g_flag[1024];
__device__ unsigned int g_epoch[NCTA];

constexpr float SM_C = 0.07216878364870322f * 1.4426950408889634f;

__device__ __forceinline__ void mbar_init(uint32_t a, uint32_t c) {
    asm volatile("mbarrier.init.shared::cta.b64 [%0], %1;" ::"r"(a), "r"(c) : "memory");
}
__device__ __forceinline__ void mbar_expect(uint32_t a, uint32_t b) {
    asm volatile("mbarrier.arrive.expect_tx.shared::cta.b64 _, [%0], %1;" ::"r"(a), "r"(b) : "memory");
}
__device__ __forceinline__ void mbar_arrive_warp(uint32_t a, uint32_t cnt) {
    asm volatile(
        "{\n.reg .pred p;\nelect.sync _|p, 0xffffffff;\n"
        "@p mbarrier.arrive.shared::cta.b64 _, [%0], %1;\n}" ::"r"(a), "r"(cnt)
        : "memory");
}
__device__ __forceinline__ void mbar_wait(uint32_t a, uint32_t ph) {
    asm volatile(
        "{\n.reg .pred p;\n.reg .u32 n;\n"
        "mbarrier.try_wait.parity.shared::cta.b64 p, [%0], %1;\n"
        "@p bra DONE;\n"
        "mov.u32 n, 0;\n"
        "LOOP:\n"
        "mbarrier.try_wait.parity.shared::cta.b64 p, [%0], %1;\n"
        "@p bra DONE;\n"
        "add.u32 n, n, 1;\n"
        "setp.lt.u32 p, n, 0x4000000;\n"
        "@p bra LOOP;\n"
        "trap;\n"
        "DONE:\n}" ::"r"(a), "r"(ph)
        : "memory");
}
template <int ID, int CNT>
__device__ __forceinline__ void nb_sync() { asm volatile("bar.sync %0, %1;" ::"n"(ID), "n"(CNT) : "memory"); }
template <int ID, int CNT>
__device__ __forceinline__ void nb_arrive() { asm volatile("bar.arrive %0, %1;" ::"n"(ID), "n"(CNT) : "memory"); }
__device__ __forceinline__ void nb_sync_r(uint32_t id) { asm volatile("bar.sync %0, 256;" ::"r"(id) : "memory"); }
__device__ __forceinline__ void nb_arrive_r(uint32_t id) { asm volatile("bar.arrive %0, 256;" ::"r"(id) : "memory"); }
__device__ __forceinline__ void fence_async_smem() { asm volatile("fence.proxy.async.shared::cta;" ::: "memory"); }

__device__ __forceinline__ void tma3(uint32_t dst, const CUtensorMap* m, int c1, int c2, uint32_t bar, uint64_t pol) {
    asm volatile(
        "cp.async.bulk.tensor.3d.shared::cluster.global.mbarrier::complete_tx::bytes.L2::cache_hint [%0], [%1, {%3,%4,%5}], [%2], %6;" ::"r"(dst),
        "l"(m), "r"(bar), "r"(0), "r"(c1), "r"(c2), "l"(pol)
        : "memory");
}
__device__ __forceinline__ void bulk_load(uint32_t dst, const void* src, uint32_t bytes, uint32_t bar) {
    asm volatile("cp.async.bulk.shared::cluster.global.mbarrier::complete_tx::bytes [%0], [%1], %2, [%3];" ::"r"(dst),
                 "l"(src), "r"(bytes), "r"(bar)
                 : "memory");
}
__device__ __forceinline__ void wg_fence() { asm volatile("wgmma.fence.sync.aligned;" ::: "memory"); }
__device__ __forceinline__ void wg_commit() { asm volatile("wgmma.commit_group.sync.aligned;" ::: "memory"); }
template <int N>
__device__ __forceinline__ void wg_wait() { asm volatile("wgmma.wait_group.sync.aligned %0;" ::"n"(N) : "memory"); }

#define RW80(c, d) c(d[0]), c(d[1]), c(d[2]), c(d[3]), c(d[4]), c(d[5]), c(d[6]), c(d[7]), c(d[8]), c(d[9]), c(d[10]), c(d[11]), c(d[12]), c(d[13]), c(d[14]), c(d[15]), c(d[16]), c(d[17]), c(d[18]), c(d[19]), c(d[20]), c(d[21]), c(d[22]), c(d[23]), c(d[24]), c(d[25]), c(d[26]), c(d[27]), c(d[28]), c(d[29]), c(d[30]), c(d[31]), c(d[32]), c(d[33]), c(d[34]), c(d[35]), c(d[36]), c(d[37]), c(d[38]), c(d[39]), c(d[40]), c(d[41]), c(d[42]), c(d[43]), c(d[44]), c(d[45]), c(d[46]), c(d[47]), c(d[48]), c(d[49]), c(d[50]), c(d[51]), c(d[52]), c(d[53]), c(d[54]), c(d[55]), c(d[56]), c(d[57]), c(d[58]), c(d[59]), c(d[60]), c(d[61]), c(d[62]), c(d[63]), c(d[64]), c(d[65]), c(d[66]), c(d[67]), c(d[68]), c(d[69]), c(d[70]), c(d[71]), c(d[72]), c(d[73]), c(d[74]), c(d[75]), c(d[76]), c(d[77]), c(d[78]), c(d[79])
#define RW48(c, d) c(d[0]), c(d[1]), c(d[2]), c(d[3]), c(d[4]), c(d[5]), c(d[6]), c(d[7]), c(d[8]), c(d[9]), c(d[10]), c(d[11]), c(d[12]), c(d[13]), c(d[14]), c(d[15]), c(d[16]), c(d[17]), c(d[18]), c(d[19]), c(d[20]), c(d[21]), c(d[22]), c(d[23]), c(d[24]), c(d[25]), c(d[26]), c(d[27]), c(d[28]), c(d[29]), c(d[30]), c(d[31]), c(d[32]), c(d[33]), c(d[34]), c(d[35]), c(d[36]), c(d[37]), c(d[38]), c(d[39]), c(d[40]), c(d[41]), c(d[42]), c(d[43]), c(d[44]), c(d[45]), c(d[46]), c(d[47])
#define RW32(c, d) c(d[0]), c(d[1]), c(d[2]), c(d[3]), c(d[4]), c(d[5]), c(d[6]), c(d[7]), c(d[8]), c(d[9]), c(d[10]), c(d[11]), c(d[12]), c(d[13]), c(d[14]), c(d[15]), c(d[16]), c(d[17]), c(d[18]), c(d[19]), c(d[20]), c(d[21]), c(d[22]), c(d[23]), c(d[24]), c(d[25]), c(d[26]), c(d[27]), c(d[28]), c(d[29]), c(d[30]), c(d[31])

__device__ __forceinline__ void reg_fence(float (&d)[80]) { asm volatile("" : RW80("+f", d)::"memory"); }
__device__ __forceinline__ void reg_fence(float (&d)[48]) { asm volatile("" : RW48("+f", d)::"memory"); }
__device__ __forceinline__ void reg_fence(float (&d)[32]) { asm volatile("" : RW32("+f", d)::"memory"); }

constexpr uint32_t HI_SW128 = (1024u >> 4) | (1u << 30);
constexpr uint32_t HI_OST = (128u >> 4);
constexpr uint32_t LO_LBO1 = (1u << 16);
constexpr uint32_t LO_OST = ((2560u >> 4) << 16);

template <int TA, int TB, uint32_t HIB, bool ACC>
__device__ __forceinline__ void wgmma(float (&d)[80], uint32_t loA, uint32_t loB) {
#define WG_ASM(SD)                                                          \
    "{\n.reg .b64 da, db;\nmov.b64 da, {%80, %82};\nmov.b64 db, {%81, %83};\n" \
    "wgmma.mma_async.sync.aligned.m64n160k16.f32.bf16.bf16 "               \
    "{%0,%1,%2,%3,%4,%5,%6,%7,%8,%9,%10,%11,%12,%13,%14,%15,%16,%17,%18,%19,%20,%21,%22,%23,%24,%25,%26,%27,%28,%29,%30,%31,%32,%33,%34,%35,%36,%37,%38,%39,%40,%41,%42,%43,%44,%45,%46,%47,%48,%49,%50,%51,%52,%53,%54,%55,%56,%57,%58,%59,%60,%61,%62,%63,%64,%65,%66,%67,%68,%69,%70,%71,%72,%73,%74,%75,%76,%77,%78,%79}, da, db, " SD ", 1, 1, %84, %85;\n}"
    if constexpr (ACC)
        asm volatile(WG_ASM("1") : RW80("+f", d) : "r"(loA), "r"(loB), "n"(HI_SW128), "n"(HIB), "n"(TA), "n"(TB));
    else
        asm volatile(WG_ASM("0") : RW80("=f", d) : "r"(loA), "r"(loB), "n"(HI_SW128), "n"(HIB), "n"(TA), "n"(TB));
#undef WG_ASM
}
template <int TA, int TB, uint32_t HIB, bool ACC>
__device__ __forceinline__ void wgmma(float (&d)[48], uint32_t loA, uint32_t loB) {
#define WG_ASM(SD)                                                          \
    "{\n.reg .b64 da, db;\nmov.b64 da, {%48, %50};\nmov.b64 db, {%49, %51};\n" \
    "wgmma.mma_async.sync.aligned.m64n96k16.f32.bf16.bf16 "               \
    "{%0,%1,%2,%3,%4,%5,%6,%7,%8,%9,%10,%11,%12,%13,%14,%15,%16,%17,%18,%19,%20,%21,%22,%23,%24,%25,%26,%27,%28,%29,%30,%31,%32,%33,%34,%35,%36,%37,%38,%39,%40,%41,%42,%43,%44,%45,%46,%47}, da, db, " SD ", 1, 1, %52, %53;\n}"
    if constexpr (ACC)
        asm volatile(WG_ASM("1") : RW48("+f", d) : "r"(loA), "r"(loB), "n"(HI_SW128), "n"(HIB), "n"(TA), "n"(TB));
    else
        asm volatile(WG_ASM("0") : RW48("=f", d) : "r"(loA), "r"(loB), "n"(HI_SW128), "n"(HIB), "n"(TA), "n"(TB));
#undef WG_ASM
}
template <int TA, int TB, uint32_t HIB, bool ACC>
__device__ __forceinline__ void wgmma(float (&d)[32], uint32_t loA, uint32_t loB) {
#define WG_ASM(SD)                                                          \
    "{\n.reg .b64 da, db;\nmov.b64 da, {%32, %34};\nmov.b64 db, {%33, %35};\n" \
    "wgmma.mma_async.sync.aligned.m64n64k16.f32.bf16.bf16 "               \
    "{%0,%1,%2,%3,%4,%5,%6,%7,%8,%9,%10,%11,%12,%13,%14,%15,%16,%17,%18,%19,%20,%21,%22,%23,%24,%25,%26,%27,%28,%29,%30,%31}, da, db, " SD ", 1, 1, %36, %37;\n}"
    if constexpr (ACC)
        asm volatile(WG_ASM("1") : RW32("+f", d) : "r"(loA), "r"(loB), "n"(HI_SW128), "n"(HIB), "n"(TA), "n"(TB));
    else
        asm volatile(WG_ASM("0") : RW32("=f", d) : "r"(loA), "r"(loB), "n"(HI_SW128), "n"(HIB), "n"(TA), "n"(TB));
#undef WG_ASM
}

__device__ __forceinline__ uint32_t pack_bf16(float lo, float hi) {
    uint32_t r;
    asm("cvt.rn.bf16x2.f32 %0, %1, %2;" : "=r"(r) : "f"(hi), "f"(lo));
    return r;
}
__device__ __forceinline__ float ex2(float x) {
    float r;
    asm("ex2.approx.ftz.f32 %0, %1;" : "=f"(r) : "f"(x));
    return r;
}
__device__ __forceinline__ void stsm4t(uint32_t a, uint32_t r0, uint32_t r1, uint32_t r2, uint32_t r3) {
    asm volatile("stmatrix.sync.aligned.m8n8.x4.trans.shared.b16 [%0], {%1,%2,%3,%4};" ::"r"(a), "r"(r0), "r"(r1), "r"(r2), "r"(r3)
                 : "memory");
}
__device__ __forceinline__ uint32_t lds_u(uint32_t a) {
    uint32_t v;
    asm volatile("ld.shared.u32 %0, [%1];" : "=r"(v) : "r"(a) : "memory");
    return v;
}
__device__ __forceinline__ float2 lds_f2(uint32_t a) {
    float2 v;
    asm volatile("ld.shared.v2.f32 {%0,%1}, [%2];" : "=f"(v.x), "=f"(v.y) : "r"(a) : "memory");
    return v;
}
__device__ __forceinline__ void sts_f(uint32_t a, float v) { asm volatile("st.shared.f32 [%0], %1;" ::"r"(a), "f"(v) : "memory"); }
__device__ __forceinline__ void sts_u(uint32_t a, uint32_t v) { asm volatile("st.shared.u32 [%0], %1;" ::"r"(a), "r"(v) : "memory"); }
__device__ __forceinline__ void sts_f2(uint32_t a, float x, float y) {
    asm volatile("st.shared.v2.f32 [%0], {%1,%2};" ::"r"(a), "f"(x), "f"(y) : "memory");
}

__device__ __forceinline__ void store_tile_t(const float (&d)[80], uint32_t addr) {
#pragma unroll
    for (int j = 0; j < 10; j++)
        stsm4t(addr + j * 2048, pack_bf16(d[8 * j], d[8 * j + 1]), pack_bf16(d[8 * j + 2], d[8 * j + 3]),
               pack_bf16(d[8 * j + 4], d[8 * j + 5]), pack_bf16(d[8 * j + 6], d[8 * j + 7]));
}
template <int NR>
__device__ __forceinline__ void store_out_tile(const float (&d)[NR], uint32_t base, uint32_t lane, uint32_t w) {
    const uint32_t mi = lane >> 3, i = lane & 7;
    const uint32_t chunk = 2 * w + (mi & 1);
    const uint32_t q0 = 8 * (i >> 1) + 2 * (mi >> 1) + (i & 1);
    const uint32_t a0 = base + q0 * 128 + ((chunk ^ (q0 & 7)) << 4);
    const uint32_t a1 = base + (q0 + 4) * 128 + ((chunk ^ ((q0 + 4) & 7)) << 4);
#pragma unroll
    for (int j = 0; j < NR / 8; j++)
        stsm4t(((j & 1) ? a1 : a0) + (j >> 1) * 4096, pack_bf16(d[8 * j], d[8 * j + 1]), pack_bf16(d[8 * j + 2], d[8 * j + 3]),
               pack_bf16(d[8 * j + 4], d[8 * j + 5]), pack_bf16(d[8 * j + 6], d[8 * j + 7]));
}

struct TrueT { static constexpr bool value = true; };
struct FalseT { static constexpr bool value = false; };

struct Ring {
    uint32_t slot, ph;
    __device__ __forceinline__ void adv(uint32_t k) {
        slot += k;
        if (slot >= NSLOT) { slot -= NSLOT; ph ^= 1; }
    }
};

template <int BUF>
__device__ __forceinline__ void softmax_block(float (&s)[80], float (&l)[20], uint32_t sb, uint32_t stoff, bool hi,
                                              bool first, bool need_empty, float& mref) {
    if (BUF == 0 && first) {
        float m0 = fmaxf(s[0], s[1]), m1 = fmaxf(s[2], s[3]), m2 = fmaxf(s[4], s[5]), m3 = fmaxf(s[6], s[7]);
#pragma unroll
        for (int i = 8; i < 80; i += 4) {
            m0 = fmaxf(m0, s[i]); m1 = fmaxf(m1, s[i + 1]); m2 = fmaxf(m2, s[i + 2]); m3 = fmaxf(m3, s[i + 3]);
        }
        float mx = fmaxf(fmaxf(m0, m1), fmaxf(m2, m3));
#pragma unroll
        for (int o = 16; o > 0; o >>= 1) mx = fmaxf(mx, __shfl_xor_sync(0xffffffffu, mx, o));
        sts_f(sb + OFF_GM + ((threadIdx.x >> 3) & 12), mx);
        nb_sync<NB_S, 128>();
        const float2 u = lds_f2(sb + OFF_GM), v = lds_f2(sb + OFF_GM + 8);
        mref = fmaxf(fmaxf(u.x, u.y), fmaxf(v.x, v.y)) * SM_C;
    }
    if (need_empty) nb_sync<NB_PEMPTY + BUF, 256>();
    const uint32_t pa = sb + OFF_R + (3 + BUF) * XS + stoff;
#pragma unroll
    for (int j = 0; j < 10; j++) {
        float p[8];
#pragma unroll
        for (int i = 0; i < 8; i++) p[i] = ex2(fmaf(s[8 * j + i], SM_C, -mref));
        stsm4t(pa + j * 2048, pack_bf16(p[0], p[1]), pack_bf16(p[2], p[3]), pack_bf16(p[4], p[5]), pack_bf16(p[6], p[7]));
        const float a0 = p[0] + p[2], a1 = p[1] + p[3], b0 = p[4] + p[6], b1 = p[5] + p[7];
        l[2 * j] += (hi ? b0 : a0) + __shfl_xor_sync(0xffffffffu, hi ? a0 : b0, 16);
        l[2 * j + 1] += (hi ? b1 : a1) + __shfl_xor_sync(0xffffffffu, hi ? a1 : b1, 16);
    }
    fence_async_smem();
    nb_arrive<NB_PFULL + BUF, 256>();
}

__device__ __forceinline__ void fallback_unit(const Params& P, uint32_t e, uint32_t tid) {
    const uint32_t lane = tid & 31, br = IT_BR(e), b = IT_B(e), h = IT_H0(e);
    const uint32_t u = (br * 16 + b) * 32 + h;
    const __nv_bfloat162* wq = (const __nv_bfloat162*)(P.pwq[br] + h * 192) + lane;
    const __nv_bfloat162* kp = (const __nv_bfloat162*)(P.pk[br] + (size_t)(b * 32 + h) * 512 * 192) + lane;
    const __nv_bfloat162* vp = (const __nv_bfloat162*)(P.pv[br] + (size_t)(b * 32 + h) * 512 * 192) + lane;
#pragma unroll 1
    for (uint32_t q = tid >> 5; q < 160; q += 4) {
        const __nv_bfloat16* xr = P.px[br] + (size_t)(b * 160 + q) * 640;
        float a[6] = {0.f, 0.f, 0.f, 0.f, 0.f, 0.f};
#pragma unroll 4
        for (int k = 0; k < 640; k++) {
            const float xv = __bfloat162float(xr[k]);
#pragma unroll
            for (int i = 0; i < 3; i++) {
                const float2 wv = __bfloat1622float2(wq[(size_t)k * 3072 + i * 32]);
                a[2 * i] = fmaf(xv, wv.x, a[2 * i]);
                a[2 * i + 1] = fmaf(xv, wv.y, a[2 * i + 1]);
            }
        }
#pragma unroll
        for (int i = 0; i < 6; i++) a[i] = __bfloat162float(__float2bfloat16(a[i]));
        auto score = [&](int key) {
            float d = 0.f;
#pragma unroll
            for (int i = 0; i < 3; i++) {
                const float2 kv = __bfloat1622float2(kp[key * 96 + i * 32]);
                d = fmaf(a[2 * i], kv.x, fmaf(a[2 * i + 1], kv.y, d));
            }
#pragma unroll
            for (int o = 16; o > 0; o >>= 1) d += __shfl_xor_sync(0xffffffffu, d, o);
            return d;
        };
        float m = -INFINITY;
#pragma unroll 4
        for (int key = 0; key < 512; key++) m = fmaxf(m, score(key));
        float o[6] = {0.f, 0.f, 0.f, 0.f, 0.f, 0.f}, sum = 0.f;
#pragma unroll 4
        for (int key = 0; key < 512; key++) {
            const float p = ex2((score(key) - m) * SM_C);
            sum += p;
#pragma unroll
            for (int i = 0; i < 3; i++) {
                const float2 vv = __bfloat1622float2(vp[key * 96 + i * 32]);
                o[2 * i] = fmaf(p, vv.x, o[2 * i]);
                o[2 * i + 1] = fmaf(p, vv.y, o[2 * i + 1]);
            }
        }
        const float inv = 1.f / sum;
        const uint32_t np = (q & ~31u) + 8 * ((q & 7) >> 1) + 2 * ((q & 31) >> 3) + (q & 1);
        __nv_bfloat16* op = (__nv_bfloat16*)(g_ostash + (size_t)u * OUNIT) + (np >> 3) * 64 + (np & 7);
#pragma unroll
        for (int i = 0; i < 6; i++) {
            const uint32_t d = (i >> 1) * 64 + 2 * lane + (i & 1);
            op[(d >> 3) * 1280 + (d & 7) * 8] = __float2bfloat16(o[i] * inv);
        }
    }
}

template <int K0, int K1>
__device__ __forceinline__ void qk_steps(float (&s)[80], uint32_t loK, uint32_t loQ) {
#pragma unroll
    for (int k = K0; k < K1; k++) {
        if (k == 0) wgmma<0, 0, HI_SW128, false>(s, loK, loQ);
        else wgmma<0, 0, HI_SW128, true>(s, loK + (k >> 2) * (8192 >> 4) + (k & 3) * 2, loQ + (k >> 2) * (XS >> 4) + (k & 3) * 2);
    }
}

template <bool IS_S>
__device__ __forceinline__ void qproj(float (&q0)[80], float (&q1)[80], uint32_t sb, Ring& r, uint32_t& phm) {
    const uint32_t loR = ((sb + OFF_R) >> 4) | LO_LBO1;
    const uint32_t loRing = ((sb + OFF_RING) >> 4) | LO_LBO1;
    uint32_t xs = 0;
    auto step = [&](auto first) {
        constexpr bool F = decltype(first)::value;
        mbar_wait(sb + BAR_RFULL + r.slot * 8, r.ph);
        mbar_wait(sb + BAR_XFULL + xs * 8, (phm >> xs) & 1);
        phm ^= 1u << xs;
        const uint32_t a = loRing + r.slot * (SLOT >> 4) + (IS_S ? 0 : 1024), b = loR + xs * (XS >> 4);
        wg_fence();
        wgmma<1, 0, HI_SW128, !F>(q0, a, b);
        if (IS_S) wgmma<1, 0, HI_SW128, !F>(q1, a + 512, b);
#pragma unroll
        for (int k = 1; k < 4; k++) {
            wgmma<1, 0, HI_SW128, true>(q0, a + k * 128, b + k * 2);
            if (IS_S) wgmma<1, 0, HI_SW128, true>(q1, a + 512 + k * 128, b + k * 2);
        }
        wg_commit();
    };
    step(TrueT{});
#pragma unroll 1
    for (int kk = 1; kk < 10; kk++) {
        const uint32_t pslot = r.slot;
        r.adv(1);
        if (++xs == 5) xs = 0;
        if (!IS_S && kk == 8) nb_sync<NB_SDONE, 256>();
        step(FalseT{});
        wg_wait<1>();
        mbar_arrive_warp(sb + BAR_REMPTY + pslot * 8, 1);
        if (kk <= 5) mbar_arrive_warp(sb + BAR_XEMPTY + (kk - 1) * 8, 1);
        if (!IS_S && kk == 7) nb_arrive<NB_PDONE, 256>();
    }
    if (IS_S) nb_arrive<NB_SDONE, 256>();
    wg_wait<0>();
    reg_fence(q0);
    if (IS_S) reg_fence(q1);
    mbar_arrive_warp(sb + BAR_REMPTY + r.slot * 8, 1);
    r.adv(1);
}

template <int NR>
__device__ __forceinline__ void ostore(const float (&o)[NR], int gl, const float2 (&sc)[4], unsigned char* gp) {
#pragma unroll
    for (int hh = 0; hh < 2; hh++)
        asm volatile("st.global.v4.b32 [%0], {%1,%2,%3,%4};" ::"l"(gp + hh * 2560),
                     "r"(pack_bf16(o[16 * gl + 2 * hh] * sc[0].x, o[16 * gl + 2 * hh + 1] * sc[0].y)),
                     "r"(pack_bf16(o[16 * gl + 4 + 2 * hh] * sc[1].x, o[16 * gl + 5 + 2 * hh] * sc[1].y)),
                     "r"(pack_bf16(o[16 * gl + 8 + 2 * hh] * sc[2].x, o[16 * gl + 9 + 2 * hh] * sc[2].y)),
                     "r"(pack_bf16(o[16 * gl + 12 + 2 * hh] * sc[3].x, o[16 * gl + 13 + 2 * hh] * sc[3].y))
                     : "memory");
}
__device__ __forceinline__ unsigned char* ostash_ptr(uint32_t e) {
    const uint32_t u = (IT_BR(e) * 16 + IT_B(e)) * 32 + IT_H0(e);
    const uint32_t lane = threadIdx.x & 31, w = (threadIdx.x >> 5) & 3;
    return g_ostash + (size_t)u * OUNIT + w * 5120 + (lane & 3) * 128 + (lane >> 2) * 16;
}

template <bool IS_S>
__device__ __forceinline__ void op_item(const Params& P, uint32_t e, uint32_t sb, Ring& r, uint32_t& phm) {
    constexpr int T0 = IS_S ? 0 : 2;
    constexpr uint32_t BOFF = IS_S ? (12 * 128) >> 4 : 0;
    const uint32_t loRing = ((sb + OFF_RING) >> 4) | LO_LBO1;
    const uint32_t loO = ((sb + OFF_R) >> 4) | LO_OST;
    float c0[80], c1[80], c2[IS_S ? 32 : 48];
    const int T2 = 6 * (IT_H1(e) - IT_H0(e));
    uint32_t xs = 0;
    auto step = [&](auto first, uint32_t hf) {
        constexpr bool F = decltype(first)::value;
        if (hf == 0) {
            mbar_wait(sb + BAR_XFULL + xs * 8, (phm >> xs) & 1);
            phm ^= 1u << xs;
        }
        mbar_wait(sb + BAR_RFULL + r.slot * 8, r.ph);
        const uint32_t a = loRing + r.slot * (SLOT >> 4), b = loO + xs * (XS >> 4) + hf * 640;
        wg_fence();
        wgmma<1, 1, HI_OST, !F>(c0, a + T0 * 256, b);
        wgmma<1, 1, HI_OST, !F>(c1, a + T0 * 256 + 256, b);
        wgmma<1, 1, HI_OST, !F>(c2, a + 1024, b + BOFF);
        wgmma<1, 1, HI_OST, true>(c0, a + T0 * 256 + 128, b + 320);
        wgmma<1, 1, HI_OST, true>(c1, a + T0 * 256 + 384, b + 320);
        wgmma<1, 1, HI_OST, true>(c2, a + 1024 + 128, b + 320 + BOFF);
        wg_commit();
    };
    step(TrueT{}, 0);
#pragma unroll 1
    for (int t = 1; t < T2; t++) {
        const uint32_t pslot = r.slot, pxs = xs;
        r.adv(1);
        if ((t & 1) == 0 && ++xs == 5) xs = 0;
        step(FalseT{}, t & 1);
        wg_wait<1>();
        mbar_arrive_warp(sb + BAR_REMPTY + pslot * 8, 1);
        if ((t & 1) == 0 && t + 8 < T2) mbar_arrive_warp(sb + BAR_XEMPTY + pxs * 8, 1);
    }
    wg_wait<0>();
    reg_fence(c0);
    reg_fence(c1);
    reg_fence(c2);
    mbar_arrive_warp(sb + BAR_REMPTY + r.slot * 8, 1);
    r.adv(1);
    nb_sync<NB_OPEND, 256>();
    const uint32_t lane = threadIdx.x & 31, w = (threadIdx.x >> 5) & 3;
    store_out_tile(c0, sb + OFF_R + T0 * XS, lane, w);
    store_out_tile(c1, sb + OFF_R + (T0 + 1) * XS, lane, w);
    store_out_tile(c2, sb + OFF_R + 4 * XS + (IS_S ? 96 * 128 : 0), lane, w);
    fence_async_smem();
    if (IS_S) {
        nb_arrive<NB_OPST, 256>();
    } else {
        nb_sync<NB_OPST, 256>();
        if ((threadIdx.x & 127) == 0) {
            const int cc0 = IT_BR(e) * 640 + IT_HALF(e) * 320;
#pragma unroll
            for (int m = 0; m < 5; m++)
                asm volatile("cp.async.bulk.tensor.2d.global.shared::cta.bulk_group [%0, {%2,%3}], [%1];" ::"l"(&P.out),
                             "r"(sb + OFF_R + m * XS), "r"(cc0 + m * 64), "r"((int)IT_B(e) * 160)
                             : "memory");
            asm volatile("cp.async.bulk.commit_group;" ::: "memory");
            asm volatile("cp.async.bulk.wait_group 0;" ::: "memory");
#pragma unroll
            for (int m = 0; m < 5; m++)
                asm volatile("mbarrier.arrive.shared::cta.b64 _, [%0], 8;" ::"r"(sb + BAR_XEMPTY + m * 8) : "memory");
        }
        __syncwarp();
    }
}

__global__ void __launch_bounds__(384, 1) fused_kernel(const __grid_constant__ Params P) {
    extern __shared__ __align__(1024) unsigned char smem_raw[];
    const uint32_t sb = (uint32_t)__cvta_generic_to_shared(smem_raw);
    const uint32_t wgid = __shfl_sync(0xffffffffu, threadIdx.x >> 7, 0);
    const uint32_t cta = blockIdx.x;
    const uint32_t* items = P.items[cta];

    uint32_t epoch = 0;
    if (wgid == 0) epoch = *(volatile unsigned int*)&g_epoch[cta] + 1;
    if (threadIdx.x == 0) {
        if (sb & 1023) __trap();
        for (int i = 0; i < NSLOT; i++) {
            mbar_init(sb + BAR_RFULL + i * 8, 1);
            mbar_init(sb + BAR_REMPTY + i * 8, 8);
            mbar_init(sb + BAR_XFULL + i * 8, 1);
            mbar_init(sb + BAR_XEMPTY + i * 8, 8);
        }
        asm volatile("fence.mbarrier_init.release.cluster;" ::: "memory");
        fence_async_smem();
    }
    __syncthreads();

    if (wgid == 0) {
        asm volatile("setmaxnreg.dec.sync.aligned.u32 24;");
        const uint32_t warp = __shfl_sync(0xffffffffu, threadIdx.x >> 5, 0);
        if (warp == 0) {
            if (threadIdx.x == 0) {
                *(volatile unsigned int*)&g_epoch[cta] = epoch;
                uint64_t pol_first, pol_norm;
                asm volatile("createpolicy.fractional.L2::evict_first.b64 %0, 1.0;" : "=l"(pol_first));
                asm volatile("createpolicy.fractional.L2::evict_normal.b64 %0, 1.0;" : "=l"(pol_norm));
                Ring r{0, 1};
                for (int it = 0; it < MAXI; it++) {
                    const uint32_t e = items[it];
                    if (e == 0) break;
                    const uint32_t br = IT_BR(e);
                    if (IT_TYPE(e) == IT_QA) {
                        const uint32_t h = IT_H0(e);
#pragma unroll 1
                        for (int kk = 0; kk < 10; kk++) {
                            mbar_wait(sb + BAR_REMPTY + r.slot * 8, r.ph);
                            mbar_expect(sb + BAR_RFULL + r.slot * 8, SLOT);
                            tma3(sb + OFF_RING + r.slot * SLOT, &P.wq[br], kk * 64, h * 3, sb + BAR_RFULL + r.slot * 8, pol_norm);
                            r.adv(1);
                        }
                        const int row0 = (IT_B(e) * 32 + h) * 512;
#pragma unroll 1
                        for (int n = 0; n < 16; n++) {
                            bool isv;
                            int j;
                            if (n < 2) { isv = false; j = n; }
                            else if (n >= 14) { isv = true; j = n - 8; }
                            else { isv = n & 1; j = isv ? (n - 3) >> 1 : (n + 2) >> 1; }
                            mbar_wait(sb + BAR_REMPTY + r.slot * 8, r.ph);
                            mbar_expect(sb + BAR_RFULL + r.slot * 8, SLOT);
                            tma3(sb + OFF_RING + r.slot * SLOT, isv ? &P.v[br] : &P.k[br], row0 + j * 64, 0,
                                 sb + BAR_RFULL + r.slot * 8, pol_first);
                            r.adv(1);
                        }
                    } else {
                        const int r0 = IT_H0(e) * 192, r1 = IT_H1(e) * 192;
#pragma unroll 1
                        for (int row = r0; row < r1; row += 32) {
                            mbar_wait(sb + BAR_REMPTY + r.slot * 8, r.ph);
                            mbar_expect(sb + BAR_RFULL + r.slot * 8, XS);
                            tma3(sb + OFF_RING + r.slot * SLOT, &P.wo[br], row, IT_HALF(e) * 5, sb + BAR_RFULL + r.slot * 8, pol_norm);
                            r.adv(1);
                        }
                    }
                }
            }
        } else if (warp == 1) {
            if (threadIdx.x == 32) {
                uint64_t pol_norm;
                asm volatile("createpolicy.fractional.L2::evict_normal.b64 %0, 1.0;" : "=l"(pol_norm));
                uint32_t phm = 0x1f;
                for (int it = 0; it < MAXI; it++) {
                    const uint32_t e = items[it];
                    if (e == 0) break;
                    const uint32_t br = IT_BR(e);
                    uint32_t xs = 0;
                    if (IT_TYPE(e) == IT_QA) {
#pragma unroll 1
                        for (int kk = 0; kk < 10; kk++) {
                            mbar_wait(sb + BAR_XEMPTY + xs * 8, (phm >> xs) & 1);
                            phm ^= 1u << xs;
                            mbar_expect(sb + BAR_XFULL + xs * 8, XS);
                            tma3(sb + OFF_R + xs * XS, &P.x[br], IT_B(e) * 160, kk, sb + BAR_XFULL + xs * 8, pol_norm);
                            if (++xs == 5) xs = 0;
                        }
                    } else {
                        const uint32_t u0 = (br * 16 + IT_B(e)) * 32;
#pragma unroll 1
                        for (uint32_t u = u0 + IT_H0(e); u < u0 + IT_H1(e); u++) {
                            uint32_t v, n = 0;
                            do {
                                asm volatile("ld.acquire.gpu.global.u32 %0, [%1];" : "=r"(v) : "l"(&g_flag[u]) : "memory");
                                if (++n > 0x2000000) __trap();
                            } while (v != epoch);
                            asm volatile("fence.proxy.async;" ::: "memory");
#pragma unroll 1
                            for (int t = 0; t < 3; t++) {
                                mbar_wait(sb + BAR_XEMPTY + xs * 8, (phm >> xs) & 1);
                                phm ^= 1u << xs;
                                mbar_expect(sb + BAR_XFULL + xs * 8, XS);
                                bulk_load(sb + OFF_R + xs * XS, g_ostash + (size_t)u * OUNIT + t * XS, XS, sb + BAR_XFULL + xs * 8);
                                if (++xs == 5) xs = 0;
                            }
                        }
                    }
                }
            }
        } else if (warp == 2) {
            for (int it = 0; it < MAXI; it++) {
                const uint32_t e = items[it];
                if (e == 0) break;
                if (IT_TYPE(e) == IT_QA) {
                    nb_sync<NB_ODONE, 288>();
                    if (threadIdx.x == 64) {
                        __threadfence();
                        const uint32_t u = (IT_BR(e) * 16 + IT_B(e)) * 32 + IT_H0(e);
                        asm volatile("st.relaxed.gpu.global.u32 [%0], %1;" ::"l"(&g_flag[u]), "r"(epoch) : "memory");
                    }
                    __syncwarp();
                }
            }
        }
    } else if (wgid == 1) {
        asm volatile("setmaxnreg.inc.sync.aligned.u32 240;");
        const uint32_t loR = ((sb + OFF_R) >> 4) | LO_LBO1;
        const uint32_t loRing = ((sb + OFF_RING) >> 4) | LO_LBO1;
        Ring r{0, 0};
        uint32_t phm = 0;
#pragma unroll 1
        for (int it = 0; it < MAXI; it++) {
            const uint32_t e = items[it];
            if (e == 0) break;
            if (IT_TYPE(e) == IT_QA) {
                const uint32_t lane = threadIdx.x & 31, w = (threadIdx.x >> 5) & 3;
                const uint32_t stoff = (lane >> 4) * 1024 + (lane & 7) * 128 + (((2 * w + ((lane >> 3) & 1)) ^ (lane & 7)) << 4);
                const bool hi = lane & 16;
                {
                    float q0[80], q1[80];
                    qproj<true>(q0, q1, sb, r, phm);
                    nb_sync<NB_PDONE, 256>();
                    store_tile_t(q0, sb + OFF_R + stoff);
                    store_tile_t(q1, sb + OFF_R + XS + stoff);
                }
                fence_async_smem();
                float s0[80], s1[80], ob[32], l[20];
#pragma unroll
                for (int i = 0; i < 32; i++) ob[i] = 0.f;
                reg_fence(ob);
                nb_sync<NB_S, 128>();
                uint32_t rel = r.slot;
                auto release = [&](uint32_t cnt) {
                    mbar_arrive_warp(sb + BAR_REMPTY + rel * 8, cnt);
                    if (++rel == NSLOT) rel = 0;
                };
                auto pvb = [&](uint32_t buf) {
                    mbar_wait(sb + BAR_RFULL + r.slot * 8, r.ph);
                    const uint32_t a = loRing + r.slot * (SLOT >> 4) + 1024, b = loR + (3 + buf) * (XS >> 4) + ((96 * 128) >> 4);
#pragma unroll
                    for (int k = 0; k < 4; k++) wgmma<1, 0, HI_SW128, true>(ob, a + k * 128, b + k * 2);
                    r.adv(1);
                };
                mbar_wait(sb + BAR_RFULL + r.slot * 8, r.ph);
                wg_fence();
                qk_steps<0, 8>(s0, loRing + r.slot * (SLOT >> 4), loR);
                nb_sync<NB_Q2, 256>();
                qk_steps<8, 12>(s0, loRing + r.slot * (SLOT >> 4), loR);
                wg_commit();
                r.adv(1);
                mbar_wait(sb + BAR_RFULL + r.slot * 8, r.ph);
                wg_fence();
                qk_steps<0, 12>(s1, loRing + r.slot * (SLOT >> 4), loR);
                wg_commit();
                r.adv(1);
#pragma unroll
                for (int i = 0; i < 20; i++) l[i] = 0.f;
                float mref = 0.f;
#pragma unroll 1
                for (int jp = 0; jp < 3; jp++) {
                    wg_wait<1>();
                    reg_fence(s0);
                    release(2);
                    if (jp > 0) release(1);
                    softmax_block<0>(s0, l, sb, stoff, hi, jp == 0, jp > 0, mref);
                    mbar_wait(sb + BAR_RFULL + r.slot * 8, r.ph);
                    wg_fence();
                    qk_steps<0, 12>(s0, loRing + r.slot * (SLOT >> 4), loR);
                    r.adv(1);
                    nb_sync<NB_S, 128>();
                    pvb(0);
                    wg_commit();
                    wg_wait<1>();
                    reg_fence(s1);
                    release(2);
                    if (jp > 0) release(1);
                    softmax_block<1>(s1, l, sb, stoff, hi, false, jp > 0, mref);
                    mbar_wait(sb + BAR_RFULL + r.slot * 8, r.ph);
                    wg_fence();
                    qk_steps<0, 12>(s1, loRing + r.slot * (SLOT >> 4), loR);
                    r.adv(1);
                    nb_sync<NB_S, 128>();
                    pvb(1);
                    wg_commit();
                }
                wg_wait<1>();
                reg_fence(s0);
                release(2);
                release(1);
                softmax_block<0>(s0, l, sb, stoff, hi, false, true, mref);
                nb_sync<NB_S, 128>();
                wg_fence();
                pvb(0);
                wg_commit();
                wg_wait<1>();
                reg_fence(s1);
                release(2);
                release(1);
                mbar_arrive_warp(sb + BAR_XEMPTY + 0, 2);
                mbar_arrive_warp(sb + BAR_XEMPTY + 8, 2);
                mbar_arrive_warp(sb + BAR_XEMPTY + 16, 2);
                softmax_block<1>(s1, l, sb, stoff, hi, false, true, mref);
                nb_sync<NB_S, 128>();
                wg_fence();
                pvb(1);
                wg_commit();
                wg_wait<1>();
                release(1);
                mbar_arrive_warp(sb + BAR_XEMPTY + 24, 1);
                const bool b3 = lane & 8, b2 = lane & 4;
#pragma unroll
                for (int i = 0; i < 10; i++)
                    l[i] = (b3 ? l[i + 10] : l[i]) + __shfl_xor_sync(0xffffffffu, b3 ? l[i] : l[i + 10], 8);
#pragma unroll
                for (int i = 0; i < 5; i++)
                    l[i] = (b2 ? l[2 * i + 1] : l[2 * i]) + __shfl_xor_sync(0xffffffffu, b2 ? l[2 * i] : l[2 * i + 1], 4);
                const uint32_t col0 = (b3 ? 80 : 0) + (hi ? 8 : 0) + 2 * (lane & 3) + (b2 ? 1 : 0);
#pragma unroll
                for (int i = 0; i < 5; i++) sts_f(sb + OFF_LX + w * 640 + (col0 + 16 * i) * 4, l[i]);
                nb_sync<NB_S, 128>();
                const uint32_t tid = threadIdx.x & 127;
                float la = 1.f, lb = 1.f;
                if (tid < 80) {
                    float2 v = lds_f2(sb + OFF_LX + tid * 8);
#pragma unroll
                    for (int i = 1; i < 4; i++) {
                        const float2 u = lds_f2(sb + OFF_LX + i * 640 + tid * 8);
                        v.x += u.x;
                        v.y += u.y;
                    }
                    sts_f2(sb + OFF_LINV + tid * 8, __frcp_rn(v.x), __frcp_rn(v.y));
                    la = v.x;
                    lb = v.y;
                }
                const uint32_t bad = !(la >= 5.421010862e-20f && la <= 1.8446744e19f && lb >= 5.421010862e-20f && lb <= 1.8446744e19f);
                uint32_t any;
                asm volatile(
                    "{\n.reg .pred p, q;\nsetp.ne.u32 p, %1, 0;\n"
                    "bar.red.or.pred q, %2, 128, p;\nselp.u32 %0, 1, 0, q;\n}"
                    : "=r"(any)
                    : "r"(bad), "n"(NB_VOTE)
                    : "memory");
                if (tid == 0) sts_u(sb + OFF_FB, any);
                nb_arrive<NB_L, 256>();
                wg_wait<0>();
                reg_fence(ob);
                release(1);
                mbar_arrive_warp(sb + BAR_XEMPTY + 32, 1);
                if (!any) {
                    unsigned char* gp = ostash_ptr(e) + 2 * XS;
#pragma unroll
                    for (int g = 3; g < 5; g++) {
                        float2 sc[4];
#pragma unroll
                        for (int t = 0; t < 4; t++) sc[t] = lds_f2(sb + OFF_LINV + (lane & 3) * 8 + (4 * g + t) * 32);
                        ostore(ob, g - 3, sc, gp + g * 512);
                    }
                } else {
                    fallback_unit(P, e, tid);
                }
                nb_arrive<NB_ODONE, 288>();
            } else {
                op_item<true>(P, e, sb, r, phm);
            }
        }
    } else {
        asm volatile("setmaxnreg.inc.sync.aligned.u32 240;");
        const uint32_t loR = ((sb + OFF_R) >> 4) | LO_LBO1;
        const uint32_t loRing = ((sb + OFF_RING) >> 4) | LO_LBO1;
        Ring r{0, 0};
        uint32_t phm = 0;
#pragma unroll 1
        for (int it = 0; it < MAXI; it++) {
            const uint32_t e = items[it];
            if (e == 0) break;
            if (IT_TYPE(e) == IT_QA) {
                {
                    float q2[80];
                    qproj<false>(q2, q2, sb, r, phm);
                    const uint32_t lane = threadIdx.x & 31, w = (threadIdx.x >> 5) & 3;
                    const uint32_t stoff = (lane >> 4) * 1024 + (lane & 7) * 128 + (((2 * w + ((lane >> 3) & 1)) ^ (lane & 7)) << 4);
                    store_tile_t(q2, sb + OFF_R + 2 * XS + stoff);
                }
                fence_async_smem();
                nb_arrive<NB_Q2, 256>();
                float o0[80], o1[80], o2[48];
                r.adv(3);
                auto pv = [&](auto first, uint32_t buf) {
                    constexpr bool F = decltype(first)::value;
                    nb_sync_r(NB_PFULL + buf);
                    mbar_wait(sb + BAR_RFULL + r.slot * 8, r.ph);
                    const uint32_t a = loRing + r.slot * (SLOT >> 4), b = loR + (3 + buf) * (XS >> 4);
                    wg_fence();
                    wgmma<1, 0, HI_SW128, !F>(o0, a, b);
                    wgmma<1, 0, HI_SW128, !F>(o1, a + 512, b);
                    wgmma<1, 0, HI_SW128, !F>(o2, a + 1024, b);
#pragma unroll
                    for (int k = 1; k < 4; k++) {
                        wgmma<1, 0, HI_SW128, true>(o0, a + k * 128, b + k * 2);
                        wgmma<1, 0, HI_SW128, true>(o1, a + 512 + k * 128, b + k * 2);
                        wgmma<1, 0, HI_SW128, true>(o2, a + 1024 + k * 128, b + k * 2);
                    }
                    wg_commit();
                };
                pv(TrueT{}, 0);
#pragma unroll 1
                for (int j = 1; j < 8; j++) {
                    const uint32_t pslot = r.slot;
                    r.adv(j < 6 ? 2 : 1);
                    pv(FalseT{}, j & 1);
                    wg_wait<1>();
                    mbar_arrive_warp(sb + BAR_REMPTY + pslot * 8, 1);
                    if (j < 7) nb_arrive_r(NB_PEMPTY + ((j - 1) & 1));
                    else mbar_arrive_warp(sb + BAR_XEMPTY + 24, 1);
                }
                wg_wait<0>();
                reg_fence(o0);
                reg_fence(o1);
                reg_fence(o2);
                mbar_arrive_warp(sb + BAR_REMPTY + r.slot * 8, 1);
                mbar_arrive_warp(sb + BAR_XEMPTY + 32, 1);
                r.adv(1);
                nb_sync<NB_L, 256>();
                if (lds_u(sb + OFF_FB) == 0) {
                    unsigned char* gp = ostash_ptr(e);
#pragma unroll
                    for (int g = 0; g < 5; g++) {
                        float2 sc[4];
#pragma unroll
                        for (int t = 0; t < 4; t++) sc[t] = lds_f2(sb + OFF_LINV + (threadIdx.x & 3) * 8 + (4 * g + t) * 32);
                        ostore(o0, g, sc, gp + g * 512);
                        ostore(o1, g, sc, gp + XS + g * 512);
                        if (g < 3) ostore(o2, g, sc, gp + 2 * XS + g * 512);
                    }
                }
                nb_arrive<NB_ODONE, 288>();
            } else {
                op_item<false>(P, e, sb, r, phm);
            }
        }
    }
}

typedef CUresult (*EncFn)(CUtensorMap*, CUtensorMapDataType, cuuint32_t, void*, const cuuint64_t*, const cuuint64_t*,
                          const cuuint32_t*, const cuuint32_t*, CUtensorMapInterleave, CUtensorMapSwizzle,
                          CUtensorMapL2promotion, CUtensorMapFloatOOBfill);

void make_map3(EncFn enc, CUtensorMap* m, void* p, uint64_t rows, uint64_t rowbytes, uint64_t nblk, uint32_t boxrows,
               uint32_t boxblk) {
    cuuint64_t dims[3] = {64, rows, nblk};
    cuuint64_t str[2] = {rowbytes, 128};
    cuuint32_t box[3] = {64, boxrows, boxblk};
    cuuint32_t es[3] = {1, 1, 1};
    enc(m, CU_TENSOR_MAP_DATA_TYPE_BFLOAT16, 3, p, dims, str, box, es, CU_TENSOR_MAP_INTERLEAVE_NONE,
        CU_TENSOR_MAP_SWIZZLE_128B, CU_TENSOR_MAP_L2_PROMOTION_NONE, CU_TENSOR_MAP_FLOAT_OOB_FILL_NONE);
}

#define SCHED_MODE 0

void build_schedule(Params& P) {
    int n[NCTA];
    for (int c = 0; c < NCTA; c++) {
        n[c] = 0;
        for (int i = 0; i < MAXI; i++) P.items[c][i] = 0;
    }
    for (int u = 0; u < 1024; u++) {
        const int br = u >> 9, h = (u >> 4) & 31, b = u & 15;
        const int c = u % NCTA;
        P.items[c][n[c]++] = mk_item(IT_QA, br, b, h, 0, 0);
    }
    if (SCHED_MODE == 0) {
        for (int t = 0; t < 64; t++) {
            const int c = NCTA - 1 - t;
            P.items[c][n[c]++] = mk_item(IT_OP, t >> 5, (t >> 1) & 15, 0, 32, t & 1);
        }
    }
}

}

extern "C" void kernel_launch(void* const* d_in, const int* in_sizes, int n_in, void* d_out, int out_size) {
    static Params P;
    static bool init = false;
    if (!init) {
        EncFn enc = nullptr;
        cudaDriverEntryPointQueryResult qr;
        cudaGetDriverEntryPoint("cuTensorMapEncodeTiled", (void**)&enc, cudaEnableDefault, &qr);
        for (int i = 0; i < 2; i++) {
            P.px[i] = (const __nv_bfloat16*)d_in[5 * i + 0];
            P.pk[i] = (const __nv_bfloat16*)d_in[5 * i + 1];
            P.pv[i] = (const __nv_bfloat16*)d_in[5 * i + 2];
            P.pwq[i] = (const __nv_bfloat16*)d_in[5 * i + 3];
            make_map3(enc, &P.x[i], d_in[5 * i + 0], 2560, 1280, 10, 160, 1);
            make_map3(enc, &P.k[i], d_in[5 * i + 1], 16 * 32 * 512, 384, 3, 64, 3);
            make_map3(enc, &P.v[i], d_in[5 * i + 2], 16 * 32 * 512, 384, 3, 64, 3);
            make_map3(enc, &P.wq[i], d_in[5 * i + 3], 640, 12288, 96, 64, 3);
            make_map3(enc, &P.wo[i], d_in[5 * i + 4], 6144, 1280, 10, 32, 5);
        }
        cuuint64_t dims[2] = {1280, 2560};
        cuuint64_t str[1] = {2560};
        cuuint32_t box[2] = {64, 160};
        cuuint32_t es[2] = {1, 1};
        enc(&P.out, CU_TENSOR_MAP_DATA_TYPE_BFLOAT16, 2, d_out, dims, str, box, es, CU_TENSOR_MAP_INTERLEAVE_NONE,
            CU_TENSOR_MAP_SWIZZLE_128B, CU_TENSOR_MAP_L2_PROMOTION_NONE, CU_TENSOR_MAP_FLOAT_OOB_FILL_NONE);
        build_schedule(P);
        cudaFuncSetAttribute(fused_kernel, cudaFuncAttributeMaxDynamicSharedMemorySize, SMEM_BYTES);
        init = true;
    }
    fused_kernel<<<NCTA, 384, SMEM_BYTES>>>(P);
}
```

```cpp
#include <cuda_runtime.h>
#include <cuda.h>
#include <cuda_bf16.h>
#include <stdint.h>

namespace {

constexpr int NCTA = 132;
constexpr int MAXI = 16;
constexpr int SLOT = 24576;
constexpr int NSLOT = 5;
constexpr int XS = 20480;
constexpr int OFF_R = 0;
constexpr int OFF_RING = 5 * XS;
constexpr int OFF_MISC = OFF_RING + NSLOT * SLOT;
constexpr int OFF_LX = OFF_MISC;
constexpr int OFF_LINV = OFF_LX + 2560;
constexpr int OFF_FB = OFF_LINV + 640;
constexpr int OFF_GM = OFF_FB + 16;
constexpr int OFF_BAR = OFF_GM + 16;
constexpr int BAR_RFULL = OFF_BAR;
constexpr int BAR_REMPTY = BAR_RFULL + 40;
constexpr int BAR_XFULL = BAR_REMPTY + 40;
constexpr int BAR_XEMPTY = BAR_XFULL + 40;
constexpr int SMEM_BYTES = BAR_XEMPTY + 40;
static_assert(SMEM_BYTES <= 232448, "smem");

constexpr int NB_S = 1, NB_VOTE = 2, NB_PFULL = 3, NB_PEMPTY = 5, NB_Q2 = 7, NB_SDONE = 8, NB_PDONE = 9,
              NB_L = 10, NB_OPST = 11, NB_ODONE = 12, NB_OPEND = 13;

constexpr uint32_t IT_QA = 1, IT_OP = 2;
__host__ __device__ constexpr uint32_t mk_item(uint32_t type, uint32_t br, uint32_t b, uint32_t h0, uint32_t h1, uint32_t half) {
    return type | (br << 2) | (b << 3) | (h0 << 7) | (h1 << 13) | (half << 19);
}
#define IT_TYPE(e) ((e) & 3u)
#define IT_BR(e) (((e) >> 2) & 1u)
#define IT_B(e) (((e) >> 3) & 15u)
#define IT_H0(e) (((e) >> 7) & 63u)
#define IT_H1(e) (((e) >> 13) & 63u)
#define IT_HALF(e) (((e) >> 19) & 1u)

struct Params {
    CUtensorMap x[2], wq[2], k[2], v[2], wo[2], out;
    const __nv_bfloat16 *px[2], *pwq[2], *pk[2], *pv[2];
    uint32_t items[NCTA][MAXI];
};

constexpr int OUNIT = 61440;
__device__ __align__(1024) unsigned char g_ostash[(size_t)1024 * OUNIT];
__device__ unsigned int g_flag[1024];
__device__ unsigned int g_epoch[NCTA];

constexpr int SMEM_LAUNCH = SMEM_BYTES;
#define TS(role, idx)
#define TS_DUMP(role)
#define TS2(cond, idx)

#define SP_J0 6
#define PF_POS 12
constexpr float SM_C = 0.07216878364870322f * 1.4426950408889634f;

__device__ __forceinline__ void mbar_init(uint32_t a, uint32_t c) {
    asm volatile("mbarrier.init.shared::cta.b64 [%0], %1;" ::"r"(a), "r"(c) : "memory");
}
__device__ __forceinline__ void mbar_expect(uint32_t a, uint32_t b) {
    asm volatile("mbarrier.arrive.expect_tx.shared::cta.b64 _, [%0], %1;" ::"r"(a), "r"(b) : "memory");
}
__device__ __forceinline__ void mbar_arrive_warp(uint32_t a, uint32_t cnt) {
    asm volatile(
        "{\n.reg .pred p;\nelect.sync _|p, 0xffffffff;\n"
        "@p mbarrier.arrive.shared::cta.b64 _, [%0], %1;\n}" ::"r"(a), "r"(cnt)
        : "memory");
}
__device__ __forceinline__ void mbar_wait(uint32_t a, uint32_t ph) {
    asm volatile(
        "{\n.reg .pred p;\n.reg .u32 n;\n"
        "mbarrier.try_wait.parity.shared::cta.b64 p, [%0], %1;\n"
        "@p bra DONE;\n"
        "mov.u32 n, 0;\n"
        "LOOP:\n"
        "mbarrier.try_wait.parity.shared::cta.b64 p, [%0], %1;\n"
        "@p bra DONE;\n"
        "add.u32 n, n, 1;\n"
        "setp.lt.u32 p, n, 0x4000000;\n"
        "@p bra LOOP;\n"
        "trap;\n"
        "DONE:\n}" ::"r"(a), "r"(ph)
        : "memory");
}
template <int ID, int CNT>
__device__ __forceinline__ void nb_sync() { asm volatile("bar.sync %0, %1;" ::"n"(ID), "n"(CNT) : "memory"); }
template <int ID, int CNT>
__device__ __forceinline__ void nb_arrive() { asm volatile("bar.arrive %0, %1;" ::"n"(ID), "n"(CNT) : "memory"); }
__device__ __forceinline__ void nb_sync_r(uint32_t id) { asm volatile("bar.sync %0, 256;" ::"r"(id) : "memory"); }
__device__ __forceinline__ void nb_arrive_r(uint32_t id) { asm volatile("bar.arrive %0, 256;" ::"r"(id) : "memory"); }
__device__ __forceinline__ void fence_async_smem() { asm volatile("fence.proxy.async.shared::cta;" ::: "memory"); }

__device__ __forceinline__ void tma3(uint32_t dst, const CUtensorMap* m, int c1, int c2, uint32_t bar, uint64_t pol) {
    asm volatile(
        "cp.async.bulk.tensor.3d.shared::cluster.global.mbarrier::complete_tx::bytes.L2::cache_hint [%0], [%1, {%3,%4,%5}], [%2], %6;" ::"r"(dst),
        "l"(m), "r"(bar), "r"(0), "r"(c1), "r"(c2), "l"(pol)
        : "memory");
}
__device__ __forceinline__ void bulk_load(uint32_t dst, const void* src, uint32_t bytes, uint32_t bar) {
    asm volatile("cp.async.bulk.shared::cluster.global.mbarrier::complete_tx::bytes [%0], [%1], %2, [%3];" ::"r"(dst),
                 "l"(src), "r"(bytes), "r"(bar)
                 : "memory");
}
__device__ __forceinline__ void wg_fence() { asm volatile("wgmma.fence.sync.aligned;" ::: "memory"); }
__device__ __forceinline__ void wg_commit() { asm volatile("wgmma.commit_group.sync.aligned;" ::: "memory"); }
template <int N>
__device__ __forceinline__ void wg_wait() { asm volatile("wgmma.wait_group.sync.aligned %0;" ::"n"(N) : "memory"); }

#define RW80(c, d) c(d[0]), c(d[1]), c(d[2]), c(d[3]), c(d[4]), c(d[5]), c(d[6]), c(d[7]), c(d[8]), c(d[9]), c(d[10]), c(d[11]), c(d[12]), c(d[13]), c(d[14]), c(d[15]), c(d[16]), c(d[17]), c(d[18]), c(d[19]), c(d[20]), c(d[21]), c(d[22]), c(d[23]), c(d[24]), c(d[25]), c(d[26]), c(d[27]), c(d[28]), c(d[29]), c(d[30]), c(d[31]), c(d[32]), c(d[33]), c(d[34]), c(d[35]), c(d[36]), c(d[37]), c(d[38]), c(d[39]), c(d[40]), c(d[41]), c(d[42]), c(d[43]), c(d[44]), c(d[45]), c(d[46]), c(d[47]), c(d[48]), c(d[49]), c(d[50]), c(d[51]), c(d[52]), c(d[53]), c(d[54]), c(d[55]), c(d[56]), c(d[57]), c(d[58]), c(d[59]), c(d[60]), c(d[61]), c(d[62]), c(d[63]), c(d[64]), c(d[65]), c(d[66]), c(d[67]), c(d[68]), c(d[69]), c(d[70]), c(d[71]), c(d[72]), c(d[73]), c(d[74]), c(d[75]), c(d[76]), c(d[77]), c(d[78]), c(d[79])
#define RW48(c, d) c(d[0]), c(d[1]), c(d[2]), c(d[3]), c(d[4]), c(d[5]), c(d[6]), c(d[7]), c(d[8]), c(d[9]), c(d[10]), c(d[11]), c(d[12]), c(d[13]), c(d[14]), c(d[15]), c(d[16]), c(d[17]), c(d[18]), c(d[19]), c(d[20]), c(d[21]), c(d[22]), c(d[23]), c(d[24]), c(d[25]), c(d[26]), c(d[27]), c(d[28]), c(d[29]), c(d[30]), c(d[31]), c(d[32]), c(d[33]), c(d[34]), c(d[35]), c(d[36]), c(d[37]), c(d[38]), c(d[39]), c(d[40]), c(d[41]), c(d[42]), c(d[43]), c(d[44]), c(d[45]), c(d[46]), c(d[47])
#define RW32(c, d) c(d[0]), c(d[1]), c(d[2]), c(d[3]), c(d[4]), c(d[5]), c(d[6]), c(d[7]), c(d[8]), c(d[9]), c(d[10]), c(d[11]), c(d[12]), c(d[13]), c(d[14]), c(d[15]), c(d[16]), c(d[17]), c(d[18]), c(d[19]), c(d[20]), c(d[21]), c(d[22]), c(d[23]), c(d[24]), c(d[25]), c(d[26]), c(d[27]), c(d[28]), c(d[29]), c(d[30]), c(d[31])

__device__ __forceinline__ void reg_fence(float (&d)[80]) { asm volatile("" : RW80("+f", d)::"memory"); }
__device__ __forceinline__ void reg_fence(float (&d)[48]) { asm volatile("" : RW48("+f", d)::"memory"); }
__device__ __forceinline__ void reg_fence(float (&d)[32]) { asm volatile("" : RW32("+f", d)::"memory"); }

constexpr uint32_t HI_SW128 = (1024u >> 4) | (1u << 30);
constexpr uint32_t HI_OST = (2560u >> 4) | (2u << 30);
constexpr uint32_t LO_LBO1 = (1u << 16);
constexpr uint32_t LO_OST = ((512u >> 4) << 16);

template <int TA, int TB, uint32_t HIB, bool ACC>
__device__ __forceinline__ void wgmma(float (&d)[80], uint32_t loA, uint32_t loB) {
#define WG_ASM(SD)                                                          \
    "{\n.reg .b64 da, db;\nmov.b64 da, {%80, %82};\nmov.b64 db, {%81, %83};\n" \
    "wgmma.mma_async.sync.aligned.m64n160k16.f32.bf16.bf16 "               \
    "{%0,%1,%2,%3,%4,%5,%6,%7,%8,%9,%10,%11,%12,%13,%14,%15,%16,%17,%18,%19,%20,%21,%22,%23,%24,%25,%26,%27,%28,%29,%30,%31,%32,%33,%34,%35,%36,%37,%38,%39,%40,%41,%42,%43,%44,%45,%46,%47,%48,%49,%50,%51,%52,%53,%54,%55,%56,%57,%58,%59,%60,%61,%62,%63,%64,%65,%66,%67,%68,%69,%70,%71,%72,%73,%74,%75,%76,%77,%78,%79}, da, db, " SD ", 1, 1, %84, %85;\n}"
    if constexpr (ACC)
        asm volatile(WG_ASM("1") : RW80("+f", d) : "r"(loA), "r"(loB), "n"(HI_SW128), "n"(HIB), "n"(TA), "n"(TB));
    else
        asm volatile(WG_ASM("0") : RW80("=f", d) : "r"(loA), "r"(loB), "n"(HI_SW128), "n"(HIB), "n"(TA), "n"(TB));
#undef WG_ASM
}
template <int TA, int TB, uint32_t HIB, bool ACC>
__device__ __forceinline__ void wgmma(float (&d)[48], uint32_t loA, uint32_t loB) {
#define WG_ASM(SD)                                                          \
    "{\n.reg .b64 da, db;\nmov.b64 da, {%48, %50};\nmov.b64 db, {%49, %51};\n" \
    "wgmma.mma_async.sync.aligned.m64n96k16.f32.bf16.bf16 "               \
    "{%0,%1,%2,%3,%4,%5,%6,%7,%8,%9,%10,%11,%12,%13,%14,%15,%16,%17,%18,%19,%20,%21,%22,%23,%24,%25,%26,%27,%28,%29,%30,%31,%32,%33,%34,%35,%36,%37,%38,%39,%40,%41,%42,%43,%44,%45,%46,%47}, da, db, " SD ", 1, 1, %52, %53;\n}"
    if constexpr (ACC)
        asm volatile(WG_ASM("1") : RW48("+f", d) : "r"(loA), "r"(loB), "n"(HI_SW128), "n"(HIB), "n"(TA), "n"(TB));
    else
        asm volatile(WG_ASM("0") : RW48("=f", d) : "r"(loA), "r"(loB), "n"(HI_SW128), "n"(HIB), "n"(TA), "n"(TB));
#undef WG_ASM
}
template <int TA, int TB, uint32_t HIB, bool ACC>
__device__ __forceinline__ void wgmma(float (&d)[32], uint32_t loA, uint32_t loB) {
#define WG_ASM(SD)                                                          \
    "{\n.reg .b64 da, db;\nmov.b64 da, {%32, %34};\nmov.b64 db, {%33, %35};\n" \
    "wgmma.mma_async.sync.aligned.m64n64k16.f32.bf16.bf16 "               \
    "{%0,%1,%2,%3,%4,%5,%6,%7,%8,%9,%10,%11,%12,%13,%14,%15,%16,%17,%18,%19,%20,%21,%22,%23,%24,%25,%26,%27,%28,%29,%30,%31}, da, db, " SD ", 1, 1, %36, %37;\n}"
    if constexpr (ACC)
        asm volatile(WG_ASM("1") : RW32("+f", d) : "r"(loA), "r"(loB), "n"(HI_SW128), "n"(HIB), "n"(TA), "n"(TB));
    else
        asm volatile(WG_ASM("0") : RW32("=f", d) : "r"(loA), "r"(loB), "n"(HI_SW128), "n"(HIB), "n"(TA), "n"(TB));
#undef WG_ASM
}

__device__ __forceinline__ uint32_t pack_bf16(float lo, float hi) {
    uint32_t r;
    asm("cvt.rn.bf16x2.f32 %0, %1, %2;" : "=r"(r) : "f"(hi), "f"(lo));
    return r;
}
__device__ __forceinline__ float ex2(float x) {
    float r;
    asm("ex2.approx.ftz.f32 %0, %1;" : "=f"(r) : "f"(x));
    return r;
}
__device__ __forceinline__ void stsm4t(uint32_t a, uint32_t r0, uint32_t r1, uint32_t r2, uint32_t r3) {
    asm volatile("stmatrix.sync.aligned.m8n8.x4.trans.shared.b16 [%0], {%1,%2,%3,%4};" ::"r"(a), "r"(r0), "r"(r1), "r"(r2), "r"(r3)
                 : "memory");
}
__device__ __forceinline__ uint32_t lds_u(uint32_t a) {
    uint32_t v;
    asm volatile("ld.shared.u32 %0, [%1];" : "=r"(v) : "r"(a) : "memory");
    return v;
}
__device__ __forceinline__ float2 lds_f2(uint32_t a) {
    float2 v;
    asm volatile("ld.shared.v2.f32 {%0,%1}, [%2];" : "=f"(v.x), "=f"(v.y) : "r"(a) : "memory");
    return v;
}
__device__ __forceinline__ void sts_f(uint32_t a, float v) { asm volatile("st.shared.f32 [%0], %1;" ::"r"(a), "f"(v) : "memory"); }
__device__ __forceinline__ void sts_u(uint32_t a, uint32_t v) { asm volatile("st.shared.u32 [%0], %1;" ::"r"(a), "r"(v) : "memory"); }
__device__ __forceinline__ void sts_f2(uint32_t a, float x, float y) {
    asm volatile("st.shared.v2.f32 [%0], {%1,%2};" ::"r"(a), "f"(x), "f"(y) : "memory");
}

__device__ __forceinline__ void store_tile_t(const float (&d)[80], uint32_t addr) {
#pragma unroll
    for (int j = 0; j < 10; j++)
        stsm4t(addr + j * 2048, pack_bf16(d[8 * j], d[8 * j + 1]), pack_bf16(d[8 * j + 2], d[8 * j + 3]),
               pack_bf16(d[8 * j + 4], d[8 * j + 5]), pack_bf16(d[8 * j + 6], d[8 * j + 7]));
}
template <int NR>
__device__ __forceinline__ void store_out_tile(const float (&d)[NR], uint32_t base, uint32_t lane, uint32_t w) {
    const uint32_t mi = lane >> 3, i = lane & 7;
    const uint32_t chunk = 2 * w + (mi & 1);
    const uint32_t q0 = 8 * (i >> 1) + 2 * (mi >> 1) + (i & 1);
    const uint32_t a0 = base + q0 * 128 + ((chunk ^ (q0 & 7)) << 4);
    const uint32_t a1 = base + (q0 + 4) * 128 + ((chunk ^ ((q0 + 4) & 7)) << 4);
#pragma unroll
    for (int j = 0; j < NR / 8; j++)
        stsm4t(((j & 1) ? a1 : a0) + (j >> 1) * 4096, pack_bf16(d[8 * j], d[8 * j + 1]), pack_bf16(d[8 * j + 2], d[8 * j + 3]),
               pack_bf16(d[8 * j + 4], d[8 * j + 5]), pack_bf16(d[8 * j + 6], d[8 * j + 7]));
}

struct TrueT { static constexpr bool value = true; };
struct FalseT { static constexpr bool value = false; };

template <int V>
struct IntT { static constexpr int value = V; };

struct Ring {
    uint32_t slot, ph;
    __device__ __forceinline__ void adv(uint32_t k) {
        slot += k;
        if (slot >= NSLOT) { slot -= NSLOT; ph ^= 1; }
    }
};

template <int K>
__device__ __forceinline__ void qk_step(float (&s)[80], uint32_t loK, uint32_t loQ) {
    wgmma<0, 0, HI_SW128, K != 0>(s, loK + (K >> 2) * (8192 >> 4) + (K & 3) * 2, loQ + (K >> 2) * (XS >> 4) + (K & 3) * 2);
}
template <int K0, int K1>
__device__ __forceinline__ void qk_steps(float (&s)[80], uint32_t loK, uint32_t loQ) {
    if constexpr (K0 < K1) {
        qk_step<K0>(s, loK, loQ);
        qk_steps<K0 + 1, K1>(s, loK, loQ);
    }
}
template <int J>
__device__ __forceinline__ void exp_chunk(const float (&s)[80], float (&ps)[40], uint32_t pa, float mref) {
    float p[8];
#pragma unroll
    for (int i = 0; i < 8; i++) p[i] = ex2(fmaf(s[8 * J + i], SM_C, -mref));
    stsm4t(pa + J * 2048, pack_bf16(p[0], p[1]), pack_bf16(p[2], p[3]), pack_bf16(p[4], p[5]), pack_bf16(p[6], p[7]));
    ps[4 * J] = p[0] + p[2];
    ps[4 * J + 1] = p[1] + p[3];
    ps[4 * J + 2] = p[4] + p[6];
    ps[4 * J + 3] = p[5] + p[7];
}
template <int J, int J0, int K0, bool QK, bool PVB>
__device__ __forceinline__ void exp_interleaved(const float (&s)[80], float (&ps)[40], float (&sn)[80], float (&ob)[32],
                                                uint32_t pa, float mref, uint32_t loK, uint32_t loQ, uint32_t loV, uint32_t loP) {
    if constexpr (J < 10) {
        if constexpr (J == J0) wg_fence();
        if constexpr (PVB && J >= J0 && J < J0 + 4) wgmma<1, 0, HI_SW128, true>(ob, loV + (J - J0) * 128, loP + (J - J0) * 2);
        if constexpr (QK && J >= J0) qk_step<K0 + J - J0>(sn, loK, loQ);
        exp_chunk<J>(s, ps, pa, mref);
        exp_interleaved<J + 1, J0, K0, QK, PVB>(s, ps, sn, ob, pa, mref, loK, loQ, loV, loP);
    }
}
__device__ __forceinline__ void sum_block(const float (&ps)[40], float (&l)[20], bool hi) {
#pragma unroll
    for (int j = 0; j < 10; j++) {
        l[2 * j] += (hi ? ps[4 * j + 2] : ps[4 * j]) + __shfl_xor_sync(0xffffffffu, hi ? ps[4 * j] : ps[4 * j + 2], 16);
        l[2 * j + 1] += (hi ? ps[4 * j + 3] : ps[4 * j + 1]) + __shfl_xor_sync(0xffffffffu, hi ? ps[4 * j + 1] : ps[4 * j + 3], 16);
    }
}

__device__ __forceinline__ void fallback_unit(const Params& P, uint32_t e, uint32_t tid) {
    const uint32_t lane = tid & 31, br = IT_BR(e), b = IT_B(e), h = IT_H0(e);
    const uint32_t u = (br * 16 + b) * 32 + h;
    const __nv_bfloat162* wq = (const __nv_bfloat162*)(P.pwq[br] + h * 192) + lane;
    const __nv_bfloat162* kp = (const __nv_bfloat162*)(P.pk[br] + (size_t)(b * 32 + h) * 512 * 192) + lane;
    const __nv_bfloat162* vp = (const __nv_bfloat162*)(P.pv[br] + (size_t)(b * 32 + h) * 512 * 192) + lane;
#pragma unroll 1
    for (uint32_t q = tid >> 5; q < 160; q += 4) {
        const __nv_bfloat16* xr = P.px[br] + (size_t)(b * 160 + q) * 640;
        float a[6] = {0.f, 0.f, 0.f, 0.f, 0.f, 0.f};
#pragma unroll 4
        for (int k = 0; k < 640; k++) {
            const float xv = __bfloat162float(xr[k]);
#pragma unroll
            for (int i = 0; i < 3; i++) {
                const float2 wv = __bfloat1622float2(wq[(size_t)k * 3072 + i * 32]);
                a[2 * i] = fmaf(xv, wv.x, a[2 * i]);
                a[2 * i + 1] = fmaf(xv, wv.y, a[2 * i + 1]);
            }
        }
#pragma unroll
        for (int i = 0; i < 6; i++) a[i] = __bfloat162float(__float2bfloat16(a[i]));
        auto score = [&](int key) {
            float d = 0.f;
#pragma unroll
            for (int i = 0; i < 3; i++) {
                const float2 kv = __bfloat1622float2(kp[key * 96 + i * 32]);
                d = fmaf(a[2 * i], kv.x, fmaf(a[2 * i + 1], kv.y, d));
            }
#pragma unroll
            for (int o = 16; o > 0; o >>= 1) d += __shfl_xor_sync(0xffffffffu, d, o);
            return d;
        };
        float m = -INFINITY;
#pragma unroll 4
        for (int key = 0; key < 512; key++) m = fmaxf(m, score(key));
        float o[6] = {0.f, 0.f, 0.f, 0.f, 0.f, 0.f}, sum = 0.f;
#pragma unroll 4
        for (int key = 0; key < 512; key++) {
            const float p = ex2((score(key) - m) * SM_C);
            sum += p;
#pragma unroll
            for (int i = 0; i < 3; i++) {
                const float2 vv = __bfloat1622float2(vp[key * 96 + i * 32]);
                o[2 * i] = fmaf(p, vv.x, o[2 * i]);
                o[2 * i + 1] = fmaf(p, vv.y, o[2 * i + 1]);
            }
        }
        const float inv = 1.f / sum;
        __nv_bfloat16* op = (__nv_bfloat16*)(g_ostash + (size_t)u * OUNIT) + (q >> 5) * 256 + 2 * ((q & 31) >> 3) + (q & 1);
#pragma unroll
        for (int i = 0; i < 6; i++) {
            const uint32_t d = (i >> 1) * 64 + 2 * lane + (i & 1);
            op[(d >> 3) * 1280 + (d & 7) * 32 + ((((q & 7) >> 1) ^ ((d & 7) >> 1)) << 3)] = __float2bfloat16(o[i] * inv);
        }
    }
}

template <bool IS_S>
__device__ __forceinline__ void qproj(float (&q0)[80], float (&q1)[80], uint32_t sb, Ring& r, uint32_t& phm) {
    const uint32_t loR = ((sb + OFF_R) >> 4) | LO_LBO1;
    const uint32_t loRing = ((sb + OFF_RING) >> 4) | LO_LBO1;
    uint32_t xs = 0;
    auto step = [&](auto first) {
        constexpr bool F = decltype(first)::value;
        mbar_wait(sb + BAR_RFULL + r.slot * 8, r.ph);
        mbar_wait(sb + BAR_XFULL + xs * 8, (phm >> xs) & 1);
        phm ^= 1u << xs;
        const uint32_t a = loRing + r.slot * (SLOT >> 4) + (IS_S ? 0 : 1024), b = loR + xs * (XS >> 4);
        wg_fence();
        wgmma<1, 0, HI_SW128, !F>(q0, a, b);
        if (IS_S) wgmma<1, 0, HI_SW128, !F>(q1, a + 512, b);
#pragma unroll
        for (int k = 1; k < 4; k++) {
            wgmma<1, 0, HI_SW128, true>(q0, a + k * 128, b + k * 2);
            if (IS_S) wgmma<1, 0, HI_SW128, true>(q1, a + 512 + k * 128, b + k * 2);
        }
        wg_commit();
    };
    step(TrueT{});
#pragma unroll 1
    for (int kk = 1; kk < 10; kk++) {
        const uint32_t pslot = r.slot;
        r.adv(1);
        if (++xs == 5) xs = 0;
        if (!IS_S && kk == 8) nb_sync<NB_SDONE, 256>();
        step(FalseT{});
        wg_wait<1>();
        mbar_arrive_warp(sb + BAR_REMPTY + pslot * 8, 1);
        if (kk <= 5) mbar_arrive_warp(sb + BAR_XEMPTY + (kk - 1) * 8, 1);
        if (!IS_S && kk == 7) nb_arrive<NB_PDONE, 256>();
    }
    if (IS_S) nb_arrive<NB_SDONE, 256>();
    wg_wait<0>();
    reg_fence(q0);
    if (IS_S) reg_fence(q1);
    mbar_arrive_warp(sb + BAR_REMPTY + r.slot * 8, 1);
    r.adv(1);
}

template <int NR>
__device__ __forceinline__ void ostore(const float (&o)[NR], int gl, const float2 (&sc)[4], unsigned char* gp) {
#pragma unroll
    for (int hh = 0; hh < 2; hh++)
        asm volatile("st.global.v4.b32 [%0], {%1,%2,%3,%4};" ::"l"(gp + hh * 2560),
                     "r"(pack_bf16(o[16 * gl + 2 * hh] * sc[0].x, o[16 * gl + 2 * hh + 1] * sc[0].y)),
                     "r"(pack_bf16(o[16 * gl + 4 + 2 * hh] * sc[1].x, o[16 * gl + 5 + 2 * hh] * sc[1].y)),
                     "r"(pack_bf16(o[16 * gl + 8 + 2 * hh] * sc[2].x, o[16 * gl + 9 + 2 * hh] * sc[2].y)),
                     "r"(pack_bf16(o[16 * gl + 12 + 2 * hh] * sc[3].x, o[16 * gl + 13 + 2 * hh] * sc[3].y))
                     : "memory");
}
__device__ __forceinline__ unsigned char* ostash_ptr(uint32_t e) {
    const uint32_t u = (IT_BR(e) * 16 + IT_B(e)) * 32 + IT_H0(e);
    const uint32_t lane = threadIdx.x & 31, w = (threadIdx.x >> 5) & 3;
    return g_ostash + (size_t)u * OUNIT + w * 5120 + (lane >> 2) * 64 + (((lane ^ (lane >> 3)) & 3) << 4);
}

template <bool IS_S>
__device__ __forceinline__ void op_item(const Params& P, uint32_t e, uint32_t sb, Ring& r, uint32_t& phm) {
    constexpr int T0 = IS_S ? 0 : 2;
    constexpr uint32_t BOFF = IS_S ? (3 * 512) >> 4 : 0;
    const uint32_t loRing = ((sb + OFF_RING) >> 4) | LO_LBO1;
    const uint32_t loO = ((sb + OFF_R) >> 4) | LO_OST;
    float c0[80], c1[80], c2[IS_S ? 32 : 48];
    const int T2 = 6 * (IT_H1(e) - IT_H0(e));
    uint32_t xs = 0;
    auto step = [&](auto first, uint32_t hf) {
        constexpr bool F = decltype(first)::value;
        if (hf == 0) {
            mbar_wait(sb + BAR_XFULL + xs * 8, (phm >> xs) & 1);
            phm ^= 1u << xs;
        }
        mbar_wait(sb + BAR_RFULL + r.slot * 8, r.ph);
        const uint32_t a = loRing + r.slot * (SLOT >> 4), b = loO + xs * (XS >> 4) + hf * 640;
        wg_fence();
        wgmma<1, 1, HI_OST, !F>(c0, a + T0 * 256, b);
        wgmma<1, 1, HI_OST, !F>(c1, a + T0 * 256 + 256, b);
        wgmma<1, 1, HI_OST, !F>(c2, a + 1024, b + BOFF);
        wgmma<1, 1, HI_OST, true>(c0, a + T0 * 256 + 128, b + 320);
        wgmma<1, 1, HI_OST, true>(c1, a + T0 * 256 + 384, b + 320);
        wgmma<1, 1, HI_OST, true>(c2, a + 1024 + 128, b + 320 + BOFF);
        wg_commit();
    };
    step(TrueT{}, 0);
#pragma unroll 1
    for (int t = 1; t < T2; t++) {
        const uint32_t pslot = r.slot, pxs = xs;
        r.adv(1);
        if ((t & 1) == 0 && ++xs == 5) xs = 0;
        step(FalseT{}, t & 1);
        wg_wait<1>();
        mbar_arrive_warp(sb + BAR_REMPTY + pslot * 8, 1);
        if ((t & 1) == 0 && t + 8 < T2) mbar_arrive_warp(sb + BAR_XEMPTY + pxs * 8, 1);
    }
    wg_wait<0>();
    reg_fence(c0);
    reg_fence(c1);
    reg_fence(c2);
    mbar_arrive_warp(sb + BAR_REMPTY + r.slot * 8, 1);
    r.adv(1);
    nb_sync<NB_OPEND, 256>();
    const uint32_t lane = threadIdx.x & 31, w = (threadIdx.x >> 5) & 3;
    store_out_tile(c0, sb + OFF_R + T0 * XS, lane, w);
    store_out_tile(c1, sb + OFF_R + (T0 + 1) * XS, lane, w);
    store_out_tile(c2, sb + OFF_R + 4 * XS + (IS_S ? 96 * 128 : 0), lane, w);
    fence_async_smem();
    if (IS_S) {
        nb_arrive<NB_OPST, 256>();
    } else {
        nb_sync<NB_OPST, 256>();
        if ((threadIdx.x & 127) == 0) {
            const int cc0 = IT_BR(e) * 640 + IT_HALF(e) * 320;
#pragma unroll
            for (int m = 0; m < 5; m++)
                asm volatile("cp.async.bulk.tensor.2d.global.shared::cta.bulk_group [%0, {%2,%3}], [%1];" ::"l"(&P.out),
                             "r"(sb + OFF_R + m * XS), "r"(cc0 + m * 64), "r"((int)IT_B(e) * 160)
                             : "memory");
            asm volatile("cp.async.bulk.commit_group;" ::: "memory");
            asm volatile("cp.async.bulk.wait_group 0;" ::: "memory");
#pragma unroll
            for (int m = 0; m < 5; m++)
                asm volatile("mbarrier.arrive.shared::cta.b64 _, [%0], 8;" ::"r"(sb + BAR_XEMPTY + m * 8) : "memory");
        }
        __syncwarp();
    }
}

__global__ void __launch_bounds__(384, 1) fused_kernel(const __grid_constant__ Params P) {
    extern __shared__ __align__(1024) unsigned char smem_raw[];
    const uint32_t sb = (uint32_t)__cvta_generic_to_shared(smem_raw);
    const uint32_t wgid = __shfl_sync(0xffffffffu, threadIdx.x >> 7, 0);
    const uint32_t cta = blockIdx.x;
    const uint32_t* items = P.items[cta];

    uint32_t epoch = 0;
    if (wgid == 0) epoch = *(volatile unsigned int*)&g_epoch[cta] + 1;
    if (threadIdx.x == 0) {
        if (sb & 1023) __trap();
        for (int i = 0; i < NSLOT; i++) {
            mbar_init(sb + BAR_RFULL + i * 8, 1);
            mbar_init(sb + BAR_REMPTY + i * 8, 8);
            mbar_init(sb + BAR_XFULL + i * 8, 1);
            mbar_init(sb + BAR_XEMPTY + i * 8, 8);
        }
        asm volatile("fence.mbarrier_init.release.cluster;" ::: "memory");
        fence_async_smem();
    }
    __syncthreads();

    if (wgid == 0) {
        asm volatile("setmaxnreg.dec.sync.aligned.u32 24;");
        const uint32_t warp = __shfl_sync(0xffffffffu, threadIdx.x >> 5, 0);
        if (warp == 0) {
            if (threadIdx.x == 0) {
                *(volatile unsigned int*)&g_epoch[cta] = epoch;
                uint64_t pol_first, pol_norm;
                asm volatile("createpolicy.fractional.L2::evict_first.b64 %0, 1.0;" : "=l"(pol_first));
                asm volatile("createpolicy.fractional.L2::evict_normal.b64 %0, 1.0;" : "=l"(pol_norm));
                Ring r{0, 1};
                for (int it = 0; it < MAXI; it++) {
                    const uint32_t e = items[it];
                    if (e == 0) break;
                    const uint32_t br = IT_BR(e);
                    if (IT_TYPE(e) == IT_QA) {
                        const uint32_t h = IT_H0(e);
#pragma unroll 1
                        for (int kk = 0; kk < 10; kk++) {
                            mbar_wait(sb + BAR_REMPTY + r.slot * 8, r.ph);
                            mbar_expect(sb + BAR_RFULL + r.slot * 8, SLOT);
                            tma3(sb + OFF_RING + r.slot * SLOT, &P.wq[br], kk * 64, h * 3, sb + BAR_RFULL + r.slot * 8, pol_norm);
                            r.adv(1);
                        }
                        const int row0 = (IT_B(e) * 32 + h) * 512;
#pragma unroll 1
                        for (int n = 0; n < 16; n++) {
                            const bool isv = n == 15 || (n > 0 && !(n & 1));
                            const int j = n == 15 ? 7 : isv ? (n - 2) >> 1 : (n + 1) >> 1;
                            mbar_wait(sb + BAR_REMPTY + r.slot * 8, r.ph);
                            mbar_expect(sb + BAR_RFULL + r.slot * 8, SLOT);
                            tma3(sb + OFF_RING + r.slot * SLOT, isv ? &P.v[br] : &P.k[br], row0 + j * 64, 0,
                                 sb + BAR_RFULL + r.slot * 8, pol_first);
                            r.adv(1);
                        }
                    } else {
                        const int r0 = IT_H0(e) * 192, r1 = IT_H1(e) * 192;
#pragma unroll 1
                        for (int row = r0; row < r1; row += 32) {
                            mbar_wait(sb + BAR_REMPTY + r.slot * 8, r.ph);
                            mbar_expect(sb + BAR_RFULL + r.slot * 8, XS);
                            tma3(sb + OFF_RING + r.slot * SLOT, &P.wo[br], row, IT_HALF(e) * 5, sb + BAR_RFULL + r.slot * 8, pol_norm);
                            r.adv(1);
                        }
                    }
                }
            }
        } else if (warp == 1) {
            if (threadIdx.x == 32) {
                uint64_t pol_norm;
                asm volatile("createpolicy.fractional.L2::evict_normal.b64 %0, 1.0;" : "=l"(pol_norm));
                uint32_t phm = 0x1f;
                for (int it = 0; it < MAXI; it++) {
                    const uint32_t e = items[it];
                    if (e == 0) break;
                    const uint32_t br = IT_BR(e);
                    uint32_t xs = 0;
                    if (IT_TYPE(e) == IT_QA) {
#pragma unroll 1
                        for (int kk = 0; kk < 10; kk++) {
                            mbar_wait(sb + BAR_XEMPTY + xs * 8, (phm >> xs) & 1);
                            phm ^= 1u << xs;
                            mbar_expect(sb + BAR_XFULL + xs * 8, XS);
                            tma3(sb + OFF_R + xs * XS, &P.x[br], IT_B(e) * 160, kk, sb + BAR_XFULL + xs * 8, pol_norm);
                            if (++xs == 5) xs = 0;
                        }
                    } else {
                        const uint32_t u0 = (br * 16 + IT_B(e)) * 32;
#pragma unroll 1
                        for (uint32_t u = u0 + IT_H0(e); u < u0 + IT_H1(e); u++) {
                            uint32_t v, n = 0;
                            do {
                                asm volatile("ld.acquire.gpu.global.u32 %0, [%1];" : "=r"(v) : "l"(&g_flag[u]) : "memory");
                                if (++n > 0x2000000) __trap();
                            } while (v != epoch);
                            asm volatile("fence.proxy.async;" ::: "memory");
#pragma unroll 1
                            for (int t = 0; t < 3; t++) {
                                mbar_wait(sb + BAR_XEMPTY + xs * 8, (phm >> xs) & 1);
                                phm ^= 1u << xs;
                                mbar_expect(sb + BAR_XFULL + xs * 8, XS);
                                bulk_load(sb + OFF_R + xs * XS, g_ostash + (size_t)u * OUNIT + t * XS, XS, sb + BAR_XFULL + xs * 8);
                                if (++xs == 5) xs = 0;
                            }
                        }
                    }
                }
            }
        } else if (warp == 2) {
            for (int it = 0; it < MAXI; it++) {
                const uint32_t e = items[it];
                if (e == 0) break;
                if (IT_TYPE(e) == IT_QA) {
                    nb_sync<NB_ODONE, 288>();
                    if (threadIdx.x == 64) {
                        __threadfence();
                        const uint32_t u = (IT_BR(e) * 16 + IT_B(e)) * 32 + IT_H0(e);
                        asm volatile("st.relaxed.gpu.global.u32 [%0], %1;" ::"l"(&g_flag[u]), "r"(epoch) : "memory");
                    }
                    __syncwarp();
                }
            }
        }
    } else if (wgid == 1) {
        asm volatile("setmaxnreg.inc.sync.aligned.u32 240;");
        const uint32_t loR = ((sb + OFF_R) >> 4) | LO_LBO1;
        const uint32_t loRing = ((sb + OFF_RING) >> 4) | LO_LBO1;
        Ring r{0, 0};
        uint32_t phm = 0;
#pragma unroll 1
        for (int it = 0; it < MAXI; it++) {
            const uint32_t e = items[it];
            if (e == 0) break;
            if (IT_TYPE(e) == IT_QA) {
                const uint32_t lane = threadIdx.x & 31, w = (threadIdx.x >> 5) & 3;
                const uint32_t stoff = (lane >> 4) * 1024 + (lane & 7) * 128 + (((2 * w + ((lane >> 3) & 1)) ^ (lane & 7)) << 4);
                const bool hi = lane & 16;
                {
                    float q0[80], q1[80];
                    TS(0, 0);
                    qproj<true>(q0, q1, sb, r, phm);
                    TS(0, 1);
                    nb_sync<NB_PDONE, 256>();
                    store_tile_t(q0, sb + OFF_R + stoff);
                    store_tile_t(q1, sb + OFF_R + XS + stoff);
                }
                fence_async_smem();
                float s0[80], s1[80], ob[32], l[20];
#pragma unroll
                for (int i = 0; i < 32; i++) ob[i] = 0.f;
                reg_fence(ob);
                nb_sync<NB_S, 128>();
                TS(0, 2);
                const uint32_t pa = sb + OFF_R + 3 * XS + stoff;
                const uint32_t loPb = loR + 3 * (XS >> 4) + ((96 * 128) >> 4);
                uint32_t kslot = r.slot;
                mbar_wait(sb + BAR_RFULL + r.slot * 8, r.ph);
                wg_fence();
                qk_steps<0, 8>(s0, loRing + r.slot * (SLOT >> 4), loR);
                nb_sync<NB_Q2, 256>();
                qk_steps<8, 12>(s0, loRing + r.slot * (SLOT >> 4), loR);
                wg_commit();
                r.adv(1);
#pragma unroll
                for (int i = 0; i < 20; i++) l[i] = 0.f;
                float mref;
                TS(0, 3);
                auto block = [&](auto mode, float (&cur)[80], float (&nxt)[80], uint32_t buf, bool need_empty, int tsi) {
                    constexpr int MODE = decltype(mode)::value;
                    constexpr int K0 = MODE == 0 ? 4 : 0;
                    uint32_t loK = 0, loV = 0, vslot = 0;
                    const uint32_t pk = kslot;
                    if (MODE != 0) {
                        vslot = r.slot;
                        loV = loRing + r.slot * (SLOT >> 4) + 1024;
                        r.adv(1);
                    }
                    if (MODE == 0) {
                        mbar_wait(sb + BAR_RFULL + r.slot * 8, r.ph);
                        loK = loRing + r.slot * (SLOT >> 4);
                        kslot = r.slot;
                        r.adv(1);
                        wg_fence();
                        qk_steps<0, K0>(nxt, loK, loR);
                        wg_commit();
                        wg_wait<1>();
                    } else {
                        wg_wait<0>();
                    }
                    reg_fence(cur);
                    TS2(tsi == 14, 27);
                    mbar_arrive_warp(sb + BAR_REMPTY + pk * 8, 2);
                    if (MODE == 2) {
                        mbar_arrive_warp(sb + BAR_XEMPTY + 0, 2);
                        mbar_arrive_warp(sb + BAR_XEMPTY + 8, 2);
                        mbar_arrive_warp(sb + BAR_XEMPTY + 16, 2);
                    }
                    if (MODE == 1) {
                        mbar_wait(sb + BAR_RFULL + r.slot * 8, r.ph);
                        loK = loRing + r.slot * (SLOT >> 4);
                        kslot = r.slot;
                        r.adv(1);
                    }
                    TS(0, tsi);
                    if (MODE == 0) {
                        float m0 = fmaxf(cur[0], cur[5]), m1 = fmaxf(cur[10], cur[15]);
#pragma unroll
                        for (int i = 20; i < 80; i += 10) {
                            m0 = fmaxf(m0, cur[i]);
                            m1 = fmaxf(m1, cur[i + 5]);
                        }
                        int key = __float_as_int(fmaxf(m0, m1));
                        key ^= (key >> 31) & 0x7fffffff;
                        key = __reduce_max_sync(0xffffffffu, key);
                        key ^= (key >> 31) & 0x7fffffff;
                        sts_u(sb + OFF_GM + w * 4, key);
                        nb_sync<NB_S, 128>();
                        const float2 u = lds_f2(sb + OFF_GM), v = lds_f2(sb + OFF_GM + 8);
                        mref = fmaxf(fmaxf(u.x, u.y), fmaxf(v.x, v.y)) * SM_C;
                    } else {
                        if (need_empty) nb_sync_r(NB_PEMPTY + buf);
                        else nb_sync<NB_S, 128>();
                    }
                    TS2(tsi == 12, 22);
                    float ps[40];
                    constexpr int J0 = MODE == 0 ? 2 : SP_J0;
                    exp_interleaved<0, J0, K0, MODE != 2, MODE != 0>(cur, ps, nxt, ob, pa + buf * XS, mref, loK, loR, loV,
                                                                 loPb + (buf ^ 1) * (XS >> 4));
                    wg_commit();
                    TS2(tsi == 12, 23);
                    fence_async_smem();
                    TS(0, tsi + 1);
                    if (MODE == 1) {
                        wg_fence();
                        qk_steps<10 - J0, PF_POS>(nxt, loK, loR);
                    }
                    nb_arrive_r(NB_PFULL + buf);
                    if (MODE == 1) {
                        qk_steps<PF_POS, 12>(nxt, loK, loR);
                        wg_commit();
                    }
                    TS2(tsi == 12, 24);
                    if (MODE != 0) {
                        if (MODE == 1) wg_wait<1>();
                        else wg_wait<0>();
                        mbar_arrive_warp(sb + BAR_REMPTY + vslot * 8, 1);
                        if (MODE == 2) mbar_arrive_warp(sb + BAR_XEMPTY + 24, 1);
                    }
                    mbar_wait(sb + BAR_RFULL + r.slot * 8, r.ph);
                    if (MODE == 2) {
                        nb_sync<NB_S, 128>();
                        wg_fence();
#pragma unroll
                        for (int k = 0; k < 4; k++)
                            wgmma<1, 0, HI_SW128, true>(ob, loRing + r.slot * (SLOT >> 4) + 1024 + k * 128, loPb + (XS >> 4) + k * 2);
                        wg_commit();
                    }
                    TS2(tsi == 12, 25);
                    sum_block(ps, l, hi);
                    TS2(tsi == 12, 26);
                };
                block(IntT<0>{}, s0, s1, 0, false, 4);
#pragma unroll 1
                for (int jp = 0; jp < 3; jp++) {
                    block(IntT<1>{}, s1, s0, 1, jp > 0, 6 + 4 * jp);
                    block(IntT<1>{}, s0, s1, 0, true, 8 + 4 * jp);
                }
                block(IntT<2>{}, s1, s0, 1, true, 18);
                const bool b3 = lane & 8, b2 = lane & 4;
#pragma unroll
                for (int i = 0; i < 10; i++)
                    l[i] = (b3 ? l[i + 10] : l[i]) + __shfl_xor_sync(0xffffffffu, b3 ? l[i] : l[i + 10], 8);
#pragma unroll
                for (int i = 0; i < 5; i++)
                    l[i] = (b2 ? l[2 * i + 1] : l[2 * i]) + __shfl_xor_sync(0xffffffffu, b2 ? l[2 * i] : l[2 * i + 1], 4);
                const uint32_t col0 = (b3 ? 80 : 0) + (hi ? 8 : 0) + 2 * (lane & 3) + (b2 ? 1 : 0);
#pragma unroll
                for (int i = 0; i < 5; i++) sts_f(sb + OFF_LX + w * 640 + (col0 + 16 * i) * 4, l[i]);
                nb_sync<NB_S, 128>();
                const uint32_t tid = threadIdx.x & 127;
                float la = 1.f, lb = 1.f;
                if (tid < 80) {
                    float2 v = lds_f2(sb + OFF_LX + tid * 8);
#pragma unroll
                    for (int i = 1; i < 4; i++) {
                        const float2 u = lds_f2(sb + OFF_LX + i * 640 + tid * 8);
                        v.x += u.x;
                        v.y += u.y;
                    }
                    sts_f2(sb + OFF_LINV + tid * 8, __fdividef(1.f, v.x), __fdividef(1.f, v.y));
                    la = v.x;
                    lb = v.y;
                }
                const uint32_t bad = !(la >= 5.421010862e-20f && la <= 1.8446744e19f && lb >= 5.421010862e-20f && lb <= 1.8446744e19f);
                uint32_t any;
                asm volatile(
                    "{\n.reg .pred p, q;\nsetp.ne.u32 p, %1, 0;\n"
                    "bar.red.or.pred q, %2, 128, p;\nselp.u32 %0, 1, 0, q;\n}"
                    : "=r"(any)
                    : "r"(bad), "n"(NB_VOTE)
                    : "memory");
                if (tid == 0) sts_u(sb + OFF_FB, any);
                nb_arrive<NB_L, 256>();
                TS(0, 20);
                wg_wait<0>();
                reg_fence(ob);
                mbar_arrive_warp(sb + BAR_REMPTY + r.slot * 8, 1);
                mbar_arrive_warp(sb + BAR_XEMPTY + 32, 1);
                r.adv(1);
                if (!any) {
                    unsigned char* gp = ostash_ptr(e) + 2 * XS;
#pragma unroll
                    for (int g = 3; g < 5; g++) {
                        float2 sc[4];
#pragma unroll
                        for (int t = 0; t < 4; t++) sc[t] = lds_f2(sb + OFF_LINV + (lane & 3) * 8 + (4 * g + t) * 32);
                        ostore(ob, g - 3, sc, gp + g * 512);
                    }
                } else {
                    fallback_unit(P, e, tid);
                }
                nb_arrive<NB_ODONE, 288>();
                TS(0, 21);
            } else {
                TS(0, 0);
                op_item<true>(P, e, sb, r, phm);
                TS(0, 21);
            }
        }
        TS_DUMP(0);
    } else {
        asm volatile("setmaxnreg.inc.sync.aligned.u32 240;");
        const uint32_t loR = ((sb + OFF_R) >> 4) | LO_LBO1;
        const uint32_t loRing = ((sb + OFF_RING) >> 4) | LO_LBO1;
        Ring r{0, 0};
        uint32_t phm = 0;
#pragma unroll 1
        for (int it = 0; it < MAXI; it++) {
            const uint32_t e = items[it];
            if (e == 0) break;
            if (IT_TYPE(e) == IT_QA) {
                {
                    float q2[80];
                    TS(1, 0);
                    qproj<false>(q2, q2, sb, r, phm);
                    TS(1, 1);
                    const uint32_t lane = threadIdx.x & 31, w = (threadIdx.x >> 5) & 3;
                    const uint32_t stoff = (lane >> 4) * 1024 + (lane & 7) * 128 + (((2 * w + ((lane >> 3) & 1)) ^ (lane & 7)) << 4);
                    store_tile_t(q2, sb + OFF_R + 2 * XS + stoff);
                }
                fence_async_smem();
                nb_arrive<NB_Q2, 256>();
                TS(1, 2);
                float o0[80], o1[80], o2[48];
                r.adv(2);
                auto pv = [&](auto first, uint32_t buf) {
                    constexpr bool F = decltype(first)::value;
                    nb_sync_r(NB_PFULL + buf);
                    mbar_wait(sb + BAR_RFULL + r.slot * 8, r.ph);
                    const uint32_t a = loRing + r.slot * (SLOT >> 4), b = loR + (3 + buf) * (XS >> 4);
                    wg_fence();
                    wgmma<1, 0, HI_SW128, !F>(o0, a, b);
                    wgmma<1, 0, HI_SW128, !F>(o1, a + 512, b);
                    wgmma<1, 0, HI_SW128, !F>(o2, a + 1024, b);
#pragma unroll
                    for (int k = 1; k < 4; k++) {
                        wgmma<1, 0, HI_SW128, true>(o0, a + k * 128, b + k * 2);
                        wgmma<1, 0, HI_SW128, true>(o1, a + 512 + k * 128, b + k * 2);
                        wgmma<1, 0, HI_SW128, true>(o2, a + 1024 + k * 128, b + k * 2);
                    }
                    wg_commit();
                };
                pv(TrueT{}, 0);
                TS(1, 3);
#pragma unroll 1
                for (int j = 1; j < 8; j++) {
                    wg_wait<0>();
                    TS(1, 2 + 2 * j);
                    mbar_arrive_warp(sb + BAR_REMPTY + r.slot * 8, 1);
                    if (j < 7) nb_arrive_r(NB_PEMPTY + ((j - 1) & 1));
                    else mbar_arrive_warp(sb + BAR_XEMPTY + 24, 1);
                    r.adv(j < 7 ? 2 : 1);
                    pv(FalseT{}, j & 1);
                    TS(1, 3 + 2 * j);
                }
                wg_wait<0>();
                reg_fence(o0);
                reg_fence(o1);
                reg_fence(o2);
                mbar_arrive_warp(sb + BAR_REMPTY + r.slot * 8, 1);
                mbar_arrive_warp(sb + BAR_XEMPTY + 32, 1);
                r.adv(1);
                TS(1, 18);
                nb_sync<NB_L, 256>();
                if (lds_u(sb + OFF_FB) == 0) {
                    unsigned char* gp = ostash_ptr(e);
#pragma unroll
                    for (int g = 0; g < 5; g++) {
                        float2 sc[4];
#pragma unroll
                        for (int t = 0; t < 4; t++) sc[t] = lds_f2(sb + OFF_LINV + (threadIdx.x & 3) * 8 + (4 * g + t) * 32);
                        ostore(o0, g, sc, gp + g * 512);
                        ostore(o1, g, sc, gp + XS + g * 512);
                        if (g < 3) ostore(o2, g, sc, gp + 2 * XS + g * 512);
                    }
                }
                nb_arrive<NB_ODONE, 288>();
                TS(1, 19);
            } else {
                TS(1, 0);
                op_item<false>(P, e, sb, r, phm);
                TS(1, 19);
            }
        }
        TS_DUMP(1);
    }
}

typedef CUresult (*EncFn)(CUtensorMap*, CUtensorMapDataType, cuuint32_t, void*, const cuuint64_t*, const cuuint64_t*,
                          const cuuint32_t*, const cuuint32_t*, CUtensorMapInterleave, CUtensorMapSwizzle,
                          CUtensorMapL2promotion, CUtensorMapFloatOOBfill);

void make_map3(EncFn enc, CUtensorMap* m, void* p, uint64_t rows, uint64_t rowbytes, uint64_t nblk, uint32_t boxrows,
               uint32_t boxblk) {
    cuuint64_t dims[3] = {64, rows, nblk};
    cuuint64_t str[2] = {rowbytes, 128};
    cuuint32_t box[3] = {64, boxrows, boxblk};
    cuuint32_t es[3] = {1, 1, 1};
    enc(m, CU_TENSOR_MAP_DATA_TYPE_BFLOAT16, 3, p, dims, str, box, es, CU_TENSOR_MAP_INTERLEAVE_NONE,
        CU_TENSOR_MAP_SWIZZLE_128B, CU_TENSOR_MAP_L2_PROMOTION_NONE, CU_TENSOR_MAP_FLOAT_OOB_FILL_NONE);
}

#define SCHED_MODE 0

void build_schedule(Params& P) {
    int n[NCTA];
    for (int c = 0; c < NCTA; c++) {
        n[c] = 0;
        for (int i = 0; i < MAXI; i++) P.items[c][i] = 0;
    }
    for (int u = 0; u < 1024; u++) {
        const int br = u >> 9, h = (u >> 4) & 31, b = u & 15;
        const int c = u % NCTA;
        if (SCHED_MODE == 2 && (c & 3)) continue;
        P.items[c][n[c]++] = mk_item(IT_QA, br, b, h, 0, 0);
    }
    if (SCHED_MODE == 0) {
        for (int t = 0; t < 64; t++) {
            const int c = NCTA - 1 - t;
            P.items[c][n[c]++] = mk_item(IT_OP, t >> 5, (t >> 1) & 15, 0, 32, t & 1);
        }
    }
}

}

extern "C" void kernel_launch(void* const* d_in, const int* in_sizes, int n_in, void* d_out, int out_size) {
    static Params P;
    static bool init = false;
    if (!init) {
        EncFn enc = nullptr;
        cudaDriverEntryPointQueryResult qr;
        cudaGetDriverEntryPoint("cuTensorMapEncodeTiled", (void**)&enc, cudaEnableDefault, &qr);
        for (int i = 0; i < 2; i++) {
            P.px[i] = (const __nv_bfloat16*)d_in[5 * i + 0];
            P.pk[i] = (const __nv_bfloat16*)d_in[5 * i + 1];
            P.pv[i] = (const __nv_bfloat16*)d_in[5 * i + 2];
            P.pwq[i] = (const __nv_bfloat16*)d_in[5 * i + 3];
            make_map3(enc, &P.x[i], d_in[5 * i + 0], 2560, 1280, 10, 160, 1);
            make_map3(enc, &P.k[i], d_in[5 * i + 1], 16 * 32 * 512, 384, 3, 64, 3);
            make_map3(enc, &P.v[i], d_in[5 * i + 2], 16 * 32 * 512, 384, 3, 64, 3);
            make_map3(enc, &P.wq[i], d_in[5 * i + 3], 640, 12288, 96, 64, 3);
            make_map3(enc, &P.wo[i], d_in[5 * i + 4], 6144, 1280, 10, 32, 5);
        }
        cuuint64_t dims[2] = {1280, 2560};
        cuuint64_t str[1] = {2560};
        cuuint32_t box[2] = {64, 160};
        cuuint32_t es[2] = {1, 1};
        enc(&P.out, CU_TENSOR_MAP_DATA_TYPE_BFLOAT16, 2, d_out, dims, str, box, es, CU_TENSOR_MAP_INTERLEAVE_NONE,
            CU_TENSOR_MAP_SWIZZLE_128B, CU_TENSOR_MAP_L2_PROMOTION_NONE, CU_TENSOR_MAP_FLOAT_OOB_FILL_NONE);
        build_schedule(P);
        cudaFuncSetAttribute(fused_kernel, cudaFuncAttributeMaxDynamicSharedMemorySize, SMEM_LAUNCH);
        init = true;
    }
    fused_kernel<<<NCTA, 384, SMEM_LAUNCH>>>(P);
}
```

```cpp
#include <cuda_runtime.h>
#include <cuda.h>
#include <cuda_bf16.h>
#include <stdint.h>

namespace {

constexpr int NCTA = 132;
constexpr int MAXI = 16;
constexpr int SLOT = 24576;
constexpr int NSLOT = 5;
constexpr int XS = 20480;
constexpr int OFF_R = 0;
constexpr int OFF_RING = 5 * XS;
constexpr int OFF_MISC = OFF_RING + NSLOT * SLOT;
constexpr int OFF_LX = OFF_MISC;
constexpr int OFF_LINV = OFF_LX + 2560;
constexpr int OFF_FB = OFF_LINV + 640;
constexpr int OFF_GM = OFF_FB + 16;
constexpr int OFF_BAR = OFF_GM + 16;
constexpr int BAR_RFULL = OFF_BAR;
constexpr int BAR_REMPTY = BAR_RFULL + 40;
constexpr int BAR_XFULL = BAR_REMPTY + 40;
constexpr int BAR_XEMPTY = BAR_XFULL + 40;
constexpr int SMEM_BYTES = BAR_XEMPTY + 40;
static_assert(SMEM_BYTES <= 232448, "smem");

constexpr int NB_W = 1  , NB_PFULL = 3  , NB_VOTE = 5, NB_Q01 = 6, NB_Q2 = 7, NB_SDONE = 8, NB_PDONE = 9,
              NB_L = 10, NB_OPST = 11, NB_ODONE = 12, NB_OPEND = 13, NB_LX = 14;

constexpr uint32_t IT_QA = 1, IT_OP = 2;
__host__ __device__ constexpr uint32_t mk_item(uint32_t type, uint32_t br, uint32_t b, uint32_t h0, uint32_t h1, uint32_t half) {
    return type | (br << 2) | (b << 3) | (h0 << 7) | (h1 << 13) | (half << 19);
}
#define IT_TYPE(e) ((e) & 3u)
#define IT_BR(e) (((e) >> 2) & 1u)
#define IT_B(e) (((e) >> 3) & 15u)
#define IT_H0(e) (((e) >> 7) & 63u)
#define IT_H1(e) (((e) >> 13) & 63u)
#define IT_HALF(e) (((e) >> 19) & 1u)

struct Params {
    CUtensorMap x[2], wq[2], k[2], v[2], wo[2], out;
    const __nv_bfloat16 *px[2], *pwq[2], *pk[2], *pv[2];
    uint32_t items[NCTA][MAXI];
};

constexpr int OUNIT = 61440;
__device__ __align__(1024) unsigned char g_ostash[(size_t)1024 * OUNIT];
__device__ unsigned int g_flag[1024];
__device__ unsigned int g_epoch[NCTA];

constexpr int SMEM_LAUNCH = SMEM_BYTES;
#define TS(role, idx)
#define TS_DUMP(role)
#define TS2(cond, idx)

#define SP_J0 6
#define PF_POS 12
constexpr float SM_C = 0.07216878364870322f * 1.4426950408889634f;

__device__ __forceinline__ void mbar_init(uint32_t a, uint32_t c) {
    asm volatile("mbarrier.init.shared::cta.b64 [%0], %1;" ::"r"(a), "r"(c) : "memory");
}
__device__ __forceinline__ void mbar_expect(uint32_t a, uint32_t b) {
    asm volatile("mbarrier.arrive.expect_tx.shared::cta.b64 _, [%0], %1;" ::"r"(a), "r"(b) : "memory");
}
__device__ __forceinline__ void mbar_arrive_warp(uint32_t a, uint32_t cnt) {
    asm volatile(
        "{\n.reg .pred p;\nelect.sync _|p, 0xffffffff;\n"
        "@p mbarrier.arrive.shared::cta.b64 _, [%0], %1;\n}" ::"r"(a), "r"(cnt)
        : "memory");
}
__device__ __forceinline__ void mbar_wait(uint32_t a, uint32_t ph) {
    asm volatile(
        "{\n.reg .pred p;\n.reg .u32 n;\n"
        "mbarrier.try_wait.parity.shared::cta.b64 p, [%0], %1;\n"
        "@p bra DONE;\n"
        "mov.u32 n, 0;\n"
        "LOOP:\n"
        "mbarrier.try_wait.parity.shared::cta.b64 p, [%0], %1;\n"
        "@p bra DONE;\n"
        "add.u32 n, n, 1;\n"
        "setp.lt.u32 p, n, 0x4000000;\n"
        "@p bra LOOP;\n"
        "trap;\n"
        "DONE:\n}" ::"r"(a), "r"(ph)
        : "memory");
}
template <int ID, int CNT>
__device__ __forceinline__ void nb_sync() { asm volatile("bar.sync %0, %1;" ::"n"(ID), "n"(CNT) : "memory"); }
template <int ID, int CNT>
__device__ __forceinline__ void nb_arrive() { asm volatile("bar.arrive %0, %1;" ::"n"(ID), "n"(CNT) : "memory"); }
__device__ __forceinline__ void fence_async_smem() { asm volatile("fence.proxy.async.shared::cta;" ::: "memory"); }

__device__ __forceinline__ void tma3(uint32_t dst, const CUtensorMap* m, int c1, int c2, uint32_t bar, uint64_t pol) {
    asm volatile(
        "cp.async.bulk.tensor.3d.shared::cluster.global.mbarrier::complete_tx::bytes.L2::cache_hint [%0], [%1, {%3,%4,%5}], [%2], %6;" ::"r"(dst),
        "l"(m), "r"(bar), "r"(0), "r"(c1), "r"(c2), "l"(pol)
        : "memory");
}
__device__ __forceinline__ void bulk_load(uint32_t dst, const void* src, uint32_t bytes, uint32_t bar) {
    asm volatile("cp.async.bulk.shared::cluster.global.mbarrier::complete_tx::bytes [%0], [%1], %2, [%3];" ::"r"(dst),
                 "l"(src), "r"(bytes), "r"(bar)
                 : "memory");
}
__device__ __forceinline__ void wg_fence() { asm volatile("wgmma.fence.sync.aligned;" ::: "memory"); }
__device__ __forceinline__ void wg_commit() { asm volatile("wgmma.commit_group.sync.aligned;" ::: "memory"); }
template <int N>
__device__ __forceinline__ void wg_wait() { asm volatile("wgmma.wait_group.sync.aligned %0;" ::"n"(N) : "memory"); }

#define RW80(c, d) c(d[0]), c(d[1]), c(d[2]), c(d[3]), c(d[4]), c(d[5]), c(d[6]), c(d[7]), c(d[8]), c(d[9]), c(d[10]), c(d[11]), c(d[12]), c(d[13]), c(d[14]), c(d[15]), c(d[16]), c(d[17]), c(d[18]), c(d[19]), c(d[20]), c(d[21]), c(d[22]), c(d[23]), c(d[24]), c(d[25]), c(d[26]), c(d[27]), c(d[28]), c(d[29]), c(d[30]), c(d[31]), c(d[32]), c(d[33]), c(d[34]), c(d[35]), c(d[36]), c(d[37]), c(d[38]), c(d[39]), c(d[40]), c(d[41]), c(d[42]), c(d[43]), c(d[44]), c(d[45]), c(d[46]), c(d[47]), c(d[48]), c(d[49]), c(d[50]), c(d[51]), c(d[52]), c(d[53]), c(d[54]), c(d[55]), c(d[56]), c(d[57]), c(d[58]), c(d[59]), c(d[60]), c(d[61]), c(d[62]), c(d[63]), c(d[64]), c(d[65]), c(d[66]), c(d[67]), c(d[68]), c(d[69]), c(d[70]), c(d[71]), c(d[72]), c(d[73]), c(d[74]), c(d[75]), c(d[76]), c(d[77]), c(d[78]), c(d[79])
#define RW48(c, d) c(d[0]), c(d[1]), c(d[2]), c(d[3]), c(d[4]), c(d[5]), c(d[6]), c(d[7]), c(d[8]), c(d[9]), c(d[10]), c(d[11]), c(d[12]), c(d[13]), c(d[14]), c(d[15]), c(d[16]), c(d[17]), c(d[18]), c(d[19]), c(d[20]), c(d[21]), c(d[22]), c(d[23]), c(d[24]), c(d[25]), c(d[26]), c(d[27]), c(d[28]), c(d[29]), c(d[30]), c(d[31]), c(d[32]), c(d[33]), c(d[34]), c(d[35]), c(d[36]), c(d[37]), c(d[38]), c(d[39]), c(d[40]), c(d[41]), c(d[42]), c(d[43]), c(d[44]), c(d[45]), c(d[46]), c(d[47])
#define RW32(c, d) c(d[0]), c(d[1]), c(d[2]), c(d[3]), c(d[4]), c(d[5]), c(d[6]), c(d[7]), c(d[8]), c(d[9]), c(d[10]), c(d[11]), c(d[12]), c(d[13]), c(d[14]), c(d[15]), c(d[16]), c(d[17]), c(d[18]), c(d[19]), c(d[20]), c(d[21]), c(d[22]), c(d[23]), c(d[24]), c(d[25]), c(d[26]), c(d[27]), c(d[28]), c(d[29]), c(d[30]), c(d[31])

__device__ __forceinline__ void reg_fence(float (&d)[80]) { asm volatile("" : RW80("+f", d)::"memory"); }
__device__ __forceinline__ void reg_fence(float (&d)[48]) { asm volatile("" : RW48("+f", d)::"memory"); }
__device__ __forceinline__ void reg_fence(float (&d)[32]) { asm volatile("" : RW32("+f", d)::"memory"); }

constexpr uint32_t HI_SW128 = (1024u >> 4) | (1u << 30);
constexpr uint32_t HI_OST = (2560u >> 4) | (2u << 30);
constexpr uint32_t LO_LBO1 = (1u << 16);
constexpr uint32_t LO_OST = ((512u >> 4) << 16);

template <int TA, int TB, uint32_t HIB, bool ACC>
__device__ __forceinline__ void wgmma(float (&d)[80], uint32_t loA, uint32_t loB) {
#define WG_ASM(SD)                                                          \
    "{\n.reg .b64 da, db;\nmov.b64 da, {%80, %82};\nmov.b64 db, {%81, %83};\n" \
    "wgmma.mma_async.sync.aligned.m64n160k16.f32.bf16.bf16 "               \
    "{%0,%1,%2,%3,%4,%5,%6,%7,%8,%9,%10,%11,%12,%13,%14,%15,%16,%17,%18,%19,%20,%21,%22,%23,%24,%25,%26,%27,%28,%29,%30,%31,%32,%33,%34,%35,%36,%37,%38,%39,%40,%41,%42,%43,%44,%45,%46,%47,%48,%49,%50,%51,%52,%53,%54,%55,%56,%57,%58,%59,%60,%61,%62,%63,%64,%65,%66,%67,%68,%69,%70,%71,%72,%73,%74,%75,%76,%77,%78,%79}, da, db, " SD ", 1, 1, %84, %85;\n}"
    if constexpr (ACC)
        asm volatile(WG_ASM("1") : RW80("+f", d) : "r"(loA), "r"(loB), "n"(HI_SW128), "n"(HIB), "n"(TA), "n"(TB));
    else
        asm volatile(WG_ASM("0") : RW80("=f", d) : "r"(loA), "r"(loB), "n"(HI_SW128), "n"(HIB), "n"(TA), "n"(TB));
#undef WG_ASM
}
template <int TA, int TB, uint32_t HIB, bool ACC>
__device__ __forceinline__ void wgmma(float (&d)[48], uint32_t loA, uint32_t loB) {
#define WG_ASM(SD)                                                          \
    "{\n.reg .b64 da, db;\nmov.b64 da, {%48, %50};\nmov.b64 db, {%49, %51};\n" \
    "wgmma.mma_async.sync.aligned.m64n96k16.f32.bf16.bf16 "               \
    "{%0,%1,%2,%3,%4,%5,%6,%7,%8,%9,%10,%11,%12,%13,%14,%15,%16,%17,%18,%19,%20,%21,%22,%23,%24,%25,%26,%27,%28,%29,%30,%31,%32,%33,%34,%35,%36,%37,%38,%39,%40,%41,%42,%43,%44,%45,%46,%47}, da, db, " SD ", 1, 1, %52, %53;\n}"
    if constexpr (ACC)
        asm volatile(WG_ASM("1") : RW48("+f", d) : "r"(loA), "r"(loB), "n"(HI_SW128), "n"(HIB), "n"(TA), "n"(TB));
    else
        asm volatile(WG_ASM("0") : RW48("=f", d) : "r"(loA), "r"(loB), "n"(HI_SW128), "n"(HIB), "n"(TA), "n"(TB));
#undef WG_ASM
}
template <int TA, int TB, uint32_t HIB, bool ACC>
__device__ __forceinline__ void wgmma(float (&d)[32], uint32_t loA, uint32_t loB) {
#define WG_ASM(SD)                                                          \
    "{\n.reg .b64 da, db;\nmov.b64 da, {%32, %34};\nmov.b64 db, {%33, %35};\n" \
    "wgmma.mma_async.sync.aligned.m64n64k16.f32.bf16.bf16 "               \
    "{%0,%1,%2,%3,%4,%5,%6,%7,%8,%9,%10,%11,%12,%13,%14,%15,%16,%17,%18,%19,%20,%21,%22,%23,%24,%25,%26,%27,%28,%29,%30,%31}, da, db, " SD ", 1, 1, %36, %37;\n}"
    if constexpr (ACC)
        asm volatile(WG_ASM("1") : RW32("+f", d) : "r"(loA), "r"(loB), "n"(HI_SW128), "n"(HIB), "n"(TA), "n"(TB));
    else
        asm volatile(WG_ASM("0") : RW32("=f", d) : "r"(loA), "r"(loB), "n"(HI_SW128), "n"(HIB), "n"(TA), "n"(TB));
#undef WG_ASM
}

__device__ __forceinline__ uint32_t pack_bf16(float lo, float hi) {
    uint32_t r;
    asm("cvt.rn.bf16x2.f32 %0, %1, %2;" : "=r"(r) : "f"(hi), "f"(lo));
    return r;
}
__device__ __forceinline__ float ex2(float x) {
    float r;
    asm("ex2.approx.ftz.f32 %0, %1;" : "=f"(r) : "f"(x));
    return r;
}
__device__ __forceinline__ void stsm4t(uint32_t a, uint32_t r0, uint32_t r1, uint32_t r2, uint32_t r3) {
    asm volatile("stmatrix.sync.aligned.m8n8.x4.trans.shared.b16 [%0], {%1,%2,%3,%4};" ::"r"(a), "r"(r0), "r"(r1), "r"(r2), "r"(r3)
                 : "memory");
}
__device__ __forceinline__ float lds_f(uint32_t a) {
    float v;
    asm volatile("ld.shared.f32 %0, [%1];" : "=f"(v) : "r"(a) : "memory");
    return v;
}
__device__ __forceinline__ uint32_t lds_u(uint32_t a) {
    uint32_t v;
    asm volatile("ld.shared.u32 %0, [%1];" : "=r"(v) : "r"(a) : "memory");
    return v;
}
__device__ __forceinline__ float2 lds_f2(uint32_t a) {
    float2 v;
    asm volatile("ld.shared.v2.f32 {%0,%1}, [%2];" : "=f"(v.x), "=f"(v.y) : "r"(a) : "memory");
    return v;
}
__device__ __forceinline__ void sts_f(uint32_t a, float v) { asm volatile("st.shared.f32 [%0], %1;" ::"r"(a), "f"(v) : "memory"); }
__device__ __forceinline__ void sts_u(uint32_t a, uint32_t v) { asm volatile("st.shared.u32 [%0], %1;" ::"r"(a), "r"(v) : "memory"); }
__device__ __forceinline__ void sts_f2(uint32_t a, float x, float y) {
    asm volatile("st.shared.v2.f32 [%0], {%1,%2};" ::"r"(a), "f"(x), "f"(y) : "memory");
}

__device__ __forceinline__ void store_tile_t(const float (&d)[80], uint32_t addr) {
#pragma unroll
    for (int j = 0; j < 10; j++)
        stsm4t(addr + j * 2048, pack_bf16(d[8 * j], d[8 * j + 1]), pack_bf16(d[8 * j + 2], d[8 * j + 3]),
               pack_bf16(d[8 * j + 4], d[8 * j + 5]), pack_bf16(d[8 * j + 6], d[8 * j + 7]));
}
template <int NR>
__device__ __forceinline__ void store_out_tile(const float (&d)[NR], uint32_t base, uint32_t lane, uint32_t w) {
    const uint32_t mi = lane >> 3, i = lane & 7;
    const uint32_t chunk = 2 * w + (mi & 1);
    const uint32_t q0 = 8 * (i >> 1) + 2 * (mi >> 1) + (i & 1);
    const uint32_t a0 = base + q0 * 128 + ((chunk ^ (q0 & 7)) << 4);
    const uint32_t a1 = base + (q0 + 4) * 128 + ((chunk ^ ((q0 + 4) & 7)) << 4);
#pragma unroll
    for (int j = 0; j < NR / 8; j++)
        stsm4t(((j & 1) ? a1 : a0) + (j >> 1) * 4096, pack_bf16(d[8 * j], d[8 * j + 1]), pack_bf16(d[8 * j + 2], d[8 * j + 3]),
               pack_bf16(d[8 * j + 4], d[8 * j + 5]), pack_bf16(d[8 * j + 6], d[8 * j + 7]));
}

struct TrueT { static constexpr bool value = true; };
struct FalseT { static constexpr bool value = false; };

template <int V>
struct IntT { static constexpr int value = V; };

struct Ring {
    uint32_t slot, ph;
    __device__ __forceinline__ void adv(uint32_t k) {
        slot += k;
        if (slot >= NSLOT) { slot -= NSLOT; ph ^= 1; }
    }
};

template <int K>
__device__ __forceinline__ void qk_step(float (&s)[80], uint32_t loK, uint32_t loQ) {
    wgmma<0, 0, HI_SW128, K != 0>(s, loK + (K >> 2) * (8192 >> 4) + (K & 3) * 2, loQ + (K >> 2) * (XS >> 4) + (K & 3) * 2);
}
template <int K0, int K1>
__device__ __forceinline__ void qk_steps(float (&s)[80], uint32_t loK, uint32_t loQ) {
    if constexpr (K0 < K1) {
        qk_step<K0>(s, loK, loQ);
        qk_steps<K0 + 1, K1>(s, loK, loQ);
    }
}
template <int J>
__device__ __forceinline__ void exp_chunk(const float (&s)[80], float (&ps)[40], uint32_t pa, float mref) {
    float p[8];
#pragma unroll
    for (int i = 0; i < 8; i++) p[i] = ex2(fmaf(s[8 * J + i], SM_C, -mref));
    stsm4t(pa + J * 2048, pack_bf16(p[0], p[1]), pack_bf16(p[2], p[3]), pack_bf16(p[4], p[5]), pack_bf16(p[6], p[7]));
    ps[4 * J] = p[0] + p[2];
    ps[4 * J + 1] = p[1] + p[3];
    ps[4 * J + 2] = p[4] + p[6];
    ps[4 * J + 3] = p[5] + p[7];
}
template <int J>
__device__ __forceinline__ void exp_block(const float (&s)[80], float (&ps)[40], uint32_t pa, float mref) {
    if constexpr (J < 10) {
        exp_chunk<J>(s, ps, pa, mref);
        exp_block<J + 1>(s, ps, pa, mref);
    }
}
__device__ __forceinline__ void sum_block(const float (&ps)[40], float (&l)[5], uint32_t lane) {
    const bool b4 = lane & 16, b3 = lane & 8, b2 = lane & 4;
    float t[20];
#pragma unroll
    for (int j = 0; j < 10; j++) {
        t[2 * j] = (b4 ? ps[4 * j + 2] : ps[4 * j]) + __shfl_xor_sync(0xffffffffu, b4 ? ps[4 * j] : ps[4 * j + 2], 16);
        t[2 * j + 1] = (b4 ? ps[4 * j + 3] : ps[4 * j + 1]) + __shfl_xor_sync(0xffffffffu, b4 ? ps[4 * j + 1] : ps[4 * j + 3], 16);
    }
#pragma unroll
    for (int i = 0; i < 10; i++) t[i] = (b3 ? t[i + 10] : t[i]) + __shfl_xor_sync(0xffffffffu, b3 ? t[i] : t[i + 10], 8);
#pragma unroll
    for (int i = 0; i < 5; i++)
        l[i] += (b2 ? t[2 * i + 1] : t[2 * i]) + __shfl_xor_sync(0xffffffffu, b2 ? t[2 * i] : t[2 * i + 1], 4);
}

__device__ __forceinline__ void fallback_unit(const Params& P, uint32_t e, uint32_t tid) {
    const uint32_t lane = tid & 31, br = IT_BR(e), b = IT_B(e), h = IT_H0(e);
    const uint32_t u = (br * 16 + b) * 32 + h;
    const __nv_bfloat162* wq = (const __nv_bfloat162*)(P.pwq[br] + h * 192) + lane;
    const __nv_bfloat162* kp = (const __nv_bfloat162*)(P.pk[br] + (size_t)(b * 32 + h) * 512 * 192) + lane;
    const __nv_bfloat162* vp = (const __nv_bfloat162*)(P.pv[br] + (size_t)(b * 32 + h) * 512 * 192) + lane;
#pragma unroll 1
    for (uint32_t q = tid >> 5; q < 160; q += 4) {
        const __nv_bfloat16* xr = P.px[br] + (size_t)(b * 160 + q) * 640;
        float a[6] = {0.f, 0.f, 0.f, 0.f, 0.f, 0.f};
#pragma unroll 4
        for (int k = 0; k < 640; k++) {
            const float xv = __bfloat162float(xr[k]);
#pragma unroll
            for (int i = 0; i < 3; i++) {
                const float2 wv = __bfloat1622float2(wq[(size_t)k * 3072 + i * 32]);
                a[2 * i] = fmaf(xv, wv.x, a[2 * i]);
                a[2 * i + 1] = fmaf(xv, wv.y, a[2 * i + 1]);
            }
        }
#pragma unroll
        for (int i = 0; i < 6; i++) a[i] = __bfloat162float(__float2bfloat16(a[i]));
        auto score = [&](int key) {
            float d = 0.f;
#pragma unroll
            for (int i = 0; i < 3; i++) {
                const float2 kv = __bfloat1622float2(kp[key * 96 + i * 32]);
                d = fmaf(a[2 * i], kv.x, fmaf(a[2 * i + 1], kv.y, d));
            }
#pragma unroll
            for (int o = 16; o > 0; o >>= 1) d += __shfl_xor_sync(0xffffffffu, d, o);
            return d;
        };
        float m = -INFINITY;
#pragma unroll 4
        for (int key = 0; key < 512; key++) m = fmaxf(m, score(key));
        float o[6] = {0.f, 0.f, 0.f, 0.f, 0.f, 0.f}, sum = 0.f;
#pragma unroll 4
        for (int key = 0; key < 512; key++) {
            const float p = ex2((score(key) - m) * SM_C);
            sum += p;
#pragma unroll
            for (int i = 0; i < 3; i++) {
                const float2 vv = __bfloat1622float2(vp[key * 96 + i * 32]);
                o[2 * i] = fmaf(p, vv.x, o[2 * i]);
                o[2 * i + 1] = fmaf(p, vv.y, o[2 * i + 1]);
            }
        }
        const float inv = 1.f / sum;
        __nv_bfloat16* op = (__nv_bfloat16*)(g_ostash + (size_t)u * OUNIT) + (q >> 5) * 256 + 2 * ((q & 31) >> 3) + (q & 1);
#pragma unroll
        for (int i = 0; i < 6; i++) {
            const uint32_t d = (i >> 1) * 64 + 2 * lane + (i & 1);
            op[(d >> 3) * 1280 + (d & 7) * 32 + ((((q & 7) >> 1) ^ ((d & 7) >> 1)) << 3)] = __float2bfloat16(o[i] * inv);
        }
    }
}

template <bool IS_S>
__device__ __forceinline__ void qproj(float (&q0)[80], float (&q1)[80], uint32_t sb, Ring& r, uint32_t& phm) {
    const uint32_t loR = ((sb + OFF_R) >> 4) | LO_LBO1;
    const uint32_t loRing = ((sb + OFF_RING) >> 4) | LO_LBO1;
    uint32_t xs = 0;
    auto step = [&](auto first) {
        constexpr bool F = decltype(first)::value;
        mbar_wait(sb + BAR_RFULL + r.slot * 8, r.ph);
        mbar_wait(sb + BAR_XFULL + xs * 8, (phm >> xs) & 1);
        phm ^= 1u << xs;
        const uint32_t a = loRing + r.slot * (SLOT >> 4) + (IS_S ? 0 : 1024), b = loR + xs * (XS >> 4);
        wg_fence();
        wgmma<1, 0, HI_SW128, !F>(q0, a, b);
        if (IS_S) wgmma<1, 0, HI_SW128, !F>(q1, a + 512, b);
#pragma unroll
        for (int k = 1; k < 4; k++) {
            wgmma<1, 0, HI_SW128, true>(q0, a + k * 128, b + k * 2);
            if (IS_S) wgmma<1, 0, HI_SW128, true>(q1, a + 512 + k * 128, b + k * 2);
        }
        wg_commit();
    };
    step(TrueT{});
#pragma unroll 1
    for (int kk = 1; kk < 10; kk++) {
        const uint32_t pslot = r.slot;
        r.adv(1);
        if (++xs == 5) xs = 0;
        if (!IS_S && kk == 8) nb_sync<NB_SDONE, 256>();
        step(FalseT{});
        wg_wait<1>();
        mbar_arrive_warp(sb + BAR_REMPTY + pslot * 8, 1);
        if (kk <= 5) mbar_arrive_warp(sb + BAR_XEMPTY + (kk - 1) * 8, 1);
        if (!IS_S && kk == 7) nb_arrive<NB_PDONE, 256>();
    }
    if (IS_S) nb_arrive<NB_SDONE, 256>();
    wg_wait<0>();
    reg_fence(q0);
    if (IS_S) reg_fence(q1);
    mbar_arrive_warp(sb + BAR_REMPTY + r.slot * 8, 1);
    r.adv(1);
}

template <int NR>
__device__ __forceinline__ void ostore(const float (&o)[NR], int gl, const float2 (&sc)[4], unsigned char* gp) {
#pragma unroll
    for (int hh = 0; hh < 2; hh++)
        asm volatile("st.global.v4.b32 [%0], {%1,%2,%3,%4};" ::"l"(gp + hh * 2560),
                     "r"(pack_bf16(o[16 * gl + 2 * hh] * sc[0].x, o[16 * gl + 2 * hh + 1] * sc[0].y)),
                     "r"(pack_bf16(o[16 * gl + 4 + 2 * hh] * sc[1].x, o[16 * gl + 5 + 2 * hh] * sc[1].y)),
                     "r"(pack_bf16(o[16 * gl + 8 + 2 * hh] * sc[2].x, o[16 * gl + 9 + 2 * hh] * sc[2].y)),
                     "r"(pack_bf16(o[16 * gl + 12 + 2 * hh] * sc[3].x, o[16 * gl + 13 + 2 * hh] * sc[3].y))
                     : "memory");
}
__device__ __forceinline__ unsigned char* ostash_ptr(uint32_t e) {
    const uint32_t u = (IT_BR(e) * 16 + IT_B(e)) * 32 + IT_H0(e);
    const uint32_t lane = threadIdx.x & 31, w = (threadIdx.x >> 5) & 3;
    return g_ostash + (size_t)u * OUNIT + w * 5120 + (lane >> 2) * 64 + (((lane ^ (lane >> 3)) & 3) << 4);
}

template <bool IS_S>
__device__ __forceinline__ void op_item(const Params& P, uint32_t e, uint32_t sb, Ring& r, uint32_t& phm) {
    constexpr int T0 = IS_S ? 0 : 2;
    constexpr uint32_t BOFF = IS_S ? (3 * 512) >> 4 : 0;
    const uint32_t loRing = ((sb + OFF_RING) >> 4) | LO_LBO1;
    const uint32_t loO = ((sb + OFF_R) >> 4) | LO_OST;
    float c0[80], c1[80], c2[IS_S ? 32 : 48];
    const int T2 = 6 * (IT_H1(e) - IT_H0(e));
    uint32_t xs = 0;
    auto step = [&](auto first, uint32_t hf) {
        constexpr bool F = decltype(first)::value;
        if (hf == 0) {
            mbar_wait(sb + BAR_XFULL + xs * 8, (phm >> xs) & 1);
            phm ^= 1u << xs;
        }
        mbar_wait(sb + BAR_RFULL + r.slot * 8, r.ph);
        const uint32_t a = loRing + r.slot * (SLOT >> 4), b = loO + xs * (XS >> 4) + hf * 640;
        wg_fence();
        wgmma<1, 1, HI_OST, !F>(c0, a + T0 * 256, b);
        wgmma<1, 1, HI_OST, !F>(c1, a + T0 * 256 + 256, b);
        wgmma<1, 1, HI_OST, !F>(c2, a + 1024, b + BOFF);
        wgmma<1, 1, HI_OST, true>(c0, a + T0 * 256 + 128, b + 320);
        wgmma<1, 1, HI_OST, true>(c1, a + T0 * 256 + 384, b + 320);
        wgmma<1, 1, HI_OST, true>(c2, a + 1024 + 128, b + 320 + BOFF);
        wg_commit();
    };
    step(TrueT{}, 0);
#pragma unroll 1
    for (int t = 1; t < T2; t++) {
        const uint32_t pslot = r.slot, pxs = xs;
        r.adv(1);
        if ((t & 1) == 0 && ++xs == 5) xs = 0;
        step(FalseT{}, t & 1);
        wg_wait<1>();
        mbar_arrive_warp(sb + BAR_REMPTY + pslot * 8, 1);
        if ((t & 1) == 0 && t + 8 < T2) mbar_arrive_warp(sb + BAR_XEMPTY + pxs * 8, 1);
    }
    wg_wait<0>();
    reg_fence(c0);
    reg_fence(c1);
    reg_fence(c2);
    mbar_arrive_warp(sb + BAR_REMPTY + r.slot * 8, 1);
    r.adv(1);
    nb_sync<NB_OPEND, 256>();
    const uint32_t lane = threadIdx.x & 31, w = (threadIdx.x >> 5) & 3;
    store_out_tile(c0, sb + OFF_R + T0 * XS, lane, w);
    store_out_tile(c1, sb + OFF_R + (T0 + 1) * XS, lane, w);
    store_out_tile(c2, sb + OFF_R + 4 * XS + (IS_S ? 96 * 128 : 0), lane, w);
    fence_async_smem();
    if (IS_S) {
        nb_arrive<NB_OPST, 256>();
    } else {
        nb_sync<NB_OPST, 256>();
        if ((threadIdx.x & 127) == 0) {
            const int cc0 = IT_BR(e) * 640 + IT_HALF(e) * 320;
#pragma unroll
            for (int m = 0; m < 5; m++)
                asm volatile("cp.async.bulk.tensor.2d.global.shared::cta.bulk_group [%0, {%2,%3}], [%1];" ::"l"(&P.out),
                             "r"(sb + OFF_R + m * XS), "r"(cc0 + m * 64), "r"((int)IT_B(e) * 160)
                             : "memory");
            asm volatile("cp.async.bulk.commit_group;" ::: "memory");
            asm volatile("cp.async.bulk.wait_group 0;" ::: "memory");
#pragma unroll
            for (int m = 0; m < 5; m++)
                asm volatile("mbarrier.arrive.shared::cta.b64 _, [%0], 8;" ::"r"(sb + BAR_XEMPTY + m * 8) : "memory");
        }
        __syncwarp();
    }
}

template <int W>
__device__ __forceinline__ void qa_item(const Params& P, uint32_t e, uint32_t sb, Ring& r, uint32_t& phm, int it) {
    const uint32_t loR = ((sb + OFF_R) >> 4) | LO_LBO1;
    const uint32_t loRing = ((sb + OFF_RING) >> 4) | LO_LBO1;
    const uint32_t lane = threadIdx.x & 31, w = (threadIdx.x >> 5) & 3;
    const uint32_t sta = sb + OFF_R + (lane >> 4) * 1024 + (lane & 7) * 128 + (((2 * w + ((lane >> 3) & 1)) ^ (lane & 7)) << 4);
    {
        float q0[80], q1[80];
        qproj<W == 0>(q0, q1, sb, r, phm);
        TS(W, 1);
        if (W == 0) {
            nb_sync<NB_PDONE, 256>();
            store_tile_t(q0, sta);
            store_tile_t(q1, sta + XS);
        } else {
            store_tile_t(q0, sta + 2 * XS);
        }
    }
    fence_async_smem();
    float s[80], oa[80], ob[W == 0 ? 32 : 48], l[5];
#pragma unroll
    for (int i = 0; i < 80; i++) oa[i] = 0.f;
#pragma unroll
    for (int i = 0; i < (W == 0 ? 32 : 48); i++) ob[i] = 0.f;
#pragma unroll
    for (int i = 0; i < 5; i++) l[i] = 0.f;
    reg_fence(oa);
    reg_fence(ob);
    auto pv = [&](uint32_t buf) {
        mbar_wait(sb + BAR_RFULL + r.slot * 8, r.ph);
        const uint32_t a = loRing + r.slot * (SLOT >> 4), b = loR + (3 + buf) * (XS >> 4);
        wg_fence();
#pragma unroll
        for (int k = 0; k < 4; k++) {
            wgmma<1, 0, HI_SW128, true>(oa, a + W * 512 + k * 128, b + k * 2);
            wgmma<1, 0, HI_SW128, true>(ob, a + 1024 + k * 128, b + (W == 0 ? (96 * 128) >> 4 : 0) + k * 2);
        }
        wg_commit();
    };
    float mref;
    uint32_t kslot, vslot;
    auto tail = [&](bool rel_other, int i) {
        float ps[40];
        exp_block<0>(s, ps, sta + (3 + W) * XS, mref);
        if (rel_other) {
            wg_wait<0>();
            mbar_arrive_warp(sb + BAR_REMPTY + vslot * 8, 1);
            if (W == 1 && i == 3) mbar_arrive_warp(sb + BAR_XEMPTY + 24, 1);
        }
        fence_async_smem();
        nb_arrive<NB_PFULL + W, 256>();
        TS(W, 6 + 5 * i);
        mbar_wait(sb + BAR_RFULL + r.slot * 8, r.ph);
        sum_block(ps, l, lane);
        nb_sync<NB_W + W, 128>();
        TS(W, 7 + 5 * i);
        pv(W);
        TS(W, 8 + 5 * i);
    };
    if (W == 0) {
        nb_arrive<NB_Q01, 256>();
        nb_sync<NB_W, 128>();
        TS(W, 2);
        mbar_wait(sb + BAR_RFULL + r.slot * 8, r.ph);
        wg_fence();
        qk_steps<0, 8>(s, loRing + r.slot * (SLOT >> 4), loR);
        nb_sync<NB_Q2, 256>();
        qk_steps<8, 12>(s, loRing + r.slot * (SLOT >> 4), loR);
        wg_commit();
        TS(W, 4);
        wg_wait<0>();
        reg_fence(s);
        mbar_arrive_warp(sb + BAR_REMPTY + r.slot * 8, 2);
        r.adv(2);
        float m0 = fmaxf(s[0], s[5]), m1 = fmaxf(s[10], s[15]);
#pragma unroll
        for (int i = 20; i < 80; i += 10) {
            m0 = fmaxf(m0, s[i]);
            m1 = fmaxf(m1, s[i + 5]);
        }
        int key = __float_as_int(fmaxf(m0, m1));
        key ^= (key >> 31) & 0x7fffffff;
        key = __reduce_max_sync(0xffffffffu, key);
        key ^= (key >> 31) & 0x7fffffff;
        sts_u(sb + OFF_GM + w * 4, key);
        nb_sync<NB_W, 128>();
        const float2 u = lds_f2(sb + OFF_GM), v = lds_f2(sb + OFF_GM + 8);
        mref = fmaxf(fmaxf(u.x, u.y), fmaxf(v.x, v.y)) * SM_C;
        TS(W, 5);
        tail(false, 0);
    } else {
        nb_sync<NB_Q01, 256>();
        nb_sync<NB_Q2, 256>();
        TS(W, 2);
    }
#pragma unroll 1
    for (int i = (W == 0 ? 1 : 0); i < 4; i++) {
        const uint32_t pvslot = r.slot;
        r.adv(1);
        kslot = r.slot;
        mbar_wait(sb + BAR_RFULL + r.slot * 8, r.ph);
        wg_fence();
        qk_steps<0, 12>(s, loRing + r.slot * (SLOT >> 4), loR);
        wg_commit();
        wg_wait<1>();
        if (W == 0 || i > 0) mbar_arrive_warp(sb + BAR_REMPTY + pvslot * 8, 1);
        r.adv(1);
        vslot = r.slot;
        TS(W, 4 + 5 * i);
        nb_sync<NB_PFULL + (W ^ 1), 256>();
        pv(W ^ 1);
        if (W == 1 && i == 0) {
            const float2 u = lds_f2(sb + OFF_GM), v = lds_f2(sb + OFF_GM + 8);
            mref = fmaxf(fmaxf(u.x, u.y), fmaxf(v.x, v.y)) * SM_C;
        }
        wg_wait<1>();
        reg_fence(s);
        mbar_arrive_warp(sb + BAR_REMPTY + kslot * 8, 2);
        if (W == 1 && i == 3) {
            mbar_arrive_warp(sb + BAR_XEMPTY + 0, 2);
            mbar_arrive_warp(sb + BAR_XEMPTY + 8, 2);
            mbar_arrive_warp(sb + BAR_XEMPTY + 16, 2);
            r.adv(1);
        } else {
            r.adv(2);
        }
        TS(W, 5 + 5 * i);
        tail(true, i);
    }
    const uint32_t lxa = sb + OFF_LX + w * 640 + (((lane & 8) ? 80 : 0) + ((lane >> 1) & 8) + 2 * (lane & 3) + ((lane >> 2) & 1)) * 4;
    uint32_t any;
    if (W == 0) {
#pragma unroll
        for (int i = 0; i < 5; i++) sts_f(lxa + i * 64, l[i]);
        nb_arrive<NB_LX, 256>();
        wg_wait<0>();
        mbar_arrive_warp(sb + BAR_REMPTY + r.slot * 8, 1);
        mbar_arrive_warp(sb + BAR_XEMPTY + 24, 1);
        r.adv(1);
        nb_sync<NB_PFULL + 1, 256>();
        pv(1);
        TS(W, 24);
        nb_sync<NB_L, 256>();
        any = lds_u(sb + OFF_FB);
    } else {
        nb_sync<NB_LX, 256>();
#pragma unroll
        for (int i = 0; i < 5; i++) sts_f(lxa + i * 64, l[i] + lds_f(lxa + i * 64));
        nb_sync<NB_W + 1, 128>();
        const uint32_t tid = threadIdx.x & 127;
        float la = 1.f, lb = 1.f;
        if (tid < 80) {
            float2 v = lds_f2(sb + OFF_LX + tid * 8);
#pragma unroll
            for (int i = 1; i < 4; i++) {
                const float2 u = lds_f2(sb + OFF_LX + i * 640 + tid * 8);
                v.x += u.x;
                v.y += u.y;
            }
            sts_f2(sb + OFF_LINV + tid * 8, __fdividef(1.f, v.x), __fdividef(1.f, v.y));
            la = v.x;
            lb = v.y;
        }
        const uint32_t bad = !(la >= 5.421010862e-20f && la <= 1.8446744e19f && lb >= 5.421010862e-20f && lb <= 1.8446744e19f);
        asm volatile(
            "{\n.reg .pred p, q;\nsetp.ne.u32 p, %1, 0;\n"
            "bar.red.or.pred q, %2, 128, p;\nselp.u32 %0, 1, 0, q;\n}"
            : "=r"(any)
            : "r"(bad), "n"(NB_VOTE)
            : "memory");
        if (tid == 0) sts_u(sb + OFF_FB, any);
        nb_arrive<NB_L, 256>();
        TS(W, 24);
    }
    wg_wait<0>();
    reg_fence(oa);
    reg_fence(ob);
    mbar_arrive_warp(sb + BAR_REMPTY + r.slot * 8, 1);
    mbar_arrive_warp(sb + BAR_XEMPTY + 32, 1);
    r.adv(1);
    TS(W, 25);
    if (!any) {
        unsigned char* gp = ostash_ptr(e);
#pragma unroll
        for (int g = 0; g < 5; g++) {
            float2 sc[4];
#pragma unroll
            for (int t = 0; t < 4; t++) sc[t] = lds_f2(sb + OFF_LINV + (lane & 3) * 8 + (4 * g + t) * 32);
            ostore(oa, g, sc, gp + W * XS + g * 512);
            if (W == 0 && g >= 3) ostore(ob, g - 3, sc, gp + 2 * XS + g * 512);
            if (W == 1 && g < 3) ostore(ob, g, sc, gp + 2 * XS + g * 512);
        }
    } else if (W == 1) {
        fallback_unit(P, e, threadIdx.x & 127);
    }
    nb_arrive<NB_ODONE, 288>();
}

__global__ void __launch_bounds__(384, 1) fused_kernel(const __grid_constant__ Params P) {
    extern __shared__ __align__(1024) unsigned char smem_raw[];
    const uint32_t sb = (uint32_t)__cvta_generic_to_shared(smem_raw);
    const uint32_t wgid = __shfl_sync(0xffffffffu, threadIdx.x >> 7, 0);
    const uint32_t cta = blockIdx.x;
    const uint32_t* items = P.items[cta];

    uint32_t epoch = 0;
    if (wgid == 0) epoch = *(volatile unsigned int*)&g_epoch[cta] + 1;
    if (threadIdx.x == 0) {
        if (sb & 1023) __trap();
        for (int i = 0; i < NSLOT; i++) {
            mbar_init(sb + BAR_RFULL + i * 8, 1);
            mbar_init(sb + BAR_REMPTY + i * 8, 8);
            mbar_init(sb + BAR_XFULL + i * 8, 1);
            mbar_init(sb + BAR_XEMPTY + i * 8, 8);
        }
        asm volatile("fence.mbarrier_init.release.cluster;" ::: "memory");
        fence_async_smem();
    }
    __syncthreads();

    if (wgid == 0) {
        asm volatile("setmaxnreg.dec.sync.aligned.u32 24;");
        const uint32_t warp = __shfl_sync(0xffffffffu, threadIdx.x >> 5, 0);
        if (warp == 0) {
            if (threadIdx.x == 0) {
                *(volatile unsigned int*)&g_epoch[cta] = epoch;
                uint64_t pol_first, pol_norm;
                asm volatile("createpolicy.fractional.L2::evict_first.b64 %0, 1.0;" : "=l"(pol_first));
                asm volatile("createpolicy.fractional.L2::evict_normal.b64 %0, 1.0;" : "=l"(pol_norm));
                Ring r{0, 1};
                for (int it = 0; it < MAXI; it++) {
                    const uint32_t e = items[it];
                    if (e == 0) break;
                    const uint32_t br = IT_BR(e);
                    if (IT_TYPE(e) == IT_QA) {
                        const uint32_t h = IT_H0(e);
#pragma unroll 1
                        for (int kk = 0; kk < 10; kk++) {
                            mbar_wait(sb + BAR_REMPTY + r.slot * 8, r.ph);
                            mbar_expect(sb + BAR_RFULL + r.slot * 8, SLOT);
                            tma3(sb + OFF_RING + r.slot * SLOT, &P.wq[br], kk * 64, h * 3, sb + BAR_RFULL + r.slot * 8, pol_norm);
                            r.adv(1);
                        }
                        const int row0 = (IT_B(e) * 32 + h) * 512;
#pragma unroll 1
                        for (int n = 0; n < 16; n++) {
                            const bool isv = n == 15 || (n > 0 && !(n & 1));
                            const int j = n == 15 ? 7 : isv ? (n - 2) >> 1 : (n + 1) >> 1;
                            mbar_wait(sb + BAR_REMPTY + r.slot * 8, r.ph);
                            mbar_expect(sb + BAR_RFULL + r.slot * 8, SLOT);
                            tma3(sb + OFF_RING + r.slot * SLOT, isv ? &P.v[br] : &P.k[br], row0 + j * 64, 0,
                                 sb + BAR_RFULL + r.slot * 8, pol_first);
                            r.adv(1);
                        }
                    } else {
                        const int r0 = IT_H0(e) * 192, r1 = IT_H1(e) * 192;
#pragma unroll 1
                        for (int row = r0; row < r1; row += 32) {
                            mbar_wait(sb + BAR_REMPTY + r.slot * 8, r.ph);
                            mbar_expect(sb + BAR_RFULL + r.slot * 8, XS);
                            tma3(sb + OFF_RING + r.slot * SLOT, &P.wo[br], row, IT_HALF(e) * 5, sb + BAR_RFULL + r.slot * 8, pol_norm);
                            r.adv(1);
                        }
                    }
                }
            }
        } else if (warp == 1) {
            if (threadIdx.x == 32) {
                uint64_t pol_norm;
                asm volatile("createpolicy.fractional.L2::evict_normal.b64 %0, 1.0;" : "=l"(pol_norm));
                uint32_t phm = 0x1f;
                for (int it = 0; it < MAXI; it++) {
                    const uint32_t e = items[it];
                    if (e == 0) break;
                    const uint32_t br = IT_BR(e);
                    uint32_t xs = 0;
                    if (IT_TYPE(e) == IT_QA) {
#pragma unroll 1
                        for (int kk = 0; kk < 10; kk++) {
                            mbar_wait(sb + BAR_XEMPTY + xs * 8, (phm >> xs) & 1);
                            phm ^= 1u << xs;
                            mbar_expect(sb + BAR_XFULL + xs * 8, XS);
                            tma3(sb + OFF_R + xs * XS, &P.x[br], IT_B(e) * 160, kk, sb + BAR_XFULL + xs * 8, pol_norm);
                            if (++xs == 5) xs = 0;
                        }
                    } else {
                        const uint32_t u0 = (br * 16 + IT_B(e)) * 32;
#pragma unroll 1
                        for (uint32_t u = u0 + IT_H0(e); u < u0 + IT_H1(e); u++) {
                            uint32_t v, n = 0;
                            do {
                                asm volatile("ld.acquire.gpu.global.u32 %0, [%1];" : "=r"(v) : "l"(&g_flag[u]) : "memory");
                                if (++n > 0x2000000) __trap();
                            } while (v != epoch);
                            asm volatile("fence.proxy.async;" ::: "memory");
#pragma unroll 1
                            for (int t = 0; t < 3; t++) {
                                mbar_wait(sb + BAR_XEMPTY + xs * 8, (phm >> xs) & 1);
                                phm ^= 1u << xs;
                                mbar_expect(sb + BAR_XFULL + xs * 8, XS);
                                bulk_load(sb + OFF_R + xs * XS, g_ostash + (size_t)u * OUNIT + t * XS, XS, sb + BAR_XFULL + xs * 8);
                                if (++xs == 5) xs = 0;
                            }
                        }
                    }
                }
            }
        } else if (warp == 2) {
            for (int it = 0; it < MAXI; it++) {
                const uint32_t e = items[it];
                if (e == 0) break;
                if (IT_TYPE(e) == IT_QA) {
                    nb_sync<NB_ODONE, 288>();
                    if (threadIdx.x == 64) {
                        __threadfence();
                        const uint32_t u = (IT_BR(e) * 16 + IT_B(e)) * 32 + IT_H0(e);
                        asm volatile("st.relaxed.gpu.global.u32 [%0], %1;" ::"l"(&g_flag[u]), "r"(epoch) : "memory");
                    }
                    __syncwarp();
                }
            }
        }
    } else if (wgid == 1) {
        asm volatile("setmaxnreg.inc.sync.aligned.u32 240;");
        Ring r{0, 0};
        uint32_t phm = 0;
#pragma unroll 1
        for (int it = 0; it < MAXI; it++) {
            const uint32_t e = items[it];
            if (e == 0) break;
            TS(0, 0);
            if (IT_TYPE(e) == IT_QA) qa_item<0>(P, e, sb, r, phm, it);
            else op_item<true>(P, e, sb, r, phm);
            TS(0, 31);
        }
        TS_DUMP(0);
    } else {
        asm volatile("setmaxnreg.inc.sync.aligned.u32 240;");
        Ring r{0, 0};
        uint32_t phm = 0;
#pragma unroll 1
        for (int it = 0; it < MAXI; it++) {
            const uint32_t e = items[it];
            if (e == 0) break;
            TS(1, 0);
            if (IT_TYPE(e) == IT_QA) qa_item<1>(P, e, sb, r, phm, it);
            else op_item<false>(P, e, sb, r, phm);
            TS(1, 31);
        }
        TS_DUMP(1);
    }
}

typedef CUresult (*EncFn)(CUtensorMap*, CUtensorMapDataType, cuuint32_t, void*, const cuuint64_t*, const cuuint64_t*,
                          const cuuint32_t*, const cuuint32_t*, CUtensorMapInterleave, CUtensorMapSwizzle,
                          CUtensorMapL2promotion, CUtensorMapFloatOOBfill);

void make_map3(EncFn enc, CUtensorMap* m, void* p, uint64_t rows, uint64_t rowbytes, uint64_t nblk, uint32_t boxrows,
               uint32_t boxblk) {
    cuuint64_t dims[3] = {64, rows, nblk};
    cuuint64_t str[2] = {rowbytes, 128};
    cuuint32_t box[3] = {64, boxrows, boxblk};
    cuuint32_t es[3] = {1, 1, 1};
    enc(m, CU_TENSOR_MAP_DATA_TYPE_BFLOAT16, 3, p, dims, str, box, es, CU_TENSOR_MAP_INTERLEAVE_NONE,
        CU_TENSOR_MAP_SWIZZLE_128B, CU_TENSOR_MAP_L2_PROMOTION_NONE, CU_TENSOR_MAP_FLOAT_OOB_FILL_NONE);
}

#define SCHED_MODE 0

void build_schedule(Params& P) {
    int n[NCTA];
    for (int c = 0; c < NCTA; c++) {
        n[c] = 0;
        for (int i = 0; i < MAXI; i++) P.items[c][i] = 0;
    }
    for (int u = 0; u < 1024; u++) {
        const int br = u >> 9, h = (u >> 4) & 31, b = u & 15;
        const int c = u % NCTA;
        if (SCHED_MODE == 2 && (c & 3)) continue;
        P.items[c][n[c]++] = mk_item(IT_QA, br, b, h, 0, 0);
    }
    if (SCHED_MODE == 0) {
        for (int t = 0; t < 64; t++) {
            const int c = NCTA - 1 - t;
            P.items[c][n[c]++] = mk_item(IT_OP, t >> 5, (t >> 1) & 15, 0, 32, t & 1);
        }
    }
}

}

extern "C" void kernel_launch(void* const* d_in, const int* in_sizes, int n_in, void* d_out, int out_size) {
    static Params P;
    static bool init = false;
    if (!init) {
        EncFn enc = nullptr;
        cudaDriverEntryPointQueryResult qr;
        cudaGetDriverEntryPoint("cuTensorMapEncodeTiled", (void**)&enc, cudaEnableDefault, &qr);
        for (int i = 0; i < 2; i++) {
            P.px[i] = (const __nv_bfloat16*)d_in[5 * i + 0];
            P.pk[i] = (const __nv_bfloat16*)d_in[5 * i + 1];
            P.pv[i] = (const __nv_bfloat16*)d_in[5 * i + 2];
            P.pwq[i] = (const __nv_bfloat16*)d_in[5 * i + 3];
            make_map3(enc, &P.x[i], d_in[5 * i + 0], 2560, 1280, 10, 160, 1);
            make_map3(enc, &P.k[i], d_in[5 * i + 1], 16 * 32 * 512, 384, 3, 64, 3);
            make_map3(enc, &P.v[i], d_in[5 * i + 2], 16 * 32 * 512, 384, 3, 64, 3);
            make_map3(enc, &P.wq[i], d_in[5 * i + 3], 640, 12288, 96, 64, 3);
            make_map3(enc, &P.wo[i], d_in[5 * i + 4], 6144, 1280, 10, 32, 5);
        }
        cuuint64_t dims[2] = {1280, 2560};
        cuuint64_t str[1] = {2560};
        cuuint32_t box[2] = {64, 160};
        cuuint32_t es[2] = {1, 1};
        enc(&P.out, CU_TENSOR_MAP_DATA_TYPE_BFLOAT16, 2, d_out, dims, str, box, es, CU_TENSOR_MAP_INTERLEAVE_NONE,
            CU_TENSOR_MAP_SWIZZLE_128B, CU_TENSOR_MAP_L2_PROMOTION_NONE, CU_TENSOR_MAP_FLOAT_OOB_FILL_NONE);
        build_schedule(P);
        cudaFuncSetAttribute(fused_kernel, cudaFuncAttributeMaxDynamicSharedMemorySize, SMEM_LAUNCH);
        init = true;
    }
    fused_kernel<<<NCTA, 384, SMEM_LAUNCH>>>(P);
}
```

```cpp
#include <cuda_runtime.h>
#include <cuda.h>
#include <cuda_bf16.h>
#include <stdint.h>

namespace {

constexpr int NCTA = 132;
constexpr int MAXI = 16;
constexpr int SLOT = 24576;
constexpr int NSLOT = 5;
constexpr int XS = 20480;
constexpr int OFF_R = 0;
constexpr int OFF_RING = 5 * XS;
constexpr int OFF_MISC = OFF_RING + NSLOT * SLOT;
constexpr int OFF_LX = OFF_MISC;
constexpr int OFF_LINV = OFF_LX + 2560;
constexpr int OFF_FB = OFF_LINV + 640;
constexpr int OFF_GM = OFF_FB + 16;
constexpr int OFF_BAR = OFF_GM + 16;
constexpr int BAR_RFULL = OFF_BAR;
constexpr int BAR_REMPTY = BAR_RFULL + 40;
constexpr int BAR_XFULL = BAR_REMPTY + 40;
constexpr int BAR_XEMPTY = BAR_XFULL + 40;
constexpr int SMEM_BYTES = BAR_XEMPTY + 40;
static_assert(SMEM_BYTES <= 232448, "smem");

constexpr int NB_W = 1  , NB_PFULL = 3  , NB_VOTE = 5, NB_Q01 = 6, NB_Q2 = 7, NB_SDONE = 8, NB_PDONE = 9,
              NB_L = 10, NB_OPST = 11, NB_ODONE = 12, NB_OPEND = 13, NB_LX = 14;

constexpr uint32_t IT_QA = 1, IT_OP = 2;
__host__ __device__ constexpr uint32_t mk_item(uint32_t type, uint32_t br, uint32_t b, uint32_t h0, uint32_t h1, uint32_t half) {
    return type | (br << 2) | (b << 3) | (h0 << 7) | (h1 << 13) | (half << 19);
}
#define IT_TYPE(e) ((e) & 3u)
#define IT_BR(e) (((e) >> 2) & 1u)
#define IT_B(e) (((e) >> 3) & 15u)
#define IT_H0(e) (((e) >> 7) & 63u)
#define IT_H1(e) (((e) >> 13) & 63u)
#define IT_HALF(e) (((e) >> 19) & 1u)

struct Params {
    CUtensorMap x[2], wq[2], k[2], v[2], wo[2], out;
    const __nv_bfloat16 *px[2], *pwq[2], *pk[2], *pv[2];
    uint32_t items[NCTA][MAXI];
};

constexpr int OUNIT = 61440;
__device__ __align__(1024) unsigned char g_ostash[(size_t)1024 * OUNIT];
__device__ unsigned int g_flag[1024];
__device__ unsigned int g_epoch[NCTA];

constexpr int SMEM_LAUNCH = SMEM_BYTES;
#define TS(role, idx)
#define TS_DUMP(role)
#define TS2(cond, idx)

#define QHOLD 7
constexpr float SM_C = 0.07216878364870322f * 1.4426950408889634f;

__device__ __forceinline__ void mbar_init(uint32_t a, uint32_t c) {
    asm volatile("mbarrier.init.shared::cta.b64 [%0], %1;" ::"r"(a), "r"(c) : "memory");
}
__device__ __forceinline__ void mbar_expect(uint32_t a, uint32_t b) {
    asm volatile("mbarrier.arrive.expect_tx.shared::cta.b64 _, [%0], %1;" ::"r"(a), "r"(b) : "memory");
}
__device__ __forceinline__ void mbar_arrive_warp(uint32_t a, uint32_t cnt) {
    asm volatile(
        "{\n.reg .pred p;\nelect.sync _|p, 0xffffffff;\n"
        "@p mbarrier.arrive.shared::cta.b64 _, [%0], %1;\n}" ::"r"(a), "r"(cnt)
        : "memory");
}
__device__ __forceinline__ void mbar_arrive_warp_if(uint32_t a, uint32_t cnt, bool cond) {
    asm volatile(
        "{\n.reg .pred p, c;\nelect.sync _|p, 0xffffffff;\nsetp.ne.and.u32 c, %2, 0, p;\n"
        "@c mbarrier.arrive.shared::cta.b64 _, [%0], %1;\n}" ::"r"(a), "r"(cnt), "r"((uint32_t)cond)
        : "memory");
}
__device__ __forceinline__ void mbar_wait(uint32_t a, uint32_t ph) {
    asm volatile(
        "{\n.reg .pred p;\n.reg .u32 n, m;\n"
        "mbarrier.try_wait.parity.shared::cta.b64 p, [%0], %1;\n"
        "@p bra DONE;\n"
        "mov.u32 n, %%clock_hi;\n"
        "LOOP:\n"
        "mbarrier.try_wait.parity.shared::cta.b64 p, [%0], %1;\n"
        "@p bra DONE;\n"
        "mov.u32 m, %%clock_hi;\n"
        "sub.u32 m, m, n;\n"
        "setp.lt.u32 p, m, 2;\n"
        "@p bra LOOP;\n"
        "trap;\n"
        "DONE:\n}" ::"r"(a), "r"(ph)
        : "memory");
}
template <int ID, int CNT>
__device__ __forceinline__ void nb_sync() { asm volatile("bar.sync %0, %1;" ::"n"(ID), "n"(CNT) : "memory"); }
template <int ID, int CNT>
__device__ __forceinline__ void nb_arrive() { asm volatile("bar.arrive %0, %1;" ::"n"(ID), "n"(CNT) : "memory"); }
__device__ __forceinline__ void fence_async_smem() { asm volatile("fence.proxy.async.shared::cta;" ::: "memory"); }

__device__ __forceinline__ void tma3(uint32_t dst, const CUtensorMap* m, int c1, int c2, uint32_t bar, uint64_t pol) {
    asm volatile(
        "cp.async.bulk.tensor.3d.shared::cluster.global.mbarrier::complete_tx::bytes.L2::cache_hint [%0], [%1, {%3,%4,%5}], [%2], %6;" ::"r"(dst),
        "l"(m), "r"(bar), "r"(0), "r"(c1), "r"(c2), "l"(pol)
        : "memory");
}
__device__ __forceinline__ void bulk_load(uint32_t dst, const void* src, uint32_t bytes, uint32_t bar) {
    asm volatile("cp.async.bulk.shared::cluster.global.mbarrier::complete_tx::bytes [%0], [%1], %2, [%3];" ::"r"(dst),
                 "l"(src), "r"(bytes), "r"(bar)
                 : "memory");
}
__device__ __forceinline__ void wg_fence() { asm volatile("wgmma.fence.sync.aligned;" ::: "memory"); }
__device__ __forceinline__ void wg_commit() { asm volatile("wgmma.commit_group.sync.aligned;" ::: "memory"); }
template <int N>
__device__ __forceinline__ void wg_wait() { asm volatile("wgmma.wait_group.sync.aligned %0;" ::"n"(N) : "memory"); }

#define RW80(c, d) c(d[0]), c(d[1]), c(d[2]), c(d[3]), c(d[4]), c(d[5]), c(d[6]), c(d[7]), c(d[8]), c(d[9]), c(d[10]), c(d[11]), c(d[12]), c(d[13]), c(d[14]), c(d[15]), c(d[16]), c(d[17]), c(d[18]), c(d[19]), c(d[20]), c(d[21]), c(d[22]), c(d[23]), c(d[24]), c(d[25]), c(d[26]), c(d[27]), c(d[28]), c(d[29]), c(d[30]), c(d[31]), c(d[32]), c(d[33]), c(d[34]), c(d[35]), c(d[36]), c(d[37]), c(d[38]), c(d[39]), c(d[40]), c(d[41]), c(d[42]), c(d[43]), c(d[44]), c(d[45]), c(d[46]), c(d[47]), c(d[48]), c(d[49]), c(d[50]), c(d[51]), c(d[52]), c(d[53]), c(d[54]), c(d[55]), c(d[56]), c(d[57]), c(d[58]), c(d[59]), c(d[60]), c(d[61]), c(d[62]), c(d[63]), c(d[64]), c(d[65]), c(d[66]), c(d[67]), c(d[68]), c(d[69]), c(d[70]), c(d[71]), c(d[72]), c(d[73]), c(d[74]), c(d[75]), c(d[76]), c(d[77]), c(d[78]), c(d[79])
#define RW48(c, d) c(d[0]), c(d[1]), c(d[2]), c(d[3]), c(d[4]), c(d[5]), c(d[6]), c(d[7]), c(d[8]), c(d[9]), c(d[10]), c(d[11]), c(d[12]), c(d[13]), c(d[14]), c(d[15]), c(d[16]), c(d[17]), c(d[18]), c(d[19]), c(d[20]), c(d[21]), c(d[22]), c(d[23]), c(d[24]), c(d[25]), c(d[26]), c(d[27]), c(d[28]), c(d[29]), c(d[30]), c(d[31]), c(d[32]), c(d[33]), c(d[34]), c(d[35]), c(d[36]), c(d[37]), c(d[38]), c(d[39]), c(d[40]), c(d[41]), c(d[42]), c(d[43]), c(d[44]), c(d[45]), c(d[46]), c(d[47])
#define RW32(c, d) c(d[0]), c(d[1]), c(d[2]), c(d[3]), c(d[4]), c(d[5]), c(d[6]), c(d[7]), c(d[8]), c(d[9]), c(d[10]), c(d[11]), c(d[12]), c(d[13]), c(d[14]), c(d[15]), c(d[16]), c(d[17]), c(d[18]), c(d[19]), c(d[20]), c(d[21]), c(d[22]), c(d[23]), c(d[24]), c(d[25]), c(d[26]), c(d[27]), c(d[28]), c(d[29]), c(d[30]), c(d[31])

__device__ __forceinline__ void reg_fence(float (&d)[80]) { asm volatile("" : RW80("+f", d)::"memory"); }
__device__ __forceinline__ void reg_fence(float (&d)[48]) { asm volatile("" : RW48("+f", d)::"memory"); }
__device__ __forceinline__ void reg_fence(float (&d)[32]) { asm volatile("" : RW32("+f", d)::"memory"); }

constexpr uint32_t HI_SW128 = (1024u >> 4) | (1u << 30);
constexpr uint32_t HI_OST = (2560u >> 4) | (2u << 30);
constexpr uint32_t LO_LBO1 = (1u << 16);
constexpr uint32_t LO_OST = ((512u >> 4) << 16);

template <int TA, int TB, uint32_t HIB, bool ACC>
__device__ __forceinline__ void wgmma(float (&d)[80], uint32_t loA, uint32_t loB) {
#define WG_ASM(SD)                                                          \
    "{\n.reg .b64 da, db;\nmov.b64 da, {%80, %82};\nmov.b64 db, {%81, %83};\n" \
    "wgmma.mma_async.sync.aligned.m64n160k16.f32.bf16.bf16 "               \
    "{%0,%1,%2,%3,%4,%5,%6,%7,%8,%9,%10,%11,%12,%13,%14,%15,%16,%17,%18,%19,%20,%21,%22,%23,%24,%25,%26,%27,%28,%29,%30,%31,%32,%33,%34,%35,%36,%37,%38,%39,%40,%41,%42,%43,%44,%45,%46,%47,%48,%49,%50,%51,%52,%53,%54,%55,%56,%57,%58,%59,%60,%61,%62,%63,%64,%65,%66,%67,%68,%69,%70,%71,%72,%73,%74,%75,%76,%77,%78,%79}, da, db, " SD ", 1, 1, %84, %85;\n}"
    if constexpr (ACC)
        asm volatile(WG_ASM("1") : RW80("+f", d) : "r"(loA), "r"(loB), "n"(HI_SW128), "n"(HIB), "n"(TA), "n"(TB));
    else
        asm volatile(WG_ASM("0") : RW80("=f", d) : "r"(loA), "r"(loB), "n"(HI_SW128), "n"(HIB), "n"(TA), "n"(TB));
#undef WG_ASM
}
template <int TA, int TB, uint32_t HIB, bool ACC>
__device__ __forceinline__ void wgmma(float (&d)[48], uint32_t loA, uint32_t loB) {
#define WG_ASM(SD)                                                          \
    "{\n.reg .b64 da, db;\nmov.b64 da, {%48, %50};\nmov.b64 db, {%49, %51};\n" \
    "wgmma.mma_async.sync.aligned.m64n96k16.f32.bf16.bf16 "               \
    "{%0,%1,%2,%3,%4,%5,%6,%7,%8,%9,%10,%11,%12,%13,%14,%15,%16,%17,%18,%19,%20,%21,%22,%23,%24,%25,%26,%27,%28,%29,%30,%31,%32,%33,%34,%35,%36,%37,%38,%39,%40,%41,%42,%43,%44,%45,%46,%47}, da, db, " SD ", 1, 1, %52, %53;\n}"
    if constexpr (ACC)
        asm volatile(WG_ASM("1") : RW48("+f", d) : "r"(loA), "r"(loB), "n"(HI_SW128), "n"(HIB), "n"(TA), "n"(TB));
    else
        asm volatile(WG_ASM("0") : RW48("=f", d) : "r"(loA), "r"(loB), "n"(HI_SW128), "n"(HIB), "n"(TA), "n"(TB));
#undef WG_ASM
}
template <int TA, int TB, uint32_t HIB, bool ACC>
__device__ __forceinline__ void wgmma(float (&d)[32], uint32_t loA, uint32_t loB) {
#define WG_ASM(SD)                                                          \
    "{\n.reg .b64 da, db;\nmov.b64 da, {%32, %34};\nmov.b64 db, {%33, %35};\n" \
    "wgmma.mma_async.sync.aligned.m64n64k16.f32.bf16.bf16 "               \
    "{%0,%1,%2,%3,%4,%5,%6,%7,%8,%9,%10,%11,%12,%13,%14,%15,%16,%17,%18,%19,%20,%21,%22,%23,%24,%25,%26,%27,%28,%29,%30,%31}, da, db, " SD ", 1, 1, %36, %37;\n}"
    if constexpr (ACC)
        asm volatile(WG_ASM("1") : RW32("+f", d) : "r"(loA), "r"(loB), "n"(HI_SW128), "n"(HIB), "n"(TA), "n"(TB));
    else
        asm volatile(WG_ASM("0") : RW32("=f", d) : "r"(loA), "r"(loB), "n"(HI_SW128), "n"(HIB), "n"(TA), "n"(TB));
#undef WG_ASM
}

__device__ __forceinline__ uint32_t pack_bf16(float lo, float hi) {
    uint32_t r;
    asm("cvt.rn.bf16x2.f32 %0, %1, %2;" : "=r"(r) : "f"(hi), "f"(lo));
    return r;
}
__device__ __forceinline__ float ex2(float x) {
    float r;
    asm("ex2.approx.ftz.f32 %0, %1;" : "=f"(r) : "f"(x));
    return r;
}
__device__ __forceinline__ void stsm4t(uint32_t a, uint32_t r0, uint32_t r1, uint32_t r2, uint32_t r3) {
    asm volatile("stmatrix.sync.aligned.m8n8.x4.trans.shared.b16 [%0], {%1,%2,%3,%4};" ::"r"(a), "r"(r0), "r"(r1), "r"(r2), "r"(r3)
                 : "memory");
}
__device__ __forceinline__ uint32_t lds_u(uint32_t a) {
    uint32_t v;
    asm volatile("ld.shared.u32 %0, [%1];" : "=r"(v) : "r"(a) : "memory");
    return v;
}
__device__ __forceinline__ float2 lds_f2(uint32_t a) {
    float2 v;
    asm volatile("ld.shared.v2.f32 {%0,%1}, [%2];" : "=f"(v.x), "=f"(v.y) : "r"(a) : "memory");
    return v;
}
__device__ __forceinline__ void sts_f(uint32_t a, float v) { asm volatile("st.shared.f32 [%0], %1;" ::"r"(a), "f"(v) : "memory"); }
__device__ __forceinline__ void sts_u(uint32_t a, uint32_t v) { asm volatile("st.shared.u32 [%0], %1;" ::"r"(a), "r"(v) : "memory"); }
__device__ __forceinline__ void sts_f2(uint32_t a, float x, float y) {
    asm volatile("st.shared.v2.f32 [%0], {%1,%2};" ::"r"(a), "f"(x), "f"(y) : "memory");
}

__device__ __forceinline__ void store_tile_t(const float (&d)[80], uint32_t addr) {
#pragma unroll
    for (int j = 0; j < 10; j++)
        stsm4t(addr + j * 2048, pack_bf16(d[8 * j], d[8 * j + 1]), pack_bf16(d[8 * j + 2], d[8 * j + 3]),
               pack_bf16(d[8 * j + 4], d[8 * j + 5]), pack_bf16(d[8 * j + 6], d[8 * j + 7]));
}
template <int NR>
__device__ __forceinline__ void store_out_tile(const float (&d)[NR], uint32_t base, uint32_t lane, uint32_t w) {
    const uint32_t mi = lane >> 3, i = lane & 7;
    const uint32_t chunk = 2 * w + (mi & 1);
    const uint32_t q0 = 8 * (i >> 1) + 2 * (mi >> 1) + (i & 1);
    const uint32_t a0 = base + q0 * 128 + ((chunk ^ (q0 & 7)) << 4);
    const uint32_t a1 = base + (q0 + 4) * 128 + ((chunk ^ ((q0 + 4) & 7)) << 4);
#pragma unroll
    for (int j = 0; j < NR / 8; j++)
        stsm4t(((j & 1) ? a1 : a0) + (j >> 1) * 4096, pack_bf16(d[8 * j], d[8 * j + 1]), pack_bf16(d[8 * j + 2], d[8 * j + 3]),
               pack_bf16(d[8 * j + 4], d[8 * j + 5]), pack_bf16(d[8 * j + 6], d[8 * j + 7]));
}

struct TrueT { static constexpr bool value = true; };
struct FalseT { static constexpr bool value = false; };

template <int V>
struct IntT { static constexpr int value = V; };

struct Ring {
    uint32_t slot, ph;
    __device__ __forceinline__ void adv(uint32_t k) {
        slot += k;
        if (slot >= NSLOT) { slot -= NSLOT; ph ^= 1; }
    }
};

template <int K>
__device__ __forceinline__ void qk_step(float (&s)[80], uint32_t loK, uint32_t loQ) {
    wgmma<0, 0, HI_SW128, K != 0>(s, loK + (K >> 2) * (8192 >> 4) + (K & 3) * 2, loQ + (K >> 2) * (XS >> 4) + (K & 3) * 2);
}
template <int K0, int K1>
__device__ __forceinline__ void qk_steps(float (&s)[80], uint32_t loK, uint32_t loQ) {
    if constexpr (K0 < K1) {
        qk_step<K0>(s, loK, loQ);
        qk_steps<K0 + 1, K1>(s, loK, loQ);
    }
}
template <int J>
__device__ __forceinline__ void exp_chunk(const float (&s)[80], float (&ps)[40], uint32_t pa, float mref) {
    float p[8];
#pragma unroll
    for (int i = 0; i < 8; i++) p[i] = ex2(fmaf(s[8 * J + i], SM_C, -mref));
    stsm4t(pa + J * 2048, pack_bf16(p[0], p[1]), pack_bf16(p[2], p[3]), pack_bf16(p[4], p[5]), pack_bf16(p[6], p[7]));
    ps[4 * J] = p[0] + p[2];
    ps[4 * J + 1] = p[1] + p[3];
    ps[4 * J + 2] = p[4] + p[6];
    ps[4 * J + 3] = p[5] + p[7];
}
template <int J>
__device__ __forceinline__ void exp_block(const float (&s)[80], float (&ps)[40], uint32_t pa, float mref) {
    if constexpr (J < 10) {
        exp_chunk<J>(s, ps, pa, mref);
        exp_block<J + 1>(s, ps, pa, mref);
    }
}
__device__ __forceinline__ void sum_block(const float (&ps)[40], float (&l)[5], uint32_t lane) {
    const bool b4 = lane & 16, b3 = lane & 8, b2 = lane & 4;
    float t[20];
#pragma unroll
    for (int j = 0; j < 10; j++) {
        t[2 * j] = (b4 ? ps[4 * j + 2] : ps[4 * j]) + __shfl_xor_sync(0xffffffffu, b4 ? ps[4 * j] : ps[4 * j + 2], 16);
        t[2 * j + 1] = (b4 ? ps[4 * j + 3] : ps[4 * j + 1]) + __shfl_xor_sync(0xffffffffu, b4 ? ps[4 * j + 1] : ps[4 * j + 3], 16);
    }
#pragma unroll
    for (int i = 0; i < 10; i++) t[i] = (b3 ? t[i + 10] : t[i]) + __shfl_xor_sync(0xffffffffu, b3 ? t[i] : t[i + 10], 8);
#pragma unroll
    for (int i = 0; i < 5; i++)
        l[i] += (b2 ? t[2 * i + 1] : t[2 * i]) + __shfl_xor_sync(0xffffffffu, b2 ? t[2 * i] : t[2 * i + 1], 4);
}

__device__ __forceinline__ void fallback_unit(const Params& P, uint32_t e, uint32_t tid) {
    const uint32_t lane = tid & 31, br = IT_BR(e), b = IT_B(e), h = IT_H0(e);
    const uint32_t u = (br * 16 + b) * 32 + h;
    const __nv_bfloat162* wq = (const __nv_bfloat162*)(P.pwq[br] + h * 192) + lane;
    const __nv_bfloat162* kp = (const __nv_bfloat162*)(P.pk[br] + (size_t)(b * 32 + h) * 512 * 192) + lane;
    const __nv_bfloat162* vp = (const __nv_bfloat162*)(P.pv[br] + (size_t)(b * 32 + h) * 512 * 192) + lane;
#pragma unroll 1
    for (uint32_t q = tid >> 5; q < 160; q += 4) {
        const __nv_bfloat16* xr = P.px[br] + (size_t)(b * 160 + q) * 640;
        float a[6] = {0.f, 0.f, 0.f, 0.f, 0.f, 0.f};
#pragma unroll 4
        for (int k = 0; k < 640; k++) {
            const float xv = __bfloat162float(xr[k]);
#pragma unroll
            for (int i = 0; i < 3; i++) {
                const float2 wv = __bfloat1622float2(wq[(size_t)k * 3072 + i * 32]);
                a[2 * i] = fmaf(xv, wv.x, a[2 * i]);
                a[2 * i + 1] = fmaf(xv, wv.y, a[2 * i + 1]);
            }
        }
#pragma unroll
        for (int i = 0; i < 6; i++) a[i] = __bfloat162float(__float2bfloat16(a[i]));
        auto score = [&](int key) {
            float d = 0.f;
#pragma unroll
            for (int i = 0; i < 3; i++) {
                const float2 kv = __bfloat1622float2(kp[key * 96 + i * 32]);
                d = fmaf(a[2 * i], kv.x, fmaf(a[2 * i + 1], kv.y, d));
            }
#pragma unroll
            for (int o = 16; o > 0; o >>= 1) d += __shfl_xor_sync(0xffffffffu, d, o);
            return d;
        };
        float m = -INFINITY;
#pragma unroll 4
        for (int key = 0; key < 512; key++) m = fmaxf(m, score(key));
        float o[6] = {0.f, 0.f, 0.f, 0.f, 0.f, 0.f}, sum = 0.f;
#pragma unroll 4
        for (int key = 0; key < 512; key++) {
            const float p = ex2((score(key) - m) * SM_C);
            sum += p;
#pragma unroll
            for (int i = 0; i < 3; i++) {
                const float2 vv = __bfloat1622float2(vp[key * 96 + i * 32]);
                o[2 * i] = fmaf(p, vv.x, o[2 * i]);
                o[2 * i + 1] = fmaf(p, vv.y, o[2 * i + 1]);
            }
        }
        const float inv = 1.f / sum;
        __nv_bfloat16* op = (__nv_bfloat16*)(g_ostash + (size_t)u * OUNIT) + (q >> 5) * 256 + 2 * ((q & 31) >> 3) + (q & 1);
#pragma unroll
        for (int i = 0; i < 6; i++) {
            const uint32_t d = (i >> 1) * 64 + 2 * lane + (i & 1);
            op[(d >> 3) * 1280 + (d & 7) * 32 + ((((q & 7) >> 1) ^ ((d & 7) >> 1)) << 3)] = __float2bfloat16(o[i] * inv);
        }
    }
}

template <int W>
struct PendO {
    static constexpr int N = W == 0 ? 14 : 16;
    uint32_t v[4 * N];
    unsigned char* gp;
    uint32_t pend;
    template <int I>
    __device__ __forceinline__ void store() const {
        if constexpr (I < N) {
            constexpr int g = I < 10 ? I / 2 : (I - 10) / 2 + (W == 0 ? 3 : 0);
            constexpr int off = (I < 10 ? W : 2) * XS + g * 512 + (I & 1) * 2560;
            asm volatile(
                "{\n.reg .pred p;\nsetp.ne.u32 p, %6, 0;\n@p st.global.v4.b32 [%0+%5], {%1,%2,%3,%4};\n}" ::"l"(gp),
                "r"(v[4 * I]), "r"(v[4 * I + 1]), "r"(v[4 * I + 2]), "r"(v[4 * I + 3]), "n"(off), "r"(pend)
                : "memory");
        }
    }
    template <int I>
    __device__ __forceinline__ void flush() const {
        if constexpr (I < N) {
            store<I>();
            flush<I + 1>();
        }
    }
    __device__ __forceinline__ void clear() {
#pragma unroll
        for (int i = 0; i < 4 * N; i++) v[i] = 0;
        gp = nullptr;
        pend = 0;
    }
};

template <int W, int KK>
__device__ __forceinline__ void qproj(float (&q0)[80], float (&q1)[80], uint32_t sb, Ring& r, uint32_t phm, const PendO<W>& po) {
    const uint32_t loR = ((sb + OFF_R) >> 4) | LO_LBO1;
    const uint32_t loRing = ((sb + OFF_RING) >> 4) | LO_LBO1;
    constexpr int xs = KK % 5;
    const uint32_t pslot = r.slot;
    if (KK > 0) r.adv(1);
    if (W == 1 && KK == QHOLD) nb_sync<NB_SDONE, 256>();
    mbar_wait(sb + BAR_RFULL + r.slot * 8, r.ph);
    mbar_wait(sb + BAR_XFULL + xs * 8, ((phm >> xs) ^ (KK / 5)) & 1);
    const uint32_t a = loRing + r.slot * (SLOT >> 4) + (W == 0 ? 0 : 1024), b = loR + xs * (XS >> 4);
    wg_fence();
    wgmma<1, 0, HI_SW128, KK != 0>(q0, a, b);
    if (W == 0) wgmma<1, 0, HI_SW128, KK != 0>(q1, a + 512, b);
#pragma unroll
    for (int k = 1; k < 4; k++) {
        wgmma<1, 0, HI_SW128, true>(q0, a + k * 128, b + k * 2);
        if (W == 0) wgmma<1, 0, HI_SW128, true>(q1, a + 512 + k * 128, b + k * 2);
    }
    wg_commit();
    if (KK > 0) {
        wg_wait<1>();
        mbar_arrive_warp(sb + BAR_REMPTY + pslot * 8, 1);
        if (KK <= 5) mbar_arrive_warp(sb + (BAR_XEMPTY + (KK - 1) * 8), 1);
        if (W == 1 && KK == 7) nb_arrive<NB_PDONE, 256>();
    }
    if (KK < 6) {
        po.template store<3 * KK>();
        po.template store<3 * KK + 1>();
        po.template store<3 * KK + 2>();
        if (KK == 5 && po.pend) nb_arrive<NB_ODONE, 288>();
    }
    if constexpr (KK < 9) {
        qproj<W, KK + 1>(q0, q1, sb, r, phm, po);
    } else {
        if (W == 0) nb_arrive<NB_SDONE, 256>();
        wg_wait<0>();
        reg_fence(q0);
        if (W == 0) reg_fence(q1);
        mbar_arrive_warp(sb + BAR_REMPTY + r.slot * 8, 1);
        r.adv(1);
    }
}

template <int NR>
__device__ __forceinline__ void opack(const float (&o)[NR], int gl, const float2* sc, uint32_t* v) {
#pragma unroll
    for (int hh = 0; hh < 2; hh++)
#pragma unroll
        for (int t = 0; t < 4; t++)
            v[4 * hh + t] = pack_bf16(o[16 * gl + 4 * t + 2 * hh] * sc[t].x, o[16 * gl + 4 * t + 2 * hh + 1] * sc[t].y);
}

template <bool IS_S>
__device__ __forceinline__ void op_item(const Params& P, uint32_t e, uint32_t sb, Ring& r, uint32_t& phm) {
    constexpr int T0 = IS_S ? 0 : 2;
    constexpr uint32_t BOFF = IS_S ? (3 * 512) >> 4 : 0;
    const uint32_t loRing = ((sb + OFF_RING) >> 4) | LO_LBO1;
    const uint32_t loO = ((sb + OFF_R) >> 4) | LO_OST;
    float c0[80], c1[80], c2[IS_S ? 32 : 48];
    const int T2 = 6 * (IT_H1(e) - IT_H0(e));
    uint32_t xs = 0;
    auto step = [&](auto first, uint32_t hf) {
        constexpr bool F = decltype(first)::value;
        if (hf == 0) {
            mbar_wait(sb + BAR_XFULL + xs * 8, (phm >> xs) & 1);
            phm ^= 1u << xs;
        }
        mbar_wait(sb + BAR_RFULL + r.slot * 8, r.ph);
        const uint32_t a = loRing + r.slot * (SLOT >> 4), b = loO + xs * (XS >> 4) + hf * 640;
        wg_fence();
        wgmma<1, 1, HI_OST, !F>(c0, a + T0 * 256, b);
        wgmma<1, 1, HI_OST, !F>(c1, a + T0 * 256 + 256, b);
        wgmma<1, 1, HI_OST, !F>(c2, a + 1024, b + BOFF);
        wgmma<1, 1, HI_OST, true>(c0, a + T0 * 256 + 128, b + 320);
        wgmma<1, 1, HI_OST, true>(c1, a + T0 * 256 + 384, b + 320);
        wgmma<1, 1, HI_OST, true>(c2, a + 1024 + 128, b + 320 + BOFF);
        wg_commit();
    };
    step(TrueT{}, 0);
#pragma unroll 1
    for (int t = 1; t < T2; t++) {
        const uint32_t pslot = r.slot, pxs = xs;
        r.adv(1);
        if ((t & 1) == 0 && ++xs == 5) xs = 0;
        step(FalseT{}, t & 1);
        wg_wait<1>();
        mbar_arrive_warp(sb + BAR_REMPTY + pslot * 8, 1);
        if ((t & 1) == 0 && t + 8 < T2) mbar_arrive_warp(sb + BAR_XEMPTY + pxs * 8, 1);
    }
    wg_wait<0>();
    reg_fence(c0);
    reg_fence(c1);
    reg_fence(c2);
    mbar_arrive_warp(sb + BAR_REMPTY + r.slot * 8, 1);
    r.adv(1);
    nb_sync<NB_OPEND, 256>();
    const uint32_t lane = threadIdx.x & 31, w = (threadIdx.x >> 5) & 3;
    store_out_tile(c0, sb + OFF_R + T0 * XS, lane, w);
    store_out_tile(c1, sb + OFF_R + (T0 + 1) * XS, lane, w);
    store_out_tile(c2, sb + OFF_R + 4 * XS + (IS_S ? 96 * 128 : 0), lane, w);
    fence_async_smem();
    if (IS_S) {
        nb_arrive<NB_OPST, 256>();
    } else {
        nb_sync<NB_OPST, 256>();
        if ((threadIdx.x & 127) == 0) {
            const int cc0 = IT_BR(e) * 640 + IT_HALF(e) * 320;
#pragma unroll
            for (int m = 0; m < 5; m++)
                asm volatile("cp.async.bulk.tensor.2d.global.shared::cta.bulk_group [%0, {%2,%3}], [%1];" ::"l"(&P.out),
                             "r"(sb + OFF_R + m * XS), "r"(cc0 + m * 64), "r"((int)IT_B(e) * 160)
                             : "memory");
            asm volatile("cp.async.bulk.commit_group;" ::: "memory");
            asm volatile("cp.async.bulk.wait_group 0;" ::: "memory");
#pragma unroll
            for (int m = 0; m < 5; m++)
                asm volatile("mbarrier.arrive.shared::cta.b64 _, [%0], 8;" ::"r"(sb + BAR_XEMPTY + m * 8) : "memory");
        }
        __syncwarp();
    }
}

template <int W>
__device__ __forceinline__ void qa_item(const Params& P, const uint32_t* items, uint32_t sb, Ring& r, uint32_t phm, PendO<W>& po, int it) {
    const uint32_t loR = ((sb + OFF_R) >> 4) | LO_LBO1;
    const uint32_t loRing = ((sb + OFF_RING) >> 4) | LO_LBO1;
    const uint32_t lane = threadIdx.x & 31, w = (threadIdx.x >> 5) & 3;
    const uint32_t sta = sb + OFF_R + (lane >> 4) * 1024 + (lane & 7) * 128 + (((2 * w + ((lane >> 3) & 1)) ^ (lane & 7)) << 4);
    {
        float q0[80], q1[80];
        qproj<W, 0>(q0, q1, sb, r, phm, po);
        TS(W, 1);
        if (W == 0) {
            nb_sync<NB_PDONE, 256>();
            store_tile_t(q0, sta);
            store_tile_t(q1, sta + XS);
        } else {
            store_tile_t(q0, sta + 2 * XS);
        }
    }
    fence_async_smem();
    float s[80], oa[80], ob[W == 0 ? 32 : 48], l[5];
#pragma unroll
    for (int i = 0; i < 80; i++) oa[i] = 0.f;
#pragma unroll
    for (int i = 0; i < (W == 0 ? 32 : 48); i++) ob[i] = 0.f;
#pragma unroll
    for (int i = 0; i < 5; i++) l[i] = 0.f;
    reg_fence(oa);
    reg_fence(ob);
    auto pv = [&](uint32_t buf) {
        mbar_wait(sb + BAR_RFULL + r.slot * 8, r.ph);
        const uint32_t a = loRing + r.slot * (SLOT >> 4), b = loR + (3 + buf) * (XS >> 4);
        wg_fence();
#pragma unroll
        for (int k = 0; k < 4; k++) {
            wgmma<1, 0, HI_SW128, true>(oa, a + W * 512 + k * 128, b + k * 2);
            wgmma<1, 0, HI_SW128, true>(ob, a + 1024 + k * 128, b + (W == 0 ? (96 * 128) >> 4 : 0) + k * 2);
        }
        wg_commit();
    };
    float mref;
    uint32_t kslot, vslot;
    const uint32_t lxa = sb + OFF_LX + w * 640 + (((lane & 8) ? 80 : 0) + ((lane >> 1) & 8) + 2 * (lane & 3) + ((lane >> 2) & 1)) * 4;
    auto tail = [&](bool rel_other, int i) {
        float ps[40];
        exp_block<0>(s, ps, sta + (3 + W) * XS, mref);
        if (rel_other) {
            wg_wait<0>();
            mbar_arrive_warp(sb + BAR_REMPTY + vslot * 8, 1);
            if (W == 1) mbar_arrive_warp_if(sb + BAR_XEMPTY + 24, 1, i == 3);
        }
        fence_async_smem();
        nb_arrive<NB_PFULL + W, 256>();
        TS(W, 6 + 5 * i);
        mbar_wait(sb + BAR_RFULL + r.slot * 8, r.ph);
        sum_block(ps, l, lane);
        if (W == 1 && i == 3) {
            nb_sync<NB_LX, 256>();
#pragma unroll
            for (int k = 0; k < 5; k++) sts_f(lxa + k * 64, l[k]);
            nb_arrive<NB_L, 256>();
        }
        nb_sync<NB_W + W, 128>();
        TS(W, 7 + 5 * i);
        pv(W);
        TS(W, 8 + 5 * i);
    };
    if (W == 0) {
        nb_sync<NB_W, 128>();
        TS(W, 2);
        mbar_wait(sb + BAR_RFULL + r.slot * 8, r.ph);
        wg_fence();
        qk_steps<0, 8>(s, loRing + r.slot * (SLOT >> 4), loR);
        nb_sync<NB_Q2, 256>();
        qk_steps<8, 12>(s, loRing + r.slot * (SLOT >> 4), loR);
        wg_commit();
        nb_arrive<NB_Q01, 256>();
        TS(W, 4);
        wg_wait<0>();
        reg_fence(s);
        mbar_arrive_warp(sb + BAR_REMPTY + r.slot * 8, 2);
        r.adv(2);
        float m0 = fmaxf(s[0], s[5]), m1 = fmaxf(s[10], s[15]);
#pragma unroll
        for (int i = 20; i < 80; i += 10) {
            m0 = fmaxf(m0, s[i]);
            m1 = fmaxf(m1, s[i + 5]);
        }
        int key = __float_as_int(fmaxf(m0, m1));
        key ^= (key >> 31) & 0x7fffffff;
        key = __reduce_max_sync(0xffffffffu, key);
        key ^= (key >> 31) & 0x7fffffff;
        sts_u(sb + OFF_GM + w * 4, key);
        sts_u(sb + OFF_FB, 0);
        nb_sync<NB_W, 128>();
        const float2 u = lds_f2(sb + OFF_GM), v = lds_f2(sb + OFF_GM + 8);
        mref = fmaxf(fmaxf(u.x, u.y), fmaxf(v.x, v.y)) * SM_C;
        TS(W, 5);
        tail(false, 0);
    } else {
        nb_arrive<NB_Q2, 256>();
        TS(W, 2);
        nb_sync<NB_Q01, 256>();
    }
#pragma unroll 1
    for (int i = (W == 0 ? 1 : 0); i < 4; i++) {
        const uint32_t pvslot = r.slot;
        r.adv(1);
        kslot = r.slot;
        mbar_wait(sb + BAR_RFULL + r.slot * 8, r.ph);
        wg_fence();
        qk_steps<0, 12>(s, loRing + r.slot * (SLOT >> 4), loR);
        wg_commit();
        wg_wait<1>();
        mbar_arrive_warp_if(sb + BAR_REMPTY + pvslot * 8, 1, W == 0 || i > 0);
        r.adv(1);
        vslot = r.slot;
        TS(W, 4 + 5 * i);
        nb_sync<NB_PFULL + (W ^ 1), 256>();
        pv(W ^ 1);
        if (W == 1) {
            const float2 u = lds_f2(sb + OFF_GM), v = lds_f2(sb + OFF_GM + 8);
            mref = fmaxf(fmaxf(u.x, u.y), fmaxf(v.x, v.y)) * SM_C;
        }
        wg_wait<1>();
        reg_fence(s);
        mbar_arrive_warp(sb + BAR_REMPTY + kslot * 8, 2);
        if (W == 1) {
            mbar_arrive_warp_if(sb + BAR_XEMPTY + 0, 2, i == 3);
            mbar_arrive_warp_if(sb + BAR_XEMPTY + 8, 2, i == 3);
            mbar_arrive_warp_if(sb + BAR_XEMPTY + 16, 2, i == 3);
        }
        r.adv(W == 1 && i == 3 ? 1 : 2);
        TS(W, 5 + 5 * i);
        tail(true, i);
    }
    if (W == 0) {
        const uint32_t tid = threadIdx.x & 127;
        float2 v = make_float2(0.f, 0.f);
        auto gather = [&]() {
            if (tid < 80) {
#pragma unroll
                for (int i = 0; i < 4; i++) {
                    const float2 u = lds_f2(sb + OFF_LX + i * 640 + tid * 8);
                    v.x += u.x;
                    v.y += u.y;
                }
            }
        };
#pragma unroll
        for (int i = 0; i < 5; i++) sts_f(lxa + i * 64, l[i]);
        nb_sync<NB_W, 128>();
        gather();
        nb_arrive<NB_LX, 256>();
        wg_wait<0>();
        mbar_arrive_warp(sb + BAR_REMPTY + r.slot * 8, 1);
        mbar_arrive_warp(sb + BAR_XEMPTY + 24, 1);
        r.adv(1);
        nb_sync<NB_PFULL + 1, 256>();
        pv(1);
        TS(W, 24);
        nb_sync<NB_L, 256>();
        gather();
        if (tid < 80) {
            sts_f2(sb + OFF_LINV + tid * 8, __fdividef(1.f, v.x), __fdividef(1.f, v.y));
            if (!(v.x >= 5.421010862e-20f && v.x <= 1.8446744e19f && v.y >= 5.421010862e-20f && v.y <= 1.8446744e19f))
                sts_u(sb + OFF_FB, 1);
        }
    }
    nb_sync<NB_VOTE, 256>();
    const bool any = __any_sync(0xffffffffu, lds_u(sb + OFF_FB) != 0);
    float2 sc[20];
#pragma unroll
    for (int t = 0; t < 20; t++) sc[t] = lds_f2(sb + OFF_LINV + (lane & 3) * 8 + t * 32);
    wg_wait<0>();
    reg_fence(oa);
    reg_fence(ob);
    mbar_arrive_warp(sb + BAR_REMPTY + r.slot * 8, 1);
    mbar_arrive_warp(sb + BAR_XEMPTY + 32, 1);
    r.adv(1);
    TS(W, 25);
#pragma unroll
    for (int g = 0; g < 5; g++) {
        opack(oa, g, sc + 4 * g, po.v + 8 * g);
        if (W == 0 && g >= 3) opack(ob, g - 3, sc + 4 * g, po.v + 40 + 8 * (g - 3));
        if (W == 1 && g < 3) opack(ob, g, sc + 4 * g, po.v + 40 + 8 * g);
    }
    const uint32_t e = items[it];
    po.gp = g_ostash + (size_t)((IT_BR(e) * 16 + IT_B(e)) * 32 + IT_H0(e)) * OUNIT + w * 5120 + (lane >> 2) * 64 +
            (((lane ^ (lane >> 3)) & 3) << 4);
    po.pend = 1;
    if (any || IT_TYPE(items[it + 1]) != IT_QA) {
        if (!any) po.template flush<0>();
        else if (W == 1) fallback_unit(P, e, threadIdx.x & 127);
        nb_arrive<NB_ODONE, 288>();
        po.pend = 0;
    }
}

__global__ void __launch_bounds__(384, 1) fused_kernel(const __grid_constant__ Params P) {
    extern __shared__ __align__(1024) unsigned char smem_raw[];
    const uint32_t sb = (uint32_t)__cvta_generic_to_shared(smem_raw);
    const uint32_t wgid = __shfl_sync(0xffffffffu, threadIdx.x >> 7, 0);
    const uint32_t cta = blockIdx.x;
    const uint32_t* items = P.items[cta];

    uint32_t epoch = 0;
    if (wgid == 0) epoch = *(volatile unsigned int*)&g_epoch[cta] + 1;
    if (threadIdx.x == 0) {
        if (sb & 1023) __trap();
        for (int i = 0; i < NSLOT; i++) {
            mbar_init(sb + BAR_RFULL + i * 8, 1);
            mbar_init(sb + BAR_REMPTY + i * 8, 8);
            mbar_init(sb + BAR_XFULL + i * 8, 1);
            mbar_init(sb + BAR_XEMPTY + i * 8, 8);
        }
        asm volatile("fence.mbarrier_init.release.cluster;" ::: "memory");
        fence_async_smem();
    }
    __syncthreads();

    if (wgid == 0) {
        asm volatile("setmaxnreg.dec.sync.aligned.u32 24;");
        const uint32_t warp = __shfl_sync(0xffffffffu, threadIdx.x >> 5, 0);
        if (warp == 0) {
            if (threadIdx.x == 0) {
                *(volatile unsigned int*)&g_epoch[cta] = epoch;
                uint64_t pol_first, pol_norm;
                asm volatile("createpolicy.fractional.L2::evict_first.b64 %0, 1.0;" : "=l"(pol_first));
                asm volatile("createpolicy.fractional.L2::evict_normal.b64 %0, 1.0;" : "=l"(pol_norm));
                Ring r{0, 1};
                for (int it = 0; it < MAXI; it++) {
                    const uint32_t e = items[it];
                    if (e == 0) break;
                    const uint32_t br = IT_BR(e);
                    if (IT_TYPE(e) == IT_QA) {
                        const uint32_t h = IT_H0(e);
#pragma unroll 1
                        for (int kk = 0; kk < 10; kk++) {
                            mbar_wait(sb + BAR_REMPTY + r.slot * 8, r.ph);
                            mbar_expect(sb + BAR_RFULL + r.slot * 8, SLOT);
                            tma3(sb + OFF_RING + r.slot * SLOT, &P.wq[br], kk * 64, h * 3, sb + BAR_RFULL + r.slot * 8, pol_norm);
                            r.adv(1);
                        }
                        const int row0 = (IT_B(e) * 32 + h) * 512;
#pragma unroll 1
                        for (int n = 0; n < 16; n++) {
                            const bool isv = n == 15 || (n > 0 && !(n & 1));
                            const int j = n == 15 ? 7 : isv ? (n - 2) >> 1 : (n + 1) >> 1;
                            mbar_wait(sb + BAR_REMPTY + r.slot * 8, r.ph);
                            mbar_expect(sb + BAR_RFULL + r.slot * 8, SLOT);
                            tma3(sb + OFF_RING + r.slot * SLOT, isv ? &P.v[br] : &P.k[br], row0 + j * 64, 0,
                                 sb + BAR_RFULL + r.slot * 8, pol_first);
                            r.adv(1);
                        }
                    } else {
                        const int r0 = IT_H0(e) * 192, r1 = IT_H1(e) * 192;
#pragma unroll 1
                        for (int row = r0; row < r1; row += 32) {
                            mbar_wait(sb + BAR_REMPTY + r.slot * 8, r.ph);
                            mbar_expect(sb + BAR_RFULL + r.slot * 8, XS);
                            tma3(sb + OFF_RING + r.slot * SLOT, &P.wo[br], row, IT_HALF(e) * 5, sb + BAR_RFULL + r.slot * 8, pol_norm);
                            r.adv(1);
                        }
                    }
                }
            }
        } else if (warp == 1) {
            if (threadIdx.x == 32) {
                uint64_t pol_norm;
                asm volatile("createpolicy.fractional.L2::evict_normal.b64 %0, 1.0;" : "=l"(pol_norm));
                uint32_t phm = 0x1f;
                for (int it = 0; it < MAXI; it++) {
                    const uint32_t e = items[it];
                    if (e == 0) break;
                    const uint32_t br = IT_BR(e);
                    uint32_t xs = 0;
                    if (IT_TYPE(e) == IT_QA) {
#pragma unroll 1
                        for (int kk = 0; kk < 10; kk++) {
                            mbar_wait(sb + BAR_XEMPTY + xs * 8, (phm >> xs) & 1);
                            phm ^= 1u << xs;
                            mbar_expect(sb + BAR_XFULL + xs * 8, XS);
                            tma3(sb + OFF_R + xs * XS, &P.x[br], IT_B(e) * 160, kk, sb + BAR_XFULL + xs * 8, pol_norm);
                            if (++xs == 5) xs = 0;
                        }
                    } else {
                        const uint32_t u0 = (br * 16 + IT_B(e)) * 32;
#pragma unroll 1
                        for (uint32_t u = u0 + IT_H0(e); u < u0 + IT_H1(e); u++) {
                            uint32_t v, n = 0;
                            do {
                                asm volatile("ld.acquire.gpu.global.u32 %0, [%1];" : "=r"(v) : "l"(&g_flag[u]) : "memory");
                                if (++n > 0x400000) __trap();
                            } while (v != epoch);
                            asm volatile("fence.proxy.async;" ::: "memory");
#pragma unroll 1
                            for (int t = 0; t < 3; t++) {
                                mbar_wait(sb + BAR_XEMPTY + xs * 8, (phm >> xs) & 1);
                                phm ^= 1u << xs;
                                mbar_expect(sb + BAR_XFULL + xs * 8, XS);
                                bulk_load(sb + OFF_R + xs * XS, g_ostash + (size_t)u * OUNIT + t * XS, XS, sb + BAR_XFULL + xs * 8);
                                if (++xs == 5) xs = 0;
                            }
                        }
                    }
                }
            }
        } else if (warp == 2) {
#pragma unroll 1
            for (int it = 0; it < MAXI; it++) {
                const uint32_t e = items[it];
                if (e == 0) break;
                if (IT_TYPE(e) == IT_QA) {
                    nb_sync<NB_ODONE, 288>();
                    if (threadIdx.x == 64) {
                        __threadfence();
                        const uint32_t u = (IT_BR(e) * 16 + IT_B(e)) * 32 + IT_H0(e);
                        asm volatile("st.relaxed.gpu.global.u32 [%0], %1;" ::"l"(&g_flag[u]), "r"(epoch) : "memory");
                    }
                    __syncwarp();
                }
            }
        }
    } else if (wgid == 1) {
        asm volatile("setmaxnreg.inc.sync.aligned.u32 240;");
        PendO<0> po;
        po.clear();
        Ring r{0, 0};
        uint32_t phm = 0;
#pragma unroll 1
        for (int it = 0; it < MAXI; it++) {
            const uint32_t e = items[it];
            if (e == 0) break;
            TS(0, 0);
            if (IT_TYPE(e) == IT_QA) {
                qa_item<0>(P, items, sb, r, phm, po, it);
            } else {
                op_item<true>(P, e, sb, r, phm);
                po.clear();
            }
            TS(0, 31);
        }
        TS_DUMP(0);
    } else {
        asm volatile("setmaxnreg.inc.sync.aligned.u32 240;");
        PendO<1> po;
        po.clear();
        Ring r{0, 0};
        uint32_t phm = 0;
#pragma unroll 1
        for (int it = 0; it < MAXI; it++) {
            const uint32_t e = items[it];
            if (e == 0) break;
            TS(1, 0);
            if (IT_TYPE(e) == IT_QA) {
                qa_item<1>(P, items, sb, r, phm, po, it);
            } else {
                op_item<false>(P, e, sb, r, phm);
                po.clear();
            }
            TS(1, 31);
        }
        TS_DUMP(1);
    }
}

typedef CUresult (*EncFn)(CUtensorMap*, CUtensorMapDataType, cuuint32_t, void*, const cuuint64_t*, const cuuint64_t*,
                          const cuuint32_t*, const cuuint32_t*, CUtensorMapInterleave, CUtensorMapSwizzle,
                          CUtensorMapL2promotion, CUtensorMapFloatOOBfill);

void make_map3(EncFn enc, CUtensorMap* m, void* p, uint64_t rows, uint64_t rowbytes, uint64_t nblk, uint32_t boxrows,
               uint32_t boxblk) {
    cuuint64_t dims[3] = {64, rows, nblk};
    cuuint64_t str[2] = {rowbytes, 128};
    cuuint32_t box[3] = {64, boxrows, boxblk};
    cuuint32_t es[3] = {1, 1, 1};
    enc(m, CU_TENSOR_MAP_DATA_TYPE_BFLOAT16, 3, p, dims, str, box, es, CU_TENSOR_MAP_INTERLEAVE_NONE,
        CU_TENSOR_MAP_SWIZZLE_128B, CU_TENSOR_MAP_L2_PROMOTION_NONE, CU_TENSOR_MAP_FLOAT_OOB_FILL_NONE);
}

#define SCHED_MODE 0

void build_schedule(Params& P) {
    int n[NCTA];
    for (int c = 0; c < NCTA; c++) {
        n[c] = 0;
        for (int i = 0; i < MAXI; i++) P.items[c][i] = 0;
    }
    for (int u = 0; u < 1024; u++) {
        const int br = u >> 9, h = (u >> 4) & 31, b = u & 15;
        const int c = u % NCTA;
        if (SCHED_MODE == 2 && (c & 3)) continue;
        P.items[c][n[c]++] = mk_item(IT_QA, br, b, h, 0, 0);
    }
    if (SCHED_MODE == 0) {
        for (int t = 0; t < 64; t++) {
            const int c = NCTA - 1 - t;
            P.items[c][n[c]++] = mk_item(IT_OP, t >> 5, (t >> 1) & 15, 0, 32, t & 1);
        }
    }
}

}

extern "C" void kernel_launch(void* const* d_in, const int* in_sizes, int n_in, void* d_out, int out_size) {
    static Params P;
    static bool init = false;
    if (!init) {
        EncFn enc = nullptr;
        cudaDriverEntryPointQueryResult qr;
        cudaGetDriverEntryPoint("cuTensorMapEncodeTiled", (void**)&enc, cudaEnableDefault, &qr);
        for (int i = 0; i < 2; i++) {
            P.px[i] = (const __nv_bfloat16*)d_in[5 * i + 0];
            P.pk[i] = (const __nv_bfloat16*)d_in[5 * i + 1];
            P.pv[i] = (const __nv_bfloat16*)d_in[5 * i + 2];
            P.pwq[i] = (const __nv_bfloat16*)d_in[5 * i + 3];
            make_map3(enc, &P.x[i], d_in[5 * i + 0], 2560, 1280, 10, 160, 1);
            make_map3(enc, &P.k[i], d_in[5 * i + 1], 16 * 32 * 512, 384, 3, 64, 3);
            make_map3(enc, &P.v[i], d_in[5 * i + 2], 16 * 32 * 512, 384, 3, 64, 3);
            make_map3(enc, &P.wq[i], d_in[5 * i + 3], 640, 12288, 96, 64, 3);
            make_map3(enc, &P.wo[i], d_in[5 * i + 4], 6144, 1280, 10, 32, 5);
        }
        cuuint64_t dims[2] = {1280, 2560};
        cuuint64_t str[1] = {2560};
        cuuint32_t box[2] = {64, 160};
        cuuint32_t es[2] = {1, 1};
        enc(&P.out, CU_TENSOR_MAP_DATA_TYPE_BFLOAT16, 2, d_out, dims, str, box, es, CU_TENSOR_MAP_INTERLEAVE_NONE,
            CU_TENSOR_MAP_SWIZZLE_128B, CU_TENSOR_MAP_L2_PROMOTION_NONE, CU_TENSOR_MAP_FLOAT_OOB_FILL_NONE);
        build_schedule(P);
        cudaFuncSetAttribute(fused_kernel, cudaFuncAttributeMaxDynamicSharedMemorySize, SMEM_LAUNCH);
        init = true;
    }
    fused_kernel<<<NCTA, 384, SMEM_LAUNCH>>>(P);
}
```

```cpp
#include <cuda_runtime.h>
#include <cuda.h>
#include <cuda_bf16.h>
#include <stdint.h>

namespace {

constexpr int NCTA = 132;
constexpr int MAXI = 16;
constexpr int SLOT = 24576;
constexpr int NSLOT = 5;
constexpr int XS = 20480;
constexpr int OFF_R = 0;
constexpr int OFF_RING = 5 * XS;
constexpr int OFF_MISC = OFF_RING + NSLOT * SLOT;
constexpr int OFF_LX = OFF_MISC;
constexpr int OFF_LINV = OFF_LX + 2560;
constexpr int OFF_FB = OFF_LINV + 640;
constexpr int OFF_GM = OFF_FB + 16;
constexpr int OFF_BAR = OFF_GM + 16;
constexpr int BAR_RFULL = OFF_BAR;
constexpr int BAR_REMPTY = BAR_RFULL + 40;
constexpr int BAR_XFULL = BAR_REMPTY + 40;
constexpr int BAR_XEMPTY = BAR_XFULL + 40;
constexpr int SMEM_BYTES = BAR_XEMPTY + 40;
static_assert(SMEM_BYTES <= 232448, "smem");

constexpr int NB_W = 1  , NB_PFULL = 3  , NB_VOTE = 5, NB_Q01 = 6, NB_Q2 = 7, NB_SDONE = 8, NB_PDONE = 9,
              NB_L = 10, NB_OPST = 11, NB_ODONE = 12, NB_OPEND = 13, NB_LX = 14;

constexpr uint32_t IT_QA = 1, IT_OP = 2;
__host__ __device__ constexpr uint32_t mk_item(uint32_t type, uint32_t br, uint32_t b, uint32_t h0, uint32_t h1, uint32_t half) {
    return type | (br << 2) | (b << 3) | (h0 << 7) | (h1 << 13) | (half << 19);
}
#define IT_TYPE(e) ((e) & 3u)
#define IT_BR(e) (((e) >> 2) & 1u)
#define IT_B(e) (((e) >> 3) & 15u)
#define IT_H0(e) (((e) >> 7) & 63u)
#define IT_H1(e) (((e) >> 13) & 63u)
#define IT_HALF(e) (((e) >> 19) & 1u)

struct Params {
    CUtensorMap x[2], wq[2], k[2], v[2], wo[2], out;
    const __nv_bfloat16 *px[2], *pwq[2], *pk[2], *pv[2];
    uint32_t items[NCTA][MAXI];
};

constexpr int OUNIT = 61440;
__device__ __align__(1024) unsigned char g_ostash[(size_t)1024 * OUNIT];
__device__ unsigned int g_flag[1024];
__device__ unsigned int g_epoch[NCTA];

constexpr int SMEM_LAUNCH = SMEM_BYTES;
#define TS(role, idx)
#define TS_DUMP(role)
#define TS2(cond, idx)

#define POL_W 0
#define POL_X 0
#define POL_O 0
template <int M>
__device__ __forceinline__ uint64_t mkpol() {
    uint64_t p;
    if (M == 0) asm volatile("createpolicy.fractional.L2::evict_normal.b64 %0, 1.0;" : "=l"(p));
    if (M == 1) asm volatile("createpolicy.fractional.L2::evict_first.b64 %0, 1.0;" : "=l"(p));
    if (M == 2) asm volatile("createpolicy.fractional.L2::evict_unchanged.b64 %0, 1.0;" : "=l"(p));
    if (M == 3) asm volatile("createpolicy.fractional.L2::evict_normal.L2::evict_unchanged.b64 %0, 0.25;" : "=l"(p));
    return p;
}
#define QHOLD 7
constexpr float SM_C = 0.07216878364870322f * 1.4426950408889634f;

__device__ __forceinline__ void mbar_init(uint32_t a, uint32_t c) {
    asm volatile("mbarrier.init.shared::cta.b64 [%0], %1;" ::"r"(a), "r"(c) : "memory");
}
__device__ __forceinline__ void mbar_expect(uint32_t a, uint32_t b) {
    asm volatile("mbarrier.arrive.expect_tx.shared::cta.b64 _, [%0], %1;" ::"r"(a), "r"(b) : "memory");
}
__device__ __forceinline__ void mbar_arrive_warp(uint32_t a, uint32_t cnt) {
    asm volatile(
        "{\n.reg .pred p;\nelect.sync _|p, 0xffffffff;\n"
        "@p mbarrier.arrive.shared::cta.b64 _, [%0], %1;\n}" ::"r"(a), "r"(cnt)
        : "memory");
}
__device__ __forceinline__ void mbar_arrive_warp_if(uint32_t a, uint32_t cnt, bool cond) {
    asm volatile(
        "{\n.reg .pred p, c;\nelect.sync _|p, 0xffffffff;\nsetp.ne.and.u32 c, %2, 0, p;\n"
        "@c mbarrier.arrive.shared::cta.b64 _, [%0], %1;\n}" ::"r"(a), "r"(cnt), "r"((uint32_t)cond)
        : "memory");
}
__device__ __forceinline__ void mbar_wait(uint32_t a, uint32_t ph) {
    asm volatile(
        "{\n.reg .pred p;\n.reg .u32 n, m;\n"
        "mbarrier.try_wait.parity.shared::cta.b64 p, [%0], %1;\n"
        "@p bra DONE;\n"
        "mov.u32 n, %%clock_hi;\n"
        "LOOP:\n"
        "mbarrier.try_wait.parity.shared::cta.b64 p, [%0], %1;\n"
        "@p bra DONE;\n"
        "mov.u32 m, %%clock_hi;\n"
        "sub.u32 m, m, n;\n"
        "setp.lt.u32 p, m, 2;\n"
        "@p bra LOOP;\n"
        "trap;\n"
        "DONE:\n}" ::"r"(a), "r"(ph)
        : "memory");
}
template <int ID, int CNT>
__device__ __forceinline__ void nb_sync() { asm volatile("bar.sync %0, %1;" ::"n"(ID), "n"(CNT) : "memory"); }
template <int ID, int CNT>
__device__ __forceinline__ void nb_arrive() { asm volatile("bar.arrive %0, %1;" ::"n"(ID), "n"(CNT) : "memory"); }
__device__ __forceinline__ void fence_async_smem() { asm volatile("fence.proxy.async.shared::cta;" ::: "memory"); }

__device__ __forceinline__ void tma3(uint32_t dst, const CUtensorMap* m, int c1, int c2, uint32_t bar, uint64_t pol) {
    asm volatile(
        "cp.async.bulk.tensor.3d.shared::cluster.global.mbarrier::complete_tx::bytes.L2::cache_hint [%0], [%1, {%3,%4,%5}], [%2], %6;" ::"r"(dst),
        "l"(m), "r"(bar), "r"(0), "r"(c1), "r"(c2), "l"(pol)
        : "memory");
}
__device__ __forceinline__ void bulk_load(uint32_t dst, const void* src, uint32_t bytes, uint32_t bar, uint64_t pol) {
    asm volatile("cp.async.bulk.shared::cluster.global.mbarrier::complete_tx::bytes.L2::cache_hint [%0], [%1], %2, [%3], %4;" ::"r"(dst),
                 "l"(src), "r"(bytes), "r"(bar), "l"(pol)
                 : "memory");
}
__device__ __forceinline__ void wg_fence() { asm volatile("wgmma.fence.sync.aligned;" ::: "memory"); }
__device__ __forceinline__ void wg_commit() { asm volatile("wgmma.commit_group.sync.aligned;" ::: "memory"); }
template <int N>
__device__ __forceinline__ void wg_wait() { asm volatile("wgmma.wait_group.sync.aligned %0;" ::"n"(N) : "memory"); }

#define RW80(c, d) c(d[0]), c(d[1]), c(d[2]), c(d[3]), c(d[4]), c(d[5]), c(d[6]), c(d[7]), c(d[8]), c(d[9]), c(d[10]), c(d[11]), c(d[12]), c(d[13]), c(d[14]), c(d[15]), c(d[16]), c(d[17]), c(d[18]), c(d[19]), c(d[20]), c(d[21]), c(d[22]), c(d[23]), c(d[24]), c(d[25]), c(d[26]), c(d[27]), c(d[28]), c(d[29]), c(d[30]), c(d[31]), c(d[32]), c(d[33]), c(d[34]), c(d[35]), c(d[36]), c(d[37]), c(d[38]), c(d[39]), c(d[40]), c(d[41]), c(d[42]), c(d[43]), c(d[44]), c(d[45]), c(d[46]), c(d[47]), c(d[48]), c(d[49]), c(d[50]), c(d[51]), c(d[52]), c(d[53]), c(d[54]), c(d[55]), c(d[56]), c(d[57]), c(d[58]), c(d[59]), c(d[60]), c(d[61]), c(d[62]), c(d[63]), c(d[64]), c(d[65]), c(d[66]), c(d[67]), c(d[68]), c(d[69]), c(d[70]), c(d[71]), c(d[72]), c(d[73]), c(d[74]), c(d[75]), c(d[76]), c(d[77]), c(d[78]), c(d[79])
#define RW48(c, d) c(d[0]), c(d[1]), c(d[2]), c(d[3]), c(d[4]), c(d[5]), c(d[6]), c(d[7]), c(d[8]), c(d[9]), c(d[10]), c(d[11]), c(d[12]), c(d[13]), c(d[14]), c(d[15]), c(d[16]), c(d[17]), c(d[18]), c(d[19]), c(d[20]), c(d[21]), c(d[22]), c(d[23]), c(d[24]), c(d[25]), c(d[26]), c(d[27]), c(d[28]), c(d[29]), c(d[30]), c(d[31]), c(d[32]), c(d[33]), c(d[34]), c(d[35]), c(d[36]), c(d[37]), c(d[38]), c(d[39]), c(d[40]), c(d[41]), c(d[42]), c(d[43]), c(d[44]), c(d[45]), c(d[46]), c(d[47])
#define RW32(c, d) c(d[0]), c(d[1]), c(d[2]), c(d[3]), c(d[4]), c(d[5]), c(d[6]), c(d[7]), c(d[8]), c(d[9]), c(d[10]), c(d[11]), c(d[12]), c(d[13]), c(d[14]), c(d[15]), c(d[16]), c(d[17]), c(d[18]), c(d[19]), c(d[20]), c(d[21]), c(d[22]), c(d[23]), c(d[24]), c(d[25]), c(d[26]), c(d[27]), c(d[28]), c(d[29]), c(d[30]), c(d[31])

__device__ __forceinline__ void reg_fence(float (&d)[80]) { asm volatile("" : RW80("+f", d)::"memory"); }
__device__ __forceinline__ void reg_fence(float (&d)[48]) { asm volatile("" : RW48("+f", d)::"memory"); }
__device__ __forceinline__ void reg_fence(float (&d)[32]) { asm volatile("" : RW32("+f", d)::"memory"); }

constexpr uint32_t HI_SW128 = (1024u >> 4) | (1u << 30);
constexpr uint32_t HI_OST = (2560u >> 4) | (2u << 30);
constexpr uint32_t LO_LBO1 = (1u << 16);
constexpr uint32_t LO_OST = ((512u >> 4) << 16);

template <int TA, int TB, uint32_t HIB, bool ACC>
__device__ __forceinline__ void wgmma(float (&d)[80], uint32_t loA, uint32_t loB) {
#define WG_ASM(SD)                                                          \
    "{\n.reg .b64 da, db;\nmov.b64 da, {%80, %82};\nmov.b64 db, {%81, %83};\n" \
    "wgmma.mma_async.sync.aligned.m64n160k16.f32.bf16.bf16 "               \
    "{%0,%1,%2,%3,%4,%5,%6,%7,%8,%9,%10,%11,%12,%13,%14,%15,%16,%17,%18,%19,%20,%21,%22,%23,%24,%25,%26,%27,%28,%29,%30,%31,%32,%33,%34,%35,%36,%37,%38,%39,%40,%41,%42,%43,%44,%45,%46,%47,%48,%49,%50,%51,%52,%53,%54,%55,%56,%57,%58,%59,%60,%61,%62,%63,%64,%65,%66,%67,%68,%69,%70,%71,%72,%73,%74,%75,%76,%77,%78,%79}, da, db, " SD ", 1, 1, %84, %85;\n}"
    if constexpr (ACC)
        asm volatile(WG_ASM("1") : RW80("+f", d) : "r"(loA), "r"(loB), "n"(HI_SW128), "n"(HIB), "n"(TA), "n"(TB));
    else
        asm volatile(WG_ASM("0") : RW80("=f", d) : "r"(loA), "r"(loB), "n"(HI_SW128), "n"(HIB), "n"(TA), "n"(TB));
#undef WG_ASM
}
template <int TA, int TB, uint32_t HIB, bool ACC>
__device__ __forceinline__ void wgmma(float (&d)[48], uint32_t loA, uint32_t loB) {
#define WG_ASM(SD)                                                          \
    "{\n.reg .b64 da, db;\nmov.b64 da, {%48, %50};\nmov.b64 db, {%49, %51};\n" \
    "wgmma.mma_async.sync.aligned.m64n96k16.f32.bf16.bf16 "               \
    "{%0,%1,%2,%3,%4,%5,%6,%7,%8,%9,%10,%11,%12,%13,%14,%15,%16,%17,%18,%19,%20,%21,%22,%23,%24,%25,%26,%27,%28,%29,%30,%31,%32,%33,%34,%35,%36,%37,%38,%39,%40,%41,%42,%43,%44,%45,%46,%47}, da, db, " SD ", 1, 1, %52, %53;\n}"
    if constexpr (ACC)
        asm volatile(WG_ASM("1") : RW48("+f", d) : "r"(loA), "r"(loB), "n"(HI_SW128), "n"(HIB), "n"(TA), "n"(TB));
    else
        asm volatile(WG_ASM("0") : RW48("=f", d) : "r"(loA), "r"(loB), "n"(HI_SW128), "n"(HIB), "n"(TA), "n"(TB));
#undef WG_ASM
}
template <int TA, int TB, uint32_t HIB, bool ACC>
__device__ __forceinline__ void wgmma(float (&d)[32], uint32_t loA, uint32_t loB) {
#define WG_ASM(SD)                                                          \
    "{\n.reg .b64 da, db;\nmov.b64 da, {%32, %34};\nmov.b64 db, {%33, %35};\n" \
    "wgmma.mma_async.sync.aligned.m64n64k16.f32.bf16.bf16 "               \
    "{%0,%1,%2,%3,%4,%5,%6,%7,%8,%9,%10,%11,%12,%13,%14,%15,%16,%17,%18,%19,%20,%21,%22,%23,%24,%25,%26,%27,%28,%29,%30,%31}, da, db, " SD ", 1, 1, %36, %37;\n}"
    if constexpr (ACC)
        asm volatile(WG_ASM("1") : RW32("+f", d) : "r"(loA), "r"(loB), "n"(HI_SW128), "n"(HIB), "n"(TA), "n"(TB));
    else
        asm volatile(WG_ASM("0") : RW32("=f", d) : "r"(loA), "r"(loB), "n"(HI_SW128), "n"(HIB), "n"(TA), "n"(TB));
#undef WG_ASM
}

__device__ __forceinline__ uint32_t pack_bf16(float lo, float hi) {
    uint32_t r;
    asm("cvt.rn.bf16x2.f32 %0, %1, %2;" : "=r"(r) : "f"(hi), "f"(lo));
    return r;
}
__device__ __forceinline__ float ex2(float x) {
    float r;
    asm("ex2.approx.ftz.f32 %0, %1;" : "=f"(r) : "f"(x));
    return r;
}
__device__ __forceinline__ void stsm4t(uint32_t a, uint32_t r0, uint32_t r1, uint32_t r2, uint32_t r3) {
    asm volatile("stmatrix.sync.aligned.m8n8.x4.trans.shared.b16 [%0], {%1,%2,%3,%4};" ::"r"(a), "r"(r0), "r"(r1), "r"(r2), "r"(r3)
                 : "memory");
}
__device__ __forceinline__ uint32_t lds_u(uint32_t a) {
    uint32_t v;
    asm volatile("ld.shared.u32 %0, [%1];" : "=r"(v) : "r"(a) : "memory");
    return v;
}
__device__ __forceinline__ float2 lds_f2(uint32_t a) {
    float2 v;
    asm volatile("ld.shared.v2.f32 {%0,%1}, [%2];" : "=f"(v.x), "=f"(v.y) : "r"(a) : "memory");
    return v;
}
__device__ __forceinline__ void sts_f(uint32_t a, float v) { asm volatile("st.shared.f32 [%0], %1;" ::"r"(a), "f"(v) : "memory"); }
__device__ __forceinline__ void sts_u(uint32_t a, uint32_t v) { asm volatile("st.shared.u32 [%0], %1;" ::"r"(a), "r"(v) : "memory"); }
__device__ __forceinline__ void sts_f2(uint32_t a, float x, float y) {
    asm volatile("st.shared.v2.f32 [%0], {%1,%2};" ::"r"(a), "f"(x), "f"(y) : "memory");
}

__device__ __forceinline__ void store_tile_t(const float (&d)[80], uint32_t addr) {
#pragma unroll
    for (int j = 0; j < 10; j++)
        stsm4t(addr + j * 2048, pack_bf16(d[8 * j], d[8 * j + 1]), pack_bf16(d[8 * j + 2], d[8 * j + 3]),
               pack_bf16(d[8 * j + 4], d[8 * j + 5]), pack_bf16(d[8 * j + 6], d[8 * j + 7]));
}
template <int NR>
__device__ __forceinline__ void store_out_tile(const float (&d)[NR], uint32_t base, uint32_t lane, uint32_t w) {
    const uint32_t mi = lane >> 3, i = lane & 7;
    const uint32_t chunk = 2 * w + (mi & 1);
    const uint32_t q0 = 8 * (i >> 1) + 2 * (mi >> 1) + (i & 1);
    const uint32_t a0 = base + q0 * 128 + ((chunk ^ (q0 & 7)) << 4);
    const uint32_t a1 = base + (q0 + 4) * 128 + ((chunk ^ ((q0 + 4) & 7)) << 4);
#pragma unroll
    for (int j = 0; j < NR / 8; j++)
        stsm4t(((j & 1) ? a1 : a0) + (j >> 1) * 4096, pack_bf16(d[8 * j], d[8 * j + 1]), pack_bf16(d[8 * j + 2], d[8 * j + 3]),
               pack_bf16(d[8 * j + 4], d[8 * j + 5]), pack_bf16(d[8 * j + 6], d[8 * j + 7]));
}

struct TrueT { static constexpr bool value = true; };
struct FalseT { static constexpr bool value = false; };

template <int V>
struct IntT { static constexpr int value = V; };

struct Ring {
    uint32_t slot, ph;
    __device__ __forceinline__ void adv(uint32_t k) {
        slot += k;
        if (slot >= NSLOT) { slot -= NSLOT; ph ^= 1; }
    }
};

template <int K>
__device__ __forceinline__ void qk_step(float (&s)[80], uint32_t loK, uint32_t loQ) {
    wgmma<0, 0, HI_SW128, K != 0>(s, loK + (K >> 2) * (8192 >> 4) + (K & 3) * 2, loQ + (K >> 2) * (XS >> 4) + (K & 3) * 2);
}
template <int K0, int K1>
__device__ __forceinline__ void qk_steps(float (&s)[80], uint32_t loK, uint32_t loQ) {
    if constexpr (K0 < K1) {
        qk_step<K0>(s, loK, loQ);
        qk_steps<K0 + 1, K1>(s, loK, loQ);
    }
}
template <int J>
__device__ __forceinline__ void exp_chunk(const float (&s)[80], float (&ps)[40], uint32_t pa, float mref) {
    float p[8];
#pragma unroll
    for (int i = 0; i < 8; i++) p[i] = ex2(fmaf(s[8 * J + i], SM_C, -mref));
    stsm4t(pa + J * 2048, pack_bf16(p[0], p[1]), pack_bf16(p[2], p[3]), pack_bf16(p[4], p[5]), pack_bf16(p[6], p[7]));
    ps[4 * J] = p[0] + p[2];
    ps[4 * J + 1] = p[1] + p[3];
    ps[4 * J + 2] = p[4] + p[6];
    ps[4 * J + 3] = p[5] + p[7];
}
template <int J>
__device__ __forceinline__ void exp_block(const float (&s)[80], float (&ps)[40], uint32_t pa, float mref) {
    if constexpr (J < 10) {
        exp_chunk<J>(s, ps, pa, mref);
        exp_block<J + 1>(s, ps, pa, mref);
    }
}
__device__ __forceinline__ void sum_block(const float (&ps)[40], float (&l)[5], uint32_t lane) {
    const bool b4 = lane & 16, b3 = lane & 8, b2 = lane & 4;
    float t[20];
#pragma unroll
    for (int j = 0; j < 10; j++) {
        t[2 * j] = (b4 ? ps[4 * j + 2] : ps[4 * j]) + __shfl_xor_sync(0xffffffffu, b4 ? ps[4 * j] : ps[4 * j + 2], 16);
        t[2 * j + 1] = (b4 ? ps[4 * j + 3] : ps[4 * j + 1]) + __shfl_xor_sync(0xffffffffu, b4 ? ps[4 * j + 1] : ps[4 * j + 3], 16);
    }
#pragma unroll
    for (int i = 0; i < 10; i++) t[i] = (b3 ? t[i + 10] : t[i]) + __shfl_xor_sync(0xffffffffu, b3 ? t[i] : t[i + 10], 8);
#pragma unroll
    for (int i = 0; i < 5; i++)
        l[i] += (b2 ? t[2 * i + 1] : t[2 * i]) + __shfl_xor_sync(0xffffffffu, b2 ? t[2 * i] : t[2 * i + 1], 4);
}

__device__ __forceinline__ void fallback_unit(const Params& P, uint32_t e, uint32_t tid) {
    const uint32_t lane = tid & 31, br = IT_BR(e), b = IT_B(e), h = IT_H0(e);
    const uint32_t u = (br * 16 + b) * 32 + h;
    const __nv_bfloat162* wq = (const __nv_bfloat162*)(P.pwq[br] + h * 192) + lane;
    const __nv_bfloat162* kp = (const __nv_bfloat162*)(P.pk[br] + (size_t)(b * 32 + h) * 512 * 192) + lane;
    const __nv_bfloat162* vp = (const __nv_bfloat162*)(P.pv[br] + (size_t)(b * 32 + h) * 512 * 192) + lane;
#pragma unroll 1
    for (uint32_t q = tid >> 5; q < 160; q += 4) {
        const __nv_bfloat16* xr = P.px[br] + (size_t)(b * 160 + q) * 640;
        float a[6] = {0.f, 0.f, 0.f, 0.f, 0.f, 0.f};
#pragma unroll 4
        for (int k = 0; k < 640; k++) {
            const float xv = __bfloat162float(xr[k]);
#pragma unroll
            for (int i = 0; i < 3; i++) {
                const float2 wv = __bfloat1622float2(wq[(size_t)k * 3072 + i * 32]);
                a[2 * i] = fmaf(xv, wv.x, a[2 * i]);
                a[2 * i + 1] = fmaf(xv, wv.y, a[2 * i + 1]);
            }
        }
#pragma unroll
        for (int i = 0; i < 6; i++) a[i] = __bfloat162float(__float2bfloat16(a[i]));
        auto score = [&](int key) {
            float d = 0.f;
#pragma unroll
            for (int i = 0; i < 3; i++) {
                const float2 kv = __bfloat1622float2(kp[key * 96 + i * 32]);
                d = fmaf(a[2 * i], kv.x, fmaf(a[2 * i + 1], kv.y, d));
            }
#pragma unroll
            for (int o = 16; o > 0; o >>= 1) d += __shfl_xor_sync(0xffffffffu, d, o);
            return d;
        };
        float m = -INFINITY;
#pragma unroll 4
        for (int key = 0; key < 512; key++) m = fmaxf(m, score(key));
        float o[6] = {0.f, 0.f, 0.f, 0.f, 0.f, 0.f}, sum = 0.f;
#pragma unroll 4
        for (int key = 0; key < 512; key++) {
            const float p = ex2((score(key) - m) * SM_C);
            sum += p;
#pragma unroll
            for (int i = 0; i < 3; i++) {
                const float2 vv = __bfloat1622float2(vp[key * 96 + i * 32]);
                o[2 * i] = fmaf(p, vv.x, o[2 * i]);
                o[2 * i + 1] = fmaf(p, vv.y, o[2 * i + 1]);
            }
        }
        const float inv = 1.f / sum;
        __nv_bfloat16* op = (__nv_bfloat16*)(g_ostash + (size_t)u * OUNIT) + (q >> 5) * 256 + 2 * ((q & 31) >> 3) + (q & 1);
#pragma unroll
        for (int i = 0; i < 6; i++) {
            const uint32_t d = (i >> 1) * 64 + 2 * lane + (i & 1);
            op[(d >> 3) * 1280 + (d & 7) * 32 + ((((q & 7) >> 1) ^ ((d & 7) >> 1)) << 3)] = __float2bfloat16(o[i] * inv);
        }
    }
}

template <int W>
struct PendO {
    static constexpr int N = W == 0 ? 14 : 16;
    uint32_t v[4 * N];
    unsigned char* gp;
    uint32_t pend;
    template <int I>
    __device__ __forceinline__ void store() const {
        if constexpr (I < N) {
            constexpr int g = I < 10 ? I / 2 : (I - 10) / 2 + (W == 0 ? 3 : 0);
            constexpr int off = (I < 10 ? W : 2) * XS + g * 512 + (I & 1) * 2560;
            asm volatile(
                "{\n.reg .pred p;\nsetp.ne.u32 p, %6, 0;\n@p st.global.v4.b32 [%0+%5], {%1,%2,%3,%4};\n}" ::"l"(gp),
                "r"(v[4 * I]), "r"(v[4 * I + 1]), "r"(v[4 * I + 2]), "r"(v[4 * I + 3]), "n"(off), "r"(pend)
                : "memory");
        }
    }
    template <int I>
    __device__ __forceinline__ void flush() const {
        if constexpr (I < N) {
            store<I>();
            flush<I + 1>();
        }
    }
    __device__ __forceinline__ void clear() {
#pragma unroll
        for (int i = 0; i < 4 * N; i++) v[i] = 0;
        gp = nullptr;
        pend = 0;
    }
};

template <int W, int KK>
__device__ __forceinline__ void qproj(float (&q0)[80], float (&q1)[80], uint32_t sb, Ring& r, uint32_t phm, const PendO<W>& po) {
    const uint32_t loR = ((sb + OFF_R) >> 4) | LO_LBO1;
    const uint32_t loRing = ((sb + OFF_RING) >> 4) | LO_LBO1;
    constexpr int xs = KK % 5;
    const uint32_t pslot = r.slot;
    if (KK > 0) r.adv(1);
    if (W == 1 && KK == QHOLD) nb_sync<NB_SDONE, 256>();
    mbar_wait(sb + BAR_RFULL + r.slot * 8, r.ph);
    mbar_wait(sb + BAR_XFULL + xs * 8, ((phm >> xs) ^ (KK / 5)) & 1);
    const uint32_t a = loRing + r.slot * (SLOT >> 4) + (W == 0 ? 0 : 1024), b = loR + xs * (XS >> 4);
    wg_fence();
    wgmma<1, 0, HI_SW128, KK != 0>(q0, a, b);
    if (W == 0) wgmma<1, 0, HI_SW128, KK != 0>(q1, a + 512, b);
#pragma unroll
    for (int k = 1; k < 4; k++) {
        wgmma<1, 0, HI_SW128, true>(q0, a + k * 128, b + k * 2);
        if (W == 0) wgmma<1, 0, HI_SW128, true>(q1, a + 512 + k * 128, b + k * 2);
    }
    wg_commit();
    if (KK > 0) {
        wg_wait<1>();
        mbar_arrive_warp(sb + BAR_REMPTY + pslot * 8, 1);
        if (KK <= 5) mbar_arrive_warp(sb + (BAR_XEMPTY + (KK - 1) * 8), 1);
        if (W == 1 && KK == 7) nb_arrive<NB_PDONE, 256>();
    }
    if (KK < 6) {
        po.template store<3 * KK>();
        po.template store<3 * KK + 1>();
        po.template store<3 * KK + 2>();
        if (KK == 5 && po.pend) nb_arrive<NB_ODONE, 288>();
    }
    if constexpr (KK < 9) {
        qproj<W, KK + 1>(q0, q1, sb, r, phm, po);
    } else {
        if (W == 0) nb_arrive<NB_SDONE, 256>();
        wg_wait<0>();
        reg_fence(q0);
        if (W == 0) reg_fence(q1);
        mbar_arrive_warp(sb + BAR_REMPTY + r.slot * 8, 1);
        r.adv(1);
    }
}

template <int NR>
__device__ __forceinline__ void opack(const float (&o)[NR], int gl, const float2* sc, uint32_t* v) {
#pragma unroll
    for (int hh = 0; hh < 2; hh++)
#pragma unroll
        for (int t = 0; t < 4; t++)
            v[4 * hh + t] = pack_bf16(o[16 * gl + 4 * t + 2 * hh] * sc[t].x, o[16 * gl + 4 * t + 2 * hh + 1] * sc[t].y);
}

template <bool IS_S>
__device__ __forceinline__ void op_item(const Params& P, uint32_t e, uint32_t sb, Ring& r, uint32_t& phm) {
    constexpr int T0 = IS_S ? 0 : 2;
    constexpr uint32_t BOFF = IS_S ? (3 * 512) >> 4 : 0;
    const uint32_t loRing = ((sb + OFF_RING) >> 4) | LO_LBO1;
    const uint32_t loO = ((sb + OFF_R) >> 4) | LO_OST;
    float c0[80], c1[80], c2[IS_S ? 32 : 48];
    const int T2 = 6 * (IT_H1(e) - IT_H0(e));
    uint32_t xs = 0;
    auto step = [&](auto first, uint32_t hf) {
        constexpr bool F = decltype(first)::value;
        if (hf == 0) {
            mbar_wait(sb + BAR_XFULL + xs * 8, (phm >> xs) & 1);
            phm ^= 1u << xs;
        }
        mbar_wait(sb + BAR_RFULL + r.slot * 8, r.ph);
        const uint32_t a = loRing + r.slot * (SLOT >> 4), b = loO + xs * (XS >> 4) + hf * 640;
        wg_fence();
        wgmma<1, 1, HI_OST, !F>(c0, a + T0 * 256, b);
        wgmma<1, 1, HI_OST, !F>(c1, a + T0 * 256 + 256, b);
        wgmma<1, 1, HI_OST, !F>(c2, a + 1024, b + BOFF);
        wgmma<1, 1, HI_OST, true>(c0, a + T0 * 256 + 128, b + 320);
        wgmma<1, 1, HI_OST, true>(c1, a + T0 * 256 + 384, b + 320);
        wgmma<1, 1, HI_OST, true>(c2, a + 1024 + 128, b + 320 + BOFF);
        wg_commit();
    };
    step(TrueT{}, 0);
#pragma unroll 1
    for (int t = 1; t < T2; t++) {
        const uint32_t pslot = r.slot, pxs = xs;
        r.adv(1);
        if ((t & 1) == 0 && ++xs == 5) xs = 0;
        step(FalseT{}, t & 1);
        wg_wait<1>();
        mbar_arrive_warp(sb + BAR_REMPTY + pslot * 8, 1);
        if ((t & 1) == 0 && t + 8 < T2) mbar_arrive_warp(sb + BAR_XEMPTY + pxs * 8, 1);
    }
    wg_wait<0>();
    reg_fence(c0);
    reg_fence(c1);
    reg_fence(c2);
    mbar_arrive_warp(sb + BAR_REMPTY + r.slot * 8, 1);
    r.adv(1);
    nb_sync<NB_OPEND, 256>();
    const uint32_t lane = threadIdx.x & 31, w = (threadIdx.x >> 5) & 3;
    store_out_tile(c0, sb + OFF_R + T0 * XS, lane, w);
    store_out_tile(c1, sb + OFF_R + (T0 + 1) * XS, lane, w);
    store_out_tile(c2, sb + OFF_R + 4 * XS + (IS_S ? 96 * 128 : 0), lane, w);
    fence_async_smem();
    if (IS_S) {
        nb_arrive<NB_OPST, 256>();
    } else {
        nb_sync<NB_OPST, 256>();
        if ((threadIdx.x & 127) == 0) {
            const int cc0 = IT_BR(e) * 640 + IT_HALF(e) * 320;
#pragma unroll
            for (int m = 0; m < 5; m++)
                asm volatile("cp.async.bulk.tensor.2d.global.shared::cta.bulk_group [%0, {%2,%3}], [%1];" ::"l"(&P.out),
                             "r"(sb + OFF_R + m * XS), "r"(cc0 + m * 64), "r"((int)IT_B(e) * 160)
                             : "memory");
            asm volatile("cp.async.bulk.commit_group;" ::: "memory");
            asm volatile("cp.async.bulk.wait_group 0;" ::: "memory");
#pragma unroll
            for (int m = 0; m < 5; m++)
                asm volatile("mbarrier.arrive.shared::cta.b64 _, [%0], 8;" ::"r"(sb + BAR_XEMPTY + m * 8) : "memory");
        }
        __syncwarp();
    }
}

template <int W>
__device__ __forceinline__ void qa_item(const Params& P, const uint32_t* items, uint32_t sb, Ring& r, uint32_t phm, PendO<W>& po, int it) {
    const uint32_t loR = ((sb + OFF_R) >> 4) | LO_LBO1;
    const uint32_t loRing = ((sb + OFF_RING) >> 4) | LO_LBO1;
    const uint32_t lane = threadIdx.x & 31, w = (threadIdx.x >> 5) & 3;
    const uint32_t sta = sb + OFF_R + (lane >> 4) * 1024 + (lane & 7) * 128 + (((2 * w + ((lane >> 3) & 1)) ^ (lane & 7)) << 4);
    {
        float q0[80], q1[80];
        qproj<W, 0>(q0, q1, sb, r, phm, po);
        TS(W, 1);
        if (W == 0) {
            nb_sync<NB_PDONE, 256>();
            store_tile_t(q0, sta);
            store_tile_t(q1, sta + XS);
        } else {
            store_tile_t(q0, sta + 2 * XS);
        }
    }
    fence_async_smem();
    float s[80], oa[80], ob[W == 0 ? 32 : 48], l[5];
#pragma unroll
    for (int i = 0; i < 80; i++) oa[i] = 0.f;
#pragma unroll
    for (int i = 0; i < (W == 0 ? 32 : 48); i++) ob[i] = 0.f;
#pragma unroll
    for (int i = 0; i < 5; i++) l[i] = 0.f;
    reg_fence(oa);
    reg_fence(ob);
    auto pv = [&](uint32_t buf) {
        mbar_wait(sb + BAR_RFULL + r.slot * 8, r.ph);
        const uint32_t a = loRing + r.slot * (SLOT >> 4), b = loR + (3 + buf) * (XS >> 4);
        wg_fence();
#pragma unroll
        for (int k = 0; k < 4; k++) {
            wgmma<1, 0, HI_SW128, true>(oa, a + W * 512 + k * 128, b + k * 2);
            wgmma<1, 0, HI_SW128, true>(ob, a + 1024 + k * 128, b + (W == 0 ? (96 * 128) >> 4 : 0) + k * 2);
        }
        wg_commit();
    };
    float mref;
    uint32_t kslot, vslot;
    const uint32_t lxa = sb + OFF_LX + w * 640 + (((lane & 8) ? 80 : 0) + ((lane >> 1) & 8) + 2 * (lane & 3) + ((lane >> 2) & 1)) * 4;
    auto tail = [&](bool rel_other, int i) {
        float ps[40];
        exp_block<0>(s, ps, sta + (3 + W) * XS, mref);
        if (rel_other) {
            wg_wait<0>();
            mbar_arrive_warp(sb + BAR_REMPTY + vslot * 8, 1);
            if (W == 1) mbar_arrive_warp_if(sb + BAR_XEMPTY + 24, 1, i == 3);
        }
        fence_async_smem();
        nb_arrive<NB_PFULL + W, 256>();
        TS(W, 6 + 5 * i);
        mbar_wait(sb + BAR_RFULL + r.slot * 8, r.ph);
        sum_block(ps, l, lane);
        if (W == 1 && i == 3) {
            nb_sync<NB_LX, 256>();
#pragma unroll
            for (int k = 0; k < 5; k++) sts_f(lxa + k * 64, l[k]);
            nb_arrive<NB_L, 256>();
        }
        nb_sync<NB_W + W, 128>();
        TS(W, 7 + 5 * i);
        pv(W);
        TS(W, 8 + 5 * i);
    };
    if (W == 0) {
        nb_sync<NB_W, 128>();
        TS(W, 2);
        mbar_wait(sb + BAR_RFULL + r.slot * 8, r.ph);
        wg_fence();
        qk_steps<0, 8>(s, loRing + r.slot * (SLOT >> 4), loR);
        nb_sync<NB_Q2, 256>();
        qk_steps<8, 12>(s, loRing + r.slot * (SLOT >> 4), loR);
        wg_commit();
        nb_arrive<NB_Q01, 256>();
        TS(W, 4);
        wg_wait<0>();
        reg_fence(s);
        mbar_arrive_warp(sb + BAR_REMPTY + r.slot * 8, 2);
        r.adv(2);
        float m0 = fmaxf(s[0], s[5]), m1 = fmaxf(s[10], s[15]);
#pragma unroll
        for (int i = 20; i < 80; i += 10) {
            m0 = fmaxf(m0, s[i]);
            m1 = fmaxf(m1, s[i + 5]);
        }
        int key = __float_as_int(fmaxf(m0, m1));
        key ^= (key >> 31) & 0x7fffffff;
        key = __reduce_max_sync(0xffffffffu, key);
        key ^= (key >> 31) & 0x7fffffff;
        sts_u(sb + OFF_GM + w * 4, key);
        sts_u(sb + OFF_FB, 0);
        nb_sync<NB_W, 128>();
        const float2 u = lds_f2(sb + OFF_GM), v = lds_f2(sb + OFF_GM + 8);
        mref = fmaxf(fmaxf(u.x, u.y), fmaxf(v.x, v.y)) * SM_C;
        TS(W, 5);
        tail(false, 0);
    } else {
        nb_arrive<NB_Q2, 256>();
        TS(W, 2);
        nb_sync<NB_Q01, 256>();
    }
#pragma unroll 1
    for (int i = (W == 0 ? 1 : 0); i < 4; i++) {
        const uint32_t pvslot = r.slot;
        r.adv(1);
        kslot = r.slot;
        mbar_wait(sb + BAR_RFULL + r.slot * 8, r.ph);
        wg_fence();
        qk_steps<0, 12>(s, loRing + r.slot * (SLOT >> 4), loR);
        wg_commit();
        wg_wait<1>();
        mbar_arrive_warp_if(sb + BAR_REMPTY + pvslot * 8, 1, W == 0 || i > 0);
        r.adv(1);
        vslot = r.slot;
        TS(W, 4 + 5 * i);
        nb_sync<NB_PFULL + (W ^ 1), 256>();
        pv(W ^ 1);
        if (W == 1) {
            const float2 u = lds_f2(sb + OFF_GM), v = lds_f2(sb + OFF_GM + 8);
            mref = fmaxf(fmaxf(u.x, u.y), fmaxf(v.x, v.y)) * SM_C;
        }
        wg_wait<1>();
        reg_fence(s);
        mbar_arrive_warp(sb + BAR_REMPTY + kslot * 8, 2);
        if (W == 1) {
            mbar_arrive_warp_if(sb + BAR_XEMPTY + 0, 2, i == 3);
            mbar_arrive_warp_if(sb + BAR_XEMPTY + 8, 2, i == 3);
            mbar_arrive_warp_if(sb + BAR_XEMPTY + 16, 2, i == 3);
        }
        r.adv(W == 1 && i == 3 ? 1 : 2);
        TS(W, 5 + 5 * i);
        tail(true, i);
    }
    if (W == 0) {
        const uint32_t tid = threadIdx.x & 127;
        float2 v = make_float2(0.f, 0.f);
        auto gather = [&]() {
            if (tid < 80) {
#pragma unroll
                for (int i = 0; i < 4; i++) {
                    const float2 u = lds_f2(sb + OFF_LX + i * 640 + tid * 8);
                    v.x += u.x;
                    v.y += u.y;
                }
            }
        };
#pragma unroll
        for (int i = 0; i < 5; i++) sts_f(lxa + i * 64, l[i]);
        nb_sync<NB_W, 128>();
        gather();
        nb_arrive<NB_LX, 256>();
        wg_wait<0>();
        mbar_arrive_warp(sb + BAR_REMPTY + r.slot * 8, 1);
        mbar_arrive_warp(sb + BAR_XEMPTY + 24, 1);
        r.adv(1);
        nb_sync<NB_PFULL + 1, 256>();
        pv(1);
        TS(W, 24);
        nb_sync<NB_L, 256>();
        gather();
        if (tid < 80) {
            sts_f2(sb + OFF_LINV + tid * 8, __fdividef(1.f, v.x), __fdividef(1.f, v.y));
            if (!(v.x >= 5.421010862e-20f && v.x <= 1.8446744e19f && v.y >= 5.421010862e-20f && v.y <= 1.8446744e19f))
                sts_u(sb + OFF_FB, 1);
        }
    }
    nb_sync<NB_VOTE, 256>();
    const bool any = __any_sync(0xffffffffu, lds_u(sb + OFF_FB) != 0);
    float2 sc[20];
#pragma unroll
    for (int t = 0; t < 20; t++) sc[t] = lds_f2(sb + OFF_LINV + (lane & 3) * 8 + t * 32);
    wg_wait<0>();
    reg_fence(oa);
    reg_fence(ob);
    mbar_arrive_warp(sb + BAR_REMPTY + r.slot * 8, 1);
    mbar_arrive_warp(sb + BAR_XEMPTY + 32, 1);
    r.adv(1);
    TS(W, 25);
#pragma unroll
    for (int g = 0; g < 5; g++) {
        opack(oa, g, sc + 4 * g, po.v + 8 * g);
        if (W == 0 && g >= 3) opack(ob, g - 3, sc + 4 * g, po.v + 40 + 8 * (g - 3));
        if (W == 1 && g < 3) opack(ob, g, sc + 4 * g, po.v + 40 + 8 * g);
    }
    const uint32_t e = items[it];
    po.gp = g_ostash + (size_t)((IT_BR(e) * 16 + IT_B(e)) * 32 + IT_H0(e)) * OUNIT + w * 5120 + (lane >> 2) * 64 +
            (((lane ^ (lane >> 3)) & 3) << 4);
    po.pend = 1;
    if (any || IT_TYPE(items[it + 1]) != IT_QA) {
        if (!any) po.template flush<0>();
        else if (W == 1) fallback_unit(P, e, threadIdx.x & 127);
        nb_arrive<NB_ODONE, 288>();
        po.pend = 0;
    }
}

__global__ void __launch_bounds__(384, 1) fused_kernel(const __grid_constant__ Params P) {
    extern __shared__ __align__(1024) unsigned char smem_raw[];
    const uint32_t sb = (uint32_t)__cvta_generic_to_shared(smem_raw);
    const uint32_t wgid = __shfl_sync(0xffffffffu, threadIdx.x >> 7, 0);
    const uint32_t cta = blockIdx.x;
    const uint32_t* items = P.items[cta];

    uint32_t epoch = 0;
    if (wgid == 0) epoch = *(volatile unsigned int*)&g_epoch[cta] + 1;
    if (threadIdx.x == 0) {
        if (sb & 1023) __trap();
        for (int i = 0; i < NSLOT; i++) {
            mbar_init(sb + BAR_RFULL + i * 8, 1);
            mbar_init(sb + BAR_REMPTY + i * 8, 8);
            mbar_init(sb + BAR_XFULL + i * 8, 1);
            mbar_init(sb + BAR_XEMPTY + i * 8, 8);
        }
        asm volatile("fence.mbarrier_init.release.cluster;" ::: "memory");
        fence_async_smem();
    }
    __syncthreads();

    if (wgid == 0) {
        asm volatile("setmaxnreg.dec.sync.aligned.u32 24;");
        const uint32_t warp = __shfl_sync(0xffffffffu, threadIdx.x >> 5, 0);
        if (warp == 0) {
            if (threadIdx.x == 0) {
                *(volatile unsigned int*)&g_epoch[cta] = epoch;
                const uint64_t pol_first = mkpol<1>(), pol_norm = mkpol<POL_W>();
                Ring r{0, 1};
                for (int it = 0; it < MAXI; it++) {
                    const uint32_t e = items[it];
                    if (e == 0) break;
                    const uint32_t br = IT_BR(e);
                    if (IT_TYPE(e) == IT_QA) {
                        const uint32_t h = IT_H0(e);
#pragma unroll 1
                        for (int kk = 0; kk < 10; kk++) {
                            mbar_wait(sb + BAR_REMPTY + r.slot * 8, r.ph);
                            mbar_expect(sb + BAR_RFULL + r.slot * 8, SLOT);
                            tma3(sb + OFF_RING + r.slot * SLOT, &P.wq[br], kk * 64, h * 3, sb + BAR_RFULL + r.slot * 8, pol_norm);
                            r.adv(1);
                        }
                        const int row0 = (IT_B(e) * 32 + h) * 512;
#pragma unroll 1
                        for (int n = 0; n < 16; n++) {
                            const bool isv = n == 15 || (n > 0 && !(n & 1));
                            const int j = n == 15 ? 7 : isv ? (n - 2) >> 1 : (n + 1) >> 1;
                            mbar_wait(sb + BAR_REMPTY + r.slot * 8, r.ph);
                            mbar_expect(sb + BAR_RFULL + r.slot * 8, SLOT);
                            tma3(sb + OFF_RING + r.slot * SLOT, isv ? &P.v[br] : &P.k[br], row0 + j * 64, 0,
                                 sb + BAR_RFULL + r.slot * 8, pol_first);
                            r.adv(1);
                        }
                    } else {
                        const int r0 = IT_H0(e) * 192, r1 = IT_H1(e) * 192;
#pragma unroll 1
                        for (int row = r0; row < r1; row += 32) {
                            mbar_wait(sb + BAR_REMPTY + r.slot * 8, r.ph);
                            mbar_expect(sb + BAR_RFULL + r.slot * 8, XS);
                            tma3(sb + OFF_RING + r.slot * SLOT, &P.wo[br], row, IT_HALF(e) * 5, sb + BAR_RFULL + r.slot * 8, pol_norm);
                            r.adv(1);
                        }
                    }
                }
            }
        } else if (warp == 1) {
            if (threadIdx.x == 32) {
                const uint64_t pol_norm = mkpol<POL_X>(), pol_o = mkpol<POL_O>();
                uint32_t phm = 0x1f;
                for (int it = 0; it < MAXI; it++) {
                    const uint32_t e = items[it];
                    if (e == 0) break;
                    const uint32_t br = IT_BR(e);
                    uint32_t xs = 0;
                    if (IT_TYPE(e) == IT_QA) {
#pragma unroll 1
                        for (int kk = 0; kk < 10; kk++) {
                            mbar_wait(sb + BAR_XEMPTY + xs * 8, (phm >> xs) & 1);
                            phm ^= 1u << xs;
                            mbar_expect(sb + BAR_XFULL + xs * 8, XS);
                            tma3(sb + OFF_R + xs * XS, &P.x[br], IT_B(e) * 160, kk, sb + BAR_XFULL + xs * 8, pol_norm);
                            if (++xs == 5) xs = 0;
                        }
                    } else {
                        const uint32_t u0 = (br * 16 + IT_B(e)) * 32;
#pragma unroll 1
                        for (uint32_t u = u0 + IT_H0(e); u < u0 + IT_H1(e); u++) {
                            uint32_t v, n = 0;
                            do {
                                asm volatile("ld.acquire.gpu.global.u32 %0, [%1];" : "=r"(v) : "l"(&g_flag[u]) : "memory");
                                if (++n > 0x400000) __trap();
                            } while (v != epoch);
                            asm volatile("fence.proxy.async;" ::: "memory");
#pragma unroll 1
                            for (int t = 0; t < 3; t++) {
                                mbar_wait(sb + BAR_XEMPTY + xs * 8, (phm >> xs) & 1);
                                phm ^= 1u << xs;
                                mbar_expect(sb + BAR_XFULL + xs * 8, XS);
                                bulk_load(sb + OFF_R + xs * XS, g_ostash + (size_t)u * OUNIT + t * XS, XS, sb + BAR_XFULL + xs * 8, pol_o);
                                if (++xs == 5) xs = 0;
                            }
                        }
                    }
                }
            }
        } else if (warp == 2) {
#pragma unroll 1
            for (int it = 0; it < MAXI; it++) {
                const uint32_t e = items[it];
                if (e == 0) break;
                if (IT_TYPE(e) == IT_QA) {
                    nb_sync<NB_ODONE, 288>();
                    if (threadIdx.x == 64) {
                        __threadfence();
                        const uint32_t u = (IT_BR(e) * 16 + IT_B(e)) * 32 + IT_H0(e);
                        asm volatile("st.relaxed.gpu.global.u32 [%0], %1;" ::"l"(&g_flag[u]), "r"(epoch) : "memory");
                    }
                    __syncwarp();
                }
            }
        }
    } else if (wgid == 1) {
        asm volatile("setmaxnreg.inc.sync.aligned.u32 240;");
        PendO<0> po;
        po.clear();
        Ring r{0, 0};
        uint32_t phm = 0;
#pragma unroll 1
        for (int it = 0; it < MAXI; it++) {
            const uint32_t e = items[it];
            if (e == 0) break;
            TS(0, 0);
            if (IT_TYPE(e) == IT_QA) {
                qa_item<0>(P, items, sb, r, phm, po, it);
            } else {
                op_item<true>(P, e, sb, r, phm);
                po.clear();
            }
            TS(0, 31);
        }
        TS_DUMP(0);
    } else {
        asm volatile("setmaxnreg.inc.sync.aligned.u32 240;");
        PendO<1> po;
        po.clear();
        Ring r{0, 0};
        uint32_t phm = 0;
#pragma unroll 1
        for (int it = 0; it < MAXI; it++) {
            const uint32_t e = items[it];
            if (e == 0) break;
            TS(1, 0);
            if (IT_TYPE(e) == IT_QA) {
                qa_item<1>(P, items, sb, r, phm, po, it);
            } else {
                op_item<false>(P, e, sb, r, phm);
                po.clear();
            }
            TS(1, 31);
        }
        TS_DUMP(1);
    }
}

typedef CUresult (*EncFn)(CUtensorMap*, CUtensorMapDataType, cuuint32_t, void*, const cuuint64_t*, const cuuint64_t*,
                          const cuuint32_t*, const cuuint32_t*, CUtensorMapInterleave, CUtensorMapSwizzle,
                          CUtensorMapL2promotion, CUtensorMapFloatOOBfill);

void make_map3(EncFn enc, CUtensorMap* m, void* p, uint64_t rows, uint64_t rowbytes, uint64_t nblk, uint32_t boxrows,
               uint32_t boxblk) {
    cuuint64_t dims[3] = {64, rows, nblk};
    cuuint64_t str[2] = {rowbytes, 128};
    cuuint32_t box[3] = {64, boxrows, boxblk};
    cuuint32_t es[3] = {1, 1, 1};
    enc(m, CU_TENSOR_MAP_DATA_TYPE_BFLOAT16, 3, p, dims, str, box, es, CU_TENSOR_MAP_INTERLEAVE_NONE,
        CU_TENSOR_MAP_SWIZZLE_128B, CU_TENSOR_MAP_L2_PROMOTION_NONE, CU_TENSOR_MAP_FLOAT_OOB_FILL_NONE);
}

#define SCHED_MODE 0

void build_schedule(Params& P) {
    int n[NCTA];
    for (int c = 0; c < NCTA; c++) {
        n[c] = 0;
        for (int i = 0; i < MAXI; i++) P.items[c][i] = 0;
    }
    if (SCHED_MODE == 3) {
        int qa[NCTA], nq = 0, op[NCTA], no = 0;
        for (int c = 0; c < NCTA; c++) {
            if (c < 128 && (c & 3) == 3) op[no++] = c;
            else qa[nq++] = c;
        }
        int u = 0;
        auto put = [&](int c) {
            const int br = u >> 9, h = (u >> 4) & 31, b = u & 15;
            P.items[c][n[c]++] = mk_item(IT_QA, br, b, h, 0, 0);
            u++;
        };
        for (int c = 0; c < NCTA; c++) put(c);
        while (u < 1024)
            for (int i = 0; i < nq && u < 1024; i++) put(qa[i]);
        for (int br = 0; br < 2; br++)
            for (int t = 0; t < 32; t++) P.items[op[t]][n[op[t]]++] = mk_item(IT_OP, br, t >> 1, 0, 32, t & 1);
        return;
    }
    for (int u = 0; u < 1024; u++) {
        const int br = u >> 9, h = (u >> 4) & 31, b = u & 15;
        const int c = u % NCTA;
        if (SCHED_MODE == 2 && (c & 3)) continue;
        P.items[c][n[c]++] = mk_item(IT_QA, br, b, h, 0, 0);
    }
    if (SCHED_MODE == 0) {
        for (int t = 0; t < 64; t++) {
            const int c = NCTA - 1 - t;
            P.items[c][n[c]++] = mk_item(IT_OP, t >> 5, (t >> 1) & 15, 0, 32, t & 1);
        }
    }
}

}

extern "C" void kernel_launch(void* const* d_in, const int* in_sizes, int n_in, void* d_out, int out_size) {
    static Params P;
    static bool init = false;
    if (!init) {
        EncFn enc = nullptr;
        cudaDriverEntryPointQueryResult qr;
        cudaGetDriverEntryPoint("cuTensorMapEncodeTiled", (void**)&enc, cudaEnableDefault, &qr);
        for (int i = 0; i < 2; i++) {
            P.px[i] = (const __nv_bfloat16*)d_in[5 * i + 0];
            P.pk[i] = (const __nv_bfloat16*)d_in[5 * i + 1];
            P.pv[i] = (const __nv_bfloat16*)d_in[5 * i + 2];
            P.pwq[i] = (const __nv_bfloat16*)d_in[5 * i + 3];
            make_map3(enc, &P.x[i], d_in[5 * i + 0], 2560, 1280, 10, 160, 1);
            make_map3(enc, &P.k[i], d_in[5 * i + 1], 16 * 32 * 512, 384, 3, 64, 3);
            make_map3(enc, &P.v[i], d_in[5 * i + 2], 16 * 32 * 512, 384, 3, 64, 3);
            make_map3(enc, &P.wq[i], d_in[5 * i + 3], 640, 12288, 96, 64, 3);
            make_map3(enc, &P.wo[i], d_in[5 * i + 4], 6144, 1280, 10, 32, 5);
        }
        cuuint64_t dims[2] = {1280, 2560};
        cuuint64_t str[1] = {2560};
        cuuint32_t box[2] = {64, 160};
        cuuint32_t es[2] = {1, 1};
        enc(&P.out, CU_TENSOR_MAP_DATA_TYPE_BFLOAT16, 2, d_out, dims, str, box, es, CU_TENSOR_MAP_INTERLEAVE_NONE,
            CU_TENSOR_MAP_SWIZZLE_128B, CU_TENSOR_MAP_L2_PROMOTION_NONE, CU_TENSOR_MAP_FLOAT_OOB_FILL_NONE);
        build_schedule(P);
        cudaFuncSetAttribute(fused_kernel, cudaFuncAttributeMaxDynamicSharedMemorySize, SMEM_LAUNCH);
        init = true;
    }
    fused_kernel<<<NCTA, 384, SMEM_LAUNCH>>>(P);
}
```

```cpp
#include <cuda_runtime.h>
#include <cuda.h>
#include <cuda_bf16.h>
#include <stdint.h>

namespace {

constexpr int NCTA = 132;
constexpr int MAXI = 16;
constexpr int SLOT = 24576;
constexpr int NSLOT = 5;
constexpr int XS = 20480;
constexpr int OFF_R = 0;
constexpr int OFF_RING = 5 * XS;
constexpr int OFF_MISC = OFF_RING + NSLOT * SLOT;
constexpr int OFF_LX = OFF_MISC;
constexpr int OFF_LINV = OFF_LX + 2560;
constexpr int OFF_FB = OFF_LINV + 640;
constexpr int OFF_GM = OFF_FB + 16;
constexpr int OFF_BAR = OFF_GM + 16;
constexpr int BAR_RFULL = OFF_BAR;
constexpr int BAR_REMPTY = BAR_RFULL + 40;
constexpr int BAR_XFULL = BAR_REMPTY + 40;
constexpr int BAR_XEMPTY = BAR_XFULL + 40;
constexpr int SMEM_BYTES = BAR_XEMPTY + 40;
static_assert(SMEM_BYTES <= 232448, "smem");

constexpr int NB_W = 1  , NB_PFULL = 3  , NB_VOTE = 5, NB_Q01 = 6, NB_Q2 = 7, NB_SDONE = 8, NB_PDONE = 9,
              NB_L = 10, NB_OPST = 11, NB_ODONE = 12, NB_OPEND = 13, NB_LX = 14;

constexpr uint32_t IT_QA = 1, IT_OP = 2, IT_ON = 3;
__host__ __device__ constexpr uint32_t mk_item(uint32_t type, uint32_t br, uint32_t b, uint32_t h0, uint32_t h1, uint32_t half,
                                               uint32_t part = 0) {
    return type | (br << 2) | (b << 3) | (h0 << 7) | (h1 << 13) | (half << 19) | (part << 22);
}
#define IT_TYPE(e) ((e) & 3u)
#define IT_BR(e) (((e) >> 2) & 1u)
#define IT_B(e) (((e) >> 3) & 15u)
#define IT_H0(e) (((e) >> 7) & 63u)
#define IT_H1(e) (((e) >> 13) & 63u)
#define IT_HALF(e) (((e) >> 19) & 7u)
#define IT_PART(e) (((e) >> 22) & 1u)

struct Params {
    CUtensorMap x[2], wq[2], k[2], v[2], wo[2], won[2], out;
    const __nv_bfloat16 *px[2], *pwq[2], *pk[2], *pv[2];
    uint32_t items[NCTA][MAXI];
};

constexpr int OUNIT = 61440;
__device__ __align__(1024) unsigned char g_ostash[(size_t)1024 * OUNIT];
__device__ unsigned int g_flag[1024];
__device__ float4 g_part[2 * 16 * 10 * 2560];
__device__ unsigned int g_pflag[64];
#define ORING 64
__device__ __forceinline__ unsigned char* ostash(uint32_t br, uint32_t b, uint32_t h) {
    return g_ostash + (size_t)(((br * 32 + h) % ORING) * 16 + b) * OUNIT;
}
__device__ unsigned int g_epoch[NCTA];

constexpr int SMEM_LAUNCH = SMEM_BYTES;
#define TS(role, idx)
#define TS_DUMP(role)
#define TS2(cond, idx)

#define POL_W 2
#define POL_X 2
#define POL_O 2
template <int M>
__device__ __forceinline__ uint64_t mkpol() {
    uint64_t p;
    if (M == 0) asm volatile("createpolicy.fractional.L2::evict_normal.b64 %0, 1.0;" : "=l"(p));
    if (M == 1) asm volatile("createpolicy.fractional.L2::evict_first.b64 %0, 1.0;" : "=l"(p));
    if (M == 2) asm volatile("createpolicy.fractional.L2::evict_unchanged.b64 %0, 1.0;" : "=l"(p));
    if (M == 3) asm volatile("createpolicy.fractional.L2::evict_normal.L2::evict_unchanged.b64 %0, 0.25;" : "=l"(p));
    return p;
}
#define QHOLD 7
constexpr float SM_C = 0.07216878364870322f * 1.4426950408889634f;

__device__ __forceinline__ void mbar_init(uint32_t a, uint32_t c) {
    asm volatile("mbarrier.init.shared::cta.b64 [%0], %1;" ::"r"(a), "r"(c) : "memory");
}
__device__ __forceinline__ void mbar_expect(uint32_t a, uint32_t b) {
    asm volatile("mbarrier.arrive.expect_tx.shared::cta.b64 _, [%0], %1;" ::"r"(a), "r"(b) : "memory");
}
__device__ __forceinline__ void mbar_arrive_warp(uint32_t a, uint32_t cnt) {
    asm volatile(
        "{\n.reg .pred p;\nelect.sync _|p, 0xffffffff;\n"
        "@p mbarrier.arrive.shared::cta.b64 _, [%0], %1;\n}" ::"r"(a), "r"(cnt)
        : "memory");
}
__device__ __forceinline__ void mbar_arrive_warp_if(uint32_t a, uint32_t cnt, bool cond) {
    asm volatile(
        "{\n.reg .pred p, c;\nelect.sync _|p, 0xffffffff;\nsetp.ne.and.u32 c, %2, 0, p;\n"
        "@c mbarrier.arrive.shared::cta.b64 _, [%0], %1;\n}" ::"r"(a), "r"(cnt), "r"((uint32_t)cond)
        : "memory");
}
__device__ __forceinline__ void mbar_wait(uint32_t a, uint32_t ph) {
    asm volatile(
        "{\n.reg .pred p;\n.reg .u32 n, m;\n"
        "mbarrier.try_wait.parity.shared::cta.b64 p, [%0], %1;\n"
        "@p bra DONE;\n"
        "mov.u32 n, %%clock_hi;\n"
        "LOOP:\n"
        "mbarrier.try_wait.parity.shared::cta.b64 p, [%0], %1;\n"
        "@p bra DONE;\n"
        "mov.u32 m, %%clock_hi;\n"
        "sub.u32 m, m, n;\n"
        "setp.lt.u32 p, m, 2;\n"
        "@p bra LOOP;\n"
        "trap;\n"
        "DONE:\n}" ::"r"(a), "r"(ph)
        : "memory");
}
template <int ID, int CNT>
__device__ __forceinline__ void nb_sync() { asm volatile("bar.sync %0, %1;" ::"n"(ID), "n"(CNT) : "memory"); }
template <int ID, int CNT>
__device__ __forceinline__ void nb_arrive() { asm volatile("bar.arrive %0, %1;" ::"n"(ID), "n"(CNT) : "memory"); }
__device__ __forceinline__ void fence_async_smem() { asm volatile("fence.proxy.async.shared::cta;" ::: "memory"); }

__device__ __forceinline__ void tma3(uint32_t dst, const CUtensorMap* m, int c1, int c2, uint32_t bar, uint64_t pol) {
    asm volatile(
        "cp.async.bulk.tensor.3d.shared::cluster.global.mbarrier::complete_tx::bytes.L2::cache_hint [%0], [%1, {%3,%4,%5}], [%2], %6;" ::"r"(dst),
        "l"(m), "r"(bar), "r"(0), "r"(c1), "r"(c2), "l"(pol)
        : "memory");
}
__device__ __forceinline__ void bulk_load(uint32_t dst, const void* src, uint32_t bytes, uint32_t bar, uint64_t pol) {
    asm volatile("cp.async.bulk.shared::cluster.global.mbarrier::complete_tx::bytes.L2::cache_hint [%0], [%1], %2, [%3], %4;" ::"r"(dst),
                 "l"(src), "r"(bytes), "r"(bar), "l"(pol)
                 : "memory");
}
__device__ __forceinline__ void wg_fence() { asm volatile("wgmma.fence.sync.aligned;" ::: "memory"); }
__device__ __forceinline__ void wg_commit() { asm volatile("wgmma.commit_group.sync.aligned;" ::: "memory"); }
template <int N>
__device__ __forceinline__ void wg_wait() { asm volatile("wgmma.wait_group.sync.aligned %0;" ::"n"(N) : "memory"); }

#define RW80(c, d) c(d[0]), c(d[1]), c(d[2]), c(d[3]), c(d[4]), c(d[5]), c(d[6]), c(d[7]), c(d[8]), c(d[9]), c(d[10]), c(d[11]), c(d[12]), c(d[13]), c(d[14]), c(d[15]), c(d[16]), c(d[17]), c(d[18]), c(d[19]), c(d[20]), c(d[21]), c(d[22]), c(d[23]), c(d[24]), c(d[25]), c(d[26]), c(d[27]), c(d[28]), c(d[29]), c(d[30]), c(d[31]), c(d[32]), c(d[33]), c(d[34]), c(d[35]), c(d[36]), c(d[37]), c(d[38]), c(d[39]), c(d[40]), c(d[41]), c(d[42]), c(d[43]), c(d[44]), c(d[45]), c(d[46]), c(d[47]), c(d[48]), c(d[49]), c(d[50]), c(d[51]), c(d[52]), c(d[53]), c(d[54]), c(d[55]), c(d[56]), c(d[57]), c(d[58]), c(d[59]), c(d[60]), c(d[61]), c(d[62]), c(d[63]), c(d[64]), c(d[65]), c(d[66]), c(d[67]), c(d[68]), c(d[69]), c(d[70]), c(d[71]), c(d[72]), c(d[73]), c(d[74]), c(d[75]), c(d[76]), c(d[77]), c(d[78]), c(d[79])
#define RW48(c, d) c(d[0]), c(d[1]), c(d[2]), c(d[3]), c(d[4]), c(d[5]), c(d[6]), c(d[7]), c(d[8]), c(d[9]), c(d[10]), c(d[11]), c(d[12]), c(d[13]), c(d[14]), c(d[15]), c(d[16]), c(d[17]), c(d[18]), c(d[19]), c(d[20]), c(d[21]), c(d[22]), c(d[23]), c(d[24]), c(d[25]), c(d[26]), c(d[27]), c(d[28]), c(d[29]), c(d[30]), c(d[31]), c(d[32]), c(d[33]), c(d[34]), c(d[35]), c(d[36]), c(d[37]), c(d[38]), c(d[39]), c(d[40]), c(d[41]), c(d[42]), c(d[43]), c(d[44]), c(d[45]), c(d[46]), c(d[47])
#define RW32(c, d) c(d[0]), c(d[1]), c(d[2]), c(d[3]), c(d[4]), c(d[5]), c(d[6]), c(d[7]), c(d[8]), c(d[9]), c(d[10]), c(d[11]), c(d[12]), c(d[13]), c(d[14]), c(d[15]), c(d[16]), c(d[17]), c(d[18]), c(d[19]), c(d[20]), c(d[21]), c(d[22]), c(d[23]), c(d[24]), c(d[25]), c(d[26]), c(d[27]), c(d[28]), c(d[29]), c(d[30]), c(d[31])

__device__ __forceinline__ void reg_fence(float (&d)[80]) { asm volatile("" : RW80("+f", d)::"memory"); }
__device__ __forceinline__ void reg_fence(float (&d)[48]) { asm volatile("" : RW48("+f", d)::"memory"); }
__device__ __forceinline__ void reg_fence(float (&d)[32]) { asm volatile("" : RW32("+f", d)::"memory"); }

constexpr uint32_t HI_SW128 = (1024u >> 4) | (1u << 30);
constexpr uint32_t HI_OST = (2560u >> 4) | (2u << 30);
constexpr uint32_t LO_LBO1 = (1u << 16);
constexpr uint32_t LO_OST = ((512u >> 4) << 16);

template <int TA, int TB, uint32_t HIB, bool ACC>
__device__ __forceinline__ void wgmma(float (&d)[80], uint32_t loA, uint32_t loB) {
#define WG_ASM(SD)                                                          \
    "{\n.reg .b64 da, db;\nmov.b64 da, {%80, %82};\nmov.b64 db, {%81, %83};\n" \
    "wgmma.mma_async.sync.aligned.m64n160k16.f32.bf16.bf16 "               \
    "{%0,%1,%2,%3,%4,%5,%6,%7,%8,%9,%10,%11,%12,%13,%14,%15,%16,%17,%18,%19,%20,%21,%22,%23,%24,%25,%26,%27,%28,%29,%30,%31,%32,%33,%34,%35,%36,%37,%38,%39,%40,%41,%42,%43,%44,%45,%46,%47,%48,%49,%50,%51,%52,%53,%54,%55,%56,%57,%58,%59,%60,%61,%62,%63,%64,%65,%66,%67,%68,%69,%70,%71,%72,%73,%74,%75,%76,%77,%78,%79}, da, db, " SD ", 1, 1, %84, %85;\n}"
    if constexpr (ACC)
        asm volatile(WG_ASM("1") : RW80("+f", d) : "r"(loA), "r"(loB), "n"(HI_SW128), "n"(HIB), "n"(TA), "n"(TB));
    else
        asm volatile(WG_ASM("0") : RW80("=f", d) : "r"(loA), "r"(loB), "n"(HI_SW128), "n"(HIB), "n"(TA), "n"(TB));
#undef WG_ASM
}
template <int TA, int TB, uint32_t HIB, bool ACC>
__device__ __forceinline__ void wgmma(float (&d)[48], uint32_t loA, uint32_t loB) {
#define WG_ASM(SD)                                                          \
    "{\n.reg .b64 da, db;\nmov.b64 da, {%48, %50};\nmov.b64 db, {%49, %51};\n" \
    "wgmma.mma_async.sync.aligned.m64n96k16.f32.bf16.bf16 "               \
    "{%0,%1,%2,%3,%4,%5,%6,%7,%8,%9,%10,%11,%12,%13,%14,%15,%16,%17,%18,%19,%20,%21,%22,%23,%24,%25,%26,%27,%28,%29,%30,%31,%32,%33,%34,%35,%36,%37,%38,%39,%40,%41,%42,%43,%44,%45,%46,%47}, da, db, " SD ", 1, 1, %52, %53;\n}"
    if constexpr (ACC)
        asm volatile(WG_ASM("1") : RW48("+f", d) : "r"(loA), "r"(loB), "n"(HI_SW128), "n"(HIB), "n"(TA), "n"(TB));
    else
        asm volatile(WG_ASM("0") : RW48("=f", d) : "r"(loA), "r"(loB), "n"(HI_SW128), "n"(HIB), "n"(TA), "n"(TB));
#undef WG_ASM
}
template <int TA, int TB, uint32_t HIB, bool ACC>
__device__ __forceinline__ void wgmma(float (&d)[32], uint32_t loA, uint32_t loB) {
#define WG_ASM(SD)                                                          \
    "{\n.reg .b64 da, db;\nmov.b64 da, {%32, %34};\nmov.b64 db, {%33, %35};\n" \
    "wgmma.mma_async.sync.aligned.m64n64k16.f32.bf16.bf16 "               \
    "{%0,%1,%2,%3,%4,%5,%6,%7,%8,%9,%10,%11,%12,%13,%14,%15,%16,%17,%18,%19,%20,%21,%22,%23,%24,%25,%26,%27,%28,%29,%30,%31}, da, db, " SD ", 1, 1, %36, %37;\n}"
    if constexpr (ACC)
        asm volatile(WG_ASM("1") : RW32("+f", d) : "r"(loA), "r"(loB), "n"(HI_SW128), "n"(HIB), "n"(TA), "n"(TB));
    else
        asm volatile(WG_ASM("0") : RW32("=f", d) : "r"(loA), "r"(loB), "n"(HI_SW128), "n"(HIB), "n"(TA), "n"(TB));
#undef WG_ASM
}

__device__ __forceinline__ uint32_t pack_bf16(float lo, float hi) {
    uint32_t r;
    asm("cvt.rn.bf16x2.f32 %0, %1, %2;" : "=r"(r) : "f"(hi), "f"(lo));
    return r;
}
__device__ __forceinline__ float ex2(float x) {
    float r;
    asm("ex2.approx.ftz.f32 %0, %1;" : "=f"(r) : "f"(x));
    return r;
}
__device__ __forceinline__ void stsm4t(uint32_t a, uint32_t r0, uint32_t r1, uint32_t r2, uint32_t r3) {
    asm volatile("stmatrix.sync.aligned.m8n8.x4.trans.shared.b16 [%0], {%1,%2,%3,%4};" ::"r"(a), "r"(r0), "r"(r1), "r"(r2), "r"(r3)
                 : "memory");
}
__device__ __forceinline__ uint32_t lds_u(uint32_t a) {
    uint32_t v;
    asm volatile("ld.shared.u32 %0, [%1];" : "=r"(v) : "r"(a) : "memory");
    return v;
}
__device__ __forceinline__ float2 lds_f2(uint32_t a) {
    float2 v;
    asm volatile("ld.shared.v2.f32 {%0,%1}, [%2];" : "=f"(v.x), "=f"(v.y) : "r"(a) : "memory");
    return v;
}
__device__ __forceinline__ void sts_f(uint32_t a, float v) { asm volatile("st.shared.f32 [%0], %1;" ::"r"(a), "f"(v) : "memory"); }
__device__ __forceinline__ void sts_u(uint32_t a, uint32_t v) { asm volatile("st.shared.u32 [%0], %1;" ::"r"(a), "r"(v) : "memory"); }
__device__ __forceinline__ void sts_f2(uint32_t a, float x, float y) {
    asm volatile("st.shared.v2.f32 [%0], {%1,%2};" ::"r"(a), "f"(x), "f"(y) : "memory");
}

__device__ __forceinline__ void store_tile_t(const float (&d)[80], uint32_t addr) {
#pragma unroll
    for (int j = 0; j < 10; j++)
        stsm4t(addr + j * 2048, pack_bf16(d[8 * j], d[8 * j + 1]), pack_bf16(d[8 * j + 2], d[8 * j + 3]),
               pack_bf16(d[8 * j + 4], d[8 * j + 5]), pack_bf16(d[8 * j + 6], d[8 * j + 7]));
}
template <int NR>
__device__ __forceinline__ void store_out_tile(const float (&d)[NR], uint32_t base, uint32_t lane, uint32_t w) {
    const uint32_t mi = lane >> 3, i = lane & 7;
    const uint32_t chunk = 2 * w + (mi & 1);
    const uint32_t q0 = 8 * (i >> 1) + 2 * (mi >> 1) + (i & 1);
    const uint32_t a0 = base + q0 * 128 + ((chunk ^ (q0 & 7)) << 4);
    const uint32_t a1 = base + (q0 + 4) * 128 + ((chunk ^ ((q0 + 4) & 7)) << 4);
#pragma unroll
    for (int j = 0; j < NR / 8; j++)
        stsm4t(((j & 1) ? a1 : a0) + (j >> 1) * 4096, pack_bf16(d[8 * j], d[8 * j + 1]), pack_bf16(d[8 * j + 2], d[8 * j + 3]),
               pack_bf16(d[8 * j + 4], d[8 * j + 5]), pack_bf16(d[8 * j + 6], d[8 * j + 7]));
}

struct TrueT { static constexpr bool value = true; };
struct FalseT { static constexpr bool value = false; };

template <int V>
struct IntT { static constexpr int value = V; };

struct Ring {
    uint32_t slot, ph;
    __device__ __forceinline__ void adv(uint32_t k) {
        slot += k;
        if (slot >= NSLOT) { slot -= NSLOT; ph ^= 1; }
    }
};

template <int K>
__device__ __forceinline__ void qk_step(float (&s)[80], uint32_t loK, uint32_t loQ) {
    wgmma<0, 0, HI_SW128, K != 0>(s, loK + (K >> 2) * (8192 >> 4) + (K & 3) * 2, loQ + (K >> 2) * (XS >> 4) + (K & 3) * 2);
}
template <int K0, int K1>
__device__ __forceinline__ void qk_steps(float (&s)[80], uint32_t loK, uint32_t loQ) {
    if constexpr (K0 < K1) {
        qk_step<K0>(s, loK, loQ);
        qk_steps<K0 + 1, K1>(s, loK, loQ);
    }
}
template <int J>
__device__ __forceinline__ void exp_chunk(const float (&s)[80], float (&ps)[40], uint32_t pa, float mref) {
    float p[8];
#pragma unroll
    for (int i = 0; i < 8; i++) p[i] = ex2(fmaf(s[8 * J + i], SM_C, -mref));
    stsm4t(pa + J * 2048, pack_bf16(p[0], p[1]), pack_bf16(p[2], p[3]), pack_bf16(p[4], p[5]), pack_bf16(p[6], p[7]));
    ps[4 * J] = p[0] + p[2];
    ps[4 * J + 1] = p[1] + p[3];
    ps[4 * J + 2] = p[4] + p[6];
    ps[4 * J + 3] = p[5] + p[7];
}
template <int J>
__device__ __forceinline__ void exp_block(const float (&s)[80], float (&ps)[40], uint32_t pa, float mref) {
    if constexpr (J < 10) {
        exp_chunk<J>(s, ps, pa, mref);
        exp_block<J + 1>(s, ps, pa, mref);
    }
}
__device__ __forceinline__ void sum_block(const float (&ps)[40], float (&l)[5], uint32_t lane) {
    const bool b4 = lane & 16, b3 = lane & 8, b2 = lane & 4;
    float t[20];
#pragma unroll
    for (int j = 0; j < 10; j++) {
        t[2 * j] = (b4 ? ps[4 * j + 2] : ps[4 * j]) + __shfl_xor_sync(0xffffffffu, b4 ? ps[4 * j] : ps[4 * j + 2], 16);
        t[2 * j + 1] = (b4 ? ps[4 * j + 3] : ps[4 * j + 1]) + __shfl_xor_sync(0xffffffffu, b4 ? ps[4 * j + 1] : ps[4 * j + 3], 16);
    }
#pragma unroll
    for (int i = 0; i < 10; i++) t[i] = (b3 ? t[i + 10] : t[i]) + __shfl_xor_sync(0xffffffffu, b3 ? t[i] : t[i + 10], 8);
#pragma unroll
    for (int i = 0; i < 5; i++)
        l[i] += (b2 ? t[2 * i + 1] : t[2 * i]) + __shfl_xor_sync(0xffffffffu, b2 ? t[2 * i] : t[2 * i + 1], 4);
}

__device__ __forceinline__ void fallback_unit(const Params& P, uint32_t e, uint32_t tid) {
    const uint32_t lane = tid & 31, br = IT_BR(e), b = IT_B(e), h = IT_H0(e);
    const __nv_bfloat162* wq = (const __nv_bfloat162*)(P.pwq[br] + h * 192) + lane;
    const __nv_bfloat162* kp = (const __nv_bfloat162*)(P.pk[br] + (size_t)(b * 32 + h) * 512 * 192) + lane;
    const __nv_bfloat162* vp = (const __nv_bfloat162*)(P.pv[br] + (size_t)(b * 32 + h) * 512 * 192) + lane;
#pragma unroll 1
    for (uint32_t q = tid >> 5; q < 160; q += 4) {
        const __nv_bfloat16* xr = P.px[br] + (size_t)(b * 160 + q) * 640;
        float a[6] = {0.f, 0.f, 0.f, 0.f, 0.f, 0.f};
#pragma unroll 4
        for (int k = 0; k < 640; k++) {
            const float xv = __bfloat162float(xr[k]);
#pragma unroll
            for (int i = 0; i < 3; i++) {
                const float2 wv = __bfloat1622float2(wq[(size_t)k * 3072 + i * 32]);
                a[2 * i] = fmaf(xv, wv.x, a[2 * i]);
                a[2 * i + 1] = fmaf(xv, wv.y, a[2 * i + 1]);
            }
        }
#pragma unroll
        for (int i = 0; i < 6; i++) a[i] = __bfloat162float(__float2bfloat16(a[i]));
        auto score = [&](int key) {
            float d = 0.f;
#pragma unroll
            for (int i = 0; i < 3; i++) {
                const float2 kv = __bfloat1622float2(kp[key * 96 + i * 32]);
                d = fmaf(a[2 * i], kv.x, fmaf(a[2 * i + 1], kv.y, d));
            }
#pragma unroll
            for (int o = 16; o > 0; o >>= 1) d += __shfl_xor_sync(0xffffffffu, d, o);
            return d;
        };
        float m = -INFINITY;
#pragma unroll 4
        for (int key = 0; key < 512; key++) m = fmaxf(m, score(key));
        float o[6] = {0.f, 0.f, 0.f, 0.f, 0.f, 0.f}, sum = 0.f;
#pragma unroll 4
        for (int key = 0; key < 512; key++) {
            const float p = ex2((score(key) - m) * SM_C);
            sum += p;
#pragma unroll
            for (int i = 0; i < 3; i++) {
                const float2 vv = __bfloat1622float2(vp[key * 96 + i * 32]);
                o[2 * i] = fmaf(p, vv.x, o[2 * i]);
                o[2 * i + 1] = fmaf(p, vv.y, o[2 * i + 1]);
            }
        }
        const float inv = 1.f / sum;
        __nv_bfloat16* op = (__nv_bfloat16*)ostash(br, b, h) + (q >> 5) * 256 + 2 * ((q & 31) >> 3) + (q & 1);
#pragma unroll
        for (int i = 0; i < 6; i++) {
            const uint32_t d = (i >> 1) * 64 + 2 * lane + (i & 1);
            op[(d >> 3) * 1280 + (d & 7) * 32 + ((((q & 7) >> 1) ^ ((d & 7) >> 1)) << 3)] = __float2bfloat16(o[i] * inv);
        }
    }
}

template <int W>
struct PendO {
    static constexpr int N = W == 0 ? 14 : 16;
    uint32_t v[4 * N];
    unsigned char* gp;
    uint32_t pend;
    template <int I>
    __device__ __forceinline__ void store() const {
        if constexpr (I < N) {
            constexpr int g = I < 10 ? I / 2 : (I - 10) / 2 + (W == 0 ? 3 : 0);
            constexpr int off = (I < 10 ? W : 2) * XS + g * 512 + (I & 1) * 2560;
            asm volatile(
                "{\n.reg .pred p;\nsetp.ne.u32 p, %6, 0;\n@p st.global.v4.b32 [%0+%5], {%1,%2,%3,%4};\n}" ::"l"(gp),
                "r"(v[4 * I]), "r"(v[4 * I + 1]), "r"(v[4 * I + 2]), "r"(v[4 * I + 3]), "n"(off), "r"(pend)
                : "memory");
        }
    }
    template <int I>
    __device__ __forceinline__ void flush() const {
        if constexpr (I < N) {
            store<I>();
            flush<I + 1>();
        }
    }
    __device__ __forceinline__ void clear() {
#pragma unroll
        for (int i = 0; i < 4 * N; i++) v[i] = 0;
        gp = nullptr;
        pend = 0;
    }
};

template <int W, int KK>
__device__ __forceinline__ void qproj(float (&q0)[80], float (&q1)[80], uint32_t sb, Ring& r, uint32_t phm, const PendO<W>& po) {
    const uint32_t loR = ((sb + OFF_R) >> 4) | LO_LBO1;
    const uint32_t loRing = ((sb + OFF_RING) >> 4) | LO_LBO1;
    constexpr int xs = KK % 5;
    const uint32_t pslot = r.slot;
    if (KK > 0) r.adv(1);
    if (W == 1 && KK == QHOLD) nb_sync<NB_SDONE, 256>();
    mbar_wait(sb + BAR_RFULL + r.slot * 8, r.ph);
    mbar_wait(sb + BAR_XFULL + xs * 8, ((phm >> xs) ^ (KK / 5)) & 1);
    const uint32_t a = loRing + r.slot * (SLOT >> 4) + (W == 0 ? 0 : 1024), b = loR + xs * (XS >> 4);
    wg_fence();
    wgmma<1, 0, HI_SW128, KK != 0>(q0, a, b);
    if (W == 0) wgmma<1, 0, HI_SW128, KK != 0>(q1, a + 512, b);
#pragma unroll
    for (int k = 1; k < 4; k++) {
        wgmma<1, 0, HI_SW128, true>(q0, a + k * 128, b + k * 2);
        if (W == 0) wgmma<1, 0, HI_SW128, true>(q1, a + 512 + k * 128, b + k * 2);
    }
    wg_commit();
    if (KK > 0) {
        wg_wait<1>();
        mbar_arrive_warp(sb + BAR_REMPTY + pslot * 8, 1);
        if (KK <= 5) mbar_arrive_warp(sb + (BAR_XEMPTY + (KK - 1) * 8), 1);
        if (W == 1 && KK == 7) nb_arrive<NB_PDONE, 256>();
    }
    if (KK < 6) {
        po.template store<3 * KK>();
        po.template store<3 * KK + 1>();
        po.template store<3 * KK + 2>();
        if (KK == 5 && po.pend) nb_arrive<NB_ODONE, 288>();
    }
    if constexpr (KK < 9) {
        qproj<W, KK + 1>(q0, q1, sb, r, phm, po);
    } else {
        if (W == 0) nb_arrive<NB_SDONE, 256>();
        wg_wait<0>();
        reg_fence(q0);
        if (W == 0) reg_fence(q1);
        mbar_arrive_warp(sb + BAR_REMPTY + r.slot * 8, 1);
        r.adv(1);
    }
}

template <int NR>
__device__ __forceinline__ void opack(const float (&o)[NR], int gl, const float2* sc, uint32_t* v) {
#pragma unroll
    for (int hh = 0; hh < 2; hh++)
#pragma unroll
        for (int t = 0; t < 4; t++)
            v[4 * hh + t] = pack_bf16(o[16 * gl + 4 * t + 2 * hh] * sc[t].x, o[16 * gl + 4 * t + 2 * hh + 1] * sc[t].y);
}

template <int NR>
__device__ __forceinline__ void dump_acc(const float (&c)[NR], float4* p) {
#pragma unroll
    for (int i = 0; i < NR / 4; i++) p[i * 128] = make_float4(c[4 * i], c[4 * i + 1], c[4 * i + 2], c[4 * i + 3]);
}
__device__ __forceinline__ void wait_flag(const unsigned int* f, uint32_t epoch) {
    uint32_t v, n = 0;
    do {
        asm volatile("ld.acquire.gpu.global.u32 %0, [%1];" : "=r"(v) : "l"(f) : "memory");
        if (++n > 0x400000) __trap();
    } while (v != epoch);
}

template <bool IS_S>
__device__ __forceinline__ void op_item(uint32_t e, uint32_t sb, Ring& r, uint32_t& phm) {
    constexpr int T0 = IS_S ? 0 : 2;
    constexpr uint32_t BOFF = IS_S ? (3 * 512) >> 4 : 0;
    const uint32_t loRing = ((sb + OFF_RING) >> 4) | LO_LBO1;
    const uint32_t loO = ((sb + OFF_R) >> 4) | LO_OST;
    float c0[80], c1[80], c2[IS_S ? 32 : 48];
    const int T2 = 6 * (IT_H1(e) - IT_H0(e));
    uint32_t xs = 0;
    auto step = [&](auto first, uint32_t hf) {
        constexpr bool F = decltype(first)::value;
        if (hf == 0) {
            mbar_wait(sb + BAR_XFULL + xs * 8, (phm >> xs) & 1);
            phm ^= 1u << xs;
        }
        mbar_wait(sb + BAR_RFULL + r.slot * 8, r.ph);
        const uint32_t a = loRing + r.slot * (SLOT >> 4), b = loO + xs * (XS >> 4) + hf * 640;
        wg_fence();
        wgmma<1, 1, HI_OST, !F>(c0, a + T0 * 256, b);
        wgmma<1, 1, HI_OST, !F>(c1, a + T0 * 256 + 256, b);
        wgmma<1, 1, HI_OST, !F>(c2, a + 1024, b + BOFF);
        wgmma<1, 1, HI_OST, true>(c0, a + T0 * 256 + 128, b + 320);
        wgmma<1, 1, HI_OST, true>(c1, a + T0 * 256 + 384, b + 320);
        wgmma<1, 1, HI_OST, true>(c2, a + 1024 + 128, b + 320 + BOFF);
        wg_commit();
    };
    step(TrueT{}, 0);
#pragma unroll 1
    for (int t = 1; t < T2; t++) {
        const uint32_t pslot = r.slot, pxs = xs;
        r.adv(1);
        if ((t & 1) == 0 && ++xs == 5) xs = 0;
        step(FalseT{}, t & 1);
        wg_wait<1>();
        mbar_arrive_warp(sb + BAR_REMPTY + pslot * 8, 1);
        if ((t & 1) == 0 && t + 8 < T2) mbar_arrive_warp(sb + BAR_XEMPTY + pxs * 8, 1);
    }
    wg_wait<0>();
    reg_fence(c0);
    reg_fence(c1);
    reg_fence(c2);
    mbar_arrive_warp(sb + BAR_REMPTY + r.slot * 8, 1);
    r.adv(1);
    if (IT_PART(e)) {
#pragma unroll
        for (int m = 0; m < 5; m++) mbar_arrive_warp(sb + BAR_XEMPTY + m * 8, 1);
        float4* pp = g_part + (size_t)((IT_BR(e) * 16 + IT_B(e)) * 10 + IT_HALF(e) * 5) * 2560 + (threadIdx.x & 127);
        dump_acc(c0, pp + T0 * 2560);
        dump_acc(c1, pp + (T0 + 1) * 2560);
        dump_acc(c2, pp + 4 * 2560 + (IS_S ? 12 * 128 : 0));
    } else {
        nb_sync<NB_OPEND, 256>();
        const uint32_t lane = threadIdx.x & 31, w = (threadIdx.x >> 5) & 3;
        store_out_tile(c0, sb + OFF_R + T0 * XS, lane, w);
        store_out_tile(c1, sb + OFF_R + (T0 + 1) * XS, lane, w);
        store_out_tile(c2, sb + OFF_R + 4 * XS + (IS_S ? 96 * 128 : 0), lane, w);
        fence_async_smem();
    }
    nb_arrive<NB_ODONE, 288>();
}

template <int W>
__device__ __forceinline__ void on_item(uint32_t e, uint32_t sb, Ring& r, uint32_t& phm, uint32_t epoch) {
    const uint32_t loRing = ((sb + OFF_RING) >> 4) | LO_LBO1;
    const uint32_t loO = ((sb + OFF_R) >> 4) | LO_OST;
    float c[80];
    const int T = 3 * (IT_H1(e) - IT_H0(e));
    uint32_t xs = 0;
    auto step = [&](auto first) {
        constexpr bool F = decltype(first)::value;
        mbar_wait(sb + BAR_XFULL + xs * 8, (phm >> xs) & 1);
        phm ^= 1u << xs;
        mbar_wait(sb + BAR_RFULL + r.slot * 8, r.ph);
        const uint32_t a = loRing + r.slot * (SLOT >> 4) + W * 512, b = loO + xs * (XS >> 4);
        wg_fence();
        wgmma<1, 1, HI_OST, !F>(c, a, b);
#pragma unroll
        for (int k = 1; k < 4; k++) wgmma<1, 1, HI_OST, true>(c, a + k * 128, b + k * 320);
        wg_commit();
    };
    auto run = [&](int t0, int t1) {
#pragma unroll 1
        for (int t = t0; t < t1; t++) {
            const uint32_t pslot = r.slot, pxs = xs;
            r.adv(1);
            if (++xs == 5) xs = 0;
            step(FalseT{});
            wg_wait<1>();
            mbar_arrive_warp(sb + BAR_REMPTY + pslot * 8, 1);
            mbar_arrive_warp_if(sb + BAR_XEMPTY + pxs * 8, 1, t + 4 < T);
        }
    };
    step(TrueT{});
    const int tm = T >> 1;
    run(1, tm);
    float4 pv[20];
    {
        const uint32_t tile = 2 * IT_HALF(e) + W, bb = IT_BR(e) * 16 + IT_B(e);
        wait_flag(&g_pflag[bb * 2 + (tile >= 5)], epoch);
        const float4* pp = g_part + (size_t)(bb * 10 + tile) * 2560 + (threadIdx.x & 127);
#pragma unroll
        for (int i = 0; i < 20; i++) pv[i] = __ldcg(pp + i * 128);
    }
    run(tm, T);
    wg_wait<0>();
    reg_fence(c);
    mbar_arrive_warp(sb + BAR_REMPTY + r.slot * 8, 1);
    r.adv(1);
    nb_sync<NB_OPEND, 256>();
#pragma unroll
    for (int i = 0; i < 20; i++) {
        c[4 * i] += pv[i].x;
        c[4 * i + 1] += pv[i].y;
        c[4 * i + 2] += pv[i].z;
        c[4 * i + 3] += pv[i].w;
    }
    store_out_tile(c, sb + OFF_R + W * XS, threadIdx.x & 31, (threadIdx.x >> 5) & 3);
    fence_async_smem();
    nb_arrive<NB_ODONE, 288>();
}

template <int W>
__device__ __forceinline__ void qa_item(const Params& P, const uint32_t* items, uint32_t sb, Ring& r, uint32_t phm, PendO<W>& po, int it) {
    const uint32_t loR = ((sb + OFF_R) >> 4) | LO_LBO1;
    const uint32_t loRing = ((sb + OFF_RING) >> 4) | LO_LBO1;
    const uint32_t lane = threadIdx.x & 31, w = (threadIdx.x >> 5) & 3;
    const uint32_t sta = sb + OFF_R + (lane >> 4) * 1024 + (lane & 7) * 128 + (((2 * w + ((lane >> 3) & 1)) ^ (lane & 7)) << 4);
    {
        float q0[80], q1[80];
        qproj<W, 0>(q0, q1, sb, r, phm, po);
        TS(W, 1);
        if (W == 0) {
            nb_sync<NB_PDONE, 256>();
            store_tile_t(q0, sta);
            store_tile_t(q1, sta + XS);
        } else {
            store_tile_t(q0, sta + 2 * XS);
        }
    }
    fence_async_smem();
    float s[80], oa[80], ob[W == 0 ? 32 : 48], l[5];
#pragma unroll
    for (int i = 0; i < 80; i++) oa[i] = 0.f;
#pragma unroll
    for (int i = 0; i < (W == 0 ? 32 : 48); i++) ob[i] = 0.f;
#pragma unroll
    for (int i = 0; i < 5; i++) l[i] = 0.f;
    reg_fence(oa);
    reg_fence(ob);
    auto pv = [&](uint32_t buf) {
        mbar_wait(sb + BAR_RFULL + r.slot * 8, r.ph);
        const uint32_t a = loRing + r.slot * (SLOT >> 4), b = loR + (3 + buf) * (XS >> 4);
        wg_fence();
#pragma unroll
        for (int k = 0; k < 4; k++) {
            wgmma<1, 0, HI_SW128, true>(oa, a + W * 512 + k * 128, b + k * 2);
            wgmma<1, 0, HI_SW128, true>(ob, a + 1024 + k * 128, b + (W == 0 ? (96 * 128) >> 4 : 0) + k * 2);
        }
        wg_commit();
    };
    float mref;
    uint32_t kslot, vslot;
    const uint32_t lxa = sb + OFF_LX + w * 640 + (((lane & 8) ? 80 : 0) + ((lane >> 1) & 8) + 2 * (lane & 3) + ((lane >> 2) & 1)) * 4;
    auto tail = [&](bool rel_other, int i) {
        float ps[40];
        exp_block<0>(s, ps, sta + (3 + W) * XS, mref);
        if (rel_other) {
            wg_wait<0>();
            mbar_arrive_warp(sb + BAR_REMPTY + vslot * 8, 1);
            if (W == 1) mbar_arrive_warp_if(sb + BAR_XEMPTY + 24, 1, i == 3);
        }
        fence_async_smem();
        nb_arrive<NB_PFULL + W, 256>();
        TS(W, 6 + 5 * i);
        mbar_wait(sb + BAR_RFULL + r.slot * 8, r.ph);
        sum_block(ps, l, lane);
        if (W == 1 && i == 3) {
            nb_sync<NB_LX, 256>();
#pragma unroll
            for (int k = 0; k < 5; k++) sts_f(lxa + k * 64, l[k]);
            nb_arrive<NB_L, 256>();
        }
        nb_sync<NB_W + W, 128>();
        TS(W, 7 + 5 * i);
        pv(W);
        TS(W, 8 + 5 * i);
    };
    if (W == 0) {
        nb_sync<NB_W, 128>();
        TS(W, 2);
        mbar_wait(sb + BAR_RFULL + r.slot * 8, r.ph);
        wg_fence();
        qk_steps<0, 8>(s, loRing + r.slot * (SLOT >> 4), loR);
        nb_sync<NB_Q2, 256>();
        qk_steps<8, 12>(s, loRing + r.slot * (SLOT >> 4), loR);
        wg_commit();
        nb_arrive<NB_Q01, 256>();
        TS(W, 4);
        wg_wait<0>();
        reg_fence(s);
        mbar_arrive_warp(sb + BAR_REMPTY + r.slot * 8, 2);
        r.adv(2);
        float m0 = fmaxf(s[0], s[5]), m1 = fmaxf(s[10], s[15]);
#pragma unroll
        for (int i = 20; i < 80; i += 10) {
            m0 = fmaxf(m0, s[i]);
            m1 = fmaxf(m1, s[i + 5]);
        }
        int key = __float_as_int(fmaxf(m0, m1));
        key ^= (key >> 31) & 0x7fffffff;
        key = __reduce_max_sync(0xffffffffu, key);
        key ^= (key >> 31) & 0x7fffffff;
        sts_u(sb + OFF_GM + w * 4, key);
        sts_u(sb + OFF_FB, 0);
        nb_sync<NB_W, 128>();
        const float2 u = lds_f2(sb + OFF_GM), v = lds_f2(sb + OFF_GM + 8);
        mref = fmaxf(fmaxf(u.x, u.y), fmaxf(v.x, v.y)) * SM_C;
        TS(W, 5);
        tail(false, 0);
    } else {
        nb_arrive<NB_Q2, 256>();
        TS(W, 2);
        nb_sync<NB_Q01, 256>();
    }
#pragma unroll 1
    for (int i = (W == 0 ? 1 : 0); i < 4; i++) {
        const uint32_t pvslot = r.slot;
        r.adv(1);
        kslot = r.slot;
        mbar_wait(sb + BAR_RFULL + r.slot * 8, r.ph);
        wg_fence();
        qk_steps<0, 12>(s, loRing + r.slot * (SLOT >> 4), loR);
        wg_commit();
        wg_wait<1>();
        mbar_arrive_warp_if(sb + BAR_REMPTY + pvslot * 8, 1, W == 0 || i > 0);
        r.adv(1);
        vslot = r.slot;
        TS(W, 4 + 5 * i);
        nb_sync<NB_PFULL + (W ^ 1), 256>();
        pv(W ^ 1);
        if (W == 1) {
            const float2 u = lds_f2(sb + OFF_GM), v = lds_f2(sb + OFF_GM + 8);
            mref = fmaxf(fmaxf(u.x, u.y), fmaxf(v.x, v.y)) * SM_C;
        }
        wg_wait<1>();
        reg_fence(s);
        mbar_arrive_warp(sb + BAR_REMPTY + kslot * 8, 2);
        if (W == 1) {
            mbar_arrive_warp_if(sb + BAR_XEMPTY + 0, 2, i == 3);
            mbar_arrive_warp_if(sb + BAR_XEMPTY + 8, 2, i == 3);
            mbar_arrive_warp_if(sb + BAR_XEMPTY + 16, 2, i == 3);
        }
        r.adv(W == 1 && i == 3 ? 1 : 2);
        TS(W, 5 + 5 * i);
        tail(true, i);
    }
    if (W == 0) {
        const uint32_t tid = threadIdx.x & 127;
        float2 v = make_float2(0.f, 0.f);
        auto gather = [&]() {
            if (tid < 80) {
#pragma unroll
                for (int i = 0; i < 4; i++) {
                    const float2 u = lds_f2(sb + OFF_LX + i * 640 + tid * 8);
                    v.x += u.x;
                    v.y += u.y;
                }
            }
        };
#pragma unroll
        for (int i = 0; i < 5; i++) sts_f(lxa + i * 64, l[i]);
        nb_sync<NB_W, 128>();
        gather();
        nb_arrive<NB_LX, 256>();
        wg_wait<0>();
        mbar_arrive_warp(sb + BAR_REMPTY + r.slot * 8, 1);
        mbar_arrive_warp(sb + BAR_XEMPTY + 24, 1);
        r.adv(1);
        nb_sync<NB_PFULL + 1, 256>();
        pv(1);
        TS(W, 24);
        nb_sync<NB_L, 256>();
        gather();
        if (tid < 80) {
            sts_f2(sb + OFF_LINV + tid * 8, __fdividef(1.f, v.x), __fdividef(1.f, v.y));
            if (!(v.x >= 5.421010862e-20f && v.x <= 1.8446744e19f && v.y >= 5.421010862e-20f && v.y <= 1.8446744e19f))
                sts_u(sb + OFF_FB, 1);
        }
    }
    nb_sync<NB_VOTE, 256>();
    const bool any = __any_sync(0xffffffffu, lds_u(sb + OFF_FB) != 0);
    float2 sc[20];
#pragma unroll
    for (int t = 0; t < 20; t++) sc[t] = lds_f2(sb + OFF_LINV + (lane & 3) * 8 + t * 32);
    wg_wait<0>();
    reg_fence(oa);
    reg_fence(ob);
    mbar_arrive_warp(sb + BAR_REMPTY + r.slot * 8, 1);
    mbar_arrive_warp(sb + BAR_XEMPTY + 32, 1);
    r.adv(1);
    TS(W, 25);
#pragma unroll
    for (int g = 0; g < 5; g++) {
        opack(oa, g, sc + 4 * g, po.v + 8 * g);
        if (W == 0 && g >= 3) opack(ob, g - 3, sc + 4 * g, po.v + 40 + 8 * (g - 3));
        if (W == 1 && g < 3) opack(ob, g, sc + 4 * g, po.v + 40 + 8 * g);
    }
    const uint32_t e = items[it];
    po.gp = ostash(IT_BR(e), IT_B(e), IT_H0(e)) + w * 5120 + (lane >> 2) * 64 +
            (((lane ^ (lane >> 3)) & 3) << 4);
    po.pend = 1;
    if (any || IT_TYPE(items[it + 1]) != IT_QA) {
        if (!any) po.template flush<0>();
        else if (W == 1) fallback_unit(P, e, threadIdx.x & 127);
        nb_arrive<NB_ODONE, 288>();
        po.pend = 0;
    }
}

__global__ void __launch_bounds__(384, 1) fused_kernel(const __grid_constant__ Params P) {
    extern __shared__ __align__(1024) unsigned char smem_raw[];
    const uint32_t sb = (uint32_t)__cvta_generic_to_shared(smem_raw);
    const uint32_t wgid = __shfl_sync(0xffffffffu, threadIdx.x >> 7, 0);
    const uint32_t cta = blockIdx.x;
    const uint32_t* items = P.items[cta];

    uint32_t epoch = 0;
    if (wgid == 0) epoch = *(volatile unsigned int*)&g_epoch[cta] + 1;
    if (threadIdx.x == 0) {
        if (sb & 1023) __trap();
        sts_u(sb + OFF_FB + 4, epoch);
        for (int i = 0; i < NSLOT; i++) {
            mbar_init(sb + BAR_RFULL + i * 8, 1);
            mbar_init(sb + BAR_REMPTY + i * 8, 8);
            mbar_init(sb + BAR_XFULL + i * 8, 1);
            mbar_init(sb + BAR_XEMPTY + i * 8, 8);
        }
        asm volatile("fence.mbarrier_init.release.cluster;" ::: "memory");
        fence_async_smem();
    }
    __syncthreads();

    if (wgid == 0) {
        asm volatile("setmaxnreg.dec.sync.aligned.u32 24;");
        const uint32_t warp = __shfl_sync(0xffffffffu, threadIdx.x >> 5, 0);
        if (warp == 0) {
            if (threadIdx.x == 0) {
                *(volatile unsigned int*)&g_epoch[cta] = epoch;
                const uint64_t pol_first = mkpol<1>(), pol_norm = mkpol<POL_W>();
                Ring r{0, 1};
                for (int it = 0; it < MAXI; it++) {
                    const uint32_t e = items[it];
                    if (e == 0) break;
                    const uint32_t br = IT_BR(e);
                    if (IT_TYPE(e) == IT_QA) {
                        const uint32_t h = IT_H0(e);
#pragma unroll 1
                        for (int kk = 0; kk < 10; kk++) {
                            mbar_wait(sb + BAR_REMPTY + r.slot * 8, r.ph);
                            mbar_expect(sb + BAR_RFULL + r.slot * 8, SLOT);
                            tma3(sb + OFF_RING + r.slot * SLOT, &P.wq[br], kk * 64, h * 3, sb + BAR_RFULL + r.slot * 8, pol_norm);
                            r.adv(1);
                        }
                        const int row0 = (IT_B(e) * 32 + h) * 512;
#pragma unroll 1
                        for (int n = 0; n < 16; n++) {
                            const bool isv = n == 15 || (n > 0 && !(n & 1));
                            const int j = n == 15 ? 7 : isv ? (n - 2) >> 1 : (n + 1) >> 1;
                            mbar_wait(sb + BAR_REMPTY + r.slot * 8, r.ph);
                            mbar_expect(sb + BAR_RFULL + r.slot * 8, SLOT);
                            tma3(sb + OFF_RING + r.slot * SLOT, isv ? &P.v[br] : &P.k[br], row0 + j * 64, 0,
                                 sb + BAR_RFULL + r.slot * 8, pol_first);
                            r.adv(1);
                        }
                    } else {
                        const int r0 = IT_H0(e) * 192, r1 = IT_H1(e) * 192;
                        const bool wide = IT_TYPE(e) == IT_OP;
#pragma unroll 1
                        for (int row = r0; row < r1; row += wide ? 32 : 64) {
                            mbar_wait(sb + BAR_REMPTY + r.slot * 8, r.ph);
                            mbar_expect(sb + BAR_RFULL + r.slot * 8, wide ? XS : 16384);
                            tma3(sb + OFF_RING + r.slot * SLOT, wide ? &P.wo[br] : &P.won[br], row, IT_HALF(e) * (wide ? 5 : 2),
                                 sb + BAR_RFULL + r.slot * 8, pol_norm);
                            r.adv(1);
                        }
                    }
                }
            }
        } else if (warp == 1) {
            if (threadIdx.x == 32) {
                const uint64_t pol_norm = mkpol<POL_X>(), pol_o = mkpol<POL_O>();
                uint32_t phm = 0x1f;
                for (int it = 0; it < MAXI; it++) {
                    const uint32_t e = items[it];
                    if (e == 0) break;
                    const uint32_t br = IT_BR(e);
                    uint32_t xs = 0;
                    if (IT_TYPE(e) == IT_QA) {
#pragma unroll 1
                        for (int kk = 0; kk < 10; kk++) {
                            mbar_wait(sb + BAR_XEMPTY + xs * 8, (phm >> xs) & 1);
                            phm ^= 1u << xs;
                            mbar_expect(sb + BAR_XFULL + xs * 8, XS);
                            tma3(sb + OFF_R + xs * XS, &P.x[br], IT_B(e) * 160, kk, sb + BAR_XFULL + xs * 8, pol_norm);
                            if (++xs == 5) xs = 0;
                        }
                    } else {
                        const uint32_t u0 = (br * 16 + IT_B(e)) * 32;
#pragma unroll 1
                        for (uint32_t u = u0 + IT_H0(e); u < u0 + IT_H1(e); u++) {
                            wait_flag(&g_flag[u], epoch);
                            asm volatile("fence.proxy.async;" ::: "memory");
#pragma unroll 1
                            for (int t = 0; t < 3; t++) {
                                mbar_wait(sb + BAR_XEMPTY + xs * 8, (phm >> xs) & 1);
                                phm ^= 1u << xs;
                                mbar_expect(sb + BAR_XFULL + xs * 8, XS);
                                bulk_load(sb + OFF_R + xs * XS, ostash(br, IT_B(e), u & 31) + t * XS, XS, sb + BAR_XFULL + xs * 8, pol_o);
                                if (++xs == 5) xs = 0;
                            }
                        }
                    }
                }
            }
        } else if (warp == 2) {
#pragma unroll 1
            for (int it = 0; it < MAXI; it++) {
                const uint32_t e = items[it];
                if (e == 0) break;
                nb_sync<NB_ODONE, 288>();
                if (threadIdx.x == 64) {
                    const uint32_t bb = IT_BR(e) * 16 + IT_B(e);
                    if (IT_TYPE(e) == IT_QA || IT_PART(e)) {
                        __threadfence();
                        unsigned int* f = IT_TYPE(e) == IT_QA ? &g_flag[bb * 32 + IT_H0(e)] : &g_pflag[bb * 2 + IT_HALF(e)];
                        asm volatile("st.relaxed.gpu.global.u32 [%0], %1;" ::"l"(f), "r"(epoch) : "memory");
                    } else {
                        const int nt = IT_TYPE(e) == IT_OP ? 5 : 2;
                        const int cc0 = IT_BR(e) * 640 + IT_HALF(e) * nt * 64;
#pragma unroll
                        for (int m = 0; m < 5; m++) {
                            if (m < nt)
                                asm volatile("cp.async.bulk.tensor.2d.global.shared::cta.bulk_group [%0, {%2,%3}], [%1];" ::"l"(&P.out),
                                             "r"(sb + OFF_R + m * XS), "r"(cc0 + m * 64), "r"((int)IT_B(e) * 160)
                                             : "memory");
                            asm volatile("cp.async.bulk.commit_group;" ::: "memory");
                        }
#define REL(N)                                                          \
    asm volatile("cp.async.bulk.wait_group.read %0;" ::"n"(4 - N) : "memory"); \
    asm volatile("mbarrier.arrive.shared::cta.b64 _, [%0], 8;" ::"r"(sb + BAR_XEMPTY + N * 8) : "memory");
                        REL(0) REL(1) REL(2) REL(3) REL(4)
#undef REL
                    }
                }
                __syncwarp();
            }
            if (threadIdx.x == 64) asm volatile("cp.async.bulk.wait_group 0;" ::: "memory");
        }
    } else if (wgid == 1) {
        asm volatile("setmaxnreg.inc.sync.aligned.u32 240;");
        PendO<0> po;
        po.clear();
        Ring r{0, 0};
        uint32_t phm = 0;
#pragma unroll 1
        for (int it = 0; it < MAXI; it++) {
            const uint32_t e = items[it];
            if (e == 0) break;
            TS(0, 0);
            if (IT_TYPE(e) == IT_QA) {
                qa_item<0>(P, items, sb, r, phm, po, it);
            } else {
                if (IT_TYPE(e) == IT_OP) op_item<true>(e, sb, r, phm);
                else on_item<0>(e, sb, r, phm, lds_u(sb + OFF_FB + 4));
                po.clear();
            }
            TS(0, 31);
        }
        TS_DUMP(0);
    } else {
        asm volatile("setmaxnreg.inc.sync.aligned.u32 240;");
        PendO<1> po;
        po.clear();
        Ring r{0, 0};
        uint32_t phm = 0;
#pragma unroll 1
        for (int it = 0; it < MAXI; it++) {
            const uint32_t e = items[it];
            if (e == 0) break;
            TS(1, 0);
            if (IT_TYPE(e) == IT_QA) {
                qa_item<1>(P, items, sb, r, phm, po, it);
            } else {
                if (IT_TYPE(e) == IT_OP) op_item<false>(e, sb, r, phm);
                else on_item<1>(e, sb, r, phm, lds_u(sb + OFF_FB + 4));
                po.clear();
            }
            TS(1, 31);
        }
        TS_DUMP(1);
    }
}

typedef CUresult (*EncFn)(CUtensorMap*, CUtensorMapDataType, cuuint32_t, void*, const cuuint64_t*, const cuuint64_t*,
                          const cuuint32_t*, const cuuint32_t*, CUtensorMapInterleave, CUtensorMapSwizzle,
                          CUtensorMapL2promotion, CUtensorMapFloatOOBfill);

void make_map3(EncFn enc, CUtensorMap* m, void* p, uint64_t rows, uint64_t rowbytes, uint64_t nblk, uint32_t boxrows,
               uint32_t boxblk) {
    cuuint64_t dims[3] = {64, rows, nblk};
    cuuint64_t str[2] = {rowbytes, 128};
    cuuint32_t box[3] = {64, boxrows, boxblk};
    cuuint32_t es[3] = {1, 1, 1};
    enc(m, CU_TENSOR_MAP_DATA_TYPE_BFLOAT16, 3, p, dims, str, box, es, CU_TENSOR_MAP_INTERLEAVE_NONE,
        CU_TENSOR_MAP_SWIZZLE_128B, CU_TENSOR_MAP_L2_PROMOTION_NONE, CU_TENSOR_MAP_FLOAT_OOB_FILL_NONE);
}

#define SCHED_MODE 4
#define HSPLIT 14

void build_schedule(Params& P) {
    int n[NCTA];
    for (int c = 0; c < NCTA; c++) {
        n[c] = 0;
        for (int i = 0; i < MAXI; i++) P.items[c][i] = 0;
    }
    if (SCHED_MODE == 4) {
        int qa[NCTA], nq = 0, op[NCTA], no = 0;
        for (int c = 0; c < NCTA; c++) {
            if (c < 128 && (c & 7) >= 6) op[no++] = c;
            else qa[nq++] = c;
        }
        int u = 0;
        auto put = [&](int c) {
            const int br = u >> 9, h = (u >> 4) & 31, b = u & 15;
            P.items[c][n[c]++] = mk_item(IT_QA, br, b, h, 0, 0);
            u++;
        };
        for (int c = 0; c < NCTA; c++) put(c);
        int i = 0;
        while (u < 1024 - 52) {
            put(qa[i]);
            i = (i + 1) % nq;
        }
        for (int t = 0; t < 32; t++) {
            P.items[op[t]][n[op[t]]++] = mk_item(IT_OP, 0, t >> 1, 0, 32, t & 1);
            P.items[op[t]][n[op[t]]++] = mk_item(IT_OP, 1, t >> 1, 0, HSPLIT, t & 1, 1);
        }
        for (int k = 0; k < 20; k++) {
            put(qa[i]);
            i = (i + 1) % nq;
        }
        for (int t = 0; t < 32; t++) put(op[t]);
        for (int k = 0; k < 80; k++) {
            P.items[qa[i]][n[qa[i]]++] = mk_item(IT_ON, 1, k / 5, HSPLIT, 32, k % 5);
            i = (i + 1) % nq;
        }
        return;
    }
    if (SCHED_MODE == 3) {
        int qa[NCTA], nq = 0, op[NCTA], no = 0;
        for (int c = 0; c < NCTA; c++) {
            if (c < 128 && (c & 3) == 3) op[no++] = c;
            else qa[nq++] = c;
        }
        int u = 0;
        auto put = [&](int c) {
            const int br = u >> 9, h = (u >> 4) & 31, b = u & 15;
            P.items[c][n[c]++] = mk_item(IT_QA, br, b, h, 0, 0);
            u++;
        };
        for (int c = 0; c < NCTA; c++) put(c);
        while (u < 1024)
            for (int i = 0; i < nq && u < 1024; i++) put(qa[i]);
        for (int br = 0; br < 2; br++)
            for (int t = 0; t < 32; t++) P.items[op[t]][n[op[t]]++] = mk_item(IT_OP, br, t >> 1, 0, 32, t & 1);
        return;
    }
    for (int u = 0; u < 1024; u++) {
        const int br = u >> 9, h = (u >> 4) & 31, b = u & 15;
        const int c = u % NCTA;
        if (SCHED_MODE == 2 && (c & 3)) continue;
        P.items[c][n[c]++] = mk_item(IT_QA, br, b, h, 0, 0);
    }
    if (SCHED_MODE == 0) {
        for (int t = 0; t < 64; t++) {
            const int c = NCTA - 1 - t;
            P.items[c][n[c]++] = mk_item(IT_OP, t >> 5, (t >> 1) & 15, 0, 32, t & 1);
        }
    }
}

}

extern "C" void kernel_launch(void* const* d_in, const int* in_sizes, int n_in, void* d_out, int out_size) {
    static Params P;
    static bool init = false;
    if (!init) {
        EncFn enc = nullptr;
        cudaDriverEntryPointQueryResult qr;
        cudaGetDriverEntryPoint("cuTensorMapEncodeTiled", (void**)&enc, cudaEnableDefault, &qr);
        for (int i = 0; i < 2; i++) {
            P.px[i] = (const __nv_bfloat16*)d_in[5 * i + 0];
            P.pk[i] = (const __nv_bfloat16*)d_in[5 * i + 1];
            P.pv[i] = (const __nv_bfloat16*)d_in[5 * i + 2];
            P.pwq[i] = (const __nv_bfloat16*)d_in[5 * i + 3];
            make_map3(enc, &P.x[i], d_in[5 * i + 0], 2560, 1280, 10, 160, 1);
            make_map3(enc, &P.k[i], d_in[5 * i + 1], 16 * 32 * 512, 384, 3, 64, 3);
            make_map3(enc, &P.v[i], d_in[5 * i + 2], 16 * 32 * 512, 384, 3, 64, 3);
            make_map3(enc, &P.wq[i], d_in[5 * i + 3], 640, 12288, 96, 64, 3);
            make_map3(enc, &P.wo[i], d_in[5 * i + 4], 6144, 1280, 10, 32, 5);
            make_map3(enc, &P.won[i], d_in[5 * i + 4], 6144, 1280, 10, 64, 2);
        }
        cuuint64_t dims[2] = {1280, 2560};
        cuuint64_t str[1] = {2560};
        cuuint32_t box[2] = {64, 160};
        cuuint32_t es[2] = {1, 1};
        enc(&P.out, CU_TENSOR_MAP_DATA_TYPE_BFLOAT16, 2, d_out, dims, str, box, es, CU_TENSOR_MAP_INTERLEAVE_NONE,
            CU_TENSOR_MAP_SWIZZLE_128B, CU_TENSOR_MAP_L2_PROMOTION_NONE, CU_TENSOR_MAP_FLOAT_OOB_FILL_NONE);
        build_schedule(P);
        cudaFuncSetAttribute(fused_kernel, cudaFuncAttributeMaxDynamicSharedMemorySize, SMEM_LAUNCH);
        init = true;
    }
    fused_kernel<<<NCTA, 384, SMEM_LAUNCH>>>(P);
}
```

```cpp
#include <cuda_runtime.h>
#include <cuda.h>
#include <cuda_bf16.h>
#include <stdint.h>

namespace {

constexpr int NCTA = 132;
constexpr int MAXI = 16;
constexpr int NSTAT = 6;
constexpr uint32_t IT_DYN = 0xffffffffu;
constexpr int SLOT = 24576;
constexpr int NSLOT = 5;
constexpr int XS = 20480;
constexpr int OFF_R = 0;
constexpr int OFF_RING = 5 * XS;
constexpr int OFF_MISC = OFF_RING + NSLOT * SLOT;
constexpr int OFF_LX = OFF_MISC;
constexpr int OFF_LINV = OFF_LX + 2560;
constexpr int OFF_FB = OFF_LINV + 640;
constexpr int OFF_GM = OFF_FB + 16;
constexpr int OFF_BAR = OFF_GM + 16;
constexpr int BAR_RFULL = OFF_BAR;
constexpr int BAR_REMPTY = BAR_RFULL + 40;
constexpr int BAR_XFULL = BAR_REMPTY + 40;
constexpr int BAR_XEMPTY = BAR_XFULL + 40;
constexpr int BAR_ITEM = BAR_XEMPTY + 40;
constexpr int OFF_ITEM = BAR_ITEM + MAXI * 8;
constexpr int SMEM_BYTES = OFF_ITEM + MAXI * 4;
static_assert(SMEM_BYTES <= 232448, "smem");

constexpr int NB_W = 1  , NB_PFULL = 3  , NB_VOTE = 5, NB_Q01 = 6, NB_Q2 = 7, NB_SDONE = 8, NB_PDONE = 9,
              NB_L = 10, NB_OPST = 11, NB_ODONE = 12, NB_OPEND = 13, NB_LX = 14;

constexpr uint32_t IT_QA = 1, IT_OP = 2, IT_ON = 3;
__host__ __device__ constexpr uint32_t mk_item(uint32_t type, uint32_t br, uint32_t b, uint32_t h0, uint32_t h1, uint32_t half,
                                               uint32_t part = 0) {
    return type | (br << 2) | (b << 3) | (h0 << 7) | (h1 << 13) | (half << 19) | (part << 22);
}
#define IT_TYPE(e) ((e) & 3u)
#define IT_BR(e) (((e) >> 2) & 1u)
#define IT_B(e) (((e) >> 3) & 15u)
#define IT_H0(e) (((e) >> 7) & 63u)
#define IT_H1(e) (((e) >> 13) & 63u)
#define IT_HALF(e) (((e) >> 19) & 7u)
#define IT_PART(e) (((e) >> 22) & 1u)

struct Params {
    CUtensorMap x[2], wq[2], k[2], v[2], wo[2], won[2], out;
    const __nv_bfloat16 *px[2], *pwq[2], *pk[2], *pv[2];
    uint32_t items[NCTA][NSTAT];
    uint32_t delay[NCTA];
    uint32_t nlist;
    uint32_t list[1024];
};

constexpr int OUNIT = 61440;
__device__ __align__(1024) unsigned char g_ostash[(size_t)1024 * OUNIT];
__device__ unsigned int g_flag[1024];
__device__ float4 g_part[2 * 16 * 10 * 2560];
__device__ unsigned int g_pflag[64];
#define ORING 64
__device__ __forceinline__ unsigned char* ostash(uint32_t br, uint32_t b, uint32_t h) {
    return g_ostash + (size_t)(((br * 32 + h) % ORING) * 16 + b) * OUNIT;
}
__device__ unsigned int g_epoch[NCTA];
__device__ unsigned int g_ticket[2];

constexpr int SMEM_LAUNCH = SMEM_BYTES;
#define TS(role, idx)
#define TS_DUMP(role)
#define TS2(cond, idx)

#define POL_W 2
#define POL_X 2
#define POL_O 2
template <int M>
__device__ __forceinline__ uint64_t mkpol() {
    uint64_t p;
    if (M == 0) asm volatile("createpolicy.fractional.L2::evict_normal.b64 %0, 1.0;" : "=l"(p));
    if (M == 1) asm volatile("createpolicy.fractional.L2::evict_first.b64 %0, 1.0;" : "=l"(p));
    if (M == 2) asm volatile("createpolicy.fractional.L2::evict_unchanged.b64 %0, 1.0;" : "=l"(p));
    if (M == 3) asm volatile("createpolicy.fractional.L2::evict_normal.L2::evict_unchanged.b64 %0, 0.25;" : "=l"(p));
    return p;
}
#define QHOLD 7
constexpr float SM_C = 0.07216878364870322f * 1.4426950408889634f;

__device__ __forceinline__ void mbar_init(uint32_t a, uint32_t c) {
    asm volatile("mbarrier.init.shared::cta.b64 [%0], %1;" ::"r"(a), "r"(c) : "memory");
}
__device__ __forceinline__ void mbar_expect(uint32_t a, uint32_t b) {
    asm volatile("mbarrier.arrive.expect_tx.shared::cta.b64 _, [%0], %1;" ::"r"(a), "r"(b) : "memory");
}
__device__ __forceinline__ void mbar_arrive_warp(uint32_t a, uint32_t cnt) {
    asm volatile(
        "{\n.reg .pred p;\nelect.sync _|p, 0xffffffff;\n"
        "@p mbarrier.arrive.shared::cta.b64 _, [%0], %1;\n}" ::"r"(a), "r"(cnt)
        : "memory");
}
__device__ __forceinline__ void mbar_arrive_warp_if(uint32_t a, uint32_t cnt, bool cond) {
    asm volatile(
        "{\n.reg .pred p, c;\nelect.sync _|p, 0xffffffff;\nsetp.ne.and.u32 c, %2, 0, p;\n"
        "@c mbarrier.arrive.shared::cta.b64 _, [%0], %1;\n}" ::"r"(a), "r"(cnt), "r"((uint32_t)cond)
        : "memory");
}
__device__ __forceinline__ void mbar_wait(uint32_t a, uint32_t ph) {
    asm volatile(
        "{\n.reg .pred p;\n.reg .u32 n, m;\n"
        "mbarrier.try_wait.parity.shared::cta.b64 p, [%0], %1;\n"
        "@p bra DONE;\n"
        "mov.u32 n, %%clock_hi;\n"
        "LOOP:\n"
        "mbarrier.try_wait.parity.shared::cta.b64 p, [%0], %1;\n"
        "@p bra DONE;\n"
        "mov.u32 m, %%clock_hi;\n"
        "sub.u32 m, m, n;\n"
        "setp.lt.u32 p, m, 2;\n"
        "@p bra LOOP;\n"
        "trap;\n"
        "DONE:\n}" ::"r"(a), "r"(ph)
        : "memory");
}
template <int ID, int CNT>
__device__ __forceinline__ void nb_sync() { asm volatile("bar.sync %0, %1;" ::"n"(ID), "n"(CNT) : "memory"); }
template <int ID, int CNT>
__device__ __forceinline__ void nb_arrive() { asm volatile("bar.arrive %0, %1;" ::"n"(ID), "n"(CNT) : "memory"); }
__device__ __forceinline__ void fence_async_smem() { asm volatile("fence.proxy.async.shared::cta;" ::: "memory"); }

__device__ __forceinline__ void tma3(uint32_t dst, const CUtensorMap* m, int c1, int c2, uint32_t bar, uint64_t pol) {
    asm volatile(
        "cp.async.bulk.tensor.3d.shared::cluster.global.mbarrier::complete_tx::bytes.L2::cache_hint [%0], [%1, {%3,%4,%5}], [%2], %6;" ::"r"(dst),
        "l"(m), "r"(bar), "r"(0), "r"(c1), "r"(c2), "l"(pol)
        : "memory");
}
__device__ __forceinline__ void bulk_load(uint32_t dst, const void* src, uint32_t bytes, uint32_t bar, uint64_t pol) {
    asm volatile("cp.async.bulk.shared::cluster.global.mbarrier::complete_tx::bytes.L2::cache_hint [%0], [%1], %2, [%3], %4;" ::"r"(dst),
                 "l"(src), "r"(bytes), "r"(bar), "l"(pol)
                 : "memory");
}
__device__ __forceinline__ void wg_fence() { asm volatile("wgmma.fence.sync.aligned;" ::: "memory"); }
__device__ __forceinline__ void wg_commit() { asm volatile("wgmma.commit_group.sync.aligned;" ::: "memory"); }
template <int N>
__device__ __forceinline__ void wg_wait() { asm volatile("wgmma.wait_group.sync.aligned %0;" ::"n"(N) : "memory"); }

#define RW80(c, d) c(d[0]), c(d[1]), c(d[2]), c(d[3]), c(d[4]), c(d[5]), c(d[6]), c(d[7]), c(d[8]), c(d[9]), c(d[10]), c(d[11]), c(d[12]), c(d[13]), c(d[14]), c(d[15]), c(d[16]), c(d[17]), c(d[18]), c(d[19]), c(d[20]), c(d[21]), c(d[22]), c(d[23]), c(d[24]), c(d[25]), c(d[26]), c(d[27]), c(d[28]), c(d[29]), c(d[30]), c(d[31]), c(d[32]), c(d[33]), c(d[34]), c(d[35]), c(d[36]), c(d[37]), c(d[38]), c(d[39]), c(d[40]), c(d[41]), c(d[42]), c(d[43]), c(d[44]), c(d[45]), c(d[46]), c(d[47]), c(d[48]), c(d[49]), c(d[50]), c(d[51]), c(d[52]), c(d[53]), c(d[54]), c(d[55]), c(d[56]), c(d[57]), c(d[58]), c(d[59]), c(d[60]), c(d[61]), c(d[62]), c(d[63]), c(d[64]), c(d[65]), c(d[66]), c(d[67]), c(d[68]), c(d[69]), c(d[70]), c(d[71]), c(d[72]), c(d[73]), c(d[74]), c(d[75]), c(d[76]), c(d[77]), c(d[78]), c(d[79])
#define RW48(c, d) c(d[0]), c(d[1]), c(d[2]), c(d[3]), c(d[4]), c(d[5]), c(d[6]), c(d[7]), c(d[8]), c(d[9]), c(d[10]), c(d[11]), c(d[12]), c(d[13]), c(d[14]), c(d[15]), c(d[16]), c(d[17]), c(d[18]), c(d[19]), c(d[20]), c(d[21]), c(d[22]), c(d[23]), c(d[24]), c(d[25]), c(d[26]), c(d[27]), c(d[28]), c(d[29]), c(d[30]), c(d[31]), c(d[32]), c(d[33]), c(d[34]), c(d[35]), c(d[36]), c(d[37]), c(d[38]), c(d[39]), c(d[40]), c(d[41]), c(d[42]), c(d[43]), c(d[44]), c(d[45]), c(d[46]), c(d[47])
#define RW32(c, d) c(d[0]), c(d[1]), c(d[2]), c(d[3]), c(d[4]), c(d[5]), c(d[6]), c(d[7]), c(d[8]), c(d[9]), c(d[10]), c(d[11]), c(d[12]), c(d[13]), c(d[14]), c(d[15]), c(d[16]), c(d[17]), c(d[18]), c(d[19]), c(d[20]), c(d[21]), c(d[22]), c(d[23]), c(d[24]), c(d[25]), c(d[26]), c(d[27]), c(d[28]), c(d[29]), c(d[30]), c(d[31])

__device__ __forceinline__ void reg_fence(float (&d)[80]) { asm volatile("" : RW80("+f", d)::"memory"); }
__device__ __forceinline__ void reg_fence(float (&d)[48]) { asm volatile("" : RW48("+f", d)::"memory"); }
__device__ __forceinline__ void reg_fence(float (&d)[32]) { asm volatile("" : RW32("+f", d)::"memory"); }

constexpr uint32_t HI_SW128 = (1024u >> 4) | (1u << 30);
constexpr uint32_t HI_OST = (2560u >> 4) | (2u << 30);
constexpr uint32_t LO_LBO1 = (1u << 16);
constexpr uint32_t LO_OST = ((512u >> 4) << 16);

template <int TA, int TB, uint32_t HIB, bool ACC>
__device__ __forceinline__ void wgmma(float (&d)[80], uint32_t loA, uint32_t loB) {
#define WG_ASM(SD)                                                          \
    "{\n.reg .b64 da, db;\nmov.b64 da, {%80, %82};\nmov.b64 db, {%81, %83};\n" \
    "wgmma.mma_async.sync.aligned.m64n160k16.f32.bf16.bf16 "               \
    "{%0,%1,%2,%3,%4,%5,%6,%7,%8,%9,%10,%11,%12,%13,%14,%15,%16,%17,%18,%19,%20,%21,%22,%23,%24,%25,%26,%27,%28,%29,%30,%31,%32,%33,%34,%35,%36,%37,%38,%39,%40,%41,%42,%43,%44,%45,%46,%47,%48,%49,%50,%51,%52,%53,%54,%55,%56,%57,%58,%59,%60,%61,%62,%63,%64,%65,%66,%67,%68,%69,%70,%71,%72,%73,%74,%75,%76,%77,%78,%79}, da, db, " SD ", 1, 1, %84, %85;\n}"
    if constexpr (ACC)
        asm volatile(WG_ASM("1") : RW80("+f", d) : "r"(loA), "r"(loB), "n"(HI_SW128), "n"(HIB), "n"(TA), "n"(TB));
    else
        asm volatile(WG_ASM("0") : RW80("=f", d) : "r"(loA), "r"(loB), "n"(HI_SW128), "n"(HIB), "n"(TA), "n"(TB));
#undef WG_ASM
}
template <int TA, int TB, uint32_t HIB, bool ACC>
__device__ __forceinline__ void wgmma(float (&d)[48], uint32_t loA, uint32_t loB) {
#define WG_ASM(SD)                                                          \
    "{\n.reg .b64 da, db;\nmov.b64 da, {%48, %50};\nmov.b64 db, {%49, %51};\n" \
    "wgmma.mma_async.sync.aligned.m64n96k16.f32.bf16.bf16 "               \
    "{%0,%1,%2,%3,%4,%5,%6,%7,%8,%9,%10,%11,%12,%13,%14,%15,%16,%17,%18,%19,%20,%21,%22,%23,%24,%25,%26,%27,%28,%29,%30,%31,%32,%33,%34,%35,%36,%37,%38,%39,%40,%41,%42,%43,%44,%45,%46,%47}, da, db, " SD ", 1, 1, %52, %53;\n}"
    if constexpr (ACC)
        asm volatile(WG_ASM("1") : RW48("+f", d) : "r"(loA), "r"(loB), "n"(HI_SW128), "n"(HIB), "n"(TA), "n"(TB));
    else
        asm volatile(WG_ASM("0") : RW48("=f", d) : "r"(loA), "r"(loB), "n"(HI_SW128), "n"(HIB), "n"(TA), "n"(TB));
#undef WG_ASM
}
template <int TA, int TB, uint32_t HIB, bool ACC>
__device__ __forceinline__ void wgmma(float (&d)[32], uint32_t loA, uint32_t loB) {
#define WG_ASM(SD)                                                          \
    "{\n.reg .b64 da, db;\nmov.b64 da, {%32, %34};\nmov.b64 db, {%33, %35};\n" \
    "wgmma.mma_async.sync.aligned.m64n64k16.f32.bf16.bf16 "               \
    "{%0,%1,%2,%3,%4,%5,%6,%7,%8,%9,%10,%11,%12,%13,%14,%15,%16,%17,%18,%19,%20,%21,%22,%23,%24,%25,%26,%27,%28,%29,%30,%31}, da, db, " SD ", 1, 1, %36, %37;\n}"
    if constexpr (ACC)
        asm volatile(WG_ASM("1") : RW32("+f", d) : "r"(loA), "r"(loB), "n"(HI_SW128), "n"(HIB), "n"(TA), "n"(TB));
    else
        asm volatile(WG_ASM("0") : RW32("=f", d) : "r"(loA), "r"(loB), "n"(HI_SW128), "n"(HIB), "n"(TA), "n"(TB));
#undef WG_ASM
}

__device__ __forceinline__ uint32_t pack_bf16(float lo, float hi) {
    uint32_t r;
    asm("cvt.rn.bf16x2.f32 %0, %1, %2;" : "=r"(r) : "f"(hi), "f"(lo));
    return r;
}
__device__ __forceinline__ float ex2(float x) {
    float r;
    asm("ex2.approx.ftz.f32 %0, %1;" : "=f"(r) : "f"(x));
    return r;
}
__device__ __forceinline__ void stsm4t(uint32_t a, uint32_t r0, uint32_t r1, uint32_t r2, uint32_t r3) {
    asm volatile("stmatrix.sync.aligned.m8n8.x4.trans.shared.b16 [%0], {%1,%2,%3,%4};" ::"r"(a), "r"(r0), "r"(r1), "r"(r2), "r"(r3)
                 : "memory");
}
__device__ __forceinline__ uint32_t lds_u(uint32_t a) {
    uint32_t v;
    asm volatile("ld.shared.u32 %0, [%1];" : "=r"(v) : "r"(a) : "memory");
    return v;
}
__device__ __forceinline__ float2 lds_f2(uint32_t a) {
    float2 v;
    asm volatile("ld.shared.v2.f32 {%0,%1}, [%2];" : "=f"(v.x), "=f"(v.y) : "r"(a) : "memory");
    return v;
}
__device__ __forceinline__ void sts_f(uint32_t a, float v) { asm volatile("st.shared.f32 [%0], %1;" ::"r"(a), "f"(v) : "memory"); }
__device__ __forceinline__ void sts_u(uint32_t a, uint32_t v) { asm volatile("st.shared.u32 [%0], %1;" ::"r"(a), "r"(v) : "memory"); }
__device__ __forceinline__ void sts_f2(uint32_t a, float x, float y) {
    asm volatile("st.shared.v2.f32 [%0], {%1,%2};" ::"r"(a), "f"(x), "f"(y) : "memory");
}

__device__ __forceinline__ void store_tile_t(const float (&d)[80], uint32_t addr) {
#pragma unroll
    for (int j = 0; j < 10; j++)
        stsm4t(addr + j * 2048, pack_bf16(d[8 * j], d[8 * j + 1]), pack_bf16(d[8 * j + 2], d[8 * j + 3]),
               pack_bf16(d[8 * j + 4], d[8 * j + 5]), pack_bf16(d[8 * j + 6], d[8 * j + 7]));
}
template <int NR>
__device__ __forceinline__ void store_out_tile(const float (&d)[NR], uint32_t base, uint32_t lane, uint32_t w) {
    const uint32_t mi = lane >> 3, i = lane & 7;
    const uint32_t chunk = 2 * w + (mi & 1);
    const uint32_t q0 = 8 * (i >> 1) + 2 * (mi >> 1) + (i & 1);
    const uint32_t a0 = base + q0 * 128 + ((chunk ^ (q0 & 7)) << 4);
    const uint32_t a1 = base + (q0 + 4) * 128 + ((chunk ^ ((q0 + 4) & 7)) << 4);
#pragma unroll
    for (int j = 0; j < NR / 8; j++)
        stsm4t(((j & 1) ? a1 : a0) + (j >> 1) * 4096, pack_bf16(d[8 * j], d[8 * j + 1]), pack_bf16(d[8 * j + 2], d[8 * j + 3]),
               pack_bf16(d[8 * j + 4], d[8 * j + 5]), pack_bf16(d[8 * j + 6], d[8 * j + 7]));
}

struct TrueT { static constexpr bool value = true; };
struct FalseT { static constexpr bool value = false; };

template <int V>
struct IntT { static constexpr int value = V; };

__device__ __forceinline__ uint32_t get_item(uint32_t sb, int it) {
    mbar_wait(sb + BAR_ITEM + it * 8, 0);
    return lds_u(sb + OFF_ITEM + it * 4);
}
__device__ __forceinline__ uint32_t get_item_warp(uint32_t sb, int it) { return __shfl_sync(0xffffffffu, get_item(sb, it), 0); }

struct Ring {
    uint32_t slot, ph;
    __device__ __forceinline__ void adv(uint32_t k) {
        slot += k;
        if (slot >= NSLOT) { slot -= NSLOT; ph ^= 1; }
    }
};

template <int K>
__device__ __forceinline__ void qk_step(float (&s)[80], uint32_t loK, uint32_t loQ) {
    wgmma<0, 0, HI_SW128, K != 0>(s, loK + (K >> 2) * (8192 >> 4) + (K & 3) * 2, loQ + (K >> 2) * (XS >> 4) + (K & 3) * 2);
}
template <int K0, int K1>
__device__ __forceinline__ void qk_steps(float (&s)[80], uint32_t loK, uint32_t loQ) {
    if constexpr (K0 < K1) {
        qk_step<K0>(s, loK, loQ);
        qk_steps<K0 + 1, K1>(s, loK, loQ);
    }
}
template <int J>
__device__ __forceinline__ void exp_chunk(const float (&s)[80], float (&ps)[40], uint32_t pa, float mref) {
    float p[8];
#pragma unroll
    for (int i = 0; i < 8; i++) p[i] = ex2(fmaf(s[8 * J + i], SM_C, -mref));
    stsm4t(pa + J * 2048, pack_bf16(p[0], p[1]), pack_bf16(p[2], p[3]), pack_bf16(p[4], p[5]), pack_bf16(p[6], p[7]));
    ps[4 * J] = p[0] + p[2];
    ps[4 * J + 1] = p[1] + p[3];
    ps[4 * J + 2] = p[4] + p[6];
    ps[4 * J + 3] = p[5] + p[7];
}
template <int J>
__device__ __forceinline__ void exp_block(const float (&s)[80], float (&ps)[40], uint32_t pa, float mref) {
    if constexpr (J < 10) {
        exp_chunk<J>(s, ps, pa, mref);
        exp_block<J + 1>(s, ps, pa, mref);
    }
}
__device__ __forceinline__ void sum_block(const float (&ps)[40], float (&l)[5], uint32_t lane) {
    const bool b4 = lane & 16, b3 = lane & 8, b2 = lane & 4;
    float t[20];
#pragma unroll
    for (int j = 0; j < 10; j++) {
        t[2 * j] = (b4 ? ps[4 * j + 2] : ps[4 * j]) + __shfl_xor_sync(0xffffffffu, b4 ? ps[4 * j] : ps[4 * j + 2], 16);
        t[2 * j + 1] = (b4 ? ps[4 * j + 3] : ps[4 * j + 1]) + __shfl_xor_sync(0xffffffffu, b4 ? ps[4 * j + 1] : ps[4 * j + 3], 16);
    }
#pragma unroll
    for (int i = 0; i < 10; i++) t[i] = (b3 ? t[i + 10] : t[i]) + __shfl_xor_sync(0xffffffffu, b3 ? t[i] : t[i + 10], 8);
#pragma unroll
    for (int i = 0; i < 5; i++)
        l[i] += (b2 ? t[2 * i + 1] : t[2 * i]) + __shfl_xor_sync(0xffffffffu, b2 ? t[2 * i] : t[2 * i + 1], 4);
}

__device__ __forceinline__ void fallback_unit(const Params& P, uint32_t e, uint32_t tid) {
    const uint32_t lane = tid & 31, br = IT_BR(e), b = IT_B(e), h = IT_H0(e);
    const __nv_bfloat162* wq = (const __nv_bfloat162*)(P.pwq[br] + h * 192) + lane;
    const __nv_bfloat162* kp = (const __nv_bfloat162*)(P.pk[br] + (size_t)(b * 32 + h) * 512 * 192) + lane;
    const __nv_bfloat162* vp = (const __nv_bfloat162*)(P.pv[br] + (size_t)(b * 32 + h) * 512 * 192) + lane;
#pragma unroll 1
    for (uint32_t q = tid >> 5; q < 160; q += 4) {
        const __nv_bfloat16* xr = P.px[br] + (size_t)(b * 160 + q) * 640;
        float a[6] = {0.f, 0.f, 0.f, 0.f, 0.f, 0.f};
#pragma unroll 4
        for (int k = 0; k < 640; k++) {
            const float xv = __bfloat162float(xr[k]);
#pragma unroll
            for (int i = 0; i < 3; i++) {
                const float2 wv = __bfloat1622float2(wq[(size_t)k * 3072 + i * 32]);
                a[2 * i] = fmaf(xv, wv.x, a[2 * i]);
                a[2 * i + 1] = fmaf(xv, wv.y, a[2 * i + 1]);
            }
        }
#pragma unroll
        for (int i = 0; i < 6; i++) a[i] = __bfloat162float(__float2bfloat16(a[i]));
        auto score = [&](int key) {
            float d = 0.f;
#pragma unroll
            for (int i = 0; i < 3; i++) {
                const float2 kv = __bfloat1622float2(kp[key * 96 + i * 32]);
                d = fmaf(a[2 * i], kv.x, fmaf(a[2 * i + 1], kv.y, d));
            }
#pragma unroll
            for (int o = 16; o > 0; o >>= 1) d += __shfl_xor_sync(0xffffffffu, d, o);
            return d;
        };
        float m = -INFINITY;
#pragma unroll 4
        for (int key = 0; key < 512; key++) m = fmaxf(m, score(key));
        float o[6] = {0.f, 0.f, 0.f, 0.f, 0.f, 0.f}, sum = 0.f;
#pragma unroll 4
        for (int key = 0; key < 512; key++) {
            const float p = ex2((score(key) - m) * SM_C);
            sum += p;
#pragma unroll
            for (int i = 0; i < 3; i++) {
                const float2 vv = __bfloat1622float2(vp[key * 96 + i * 32]);
                o[2 * i] = fmaf(p, vv.x, o[2 * i]);
                o[2 * i + 1] = fmaf(p, vv.y, o[2 * i + 1]);
            }
        }
        const float inv = 1.f / sum;
        __nv_bfloat16* op = (__nv_bfloat16*)ostash(br, b, h) + (q >> 5) * 256 + 2 * ((q & 31) >> 3) + (q & 1);
#pragma unroll
        for (int i = 0; i < 6; i++) {
            const uint32_t d = (i >> 1) * 64 + 2 * lane + (i & 1);
            op[(d >> 3) * 1280 + (d & 7) * 32 + ((((q & 7) >> 1) ^ ((d & 7) >> 1)) << 3)] = __float2bfloat16(o[i] * inv);
        }
    }
}

template <int W>
struct PendO {
    static constexpr int N = W == 0 ? 14 : 16;
    uint32_t v[4 * N];
    unsigned char* gp;
    uint32_t pend;
    template <int I>
    __device__ __forceinline__ void store() const {
        if constexpr (I < N) {
            constexpr int g = I < 10 ? I / 2 : (I - 10) / 2 + (W == 0 ? 3 : 0);
            constexpr int off = (I < 10 ? W : 2) * XS + g * 512 + (I & 1) * 2560;
            asm volatile(
                "{\n.reg .pred p;\nsetp.ne.u32 p, %6, 0;\n@p st.global.v4.b32 [%0+%5], {%1,%2,%3,%4};\n}" ::"l"(gp),
                "r"(v[4 * I]), "r"(v[4 * I + 1]), "r"(v[4 * I + 2]), "r"(v[4 * I + 3]), "n"(off), "r"(pend)
                : "memory");
        }
    }
    template <int I>
    __device__ __forceinline__ void flush() const {
        if constexpr (I < N) {
            store<I>();
            flush<I + 1>();
        }
    }
    __device__ __forceinline__ void clear() {
#pragma unroll
        for (int i = 0; i < 4 * N; i++) v[i] = 0;
        gp = nullptr;
        pend = 0;
    }
};

template <int W, int KK>
__device__ __forceinline__ void qproj(float (&q0)[80], float (&q1)[80], uint32_t sb, Ring& r, uint32_t phm, const PendO<W>& po) {
    const uint32_t loR = ((sb + OFF_R) >> 4) | LO_LBO1;
    const uint32_t loRing = ((sb + OFF_RING) >> 4) | LO_LBO1;
    constexpr int xs = KK % 5;
    const uint32_t pslot = r.slot;
    if (KK > 0) r.adv(1);
    if (W == 1 && KK == QHOLD) nb_sync<NB_SDONE, 256>();
    mbar_wait(sb + BAR_RFULL + r.slot * 8, r.ph);
    mbar_wait(sb + BAR_XFULL + xs * 8, ((phm >> xs) ^ (KK / 5)) & 1);
    const uint32_t a = loRing + r.slot * (SLOT >> 4) + (W == 0 ? 0 : 1024), b = loR + xs * (XS >> 4);
    wg_fence();
    wgmma<1, 0, HI_SW128, KK != 0>(q0, a, b);
    if (W == 0) wgmma<1, 0, HI_SW128, KK != 0>(q1, a + 512, b);
#pragma unroll
    for (int k = 1; k < 4; k++) {
        wgmma<1, 0, HI_SW128, true>(q0, a + k * 128, b + k * 2);
        if (W == 0) wgmma<1, 0, HI_SW128, true>(q1, a + 512 + k * 128, b + k * 2);
    }
    wg_commit();
    if (KK > 0) {
        wg_wait<1>();
        mbar_arrive_warp(sb + BAR_REMPTY + pslot * 8, 1);
        if (KK <= 5) mbar_arrive_warp(sb + (BAR_XEMPTY + (KK - 1) * 8), 1);
        if (W == 1 && KK == 7) nb_arrive<NB_PDONE, 256>();
    }
    if (KK < 6) {
        po.template store<3 * KK>();
        po.template store<3 * KK + 1>();
        po.template store<3 * KK + 2>();
        if (KK == 5 && po.pend) nb_arrive<NB_ODONE, 288>();
    }
    if constexpr (KK < 9) {
        qproj<W, KK + 1>(q0, q1, sb, r, phm, po);
    } else {
        if (W == 0) nb_arrive<NB_SDONE, 256>();
        wg_wait<0>();
        reg_fence(q0);
        if (W == 0) reg_fence(q1);
        mbar_arrive_warp(sb + BAR_REMPTY + r.slot * 8, 1);
        r.adv(1);
    }
}

template <int NR>
__device__ __forceinline__ void opack(const float (&o)[NR], int gl, const float2* sc, uint32_t* v) {
#pragma unroll
    for (int hh = 0; hh < 2; hh++)
#pragma unroll
        for (int t = 0; t < 4; t++)
            v[4 * hh + t] = pack_bf16(o[16 * gl + 4 * t + 2 * hh] * sc[t].x, o[16 * gl + 4 * t + 2 * hh + 1] * sc[t].y);
}

template <int NR>
__device__ __forceinline__ void dump_acc(const float (&c)[NR], float4* p) {
#pragma unroll
    for (int i = 0; i < NR / 4; i++) p[i * 128] = make_float4(c[4 * i], c[4 * i + 1], c[4 * i + 2], c[4 * i + 3]);
}
__device__ __forceinline__ void wait_flag(const unsigned int* f, uint32_t epoch) {
    uint32_t v, n = 0;
    do {
        asm volatile("ld.acquire.gpu.global.u32 %0, [%1];" : "=r"(v) : "l"(f) : "memory");
        if (++n > 0x400000) __trap();
    } while (v != epoch);
}

template <bool IS_S>
__device__ __forceinline__ void op_item(uint32_t e, uint32_t sb, Ring& r, uint32_t& phm) {
    constexpr int T0 = IS_S ? 0 : 2;
    constexpr uint32_t BOFF = IS_S ? (3 * 512) >> 4 : 0;
    const uint32_t loRing = ((sb + OFF_RING) >> 4) | LO_LBO1;
    const uint32_t loO = ((sb + OFF_R) >> 4) | LO_OST;
    float c0[80], c1[80], c2[IS_S ? 32 : 48];
    const int T2 = 6 * (IT_H1(e) - IT_H0(e));
    uint32_t xs = 0;
    auto step = [&](auto first, uint32_t hf) {
        constexpr bool F = decltype(first)::value;
        if (hf == 0) {
            mbar_wait(sb + BAR_XFULL + xs * 8, (phm >> xs) & 1);
            phm ^= 1u << xs;
        }
        mbar_wait(sb + BAR_RFULL + r.slot * 8, r.ph);
        const uint32_t a = loRing + r.slot * (SLOT >> 4), b = loO + xs * (XS >> 4) + hf * 640;
        wg_fence();
        wgmma<1, 1, HI_OST, !F>(c0, a + T0 * 256, b);
        wgmma<1, 1, HI_OST, !F>(c1, a + T0 * 256 + 256, b);
        wgmma<1, 1, HI_OST, !F>(c2, a + 1024, b + BOFF);
        wgmma<1, 1, HI_OST, true>(c0, a + T0 * 256 + 128, b + 320);
        wgmma<1, 1, HI_OST, true>(c1, a + T0 * 256 + 384, b + 320);
        wgmma<1, 1, HI_OST, true>(c2, a + 1024 + 128, b + 320 + BOFF);
        wg_commit();
    };
    step(TrueT{}, 0);
#pragma unroll 1
    for (int t = 1; t < T2; t++) {
        const uint32_t pslot = r.slot, pxs = xs;
        r.adv(1);
        if ((t & 1) == 0 && ++xs == 5) xs = 0;
        step(FalseT{}, t & 1);
        wg_wait<1>();
        mbar_arrive_warp(sb + BAR_REMPTY + pslot * 8, 1);
        if ((t & 1) == 0 && t + 8 < T2) mbar_arrive_warp(sb + BAR_XEMPTY + pxs * 8, 1);
    }
    wg_wait<0>();
    reg_fence(c0);
    reg_fence(c1);
    reg_fence(c2);
    mbar_arrive_warp(sb + BAR_REMPTY + r.slot * 8, 1);
    r.adv(1);
    if (IT_PART(e)) {
#pragma unroll
        for (int m = 0; m < 5; m++) mbar_arrive_warp(sb + BAR_XEMPTY + m * 8, 1);
        float4* pp = g_part + (size_t)((IT_BR(e) * 16 + IT_B(e)) * 10 + IT_HALF(e) * 5) * 2560 + (threadIdx.x & 127);
        dump_acc(c0, pp + T0 * 2560);
        dump_acc(c1, pp + (T0 + 1) * 2560);
        dump_acc(c2, pp + 4 * 2560 + (IS_S ? 12 * 128 : 0));
    } else {
        nb_sync<NB_OPEND, 256>();
        const uint32_t lane = threadIdx.x & 31, w = (threadIdx.x >> 5) & 3;
        store_out_tile(c0, sb + OFF_R + T0 * XS, lane, w);
        store_out_tile(c1, sb + OFF_R + (T0 + 1) * XS, lane, w);
        store_out_tile(c2, sb + OFF_R + 4 * XS + (IS_S ? 96 * 128 : 0), lane, w);
        fence_async_smem();
    }
    nb_arrive<NB_ODONE, 288>();
}

template <int W>
__device__ __forceinline__ void on_item(uint32_t e, uint32_t sb, Ring& r, uint32_t& phm, uint32_t epoch) {
    const uint32_t loRing = ((sb + OFF_RING) >> 4) | LO_LBO1;
    const uint32_t loO = ((sb + OFF_R) >> 4) | LO_OST;
    float c[80];
    const int T = 3 * (IT_H1(e) - IT_H0(e));
    uint32_t xs = 0;
    auto step = [&](auto first) {
        constexpr bool F = decltype(first)::value;
        mbar_wait(sb + BAR_XFULL + xs * 8, (phm >> xs) & 1);
        phm ^= 1u << xs;
        mbar_wait(sb + BAR_RFULL + r.slot * 8, r.ph);
        const uint32_t a = loRing + r.slot * (SLOT >> 4) + W * 512, b = loO + xs * (XS >> 4);
        wg_fence();
        wgmma<1, 1, HI_OST, !F>(c, a, b);
#pragma unroll
        for (int k = 1; k < 4; k++) wgmma<1, 1, HI_OST, true>(c, a + k * 128, b + k * 320);
        wg_commit();
    };
    auto run = [&](int t0, int t1) {
#pragma unroll 1
        for (int t = t0; t < t1; t++) {
            const uint32_t pslot = r.slot, pxs = xs;
            r.adv(1);
            if (++xs == 5) xs = 0;
            step(FalseT{});
            wg_wait<1>();
            mbar_arrive_warp(sb + BAR_REMPTY + pslot * 8, 1);
            mbar_arrive_warp_if(sb + BAR_XEMPTY + pxs * 8, 1, t + 4 < T);
        }
    };
    step(TrueT{});
    const int tm = T >> 1;
    run(1, tm);
    float4 pv[20];
    {
        const uint32_t tile = 2 * IT_HALF(e) + W, bb = IT_BR(e) * 16 + IT_B(e);
        wait_flag(&g_pflag[bb * 2 + (tile >= 5)], epoch);
        const float4* pp = g_part + (size_t)(bb * 10 + tile) * 2560 + (threadIdx.x & 127);
#pragma unroll
        for (int i = 0; i < 20; i++) pv[i] = __ldcg(pp + i * 128);
    }
    run(tm, T);
    wg_wait<0>();
    reg_fence(c);
    mbar_arrive_warp(sb + BAR_REMPTY + r.slot * 8, 1);
    r.adv(1);
    nb_sync<NB_OPEND, 256>();
#pragma unroll
    for (int i = 0; i < 20; i++) {
        c[4 * i] += pv[i].x;
        c[4 * i + 1] += pv[i].y;
        c[4 * i + 2] += pv[i].z;
        c[4 * i + 3] += pv[i].w;
    }
    store_out_tile(c, sb + OFF_R + W * XS, threadIdx.x & 31, (threadIdx.x >> 5) & 3);
    fence_async_smem();
    nb_arrive<NB_ODONE, 288>();
}

template <int W>
__device__ __forceinline__ uint32_t qa_item(const Params& P, uint32_t sb, Ring& r, uint32_t phm, PendO<W>& po, int it) {
    const uint32_t loR = ((sb + OFF_R) >> 4) | LO_LBO1;
    const uint32_t loRing = ((sb + OFF_RING) >> 4) | LO_LBO1;
    const uint32_t lane = threadIdx.x & 31, w = (threadIdx.x >> 5) & 3;
    const uint32_t sta = sb + OFF_R + (lane >> 4) * 1024 + (lane & 7) * 128 + (((2 * w + ((lane >> 3) & 1)) ^ (lane & 7)) << 4);
    {
        float q0[80], q1[80];
        qproj<W, 0>(q0, q1, sb, r, phm, po);
        TS(W, 1);
        if (W == 0) {
            nb_sync<NB_PDONE, 256>();
            store_tile_t(q0, sta);
            store_tile_t(q1, sta + XS);
        } else {
            store_tile_t(q0, sta + 2 * XS);
        }
    }
    fence_async_smem();
    float s[80], oa[80], ob[W == 0 ? 32 : 48], l[5];
#pragma unroll
    for (int i = 0; i < 80; i++) oa[i] = 0.f;
#pragma unroll
    for (int i = 0; i < (W == 0 ? 32 : 48); i++) ob[i] = 0.f;
#pragma unroll
    for (int i = 0; i < 5; i++) l[i] = 0.f;
    reg_fence(oa);
    reg_fence(ob);
    auto pv = [&](uint32_t buf) {
        mbar_wait(sb + BAR_RFULL + r.slot * 8, r.ph);
        const uint32_t a = loRing + r.slot * (SLOT >> 4), b = loR + (3 + buf) * (XS >> 4);
        wg_fence();
#pragma unroll
        for (int k = 0; k < 4; k++) {
            wgmma<1, 0, HI_SW128, true>(oa, a + W * 512 + k * 128, b + k * 2);
            wgmma<1, 0, HI_SW128, true>(ob, a + 1024 + k * 128, b + (W == 0 ? (96 * 128) >> 4 : 0) + k * 2);
        }
        wg_commit();
    };
    float mref;
    uint32_t kslot, vslot;
    const uint32_t lxa = sb + OFF_LX + w * 640 + (((lane & 8) ? 80 : 0) + ((lane >> 1) & 8) + 2 * (lane & 3) + ((lane >> 2) & 1)) * 4;
    auto tail = [&](bool rel_other, int i) {
        float ps[40];
        exp_block<0>(s, ps, sta + (3 + W) * XS, mref);
        if (rel_other) {
            wg_wait<0>();
            mbar_arrive_warp(sb + BAR_REMPTY + vslot * 8, 1);
            if (W == 1) mbar_arrive_warp_if(sb + BAR_XEMPTY + 24, 1, i == 3);
        }
        fence_async_smem();
        nb_arrive<NB_PFULL + W, 256>();
        TS(W, 6 + 5 * i);
        mbar_wait(sb + BAR_RFULL + r.slot * 8, r.ph);
        sum_block(ps, l, lane);
        if (W == 1 && i == 3) {
            nb_sync<NB_LX, 256>();
#pragma unroll
            for (int k = 0; k < 5; k++) sts_f(lxa + k * 64, l[k]);
            nb_arrive<NB_L, 256>();
        }
        nb_sync<NB_W + W, 128>();
        TS(W, 7 + 5 * i);
        pv(W);
        TS(W, 8 + 5 * i);
    };
    if (W == 0) {
        nb_sync<NB_W, 128>();
        TS(W, 2);
        mbar_wait(sb + BAR_RFULL + r.slot * 8, r.ph);
        wg_fence();
        qk_steps<0, 8>(s, loRing + r.slot * (SLOT >> 4), loR);
        nb_sync<NB_Q2, 256>();
        qk_steps<8, 12>(s, loRing + r.slot * (SLOT >> 4), loR);
        wg_commit();
        nb_arrive<NB_Q01, 256>();
        TS(W, 4);
        wg_wait<0>();
        reg_fence(s);
        mbar_arrive_warp(sb + BAR_REMPTY + r.slot * 8, 2);
        r.adv(2);
        float m0 = fmaxf(s[0], s[5]), m1 = fmaxf(s[10], s[15]);
#pragma unroll
        for (int i = 20; i < 80; i += 10) {
            m0 = fmaxf(m0, s[i]);
            m1 = fmaxf(m1, s[i + 5]);
        }
        int key = __float_as_int(fmaxf(m0, m1));
        key ^= (key >> 31) & 0x7fffffff;
        key = __reduce_max_sync(0xffffffffu, key);
        key ^= (key >> 31) & 0x7fffffff;
        sts_u(sb + OFF_GM + w * 4, key);
        sts_u(sb + OFF_FB, 0);
        nb_sync<NB_W, 128>();
        const float2 u = lds_f2(sb + OFF_GM), v = lds_f2(sb + OFF_GM + 8);
        mref = fmaxf(fmaxf(u.x, u.y), fmaxf(v.x, v.y)) * SM_C;
        TS(W, 5);
        tail(false, 0);
    } else {
        nb_arrive<NB_Q2, 256>();
        TS(W, 2);
        nb_sync<NB_Q01, 256>();
    }
#pragma unroll 1
    for (int i = (W == 0 ? 1 : 0); i < 4; i++) {
        const uint32_t pvslot = r.slot;
        r.adv(1);
        kslot = r.slot;
        mbar_wait(sb + BAR_RFULL + r.slot * 8, r.ph);
        wg_fence();
        qk_steps<0, 12>(s, loRing + r.slot * (SLOT >> 4), loR);
        wg_commit();
        wg_wait<1>();
        mbar_arrive_warp_if(sb + BAR_REMPTY + pvslot * 8, 1, W == 0 || i > 0);
        r.adv(1);
        vslot = r.slot;
        TS(W, 4 + 5 * i);
        nb_sync<NB_PFULL + (W ^ 1), 256>();
        pv(W ^ 1);
        if (W == 1) {
            const float2 u = lds_f2(sb + OFF_GM), v = lds_f2(sb + OFF_GM + 8);
            mref = fmaxf(fmaxf(u.x, u.y), fmaxf(v.x, v.y)) * SM_C;
        }
        wg_wait<1>();
        reg_fence(s);
        mbar_arrive_warp(sb + BAR_REMPTY + kslot * 8, 2);
        if (W == 1) {
            mbar_arrive_warp_if(sb + BAR_XEMPTY + 0, 2, i == 3);
            mbar_arrive_warp_if(sb + BAR_XEMPTY + 8, 2, i == 3);
            mbar_arrive_warp_if(sb + BAR_XEMPTY + 16, 2, i == 3);
        }
        r.adv(W == 1 && i == 3 ? 1 : 2);
        TS(W, 5 + 5 * i);
        tail(true, i);
    }
    if (W == 0) {
        const uint32_t tid = threadIdx.x & 127;
        float2 v = make_float2(0.f, 0.f);
        auto gather = [&]() {
            if (tid < 80) {
#pragma unroll
                for (int i = 0; i < 4; i++) {
                    const float2 u = lds_f2(sb + OFF_LX + i * 640 + tid * 8);
                    v.x += u.x;
                    v.y += u.y;
                }
            }
        };
#pragma unroll
        for (int i = 0; i < 5; i++) sts_f(lxa + i * 64, l[i]);
        nb_sync<NB_W, 128>();
        gather();
        nb_arrive<NB_LX, 256>();
        wg_wait<0>();
        mbar_arrive_warp(sb + BAR_REMPTY + r.slot * 8, 1);
        mbar_arrive_warp(sb + BAR_XEMPTY + 24, 1);
        r.adv(1);
        nb_sync<NB_PFULL + 1, 256>();
        pv(1);
        TS(W, 24);
        nb_sync<NB_L, 256>();
        gather();
        if (tid < 80) {
            sts_f2(sb + OFF_LINV + tid * 8, __fdividef(1.f, v.x), __fdividef(1.f, v.y));
            if (!(v.x >= 5.421010862e-20f && v.x <= 1.8446744e19f && v.y >= 5.421010862e-20f && v.y <= 1.8446744e19f))
                sts_u(sb + OFF_FB, 1);
        }
    }
    nb_sync<NB_VOTE, 256>();
    const bool any = __any_sync(0xffffffffu, lds_u(sb + OFF_FB) != 0);
    const uint32_t e = lds_u(sb + OFF_ITEM + it * 4), nx = get_item_warp(sb, it + 1);
    float2 sc[20];
#pragma unroll
    for (int t = 0; t < 20; t++) sc[t] = lds_f2(sb + OFF_LINV + (lane & 3) * 8 + t * 32);
    wg_wait<0>();
    reg_fence(oa);
    reg_fence(ob);
    mbar_arrive_warp(sb + BAR_REMPTY + r.slot * 8, 1);
    mbar_arrive_warp(sb + BAR_XEMPTY + 32, 1);
    r.adv(1);
    TS(W, 25);
#pragma unroll
    for (int g = 0; g < 5; g++) {
        opack(oa, g, sc + 4 * g, po.v + 8 * g);
        if (W == 0 && g >= 3) opack(ob, g - 3, sc + 4 * g, po.v + 40 + 8 * (g - 3));
        if (W == 1 && g < 3) opack(ob, g, sc + 4 * g, po.v + 40 + 8 * g);
    }
    po.gp = ostash(IT_BR(e), IT_B(e), IT_H0(e)) + w * 5120 + (lane >> 2) * 64 +
            (((lane ^ (lane >> 3)) & 3) << 4);
    po.pend = 1;
    if (any || IT_TYPE(nx) != IT_QA) {
        if (!any) po.template flush<0>();
        else if (W == 1) fallback_unit(P, e, threadIdx.x & 127);
        nb_arrive<NB_ODONE, 288>();
        po.pend = 0;
    }
    return nx;
}

__global__ void __launch_bounds__(384, 1) fused_kernel(const __grid_constant__ Params P) {
    extern __shared__ __align__(1024) unsigned char smem_raw[];
    const uint32_t sb = (uint32_t)__cvta_generic_to_shared(smem_raw);
    const uint32_t wgid = __shfl_sync(0xffffffffu, threadIdx.x >> 7, 0);
    const uint32_t cta = blockIdx.x;

    uint32_t epoch = 0;
    if (wgid == 0) epoch = *(volatile unsigned int*)&g_epoch[cta] + 1;
    if (threadIdx.x == 0) {
        if (sb & 1023) __trap();
        sts_u(sb + OFF_FB + 4, epoch);
        for (int i = 0; i < NSLOT; i++) {
            mbar_init(sb + BAR_RFULL + i * 8, 1);
            mbar_init(sb + BAR_REMPTY + i * 8, 8);
            mbar_init(sb + BAR_XFULL + i * 8, 1);
            mbar_init(sb + BAR_XEMPTY + i * 8, 8);
        }
        for (int i = 0; i < MAXI; i++) mbar_init(sb + BAR_ITEM + i * 8, 1);
        asm volatile("fence.mbarrier_init.release.cluster;" ::: "memory");
        fence_async_smem();
    }
    __syncthreads();

    if (wgid == 0) {
        asm volatile("setmaxnreg.dec.sync.aligned.u32 24;");
        const uint32_t warp = __shfl_sync(0xffffffffu, threadIdx.x >> 5, 0);
        if (warp == 0) {
            if (threadIdx.x == 0) {
                *(volatile unsigned int*)&g_epoch[cta] = epoch;
                const uint64_t pol_first = mkpol<1>(), pol_norm = mkpol<POL_W>();
                if (cta == 0) *(volatile unsigned int*)&g_ticket[(epoch + 1) & 1] = 0;
                Ring r{0, 1};
                {
                    const uint32_t d = P.delay[cta];
                    uint32_t t0, t1;
                    asm volatile("mov.u32 %0, %%clock;" : "=r"(t0));
                    do {
                        asm volatile("mov.u32 %0, %%clock;" : "=r"(t1));
                    } while (t1 - t0 < d);
                }
                uint32_t e = P.items[cta][0];
#pragma unroll 1
                for (int it = 0;; it++) {
                    sts_u(sb + OFF_ITEM + it * 4, e);
                    asm volatile("mbarrier.arrive.shared::cta.b64 _, [%0];" ::"r"(sb + BAR_ITEM + it * 8) : "memory");
                    if (e == 0) break;
                    uint32_t nx = P.items[cta][it + 1 < NSTAT ? it + 1 : NSTAT - 1];
                    if (IT_TYPE(e) == IT_ON || it + 2 == MAXI) nx = 0;
                    const uint32_t br = IT_BR(e);
                    if (IT_TYPE(e) == IT_QA) {
                        const uint32_t h = IT_H0(e);
#pragma unroll 1
                        for (int kk = 0; kk < 10; kk++) {
                            mbar_wait(sb + BAR_REMPTY + r.slot * 8, r.ph);
                            mbar_expect(sb + BAR_RFULL + r.slot * 8, SLOT);
                            tma3(sb + OFF_RING + r.slot * SLOT, &P.wq[br], kk * 64, h * 3, sb + BAR_RFULL + r.slot * 8, pol_norm);
                            r.adv(1);
                        }
                        const int row0 = (IT_B(e) * 32 + h) * 512;
#pragma unroll 1
                        for (int n = 0; n < 16; n++) {
                            if (n == 12 && nx == IT_DYN) {
                                const uint32_t t = atomicAdd(&g_ticket[epoch & 1], 1);
                                nx = t < P.nlist ? P.list[t] : 0;
                            }
                            const bool isv = n == 15 || (n > 0 && !(n & 1));
                            const int j = n == 15 ? 7 : isv ? (n - 2) >> 1 : (n + 1) >> 1;
                            mbar_wait(sb + BAR_REMPTY + r.slot * 8, r.ph);
                            mbar_expect(sb + BAR_RFULL + r.slot * 8, SLOT);
                            tma3(sb + OFF_RING + r.slot * SLOT, isv ? &P.v[br] : &P.k[br], row0 + j * 64, 0,
                                 sb + BAR_RFULL + r.slot * 8, pol_first);
                            r.adv(1);
                        }
                    } else {
                        const int r0 = IT_H0(e) * 192, r1 = IT_H1(e) * 192;
                        const bool wide = IT_TYPE(e) == IT_OP;
#pragma unroll 1
                        for (int row = r0; row < r1; row += wide ? 32 : 64) {
                            mbar_wait(sb + BAR_REMPTY + r.slot * 8, r.ph);
                            mbar_expect(sb + BAR_RFULL + r.slot * 8, wide ? XS : 16384);
                            tma3(sb + OFF_RING + r.slot * SLOT, wide ? &P.wo[br] : &P.won[br], row, IT_HALF(e) * (wide ? 5 : 2),
                                 sb + BAR_RFULL + r.slot * 8, pol_norm);
                            r.adv(1);
                        }
                        if (nx == IT_DYN) {
                            const uint32_t t = atomicAdd(&g_ticket[epoch & 1], 1);
                            nx = t < P.nlist ? P.list[t] : 0;
                        }
                    }
                    e = nx;
                }
            }
        } else if (warp == 1) {
            if (threadIdx.x == 32) {
                const uint64_t pol_norm = mkpol<POL_X>(), pol_o = mkpol<POL_O>();
                uint32_t phm = 0x1f;
#pragma unroll 1
                for (int it = 0;; it++) {
                    const uint32_t e = get_item(sb, it);
                    if (e == 0) break;
                    const uint32_t br = IT_BR(e);
                    uint32_t xs = 0;
                    if (IT_TYPE(e) == IT_QA) {
#pragma unroll 1
                        for (int kk = 0; kk < 10; kk++) {
                            mbar_wait(sb + BAR_XEMPTY + xs * 8, (phm >> xs) & 1);
                            phm ^= 1u << xs;
                            mbar_expect(sb + BAR_XFULL + xs * 8, XS);
                            tma3(sb + OFF_R + xs * XS, &P.x[br], IT_B(e) * 160, kk, sb + BAR_XFULL + xs * 8, pol_norm);
                            if (++xs == 5) xs = 0;
                        }
                    } else {
                        const uint32_t u0 = (br * 16 + IT_B(e)) * 32;
#pragma unroll 1
                        for (uint32_t u = u0 + IT_H0(e); u < u0 + IT_H1(e); u++) {
                            wait_flag(&g_flag[u], epoch);
                            asm volatile("fence.proxy.async;" ::: "memory");
#pragma unroll 1
                            for (int t = 0; t < 3; t++) {
                                mbar_wait(sb + BAR_XEMPTY + xs * 8, (phm >> xs) & 1);
                                phm ^= 1u << xs;
                                mbar_expect(sb + BAR_XFULL + xs * 8, XS);
                                bulk_load(sb + OFF_R + xs * XS, ostash(br, IT_B(e), u & 31) + t * XS, XS, sb + BAR_XFULL + xs * 8, pol_o);
                                if (++xs == 5) xs = 0;
                            }
                        }
                    }
                }
            }
        } else if (warp == 2) {
#pragma unroll 1
            for (int it = 0;; it++) {
                const uint32_t e = get_item_warp(sb, it);
                if (e == 0) break;
                nb_sync<NB_ODONE, 288>();
                if (threadIdx.x == 64) {
                    const uint32_t bb = IT_BR(e) * 16 + IT_B(e);
                    if (IT_TYPE(e) == IT_QA || IT_PART(e)) {
                        __threadfence();
                        unsigned int* f = IT_TYPE(e) == IT_QA ? &g_flag[bb * 32 + IT_H0(e)] : &g_pflag[bb * 2 + IT_HALF(e)];
                        asm volatile("st.relaxed.gpu.global.u32 [%0], %1;" ::"l"(f), "r"(epoch) : "memory");
                    } else {
                        const int nt = IT_TYPE(e) == IT_OP ? 5 : 2;
                        const int cc0 = IT_BR(e) * 640 + IT_HALF(e) * nt * 64;
#pragma unroll
                        for (int m = 0; m < 5; m++) {
                            if (m < nt)
                                asm volatile("cp.async.bulk.tensor.2d.global.shared::cta.bulk_group [%0, {%2,%3}], [%1];" ::"l"(&P.out),
                                             "r"(sb + OFF_R + m * XS), "r"(cc0 + m * 64), "r"((int)IT_B(e) * 160)
                                             : "memory");
                            asm volatile("cp.async.bulk.commit_group;" ::: "memory");
                        }
#define REL(N)                                                          \
    asm volatile("cp.async.bulk.wait_group.read %0;" ::"n"(4 - N) : "memory"); \
    asm volatile("mbarrier.arrive.shared::cta.b64 _, [%0], 8;" ::"r"(sb + BAR_XEMPTY + N * 8) : "memory");
                        REL(0) REL(1) REL(2) REL(3) REL(4)
#undef REL
                    }
                }
                __syncwarp();
            }
            if (threadIdx.x == 64) asm volatile("cp.async.bulk.wait_group 0;" ::: "memory");
        }
    } else if (wgid == 1) {
        asm volatile("setmaxnreg.inc.sync.aligned.u32 240;");
        PendO<0> po;
        po.clear();
        Ring r{0, 0};
        uint32_t phm = 0;
        uint32_t e = get_item_warp(sb, 0);
#pragma unroll 1
        for (int it = 0; e != 0; it++) {
            TS(0, 0);
            if (IT_TYPE(e) == IT_QA) {
                e = qa_item<0>(P, sb, r, phm, po, it);
            } else {
                if (IT_TYPE(e) == IT_OP) op_item<true>(e, sb, r, phm);
                else on_item<0>(e, sb, r, phm, lds_u(sb + OFF_FB + 4));
                po.clear();
                e = get_item_warp(sb, it + 1);
            }
            TS(0, 31);
        }
        TS_DUMP(0);
    } else {
        asm volatile("setmaxnreg.inc.sync.aligned.u32 240;");
        PendO<1> po;
        po.clear();
        Ring r{0, 0};
        uint32_t phm = 0;
        uint32_t e = get_item_warp(sb, 0);
#pragma unroll 1
        for (int it = 0; e != 0; it++) {
            TS(1, 0);
            if (IT_TYPE(e) == IT_QA) {
                e = qa_item<1>(P, sb, r, phm, po, it);
            } else {
                if (IT_TYPE(e) == IT_OP) op_item<false>(e, sb, r, phm);
                else on_item<1>(e, sb, r, phm, lds_u(sb + OFF_FB + 4));
                po.clear();
                e = get_item_warp(sb, it + 1);
            }
            TS(1, 31);
        }
        TS_DUMP(1);
    }
}

typedef CUresult (*EncFn)(CUtensorMap*, CUtensorMapDataType, cuuint32_t, void*, const cuuint64_t*, const cuuint64_t*,
                          const cuuint32_t*, const cuuint32_t*, CUtensorMapInterleave, CUtensorMapSwizzle,
                          CUtensorMapL2promotion, CUtensorMapFloatOOBfill);

void make_map3(EncFn enc, CUtensorMap* m, void* p, uint64_t rows, uint64_t rowbytes, uint64_t nblk, uint32_t boxrows,
               uint32_t boxblk) {
    cuuint64_t dims[3] = {64, rows, nblk};
    cuuint64_t str[2] = {rowbytes, 128};
    cuuint32_t box[3] = {64, boxrows, boxblk};
    cuuint32_t es[3] = {1, 1, 1};
    enc(m, CU_TENSOR_MAP_DATA_TYPE_BFLOAT16, 3, p, dims, str, box, es, CU_TENSOR_MAP_INTERLEAVE_NONE,
        CU_TENSOR_MAP_SWIZZLE_128B, CU_TENSOR_MAP_L2_PROMOTION_NONE, CU_TENSOR_MAP_FLOAT_OOB_FILL_NONE);
}

#define SCHED_MODE 4
#define HSPLIT 14
#define DELAY_MAX 28000
#define DELAY_N0 0

void build_schedule(Params& P) {
    int u = 0;
    auto unit = [&]() {
        const uint32_t e = mk_item(IT_QA, u >> 9, u & 15, (u >> 4) & 31, 0, 0);
        u++;
        return e;
    };
    int qa[NCTA], nq = 0, op[NCTA], no = 0;
    for (int c = 0; c < NCTA; c++) {
        P.delay[c] = 0;
        for (int i = 0; i < NSTAT; i++) P.items[c][i] = 0;
        if (SCHED_MODE >= 3 && c < 128 && (c & 7) >= 6) op[no++] = c;
        else if (SCHED_MODE != 2 || (c & 3) == 0) qa[nq++] = c;
    }
    for (int t = 0; t < no; t++) P.items[op[t]][0] = unit();
    for (int k = 0; k < nq; k++) {
        const int c = qa[(k * 37) % nq];
        P.items[c][0] = unit();
        for (int i = 1; i < NSTAT; i++) P.items[c][i] = IT_DYN;
        P.delay[c] = k < DELAY_N0 ? 0 : (int)((long long)DELAY_MAX * (k + 1 - DELAY_N0) / (nq - DELAY_N0));
    }
    int n = 0;
    const int uend = SCHED_MODE == 2 ? 8 * nq : 1024 - no;
    while (u < uend) P.list[n++] = unit();
    for (int t = 0; t < no; t++) {
        P.items[op[t]][1] = mk_item(IT_OP, 0, t >> 1, 0, 32, t & 1);
        P.items[op[t]][2] = mk_item(IT_OP, 1, t >> 1, 0, HSPLIT, t & 1, 1);
        P.items[op[t]][3] = unit();
    }
    if (no)
        for (int k = 0; k < 80; k++) P.list[n++] = mk_item(IT_ON, 1, k / 5, HSPLIT, 32, k % 5);
    P.nlist = n;
}

}

extern "C" void kernel_launch(void* const* d_in, const int* in_sizes, int n_in, void* d_out, int out_size) {
    static Params P;
    static bool init = false;
    if (!init) {
        EncFn enc = nullptr;
        cudaDriverEntryPointQueryResult qr;
        cudaGetDriverEntryPoint("cuTensorMapEncodeTiled", (void**)&enc, cudaEnableDefault, &qr);
        for (int i = 0; i < 2; i++) {
            P.px[i] = (const __nv_bfloat16*)d_in[5 * i + 0];
            P.pk[i] = (const __nv_bfloat16*)d_in[5 * i + 1];
            P.pv[i] = (const __nv_bfloat16*)d_in[5 * i + 2];
            P.pwq[i] = (const __nv_bfloat16*)d_in[5 * i + 3];
            make_map3(enc, &P.x[i], d_in[5 * i + 0], 2560, 1280, 10, 160, 1);
            make_map3(enc, &P.k[i], d_in[5 * i + 1], 16 * 32 * 512, 384, 3, 64, 3);
            make_map3(enc, &P.v[i], d_in[5 * i + 2], 16 * 32 * 512, 384, 3, 64, 3);
            make_map3(enc, &P.wq[i], d_in[5 * i + 3], 640, 12288, 96, 64, 3);
            make_map3(enc, &P.wo[i], d_in[5 * i + 4], 6144, 1280, 10, 32, 5);
            make_map3(enc, &P.won[i], d_in[5 * i + 4], 6144, 1280, 10, 64, 2);
        }
        cuuint64_t dims[2] = {1280, 2560};
        cuuint64_t str[1] = {2560};
        cuuint32_t box[2] = {64, 160};
        cuuint32_t es[2] = {1, 1};
        enc(&P.out, CU_TENSOR_MAP_DATA_TYPE_BFLOAT16, 2, d_out, dims, str, box, es, CU_TENSOR_MAP_INTERLEAVE_NONE,
            CU_TENSOR_MAP_SWIZZLE_128B, CU_TENSOR_MAP_L2_PROMOTION_NONE, CU_TENSOR_MAP_FLOAT_OOB_FILL_NONE);
        build_schedule(P);
        cudaFuncSetAttribute(fused_kernel, cudaFuncAttributeMaxDynamicSharedMemorySize, SMEM_LAUNCH);
        init = true;
    }
    fused_kernel<<<NCTA, 384, SMEM_LAUNCH>>>(P);
}
```

```cpp
#include <cuda_runtime.h>
#include <cuda.h>
#include <cuda_bf16.h>
#include <stdint.h>

namespace {

constexpr int NCTA = 132;
constexpr int MAXI = 16;
constexpr int NSTAT = 6;
constexpr uint32_t IT_DYN = 0xffffffffu;
constexpr int SLOT = 24576;
constexpr int NSLOT = 5;
constexpr int XS = 20480;
constexpr int OFF_R = 0;
constexpr int OFF_RING = 5 * XS;
constexpr int OFF_MISC = OFF_RING + NSLOT * SLOT;
constexpr int OFF_LX = OFF_MISC;
constexpr int OFF_LINV = OFF_LX + 2560;
constexpr int OFF_FB = OFF_LINV + 640;
constexpr int OFF_GM = OFF_FB + 16;
constexpr int OFF_BAR = OFF_GM + 16;
constexpr int BAR_RFULL = OFF_BAR;
constexpr int BAR_REMPTY = BAR_RFULL + 40;
constexpr int BAR_XFULL = BAR_REMPTY + 40;
constexpr int BAR_XEMPTY = BAR_XFULL + 40;
constexpr int BAR_ITEM = BAR_XEMPTY + 40;
constexpr int OFF_ITEM = BAR_ITEM + MAXI * 8;
constexpr int SMEM_BYTES = OFF_ITEM + MAXI * 4;
static_assert(SMEM_BYTES <= 232448, "smem");

constexpr int NB_W = 1  , NB_PFULL = 3  , NB_VOTE = 5, NB_Q01 = 6, NB_Q2 = 7, NB_SDONE = 8, NB_PDONE = 9,
              NB_L = 10, NB_OPST = 11, NB_ODONE = 12, NB_OPEND = 13, NB_LX = 14;

constexpr uint32_t IT_QA = 1, IT_OP = 2, IT_ON = 3;
__host__ __device__ constexpr uint32_t mk_item(uint32_t type, uint32_t br, uint32_t b, uint32_t h0, uint32_t h1, uint32_t half,
                                               uint32_t part = 0) {
    return type | (br << 2) | (b << 3) | (h0 << 7) | (h1 << 13) | (half << 19) | (part << 22);
}
#define IT_TYPE(e) ((e) & 3u)
#define IT_BR(e) (((e) >> 2) & 1u)
#define IT_B(e) (((e) >> 3) & 15u)
#define IT_H0(e) (((e) >> 7) & 63u)
#define IT_H1(e) (((e) >> 13) & 63u)
#define IT_HALF(e) (((e) >> 19) & 7u)
#define IT_PART(e) (((e) >> 22) & 1u)

struct Params {
    CUtensorMap x[2], wq[2], k[2], v[2], wo[2], won[2], out;
    const __nv_bfloat16 *px[2], *pwq[2], *pk[2], *pv[2];
    uint32_t items[NCTA][NSTAT];
    uint32_t delay[NCTA];
    uint32_t nlist;
    uint32_t list[1024];
};

constexpr int OUNIT = 61440;
__device__ __align__(1024) unsigned char g_ostash[(size_t)1024 * OUNIT];
__device__ unsigned int g_flag[1024];
__device__ float4 g_part[2 * 16 * 10 * 2560];
__device__ unsigned int g_pflag[64];
#define ORING 64
__device__ __forceinline__ unsigned char* ostash(uint32_t br, uint32_t b, uint32_t h) {
    return g_ostash + (size_t)(((br * 32 + h) % ORING) * 16 + b) * OUNIT;
}
__device__ unsigned int g_epoch[NCTA];
__device__ unsigned int g_ticket[2];

constexpr int SMEM_LAUNCH = SMEM_BYTES;
#define TS(role, idx)
#define TS_DUMP(role)
#define TS2(cond, idx)

#define POL_W 2
#define POL_X 2
#define POL_O 2
template <int M>
__device__ __forceinline__ uint64_t mkpol() {
    uint64_t p;
    if (M == 0) asm volatile("createpolicy.fractional.L2::evict_normal.b64 %0, 1.0;" : "=l"(p));
    if (M == 1) asm volatile("createpolicy.fractional.L2::evict_first.b64 %0, 1.0;" : "=l"(p));
    if (M == 2) asm volatile("createpolicy.fractional.L2::evict_unchanged.b64 %0, 1.0;" : "=l"(p));
    if (M == 3) asm volatile("createpolicy.fractional.L2::evict_normal.L2::evict_unchanged.b64 %0, 0.25;" : "=l"(p));
    return p;
}
#define QPRE 3
#define QHOLD 7
constexpr float SM_C = 0.07216878364870322f * 1.4426950408889634f;

__device__ __forceinline__ void mbar_init(uint32_t a, uint32_t c) {
    asm volatile("mbarrier.init.shared::cta.b64 [%0], %1;" ::"r"(a), "r"(c) : "memory");
}
__device__ __forceinline__ void mbar_expect(uint32_t a, uint32_t b) {
    asm volatile("mbarrier.arrive.expect_tx.shared::cta.b64 _, [%0], %1;" ::"r"(a), "r"(b) : "memory");
}
__device__ __forceinline__ void mbar_arrive_warp(uint32_t a, uint32_t cnt) {
    asm volatile(
        "{\n.reg .pred p;\nelect.sync _|p, 0xffffffff;\n"
        "@p mbarrier.arrive.shared::cta.b64 _, [%0], %1;\n}" ::"r"(a), "r"(cnt)
        : "memory");
}
__device__ __forceinline__ void mbar_arrive_warp_if(uint32_t a, uint32_t cnt, bool cond) {
    asm volatile(
        "{\n.reg .pred p, c;\nelect.sync _|p, 0xffffffff;\nsetp.ne.and.u32 c, %2, 0, p;\n"
        "@c mbarrier.arrive.shared::cta.b64 _, [%0], %1;\n}" ::"r"(a), "r"(cnt), "r"((uint32_t)cond)
        : "memory");
}
__device__ __forceinline__ void mbar_wait(uint32_t a, uint32_t ph) {
    asm volatile(
        "{\n.reg .pred p;\n.reg .u32 n, m;\n"
        "mbarrier.try_wait.parity.shared::cta.b64 p, [%0], %1;\n"
        "@p bra DONE;\n"
        "mov.u32 n, %%clock_hi;\n"
        "LOOP:\n"
        "mbarrier.try_wait.parity.shared::cta.b64 p, [%0], %1;\n"
        "@p bra DONE;\n"
        "mov.u32 m, %%clock_hi;\n"
        "sub.u32 m, m, n;\n"
        "setp.lt.u32 p, m, 2;\n"
        "@p bra LOOP;\n"
        "trap;\n"
        "DONE:\n}" ::"r"(a), "r"(ph)
        : "memory");
}
template <int ID, int CNT>
__device__ __forceinline__ void nb_sync() { asm volatile("bar.sync %0, %1;" ::"n"(ID), "n"(CNT) : "memory"); }
template <int ID, int CNT>
__device__ __forceinline__ void nb_arrive() { asm volatile("bar.arrive %0, %1;" ::"n"(ID), "n"(CNT) : "memory"); }
__device__ __forceinline__ void fence_async_smem() { asm volatile("fence.proxy.async.shared::cta;" ::: "memory"); }

__device__ __forceinline__ void tma3(uint32_t dst, const CUtensorMap* m, int c1, int c2, uint32_t bar, uint64_t pol) {
    asm volatile(
        "cp.async.bulk.tensor.3d.shared::cluster.global.mbarrier::complete_tx::bytes.L2::cache_hint [%0], [%1, {%3,%4,%5}], [%2], %6;" ::"r"(dst),
        "l"(m), "r"(bar), "r"(0), "r"(c1), "r"(c2), "l"(pol)
        : "memory");
}
__device__ __forceinline__ void bulk_load(uint32_t dst, const void* src, uint32_t bytes, uint32_t bar, uint64_t pol) {
    asm volatile("cp.async.bulk.shared::cluster.global.mbarrier::complete_tx::bytes.L2::cache_hint [%0], [%1], %2, [%3], %4;" ::"r"(dst),
                 "l"(src), "r"(bytes), "r"(bar), "l"(pol)
                 : "memory");
}
__device__ __forceinline__ void wg_fence() { asm volatile("wgmma.fence.sync.aligned;" ::: "memory"); }
__device__ __forceinline__ void wg_commit() { asm volatile("wgmma.commit_group.sync.aligned;" ::: "memory"); }
template <int N>
__device__ __forceinline__ void wg_wait() { asm volatile("wgmma.wait_group.sync.aligned %0;" ::"n"(N) : "memory"); }

#define RW80(c, d) c(d[0]), c(d[1]), c(d[2]), c(d[3]), c(d[4]), c(d[5]), c(d[6]), c(d[7]), c(d[8]), c(d[9]), c(d[10]), c(d[11]), c(d[12]), c(d[13]), c(d[14]), c(d[15]), c(d[16]), c(d[17]), c(d[18]), c(d[19]), c(d[20]), c(d[21]), c(d[22]), c(d[23]), c(d[24]), c(d[25]), c(d[26]), c(d[27]), c(d[28]), c(d[29]), c(d[30]), c(d[31]), c(d[32]), c(d[33]), c(d[34]), c(d[35]), c(d[36]), c(d[37]), c(d[38]), c(d[39]), c(d[40]), c(d[41]), c(d[42]), c(d[43]), c(d[44]), c(d[45]), c(d[46]), c(d[47]), c(d[48]), c(d[49]), c(d[50]), c(d[51]), c(d[52]), c(d[53]), c(d[54]), c(d[55]), c(d[56]), c(d[57]), c(d[58]), c(d[59]), c(d[60]), c(d[61]), c(d[62]), c(d[63]), c(d[64]), c(d[65]), c(d[66]), c(d[67]), c(d[68]), c(d[69]), c(d[70]), c(d[71]), c(d[72]), c(d[73]), c(d[74]), c(d[75]), c(d[76]), c(d[77]), c(d[78]), c(d[79])
#define RW48(c, d) c(d[0]), c(d[1]), c(d[2]), c(d[3]), c(d[4]), c(d[5]), c(d[6]), c(d[7]), c(d[8]), c(d[9]), c(d[10]), c(d[11]), c(d[12]), c(d[13]), c(d[14]), c(d[15]), c(d[16]), c(d[17]), c(d[18]), c(d[19]), c(d[20]), c(d[21]), c(d[22]), c(d[23]), c(d[24]), c(d[25]), c(d[26]), c(d[27]), c(d[28]), c(d[29]), c(d[30]), c(d[31]), c(d[32]), c(d[33]), c(d[34]), c(d[35]), c(d[36]), c(d[37]), c(d[38]), c(d[39]), c(d[40]), c(d[41]), c(d[42]), c(d[43]), c(d[44]), c(d[45]), c(d[46]), c(d[47])
#define RW32(c, d) c(d[0]), c(d[1]), c(d[2]), c(d[3]), c(d[4]), c(d[5]), c(d[6]), c(d[7]), c(d[8]), c(d[9]), c(d[10]), c(d[11]), c(d[12]), c(d[13]), c(d[14]), c(d[15]), c(d[16]), c(d[17]), c(d[18]), c(d[19]), c(d[20]), c(d[21]), c(d[22]), c(d[23]), c(d[24]), c(d[25]), c(d[26]), c(d[27]), c(d[28]), c(d[29]), c(d[30]), c(d[31])

__device__ __forceinline__ void reg_fence(float (&d)[80]) { asm volatile("" : RW80("+f", d)::"memory"); }
__device__ __forceinline__ void reg_fence(float (&d)[48]) { asm volatile("" : RW48("+f", d)::"memory"); }
__device__ __forceinline__ void reg_fence(float (&d)[32]) { asm volatile("" : RW32("+f", d)::"memory"); }

template <int NR>
__device__ __forceinline__ void zero(float (&d)[NR]) {
#pragma unroll
    for (int i = 0; i < NR; i++) d[i] = 0.f;
}

constexpr uint32_t HI_SW128 = (1024u >> 4) | (1u << 30);
constexpr uint32_t HI_OST = (2560u >> 4) | (2u << 30);
constexpr uint32_t LO_LBO1 = (1u << 16);
constexpr uint32_t LO_OST = ((512u >> 4) << 16);

template <int TA, int TB, uint32_t HIB, bool ACC>
__device__ __forceinline__ void wgmma(float (&d)[80], uint32_t loA, uint32_t loB) {
#define WG_ASM(SD)                                                          \
    "{\n.reg .b64 da, db;\nmov.b64 da, {%80, %82};\nmov.b64 db, {%81, %83};\n" \
    "wgmma.mma_async.sync.aligned.m64n160k16.f32.bf16.bf16 "               \
    "{%0,%1,%2,%3,%4,%5,%6,%7,%8,%9,%10,%11,%12,%13,%14,%15,%16,%17,%18,%19,%20,%21,%22,%23,%24,%25,%26,%27,%28,%29,%30,%31,%32,%33,%34,%35,%36,%37,%38,%39,%40,%41,%42,%43,%44,%45,%46,%47,%48,%49,%50,%51,%52,%53,%54,%55,%56,%57,%58,%59,%60,%61,%62,%63,%64,%65,%66,%67,%68,%69,%70,%71,%72,%73,%74,%75,%76,%77,%78,%79}, da, db, " SD ", 1, 1, %84, %85;\n}"
    if constexpr (ACC)
        asm volatile(WG_ASM("1") : RW80("+f", d) : "r"(loA), "r"(loB), "n"(HI_SW128), "n"(HIB), "n"(TA), "n"(TB));
    else
        asm volatile(WG_ASM("0") : RW80("=f", d) : "r"(loA), "r"(loB), "n"(HI_SW128), "n"(HIB), "n"(TA), "n"(TB));
#undef WG_ASM
}
template <int TA, int TB, uint32_t HIB, bool ACC>
__device__ __forceinline__ void wgmma(float (&d)[48], uint32_t loA, uint32_t loB) {
#define WG_ASM(SD)                                                          \
    "{\n.reg .b64 da, db;\nmov.b64 da, {%48, %50};\nmov.b64 db, {%49, %51};\n" \
    "wgmma.mma_async.sync.aligned.m64n96k16.f32.bf16.bf16 "               \
    "{%0,%1,%2,%3,%4,%5,%6,%7,%8,%9,%10,%11,%12,%13,%14,%15,%16,%17,%18,%19,%20,%21,%22,%23,%24,%25,%26,%27,%28,%29,%30,%31,%32,%33,%34,%35,%36,%37,%38,%39,%40,%41,%42,%43,%44,%45,%46,%47}, da, db, " SD ", 1, 1, %52, %53;\n}"
    if constexpr (ACC)
        asm volatile(WG_ASM("1") : RW48("+f", d) : "r"(loA), "r"(loB), "n"(HI_SW128), "n"(HIB), "n"(TA), "n"(TB));
    else
        asm volatile(WG_ASM("0") : RW48("=f", d) : "r"(loA), "r"(loB), "n"(HI_SW128), "n"(HIB), "n"(TA), "n"(TB));
#undef WG_ASM
}
template <int TA, int TB, uint32_t HIB, bool ACC>
__device__ __forceinline__ void wgmma(float (&d)[32], uint32_t loA, uint32_t loB) {
#define WG_ASM(SD)                                                          \
    "{\n.reg .b64 da, db;\nmov.b64 da, {%32, %34};\nmov.b64 db, {%33, %35};\n" \
    "wgmma.mma_async.sync.aligned.m64n64k16.f32.bf16.bf16 "               \
    "{%0,%1,%2,%3,%4,%5,%6,%7,%8,%9,%10,%11,%12,%13,%14,%15,%16,%17,%18,%19,%20,%21,%22,%23,%24,%25,%26,%27,%28,%29,%30,%31}, da, db, " SD ", 1, 1, %36, %37;\n}"
    if constexpr (ACC)
        asm volatile(WG_ASM("1") : RW32("+f", d) : "r"(loA), "r"(loB), "n"(HI_SW128), "n"(HIB), "n"(TA), "n"(TB));
    else
        asm volatile(WG_ASM("0") : RW32("=f", d) : "r"(loA), "r"(loB), "n"(HI_SW128), "n"(HIB), "n"(TA), "n"(TB));
#undef WG_ASM
}

__device__ __forceinline__ uint32_t pack_bf16(float lo, float hi) {
    uint32_t r;
    asm("cvt.rn.bf16x2.f32 %0, %1, %2;" : "=r"(r) : "f"(hi), "f"(lo));
    return r;
}
__device__ __forceinline__ float ex2(float x) {
    float r;
    asm("ex2.approx.ftz.f32 %0, %1;" : "=f"(r) : "f"(x));
    return r;
}
__device__ __forceinline__ void stsm4t(uint32_t a, uint32_t r0, uint32_t r1, uint32_t r2, uint32_t r3) {
    asm volatile("stmatrix.sync.aligned.m8n8.x4.trans.shared.b16 [%0], {%1,%2,%3,%4};" ::"r"(a), "r"(r0), "r"(r1), "r"(r2), "r"(r3)
                 : "memory");
}
__device__ __forceinline__ uint32_t lds_u(uint32_t a) {
    uint32_t v;
    asm volatile("ld.shared.u32 %0, [%1];" : "=r"(v) : "r"(a) : "memory");
    return v;
}
__device__ __forceinline__ float2 lds_f2(uint32_t a) {
    float2 v;
    asm volatile("ld.shared.v2.f32 {%0,%1}, [%2];" : "=f"(v.x), "=f"(v.y) : "r"(a) : "memory");
    return v;
}
__device__ __forceinline__ void sts_f(uint32_t a, float v) { asm volatile("st.shared.f32 [%0], %1;" ::"r"(a), "f"(v) : "memory"); }
__device__ __forceinline__ void sts_u(uint32_t a, uint32_t v) { asm volatile("st.shared.u32 [%0], %1;" ::"r"(a), "r"(v) : "memory"); }
__device__ __forceinline__ void sts_f2(uint32_t a, float x, float y) {
    asm volatile("st.shared.v2.f32 [%0], {%1,%2};" ::"r"(a), "f"(x), "f"(y) : "memory");
}

__device__ __forceinline__ void store_tile_t(const float (&d)[80], uint32_t addr) {
#pragma unroll
    for (int j = 0; j < 10; j++)
        stsm4t(addr + j * 2048, pack_bf16(d[8 * j], d[8 * j + 1]), pack_bf16(d[8 * j + 2], d[8 * j + 3]),
               pack_bf16(d[8 * j + 4], d[8 * j + 5]), pack_bf16(d[8 * j + 6], d[8 * j + 7]));
}
template <int NR>
__device__ __forceinline__ void store_out_tile(const float (&d)[NR], uint32_t base, uint32_t lane, uint32_t w) {
    const uint32_t mi = lane >> 3, i = lane & 7;
    const uint32_t chunk = 2 * w + (mi & 1);
    const uint32_t q0 = 8 * (i >> 1) + 2 * (mi >> 1) + (i & 1);
    const uint32_t a0 = base + q0 * 128 + ((chunk ^ (q0 & 7)) << 4);
    const uint32_t a1 = base + (q0 + 4) * 128 + ((chunk ^ ((q0 + 4) & 7)) << 4);
#pragma unroll
    for (int j = 0; j < NR / 8; j++)
        stsm4t(((j & 1) ? a1 : a0) + (j >> 1) * 4096, pack_bf16(d[8 * j], d[8 * j + 1]), pack_bf16(d[8 * j + 2], d[8 * j + 3]),
               pack_bf16(d[8 * j + 4], d[8 * j + 5]), pack_bf16(d[8 * j + 6], d[8 * j + 7]));
}

struct TrueT { static constexpr bool value = true; };
struct FalseT { static constexpr bool value = false; };

template <int V>
struct IntT { static constexpr int value = V; };

__device__ __forceinline__ uint32_t get_item(uint32_t sb, int it) {
    mbar_wait(sb + BAR_ITEM + it * 8, 0);
    return lds_u(sb + OFF_ITEM + it * 4);
}
__device__ __forceinline__ uint32_t get_item_warp(uint32_t sb, int it) { return __shfl_sync(0xffffffffu, get_item(sb, it), 0); }

struct Ring {
    uint32_t slot, ph;
    __device__ __forceinline__ void adv(uint32_t k) {
        slot += k;
        if (slot >= NSLOT) { slot -= NSLOT; ph ^= 1; }
    }
};

template <int K>
__device__ __forceinline__ void qk_step(float (&s)[80], uint32_t loK, uint32_t loQ) {
    wgmma<0, 0, HI_SW128, K != 0>(s, loK + (K >> 2) * (8192 >> 4) + (K & 3) * 2, loQ + (K >> 2) * (XS >> 4) + (K & 3) * 2);
}
template <int K0, int K1>
__device__ __forceinline__ void qk_steps(float (&s)[80], uint32_t loK, uint32_t loQ) {
    if constexpr (K0 < K1) {
        qk_step<K0>(s, loK, loQ);
        qk_steps<K0 + 1, K1>(s, loK, loQ);
    }
}
template <int J>
__device__ __forceinline__ void exp_chunk(const float (&s)[80], float (&ps)[40], uint32_t pa, float mref) {
    float p[8];
#pragma unroll
    for (int i = 0; i < 8; i++) p[i] = ex2(fmaf(s[8 * J + i], SM_C, -mref));
    stsm4t(pa + J * 2048, pack_bf16(p[0], p[1]), pack_bf16(p[2], p[3]), pack_bf16(p[4], p[5]), pack_bf16(p[6], p[7]));
    ps[4 * J] = p[0] + p[2];
    ps[4 * J + 1] = p[1] + p[3];
    ps[4 * J + 2] = p[4] + p[6];
    ps[4 * J + 3] = p[5] + p[7];
}
template <int J>
__device__ __forceinline__ void exp_block(const float (&s)[80], float (&ps)[40], uint32_t pa, float mref) {
    if constexpr (J < 10) {
        exp_chunk<J>(s, ps, pa, mref);
        exp_block<J + 1>(s, ps, pa, mref);
    }
}
__device__ __forceinline__ void sum_block(const float (&ps)[40], float (&l)[5], uint32_t lane) {
    const bool b4 = lane & 16, b3 = lane & 8, b2 = lane & 4;
    float t[20];
#pragma unroll
    for (int j = 0; j < 10; j++) {
        t[2 * j] = (b4 ? ps[4 * j + 2] : ps[4 * j]) + __shfl_xor_sync(0xffffffffu, b4 ? ps[4 * j] : ps[4 * j + 2], 16);
        t[2 * j + 1] = (b4 ? ps[4 * j + 3] : ps[4 * j + 1]) + __shfl_xor_sync(0xffffffffu, b4 ? ps[4 * j + 1] : ps[4 * j + 3], 16);
    }
#pragma unroll
    for (int i = 0; i < 10; i++) t[i] = (b3 ? t[i + 10] : t[i]) + __shfl_xor_sync(0xffffffffu, b3 ? t[i] : t[i + 10], 8);
#pragma unroll
    for (int i = 0; i < 5; i++)
        l[i] += (b2 ? t[2 * i + 1] : t[2 * i]) + __shfl_xor_sync(0xffffffffu, b2 ? t[2 * i] : t[2 * i + 1], 4);
}

__device__ __forceinline__ void fallback_unit(const Params& P, uint32_t e, uint32_t tid) {
    const uint32_t lane = tid & 31, br = IT_BR(e), b = IT_B(e), h = IT_H0(e);
    const __nv_bfloat162* wq = (const __nv_bfloat162*)(P.pwq[br] + h * 192) + lane;
    const __nv_bfloat162* kp = (const __nv_bfloat162*)(P.pk[br] + (size_t)(b * 32 + h) * 512 * 192) + lane;
    const __nv_bfloat162* vp = (const __nv_bfloat162*)(P.pv[br] + (size_t)(b * 32 + h) * 512 * 192) + lane;
#pragma unroll 1
    for (uint32_t qi = 0; qi < 40; qi++) {
        const uint32_t q = 4 * qi + (tid >> 5);
        const __nv_bfloat16* xr = P.px[br] + (size_t)(b * 160 + q) * 640;
        float a[6] = {0.f, 0.f, 0.f, 0.f, 0.f, 0.f};
#pragma unroll 4
        for (int k = 0; k < 640; k++) {
            const float xv = __bfloat162float(xr[k]);
#pragma unroll
            for (int i = 0; i < 3; i++) {
                const float2 wv = __bfloat1622float2(wq[(size_t)k * 3072 + i * 32]);
                a[2 * i] = fmaf(xv, wv.x, a[2 * i]);
                a[2 * i + 1] = fmaf(xv, wv.y, a[2 * i + 1]);
            }
        }
#pragma unroll
        for (int i = 0; i < 6; i++) a[i] = __bfloat162float(__float2bfloat16(a[i]));
        auto score = [&](int key) {
            float d = 0.f;
#pragma unroll
            for (int i = 0; i < 3; i++) {
                const float2 kv = __bfloat1622float2(kp[key * 96 + i * 32]);
                d = fmaf(a[2 * i], kv.x, fmaf(a[2 * i + 1], kv.y, d));
            }
#pragma unroll
            for (int o = 16; o > 0; o >>= 1) d += __shfl_xor_sync(0xffffffffu, d, o);
            return d;
        };
        float m = -INFINITY;
#pragma unroll 4
        for (int key = 0; key < 512; key++) m = fmaxf(m, score(key));
        float o[6] = {0.f, 0.f, 0.f, 0.f, 0.f, 0.f}, sum = 0.f;
#pragma unroll 4
        for (int key = 0; key < 512; key++) {
            const float p = ex2((score(key) - m) * SM_C);
            sum += p;
#pragma unroll
            for (int i = 0; i < 3; i++) {
                const float2 vv = __bfloat1622float2(vp[key * 96 + i * 32]);
                o[2 * i] = fmaf(p, vv.x, o[2 * i]);
                o[2 * i + 1] = fmaf(p, vv.y, o[2 * i + 1]);
            }
        }
        const float inv = __fdividef(1.f, sum);
        __nv_bfloat16* op = (__nv_bfloat16*)ostash(br, b, h) + (q >> 5) * 256 + 2 * ((q & 31) >> 3) + (q & 1);
#pragma unroll
        for (int i = 0; i < 6; i++) {
            const uint32_t d = (i >> 1) * 64 + 2 * lane + (i & 1);
            op[(d >> 3) * 1280 + (d & 7) * 32 + ((((q & 7) >> 1) ^ ((d & 7) >> 1)) << 3)] = __float2bfloat16(o[i] * inv);
        }
    }
}

template <int W>
struct PendO {
    static constexpr int N = W == 0 ? 14 : 16;
    uint32_t v[4 * N];
    unsigned char* gp;
    uint32_t pend, sig;
    template <int I>
    __device__ __forceinline__ void store() const {
        if constexpr (I < N) {
            constexpr int g = I < 10 ? I / 2 : (I - 10) / 2 + (W == 0 ? 3 : 0);
            constexpr int off = (I < 10 ? W : 2) * XS + g * 512 + (I & 1) * 2560;
            asm volatile(
                "{\n.reg .pred p;\nsetp.ne.u32 p, %6, 0;\n@p st.global.v4.b32 [%0+%5], {%1,%2,%3,%4};\n}" ::"l"(gp),
                "r"(v[4 * I]), "r"(v[4 * I + 1]), "r"(v[4 * I + 2]), "r"(v[4 * I + 3]), "n"(off), "r"(pend)
                : "memory");
        }
    }
    template <int I>
    __device__ __forceinline__ void flush() const {
        if constexpr (I < N) {
            store<I>();
            flush<I + 1>();
        }
    }
    __device__ __forceinline__ void clear() {
#pragma unroll
        for (int i = 0; i < 4 * N; i++) v[i] = 0;
        gp = nullptr;
        pend = 0;
        sig = 0;
    }
};

template <int W, int KK, int KE>
__device__ __forceinline__ void qproj(float (&q0)[80], float (&q1)[80], uint32_t sb, Ring& r, uint32_t phm, const PendO<W>& po) {
    const uint32_t loR = ((sb + OFF_R) >> 4) | LO_LBO1;
    const uint32_t loRing = ((sb + OFF_RING) >> 4) | LO_LBO1;
    constexpr int xs = KK % 5;
    const uint32_t pslot = r.slot;
    if (KK > 0) r.adv(1);
    if (W == 1 && KK == QHOLD) nb_sync<NB_SDONE, 256>();
    mbar_wait(sb + BAR_RFULL + r.slot * 8, r.ph);
    mbar_wait(sb + BAR_XFULL + xs * 8, ((phm >> xs) ^ (KK / 5)) & 1);
    const uint32_t a = loRing + r.slot * (SLOT >> 4) + (W == 0 ? 0 : 1024), b = loR + xs * (XS >> 4);
    wg_fence();
    wgmma<1, 0, HI_SW128, KK != 0>(q0, a, b);
    if (W == 0) wgmma<1, 0, HI_SW128, KK != 0>(q1, a + 512, b);
#pragma unroll
    for (int k = 1; k < 4; k++) {
        wgmma<1, 0, HI_SW128, true>(q0, a + k * 128, b + k * 2);
        if (W == 0) wgmma<1, 0, HI_SW128, true>(q1, a + 512 + k * 128, b + k * 2);
    }
    wg_commit();
    if (KK > 0) {
        wg_wait<1>();
        mbar_arrive_warp(sb + BAR_REMPTY + pslot * 8, 1);
        if (KK <= 5) mbar_arrive_warp(sb + (BAR_XEMPTY + (KK - 1) * 8), 1);
        if (W == 1 && KK == 7) nb_arrive<NB_PDONE, 256>();
    }
    if constexpr (W == 0 && KK < 5) {
        po.template store<3 * KK>();
        po.template store<3 * KK + 1>();
        po.template store<3 * KK + 2>();
        if (KK == 4 && po.sig) nb_arrive<NB_ODONE, 288>();
    }
    if constexpr (W == 1 && KK >= QPRE && KK < QPRE + 4) {
        po.template store<4 * (KK - QPRE)>();
        po.template store<4 * (KK - QPRE) + 1>();
        po.template store<4 * (KK - QPRE) + 2>();
        po.template store<4 * (KK - QPRE) + 3>();
        if (KK == QPRE + 3 && po.sig) nb_arrive<NB_ODONE, 288>();
    }
    if constexpr (KK + 1 < KE) {
        qproj<W, KK + 1, KE>(q0, q1, sb, r, phm, po);
    } else if constexpr (KE == 10) {
        if (W == 0) nb_arrive<NB_SDONE, 256>();
        wg_wait<0>();
        reg_fence(q0);
        if (W == 0) reg_fence(q1);
        mbar_arrive_warp(sb + BAR_REMPTY + r.slot * 8, 1);
        r.adv(1);
    }
}

template <int NR>
__device__ __forceinline__ void opack(const float (&o)[NR], int gl, const float2* sc, uint32_t* v) {
#pragma unroll
    for (int hh = 0; hh < 2; hh++)
#pragma unroll
        for (int t = 0; t < 4; t++)
            v[4 * hh + t] = pack_bf16(o[16 * gl + 4 * t + 2 * hh] * sc[t].x, o[16 * gl + 4 * t + 2 * hh + 1] * sc[t].y);
}

template <int NR>
__device__ __forceinline__ void dump_acc(const float (&c)[NR], float4* p) {
#pragma unroll
    for (int i = 0; i < NR / 4; i++) p[i * 128] = make_float4(c[4 * i], c[4 * i + 1], c[4 * i + 2], c[4 * i + 3]);
}
__device__ __forceinline__ void wait_flag(const unsigned int* f, uint32_t epoch) {
    uint32_t v, n = 0;
    do {
        asm volatile("ld.acquire.gpu.global.u32 %0, [%1];" : "=r"(v) : "l"(f) : "memory");
        if (++n > 0x400000) __trap();
    } while (v != epoch);
}

template <bool IS_S>
__device__ __forceinline__ void op_item(uint32_t e, uint32_t sb, Ring& r, uint32_t& phm) {
    constexpr int T0 = IS_S ? 0 : 2;
    constexpr uint32_t BOFF = IS_S ? (3 * 512) >> 4 : 0;
    const uint32_t loRing = ((sb + OFF_RING) >> 4) | LO_LBO1;
    const uint32_t loO = ((sb + OFF_R) >> 4) | LO_OST;
    float c0[80], c1[80], c2[IS_S ? 32 : 48];
    const int T2 = 6 * (IT_H1(e) - IT_H0(e));
    uint32_t xs = 0;
    auto step = [&](auto first, uint32_t hf) {
        constexpr bool F = decltype(first)::value;
        if (hf == 0) {
            mbar_wait(sb + BAR_XFULL + xs * 8, (phm >> xs) & 1);
            phm ^= 1u << xs;
        }
        mbar_wait(sb + BAR_RFULL + r.slot * 8, r.ph);
        const uint32_t a = loRing + r.slot * (SLOT >> 4), b = loO + xs * (XS >> 4) + hf * 640;
        wg_fence();
        wgmma<1, 1, HI_OST, !F>(c0, a + T0 * 256, b);
        wgmma<1, 1, HI_OST, !F>(c1, a + T0 * 256 + 256, b);
        wgmma<1, 1, HI_OST, !F>(c2, a + 1024, b + BOFF);
        wgmma<1, 1, HI_OST, true>(c0, a + T0 * 256 + 128, b + 320);
        wgmma<1, 1, HI_OST, true>(c1, a + T0 * 256 + 384, b + 320);
        wgmma<1, 1, HI_OST, true>(c2, a + 1024 + 128, b + 320 + BOFF);
        wg_commit();
    };
    step(TrueT{}, 0);
#pragma unroll 1
    for (int t = 1; t < T2; t++) {
        const uint32_t pslot = r.slot, pxs = xs;
        r.adv(1);
        if ((t & 1) == 0 && ++xs == 5) xs = 0;
        step(FalseT{}, t & 1);
        wg_wait<1>();
        mbar_arrive_warp(sb + BAR_REMPTY + pslot * 8, 1);
        if ((t & 1) == 0 && t + 8 < T2) mbar_arrive_warp(sb + BAR_XEMPTY + pxs * 8, 1);
    }
    wg_wait<0>();
    reg_fence(c0);
    reg_fence(c1);
    reg_fence(c2);
    mbar_arrive_warp(sb + BAR_REMPTY + r.slot * 8, 1);
    r.adv(1);
    if (IT_PART(e)) {
#pragma unroll
        for (int m = 0; m < 5; m++) mbar_arrive_warp(sb + BAR_XEMPTY + m * 8, 1);
        float4* pp = g_part + (size_t)((IT_BR(e) * 16 + IT_B(e)) * 10 + IT_HALF(e) * 5) * 2560 + (threadIdx.x & 127);
        dump_acc(c0, pp + T0 * 2560);
        dump_acc(c1, pp + (T0 + 1) * 2560);
        dump_acc(c2, pp + 4 * 2560 + (IS_S ? 12 * 128 : 0));
    } else {
        nb_sync<NB_OPEND, 256>();
        const uint32_t lane = threadIdx.x & 31, w = (threadIdx.x >> 5) & 3;
        store_out_tile(c0, sb + OFF_R + T0 * XS, lane, w);
        store_out_tile(c1, sb + OFF_R + (T0 + 1) * XS, lane, w);
        store_out_tile(c2, sb + OFF_R + 4 * XS + (IS_S ? 96 * 128 : 0), lane, w);
        fence_async_smem();
    }
    nb_arrive<NB_ODONE, 288>();
}

template <int W>
__device__ __forceinline__ void on_item(uint32_t e, uint32_t sb, Ring& r, uint32_t& phm, uint32_t epoch) {
    const uint32_t loRing = ((sb + OFF_RING) >> 4) | LO_LBO1;
    const uint32_t loO = ((sb + OFF_R) >> 4) | LO_OST;
    float c[80];
    const int T = 3 * (IT_H1(e) - IT_H0(e));
    uint32_t xs = 0;
    auto step = [&](auto first) {
        constexpr bool F = decltype(first)::value;
        mbar_wait(sb + BAR_XFULL + xs * 8, (phm >> xs) & 1);
        phm ^= 1u << xs;
        mbar_wait(sb + BAR_RFULL + r.slot * 8, r.ph);
        const uint32_t a = loRing + r.slot * (SLOT >> 4) + W * 512, b = loO + xs * (XS >> 4);
        wg_fence();
        wgmma<1, 1, HI_OST, !F>(c, a, b);
#pragma unroll
        for (int k = 1; k < 4; k++) wgmma<1, 1, HI_OST, true>(c, a + k * 128, b + k * 320);
        wg_commit();
    };
    auto run = [&](int t0, int t1) {
#pragma unroll 1
        for (int t = t0; t < t1; t++) {
            const uint32_t pslot = r.slot, pxs = xs;
            r.adv(1);
            if (++xs == 5) xs = 0;
            step(FalseT{});
            wg_wait<1>();
            mbar_arrive_warp(sb + BAR_REMPTY + pslot * 8, 1);
            mbar_arrive_warp_if(sb + BAR_XEMPTY + pxs * 8, 1, t + 4 < T);
        }
    };
    step(TrueT{});
    const int tm = T >> 1;
    run(1, tm);
    float4 pv[20];
    {
        const uint32_t tile = 2 * IT_HALF(e) + W, bb = IT_BR(e) * 16 + IT_B(e);
        wait_flag(&g_pflag[bb * 2 + (tile >= 5)], epoch);
        const float4* pp = g_part + (size_t)(bb * 10 + tile) * 2560 + (threadIdx.x & 127);
#pragma unroll
        for (int i = 0; i < 20; i++) pv[i] = __ldcg(pp + i * 128);
    }
    run(tm, T);
    wg_wait<0>();
    reg_fence(c);
    mbar_arrive_warp(sb + BAR_REMPTY + r.slot * 8, 1);
    r.adv(1);
    nb_sync<NB_OPEND, 256>();
#pragma unroll
    for (int i = 0; i < 20; i++) {
        c[4 * i] += pv[i].x;
        c[4 * i + 1] += pv[i].y;
        c[4 * i + 2] += pv[i].z;
        c[4 * i + 3] += pv[i].w;
    }
    store_out_tile(c, sb + OFF_R + W * XS, threadIdx.x & 31, (threadIdx.x >> 5) & 3);
    fence_async_smem();
    nb_arrive<NB_ODONE, 288>();
}

template <int W>
__device__ __forceinline__ uint32_t qa_item(const Params& P, uint32_t sb, Ring& r, uint32_t phm, PendO<W>& po,
                                            float (&oa)[80], float (&ob)[W == 0 ? 32 : 48], int it) {
    const uint32_t loR = ((sb + OFF_R) >> 4) | LO_LBO1;
    const uint32_t loRing = ((sb + OFF_RING) >> 4) | LO_LBO1;
    const uint32_t lane = threadIdx.x & 31, w = (threadIdx.x >> 5) & 3;
    const uint32_t sta = sb + OFF_R + (lane >> 4) * 1024 + (lane & 7) * 128 + (((2 * w + ((lane >> 3) & 1)) ^ (lane & 7)) << 4);
    auto pack_o = [&](int ie) {
#pragma unroll
        for (int g = 0; g < 5; g++) {
            float2 sc[4];
#pragma unroll
            for (int t = 0; t < 4; t++) sc[t] = lds_f2(sb + OFF_LINV + (lane & 3) * 8 + (4 * g + t) * 32);
            opack(oa, g, sc, po.v + 8 * g);
            if (W == 0 && g >= 3) opack(ob, g - 3, sc, po.v + 40 + 8 * (g - 3));
            if (W == 1 && g < 3) opack(ob, g, sc, po.v + 40 + 8 * g);
        }
        const uint32_t e = lds_u(sb + OFF_ITEM + ie * 4);
        po.gp = ostash(IT_BR(e), IT_B(e), IT_H0(e)) + w * 5120 + (lane >> 2) * 64 + (((lane ^ (lane >> 3)) & 3) << 4);
    };
    {
        float q0[80], q1[80];
        if constexpr (W == 0) {
            qproj<W, 0, 10>(q0, q1, sb, r, phm, po);
        } else {
            qproj<W, 0, QPRE>(q0, q1, sb, r, phm, po);
            if (po.sig) nb_sync<NB_VOTE, 256>();
            po.pend = po.sig && !__any_sync(0xffffffffu, lds_u(sb + OFF_FB) != 0);
            pack_o(it > 0 ? it - 1 : 0);
            TS(W, 26);
            qproj<W, QPRE, 10>(q0, q1, sb, r, phm, po);
        }
        TS(W, 1);
        if (W == 0) {
            nb_sync<NB_PDONE, 256>();
            store_tile_t(q0, sta);
            store_tile_t(q1, sta + XS);
        } else {
            store_tile_t(q0, sta + 2 * XS);
        }
    }
    fence_async_smem();
    float s[80], l[5];
#pragma unroll
    for (int i = 0; i < 80; i++) oa[i] = 0.f;
#pragma unroll
    for (int i = 0; i < (W == 0 ? 32 : 48); i++) ob[i] = 0.f;
#pragma unroll
    for (int i = 0; i < 5; i++) l[i] = 0.f;
    reg_fence(oa);
    reg_fence(ob);
    auto pv = [&](uint32_t buf) {
        mbar_wait(sb + BAR_RFULL + r.slot * 8, r.ph);
        const uint32_t a = loRing + r.slot * (SLOT >> 4), b = loR + (3 + buf) * (XS >> 4);
        wg_fence();
#pragma unroll
        for (int k = 0; k < 4; k++) {
            wgmma<1, 0, HI_SW128, true>(oa, a + W * 512 + k * 128, b + k * 2);
            wgmma<1, 0, HI_SW128, true>(ob, a + 1024 + k * 128, b + (W == 0 ? (96 * 128) >> 4 : 0) + k * 2);
        }
        wg_commit();
    };
    float mref;
    uint32_t kslot, vslot;
    const uint32_t lxa = sb + OFF_LX + w * 640 + (((lane & 8) ? 80 : 0) + ((lane >> 1) & 8) + 2 * (lane & 3) + ((lane >> 2) & 1)) * 4;
    auto tail = [&](bool rel_other, int i) {
        float ps[40];
        exp_block<0>(s, ps, sta + (3 + W) * XS, mref);
        if (rel_other) {
            wg_wait<0>();
            mbar_arrive_warp(sb + BAR_REMPTY + vslot * 8, 1);
            if (W == 1) mbar_arrive_warp_if(sb + BAR_XEMPTY + 24, 1, i == 3);
        }
        fence_async_smem();
        if (W == 1 && i == 3) {
            nb_sync<NB_W + W, 128>();
            pv(W);
        }
        nb_arrive<NB_PFULL + W, 256>();
        TS(W, 6 + 5 * i);
        mbar_wait(sb + BAR_RFULL + r.slot * 8, r.ph);
        sum_block(ps, l, lane);
        TS(W, 7 + 5 * i);
        if (W == 0 || i < 3) {
            nb_sync<NB_W + W, 128>();
            pv(W);
        }
        TS(W, 8 + 5 * i);
    };
    if (W == 0) {
        nb_sync<NB_W, 128>();
        TS(W, 2);
        mbar_wait(sb + BAR_RFULL + r.slot * 8, r.ph);
        wg_fence();
        qk_steps<0, 8>(s, loRing + r.slot * (SLOT >> 4), loR);
        nb_sync<NB_Q2, 256>();
        qk_steps<8, 12>(s, loRing + r.slot * (SLOT >> 4), loR);
        wg_commit();
        nb_arrive<NB_Q01, 256>();
        TS(W, 4);
        wg_wait<0>();
        reg_fence(s);
        mbar_arrive_warp(sb + BAR_REMPTY + r.slot * 8, 2);
        r.adv(2);
        float m0 = fmaxf(s[0], s[5]), m1 = fmaxf(s[10], s[15]);
#pragma unroll
        for (int i = 20; i < 80; i += 10) {
            m0 = fmaxf(m0, s[i]);
            m1 = fmaxf(m1, s[i + 5]);
        }
        int key = __float_as_int(fmaxf(m0, m1));
        key ^= (key >> 31) & 0x7fffffff;
        key = __reduce_max_sync(0xffffffffu, key);
        key ^= (key >> 31) & 0x7fffffff;
        sts_u(sb + OFF_GM + w * 4, key);
        sts_u(sb + OFF_FB, 0);
        nb_sync<NB_W, 128>();
        const float2 u = lds_f2(sb + OFF_GM), v = lds_f2(sb + OFF_GM + 8);
        mref = fmaxf(fmaxf(u.x, u.y), fmaxf(v.x, v.y)) * SM_C;
        TS(W, 5);
        tail(false, 0);
    } else {
        nb_arrive<NB_Q2, 256>();
        TS(W, 2);
        nb_sync<NB_Q01, 256>();
    }
#pragma unroll 1
    for (int i = (W == 0 ? 1 : 0); i < 4; i++) {
        const uint32_t pvslot = r.slot;
        r.adv(1);
        kslot = r.slot;
        mbar_wait(sb + BAR_RFULL + r.slot * 8, r.ph);
        wg_fence();
        qk_steps<0, 12>(s, loRing + r.slot * (SLOT >> 4), loR);
        wg_commit();
        wg_wait<1>();
        mbar_arrive_warp_if(sb + BAR_REMPTY + pvslot * 8, 1, W == 0 || i > 0);
        r.adv(1);
        vslot = r.slot;
        TS(W, 4 + 5 * i);
        nb_sync<NB_PFULL + (W ^ 1), 256>();
        pv(W ^ 1);
        if (W == 1) {
            const float2 u = lds_f2(sb + OFF_GM), v = lds_f2(sb + OFF_GM + 8);
            mref = fmaxf(fmaxf(u.x, u.y), fmaxf(v.x, v.y)) * SM_C;
        }
        wg_wait<1>();
        reg_fence(s);
        mbar_arrive_warp(sb + BAR_REMPTY + kslot * 8, 2);
        if (W == 1) {
            mbar_arrive_warp_if(sb + BAR_XEMPTY + 0, 2, i == 3);
            mbar_arrive_warp_if(sb + BAR_XEMPTY + 8, 2, i == 3);
            mbar_arrive_warp_if(sb + BAR_XEMPTY + 16, 2, i == 3);
        }
        r.adv(W == 1 && i == 3 ? 1 : 2);
        TS(W, 5 + 5 * i);
        tail(true, i);
    }
    if (W == 0) {
        const uint32_t tid = threadIdx.x & 127;
        float2 v = make_float2(0.f, 0.f);
        auto gather = [&]() {
            if (tid < 80) {
#pragma unroll
                for (int i = 0; i < 4; i++) {
                    const float2 u = lds_f2(sb + OFF_LX + i * 640 + tid * 8);
                    v.x += u.x;
                    v.y += u.y;
                }
            }
        };
#pragma unroll
        for (int i = 0; i < 5; i++) sts_f(lxa + i * 64, l[i]);
        nb_sync<NB_W, 128>();
        gather();
        nb_arrive<NB_LX, 256>();
        wg_wait<0>();
        mbar_arrive_warp(sb + BAR_REMPTY + r.slot * 8, 1);
        mbar_arrive_warp(sb + BAR_XEMPTY + 24, 1);
        r.adv(1);
        nb_sync<NB_PFULL + 1, 256>();
        pv(1);
        TS(W, 24);
        nb_sync<NB_L, 256>();
        gather();
        if (tid < 80) {
            sts_f2(sb + OFF_LINV + tid * 8, __fdividef(1.f, v.x), __fdividef(1.f, v.y));
            if (!(v.x >= 5.421010862e-20f && v.x <= 1.8446744e19f && v.y >= 5.421010862e-20f && v.y <= 1.8446744e19f))
                sts_u(sb + OFF_FB, 1);
        }
    }
    if (W == 0) {
        nb_arrive<NB_VOTE, 256>();
        nb_sync<NB_W, 128>();
    } else {
        nb_sync<NB_LX, 256>();
#pragma unroll
        for (int k = 0; k < 5; k++) sts_f(lxa + k * 64, l[k]);
        nb_arrive<NB_L, 256>();
    }
    const uint32_t nx = get_item_warp(sb, it + 1);
    wg_wait<0>();
    reg_fence(oa);
    reg_fence(ob);
    mbar_arrive_warp(sb + BAR_REMPTY + r.slot * 8, 1);
    mbar_arrive_warp(sb + BAR_XEMPTY + 32, 1);
    r.adv(1);
    TS(W, 25);
    po.sig = 1;
    if (W == 0) {
        const bool any = __any_sync(0xffffffffu, lds_u(sb + OFF_FB) != 0);
        pack_o(it);
        po.pend = !any;
        if (any) {
            fallback_unit(P, lds_u(sb + OFF_ITEM + it * 4), threadIdx.x & 127);
            __syncwarp();
        }
    }
    if (IT_TYPE(nx) != IT_QA) {
        if (W == 1) {
            nb_sync<NB_VOTE, 256>();
            po.pend = !__any_sync(0xffffffffu, lds_u(sb + OFF_FB) != 0);
            pack_o(it);
        }
        po.template flush<0>();
        nb_arrive<NB_ODONE, 288>();
        po.sig = 0;
        po.pend = 0;
    }
    return nx;
}

__global__ void __launch_bounds__(384, 1) fused_kernel(const __grid_constant__ Params P) {
    extern __shared__ __align__(1024) unsigned char smem_raw[];
    const uint32_t sb = (uint32_t)__cvta_generic_to_shared(smem_raw);
    const uint32_t wgid = __shfl_sync(0xffffffffu, threadIdx.x >> 7, 0);
    const uint32_t cta = blockIdx.x;

    uint32_t epoch = 0;
    if (wgid == 0) epoch = *(volatile unsigned int*)&g_epoch[cta] + 1;
    if (threadIdx.x == 0) {
        if (sb & 1023) __trap();
        sts_u(sb + OFF_FB + 4, epoch);
        for (int i = 0; i < NSLOT; i++) {
            mbar_init(sb + BAR_RFULL + i * 8, 1);
            mbar_init(sb + BAR_REMPTY + i * 8, 8);
            mbar_init(sb + BAR_XFULL + i * 8, 1);
            mbar_init(sb + BAR_XEMPTY + i * 8, 8);
        }
        for (int i = 0; i < MAXI; i++) mbar_init(sb + BAR_ITEM + i * 8, 1);
        asm volatile("fence.mbarrier_init.release.cluster;" ::: "memory");
        fence_async_smem();
    }
    __syncthreads();

    if (wgid == 0) {
        asm volatile("setmaxnreg.dec.sync.aligned.u32 24;");
        const uint32_t warp = __shfl_sync(0xffffffffu, threadIdx.x >> 5, 0);
        if (warp == 0) {
            if (threadIdx.x == 0) {
                *(volatile unsigned int*)&g_epoch[cta] = epoch;
                const uint64_t pol_first = mkpol<1>(), pol_norm = mkpol<POL_W>();
                if (cta == 0) *(volatile unsigned int*)&g_ticket[(epoch + 1) & 1] = 0;
                Ring r{0, 1};
                {
                    const uint32_t d = P.delay[cta];
                    uint32_t t0, t1;
                    asm volatile("mov.u32 %0, %%clock;" : "=r"(t0));
                    do {
                        asm volatile("mov.u32 %0, %%clock;" : "=r"(t1));
                    } while (t1 - t0 < d);
                }
                uint32_t e = P.items[cta][0];
#pragma unroll 1
                for (int it = 0;; it++) {
                    sts_u(sb + OFF_ITEM + it * 4, e);
                    asm volatile("mbarrier.arrive.shared::cta.b64 _, [%0];" ::"r"(sb + BAR_ITEM + it * 8) : "memory");
                    if (e == 0) break;
                    uint32_t nx = P.items[cta][it + 1 < NSTAT ? it + 1 : NSTAT - 1];
                    if (IT_TYPE(e) == IT_ON || it + 2 == MAXI) nx = 0;
                    const uint32_t br = IT_BR(e);
                    if (IT_TYPE(e) == IT_QA) {
                        const uint32_t h = IT_H0(e);
#pragma unroll 1
                        for (int kk = 0; kk < 10; kk++) {
                            mbar_wait(sb + BAR_REMPTY + r.slot * 8, r.ph);
                            mbar_expect(sb + BAR_RFULL + r.slot * 8, SLOT);
                            tma3(sb + OFF_RING + r.slot * SLOT, &P.wq[br], kk * 64, h * 3, sb + BAR_RFULL + r.slot * 8, pol_norm);
                            r.adv(1);
                        }
                        const int row0 = (IT_B(e) * 32 + h) * 512;
#pragma unroll 1
                        for (int n = 0; n < 16; n++) {
                            if (n == 12 && nx == IT_DYN) {
                                const uint32_t t = atomicAdd(&g_ticket[epoch & 1], 1);
                                nx = t < P.nlist ? P.list[t] : 0;
                            }
                            const bool isv = n == 15 || (n > 0 && !(n & 1));
                            const int j = n == 15 ? 7 : isv ? (n - 2) >> 1 : (n + 1) >> 1;
                            mbar_wait(sb + BAR_REMPTY + r.slot * 8, r.ph);
                            mbar_expect(sb + BAR_RFULL + r.slot * 8, SLOT);
                            tma3(sb + OFF_RING + r.slot * SLOT, isv ? &P.v[br] : &P.k[br], row0 + j * 64, 0,
                                 sb + BAR_RFULL + r.slot * 8, pol_first);
                            r.adv(1);
                        }
                    } else {
                        const int r0 = IT_H0(e) * 192, r1 = IT_H1(e) * 192;
                        const bool wide = IT_TYPE(e) == IT_OP;
#pragma unroll 1
                        for (int row = r0; row < r1; row += wide ? 32 : 64) {
                            mbar_wait(sb + BAR_REMPTY + r.slot * 8, r.ph);
                            mbar_expect(sb + BAR_RFULL + r.slot * 8, wide ? XS : 16384);
                            tma3(sb + OFF_RING + r.slot * SLOT, wide ? &P.wo[br] : &P.won[br], row, IT_HALF(e) * (wide ? 5 : 2),
                                 sb + BAR_RFULL + r.slot * 8, pol_norm);
                            r.adv(1);
                        }
                        if (nx == IT_DYN) {
                            const uint32_t t = atomicAdd(&g_ticket[epoch & 1], 1);
                            nx = t < P.nlist ? P.list[t] : 0;
                        }
                    }
                    e = nx;
                }
            }
        } else if (warp == 1) {
            if (threadIdx.x == 32) {
                const uint64_t pol_norm = mkpol<POL_X>(), pol_o = mkpol<POL_O>();
                uint32_t phm = 0x1f;
#pragma unroll 1
                for (int it = 0;; it++) {
                    const uint32_t e = get_item(sb, it);
                    if (e == 0) break;
                    const uint32_t br = IT_BR(e);
                    uint32_t xs = 0;
                    if (IT_TYPE(e) == IT_QA) {
#pragma unroll 1
                        for (int kk = 0; kk < 10; kk++) {
                            mbar_wait(sb + BAR_XEMPTY + xs * 8, (phm >> xs) & 1);
                            phm ^= 1u << xs;
                            mbar_expect(sb + BAR_XFULL + xs * 8, XS);
                            tma3(sb + OFF_R + xs * XS, &P.x[br], IT_B(e) * 160, kk, sb + BAR_XFULL + xs * 8, pol_norm);
                            if (++xs == 5) xs = 0;
                        }
                    } else {
                        const uint32_t u0 = (br * 16 + IT_B(e)) * 32;
#pragma unroll 1
                        for (uint32_t u = u0 + IT_H0(e); u < u0 + IT_H1(e); u++) {
                            wait_flag(&g_flag[u], epoch);
                            asm volatile("fence.proxy.async;" ::: "memory");
#pragma unroll 1
                            for (int t = 0; t < 3; t++) {
                                mbar_wait(sb + BAR_XEMPTY + xs * 8, (phm >> xs) & 1);
                                phm ^= 1u << xs;
                                mbar_expect(sb + BAR_XFULL + xs * 8, XS);
                                bulk_load(sb + OFF_R + xs * XS, ostash(br, IT_B(e), u & 31) + t * XS, XS, sb + BAR_XFULL + xs * 8, pol_o);
                                if (++xs == 5) xs = 0;
                            }
                        }
                    }
                }
            }
        } else if (warp == 2) {
#pragma unroll 1
            for (int it = 0;; it++) {
                const uint32_t e = get_item_warp(sb, it);
                if (e == 0) break;
                nb_sync<NB_ODONE, 288>();
                if (threadIdx.x == 64) {
                    const uint32_t bb = IT_BR(e) * 16 + IT_B(e);
                    if (IT_TYPE(e) == IT_QA || IT_PART(e)) {
                        __threadfence();
                        unsigned int* f = IT_TYPE(e) == IT_QA ? &g_flag[bb * 32 + IT_H0(e)] : &g_pflag[bb * 2 + IT_HALF(e)];
                        asm volatile("st.relaxed.gpu.global.u32 [%0], %1;" ::"l"(f), "r"(epoch) : "memory");
                    } else {
                        const int nt = IT_TYPE(e) == IT_OP ? 5 : 2;
                        const int cc0 = IT_BR(e) * 640 + IT_HALF(e) * nt * 64;
#pragma unroll
                        for (int m = 0; m < 5; m++) {
                            if (m < nt)
                                asm volatile("cp.async.bulk.tensor.2d.global.shared::cta.bulk_group [%0, {%2,%3}], [%1];" ::"l"(&P.out),
                                             "r"(sb + OFF_R + m * XS), "r"(cc0 + m * 64), "r"((int)IT_B(e) * 160)
                                             : "memory");
                            asm volatile("cp.async.bulk.commit_group;" ::: "memory");
                        }
#define REL(N)                                                          \
    asm volatile("cp.async.bulk.wait_group.read %0;" ::"n"(4 - N) : "memory"); \
    asm volatile("mbarrier.arrive.shared::cta.b64 _, [%0], 8;" ::"r"(sb + BAR_XEMPTY + N * 8) : "memory");
                        REL(0) REL(1) REL(2) REL(3) REL(4)
#undef REL
                    }
                }
                __syncwarp();
            }
            if (threadIdx.x == 64) asm volatile("cp.async.bulk.wait_group 0;" ::: "memory");
        }
    } else if (wgid == 1) {
        asm volatile("setmaxnreg.inc.sync.aligned.u32 240;");
        PendO<0> po;
        po.clear();
        float oa[80], ob[32];
        zero(oa);
        zero(ob);
        Ring r{0, 0};
        uint32_t phm = 0;
        uint32_t e = get_item_warp(sb, 0);
#pragma unroll 1
        for (int it = 0; e != 0; it++) {
            TS(0, 0);
            if (IT_TYPE(e) == IT_QA) {
                e = qa_item<0>(P, sb, r, phm, po, oa, ob, it);
            } else {
                if (IT_TYPE(e) == IT_OP) op_item<true>(e, sb, r, phm);
                else on_item<0>(e, sb, r, phm, lds_u(sb + OFF_FB + 4));
                po.clear();
                zero(oa);
                zero(ob);
                e = get_item_warp(sb, it + 1);
            }
            TS(0, 31);
        }
        TS_DUMP(0);
    } else {
        asm volatile("setmaxnreg.inc.sync.aligned.u32 240;");
        PendO<1> po;
        po.clear();
        float oa[80], ob[48];
        zero(oa);
        zero(ob);
        Ring r{0, 0};
        uint32_t phm = 0;
        uint32_t e = get_item_warp(sb, 0);
#pragma unroll 1
        for (int it = 0; e != 0; it++) {
            TS(1, 0);
            if (IT_TYPE(e) == IT_QA) {
                e = qa_item<1>(P, sb, r, phm, po, oa, ob, it);
            } else {
                if (IT_TYPE(e) == IT_OP) op_item<false>(e, sb, r, phm);
                else on_item<1>(e, sb, r, phm, lds_u(sb + OFF_FB + 4));
                po.clear();
                zero(oa);
                zero(ob);
                e = get_item_warp(sb, it + 1);
            }
            TS(1, 31);
        }
        TS_DUMP(1);
    }
}

typedef CUresult (*EncFn)(CUtensorMap*, CUtensorMapDataType, cuuint32_t, void*, const cuuint64_t*, const cuuint64_t*,
                          const cuuint32_t*, const cuuint32_t*, CUtensorMapInterleave, CUtensorMapSwizzle,
                          CUtensorMapL2promotion, CUtensorMapFloatOOBfill);

void make_map3(EncFn enc, CUtensorMap* m, void* p, uint64_t rows, uint64_t rowbytes, uint64_t nblk, uint32_t boxrows,
               uint32_t boxblk) {
    cuuint64_t dims[3] = {64, rows, nblk};
    cuuint64_t str[2] = {rowbytes, 128};
    cuuint32_t box[3] = {64, boxrows, boxblk};
    cuuint32_t es[3] = {1, 1, 1};
    enc(m, CU_TENSOR_MAP_DATA_TYPE_BFLOAT16, 3, p, dims, str, box, es, CU_TENSOR_MAP_INTERLEAVE_NONE,
        CU_TENSOR_MAP_SWIZZLE_128B, CU_TENSOR_MAP_L2_PROMOTION_NONE, CU_TENSOR_MAP_FLOAT_OOB_FILL_NONE);
}

#define SCHED_MODE 4
#define HSPLIT 14
#define DELAY_MAX 28000
#define DELAY_N0 0

void build_schedule(Params& P) {
    int u = 0;
    auto unit = [&]() {
        const uint32_t e = mk_item(IT_QA, u >> 9, u & 15, (u >> 4) & 31, 0, 0);
        u++;
        return e;
    };
    int qa[NCTA], nq = 0, op[NCTA], no = 0;
    for (int c = 0; c < NCTA; c++) {
        P.delay[c] = 0;
        for (int i = 0; i < NSTAT; i++) P.items[c][i] = 0;
        if (SCHED_MODE >= 3 && c < 128 && (c & 7) >= 6) op[no++] = c;
        else if (SCHED_MODE != 2 || (c & 3) == 0) qa[nq++] = c;
    }
    for (int t = 0; t < no; t++) P.items[op[t]][0] = unit();
    for (int k = 0; k < nq; k++) {
        const int c = qa[(k * 37) % nq];
        P.items[c][0] = unit();
        for (int i = 1; i < NSTAT; i++) P.items[c][i] = IT_DYN;
        P.delay[c] = k < DELAY_N0 ? 0 : (int)((long long)DELAY_MAX * (k + 1 - DELAY_N0) / (nq - DELAY_N0));
    }
    int n = 0;
    const int uend = SCHED_MODE == 2 ? 8 * nq : 1024 - no;
    while (u < uend) P.list[n++] = unit();
    for (int t = 0; t < no; t++) {
        P.items[op[t]][1] = mk_item(IT_OP, 0, t >> 1, 0, 32, t & 1);
        P.items[op[t]][2] = mk_item(IT_OP, 1, t >> 1, 0, HSPLIT, t & 1, 1);
        P.items[op[t]][3] = unit();
    }
    if (no)
        for (int k = 0; k < 80; k++) P.list[n++] = mk_item(IT_ON, 1, k / 5, HSPLIT, 32, k % 5);
    P.nlist = n;
}

}

extern "C" void kernel_launch(void* const* d_in, const int* in_sizes, int n_in, void* d_out, int out_size) {
    static Params P;
    static bool init = false;
    if (!init) {
        EncFn enc = nullptr;
        cudaDriverEntryPointQueryResult qr;
        cudaGetDriverEntryPoint("cuTensorMapEncodeTiled", (void**)&enc, cudaEnableDefault, &qr);
        for (int i = 0; i < 2; i++) {
            P.px[i] = (const __nv_bfloat16*)d_in[5 * i + 0];
            P.pk[i] = (const __nv_bfloat16*)d_in[5 * i + 1];
            P.pv[i] = (const __nv_bfloat16*)d_in[5 * i + 2];
            P.pwq[i] = (const __nv_bfloat16*)d_in[5 * i + 3];
            make_map3(enc, &P.x[i], d_in[5 * i + 0], 2560, 1280, 10, 160, 1);
            make_map3(enc, &P.k[i], d_in[5 * i + 1], 16 * 32 * 512, 384, 3, 64, 3);
            make_map3(enc, &P.v[i], d_in[5 * i + 2], 16 * 32 * 512, 384, 3, 64, 3);
            make_map3(enc, &P.wq[i], d_in[5 * i + 3], 640, 12288, 96, 64, 3);
            make_map3(enc, &P.wo[i], d_in[5 * i + 4], 6144, 1280, 10, 32, 5);
            make_map3(enc, &P.won[i], d_in[5 * i + 4], 6144, 1280, 10, 64, 2);
        }
        cuuint64_t dims[2] = {1280, 2560};
        cuuint64_t str[1] = {2560};
        cuuint32_t box[2] = {64, 160};
        cuuint32_t es[2] = {1, 1};
        enc(&P.out, CU_TENSOR_MAP_DATA_TYPE_BFLOAT16, 2, d_out, dims, str, box, es, CU_TENSOR_MAP_INTERLEAVE_NONE,
            CU_TENSOR_MAP_SWIZZLE_128B, CU_TENSOR_MAP_L2_PROMOTION_NONE, CU_TENSOR_MAP_FLOAT_OOB_FILL_NONE);
        build_schedule(P);
        cudaFuncSetAttribute(fused_kernel, cudaFuncAttributeMaxDynamicSharedMemorySize, SMEM_LAUNCH);
        init = true;
    }
    fused_kernel<<<NCTA, 384, SMEM_LAUNCH>>>(P);
}
```

```cpp
#include <cuda_runtime.h>
#include <cuda.h>
#include <cuda_bf16.h>
#include <stdint.h>

namespace {

constexpr int NCTA = 132;
constexpr int MAXI = 16;
constexpr int NSTAT = 6;
constexpr uint32_t IT_DYN = 0xffffffffu;
constexpr int SLOT = 24576;
constexpr int NSLOT = 5;
constexpr int XS = 20480;
constexpr int OFF_R = 0;
constexpr int OFF_RING = 5 * XS;
constexpr int OFF_MISC = OFF_RING + NSLOT * SLOT;
constexpr int OFF_LX = OFF_MISC;
constexpr int OFF_LINV = OFF_LX + 2560;
constexpr int OFF_FB = OFF_LINV + 640;
constexpr int OFF_GM = OFF_FB + 16;
constexpr int OFF_BAR = OFF_GM + 16;
constexpr int BAR_RFULL = OFF_BAR;
constexpr int BAR_REMPTY = BAR_RFULL + 40;
constexpr int BAR_XFULL = BAR_REMPTY + 40;
constexpr int BAR_XEMPTY = BAR_XFULL + 40;
constexpr int BAR_ITEM = BAR_XEMPTY + 40;
constexpr int OFF_ITEM = BAR_ITEM + MAXI * 8;
constexpr int SMEM_BYTES = OFF_ITEM + MAXI * 4;
static_assert(SMEM_BYTES <= 232448, "smem");

constexpr int NB_W = 1  , NB_PFULL = 3  , NB_VOTE = 5, NB_Q01 = 6, NB_Q2 = 7, NB_SDONE = 8, NB_PDONE = 9,
              NB_L = 10, NB_OPST = 11, NB_ODONE = 12, NB_OPEND = 13, NB_LX = 14;

constexpr uint32_t IT_QA = 1, IT_OP = 2, IT_ON = 3;
__host__ __device__ constexpr uint32_t mk_item(uint32_t type, uint32_t br, uint32_t b, uint32_t h0, uint32_t h1, uint32_t half,
                                               uint32_t part = 0) {
    return type | (br << 2) | (b << 3) | (h0 << 7) | (h1 << 13) | (half << 19) | (part << 22);
}
#define IT_TYPE(e) ((e) & 3u)
#define IT_BR(e) (((e) >> 2) & 1u)
#define IT_B(e) (((e) >> 3) & 15u)
#define IT_H0(e) (((e) >> 7) & 63u)
#define IT_H1(e) (((e) >> 13) & 63u)
#define IT_HALF(e) (((e) >> 19) & 7u)
#define IT_PART(e) (((e) >> 22) & 1u)

struct Params {
    CUtensorMap x[2], wq[2], k[2], v[2], wo[2], won[2], out;
    const __nv_bfloat16 *px[2], *pwq[2], *pk[2], *pv[2];
    uint32_t items[NCTA][NSTAT];
    uint32_t delay[NCTA];
    uint32_t nlist;
    uint32_t list[1024];
};

constexpr int OUNIT = 61440;
__device__ __align__(1024) unsigned char g_ostash[(size_t)1024 * OUNIT];
__device__ unsigned int g_flag[1024];
__device__ float4 g_part[2 * 16 * 10 * 2560];
__device__ unsigned int g_pflag[64];
#define ORING 64
__device__ __forceinline__ unsigned char* ostash(uint32_t br, uint32_t b, uint32_t h) {
    return g_ostash + (size_t)(((br * 32 + h) % ORING) * 16 + b) * OUNIT;
}
__device__ unsigned int g_epoch[NCTA];
__device__ unsigned int g_ticket[2];

constexpr int SMEM_LAUNCH = SMEM_BYTES;
#define TS(role, idx)
#define TS_DUMP(role)
#define TS2(cond, idx)

#define POL_W 2
#define POL_X 2
#define POL_O 2
template <int M>
__device__ __forceinline__ uint64_t mkpol() {
    uint64_t p;
    if (M == 0) asm volatile("createpolicy.fractional.L2::evict_normal.b64 %0, 1.0;" : "=l"(p));
    if (M == 1) asm volatile("createpolicy.fractional.L2::evict_first.b64 %0, 1.0;" : "=l"(p));
    if (M == 2) asm volatile("createpolicy.fractional.L2::evict_unchanged.b64 %0, 1.0;" : "=l"(p));
    if (M == 3) asm volatile("createpolicy.fractional.L2::evict_normal.L2::evict_unchanged.b64 %0, 0.25;" : "=l"(p));
    return p;
}
#define STSM_W 1
#define QPRE 3
#define QHOLD 7
constexpr float SM_C = 0.07216878364870322f * 1.4426950408889634f;

__device__ __forceinline__ void mbar_init(uint32_t a, uint32_t c) {
    asm volatile("mbarrier.init.shared::cta.b64 [%0], %1;" ::"r"(a), "r"(c) : "memory");
}
__device__ __forceinline__ void mbar_expect(uint32_t a, uint32_t b) {
    asm volatile("mbarrier.arrive.expect_tx.shared::cta.b64 _, [%0], %1;" ::"r"(a), "r"(b) : "memory");
}
__device__ __forceinline__ void mbar_arrive_warp(uint32_t a, uint32_t cnt) {
    asm volatile(
        "{\n.reg .pred p;\nelect.sync _|p, 0xffffffff;\n"
        "@p mbarrier.arrive.shared::cta.b64 _, [%0], %1;\n}" ::"r"(a), "r"(cnt)
        : "memory");
}
__device__ __forceinline__ void mbar_arrive_warp_if(uint32_t a, uint32_t cnt, bool cond) {
    asm volatile(
        "{\n.reg .pred p, c;\nelect.sync _|p, 0xffffffff;\nsetp.ne.and.u32 c, %2, 0, p;\n"
        "@c mbarrier.arrive.shared::cta.b64 _, [%0], %1;\n}" ::"r"(a), "r"(cnt), "r"((uint32_t)cond)
        : "memory");
}
__device__ __forceinline__ void mbar_wait(uint32_t a, uint32_t ph) {
    asm volatile(
        "{\n.reg .pred p;\n.reg .u32 n, m;\n"
        "mbarrier.try_wait.parity.shared::cta.b64 p, [%0], %1;\n"
        "@p bra DONE;\n"
        "mov.u32 n, %%clock_hi;\n"
        "LOOP:\n"
        "mbarrier.try_wait.parity.shared::cta.b64 p, [%0], %1;\n"
        "@p bra DONE;\n"
        "mov.u32 m, %%clock_hi;\n"
        "sub.u32 m, m, n;\n"
        "setp.lt.u32 p, m, 2;\n"
        "@p bra LOOP;\n"
        "trap;\n"
        "DONE:\n}" ::"r"(a), "r"(ph)
        : "memory");
}
template <int ID, int CNT>
__device__ __forceinline__ void nb_sync() { asm volatile("bar.sync %0, %1;" ::"n"(ID), "n"(CNT) : "memory"); }
template <int ID, int CNT>
__device__ __forceinline__ void nb_arrive() { asm volatile("bar.arrive %0, %1;" ::"n"(ID), "n"(CNT) : "memory"); }
__device__ __forceinline__ void fence_async_smem() { asm volatile("fence.proxy.async.shared::cta;" ::: "memory"); }

__device__ __forceinline__ void tma3(uint32_t dst, const CUtensorMap* m, int c1, int c2, uint32_t bar, uint64_t pol) {
    asm volatile(
        "cp.async.bulk.tensor.3d.shared::cluster.global.mbarrier::complete_tx::bytes.L2::cache_hint [%0], [%1, {%3,%4,%5}], [%2], %6;" ::"r"(dst),
        "l"(m), "r"(bar), "r"(0), "r"(c1), "r"(c2), "l"(pol)
        : "memory");
}
__device__ __forceinline__ void bulk_load(uint32_t dst, const void* src, uint32_t bytes, uint32_t bar, uint64_t pol) {
    asm volatile("cp.async.bulk.shared::cluster.global.mbarrier::complete_tx::bytes.L2::cache_hint [%0], [%1], %2, [%3], %4;" ::"r"(dst),
                 "l"(src), "r"(bytes), "r"(bar), "l"(pol)
                 : "memory");
}
__device__ __forceinline__ void wg_fence() { asm volatile("wgmma.fence.sync.aligned;" ::: "memory"); }
__device__ __forceinline__ void wg_commit() { asm volatile("wgmma.commit_group.sync.aligned;" ::: "memory"); }
template <int N>
__device__ __forceinline__ void wg_wait() { asm volatile("wgmma.wait_group.sync.aligned %0;" ::"n"(N) : "memory"); }

#define RW80(c, d) c(d[0]), c(d[1]), c(d[2]), c(d[3]), c(d[4]), c(d[5]), c(d[6]), c(d[7]), c(d[8]), c(d[9]), c(d[10]), c(d[11]), c(d[12]), c(d[13]), c(d[14]), c(d[15]), c(d[16]), c(d[17]), c(d[18]), c(d[19]), c(d[20]), c(d[21]), c(d[22]), c(d[23]), c(d[24]), c(d[25]), c(d[26]), c(d[27]), c(d[28]), c(d[29]), c(d[30]), c(d[31]), c(d[32]), c(d[33]), c(d[34]), c(d[35]), c(d[36]), c(d[37]), c(d[38]), c(d[39]), c(d[40]), c(d[41]), c(d[42]), c(d[43]), c(d[44]), c(d[45]), c(d[46]), c(d[47]), c(d[48]), c(d[49]), c(d[50]), c(d[51]), c(d[52]), c(d[53]), c(d[54]), c(d[55]), c(d[56]), c(d[57]), c(d[58]), c(d[59]), c(d[60]), c(d[61]), c(d[62]), c(d[63]), c(d[64]), c(d[65]), c(d[66]), c(d[67]), c(d[68]), c(d[69]), c(d[70]), c(d[71]), c(d[72]), c(d[73]), c(d[74]), c(d[75]), c(d[76]), c(d[77]), c(d[78]), c(d[79])
#define RW48(c, d) c(d[0]), c(d[1]), c(d[2]), c(d[3]), c(d[4]), c(d[5]), c(d[6]), c(d[7]), c(d[8]), c(d[9]), c(d[10]), c(d[11]), c(d[12]), c(d[13]), c(d[14]), c(d[15]), c(d[16]), c(d[17]), c(d[18]), c(d[19]), c(d[20]), c(d[21]), c(d[22]), c(d[23]), c(d[24]), c(d[25]), c(d[26]), c(d[27]), c(d[28]), c(d[29]), c(d[30]), c(d[31]), c(d[32]), c(d[33]), c(d[34]), c(d[35]), c(d[36]), c(d[37]), c(d[38]), c(d[39]), c(d[40]), c(d[41]), c(d[42]), c(d[43]), c(d[44]), c(d[45]), c(d[46]), c(d[47])
#define RW32(c, d) c(d[0]), c(d[1]), c(d[2]), c(d[3]), c(d[4]), c(d[5]), c(d[6]), c(d[7]), c(d[8]), c(d[9]), c(d[10]), c(d[11]), c(d[12]), c(d[13]), c(d[14]), c(d[15]), c(d[16]), c(d[17]), c(d[18]), c(d[19]), c(d[20]), c(d[21]), c(d[22]), c(d[23]), c(d[24]), c(d[25]), c(d[26]), c(d[27]), c(d[28]), c(d[29]), c(d[30]), c(d[31])

__device__ __forceinline__ void reg_fence(float (&d)[80]) { asm volatile("" : RW80("+f", d)::"memory"); }
__device__ __forceinline__ void reg_fence(float (&d)[48]) { asm volatile("" : RW48("+f", d)::"memory"); }
__device__ __forceinline__ void reg_fence(float (&d)[32]) { asm volatile("" : RW32("+f", d)::"memory"); }

template <int NR>
__device__ __forceinline__ void zero(float (&d)[NR]) {
#pragma unroll
    for (int i = 0; i < NR; i++) d[i] = 0.f;
}

constexpr uint32_t HI_SW128 = (1024u >> 4) | (1u << 30);
constexpr uint32_t HI_OST = (2560u >> 4) | (2u << 30);
constexpr uint32_t LO_LBO1 = (1u << 16);
constexpr uint32_t LO_OST = ((512u >> 4) << 16);

template <int TA, int TB, uint32_t HIB, bool ACC>
__device__ __forceinline__ void wgmma(float (&d)[80], uint32_t loA, uint32_t loB) {
#define WG_ASM(SD)                                                          \
    "{\n.reg .b64 da, db;\nmov.b64 da, {%80, %82};\nmov.b64 db, {%81, %83};\n" \
    "wgmma.mma_async.sync.aligned.m64n160k16.f32.bf16.bf16 "               \
    "{%0,%1,%2,%3,%4,%5,%6,%7,%8,%9,%10,%11,%12,%13,%14,%15,%16,%17,%18,%19,%20,%21,%22,%23,%24,%25,%26,%27,%28,%29,%30,%31,%32,%33,%34,%35,%36,%37,%38,%39,%40,%41,%42,%43,%44,%45,%46,%47,%48,%49,%50,%51,%52,%53,%54,%55,%56,%57,%58,%59,%60,%61,%62,%63,%64,%65,%66,%67,%68,%69,%70,%71,%72,%73,%74,%75,%76,%77,%78,%79}, da, db, " SD ", 1, 1, %84, %85;\n}"
    if constexpr (ACC)
        asm volatile(WG_ASM("1") : RW80("+f", d) : "r"(loA), "r"(loB), "n"(HI_SW128), "n"(HIB), "n"(TA), "n"(TB));
    else
        asm volatile(WG_ASM("0") : RW80("=f", d) : "r"(loA), "r"(loB), "n"(HI_SW128), "n"(HIB), "n"(TA), "n"(TB));
#undef WG_ASM
}
template <int TA, int TB, uint32_t HIB, bool ACC>
__device__ __forceinline__ void wgmma(float (&d)[48], uint32_t loA, uint32_t loB) {
#define WG_ASM(SD)                                                          \
    "{\n.reg .b64 da, db;\nmov.b64 da, {%48, %50};\nmov.b64 db, {%49, %51};\n" \
    "wgmma.mma_async.sync.aligned.m64n96k16.f32.bf16.bf16 "               \
    "{%0,%1,%2,%3,%4,%5,%6,%7,%8,%9,%10,%11,%12,%13,%14,%15,%16,%17,%18,%19,%20,%21,%22,%23,%24,%25,%26,%27,%28,%29,%30,%31,%32,%33,%34,%35,%36,%37,%38,%39,%40,%41,%42,%43,%44,%45,%46,%47}, da, db, " SD ", 1, 1, %52, %53;\n}"
    if constexpr (ACC)
        asm volatile(WG_ASM("1") : RW48("+f", d) : "r"(loA), "r"(loB), "n"(HI_SW128), "n"(HIB), "n"(TA), "n"(TB));
    else
        asm volatile(WG_ASM("0") : RW48("=f", d) : "r"(loA), "r"(loB), "n"(HI_SW128), "n"(HIB), "n"(TA), "n"(TB));
#undef WG_ASM
}
template <int TA, int TB, uint32_t HIB, bool ACC>
__device__ __forceinline__ void wgmma(float (&d)[32], uint32_t loA, uint32_t loB) {
#define WG_ASM(SD)                                                          \
    "{\n.reg .b64 da, db;\nmov.b64 da, {%32, %34};\nmov.b64 db, {%33, %35};\n" \
    "wgmma.mma_async.sync.aligned.m64n64k16.f32.bf16.bf16 "               \
    "{%0,%1,%2,%3,%4,%5,%6,%7,%8,%9,%10,%11,%12,%13,%14,%15,%16,%17,%18,%19,%20,%21,%22,%23,%24,%25,%26,%27,%28,%29,%30,%31}, da, db, " SD ", 1, 1, %36, %37;\n}"
    if constexpr (ACC)
        asm volatile(WG_ASM("1") : RW32("+f", d) : "r"(loA), "r"(loB), "n"(HI_SW128), "n"(HIB), "n"(TA), "n"(TB));
    else
        asm volatile(WG_ASM("0") : RW32("=f", d) : "r"(loA), "r"(loB), "n"(HI_SW128), "n"(HIB), "n"(TA), "n"(TB));
#undef WG_ASM
}

__device__ __forceinline__ uint32_t pack_bf16(float lo, float hi) {
    uint32_t r;
    asm("cvt.rn.bf16x2.f32 %0, %1, %2;" : "=r"(r) : "f"(hi), "f"(lo));
    return r;
}
__device__ __forceinline__ float ex2(float x) {
    float r;
    asm("ex2.approx.ftz.f32 %0, %1;" : "=f"(r) : "f"(x));
    return r;
}
__device__ __forceinline__ void stsm4t(uint32_t a, uint32_t r0, uint32_t r1, uint32_t r2, uint32_t r3) {
    asm volatile("stmatrix.sync.aligned.m8n8.x4.trans.shared.b16 [%0], {%1,%2,%3,%4};" ::"r"(a), "r"(r0), "r"(r1), "r"(r2), "r"(r3)
                 : "memory");
}
__device__ __forceinline__ uint32_t lds_u(uint32_t a) {
    uint32_t v;
    asm volatile("ld.shared.u32 %0, [%1];" : "=r"(v) : "r"(a) : "memory");
    return v;
}
__device__ __forceinline__ float2 lds_f2(uint32_t a) {
    float2 v;
    asm volatile("ld.shared.v2.f32 {%0,%1}, [%2];" : "=f"(v.x), "=f"(v.y) : "r"(a) : "memory");
    return v;
}
__device__ __forceinline__ void sts_f(uint32_t a, float v) { asm volatile("st.shared.f32 [%0], %1;" ::"r"(a), "f"(v) : "memory"); }
__device__ __forceinline__ void sts_u(uint32_t a, uint32_t v) { asm volatile("st.shared.u32 [%0], %1;" ::"r"(a), "r"(v) : "memory"); }
__device__ __forceinline__ void sts_f2(uint32_t a, float x, float y) {
    asm volatile("st.shared.v2.f32 [%0], {%1,%2};" ::"r"(a), "f"(x), "f"(y) : "memory");
}

__device__ __forceinline__ void store_tile_t(const float (&d)[80], uint32_t addr) {
#pragma unroll
    for (int j = 0; j < 10; j++)
        stsm4t(addr + j * 2048, pack_bf16(d[8 * j], d[8 * j + 1]), pack_bf16(d[8 * j + 2], d[8 * j + 3]),
               pack_bf16(d[8 * j + 4], d[8 * j + 5]), pack_bf16(d[8 * j + 6], d[8 * j + 7]));
}
template <int NR>
__device__ __forceinline__ void store_out_tile(const float (&d)[NR], uint32_t base, uint32_t lane, uint32_t w) {
    const uint32_t mi = lane >> 3, i = lane & 7;
    const uint32_t chunk = 2 * w + (mi & 1);
    const uint32_t q0 = 8 * (i >> 1) + 2 * (mi >> 1) + (i & 1);
    const uint32_t a0 = base + q0 * 128 + ((chunk ^ (q0 & 7)) << 4);
    const uint32_t a1 = base + (q0 + 4) * 128 + ((chunk ^ ((q0 + 4) & 7)) << 4);
#pragma unroll
    for (int j = 0; j < NR / 8; j++)
        stsm4t(((j & 1) ? a1 : a0) + (j >> 1) * 4096, pack_bf16(d[8 * j], d[8 * j + 1]), pack_bf16(d[8 * j + 2], d[8 * j + 3]),
               pack_bf16(d[8 * j + 4], d[8 * j + 5]), pack_bf16(d[8 * j + 6], d[8 * j + 7]));
}

struct TrueT { static constexpr bool value = true; };
struct FalseT { static constexpr bool value = false; };

template <int V>
struct IntT { static constexpr int value = V; };

__device__ __forceinline__ uint32_t get_item(uint32_t sb, int it) {
    mbar_wait(sb + BAR_ITEM + it * 8, 0);
    return lds_u(sb + OFF_ITEM + it * 4);
}
__device__ __forceinline__ uint32_t get_item_warp(uint32_t sb, int it) { return __shfl_sync(0xffffffffu, get_item(sb, it), 0); }

struct Ring {
    uint32_t slot, ph;
    __device__ __forceinline__ void adv(uint32_t k) {
        slot += k;
        if (slot >= NSLOT) { slot -= NSLOT; ph ^= 1; }
    }
};

template <int K>
__device__ __forceinline__ void qk_step(float (&s)[80], uint32_t loK, uint32_t loQ) {
    wgmma<0, 0, HI_SW128, K != 0>(s, loK + (K >> 2) * (8192 >> 4) + (K & 3) * 2, loQ + (K >> 2) * (XS >> 4) + (K & 3) * 2);
}
template <int K0, int K1>
__device__ __forceinline__ void qk_steps(float (&s)[80], uint32_t loK, uint32_t loQ) {
    if constexpr (K0 < K1) {
        qk_step<K0>(s, loK, loQ);
        qk_steps<K0 + 1, K1>(s, loK, loQ);
    }
}
__device__ __forceinline__ uint32_t add_bf2(uint32_t a, uint32_t b) {
    uint32_t r;
    asm("add.rn.bf16x2 %0, %1, %2;" : "=r"(r) : "r"(a), "r"(b));
    return r;
}
template <int J>
__device__ __forceinline__ void exp_block(const float (&s)[80], uint32_t (&k)[40], uint32_t pa, float mref) {
    if constexpr (J < 10) {
#pragma unroll
        for (int i = 4 * J; i < 4 * J + 4; i++)
            k[i] = pack_bf16(ex2(fmaf(s[2 * i], SM_C, -mref)), ex2(fmaf(s[2 * i + 1], SM_C, -mref)));
#pragma unroll
        for (int i = 0; i < 4; i++)
            asm volatile("stmatrix.sync.aligned.m8n8.x1.trans.shared.b16 [%0], {%1};" ::"r"(((i & 1) ? pa ^ 16 : pa) + J * 2048 + (i >> 1) * 1024),
                         "r"(k[4 * J + i])
                         : "memory");
        exp_block<J + 1>(s, k, pa, mref);
    }
}
__device__ __forceinline__ void sum_block(const uint32_t (&k)[40], float (&l)[10], uint32_t lane) {
    const bool b4 = lane & 16, b3 = lane & 8;
    uint32_t ps[20], t[10];
#pragma unroll
    for (int j = 0; j < 20; j++) ps[j] = add_bf2(k[2 * j], k[2 * j + 1]);
#pragma unroll
    for (int j = 0; j < 10; j++)
        t[j] = add_bf2(b4 ? ps[2 * j + 1] : ps[2 * j], __shfl_xor_sync(0xffffffffu, b4 ? ps[2 * j] : ps[2 * j + 1], 16));
#pragma unroll
    for (int i = 0; i < 5; i++) {
        const uint32_t a = b3 ? t[i + 5] : t[i], b = __shfl_xor_sync(0xffffffffu, b3 ? t[i] : t[i + 5], 8);
        l[2 * i] += __uint_as_float(a << 16) + __uint_as_float(b << 16);
        l[2 * i + 1] += __uint_as_float(a & 0xffff0000u) + __uint_as_float(b & 0xffff0000u);
    }
}
__device__ __forceinline__ void sum_store(const float (&l)[10], uint32_t lane, uint32_t lxa) {
    const bool b2 = lane & 4;
#pragma unroll
    for (int i = 0; i < 5; i++)
        sts_f(lxa + i * 64, (b2 ? l[2 * i + 1] : l[2 * i]) + __shfl_xor_sync(0xffffffffu, b2 ? l[2 * i] : l[2 * i + 1], 4));
}

__device__ __forceinline__ void fallback_unit(const Params& P, uint32_t e, uint32_t tid) {
    const uint32_t lane = tid & 31, br = IT_BR(e), b = IT_B(e), h = IT_H0(e);
    const __nv_bfloat162* wq = (const __nv_bfloat162*)(P.pwq[br] + h * 192) + lane;
    const __nv_bfloat162* kp = (const __nv_bfloat162*)(P.pk[br] + (size_t)(b * 32 + h) * 512 * 192) + lane;
    const __nv_bfloat162* vp = (const __nv_bfloat162*)(P.pv[br] + (size_t)(b * 32 + h) * 512 * 192) + lane;
#pragma unroll 1
    for (uint32_t qi = 0; qi < 40; qi++) {
        const uint32_t q = 4 * qi + (tid >> 5);
        const __nv_bfloat16* xr = P.px[br] + (size_t)(b * 160 + q) * 640;
        float a[6] = {0.f, 0.f, 0.f, 0.f, 0.f, 0.f};
#pragma unroll 4
        for (int k = 0; k < 640; k++) {
            const float xv = __bfloat162float(xr[k]);
#pragma unroll
            for (int i = 0; i < 3; i++) {
                const float2 wv = __bfloat1622float2(wq[(size_t)k * 3072 + i * 32]);
                a[2 * i] = fmaf(xv, wv.x, a[2 * i]);
                a[2 * i + 1] = fmaf(xv, wv.y, a[2 * i + 1]);
            }
        }
#pragma unroll
        for (int i = 0; i < 6; i++) a[i] = __bfloat162float(__float2bfloat16(a[i]));
        auto score = [&](int key) {
            float d = 0.f;
#pragma unroll
            for (int i = 0; i < 3; i++) {
                const float2 kv = __bfloat1622float2(kp[key * 96 + i * 32]);
                d = fmaf(a[2 * i], kv.x, fmaf(a[2 * i + 1], kv.y, d));
            }
#pragma unroll
            for (int o = 16; o > 0; o >>= 1) d += __shfl_xor_sync(0xffffffffu, d, o);
            return d;
        };
        float m = -INFINITY;
#pragma unroll 4
        for (int key = 0; key < 512; key++) m = fmaxf(m, score(key));
        float o[6] = {0.f, 0.f, 0.f, 0.f, 0.f, 0.f}, sum = 0.f;
#pragma unroll 4
        for (int key = 0; key < 512; key++) {
            const float p = ex2((score(key) - m) * SM_C);
            sum += p;
#pragma unroll
            for (int i = 0; i < 3; i++) {
                const float2 vv = __bfloat1622float2(vp[key * 96 + i * 32]);
                o[2 * i] = fmaf(p, vv.x, o[2 * i]);
                o[2 * i + 1] = fmaf(p, vv.y, o[2 * i + 1]);
            }
        }
        const float inv = __fdividef(1.f, sum);
        __nv_bfloat16* op = (__nv_bfloat16*)ostash(br, b, h) + (q >> 5) * 256 + 2 * ((q & 31) >> 3) + (q & 1);
#pragma unroll
        for (int i = 0; i < 6; i++) {
            const uint32_t d = (i >> 1) * 64 + 2 * lane + (i & 1);
            op[(d >> 3) * 1280 + (d & 7) * 32 + ((((q & 7) >> 1) ^ ((d & 7) >> 1)) << 3)] = __float2bfloat16(o[i] * inv);
        }
    }
}

template <int W>
struct PendO {
    static constexpr int N = W == 0 ? 14 : 16;
    uint32_t v[4 * N];
    unsigned char* gp;
    uint32_t pend, sig;
    template <int I>
    __device__ __forceinline__ void store() const {
        if constexpr (I < N) {
            constexpr int g = I < 10 ? I / 2 : (I - 10) / 2 + (W == 0 ? 3 : 0);
            constexpr int off = (I < 10 ? W : 2) * XS + g * 512 + (I & 1) * 2560;
            asm volatile(
                "{\n.reg .pred p;\nsetp.ne.u32 p, %6, 0;\n@p st.global.v4.b32 [%0+%5], {%1,%2,%3,%4};\n}" ::"l"(gp),
                "r"(v[4 * I]), "r"(v[4 * I + 1]), "r"(v[4 * I + 2]), "r"(v[4 * I + 3]), "n"(off), "r"(pend)
                : "memory");
        }
    }
    template <int I>
    __device__ __forceinline__ void flush() const {
        if constexpr (I < N) {
            store<I>();
            flush<I + 1>();
        }
    }
    __device__ __forceinline__ void clear() {
#pragma unroll
        for (int i = 0; i < 4 * N; i++) v[i] = 0;
        gp = nullptr;
        pend = 0;
        sig = 0;
    }
};

template <int W, int KK, int KE>
__device__ __forceinline__ void qproj(float (&q0)[80], float (&q1)[80], uint32_t sb, Ring& r, uint32_t phm, const PendO<W>& po) {
    const uint32_t loR = ((sb + OFF_R) >> 4) | LO_LBO1;
    const uint32_t loRing = ((sb + OFF_RING) >> 4) | LO_LBO1;
    constexpr int xs = KK % 5;
    const uint32_t pslot = r.slot;
    if (KK > 0) r.adv(1);
    if (W == 1 && KK == QHOLD) nb_sync<NB_SDONE, 256>();
    mbar_wait(sb + BAR_RFULL + r.slot * 8, r.ph);
    mbar_wait(sb + BAR_XFULL + xs * 8, ((phm >> xs) ^ (KK / 5)) & 1);
    const uint32_t a = loRing + r.slot * (SLOT >> 4) + (W == 0 ? 0 : 1024), b = loR + xs * (XS >> 4);
    wg_fence();
    wgmma<1, 0, HI_SW128, KK != 0>(q0, a, b);
    if (W == 0) wgmma<1, 0, HI_SW128, KK != 0>(q1, a + 512, b);
#pragma unroll
    for (int k = 1; k < 4; k++) {
        wgmma<1, 0, HI_SW128, true>(q0, a + k * 128, b + k * 2);
        if (W == 0) wgmma<1, 0, HI_SW128, true>(q1, a + 512 + k * 128, b + k * 2);
    }
    wg_commit();
    if (KK > 0) {
        wg_wait<1>();
        mbar_arrive_warp(sb + BAR_REMPTY + pslot * 8, 1);
        if (KK <= 5) mbar_arrive_warp(sb + (BAR_XEMPTY + (KK - 1) * 8), 1);
        if (W == 1 && KK == 7) nb_arrive<NB_PDONE, 256>();
    }
    if constexpr (W == 0 && KK < 5) {
        po.template store<3 * KK>();
        po.template store<3 * KK + 1>();
        po.template store<3 * KK + 2>();
        if (KK == 4 && po.sig) nb_arrive<NB_ODONE, 288>();
    }
    if constexpr (W == 1 && KK >= QPRE && KK < QPRE + 4) {
        po.template store<4 * (KK - QPRE)>();
        po.template store<4 * (KK - QPRE) + 1>();
        po.template store<4 * (KK - QPRE) + 2>();
        po.template store<4 * (KK - QPRE) + 3>();
        if (KK == QPRE + 3 && po.sig) nb_arrive<NB_ODONE, 288>();
    }
    if constexpr (KK + 1 < KE) {
        qproj<W, KK + 1, KE>(q0, q1, sb, r, phm, po);
    } else if constexpr (KE == 10) {
        if (W == 0) nb_arrive<NB_SDONE, 256>();
        wg_wait<0>();
        reg_fence(q0);
        if (W == 0) reg_fence(q1);
        mbar_arrive_warp(sb + BAR_REMPTY + r.slot * 8, 1);
        r.adv(1);
    }
}

template <int NR>
__device__ __forceinline__ void opack(const float (&o)[NR], int gl, const float2* sc, uint32_t* v) {
#pragma unroll
    for (int hh = 0; hh < 2; hh++)
#pragma unroll
        for (int t = 0; t < 4; t++)
            v[4 * hh + t] = pack_bf16(o[16 * gl + 4 * t + 2 * hh] * sc[t].x, o[16 * gl + 4 * t + 2 * hh + 1] * sc[t].y);
}

template <int NR>
__device__ __forceinline__ void dump_acc(const float (&c)[NR], float4* p) {
#pragma unroll
    for (int i = 0; i < NR / 4; i++) p[i * 128] = make_float4(c[4 * i], c[4 * i + 1], c[4 * i + 2], c[4 * i + 3]);
}
__device__ __forceinline__ void wait_flag(const unsigned int* f, uint32_t epoch) {
    uint32_t v, n = 0;
    do {
        asm volatile("ld.acquire.gpu.global.u32 %0, [%1];" : "=r"(v) : "l"(f) : "memory");
        if (++n > 0x400000) __trap();
    } while (v != epoch);
}

template <bool IS_S>
__device__ __forceinline__ void op_item(uint32_t e, uint32_t sb, Ring& r, uint32_t& phm) {
    constexpr int T0 = IS_S ? 0 : 2;
    constexpr uint32_t BOFF = IS_S ? (3 * 512) >> 4 : 0;
    const uint32_t loRing = ((sb + OFF_RING) >> 4) | LO_LBO1;
    const uint32_t loO = ((sb + OFF_R) >> 4) | LO_OST;
    float c0[80], c1[80], c2[IS_S ? 32 : 48];
    const int T2 = 6 * (IT_H1(e) - IT_H0(e));
    uint32_t xs = 0;
    auto step = [&](auto first, uint32_t hf) {
        constexpr bool F = decltype(first)::value;
        if (hf == 0) {
            mbar_wait(sb + BAR_XFULL + xs * 8, (phm >> xs) & 1);
            phm ^= 1u << xs;
        }
        mbar_wait(sb + BAR_RFULL + r.slot * 8, r.ph);
        const uint32_t a = loRing + r.slot * (SLOT >> 4), b = loO + xs * (XS >> 4) + hf * 640;
        wg_fence();
        wgmma<1, 1, HI_OST, !F>(c0, a + T0 * 256, b);
        wgmma<1, 1, HI_OST, !F>(c1, a + T0 * 256 + 256, b);
        wgmma<1, 1, HI_OST, !F>(c2, a + 1024, b + BOFF);
        wgmma<1, 1, HI_OST, true>(c0, a + T0 * 256 + 128, b + 320);
        wgmma<1, 1, HI_OST, true>(c1, a + T0 * 256 + 384, b + 320);
        wgmma<1, 1, HI_OST, true>(c2, a + 1024 + 128, b + 320 + BOFF);
        wg_commit();
    };
    step(TrueT{}, 0);
#pragma unroll 1
    for (int t = 1; t < T2; t++) {
        const uint32_t pslot = r.slot, pxs = xs;
        r.adv(1);
        if ((t & 1) == 0 && ++xs == 5) xs = 0;
        step(FalseT{}, t & 1);
        wg_wait<1>();
        mbar_arrive_warp(sb + BAR_REMPTY + pslot * 8, 1);
        if ((t & 1) == 0 && t + 8 < T2) mbar_arrive_warp(sb + BAR_XEMPTY + pxs * 8, 1);
    }
    wg_wait<0>();
    reg_fence(c0);
    reg_fence(c1);
    reg_fence(c2);
    mbar_arrive_warp(sb + BAR_REMPTY + r.slot * 8, 1);
    r.adv(1);
    if (IT_PART(e)) {
#pragma unroll
        for (int m = 0; m < 5; m++) mbar_arrive_warp(sb + BAR_XEMPTY + m * 8, 1);
        float4* pp = g_part + (size_t)((IT_BR(e) * 16 + IT_B(e)) * 10 + IT_HALF(e) * 5) * 2560 + (threadIdx.x & 127);
        dump_acc(c0, pp + T0 * 2560);
        dump_acc(c1, pp + (T0 + 1) * 2560);
        dump_acc(c2, pp + 4 * 2560 + (IS_S ? 12 * 128 : 0));
    } else {
        nb_sync<NB_OPEND, 256>();
        const uint32_t lane = threadIdx.x & 31, w = (threadIdx.x >> 5) & 3;
        store_out_tile(c0, sb + OFF_R + T0 * XS, lane, w);
        store_out_tile(c1, sb + OFF_R + (T0 + 1) * XS, lane, w);
        store_out_tile(c2, sb + OFF_R + 4 * XS + (IS_S ? 96 * 128 : 0), lane, w);
        fence_async_smem();
    }
    nb_arrive<NB_ODONE, 288>();
}

template <int W>
__device__ __forceinline__ void on_item(uint32_t e, uint32_t sb, Ring& r, uint32_t& phm, uint32_t epoch) {
    const uint32_t loRing = ((sb + OFF_RING) >> 4) | LO_LBO1;
    const uint32_t loO = ((sb + OFF_R) >> 4) | LO_OST;
    float c[80];
    const int T = 3 * (IT_H1(e) - IT_H0(e));
    uint32_t xs = 0;
    auto step = [&](auto first) {
        constexpr bool F = decltype(first)::value;
        mbar_wait(sb + BAR_XFULL + xs * 8, (phm >> xs) & 1);
        phm ^= 1u << xs;
        mbar_wait(sb + BAR_RFULL + r.slot * 8, r.ph);
        const uint32_t a = loRing + r.slot * (SLOT >> 4) + W * 512, b = loO + xs * (XS >> 4);
        wg_fence();
        wgmma<1, 1, HI_OST, !F>(c, a, b);
#pragma unroll
        for (int k = 1; k < 4; k++) wgmma<1, 1, HI_OST, true>(c, a + k * 128, b + k * 320);
        wg_commit();
    };
    auto run = [&](int t0, int t1) {
#pragma unroll 1
        for (int t = t0; t < t1; t++) {
            const uint32_t pslot = r.slot, pxs = xs;
            r.adv(1);
            if (++xs == 5) xs = 0;
            step(FalseT{});
            wg_wait<1>();
            mbar_arrive_warp(sb + BAR_REMPTY + pslot * 8, 1);
            mbar_arrive_warp_if(sb + BAR_XEMPTY + pxs * 8, 1, t + 4 < T);
        }
    };
    step(TrueT{});
    const int tm = T >> 1;
    run(1, tm);
    float4 pv[20];
    {
        const uint32_t tile = 2 * IT_HALF(e) + W, bb = IT_BR(e) * 16 + IT_B(e);
        wait_flag(&g_pflag[bb * 2 + (tile >= 5)], epoch);
        const float4* pp = g_part + (size_t)(bb * 10 + tile) * 2560 + (threadIdx.x & 127);
#pragma unroll
        for (int i = 0; i < 20; i++) pv[i] = __ldcg(pp + i * 128);
    }
    run(tm, T);
    wg_wait<0>();
    reg_fence(c);
    mbar_arrive_warp(sb + BAR_REMPTY + r.slot * 8, 1);
    r.adv(1);
    nb_sync<NB_OPEND, 256>();
#pragma unroll
    for (int i = 0; i < 20; i++) {
        c[4 * i] += pv[i].x;
        c[4 * i + 1] += pv[i].y;
        c[4 * i + 2] += pv[i].z;
        c[4 * i + 3] += pv[i].w;
    }
    store_out_tile(c, sb + OFF_R + W * XS, threadIdx.x & 31, (threadIdx.x >> 5) & 3);
    fence_async_smem();
    nb_arrive<NB_ODONE, 288>();
}

template <int W>
__device__ __forceinline__ uint32_t qa_item(const Params& P, uint32_t sb, Ring& r, uint32_t phm, PendO<W>& po,
                                            float (&oa)[80], float (&ob)[W == 0 ? 32 : 48], int it) {
    const uint32_t loR = ((sb + OFF_R) >> 4) | LO_LBO1;
    const uint32_t loRing = ((sb + OFF_RING) >> 4) | LO_LBO1;
    const uint32_t lane = threadIdx.x & 31, w = (threadIdx.x >> 5) & 3;
    const uint32_t sta = sb + OFF_R + (lane >> 4) * 1024 + (lane & 7) * 128 + (((2 * w + ((lane >> 3) & 1)) ^ (lane & 7)) << 4);
    auto pack_o = [&](int ie) {
#pragma unroll
        for (int g = 0; g < 5; g++) {
            float2 sc[4];
#pragma unroll
            for (int t = 0; t < 4; t++) sc[t] = lds_f2(sb + OFF_LINV + (lane & 3) * 8 + (4 * g + t) * 32);
            opack(oa, g, sc, po.v + 8 * g);
            if (W == 0 && g >= 3) opack(ob, g - 3, sc, po.v + 40 + 8 * (g - 3));
            if (W == 1 && g < 3) opack(ob, g, sc, po.v + 40 + 8 * g);
        }
        const uint32_t e = lds_u(sb + OFF_ITEM + ie * 4);
        po.gp = ostash(IT_BR(e), IT_B(e), IT_H0(e)) + w * 5120 + (lane >> 2) * 64 + (((lane ^ (lane >> 3)) & 3) << 4);
    };
    {
        float q0[80], q1[80];
        if constexpr (W == 0) {
            qproj<W, 0, 10>(q0, q1, sb, r, phm, po);
        } else {
            qproj<W, 0, QPRE>(q0, q1, sb, r, phm, po);
            if (po.sig) nb_sync<NB_VOTE, 256>();
            po.pend = po.sig && !__any_sync(0xffffffffu, lds_u(sb + OFF_FB) != 0);
            pack_o(it > 0 ? it - 1 : 0);
            TS(W, 26);
            qproj<W, QPRE, 10>(q0, q1, sb, r, phm, po);
        }
        TS(W, 1);
        if (W == 0) {
            nb_sync<NB_PDONE, 256>();
            store_tile_t(q0, sta);
            store_tile_t(q1, sta + XS);
        } else {
            store_tile_t(q0, sta + 2 * XS);
        }
    }
    fence_async_smem();
    float s[80], l[10];
#pragma unroll
    for (int i = 0; i < 80; i++) oa[i] = 0.f;
#pragma unroll
    for (int i = 0; i < (W == 0 ? 32 : 48); i++) ob[i] = 0.f;
#pragma unroll
    for (int i = 0; i < 10; i++) l[i] = 0.f;
    reg_fence(oa);
    reg_fence(ob);
    auto pv = [&](uint32_t buf) {
        mbar_wait(sb + BAR_RFULL + r.slot * 8, r.ph);
        const uint32_t a = loRing + r.slot * (SLOT >> 4), b = loR + (3 + buf) * (XS >> 4);
        wg_fence();
#pragma unroll
        for (int k = 0; k < 4; k++) {
            wgmma<1, 0, HI_SW128, true>(oa, a + W * 512 + k * 128, b + k * 2);
            wgmma<1, 0, HI_SW128, true>(ob, a + 1024 + k * 128, b + (W == 0 ? (96 * 128) >> 4 : 0) + k * 2);
        }
        wg_commit();
    };
    float mref;
    uint32_t kslot, vslot;
    const uint32_t lxa = sb + OFF_LX + w * 640 + (((lane & 8) ? 80 : 0) + ((lane >> 1) & 8) + 2 * (lane & 3) + ((lane >> 2) & 1)) * 4;
    auto tail = [&](bool rel_other, int i) {
        uint32_t ps[40];
        exp_block<0>(s, ps, sta + (3 + W) * XS, mref);
        if (rel_other) {
            wg_wait<0>();
            mbar_arrive_warp(sb + BAR_REMPTY + vslot * 8, 1);
            if (W == 1) mbar_arrive_warp_if(sb + BAR_XEMPTY + 24, 1, i == 3);
        }
        fence_async_smem();
        if (W == 1 && i == 3) {
            nb_sync<NB_W + W, 128>();
            pv(W);
        }
        nb_arrive<NB_PFULL + W, 256>();
        TS(W, 6 + 5 * i);
        mbar_wait(sb + BAR_RFULL + r.slot * 8, r.ph);
        sum_block(ps, l, lane);
        TS(W, 7 + 5 * i);
        if (W == 0 || i < 3) {
            nb_sync<NB_W + W, 128>();
            pv(W);
        }
        TS(W, 8 + 5 * i);
    };
    if (W == 0) {
        nb_sync<NB_W, 128>();
        TS(W, 2);
        mbar_wait(sb + BAR_RFULL + r.slot * 8, r.ph);
        wg_fence();
        qk_steps<0, 8>(s, loRing + r.slot * (SLOT >> 4), loR);
        nb_sync<NB_Q2, 256>();
        qk_steps<8, 12>(s, loRing + r.slot * (SLOT >> 4), loR);
        wg_commit();
        nb_arrive<NB_Q01, 256>();
        TS(W, 4);
        wg_wait<0>();
        reg_fence(s);
        mbar_arrive_warp(sb + BAR_REMPTY + r.slot * 8, 2);
        r.adv(2);
        float m0 = fmaxf(s[0], s[5]), m1 = fmaxf(s[10], s[15]);
#pragma unroll
        for (int i = 20; i < 80; i += 10) {
            m0 = fmaxf(m0, s[i]);
            m1 = fmaxf(m1, s[i + 5]);
        }
        int key = __float_as_int(fmaxf(m0, m1));
        key ^= (key >> 31) & 0x7fffffff;
        key = __reduce_max_sync(0xffffffffu, key);
        key ^= (key >> 31) & 0x7fffffff;
        sts_u(sb + OFF_GM + w * 4, key);
        sts_u(sb + OFF_FB, 0);
        nb_sync<NB_W, 128>();
        const float2 u = lds_f2(sb + OFF_GM), v = lds_f2(sb + OFF_GM + 8);
        mref = fmaxf(fmaxf(u.x, u.y), fmaxf(v.x, v.y)) * SM_C;
        TS(W, 5);
        tail(false, 0);
    } else {
        nb_arrive<NB_Q2, 256>();
        TS(W, 2);
        nb_sync<NB_Q01, 256>();
    }
#pragma unroll 1
    for (int i = (W == 0 ? 1 : 0); i < 4; i++) {
        const uint32_t pvslot = r.slot;
        r.adv(1);
        kslot = r.slot;
        mbar_wait(sb + BAR_RFULL + r.slot * 8, r.ph);
        wg_fence();
        qk_steps<0, 12>(s, loRing + r.slot * (SLOT >> 4), loR);
        wg_commit();
        wg_wait<1>();
        mbar_arrive_warp_if(sb + BAR_REMPTY + pvslot * 8, 1, W == 0 || i > 0);
        r.adv(1);
        vslot = r.slot;
        TS(W, 4 + 5 * i);
        nb_sync<NB_PFULL + (W ^ 1), 256>();
        pv(W ^ 1);
        if (W == 1) {
            const float2 u = lds_f2(sb + OFF_GM), v = lds_f2(sb + OFF_GM + 8);
            mref = fmaxf(fmaxf(u.x, u.y), fmaxf(v.x, v.y)) * SM_C;
        }
        wg_wait<1>();
        reg_fence(s);
        mbar_arrive_warp(sb + BAR_REMPTY + kslot * 8, 2);
        if (W == 1) {
            mbar_arrive_warp_if(sb + BAR_XEMPTY + 0, 2, i == 3);
            mbar_arrive_warp_if(sb + BAR_XEMPTY + 8, 2, i == 3);
            mbar_arrive_warp_if(sb + BAR_XEMPTY + 16, 2, i == 3);
        }
        r.adv(W == 1 && i == 3 ? 1 : 2);
        TS(W, 5 + 5 * i);
        tail(true, i);
    }
    if (W == 0) {
        const uint32_t tid = threadIdx.x & 127;
        float2 v = make_float2(0.f, 0.f);
        auto gather = [&]() {
            if (tid < 80) {
#pragma unroll
                for (int i = 0; i < 4; i++) {
                    const float2 u = lds_f2(sb + OFF_LX + i * 640 + tid * 8);
                    v.x += u.x;
                    v.y += u.y;
                }
            }
        };
        sum_store(l, lane, lxa);
        nb_sync<NB_W, 128>();
        gather();
        nb_arrive<NB_LX, 256>();
        wg_wait<0>();
        mbar_arrive_warp(sb + BAR_REMPTY + r.slot * 8, 1);
        mbar_arrive_warp(sb + BAR_XEMPTY + 24, 1);
        r.adv(1);
        nb_sync<NB_PFULL + 1, 256>();
        pv(1);
        TS(W, 24);
        nb_sync<NB_L, 256>();
        gather();
        if (tid < 80) {
            sts_f2(sb + OFF_LINV + tid * 8, __fdividef(1.f, v.x), __fdividef(1.f, v.y));
            if (!(v.x >= 5.421010862e-20f && v.x <= 1.8446744e19f && v.y >= 5.421010862e-20f && v.y <= 1.8446744e19f))
                sts_u(sb + OFF_FB, 1);
        }
    }
    if (W == 0) {
        nb_arrive<NB_VOTE, 256>();
        nb_sync<NB_W, 128>();
    } else {
        nb_sync<NB_LX, 256>();
        sum_store(l, lane, lxa);
        nb_arrive<NB_L, 256>();
    }
    const uint32_t nx = get_item_warp(sb, it + 1);
    wg_wait<0>();
    reg_fence(oa);
    reg_fence(ob);
    mbar_arrive_warp(sb + BAR_REMPTY + r.slot * 8, 1);
    mbar_arrive_warp(sb + BAR_XEMPTY + 32, 1);
    r.adv(1);
    TS(W, 25);
    po.sig = 1;
    if (W == 0) {
        const bool any = __any_sync(0xffffffffu, lds_u(sb + OFF_FB) != 0);
        pack_o(it);
        po.pend = !any;
        if (any) {
            fallback_unit(P, lds_u(sb + OFF_ITEM + it * 4), threadIdx.x & 127);
            __syncwarp();
        }
    }
    if (IT_TYPE(nx) != IT_QA) {
        if (W == 1) {
            nb_sync<NB_VOTE, 256>();
            po.pend = !__any_sync(0xffffffffu, lds_u(sb + OFF_FB) != 0);
            pack_o(it);
        }
        po.template flush<0>();
        nb_arrive<NB_ODONE, 288>();
        po.sig = 0;
        po.pend = 0;
    }
    return nx;
}

__global__ void __launch_bounds__(384, 1) fused_kernel(const __grid_constant__ Params P) {
    extern __shared__ __align__(1024) unsigned char smem_raw[];
    const uint32_t sb = (uint32_t)__cvta_generic_to_shared(smem_raw);
    const uint32_t wgid = __shfl_sync(0xffffffffu, threadIdx.x >> 7, 0);
    const uint32_t cta = blockIdx.x;

    uint32_t epoch = 0;
    if (wgid == 0) epoch = *(volatile unsigned int*)&g_epoch[cta] + 1;
    if (threadIdx.x == 0) {
        if (sb & 1023) __trap();
        sts_u(sb + OFF_FB + 4, epoch);
        for (int i = 0; i < NSLOT; i++) {
            mbar_init(sb + BAR_RFULL + i * 8, 1);
            mbar_init(sb + BAR_REMPTY + i * 8, 8);
            mbar_init(sb + BAR_XFULL + i * 8, 1);
            mbar_init(sb + BAR_XEMPTY + i * 8, 8);
        }
        for (int i = 0; i < MAXI; i++) mbar_init(sb + BAR_ITEM + i * 8, 1);
        asm volatile("fence.mbarrier_init.release.cluster;" ::: "memory");
        fence_async_smem();
    }
    __syncthreads();

    if (wgid == 0) {
        asm volatile("setmaxnreg.dec.sync.aligned.u32 24;");
        const uint32_t warp = __shfl_sync(0xffffffffu, threadIdx.x >> 5, 0);
        if (warp == 0) {
            if (threadIdx.x == 0) {
                *(volatile unsigned int*)&g_epoch[cta] = epoch;
                const uint64_t pol_first = mkpol<1>(), pol_norm = mkpol<POL_W>();
                if (cta == 0) *(volatile unsigned int*)&g_ticket[(epoch + 1) & 1] = 0;
                Ring r{0, 1};
                {
                    const uint32_t d = P.delay[cta];
                    uint32_t t0, t1;
                    asm volatile("mov.u32 %0, %%clock;" : "=r"(t0));
                    do {
                        asm volatile("mov.u32 %0, %%clock;" : "=r"(t1));
                    } while (t1 - t0 < d);
                }
                uint32_t e = P.items[cta][0];
#pragma unroll 1
                for (int it = 0;; it++) {
                    sts_u(sb + OFF_ITEM + it * 4, e);
                    asm volatile("mbarrier.arrive.shared::cta.b64 _, [%0];" ::"r"(sb + BAR_ITEM + it * 8) : "memory");
                    if (e == 0) break;
                    uint32_t nx = P.items[cta][it + 1 < NSTAT ? it + 1 : NSTAT - 1];
                    if (IT_TYPE(e) == IT_ON || it + 2 == MAXI) nx = 0;
                    const uint32_t br = IT_BR(e);
                    if (IT_TYPE(e) == IT_QA) {
                        const uint32_t h = IT_H0(e);
#pragma unroll 1
                        for (int kk = 0; kk < 10; kk++) {
                            mbar_wait(sb + BAR_REMPTY + r.slot * 8, r.ph);
                            mbar_expect(sb + BAR_RFULL + r.slot * 8, SLOT);
                            tma3(sb + OFF_RING + r.slot * SLOT, &P.wq[br], kk * 64, h * 3, sb + BAR_RFULL + r.slot * 8, pol_norm);
                            r.adv(1);
                        }
                        const int row0 = (IT_B(e) * 32 + h) * 512;
#pragma unroll 1
                        for (int n = 0; n < 16; n++) {
                            if (n == 12 && nx == IT_DYN) {
                                const uint32_t t = atomicAdd(&g_ticket[epoch & 1], 1);
                                nx = t < P.nlist ? P.list[t] : 0;
                            }
                            const bool isv = n == 15 || (n > 0 && !(n & 1));
                            const int j = n == 15 ? 7 : isv ? (n - 2) >> 1 : (n + 1) >> 1;
                            mbar_wait(sb + BAR_REMPTY + r.slot * 8, r.ph);
                            mbar_expect(sb + BAR_RFULL + r.slot * 8, SLOT);
                            tma3(sb + OFF_RING + r.slot * SLOT, isv ? &P.v[br] : &P.k[br], row0 + j * 64, 0,
                                 sb + BAR_RFULL + r.slot * 8, pol_first);
                            r.adv(1);
                        }
                    } else {
                        const int r0 = IT_H0(e) * 192, r1 = IT_H1(e) * 192;
                        const bool wide = IT_TYPE(e) == IT_OP;
#pragma unroll 1
                        for (int row = r0; row < r1; row += wide ? 32 : 64) {
                            mbar_wait(sb + BAR_REMPTY + r.slot * 8, r.ph);
                            mbar_expect(sb + BAR_RFULL + r.slot * 8, wide ? XS : 16384);
                            tma3(sb + OFF_RING + r.slot * SLOT, wide ? &P.wo[br] : &P.won[br], row, IT_HALF(e) * (wide ? 5 : 2),
                                 sb + BAR_RFULL + r.slot * 8, pol_norm);
                            r.adv(1);
                        }
                        if (nx == IT_DYN) {
                            const uint32_t t = atomicAdd(&g_ticket[epoch & 1], 1);
                            nx = t < P.nlist ? P.list[t] : 0;
                        }
                    }
                    e = nx;
                }
            }
        } else if (warp == 1) {
            if (threadIdx.x == 32) {
                const uint64_t pol_norm = mkpol<POL_X>(), pol_o = mkpol<POL_O>();
                uint32_t phm = 0x1f;
#pragma unroll 1
                for (int it = 0;; it++) {
                    const uint32_t e = get_item(sb, it);
                    if (e == 0) break;
                    const uint32_t br = IT_BR(e);
                    uint32_t xs = 0;
                    if (IT_TYPE(e) == IT_QA) {
#pragma unroll 1
                        for (int kk = 0; kk < 10; kk++) {
                            mbar_wait(sb + BAR_XEMPTY + xs * 8, (phm >> xs) & 1);
                            phm ^= 1u << xs;
                            mbar_expect(sb + BAR_XFULL + xs * 8, XS);
                            tma3(sb + OFF_R + xs * XS, &P.x[br], IT_B(e) * 160, kk, sb + BAR_XFULL + xs * 8, pol_norm);
                            if (++xs == 5) xs = 0;
                        }
                    } else {
                        const uint32_t u0 = (br * 16 + IT_B(e)) * 32;
#pragma unroll 1
                        for (uint32_t u = u0 + IT_H0(e); u < u0 + IT_H1(e); u++) {
                            wait_flag(&g_flag[u], epoch);
                            asm volatile("fence.proxy.async;" ::: "memory");
#pragma unroll 1
                            for (int t = 0; t < 3; t++) {
                                mbar_wait(sb + BAR_XEMPTY + xs * 8, (phm >> xs) & 1);
                                phm ^= 1u << xs;
                                mbar_expect(sb + BAR_XFULL + xs * 8, XS);
                                bulk_load(sb + OFF_R + xs * XS, ostash(br, IT_B(e), u & 31) + t * XS, XS, sb + BAR_XFULL + xs * 8, pol_o);
                                if (++xs == 5) xs = 0;
                            }
                        }
                    }
                }
            }
        } else if (warp == 2) {
#pragma unroll 1
            for (int it = 0;; it++) {
                const uint32_t e = get_item_warp(sb, it);
                if (e == 0) break;
                nb_sync<NB_ODONE, 288>();
                if (threadIdx.x == 64) {
                    const uint32_t bb = IT_BR(e) * 16 + IT_B(e);
                    if (IT_TYPE(e) == IT_QA || IT_PART(e)) {
                        __threadfence();
                        unsigned int* f = IT_TYPE(e) == IT_QA ? &g_flag[bb * 32 + IT_H0(e)] : &g_pflag[bb * 2 + IT_HALF(e)];
                        asm volatile("st.relaxed.gpu.global.u32 [%0], %1;" ::"l"(f), "r"(epoch) : "memory");
                    } else {
                        const int nt = IT_TYPE(e) == IT_OP ? 5 : 2;
                        const int cc0 = IT_BR(e) * 640 + IT_HALF(e) * nt * 64;
#pragma unroll
                        for (int m = 0; m < 5; m++) {
                            if (m < nt)
                                asm volatile("cp.async.bulk.tensor.2d.global.shared::cta.bulk_group [%0, {%2,%3}], [%1];" ::"l"(&P.out),
                                             "r"(sb + OFF_R + m * XS), "r"(cc0 + m * 64), "r"((int)IT_B(e) * 160)
                                             : "memory");
                            asm volatile("cp.async.bulk.commit_group;" ::: "memory");
                        }
#define REL(N)                                                          \
    asm volatile("cp.async.bulk.wait_group.read %0;" ::"n"(4 - N) : "memory"); \
    asm volatile("mbarrier.arrive.shared::cta.b64 _, [%0], 8;" ::"r"(sb + BAR_XEMPTY + N * 8) : "memory");
                        REL(0) REL(1) REL(2) REL(3) REL(4)
#undef REL
                    }
                }
                __syncwarp();
            }
            if (threadIdx.x == 64) asm volatile("cp.async.bulk.wait_group 0;" ::: "memory");
        }
    } else if (wgid == 1) {
        asm volatile("setmaxnreg.inc.sync.aligned.u32 240;");
        PendO<0> po;
        po.clear();
        float oa[80], ob[32];
        zero(oa);
        zero(ob);
        Ring r{0, 0};
        uint32_t phm = 0;
        uint32_t e = get_item_warp(sb, 0);
#pragma unroll 1
        for (int it = 0; e != 0; it++) {
            TS(0, 0);
            if (IT_TYPE(e) == IT_QA) {
                e = qa_item<0>(P, sb, r, phm, po, oa, ob, it);
            } else {
                if (IT_TYPE(e) == IT_OP) op_item<true>(e, sb, r, phm);
                else on_item<0>(e, sb, r, phm, lds_u(sb + OFF_FB + 4));
                po.clear();
                zero(oa);
                zero(ob);
                e = get_item_warp(sb, it + 1);
            }
            TS(0, 31);
        }
        TS_DUMP(0);
    } else {
        asm volatile("setmaxnreg.inc.sync.aligned.u32 240;");
        PendO<1> po;
        po.clear();
        float oa[80], ob[48];
        zero(oa);
        zero(ob);
        Ring r{0, 0};
        uint32_t phm = 0;
        uint32_t e = get_item_warp(sb, 0);
#pragma unroll 1
        for (int it = 0; e != 0; it++) {
            TS(1, 0);
            if (IT_TYPE(e) == IT_QA) {
                e = qa_item<1>(P, sb, r, phm, po, oa, ob, it);
            } else {
                if (IT_TYPE(e) == IT_OP) op_item<false>(e, sb, r, phm);
                else on_item<1>(e, sb, r, phm, lds_u(sb + OFF_FB + 4));
                po.clear();
                zero(oa);
                zero(ob);
                e = get_item_warp(sb, it + 1);
            }
            TS(1, 31);
        }
        TS_DUMP(1);
    }
}

typedef CUresult (*EncFn)(CUtensorMap*, CUtensorMapDataType, cuuint32_t, void*, const cuuint64_t*, const cuuint64_t*,
                          const cuuint32_t*, const cuuint32_t*, CUtensorMapInterleave, CUtensorMapSwizzle,
                          CUtensorMapL2promotion, CUtensorMapFloatOOBfill);

void make_map3(EncFn enc, CUtensorMap* m, void* p, uint64_t rows, uint64_t rowbytes, uint64_t nblk, uint32_t boxrows,
               uint32_t boxblk) {
    cuuint64_t dims[3] = {64, rows, nblk};
    cuuint64_t str[2] = {rowbytes, 128};
    cuuint32_t box[3] = {64, boxrows, boxblk};
    cuuint32_t es[3] = {1, 1, 1};
    enc(m, CU_TENSOR_MAP_DATA_TYPE_BFLOAT16, 3, p, dims, str, box, es, CU_TENSOR_MAP_INTERLEAVE_NONE,
        CU_TENSOR_MAP_SWIZZLE_128B, CU_TENSOR_MAP_L2_PROMOTION_NONE, CU_TENSOR_MAP_FLOAT_OOB_FILL_NONE);
}

#define SCHED_MODE 4
#define HSPLIT 14
#define DELAY_MAX 28000
#define DELAY_N0 0

void build_schedule(Params& P) {
    int u = 0;
    auto unit = [&]() {
        const uint32_t e = mk_item(IT_QA, u >> 9, u & 15, (u >> 4) & 31, 0, 0);
        u++;
        return e;
    };
    int qa[NCTA], nq = 0, op[NCTA], no = 0;
    for (int c = 0; c < NCTA; c++) {
        P.delay[c] = 0;
        for (int i = 0; i < NSTAT; i++) P.items[c][i] = 0;
        if (SCHED_MODE >= 3 && c < 128 && (c & 7) >= 6) op[no++] = c;
        else if (SCHED_MODE != 2 || (c & 3) == 0) qa[nq++] = c;
    }
    for (int t = 0; t < no; t++) P.items[op[t]][0] = unit();
    for (int k = 0; k < nq; k++) {
        const int c = qa[(k * 37) % nq];
        P.items[c][0] = unit();
        for (int i = 1; i < NSTAT; i++) P.items[c][i] = IT_DYN;
        P.delay[c] = k < DELAY_N0 ? 0 : (int)((long long)DELAY_MAX * (k + 1 - DELAY_N0) / (nq - DELAY_N0));
    }
    int n = 0;
    const int uend = SCHED_MODE == 2 ? 8 * nq : 1024 - no;
    while (u < uend) P.list[n++] = unit();
    for (int t = 0; t < no; t++) {
        P.items[op[t]][1] = mk_item(IT_OP, 0, t >> 1, 0, 32, t & 1);
        P.items[op[t]][2] = mk_item(IT_OP, 1, t >> 1, 0, HSPLIT, t & 1, 1);
        P.items[op[t]][3] = unit();
    }
    if (no)
        for (int k = 0; k < 80; k++) P.list[n++] = mk_item(IT_ON, 1, k / 5, HSPLIT, 32, k % 5);
    P.nlist = n;
}

}

extern "C" void kernel_launch(void* const* d_in, const int* in_sizes, int n_in, void* d_out, int out_size) {
    static Params P;
    static bool init = false;
    if (!init) {
        EncFn enc = nullptr;
        cudaDriverEntryPointQueryResult qr;
        cudaGetDriverEntryPoint("cuTensorMapEncodeTiled", (void**)&enc, cudaEnableDefault, &qr);
        for (int i = 0; i < 2; i++) {
            P.px[i] = (const __nv_bfloat16*)d_in[5 * i + 0];
            P.pk[i] = (const __nv_bfloat16*)d_in[5 * i + 1];
            P.pv[i] = (const __nv_bfloat16*)d_in[5 * i + 2];
            P.pwq[i] = (const __nv_bfloat16*)d_in[5 * i + 3];
            make_map3(enc, &P.x[i], d_in[5 * i + 0], 2560, 1280, 10, 160, 1);
            make_map3(enc, &P.k[i], d_in[5 * i + 1], 16 * 32 * 512, 384, 3, 64, 3);
            make_map3(enc, &P.v[i], d_in[5 * i + 2], 16 * 32 * 512, 384, 3, 64, 3);
            make_map3(enc, &P.wq[i], d_in[5 * i + 3], 640, 12288, 96, 64, 3);
            make_map3(enc, &P.wo[i], d_in[5 * i + 4], 6144, 1280, 10, 32, 5);
            make_map3(enc, &P.won[i], d_in[5 * i + 4], 6144, 1280, 10, 64, 2);
        }
        cuuint64_t dims[2] = {1280, 2560};
        cuuint64_t str[1] = {2560};
        cuuint32_t box[2] = {64, 160};
        cuuint32_t es[2] = {1, 1};
        enc(&P.out, CU_TENSOR_MAP_DATA_TYPE_BFLOAT16, 2, d_out, dims, str, box, es, CU_TENSOR_MAP_INTERLEAVE_NONE,
            CU_TENSOR_MAP_SWIZZLE_128B, CU_TENSOR_MAP_L2_PROMOTION_NONE, CU_TENSOR_MAP_FLOAT_OOB_FILL_NONE);
        build_schedule(P);
        cudaFuncSetAttribute(fused_kernel, cudaFuncAttributeMaxDynamicSharedMemorySize, SMEM_LAUNCH);
        init = true;
    }
    fused_kernel<<<NCTA, 384, SMEM_LAUNCH>>>(P);
}
```

```cpp
#include <cuda_runtime.h>
#include <cuda.h>
#include <cuda_bf16.h>
#include <stdint.h>

namespace {

constexpr int NCTA = 132;
constexpr int MAXI = 16;
constexpr int NSTAT = 3;
constexpr uint32_t IT_DYN = 0xffffffffu;
constexpr int SLOT = 24576;
constexpr int NSLOT = 5;
constexpr int XS = 20480;
constexpr int OFF_R = 0;
constexpr int OFF_RING = 5 * XS;
constexpr int OFF_MISC = OFF_RING + NSLOT * SLOT;
constexpr int OFF_LX = OFF_MISC;
constexpr int OFF_LINV = OFF_LX + 2560;
constexpr int OFF_FB = OFF_LINV + 640;
constexpr int OFF_GM = OFF_FB + 16;
constexpr int OFF_BAR = OFF_GM + 16;
constexpr int BAR_RFULL = OFF_BAR;
constexpr int BAR_REMPTY = BAR_RFULL + 40;
constexpr int BAR_XFULL = BAR_REMPTY + 40;
constexpr int BAR_XEMPTY = BAR_XFULL + 40;
constexpr int BAR_ITEM = BAR_XEMPTY + 40;
constexpr int OFF_ITEM = BAR_ITEM + MAXI * 8;
constexpr int SMEM_BYTES = OFF_ITEM + MAXI * 4;
static_assert(SMEM_BYTES <= 232448, "smem");

constexpr int NB_W = 1  , NB_PFULL = 3  , NB_VOTE = 5, NB_Q01 = 6, NB_Q2 = 7, NB_SDONE = 8, NB_PDONE = 9,
              NB_L = 10, NB_OPST = 11, NB_ODONE = 12, NB_OPEND = 13, NB_LX = 14;

constexpr uint32_t IT_QA = 1, IT_OP = 2, IT_ON = 3;
__host__ __device__ constexpr uint32_t mk_item(uint32_t type, uint32_t br, uint32_t b, uint32_t h0, uint32_t h1, uint32_t half,
                                               uint32_t part = 0) {
    return type | (br << 2) | (b << 3) | (h0 << 7) | (h1 << 13) | (half << 19) | (part << 22);
}
#define IT_TYPE(e) ((e) & 3u)
#define IT_BR(e) (((e) >> 2) & 1u)
#define IT_B(e) (((e) >> 3) & 15u)
#define IT_H0(e) (((e) >> 7) & 63u)
#define IT_H1(e) (((e) >> 13) & 63u)
#define IT_HALF(e) (((e) >> 19) & 7u)
#define IT_PART(e) (((e) >> 22) & 1u)

struct Params {
    CUtensorMap x[2], wq[2], k[2], v[2], wo[2], won[2], out;
    const __nv_bfloat16 *px[2], *pwq[2], *pk[2], *pv[2];
    uint32_t items[NCTA][NSTAT];
    uint32_t delay[NCTA];
    uint32_t nlist;
    uint32_t list[1024];
};

constexpr int OUNIT = 61440;
__device__ __align__(1024) unsigned char g_ostash[(size_t)1024 * OUNIT];
__device__ unsigned int g_flag[1024];
__device__ float4 g_part[2 * 16 * 10 * 2560];
__device__ unsigned int g_pflag[64];
#define ORING 64
__device__ __forceinline__ unsigned char* ostash(uint32_t br, uint32_t b, uint32_t h) {
    return g_ostash + (size_t)(((br * 32 + h) % ORING) * 16 + b) * OUNIT;
}
__device__ unsigned int g_epoch[NCTA];
__device__ unsigned int g_ticket[2];

constexpr int SMEM_LAUNCH = SMEM_BYTES;
#define TS(role, idx)
#define TS_DUMP(role)
#define TS2(cond, idx)

#define POL_W 2
#define POL_X 2
#define POL_O 2
template <int M>
__device__ __forceinline__ uint64_t mkpol() {
    uint64_t p;
    if (M == 0) asm volatile("createpolicy.fractional.L2::evict_normal.b64 %0, 1.0;" : "=l"(p));
    if (M == 1) asm volatile("createpolicy.fractional.L2::evict_first.b64 %0, 1.0;" : "=l"(p));
    if (M == 2) asm volatile("createpolicy.fractional.L2::evict_unchanged.b64 %0, 1.0;" : "=l"(p));
    if (M == 3) asm volatile("createpolicy.fractional.L2::evict_normal.L2::evict_unchanged.b64 %0, 0.25;" : "=l"(p));
    return p;
}
#define STSM_W 1
#define QPRE 3
#define QHOLD 7
constexpr float SM_C = 0.07216878364870322f * 1.4426950408889634f;

__device__ __forceinline__ void mbar_init(uint32_t a, uint32_t c) {
    asm volatile("mbarrier.init.shared::cta.b64 [%0], %1;" ::"r"(a), "r"(c) : "memory");
}
__device__ __forceinline__ void mbar_expect(uint32_t a, uint32_t b) {
    asm volatile("mbarrier.arrive.expect_tx.shared::cta.b64 _, [%0], %1;" ::"r"(a), "r"(b) : "memory");
}
__device__ __forceinline__ void mbar_arrive_warp(uint32_t a, uint32_t cnt) {
    asm volatile(
        "{\n.reg .pred p;\nelect.sync _|p, 0xffffffff;\n"
        "@p mbarrier.arrive.shared::cta.b64 _, [%0], %1;\n}" ::"r"(a), "r"(cnt)
        : "memory");
}
__device__ __forceinline__ void mbar_arrive_warp_if(uint32_t a, uint32_t cnt, bool cond) {
    asm volatile(
        "{\n.reg .pred p, c;\nelect.sync _|p, 0xffffffff;\nsetp.ne.and.u32 c, %2, 0, p;\n"
        "@c mbarrier.arrive.shared::cta.b64 _, [%0], %1;\n}" ::"r"(a), "r"(cnt), "r"((uint32_t)cond)
        : "memory");
}
__device__ __forceinline__ void mbar_wait(uint32_t a, uint32_t ph) {
    asm volatile(
        "{\n.reg .pred p;\n.reg .u32 n, m;\n"
        "mbarrier.try_wait.parity.shared::cta.b64 p, [%0], %1;\n"
        "@p bra DONE;\n"
        "mov.u32 n, %%clock_hi;\n"
        "LOOP:\n"
        "mbarrier.try_wait.parity.shared::cta.b64 p, [%0], %1;\n"
        "@p bra DONE;\n"
        "mov.u32 m, %%clock_hi;\n"
        "sub.u32 m, m, n;\n"
        "setp.lt.u32 p, m, 2;\n"
        "@p bra LOOP;\n"
        "trap;\n"
        "DONE:\n}" ::"r"(a), "r"(ph)
        : "memory");
}
template <int ID, int CNT>
__device__ __forceinline__ void nb_sync() { asm volatile("bar.sync %0, %1;" ::"n"(ID), "n"(CNT) : "memory"); }
template <int ID, int CNT>
__device__ __forceinline__ void nb_arrive() { asm volatile("bar.arrive %0, %1;" ::"n"(ID), "n"(CNT) : "memory"); }
__device__ __forceinline__ void fence_async_smem() { asm volatile("fence.proxy.async.shared::cta;" ::: "memory"); }

__device__ __forceinline__ void tma3(uint32_t dst, const CUtensorMap* m, int c1, int c2, uint32_t bar, uint64_t pol) {
    asm volatile(
        "cp.async.bulk.tensor.3d.shared::cluster.global.mbarrier::complete_tx::bytes.L2::cache_hint [%0], [%1, {%3,%4,%5}], [%2], %6;" ::"r"(dst),
        "l"(m), "r"(bar), "r"(0), "r"(c1), "r"(c2), "l"(pol)
        : "memory");
}
__device__ __forceinline__ void bulk_load(uint32_t dst, const void* src, uint32_t bytes, uint32_t bar, uint64_t pol) {
    asm volatile("cp.async.bulk.shared::cluster.global.mbarrier::complete_tx::bytes.L2::cache_hint [%0], [%1], %2, [%3], %4;" ::"r"(dst),
                 "l"(src), "r"(bytes), "r"(bar), "l"(pol)
                 : "memory");
}
__device__ __forceinline__ void wg_fence() { asm volatile("wgmma.fence.sync.aligned;" ::: "memory"); }
__device__ __forceinline__ void wg_commit() { asm volatile("wgmma.commit_group.sync.aligned;" ::: "memory"); }
template <int N>
__device__ __forceinline__ void wg_wait() { asm volatile("wgmma.wait_group.sync.aligned %0;" ::"n"(N) : "memory"); }

#define RW80(c, d) c(d[0]), c(d[1]), c(d[2]), c(d[3]), c(d[4]), c(d[5]), c(d[6]), c(d[7]), c(d[8]), c(d[9]), c(d[10]), c(d[11]), c(d[12]), c(d[13]), c(d[14]), c(d[15]), c(d[16]), c(d[17]), c(d[18]), c(d[19]), c(d[20]), c(d[21]), c(d[22]), c(d[23]), c(d[24]), c(d[25]), c(d[26]), c(d[27]), c(d[28]), c(d[29]), c(d[30]), c(d[31]), c(d[32]), c(d[33]), c(d[34]), c(d[35]), c(d[36]), c(d[37]), c(d[38]), c(d[39]), c(d[40]), c(d[41]), c(d[42]), c(d[43]), c(d[44]), c(d[45]), c(d[46]), c(d[47]), c(d[48]), c(d[49]), c(d[50]), c(d[51]), c(d[52]), c(d[53]), c(d[54]), c(d[55]), c(d[56]), c(d[57]), c(d[58]), c(d[59]), c(d[60]), c(d[61]), c(d[62]), c(d[63]), c(d[64]), c(d[65]), c(d[66]), c(d[67]), c(d[68]), c(d[69]), c(d[70]), c(d[71]), c(d[72]), c(d[73]), c(d[74]), c(d[75]), c(d[76]), c(d[77]), c(d[78]), c(d[79])
#define RW48(c, d) c(d[0]), c(d[1]), c(d[2]), c(d[3]), c(d[4]), c(d[5]), c(d[6]), c(d[7]), c(d[8]), c(d[9]), c(d[10]), c(d[11]), c(d[12]), c(d[13]), c(d[14]), c(d[15]), c(d[16]), c(d[17]), c(d[18]), c(d[19]), c(d[20]), c(d[21]), c(d[22]), c(d[23]), c(d[24]), c(d[25]), c(d[26]), c(d[27]), c(d[28]), c(d[29]), c(d[30]), c(d[31]), c(d[32]), c(d[33]), c(d[34]), c(d[35]), c(d[36]), c(d[37]), c(d[38]), c(d[39]), c(d[40]), c(d[41]), c(d[42]), c(d[43]), c(d[44]), c(d[45]), c(d[46]), c(d[47])
#define RW32(c, d) c(d[0]), c(d[1]), c(d[2]), c(d[3]), c(d[4]), c(d[5]), c(d[6]), c(d[7]), c(d[8]), c(d[9]), c(d[10]), c(d[11]), c(d[12]), c(d[13]), c(d[14]), c(d[15]), c(d[16]), c(d[17]), c(d[18]), c(d[19]), c(d[20]), c(d[21]), c(d[22]), c(d[23]), c(d[24]), c(d[25]), c(d[26]), c(d[27]), c(d[28]), c(d[29]), c(d[30]), c(d[31])

__device__ __forceinline__ void reg_fence(float (&d)[80]) { asm volatile("" : RW80("+f", d)::"memory"); }
__device__ __forceinline__ void reg_fence(float (&d)[48]) { asm volatile("" : RW48("+f", d)::"memory"); }
__device__ __forceinline__ void reg_fence(float (&d)[32]) { asm volatile("" : RW32("+f", d)::"memory"); }

template <int NR>
__device__ __forceinline__ void zero(float (&d)[NR]) {
#pragma unroll
    for (int i = 0; i < NR; i++) d[i] = 0.f;
}

constexpr uint32_t HI_SW128 = (1024u >> 4) | (1u << 30);
constexpr uint32_t HI_OST = (2560u >> 4) | (2u << 30);
constexpr uint32_t LO_LBO1 = (1u << 16);
constexpr uint32_t LO_OST = ((512u >> 4) << 16);

template <int TA, int TB, uint32_t HIB, bool ACC>
__device__ __forceinline__ void wgmma(float (&d)[80], uint32_t loA, uint32_t loB) {
#define WG_ASM(SD)                                                          \
    "{\n.reg .b64 da, db;\nmov.b64 da, {%80, %82};\nmov.b64 db, {%81, %83};\n" \
    "wgmma.mma_async.sync.aligned.m64n160k16.f32.bf16.bf16 "               \
    "{%0,%1,%2,%3,%4,%5,%6,%7,%8,%9,%10,%11,%12,%13,%14,%15,%16,%17,%18,%19,%20,%21,%22,%23,%24,%25,%26,%27,%28,%29,%30,%31,%32,%33,%34,%35,%36,%37,%38,%39,%40,%41,%42,%43,%44,%45,%46,%47,%48,%49,%50,%51,%52,%53,%54,%55,%56,%57,%58,%59,%60,%61,%62,%63,%64,%65,%66,%67,%68,%69,%70,%71,%72,%73,%74,%75,%76,%77,%78,%79}, da, db, " SD ", 1, 1, %84, %85;\n}"
    if constexpr (ACC)
        asm volatile(WG_ASM("1") : RW80("+f", d) : "r"(loA), "r"(loB), "n"(HI_SW128), "n"(HIB), "n"(TA), "n"(TB));
    else
        asm volatile(WG_ASM("0") : RW80("=f", d) : "r"(loA), "r"(loB), "n"(HI_SW128), "n"(HIB), "n"(TA), "n"(TB));
#undef WG_ASM
}
template <int TA, int TB, uint32_t HIB, bool ACC>
__device__ __forceinline__ void wgmma(float (&d)[48], uint32_t loA, uint32_t loB) {
#define WG_ASM(SD)                                                          \
    "{\n.reg .b64 da, db;\nmov.b64 da, {%48, %50};\nmov.b64 db, {%49, %51};\n" \
    "wgmma.mma_async.sync.aligned.m64n96k16.f32.bf16.bf16 "               \
    "{%0,%1,%2,%3,%4,%5,%6,%7,%8,%9,%10,%11,%12,%13,%14,%15,%16,%17,%18,%19,%20,%21,%22,%23,%24,%25,%26,%27,%28,%29,%30,%31,%32,%33,%34,%35,%36,%37,%38,%39,%40,%41,%42,%43,%44,%45,%46,%47}, da, db, " SD ", 1, 1, %52, %53;\n}"
    if constexpr (ACC)
        asm volatile(WG_ASM("1") : RW48("+f", d) : "r"(loA), "r"(loB), "n"(HI_SW128), "n"(HIB), "n"(TA), "n"(TB));
    else
        asm volatile(WG_ASM("0") : RW48("=f", d) : "r"(loA), "r"(loB), "n"(HI_SW128), "n"(HIB), "n"(TA), "n"(TB));
#undef WG_ASM
}
template <int TA, int TB, uint32_t HIB, bool ACC>
__device__ __forceinline__ void wgmma(float (&d)[32], uint32_t loA, uint32_t loB) {
#define WG_ASM(SD)                                                          \
    "{\n.reg .b64 da, db;\nmov.b64 da, {%32, %34};\nmov.b64 db, {%33, %35};\n" \
    "wgmma.mma_async.sync.aligned.m64n64k16.f32.bf16.bf16 "               \
    "{%0,%1,%2,%3,%4,%5,%6,%7,%8,%9,%10,%11,%12,%13,%14,%15,%16,%17,%18,%19,%20,%21,%22,%23,%24,%25,%26,%27,%28,%29,%30,%31}, da, db, " SD ", 1, 1, %36, %37;\n}"
    if constexpr (ACC)
        asm volatile(WG_ASM("1") : RW32("+f", d) : "r"(loA), "r"(loB), "n"(HI_SW128), "n"(HIB), "n"(TA), "n"(TB));
    else
        asm volatile(WG_ASM("0") : RW32("=f", d) : "r"(loA), "r"(loB), "n"(HI_SW128), "n"(HIB), "n"(TA), "n"(TB));
#undef WG_ASM
}

__device__ __forceinline__ uint32_t pack_bf16(float lo, float hi) {
    uint32_t r;
    asm("cvt.rn.bf16x2.f32 %0, %1, %2;" : "=r"(r) : "f"(hi), "f"(lo));
    return r;
}
__device__ __forceinline__ float ex2(float x) {
    float r;
    asm("ex2.approx.ftz.f32 %0, %1;" : "=f"(r) : "f"(x));
    return r;
}
__device__ __forceinline__ void stsm4t(uint32_t a, uint32_t r0, uint32_t r1, uint32_t r2, uint32_t r3) {
    asm volatile("stmatrix.sync.aligned.m8n8.x4.trans.shared.b16 [%0], {%1,%2,%3,%4};" ::"r"(a), "r"(r0), "r"(r1), "r"(r2), "r"(r3)
                 : "memory");
}
__device__ __forceinline__ uint32_t lds_u(uint32_t a) {
    uint32_t v;
    asm volatile("ld.shared.u32 %0, [%1];" : "=r"(v) : "r"(a) : "memory");
    return v;
}
__device__ __forceinline__ float2 lds_f2(uint32_t a) {
    float2 v;
    asm volatile("ld.shared.v2.f32 {%0,%1}, [%2];" : "=f"(v.x), "=f"(v.y) : "r"(a) : "memory");
    return v;
}
__device__ __forceinline__ void sts_f(uint32_t a, float v) { asm volatile("st.shared.f32 [%0], %1;" ::"r"(a), "f"(v) : "memory"); }
__device__ __forceinline__ void sts_u(uint32_t a, uint32_t v) { asm volatile("st.shared.u32 [%0], %1;" ::"r"(a), "r"(v) : "memory"); }
__device__ __forceinline__ void sts_f2(uint32_t a, float x, float y) {
    asm volatile("st.shared.v2.f32 [%0], {%1,%2};" ::"r"(a), "f"(x), "f"(y) : "memory");
}

__device__ __forceinline__ void store_tile_t(const float (&d)[80], uint32_t addr) {
#pragma unroll
    for (int j = 0; j < 10; j++)
        stsm4t(addr + j * 2048, pack_bf16(d[8 * j], d[8 * j + 1]), pack_bf16(d[8 * j + 2], d[8 * j + 3]),
               pack_bf16(d[8 * j + 4], d[8 * j + 5]), pack_bf16(d[8 * j + 6], d[8 * j + 7]));
}
template <int NR>
__device__ __forceinline__ void store_out_tile(const float (&d)[NR], uint32_t base, uint32_t lane, uint32_t w) {
    const uint32_t mi = lane >> 3, i = lane & 7;
    const uint32_t chunk = 2 * w + (mi & 1);
    const uint32_t q0 = 8 * (i >> 1) + 2 * (mi >> 1) + (i & 1);
    const uint32_t a0 = base + q0 * 128 + ((chunk ^ (q0 & 7)) << 4);
    const uint32_t a1 = base + (q0 + 4) * 128 + ((chunk ^ ((q0 + 4) & 7)) << 4);
#pragma unroll
    for (int j = 0; j < NR / 8; j++)
        stsm4t(((j & 1) ? a1 : a0) + (j >> 1) * 4096, pack_bf16(d[8 * j], d[8 * j + 1]), pack_bf16(d[8 * j + 2], d[8 * j + 3]),
               pack_bf16(d[8 * j + 4], d[8 * j + 5]), pack_bf16(d[8 * j + 6], d[8 * j + 7]));
}

struct TrueT { static constexpr bool value = true; };
struct FalseT { static constexpr bool value = false; };

template <int V>
struct IntT { static constexpr int value = V; };

__device__ __forceinline__ uint32_t get_item(uint32_t sb, int it) {
    mbar_wait(sb + BAR_ITEM + it * 8, 0);
    return lds_u(sb + OFF_ITEM + it * 4);
}
__device__ __forceinline__ uint32_t get_item_warp(uint32_t sb, int it) { return __shfl_sync(0xffffffffu, get_item(sb, it), 0); }

struct Ring {
    uint32_t slot, ph;
    __device__ __forceinline__ void adv(uint32_t k) {
        slot += k;
        if (slot >= NSLOT) { slot -= NSLOT; ph ^= 1; }
    }
};

template <int K>
__device__ __forceinline__ void qk_step(float (&s)[80], uint32_t loK, uint32_t loQ) {
    wgmma<0, 0, HI_SW128, K != 0>(s, loK + (K >> 2) * (8192 >> 4) + (K & 3) * 2, loQ + (K >> 2) * (XS >> 4) + (K & 3) * 2);
}
template <int K0, int K1>
__device__ __forceinline__ void qk_steps(float (&s)[80], uint32_t loK, uint32_t loQ) {
    if constexpr (K0 < K1) {
        qk_step<K0>(s, loK, loQ);
        qk_steps<K0 + 1, K1>(s, loK, loQ);
    }
}
__device__ __forceinline__ uint32_t add_bf2(uint32_t a, uint32_t b) {
    uint32_t r;
    asm("add.rn.bf16x2 %0, %1, %2;" : "=r"(r) : "r"(a), "r"(b));
    return r;
}
template <int J>
__device__ __forceinline__ void exp_block(const float (&s)[80], uint32_t (&k)[40], uint32_t pa, float mref) {
    if constexpr (J < 10) {
#pragma unroll
        for (int i = 4 * J; i < 4 * J + 4; i++)
            k[i] = pack_bf16(ex2(fmaf(s[2 * i], SM_C, -mref)), ex2(fmaf(s[2 * i + 1], SM_C, -mref)));
#pragma unroll
        for (int i = 0; i < 4; i++)
            asm volatile("stmatrix.sync.aligned.m8n8.x1.trans.shared.b16 [%0], {%1};" ::"r"(((i & 1) ? pa ^ 16 : pa) + J * 2048 + (i >> 1) * 1024),
                         "r"(k[4 * J + i])
                         : "memory");
        exp_block<J + 1>(s, k, pa, mref);
    }
}
__device__ __forceinline__ void sum_block(const uint32_t (&k)[40], float (&l)[10], uint32_t lane) {
    const bool b4 = lane & 16, b3 = lane & 8;
    uint32_t ps[20], t[10];
#pragma unroll
    for (int j = 0; j < 20; j++) ps[j] = add_bf2(k[2 * j], k[2 * j + 1]);
#pragma unroll
    for (int j = 0; j < 10; j++)
        t[j] = add_bf2(b4 ? ps[2 * j + 1] : ps[2 * j], __shfl_xor_sync(0xffffffffu, b4 ? ps[2 * j] : ps[2 * j + 1], 16));
#pragma unroll
    for (int i = 0; i < 5; i++) {
        const uint32_t a = b3 ? t[i + 5] : t[i], b = __shfl_xor_sync(0xffffffffu, b3 ? t[i] : t[i + 5], 8);
        l[2 * i] += __uint_as_float(a << 16) + __uint_as_float(b << 16);
        l[2 * i + 1] += __uint_as_float(a & 0xffff0000u) + __uint_as_float(b & 0xffff0000u);
    }
}
__device__ __forceinline__ void sum_store(const float (&l)[10], uint32_t lane, uint32_t lxa) {
    const bool b2 = lane & 4;
#pragma unroll
    for (int i = 0; i < 5; i++)
        sts_f(lxa + i * 64, (b2 ? l[2 * i + 1] : l[2 * i]) + __shfl_xor_sync(0xffffffffu, b2 ? l[2 * i] : l[2 * i + 1], 4));
}

__device__ __forceinline__ void fallback_unit(const Params& P, uint32_t e, uint32_t tid) {
    const uint32_t lane = tid & 31, br = IT_BR(e), b = IT_B(e), h = IT_H0(e);
    const __nv_bfloat162* wq = (const __nv_bfloat162*)(P.pwq[br] + h * 192) + lane;
    const __nv_bfloat162* kp = (const __nv_bfloat162*)(P.pk[br] + (size_t)(b * 32 + h) * 512 * 192) + lane;
    const __nv_bfloat162* vp = (const __nv_bfloat162*)(P.pv[br] + (size_t)(b * 32 + h) * 512 * 192) + lane;
#pragma unroll 1
    for (uint32_t qi = 0; qi < 40; qi++) {
        const uint32_t q = 4 * qi + (tid >> 5);
        const __nv_bfloat16* xr = P.px[br] + (size_t)(b * 160 + q) * 640;
        float a[6] = {0.f, 0.f, 0.f, 0.f, 0.f, 0.f};
#pragma unroll 4
        for (int k = 0; k < 640; k++) {
            const float xv = __bfloat162float(xr[k]);
#pragma unroll
            for (int i = 0; i < 3; i++) {
                const float2 wv = __bfloat1622float2(wq[(size_t)k * 3072 + i * 32]);
                a[2 * i] = fmaf(xv, wv.x, a[2 * i]);
                a[2 * i + 1] = fmaf(xv, wv.y, a[2 * i + 1]);
            }
        }
#pragma unroll
        for (int i = 0; i < 6; i++) a[i] = __bfloat162float(__float2bfloat16(a[i]));
        auto score = [&](int key) {
            float d = 0.f;
#pragma unroll
            for (int i = 0; i < 3; i++) {
                const float2 kv = __bfloat1622float2(kp[key * 96 + i * 32]);
                d = fmaf(a[2 * i], kv.x, fmaf(a[2 * i + 1], kv.y, d));
            }
#pragma unroll
            for (int o = 16; o > 0; o >>= 1) d += __shfl_xor_sync(0xffffffffu, d, o);
            return d;
        };
        float m = -INFINITY;
#pragma unroll 4
        for (int key = 0; key < 512; key++) m = fmaxf(m, score(key));
        float o[6] = {0.f, 0.f, 0.f, 0.f, 0.f, 0.f}, sum = 0.f;
#pragma unroll 4
        for (int key = 0; key < 512; key++) {
            const float p = ex2((score(key) - m) * SM_C);
            sum += p;
#pragma unroll
            for (int i = 0; i < 3; i++) {
                const float2 vv = __bfloat1622float2(vp[key * 96 + i * 32]);
                o[2 * i] = fmaf(p, vv.x, o[2 * i]);
                o[2 * i + 1] = fmaf(p, vv.y, o[2 * i + 1]);
            }
        }
        const float inv = __fdividef(1.f, sum);
        __nv_bfloat16* op = (__nv_bfloat16*)ostash(br, b, h) + (q >> 5) * 256 + 2 * ((q & 31) >> 3) + (q & 1);
#pragma unroll
        for (int i = 0; i < 6; i++) {
            const uint32_t d = (i >> 1) * 64 + 2 * lane + (i & 1);
            op[(d >> 3) * 1280 + (d & 7) * 32 + ((((q & 7) >> 1) ^ ((d & 7) >> 1)) << 3)] = __float2bfloat16(o[i] * inv);
        }
    }
}

template <int W>
struct PendO {
    static constexpr int N = W == 0 ? 14 : 16;
    uint32_t v[4 * N];
    unsigned char* gp;
    uint32_t pend, sig;
    template <int I>
    __device__ __forceinline__ void store() const {
        if constexpr (I < N) {
            constexpr int g = I < 10 ? I / 2 : (I - 10) / 2 + (W == 0 ? 3 : 0);
            constexpr int off = (I < 10 ? W : 2) * XS + g * 512 + (I & 1) * 2560;
            asm volatile(
                "{\n.reg .pred p;\nsetp.ne.u32 p, %6, 0;\n@p st.global.v4.b32 [%0+%5], {%1,%2,%3,%4};\n}" ::"l"(gp),
                "r"(v[4 * I]), "r"(v[4 * I + 1]), "r"(v[4 * I + 2]), "r"(v[4 * I + 3]), "n"(off), "r"(pend)
                : "memory");
        }
    }
    template <int I>
    __device__ __forceinline__ void flush() const {
        if constexpr (I < N) {
            store<I>();
            flush<I + 1>();
        }
    }
    __device__ __forceinline__ void clear() {
#pragma unroll
        for (int i = 0; i < 4 * N; i++) v[i] = 0;
        gp = nullptr;
        pend = 0;
        sig = 0;
    }
};

template <int W, int KK, int KE>
__device__ __forceinline__ void qproj(float (&q0)[80], float (&q1)[80], uint32_t sb, Ring& r, uint32_t phm, const PendO<W>& po) {
    const uint32_t loR = ((sb + OFF_R) >> 4) | LO_LBO1;
    const uint32_t loRing = ((sb + OFF_RING) >> 4) | LO_LBO1;
    constexpr int xs = KK % 5;
    const uint32_t pslot = r.slot;
    if (KK > 0) r.adv(1);
    if (W == 1 && KK == QHOLD) nb_sync<NB_SDONE, 256>();
    mbar_wait(sb + BAR_RFULL + r.slot * 8, r.ph);
    mbar_wait(sb + BAR_XFULL + xs * 8, ((phm >> xs) ^ (KK / 5)) & 1);
    const uint32_t a = loRing + r.slot * (SLOT >> 4) + (W == 0 ? 0 : 1024), b = loR + xs * (XS >> 4);
    wg_fence();
    wgmma<1, 0, HI_SW128, KK != 0>(q0, a, b);
    if (W == 0) wgmma<1, 0, HI_SW128, KK != 0>(q1, a + 512, b);
#pragma unroll
    for (int k = 1; k < 4; k++) {
        wgmma<1, 0, HI_SW128, true>(q0, a + k * 128, b + k * 2);
        if (W == 0) wgmma<1, 0, HI_SW128, true>(q1, a + 512 + k * 128, b + k * 2);
    }
    wg_commit();
    if (KK > 0) {
        wg_wait<1>();
        mbar_arrive_warp(sb + BAR_REMPTY + pslot * 8, 1);
        if (KK <= 5) mbar_arrive_warp(sb + (BAR_XEMPTY + (KK - 1) * 8), 1);
        if (W == 1 && KK == 7) nb_arrive<NB_PDONE, 256>();
    }
    if constexpr (W == 0 && KK < 5) {
        po.template store<3 * KK>();
        po.template store<3 * KK + 1>();
        po.template store<3 * KK + 2>();
        if (KK == 4 && po.sig) nb_arrive<NB_ODONE, 288>();
    }
    if constexpr (W == 1 && KK >= QPRE && KK < QPRE + 4) {
        po.template store<4 * (KK - QPRE)>();
        po.template store<4 * (KK - QPRE) + 1>();
        po.template store<4 * (KK - QPRE) + 2>();
        po.template store<4 * (KK - QPRE) + 3>();
        if (KK == QPRE + 3 && po.sig) nb_arrive<NB_ODONE, 288>();
    }
    if constexpr (KK + 1 < KE) {
        qproj<W, KK + 1, KE>(q0, q1, sb, r, phm, po);
    } else if constexpr (KE == 10) {
        if (W == 0) nb_arrive<NB_SDONE, 256>();
        wg_wait<0>();
        reg_fence(q0);
        if (W == 0) reg_fence(q1);
        mbar_arrive_warp(sb + BAR_REMPTY + r.slot * 8, 1);
        r.adv(1);
    }
}

template <int NR>
__device__ __forceinline__ void opack(const float (&o)[NR], int gl, const float2* sc, uint32_t* v) {
#pragma unroll
    for (int hh = 0; hh < 2; hh++)
#pragma unroll
        for (int t = 0; t < 4; t++)
            v[4 * hh + t] = pack_bf16(o[16 * gl + 4 * t + 2 * hh] * sc[t].x, o[16 * gl + 4 * t + 2 * hh + 1] * sc[t].y);
}

template <int NR>
__device__ __forceinline__ void dump_acc(const float (&c)[NR], float4* p) {
#pragma unroll
    for (int i = 0; i < NR / 4; i++) p[i * 128] = make_float4(c[4 * i], c[4 * i + 1], c[4 * i + 2], c[4 * i + 3]);
}
__device__ __forceinline__ void wait_flag(const unsigned int* f, uint32_t epoch) {
    uint32_t v, n = 0;
    do {
        asm volatile("ld.acquire.gpu.global.u32 %0, [%1];" : "=r"(v) : "l"(f) : "memory");
        if (++n > 0x400000) __trap();
    } while (v != epoch);
}

template <bool IS_S>
__device__ __forceinline__ void op_item(uint32_t e, uint32_t sb, Ring& r, uint32_t& phm) {
    constexpr int T0 = IS_S ? 0 : 2;
    constexpr uint32_t BOFF = IS_S ? (3 * 512) >> 4 : 0;
    const uint32_t loRing = ((sb + OFF_RING) >> 4) | LO_LBO1;
    const uint32_t loO = ((sb + OFF_R) >> 4) | LO_OST;
    float c0[80], c1[80], c2[IS_S ? 32 : 48];
    const int T2 = 6 * (IT_H1(e) - IT_H0(e));
    uint32_t xs = 0;
    auto step = [&](auto first, uint32_t hf) {
        constexpr bool F = decltype(first)::value;
        if (hf == 0) {
            mbar_wait(sb + BAR_XFULL + xs * 8, (phm >> xs) & 1);
            phm ^= 1u << xs;
        }
        mbar_wait(sb + BAR_RFULL + r.slot * 8, r.ph);
        const uint32_t a = loRing + r.slot * (SLOT >> 4), b = loO + xs * (XS >> 4) + hf * 640;
        wg_fence();
        wgmma<1, 1, HI_OST, !F>(c0, a + T0 * 256, b);
        wgmma<1, 1, HI_OST, !F>(c1, a + T0 * 256 + 256, b);
        wgmma<1, 1, HI_OST, !F>(c2, a + 1024, b + BOFF);
        wgmma<1, 1, HI_OST, true>(c0, a + T0 * 256 + 128, b + 320);
        wgmma<1, 1, HI_OST, true>(c1, a + T0 * 256 + 384, b + 320);
        wgmma<1, 1, HI_OST, true>(c2, a + 1024 + 128, b + 320 + BOFF);
        wg_commit();
    };
    step(TrueT{}, 0);
#pragma unroll 1
    for (int t = 1; t < T2; t++) {
        const uint32_t pslot = r.slot, pxs = xs;
        r.adv(1);
        if ((t & 1) == 0 && ++xs == 5) xs = 0;
        step(FalseT{}, t & 1);
        wg_wait<1>();
        mbar_arrive_warp(sb + BAR_REMPTY + pslot * 8, 1);
        if ((t & 1) == 0 && t + 8 < T2) mbar_arrive_warp(sb + BAR_XEMPTY + pxs * 8, 1);
    }
    wg_wait<0>();
    reg_fence(c0);
    reg_fence(c1);
    reg_fence(c2);
    mbar_arrive_warp(sb + BAR_REMPTY + r.slot * 8, 1);
    r.adv(1);
    if (IT_PART(e)) {
#pragma unroll
        for (int m = 0; m < 5; m++) mbar_arrive_warp(sb + BAR_XEMPTY + m * 8, 1);
        float4* pp = g_part + (size_t)((IT_BR(e) * 16 + IT_B(e)) * 10 + IT_HALF(e) * 5) * 2560 + (threadIdx.x & 127);
        dump_acc(c0, pp + T0 * 2560);
        dump_acc(c1, pp + (T0 + 1) * 2560);
        dump_acc(c2, pp + 4 * 2560 + (IS_S ? 12 * 128 : 0));
    } else {
        nb_sync<NB_OPEND, 256>();
        const uint32_t lane = threadIdx.x & 31, w = (threadIdx.x >> 5) & 3;
        store_out_tile(c0, sb + OFF_R + T0 * XS, lane, w);
        store_out_tile(c1, sb + OFF_R + (T0 + 1) * XS, lane, w);
        store_out_tile(c2, sb + OFF_R + 4 * XS + (IS_S ? 96 * 128 : 0), lane, w);
        fence_async_smem();
    }
    nb_arrive<NB_ODONE, 288>();
}

template <int W>
__device__ __forceinline__ void on_item(uint32_t e, uint32_t sb, Ring& r, uint32_t& phm, uint32_t epoch) {
    const uint32_t loRing = ((sb + OFF_RING) >> 4) | LO_LBO1;
    const uint32_t loO = ((sb + OFF_R) >> 4) | LO_OST;
    float c[80];
    const int T = 3 * (IT_H1(e) - IT_H0(e));
    uint32_t xs = 0;
    auto step = [&](auto first) {
        constexpr bool F = decltype(first)::value;
        mbar_wait(sb + BAR_XFULL + xs * 8, (phm >> xs) & 1);
        phm ^= 1u << xs;
        mbar_wait(sb + BAR_RFULL + r.slot * 8, r.ph);
        const uint32_t a = loRing + r.slot * (SLOT >> 4) + W * 512, b = loO + xs * (XS >> 4);
        wg_fence();
        wgmma<1, 1, HI_OST, !F>(c, a, b);
#pragma unroll
        for (int k = 1; k < 4; k++) wgmma<1, 1, HI_OST, true>(c, a + k * 128, b + k * 320);
        wg_commit();
    };
    auto run = [&](int t0, int t1) {
#pragma unroll 1
        for (int t = t0; t < t1; t++) {
            const uint32_t pslot = r.slot, pxs = xs;
            r.adv(1);
            if (++xs == 5) xs = 0;
            step(FalseT{});
            wg_wait<1>();
            mbar_arrive_warp(sb + BAR_REMPTY + pslot * 8, 1);
            mbar_arrive_warp_if(sb + BAR_XEMPTY + pxs * 8, 1, t + 4 < T);
        }
    };
    step(TrueT{});
    const int tm = T - 3;
    run(1, tm);
    float4 pv[20];
    {
        const uint32_t tile = 2 * IT_HALF(e) + W, bb = IT_BR(e) * 16 + IT_B(e);
        wait_flag(&g_pflag[bb * 2 + (tile >= 5)], epoch);
        const float4* pp = g_part + (size_t)(bb * 10 + tile) * 2560 + (threadIdx.x & 127);
#pragma unroll
        for (int i = 0; i < 20; i++) pv[i] = __ldcg(pp + i * 128);
    }
    run(tm, T);
    wg_wait<0>();
    reg_fence(c);
    mbar_arrive_warp(sb + BAR_REMPTY + r.slot * 8, 1);
    r.adv(1);
    nb_sync<NB_OPEND, 256>();
#pragma unroll
    for (int i = 0; i < 20; i++) {
        c[4 * i] += pv[i].x;
        c[4 * i + 1] += pv[i].y;
        c[4 * i + 2] += pv[i].z;
        c[4 * i + 3] += pv[i].w;
    }
    store_out_tile(c, sb + OFF_R + W * XS, threadIdx.x & 31, (threadIdx.x >> 5) & 3);
    fence_async_smem();
    nb_arrive<NB_ODONE, 288>();
}

template <int W>
__device__ __forceinline__ uint32_t qa_item(const Params& P, uint32_t sb, Ring& r, uint32_t phm, PendO<W>& po,
                                            float (&oa)[80], float (&ob)[W == 0 ? 32 : 48], int it) {
    const uint32_t loR = ((sb + OFF_R) >> 4) | LO_LBO1;
    const uint32_t loRing = ((sb + OFF_RING) >> 4) | LO_LBO1;
    const uint32_t lane = threadIdx.x & 31, w = (threadIdx.x >> 5) & 3;
    const uint32_t sta = sb + OFF_R + (lane >> 4) * 1024 + (lane & 7) * 128 + (((2 * w + ((lane >> 3) & 1)) ^ (lane & 7)) << 4);
    auto pack_o = [&](int ie) {
#pragma unroll
        for (int g = 0; g < 5; g++) {
            float2 sc[4];
#pragma unroll
            for (int t = 0; t < 4; t++) sc[t] = lds_f2(sb + OFF_LINV + (lane & 3) * 8 + (4 * g + t) * 32);
            opack(oa, g, sc, po.v + 8 * g);
            if (W == 0 && g >= 3) opack(ob, g - 3, sc, po.v + 40 + 8 * (g - 3));
            if (W == 1 && g < 3) opack(ob, g, sc, po.v + 40 + 8 * g);
        }
        const uint32_t e = lds_u(sb + OFF_ITEM + ie * 4);
        po.gp = ostash(IT_BR(e), IT_B(e), IT_H0(e)) + w * 5120 + (lane >> 2) * 64 + (((lane ^ (lane >> 3)) & 3) << 4);
    };
    {
        float q0[80], q1[80];
        if constexpr (W == 0) {
            qproj<W, 0, 10>(q0, q1, sb, r, phm, po);
        } else {
            qproj<W, 0, QPRE>(q0, q1, sb, r, phm, po);
            if (po.sig) nb_sync<NB_VOTE, 256>();
            po.pend = po.sig && !__any_sync(0xffffffffu, lds_u(sb + OFF_FB) != 0);
            pack_o(it > 0 ? it - 1 : 0);
            TS(W, 26);
            qproj<W, QPRE, 10>(q0, q1, sb, r, phm, po);
        }
        TS(W, 1);
        if (W == 0) {
            nb_sync<NB_PDONE, 256>();
            store_tile_t(q0, sta);
            store_tile_t(q1, sta + XS);
        } else {
            store_tile_t(q0, sta + 2 * XS);
        }
    }
    fence_async_smem();
    float s[80], l[10];
#pragma unroll
    for (int i = 0; i < 80; i++) oa[i] = 0.f;
#pragma unroll
    for (int i = 0; i < (W == 0 ? 32 : 48); i++) ob[i] = 0.f;
#pragma unroll
    for (int i = 0; i < 10; i++) l[i] = 0.f;
    reg_fence(oa);
    reg_fence(ob);
    auto pv = [&](uint32_t buf) {
        mbar_wait(sb + BAR_RFULL + r.slot * 8, r.ph);
        const uint32_t a = loRing + r.slot * (SLOT >> 4), b = loR + (3 + buf) * (XS >> 4);
        wg_fence();
#pragma unroll
        for (int k = 0; k < 4; k++) {
            wgmma<1, 0, HI_SW128, true>(oa, a + W * 512 + k * 128, b + k * 2);
            wgmma<1, 0, HI_SW128, true>(ob, a + 1024 + k * 128, b + (W == 0 ? (96 * 128) >> 4 : 0) + k * 2);
        }
        wg_commit();
    };
    float mref;
    uint32_t kslot, vslot;
    const uint32_t lxa = sb + OFF_LX + w * 640 + (((lane & 8) ? 80 : 0) + ((lane >> 1) & 8) + 2 * (lane & 3) + ((lane >> 2) & 1)) * 4;
    auto tail = [&](bool rel_other, int i) {
        uint32_t ps[40];
        exp_block<0>(s, ps, sta + (3 + W) * XS, mref);
        if (rel_other) {
            wg_wait<0>();
            mbar_arrive_warp(sb + BAR_REMPTY + vslot * 8, 1);
            if (W == 1) mbar_arrive_warp_if(sb + BAR_XEMPTY + 24, 1, i == 3);
        }
        fence_async_smem();
        if (W == 1 && i == 3) {
            nb_sync<NB_W + W, 128>();
            pv(W);
        }
        nb_arrive<NB_PFULL + W, 256>();
        TS(W, 6 + 5 * i);
        mbar_wait(sb + BAR_RFULL + r.slot * 8, r.ph);
        sum_block(ps, l, lane);
        TS(W, 7 + 5 * i);
        if (W == 0 || i < 3) {
            nb_sync<NB_W + W, 128>();
            pv(W);
        }
        TS(W, 8 + 5 * i);
    };
    if (W == 0) {
        nb_sync<NB_W, 128>();
        TS(W, 2);
        mbar_wait(sb + BAR_RFULL + r.slot * 8, r.ph);
        wg_fence();
        qk_steps<0, 8>(s, loRing + r.slot * (SLOT >> 4), loR);
        nb_sync<NB_Q2, 256>();
        qk_steps<8, 12>(s, loRing + r.slot * (SLOT >> 4), loR);
        wg_commit();
        nb_arrive<NB_Q01, 256>();
        TS(W, 4);
        wg_wait<0>();
        reg_fence(s);
        mbar_arrive_warp(sb + BAR_REMPTY + r.slot * 8, 2);
        r.adv(2);
        float m0 = fmaxf(s[0], s[5]), m1 = fmaxf(s[10], s[15]);
#pragma unroll
        for (int i = 20; i < 80; i += 10) {
            m0 = fmaxf(m0, s[i]);
            m1 = fmaxf(m1, s[i + 5]);
        }
        int key = __float_as_int(fmaxf(m0, m1));
        key ^= (key >> 31) & 0x7fffffff;
        key = __reduce_max_sync(0xffffffffu, key);
        key ^= (key >> 31) & 0x7fffffff;
        sts_u(sb + OFF_GM + w * 4, key);
        sts_u(sb + OFF_FB, 0);
        nb_sync<NB_W, 128>();
        const float2 u = lds_f2(sb + OFF_GM), v = lds_f2(sb + OFF_GM + 8);
        mref = fmaxf(fmaxf(u.x, u.y), fmaxf(v.x, v.y)) * SM_C;
        TS(W, 5);
        tail(false, 0);
    } else {
        nb_arrive<NB_Q2, 256>();
        TS(W, 2);
        nb_sync<NB_Q01, 256>();
    }
#pragma unroll 1
    for (int i = (W == 0 ? 1 : 0); i < 4; i++) {
        const uint32_t pvslot = r.slot;
        r.adv(1);
        kslot = r.slot;
        mbar_wait(sb + BAR_RFULL + r.slot * 8, r.ph);
        wg_fence();
        qk_steps<0, 12>(s, loRing + r.slot * (SLOT >> 4), loR);
        wg_commit();
        wg_wait<1>();
        mbar_arrive_warp_if(sb + BAR_REMPTY + pvslot * 8, 1, W == 0 || i > 0);
        r.adv(1);
        vslot = r.slot;
        TS(W, 4 + 5 * i);
        nb_sync<NB_PFULL + (W ^ 1), 256>();
        pv(W ^ 1);
        if (W == 1) {
            const float2 u = lds_f2(sb + OFF_GM), v = lds_f2(sb + OFF_GM + 8);
            mref = fmaxf(fmaxf(u.x, u.y), fmaxf(v.x, v.y)) * SM_C;
        }
        wg_wait<1>();
        reg_fence(s);
        mbar_arrive_warp(sb + BAR_REMPTY + kslot * 8, 2);
        if (W == 1) {
            mbar_arrive_warp_if(sb + BAR_XEMPTY + 0, 2, i == 3);
            mbar_arrive_warp_if(sb + BAR_XEMPTY + 8, 2, i == 3);
            mbar_arrive_warp_if(sb + BAR_XEMPTY + 16, 2, i == 3);
        }
        r.adv(W == 1 && i == 3 ? 1 : 2);
        TS(W, 5 + 5 * i);
        tail(true, i);
    }
    if (W == 0) {
        const uint32_t tid = threadIdx.x & 127;
        float2 v = make_float2(0.f, 0.f);
        auto gather = [&]() {
            if (tid < 80) {
#pragma unroll
                for (int i = 0; i < 4; i++) {
                    const float2 u = lds_f2(sb + OFF_LX + i * 640 + tid * 8);
                    v.x += u.x;
                    v.y += u.y;
                }
            }
        };
        sum_store(l, lane, lxa);
        nb_sync<NB_W, 128>();
        gather();
        nb_arrive<NB_LX, 256>();
        wg_wait<0>();
        mbar_arrive_warp(sb + BAR_REMPTY + r.slot * 8, 1);
        mbar_arrive_warp(sb + BAR_XEMPTY + 24, 1);
        r.adv(1);
        nb_sync<NB_PFULL + 1, 256>();
        pv(1);
        TS(W, 24);
        nb_sync<NB_L, 256>();
        gather();
        if (tid < 80) {
            sts_f2(sb + OFF_LINV + tid * 8, __fdividef(1.f, v.x), __fdividef(1.f, v.y));
            if (!(v.x >= 5.421010862e-20f && v.x <= 1.8446744e19f && v.y >= 5.421010862e-20f && v.y <= 1.8446744e19f))
                sts_u(sb + OFF_FB, 1);
        }
    }
    if (W == 0) {
        nb_arrive<NB_VOTE, 256>();
        nb_sync<NB_W, 128>();
    } else {
        nb_sync<NB_LX, 256>();
        sum_store(l, lane, lxa);
        nb_arrive<NB_L, 256>();
    }
    const uint32_t nx = get_item_warp(sb, it + 1);
    wg_wait<0>();
    reg_fence(oa);
    reg_fence(ob);
    mbar_arrive_warp(sb + BAR_REMPTY + r.slot * 8, 1);
    mbar_arrive_warp(sb + BAR_XEMPTY + 32, 1);
    r.adv(1);
    TS(W, 25);
    po.sig = 1;
    if (W == 0) {
        const bool any = __any_sync(0xffffffffu, lds_u(sb + OFF_FB) != 0);
        pack_o(it);
        po.pend = !any;
        if (any) {
            fallback_unit(P, lds_u(sb + OFF_ITEM + it * 4), threadIdx.x & 127);
            __syncwarp();
        }
    }
    if (IT_TYPE(nx) != IT_QA) {
        if (W == 1) {
            nb_sync<NB_VOTE, 256>();
            po.pend = !__any_sync(0xffffffffu, lds_u(sb + OFF_FB) != 0);
            pack_o(it);
        }
        po.template flush<0>();
        nb_arrive<NB_ODONE, 288>();
        po.sig = 0;
        po.pend = 0;
    }
    return nx;
}

__global__ void __launch_bounds__(384, 1) fused_kernel(const __grid_constant__ Params P) {
    extern __shared__ __align__(1024) unsigned char smem_raw[];
    const uint32_t sb = (uint32_t)__cvta_generic_to_shared(smem_raw);
    const uint32_t wgid = __shfl_sync(0xffffffffu, threadIdx.x >> 7, 0);
    const uint32_t cta = blockIdx.x;

    uint32_t epoch = 0;
    if (wgid == 0) epoch = *(volatile unsigned int*)&g_epoch[cta] + 1;
    if (threadIdx.x == 0) {
        if (sb & 1023) __trap();
        sts_u(sb + OFF_FB + 4, epoch);
        for (int i = 0; i < NSLOT; i++) {
            mbar_init(sb + BAR_RFULL + i * 8, 1);
            mbar_init(sb + BAR_REMPTY + i * 8, 8);
            mbar_init(sb + BAR_XFULL + i * 8, 1);
            mbar_init(sb + BAR_XEMPTY + i * 8, 8);
        }
        for (int i = 0; i < MAXI; i++) mbar_init(sb + BAR_ITEM + i * 8, 1);
        asm volatile("fence.mbarrier_init.release.cluster;" ::: "memory");
        fence_async_smem();
    }
    __syncthreads();

    if (wgid == 0) {
        asm volatile("setmaxnreg.dec.sync.aligned.u32 24;");
        const uint32_t warp = __shfl_sync(0xffffffffu, threadIdx.x >> 5, 0);
        if (warp == 0) {
            if (threadIdx.x == 0) {
                *(volatile unsigned int*)&g_epoch[cta] = epoch;
                const uint64_t pol_first = mkpol<1>(), pol_norm = mkpol<POL_W>();
                if (cta == 0) *(volatile unsigned int*)&g_ticket[(epoch + 1) & 1] = 0;
                Ring r{0, 1};
                {
                    const uint32_t d = P.delay[cta];
                    uint32_t t0, t1;
                    asm volatile("mov.u32 %0, %%clock;" : "=r"(t0));
                    do {
                        asm volatile("mov.u32 %0, %%clock;" : "=r"(t1));
                    } while (t1 - t0 < d);
                }
                uint32_t e = P.items[cta][0];
#pragma unroll 1
                for (int it = 0;; it++) {
                    sts_u(sb + OFF_ITEM + it * 4, e);
                    asm volatile("mbarrier.arrive.shared::cta.b64 _, [%0];" ::"r"(sb + BAR_ITEM + it * 8) : "memory");
                    if (e == 0) break;
                    uint32_t nx = P.items[cta][it + 1 < NSTAT ? it + 1 : NSTAT - 1];
                    if (IT_TYPE(e) == IT_ON || it + 2 == MAXI) nx = 0;
                    uint32_t tk = 0;
                    const uint32_t br = IT_BR(e);
                    if (IT_TYPE(e) == IT_QA) {
                        const uint32_t h = IT_H0(e);
#pragma unroll 1
                        for (int kk = 0; kk < 10; kk++) {
                            mbar_wait(sb + BAR_REMPTY + r.slot * 8, r.ph);
                            mbar_expect(sb + BAR_RFULL + r.slot * 8, SLOT);
                            tma3(sb + OFF_RING + r.slot * SLOT, &P.wq[br], kk * 64, h * 3, sb + BAR_RFULL + r.slot * 8, pol_norm);
                            r.adv(1);
                        }
                        const int row0 = (IT_B(e) * 32 + h) * 512;
#pragma unroll 1
                        for (int n = 0; n < 16; n++) {
                            if (n == 13 && nx == IT_DYN) tk = atomicAdd(&g_ticket[epoch & 1], 1);
                            const bool isv = n == 15 || (n > 0 && !(n & 1));
                            const int j = n == 15 ? 7 : isv ? (n - 2) >> 1 : (n + 1) >> 1;
                            mbar_wait(sb + BAR_REMPTY + r.slot * 8, r.ph);
                            mbar_expect(sb + BAR_RFULL + r.slot * 8, SLOT);
                            tma3(sb + OFF_RING + r.slot * SLOT, isv ? &P.v[br] : &P.k[br], row0 + j * 64, 0,
                                 sb + BAR_RFULL + r.slot * 8, pol_first);
                            r.adv(1);
                        }
                    } else {
                        const int r0 = IT_H0(e) * 192, r1 = IT_H1(e) * 192;
                        const bool wide = IT_TYPE(e) == IT_OP;
#pragma unroll 1
                        for (int row = r0; row < r1; row += wide ? 32 : 64) {
                            mbar_wait(sb + BAR_REMPTY + r.slot * 8, r.ph);
                            mbar_expect(sb + BAR_RFULL + r.slot * 8, wide ? XS : 16384);
                            tma3(sb + OFF_RING + r.slot * SLOT, wide ? &P.wo[br] : &P.won[br], row, IT_HALF(e) * (wide ? 5 : 2),
                                 sb + BAR_RFULL + r.slot * 8, pol_norm);
                            r.adv(1);
                        }
                        if (nx == IT_DYN) tk = atomicAdd(&g_ticket[epoch & 1], 1);
                    }
                    if (nx == IT_DYN) nx = tk < P.nlist ? P.list[tk] : 0;
                    e = nx;
                }
            }
        } else if (warp == 1) {
            if (threadIdx.x == 32) {
                const uint64_t pol_norm = mkpol<POL_X>(), pol_o = mkpol<POL_O>();
                uint32_t phm = 0x1f;
#pragma unroll 1
                for (int it = 0;; it++) {
                    const uint32_t e = get_item(sb, it);
                    if (e == 0) break;
                    const uint32_t br = IT_BR(e);
                    uint32_t xs = 0;
                    if (IT_TYPE(e) == IT_QA) {
#pragma unroll 1
                        for (int kk = 0; kk < 10; kk++) {
                            mbar_wait(sb + BAR_XEMPTY + xs * 8, (phm >> xs) & 1);
                            phm ^= 1u << xs;
                            mbar_expect(sb + BAR_XFULL + xs * 8, XS);
                            tma3(sb + OFF_R + xs * XS, &P.x[br], IT_B(e) * 160, kk, sb + BAR_XFULL + xs * 8, pol_norm);
                            if (++xs == 5) xs = 0;
                        }
                    } else {
                        const uint32_t u0 = (br * 16 + IT_B(e)) * 32;
#pragma unroll 1
                        for (uint32_t u = u0 + IT_H0(e); u < u0 + IT_H1(e); u++) {
                            wait_flag(&g_flag[u], epoch);
                            asm volatile("fence.proxy.async;" ::: "memory");
#pragma unroll 1
                            for (int t = 0; t < 3; t++) {
                                mbar_wait(sb + BAR_XEMPTY + xs * 8, (phm >> xs) & 1);
                                phm ^= 1u << xs;
                                mbar_expect(sb + BAR_XFULL + xs * 8, XS);
                                bulk_load(sb + OFF_R + xs * XS, ostash(br, IT_B(e), u & 31) + t * XS, XS, sb + BAR_XFULL + xs * 8, pol_o);
                                if (++xs == 5) xs = 0;
                            }
                        }
                    }
                }
            }
        } else if (warp == 2) {
#pragma unroll 1
            for (int it = 0;; it++) {
                const uint32_t e = get_item_warp(sb, it);
                if (e == 0) break;
                nb_sync<NB_ODONE, 288>();
                if (threadIdx.x == 64) {
                    const uint32_t bb = IT_BR(e) * 16 + IT_B(e);
                    if (IT_TYPE(e) == IT_QA || IT_PART(e)) {
                        __threadfence();
                        unsigned int* f = IT_TYPE(e) == IT_QA ? &g_flag[bb * 32 + IT_H0(e)] : &g_pflag[bb * 2 + IT_HALF(e)];
                        asm volatile("st.relaxed.gpu.global.u32 [%0], %1;" ::"l"(f), "r"(epoch) : "memory");
                    } else {
                        const int nt = IT_TYPE(e) == IT_OP ? 5 : 2;
                        const int cc0 = IT_BR(e) * 640 + IT_HALF(e) * nt * 64;
#pragma unroll
                        for (int m = 0; m < 5; m++) {
                            if (m < nt)
                                asm volatile("cp.async.bulk.tensor.2d.global.shared::cta.bulk_group [%0, {%2,%3}], [%1];" ::"l"(&P.out),
                                             "r"(sb + OFF_R + m * XS), "r"(cc0 + m * 64), "r"((int)IT_B(e) * 160)
                                             : "memory");
                            asm volatile("cp.async.bulk.commit_group;" ::: "memory");
                        }
#define REL(N)                                                          \
    asm volatile("cp.async.bulk.wait_group.read %0;" ::"n"(4 - N) : "memory"); \
    asm volatile("mbarrier.arrive.shared::cta.b64 _, [%0], 8;" ::"r"(sb + BAR_XEMPTY + N * 8) : "memory");
                        REL(0) REL(1) REL(2) REL(3) REL(4)
#undef REL
                    }
                }
                __syncwarp();
            }
            if (threadIdx.x == 64) asm volatile("cp.async.bulk.wait_group 0;" ::: "memory");
        }
    } else if (wgid == 1) {
        asm volatile("setmaxnreg.inc.sync.aligned.u32 240;");
        PendO<0> po;
        po.clear();
        {
            const int it = 0;
            TS(0, 30);
        }
        float oa[80], ob[32];
        zero(oa);
        zero(ob);
        Ring r{0, 0};
        uint32_t phm = 0;
        uint32_t e = get_item_warp(sb, 0);
#pragma unroll 1
        for (int it = 0; e != 0; it++) {
            TS(0, 0);
            if (IT_TYPE(e) == IT_QA) {
                e = qa_item<0>(P, sb, r, phm, po, oa, ob, it);
            } else {
                if (IT_TYPE(e) == IT_OP) op_item<true>(e, sb, r, phm);
                else on_item<0>(e, sb, r, phm, lds_u(sb + OFF_FB + 4));
                po.clear();
                zero(oa);
                zero(ob);
                e = get_item_warp(sb, it + 1);
            }
            TS(0, 31);
        }
        TS_DUMP(0);
    } else {
        asm volatile("setmaxnreg.inc.sync.aligned.u32 240;");
        PendO<1> po;
        po.clear();
        float oa[80], ob[48];
        zero(oa);
        zero(ob);
        Ring r{0, 0};
        uint32_t phm = 0;
        uint32_t e = get_item_warp(sb, 0);
#pragma unroll 1
        for (int it = 0; e != 0; it++) {
            TS(1, 0);
            if (IT_TYPE(e) == IT_QA) {
                e = qa_item<1>(P, sb, r, phm, po, oa, ob, it);
            } else {
                if (IT_TYPE(e) == IT_OP) op_item<false>(e, sb, r, phm);
                else on_item<1>(e, sb, r, phm, lds_u(sb + OFF_FB + 4));
                po.clear();
                zero(oa);
                zero(ob);
                e = get_item_warp(sb, it + 1);
            }
            TS(1, 31);
        }
        TS_DUMP(1);
    }
}

typedef CUresult (*EncFn)(CUtensorMap*, CUtensorMapDataType, cuuint32_t, void*, const cuuint64_t*, const cuuint64_t*,
                          const cuuint32_t*, const cuuint32_t*, CUtensorMapInterleave, CUtensorMapSwizzle,
                          CUtensorMapL2promotion, CUtensorMapFloatOOBfill);

void make_map3(EncFn enc, CUtensorMap* m, void* p, uint64_t rows, uint64_t rowbytes, uint64_t nblk, uint32_t boxrows,
               uint32_t boxblk) {
    cuuint64_t dims[3] = {64, rows, nblk};
    cuuint64_t str[2] = {rowbytes, 128};
    cuuint32_t box[3] = {64, boxrows, boxblk};
    cuuint32_t es[3] = {1, 1, 1};
    enc(m, CU_TENSOR_MAP_DATA_TYPE_BFLOAT16, 3, p, dims, str, box, es, CU_TENSOR_MAP_INTERLEAVE_NONE,
        CU_TENSOR_MAP_SWIZZLE_128B, CU_TENSOR_MAP_L2_PROMOTION_NONE, CU_TENSOR_MAP_FLOAT_OOB_FILL_NONE);
}

constexpr int tune(const char*, int def) { return def; }

void build_schedule(Params& P) {
    const int mode = tune("MODE", 4), dmax = tune("DMAX", 20000), n0 = tune("N0", 20);
    const int hmin = tune("HMIN", 18), hmax = tune("HMAX", 24), off = tune("OFF", -15), slope = tune("SLOPE", 1744);
    int u = 0;
    auto unit = [&]() {
        const uint32_t e = mk_item(IT_QA, u >> 9, u & 15, (u >> 4) & 31, 0, 0);
        u++;
        return e;
    };
    int qa[NCTA], nq = 0, op[NCTA], no = 0;
    for (int c = 0; c < NCTA; c++) {
        P.delay[c] = 0;
        for (int i = 0; i < NSTAT; i++) P.items[c][i] = 0;
        if (mode >= 3 && c < 128 && (c & 7) >= 6) op[no++] = c;
        else if (mode != 2 || (c & 3) == 0) qa[nq++] = c;
    }
    for (int t = 0; t < no; t++) {
        P.items[op[t]][0] = unit();
        P.items[op[t]][1] = mk_item(IT_OP, 0, t >> 1, 0, 32, t & 1);
        P.items[op[t]][2] = IT_DYN;
    }
    for (int k = 0; k < nq; k++) {
        const int c = qa[(k * 37) % nq];
        P.items[c][0] = unit();
        P.items[c][1] = P.items[c][2] = IT_DYN;
        P.delay[c] = k < n0 ? 0 : (int)((long long)dmax * (k + 1 - n0) / (nq - n0));
    }
    int H[16], pos[16];
    for (int b = 0; b < 16; b++) {
        H[b] = hmin + ((hmax - hmin) * b + 7) / 15;
        pos[b] = 1092 + off - H[b] * slope / 100;
    }
    int n = 0;
    const int uend = mode == 2 ? 8 * nq : 1024;
    while (u < uend) {
        for (int b = 0; b < 16 && no; b++)
            if (pos[b] == u) {
                P.list[n++] = mk_item(IT_OP, 1, b, 0, H[b], 0, 1);
                P.list[n++] = mk_item(IT_OP, 1, b, 0, H[b], 1, 1);
            }
        P.list[n++] = unit();
    }
    if (no)
        for (int k = 0; k < 80; k++) P.list[n++] = mk_item(IT_ON, 1, k / 5, H[k / 5], 32, k % 5);
    P.nlist = n;
}

}

extern "C" void kernel_launch(void* const* d_in, const int* in_sizes, int n_in, void* d_out, int out_size) {
    static Params P;
    static bool init = false;
    if (!init) {
        EncFn enc = nullptr;
        cudaDriverEntryPointQueryResult qr;
        cudaGetDriverEntryPoint("cuTensorMapEncodeTiled", (void**)&enc, cudaEnableDefault, &qr);
        for (int i = 0; i < 2; i++) {
            P.px[i] = (const __nv_bfloat16*)d_in[5 * i + 0];
            P.pk[i] = (const __nv_bfloat16*)d_in[5 * i + 1];
            P.pv[i] = (const __nv_bfloat16*)d_in[5 * i + 2];
            P.pwq[i] = (const __nv_bfloat16*)d_in[5 * i + 3];
            make_map3(enc, &P.x[i], d_in[5 * i + 0], 2560, 1280, 10, 160, 1);
            make_map3(enc, &P.k[i], d_in[5 * i + 1], 16 * 32 * 512, 384, 3, 64, 3);
            make_map3(enc, &P.v[i], d_in[5 * i + 2], 16 * 32 * 512, 384, 3, 64, 3);
            make_map3(enc, &P.wq[i], d_in[5 * i + 3], 640, 12288, 96, 64, 3);
            make_map3(enc, &P.wo[i], d_in[5 * i + 4], 6144, 1280, 10, 32, 5);
            make_map3(enc, &P.won[i], d_in[5 * i + 4], 6144, 1280, 10, 64, 2);
        }
        cuuint64_t dims[2] = {1280, 2560};
        cuuint64_t str[1] = {2560};
        cuuint32_t box[2] = {64, 160};
        cuuint32_t es[2] = {1, 1};
        enc(&P.out, CU_TENSOR_MAP_DATA_TYPE_BFLOAT16, 2, d_out, dims, str, box, es, CU_TENSOR_MAP_INTERLEAVE_NONE,
            CU_TENSOR_MAP_SWIZZLE_128B, CU_TENSOR_MAP_L2_PROMOTION_NONE, CU_TENSOR_MAP_FLOAT_OOB_FILL_NONE);
        build_schedule(P);
        cudaFuncSetAttribute(fused_kernel, cudaFuncAttributeMaxDynamicSharedMemorySize, SMEM_LAUNCH);
        init = true;
    }
    fused_kernel<<<NCTA, 384, SMEM_LAUNCH>>>(P);
}
```

```cpp
#include <cuda_runtime.h>
#include <cuda.h>
#include <cuda_bf16.h>
#include <stdint.h>

namespace {

constexpr int NCTA = 132;
constexpr int MAXI = 16;
constexpr int NSTAT = 4;
constexpr uint32_t IT_DYN = 0xffffffffu;
constexpr int SLOT = 24576;
constexpr int NSLOT = 5;
constexpr int XS = 20480;
constexpr int OFF_R = 0;
constexpr int OFF_RING = 5 * XS;
constexpr int OFF_MISC = OFF_RING + NSLOT * SLOT;
constexpr int OFF_LX = OFF_MISC;
constexpr int OFF_LINV = OFF_LX + 2560;
constexpr int OFF_FB = OFF_LINV + 640;
constexpr int OFF_GM = OFF_FB + 16;
constexpr int OFF_BAR = OFF_GM + 16;
constexpr int BAR_RFULL = OFF_BAR;
constexpr int BAR_REMPTY = BAR_RFULL + 40;
constexpr int BAR_XFULL = BAR_REMPTY + 40;
constexpr int BAR_XEMPTY = BAR_XFULL + 40;
constexpr int BAR_ITEM = BAR_XEMPTY + 40;
constexpr int OFF_ITEM = BAR_ITEM + MAXI * 8;
constexpr int SMEM_BYTES = OFF_ITEM + MAXI * 4;
static_assert(SMEM_BYTES <= 232448, "smem");

constexpr int NB_W = 1  , NB_PFULL = 3  , NB_VOTE = 5, NB_Q01 = 6, NB_Q2 = 7, NB_SDONE = 8, NB_PDONE = 9,
              NB_L = 10, NB_OPST = 11, NB_ODONE = 12, NB_OPEND = 13, NB_LX = 14;

constexpr uint32_t IT_QA = 1, IT_OP = 2, IT_ON = 3;
__host__ __device__ constexpr uint32_t mk_item(uint32_t type, uint32_t br, uint32_t b, uint32_t h0, uint32_t h1, uint32_t half,
                                               uint32_t part = 0) {
    return type | (br << 2) | (b << 3) | (h0 << 7) | (h1 << 13) | (half << 19) | (part << 22);
}
#define IT_TYPE(e) ((e) & 3u)
#define IT_BR(e) (((e) >> 2) & 1u)
#define IT_B(e) (((e) >> 3) & 15u)
#define IT_H0(e) (((e) >> 7) & 63u)
#define IT_H1(e) (((e) >> 13) & 63u)
#define IT_HALF(e) (((e) >> 19) & 7u)
#define IT_PART(e) (((e) >> 22) & 1u)

struct Params {
    CUtensorMap x[2], wq[2], k[2], v[2], wo[2], won[2], out;
    const __nv_bfloat16 *px[2], *pwq[2], *pk[2], *pv[2];
    uint32_t items[NCTA][NSTAT];
    uint32_t delay[NCTA];
    uint32_t nlist;
    uint32_t list[1024];
};

constexpr int OUNIT = 61440;
__device__ __align__(1024) unsigned char g_ostash[(size_t)1024 * OUNIT];
__device__ unsigned int g_flag[1024];
__device__ float4 g_part[2 * 16 * 10 * 2560];
__device__ unsigned int g_pflag[64];
#define ORING 64
__device__ __forceinline__ unsigned char* ostash(uint32_t br, uint32_t b, uint32_t h) {
    return g_ostash + (size_t)(((br * 32 + h) % ORING) * 16 + b) * OUNIT;
}
__device__ unsigned int g_epoch[NCTA];
__device__ unsigned int g_ticket[2];

constexpr int SMEM_LAUNCH = SMEM_BYTES;
#define TS(role, idx)
#define TS_DUMP(role)
#define TS2(cond, idx)

#define POL_W 2
#define POL_X 2
#define POL_O 2
template <int M>
__device__ __forceinline__ uint64_t mkpol() {
    uint64_t p;
    if (M == 0) asm volatile("createpolicy.fractional.L2::evict_normal.b64 %0, 1.0;" : "=l"(p));
    if (M == 1) asm volatile("createpolicy.fractional.L2::evict_first.b64 %0, 1.0;" : "=l"(p));
    if (M == 2) asm volatile("createpolicy.fractional.L2::evict_unchanged.b64 %0, 1.0;" : "=l"(p));
    if (M == 3) asm volatile("createpolicy.fractional.L2::evict_normal.L2::evict_unchanged.b64 %0, 0.25;" : "=l"(p));
    return p;
}
#define STSM_W 1
#define QPRE 3
#define QHOLD 7
constexpr float SM_C = 0.07216878364870322f * 1.4426950408889634f;

__device__ __forceinline__ void mbar_init(uint32_t a, uint32_t c) {
    asm volatile("mbarrier.init.shared::cta.b64 [%0], %1;" ::"r"(a), "r"(c) : "memory");
}
__device__ __forceinline__ void mbar_expect(uint32_t a, uint32_t b) {
    asm volatile("mbarrier.arrive.expect_tx.shared::cta.b64 _, [%0], %1;" ::"r"(a), "r"(b) : "memory");
}
__device__ __forceinline__ void mbar_arrive_warp(uint32_t a, uint32_t cnt) {
    asm volatile(
        "{\n.reg .pred p;\nelect.sync _|p, 0xffffffff;\n"
        "@p mbarrier.arrive.shared::cta.b64 _, [%0], %1;\n}" ::"r"(a), "r"(cnt)
        : "memory");
}
__device__ __forceinline__ void mbar_arrive_warp_if(uint32_t a, uint32_t cnt, bool cond) {
    asm volatile(
        "{\n.reg .pred p, c;\nelect.sync _|p, 0xffffffff;\nsetp.ne.and.u32 c, %2, 0, p;\n"
        "@c mbarrier.arrive.shared::cta.b64 _, [%0], %1;\n}" ::"r"(a), "r"(cnt), "r"((uint32_t)cond)
        : "memory");
}
__device__ __forceinline__ void mbar_wait(uint32_t a, uint32_t ph) {
    asm volatile(
        "{\n.reg .pred p;\n.reg .u32 n, m;\n"
        "mbarrier.try_wait.parity.shared::cta.b64 p, [%0], %1;\n"
        "@p bra DONE;\n"
        "mov.u32 n, %%clock_hi;\n"
        "LOOP:\n"
        "mbarrier.try_wait.parity.shared::cta.b64 p, [%0], %1;\n"
        "@p bra DONE;\n"
        "mov.u32 m, %%clock_hi;\n"
        "sub.u32 m, m, n;\n"
        "setp.lt.u32 p, m, 2;\n"
        "@p bra LOOP;\n"
        "trap;\n"
        "DONE:\n}" ::"r"(a), "r"(ph)
        : "memory");
}
template <int ID, int CNT>
__device__ __forceinline__ void nb_sync() { asm volatile("bar.sync %0, %1;" ::"n"(ID), "n"(CNT) : "memory"); }
template <int ID, int CNT>
__device__ __forceinline__ void nb_arrive() { asm volatile("bar.arrive %0, %1;" ::"n"(ID), "n"(CNT) : "memory"); }
__device__ __forceinline__ void fence_async_smem() { asm volatile("fence.proxy.async.shared::cta;" ::: "memory"); }

__device__ __forceinline__ void tma3(uint32_t dst, const CUtensorMap* m, int c1, int c2, uint32_t bar, uint64_t pol) {
    asm volatile(
        "cp.async.bulk.tensor.3d.shared::cluster.global.mbarrier::complete_tx::bytes.L2::cache_hint [%0], [%1, {%3,%4,%5}], [%2], %6;" ::"r"(dst),
        "l"(m), "r"(bar), "r"(0), "r"(c1), "r"(c2), "l"(pol)
        : "memory");
}
__device__ __forceinline__ void bulk_load(uint32_t dst, const void* src, uint32_t bytes, uint32_t bar, uint64_t pol) {
    asm volatile("cp.async.bulk.shared::cluster.global.mbarrier::complete_tx::bytes.L2::cache_hint [%0], [%1], %2, [%3], %4;" ::"r"(dst),
                 "l"(src), "r"(bytes), "r"(bar), "l"(pol)
                 : "memory");
}
__device__ __forceinline__ void wg_fence() { asm volatile("wgmma.fence.sync.aligned;" ::: "memory"); }
__device__ __forceinline__ void wg_commit() { asm volatile("wgmma.commit_group.sync.aligned;" ::: "memory"); }
template <int N>
__device__ __forceinline__ void wg_wait() { asm volatile("wgmma.wait_group.sync.aligned %0;" ::"n"(N) : "memory"); }

#define RW80(c, d) c(d[0]), c(d[1]), c(d[2]), c(d[3]), c(d[4]), c(d[5]), c(d[6]), c(d[7]), c(d[8]), c(d[9]), c(d[10]), c(d[11]), c(d[12]), c(d[13]), c(d[14]), c(d[15]), c(d[16]), c(d[17]), c(d[18]), c(d[19]), c(d[20]), c(d[21]), c(d[22]), c(d[23]), c(d[24]), c(d[25]), c(d[26]), c(d[27]), c(d[28]), c(d[29]), c(d[30]), c(d[31]), c(d[32]), c(d[33]), c(d[34]), c(d[35]), c(d[36]), c(d[37]), c(d[38]), c(d[39]), c(d[40]), c(d[41]), c(d[42]), c(d[43]), c(d[44]), c(d[45]), c(d[46]), c(d[47]), c(d[48]), c(d[49]), c(d[50]), c(d[51]), c(d[52]), c(d[53]), c(d[54]), c(d[55]), c(d[56]), c(d[57]), c(d[58]), c(d[59]), c(d[60]), c(d[61]), c(d[62]), c(d[63]), c(d[64]), c(d[65]), c(d[66]), c(d[67]), c(d[68]), c(d[69]), c(d[70]), c(d[71]), c(d[72]), c(d[73]), c(d[74]), c(d[75]), c(d[76]), c(d[77]), c(d[78]), c(d[79])
#define RW48(c, d) c(d[0]), c(d[1]), c(d[2]), c(d[3]), c(d[4]), c(d[5]), c(d[6]), c(d[7]), c(d[8]), c(d[9]), c(d[10]), c(d[11]), c(d[12]), c(d[13]), c(d[14]), c(d[15]), c(d[16]), c(d[17]), c(d[18]), c(d[19]), c(d[20]), c(d[21]), c(d[22]), c(d[23]), c(d[24]), c(d[25]), c(d[26]), c(d[27]), c(d[28]), c(d[29]), c(d[30]), c(d[31]), c(d[32]), c(d[33]), c(d[34]), c(d[35]), c(d[36]), c(d[37]), c(d[38]), c(d[39]), c(d[40]), c(d[41]), c(d[42]), c(d[43]), c(d[44]), c(d[45]), c(d[46]), c(d[47])
#define RW32(c, d) c(d[0]), c(d[1]), c(d[2]), c(d[3]), c(d[4]), c(d[5]), c(d[6]), c(d[7]), c(d[8]), c(d[9]), c(d[10]), c(d[11]), c(d[12]), c(d[13]), c(d[14]), c(d[15]), c(d[16]), c(d[17]), c(d[18]), c(d[19]), c(d[20]), c(d[21]), c(d[22]), c(d[23]), c(d[24]), c(d[25]), c(d[26]), c(d[27]), c(d[28]), c(d[29]), c(d[30]), c(d[31])

__device__ __forceinline__ void reg_fence(float (&d)[80]) { asm volatile("" : RW80("+f", d)::"memory"); }
__device__ __forceinline__ void reg_fence(float (&d)[48]) { asm volatile("" : RW48("+f", d)::"memory"); }
__device__ __forceinline__ void reg_fence(float (&d)[32]) { asm volatile("" : RW32("+f", d)::"memory"); }

template <int NR>
__device__ __forceinline__ void zero(float (&d)[NR]) {
#pragma unroll
    for (int i = 0; i < NR; i++) d[i] = 0.f;
}

constexpr uint32_t HI_SW128 = (1024u >> 4) | (1u << 30);
constexpr uint32_t HI_OST = (2560u >> 4) | (2u << 30);
constexpr uint32_t LO_LBO1 = (1u << 16);
constexpr uint32_t LO_OST = ((512u >> 4) << 16);

template <int TA, int TB, uint32_t HIB, bool ACC>
__device__ __forceinline__ void wgmma(float (&d)[80], uint32_t loA, uint32_t loB) {
#define WG_ASM(SD)                                                          \
    "{\n.reg .b64 da, db;\nmov.b64 da, {%80, %82};\nmov.b64 db, {%81, %83};\n" \
    "wgmma.mma_async.sync.aligned.m64n160k16.f32.bf16.bf16 "               \
    "{%0,%1,%2,%3,%4,%5,%6,%7,%8,%9,%10,%11,%12,%13,%14,%15,%16,%17,%18,%19,%20,%21,%22,%23,%24,%25,%26,%27,%28,%29,%30,%31,%32,%33,%34,%35,%36,%37,%38,%39,%40,%41,%42,%43,%44,%45,%46,%47,%48,%49,%50,%51,%52,%53,%54,%55,%56,%57,%58,%59,%60,%61,%62,%63,%64,%65,%66,%67,%68,%69,%70,%71,%72,%73,%74,%75,%76,%77,%78,%79}, da, db, " SD ", 1, 1, %84, %85;\n}"
    if constexpr (ACC)
        asm volatile(WG_ASM("1") : RW80("+f", d) : "r"(loA), "r"(loB), "n"(HI_SW128), "n"(HIB), "n"(TA), "n"(TB));
    else
        asm volatile(WG_ASM("0") : RW80("=f", d) : "r"(loA), "r"(loB), "n"(HI_SW128), "n"(HIB), "n"(TA), "n"(TB));
#undef WG_ASM
}
template <int TA, int TB, uint32_t HIB, bool ACC>
__device__ __forceinline__ void wgmma(float (&d)[48], uint32_t loA, uint32_t loB) {
#define WG_ASM(SD)                                                          \
    "{\n.reg .b64 da, db;\nmov.b64 da, {%48, %50};\nmov.b64 db, {%49, %51};\n" \
    "wgmma.mma_async.sync.aligned.m64n96k16.f32.bf16.bf16 "               \
    "{%0,%1,%2,%3,%4,%5,%6,%7,%8,%9,%10,%11,%12,%13,%14,%15,%16,%17,%18,%19,%20,%21,%22,%23,%24,%25,%26,%27,%28,%29,%30,%31,%32,%33,%34,%35,%36,%37,%38,%39,%40,%41,%42,%43,%44,%45,%46,%47}, da, db, " SD ", 1, 1, %52, %53;\n}"
    if constexpr (ACC)
        asm volatile(WG_ASM("1") : RW48("+f", d) : "r"(loA), "r"(loB), "n"(HI_SW128), "n"(HIB), "n"(TA), "n"(TB));
    else
        asm volatile(WG_ASM("0") : RW48("=f", d) : "r"(loA), "r"(loB), "n"(HI_SW128), "n"(HIB), "n"(TA), "n"(TB));
#undef WG_ASM
}
template <int TA, int TB, uint32_t HIB, bool ACC>
__device__ __forceinline__ void wgmma(float (&d)[32], uint32_t loA, uint32_t loB) {
#define WG_ASM(SD)                                                          \
    "{\n.reg .b64 da, db;\nmov.b64 da, {%32, %34};\nmov.b64 db, {%33, %35};\n" \
    "wgmma.mma_async.sync.aligned.m64n64k16.f32.bf16.bf16 "               \
    "{%0,%1,%2,%3,%4,%5,%6,%7,%8,%9,%10,%11,%12,%13,%14,%15,%16,%17,%18,%19,%20,%21,%22,%23,%24,%25,%26,%27,%28,%29,%30,%31}, da, db, " SD ", 1, 1, %36, %37;\n}"
    if constexpr (ACC)
        asm volatile(WG_ASM("1") : RW32("+f", d) : "r"(loA), "r"(loB), "n"(HI_SW128), "n"(HIB), "n"(TA), "n"(TB));
    else
        asm volatile(WG_ASM("0") : RW32("=f", d) : "r"(loA), "r"(loB), "n"(HI_SW128), "n"(HIB), "n"(TA), "n"(TB));
#undef WG_ASM
}

__device__ __forceinline__ uint32_t pack_bf16(float lo, float hi) {
    uint32_t r;
    asm("cvt.rn.bf16x2.f32 %0, %1, %2;" : "=r"(r) : "f"(hi), "f"(lo));
    return r;
}
__device__ __forceinline__ float ex2(float x) {
    float r;
    asm("ex2.approx.ftz.f32 %0, %1;" : "=f"(r) : "f"(x));
    return r;
}
__device__ __forceinline__ void stsm4t(uint32_t a, uint32_t r0, uint32_t r1, uint32_t r2, uint32_t r3) {
    asm volatile("stmatrix.sync.aligned.m8n8.x4.trans.shared.b16 [%0], {%1,%2,%3,%4};" ::"r"(a), "r"(r0), "r"(r1), "r"(r2), "r"(r3)
                 : "memory");
}
__device__ __forceinline__ uint32_t lds_u(uint32_t a) {
    uint32_t v;
    asm volatile("ld.shared.u32 %0, [%1];" : "=r"(v) : "r"(a) : "memory");
    return v;
}
__device__ __forceinline__ float2 lds_f2(uint32_t a) {
    float2 v;
    asm volatile("ld.shared.v2.f32 {%0,%1}, [%2];" : "=f"(v.x), "=f"(v.y) : "r"(a) : "memory");
    return v;
}
__device__ __forceinline__ void sts_f(uint32_t a, float v) { asm volatile("st.shared.f32 [%0], %1;" ::"r"(a), "f"(v) : "memory"); }
__device__ __forceinline__ void sts_u(uint32_t a, uint32_t v) { asm volatile("st.shared.u32 [%0], %1;" ::"r"(a), "r"(v) : "memory"); }
__device__ __forceinline__ void sts_f2(uint32_t a, float x, float y) {
    asm volatile("st.shared.v2.f32 [%0], {%1,%2};" ::"r"(a), "f"(x), "f"(y) : "memory");
}

__device__ __forceinline__ void store_tile_t(const float (&d)[80], uint32_t addr) {
#pragma unroll
    for (int j = 0; j < 10; j++)
        stsm4t(addr + j * 2048, pack_bf16(d[8 * j], d[8 * j + 1]), pack_bf16(d[8 * j + 2], d[8 * j + 3]),
               pack_bf16(d[8 * j + 4], d[8 * j + 5]), pack_bf16(d[8 * j + 6], d[8 * j + 7]));
}
template <int NR>
__device__ __forceinline__ void store_out_tile(const float (&d)[NR], uint32_t base, uint32_t lane, uint32_t w) {
    const uint32_t mi = lane >> 3, i = lane & 7;
    const uint32_t chunk = 2 * w + (mi & 1);
    const uint32_t q0 = 8 * (i >> 1) + 2 * (mi >> 1) + (i & 1);
    const uint32_t a0 = base + q0 * 128 + ((chunk ^ (q0 & 7)) << 4);
    const uint32_t a1 = base + (q0 + 4) * 128 + ((chunk ^ ((q0 + 4) & 7)) << 4);
#pragma unroll
    for (int j = 0; j < NR / 8; j++)
        stsm4t(((j & 1) ? a1 : a0) + (j >> 1) * 4096, pack_bf16(d[8 * j], d[8 * j + 1]), pack_bf16(d[8 * j + 2], d[8 * j + 3]),
               pack_bf16(d[8 * j + 4], d[8 * j + 5]), pack_bf16(d[8 * j + 6], d[8 * j + 7]));
}

struct TrueT { static constexpr bool value = true; };
struct FalseT { static constexpr bool value = false; };

template <int V>
struct IntT { static constexpr int value = V; };

__device__ __forceinline__ uint32_t get_item(uint32_t sb, int it) {
    mbar_wait(sb + BAR_ITEM + it * 8, 0);
    return lds_u(sb + OFF_ITEM + it * 4);
}
__device__ __forceinline__ uint32_t get_item_warp(uint32_t sb, int it) { return __shfl_sync(0xffffffffu, get_item(sb, it), 0); }

struct Ring {
    uint32_t slot, ph;
    __device__ __forceinline__ void adv(uint32_t k) {
        slot += k;
        if (slot >= NSLOT) { slot -= NSLOT; ph ^= 1; }
    }
};

template <int K>
__device__ __forceinline__ void qk_step(float (&s)[80], uint32_t loK, uint32_t loQ) {
    wgmma<0, 0, HI_SW128, K != 0>(s, loK + (K >> 2) * (8192 >> 4) + (K & 3) * 2, loQ + (K >> 2) * (XS >> 4) + (K & 3) * 2);
}
template <int K0, int K1>
__device__ __forceinline__ void qk_steps(float (&s)[80], uint32_t loK, uint32_t loQ) {
    if constexpr (K0 < K1) {
        qk_step<K0>(s, loK, loQ);
        qk_steps<K0 + 1, K1>(s, loK, loQ);
    }
}
__device__ __forceinline__ uint32_t add_bf2(uint32_t a, uint32_t b) {
    uint32_t r;
    asm("add.rn.bf16x2 %0, %1, %2;" : "=r"(r) : "r"(a), "r"(b));
    return r;
}
template <int J>
__device__ __forceinline__ void exp_block(const float (&s)[80], uint32_t (&k)[40], uint32_t pa, float mref) {
    if constexpr (J < 10) {
#pragma unroll
        for (int i = 4 * J; i < 4 * J + 4; i++)
            k[i] = pack_bf16(ex2(fmaf(s[2 * i], SM_C, -mref)), ex2(fmaf(s[2 * i + 1], SM_C, -mref)));
#pragma unroll
        for (int i = 0; i < 4; i++)
            asm volatile("stmatrix.sync.aligned.m8n8.x1.trans.shared.b16 [%0], {%1};" ::"r"(((i & 1) ? pa ^ 16 : pa) + J * 2048 + (i >> 1) * 1024),
                         "r"(k[4 * J + i])
                         : "memory");
        exp_block<J + 1>(s, k, pa, mref);
    }
}
__device__ __forceinline__ void sum_block(const uint32_t (&k)[40], float (&l)[10], uint32_t lane) {
    const bool b4 = lane & 16, b3 = lane & 8;
    uint32_t ps[20], t[10];
#pragma unroll
    for (int j = 0; j < 20; j++) ps[j] = add_bf2(k[2 * j], k[2 * j + 1]);
#pragma unroll
    for (int j = 0; j < 10; j++)
        t[j] = add_bf2(b4 ? ps[2 * j + 1] : ps[2 * j], __shfl_xor_sync(0xffffffffu, b4 ? ps[2 * j] : ps[2 * j + 1], 16));
#pragma unroll
    for (int i = 0; i < 5; i++) {
        const uint32_t a = b3 ? t[i + 5] : t[i], b = __shfl_xor_sync(0xffffffffu, b3 ? t[i] : t[i + 5], 8);
        l[2 * i] += __uint_as_float(a << 16) + __uint_as_float(b << 16);
        l[2 * i + 1] += __uint_as_float(a & 0xffff0000u) + __uint_as_float(b & 0xffff0000u);
    }
}
__device__ __forceinline__ void sum_store(const float (&l)[10], uint32_t lane, uint32_t lxa) {
    const bool b2 = lane & 4;
#pragma unroll
    for (int i = 0; i < 5; i++)
        sts_f(lxa + i * 64, (b2 ? l[2 * i + 1] : l[2 * i]) + __shfl_xor_sync(0xffffffffu, b2 ? l[2 * i] : l[2 * i + 1], 4));
}

__device__ __forceinline__ void fallback_unit(const Params& P, uint32_t e, uint32_t tid) {
    const uint32_t lane = tid & 31, br = IT_BR(e), b = IT_B(e), h = IT_H0(e);
    const __nv_bfloat162* wq = (const __nv_bfloat162*)(P.pwq[br] + h * 192) + lane;
    const __nv_bfloat162* kp = (const __nv_bfloat162*)(P.pk[br] + (size_t)(b * 32 + h) * 512 * 192) + lane;
    const __nv_bfloat162* vp = (const __nv_bfloat162*)(P.pv[br] + (size_t)(b * 32 + h) * 512 * 192) + lane;
#pragma unroll 1
    for (uint32_t qi = 0; qi < 40; qi++) {
        const uint32_t q = 4 * qi + (tid >> 5);
        const __nv_bfloat16* xr = P.px[br] + (size_t)(b * 160 + q) * 640;
        float a[6] = {0.f, 0.f, 0.f, 0.f, 0.f, 0.f};
#pragma unroll 4
        for (int k = 0; k < 640; k++) {
            const float xv = __bfloat162float(xr[k]);
#pragma unroll
            for (int i = 0; i < 3; i++) {
                const float2 wv = __bfloat1622float2(wq[(size_t)k * 3072 + i * 32]);
                a[2 * i] = fmaf(xv, wv.x, a[2 * i]);
                a[2 * i + 1] = fmaf(xv, wv.y, a[2 * i + 1]);
            }
        }
#pragma unroll
        for (int i = 0; i < 6; i++) a[i] = __bfloat162float(__float2bfloat16(a[i]));
        auto score = [&](int key) {
            float d = 0.f;
#pragma unroll
            for (int i = 0; i < 3; i++) {
                const float2 kv = __bfloat1622float2(kp[key * 96 + i * 32]);
                d = fmaf(a[2 * i], kv.x, fmaf(a[2 * i + 1], kv.y, d));
            }
#pragma unroll
            for (int o = 16; o > 0; o >>= 1) d += __shfl_xor_sync(0xffffffffu, d, o);
            return d;
        };
        float m = -INFINITY;
#pragma unroll 4
        for (int key = 0; key < 512; key++) m = fmaxf(m, score(key));
        float o[6] = {0.f, 0.f, 0.f, 0.f, 0.f, 0.f}, sum = 0.f;
#pragma unroll 4
        for (int key = 0; key < 512; key++) {
            const float p = ex2((score(key) - m) * SM_C);
            sum += p;
#pragma unroll
            for (int i = 0; i < 3; i++) {
                const float2 vv = __bfloat1622float2(vp[key * 96 + i * 32]);
                o[2 * i] = fmaf(p, vv.x, o[2 * i]);
                o[2 * i + 1] = fmaf(p, vv.y, o[2 * i + 1]);
            }
        }
        const float inv = __fdividef(1.f, sum);
        __nv_bfloat16* op = (__nv_bfloat16*)ostash(br, b, h) + (q >> 5) * 256 + 2 * ((q & 31) >> 3) + (q & 1);
#pragma unroll
        for (int i = 0; i < 6; i++) {
            const uint32_t d = (i >> 1) * 64 + 2 * lane + (i & 1);
            op[(d >> 3) * 1280 + (d & 7) * 32 + ((((q & 7) >> 1) ^ ((d & 7) >> 1)) << 3)] = __float2bfloat16(o[i] * inv);
        }
    }
}

template <int W>
struct PendO {
    static constexpr int N = W == 0 ? 14 : 16;
    uint32_t v[4 * N];
    unsigned char* gp;
    uint32_t pend, sig;
    template <int I>
    __device__ __forceinline__ void store() const {
        if constexpr (I < N) {
            constexpr int g = I < 10 ? I / 2 : (I - 10) / 2 + (W == 0 ? 3 : 0);
            constexpr int off = (I < 10 ? W : 2) * XS + g * 512 + (I & 1) * 2560;
            asm volatile(
                "{\n.reg .pred p;\nsetp.ne.u32 p, %6, 0;\n@p st.global.v4.b32 [%0+%5], {%1,%2,%3,%4};\n}" ::"l"(gp),
                "r"(v[4 * I]), "r"(v[4 * I + 1]), "r"(v[4 * I + 2]), "r"(v[4 * I + 3]), "n"(off), "r"(pend)
                : "memory");
        }
    }
    template <int I>
    __device__ __forceinline__ void flush() const {
        if constexpr (I < N) {
            store<I>();
            flush<I + 1>();
        }
    }
    __device__ __forceinline__ void clear() {
#pragma unroll
        for (int i = 0; i < 4 * N; i++) v[i] = 0;
        gp = nullptr;
        pend = 0;
        sig = 0;
    }
};

template <int W, int KK, int KE>
__device__ __forceinline__ void qproj(float (&q0)[80], float (&q1)[80], uint32_t sb, Ring& r, uint32_t phm, const PendO<W>& po) {
    const uint32_t loR = ((sb + OFF_R) >> 4) | LO_LBO1;
    const uint32_t loRing = ((sb + OFF_RING) >> 4) | LO_LBO1;
    constexpr int xs = KK % 5;
    const uint32_t pslot = r.slot;
    if (KK > 0) r.adv(1);
    if (W == 1 && KK == QHOLD) nb_sync<NB_SDONE, 256>();
    mbar_wait(sb + BAR_RFULL + r.slot * 8, r.ph);
    mbar_wait(sb + BAR_XFULL + xs * 8, ((phm >> xs) ^ (KK / 5)) & 1);
    const uint32_t a = loRing + r.slot * (SLOT >> 4) + (W == 0 ? 0 : 1024), b = loR + xs * (XS >> 4);
    wg_fence();
    wgmma<1, 0, HI_SW128, KK != 0>(q0, a, b);
    if (W == 0) wgmma<1, 0, HI_SW128, KK != 0>(q1, a + 512, b);
#pragma unroll
    for (int k = 1; k < 4; k++) {
        wgmma<1, 0, HI_SW128, true>(q0, a + k * 128, b + k * 2);
        if (W == 0) wgmma<1, 0, HI_SW128, true>(q1, a + 512 + k * 128, b + k * 2);
    }
    wg_commit();
    if (KK > 0) {
        wg_wait<1>();
        mbar_arrive_warp(sb + BAR_REMPTY + pslot * 8, 1);
        if (KK <= 5) mbar_arrive_warp(sb + (BAR_XEMPTY + (KK - 1) * 8), 1);
        if (W == 1 && KK == 7) nb_arrive<NB_PDONE, 256>();
    }
    if constexpr (W == 0 && KK < 5) {
        po.template store<3 * KK>();
        po.template store<3 * KK + 1>();
        po.template store<3 * KK + 2>();
        if (KK == 4 && po.sig) nb_arrive<NB_ODONE, 288>();
    }
    if constexpr (W == 1 && KK >= QPRE && KK < QPRE + 4) {
        po.template store<4 * (KK - QPRE)>();
        po.template store<4 * (KK - QPRE) + 1>();
        po.template store<4 * (KK - QPRE) + 2>();
        po.template store<4 * (KK - QPRE) + 3>();
        if (KK == QPRE + 3 && po.sig) nb_arrive<NB_ODONE, 288>();
    }
    if constexpr (KK + 1 < KE) {
        qproj<W, KK + 1, KE>(q0, q1, sb, r, phm, po);
    } else if constexpr (KE == 10) {
        if (W == 0) nb_arrive<NB_SDONE, 256>();
        wg_wait<0>();
        reg_fence(q0);
        if (W == 0) reg_fence(q1);
        mbar_arrive_warp(sb + BAR_REMPTY + r.slot * 8, 1);
        r.adv(1);
    }
}

template <int NR>
__device__ __forceinline__ void opack(const float (&o)[NR], int gl, const float2* sc, uint32_t* v) {
#pragma unroll
    for (int hh = 0; hh < 2; hh++)
#pragma unroll
        for (int t = 0; t < 4; t++)
            v[4 * hh + t] = pack_bf16(o[16 * gl + 4 * t + 2 * hh] * sc[t].x, o[16 * gl + 4 * t + 2 * hh + 1] * sc[t].y);
}

template <int NR>
__device__ __forceinline__ void dump_acc(const float (&c)[NR], float4* p) {
#pragma unroll
    for (int i = 0; i < NR / 4; i++) p[i * 128] = make_float4(c[4 * i], c[4 * i + 1], c[4 * i + 2], c[4 * i + 3]);
}
__device__ __forceinline__ void wait_flag(const unsigned int* f, uint32_t epoch) {
    uint32_t v, n = 0;
    do {
        asm volatile("ld.acquire.gpu.global.u32 %0, [%1];" : "=r"(v) : "l"(f) : "memory");
        if (++n > 0x400000) __trap();
    } while (v != epoch);
}

template <bool IS_S>
__device__ __forceinline__ void op_item(uint32_t e, uint32_t sb, Ring& r, uint32_t& phm) {
    constexpr int T0 = IS_S ? 0 : 2;
    constexpr uint32_t BOFF = IS_S ? (3 * 512) >> 4 : 0;
    const uint32_t loRing = ((sb + OFF_RING) >> 4) | LO_LBO1;
    const uint32_t loO = ((sb + OFF_R) >> 4) | LO_OST;
    float c0[80], c1[80], c2[IS_S ? 32 : 48];
    const int T2 = 6 * (IT_H1(e) - IT_H0(e));
    uint32_t xs = 0;
    auto step = [&](auto first, uint32_t hf) {
        constexpr bool F = decltype(first)::value;
        if (hf == 0) {
            mbar_wait(sb + BAR_XFULL + xs * 8, (phm >> xs) & 1);
            phm ^= 1u << xs;
        }
        mbar_wait(sb + BAR_RFULL + r.slot * 8, r.ph);
        const uint32_t a = loRing + r.slot * (SLOT >> 4), b = loO + xs * (XS >> 4) + hf * 640;
        wg_fence();
        wgmma<1, 1, HI_OST, !F>(c0, a + T0 * 256, b);
        wgmma<1, 1, HI_OST, !F>(c1, a + T0 * 256 + 256, b);
        wgmma<1, 1, HI_OST, !F>(c2, a + 1024, b + BOFF);
        wgmma<1, 1, HI_OST, true>(c0, a + T0 * 256 + 128, b + 320);
        wgmma<1, 1, HI_OST, true>(c1, a + T0 * 256 + 384, b + 320);
        wgmma<1, 1, HI_OST, true>(c2, a + 1024 + 128, b + 320 + BOFF);
        wg_commit();
    };
    step(TrueT{}, 0);
#pragma unroll 1
    for (int t = 1; t < T2; t++) {
        const uint32_t pslot = r.slot, pxs = xs;
        r.adv(1);
        if ((t & 1) == 0 && ++xs == 5) xs = 0;
        step(FalseT{}, t & 1);
        wg_wait<1>();
        mbar_arrive_warp(sb + BAR_REMPTY + pslot * 8, 1);
        if ((t & 1) == 0 && t + 8 < T2) mbar_arrive_warp(sb + BAR_XEMPTY + pxs * 8, 1);
    }
    wg_wait<0>();
    reg_fence(c0);
    reg_fence(c1);
    reg_fence(c2);
    mbar_arrive_warp(sb + BAR_REMPTY + r.slot * 8, 1);
    r.adv(1);
    if (IT_PART(e)) {
#pragma unroll
        for (int m = 0; m < 5; m++) mbar_arrive_warp(sb + BAR_XEMPTY + m * 8, 1);
        float4* pp = g_part + (size_t)((IT_BR(e) * 16 + IT_B(e)) * 10 + IT_HALF(e) * 5) * 2560 + (threadIdx.x & 127);
        dump_acc(c0, pp + T0 * 2560);
        dump_acc(c1, pp + (T0 + 1) * 2560);
        dump_acc(c2, pp + 4 * 2560 + (IS_S ? 12 * 128 : 0));
    } else {
        nb_sync<NB_OPEND, 256>();
        const uint32_t lane = threadIdx.x & 31, w = (threadIdx.x >> 5) & 3;
        store_out_tile(c0, sb + OFF_R + T0 * XS, lane, w);
        store_out_tile(c1, sb + OFF_R + (T0 + 1) * XS, lane, w);
        store_out_tile(c2, sb + OFF_R + 4 * XS + (IS_S ? 96 * 128 : 0), lane, w);
        fence_async_smem();
    }
    nb_arrive<NB_ODONE, 288>();
}

template <int W>
__device__ __forceinline__ void on_item(uint32_t e, uint32_t sb, Ring& r, uint32_t& phm, uint32_t epoch) {
    const uint32_t loRing = ((sb + OFF_RING) >> 4) | LO_LBO1;
    const uint32_t loO = ((sb + OFF_R) >> 4) | LO_OST;
    float c[80];
    const int T = 3 * (IT_H1(e) - IT_H0(e));
    uint32_t xs = 0;
    auto step = [&](auto first) {
        constexpr bool F = decltype(first)::value;
        mbar_wait(sb + BAR_XFULL + xs * 8, (phm >> xs) & 1);
        phm ^= 1u << xs;
        mbar_wait(sb + BAR_RFULL + r.slot * 8, r.ph);
        const uint32_t a = loRing + r.slot * (SLOT >> 4) + W * 512, b = loO + xs * (XS >> 4);
        wg_fence();
        wgmma<1, 1, HI_OST, !F>(c, a, b);
#pragma unroll
        for (int k = 1; k < 4; k++) wgmma<1, 1, HI_OST, true>(c, a + k * 128, b + k * 320);
        wg_commit();
    };
    auto run = [&](int t0, int t1) {
#pragma unroll 1
        for (int t = t0; t < t1; t++) {
            const uint32_t pslot = r.slot, pxs = xs;
            r.adv(1);
            if (++xs == 5) xs = 0;
            step(FalseT{});
            wg_wait<1>();
            mbar_arrive_warp(sb + BAR_REMPTY + pslot * 8, 1);
            mbar_arrive_warp_if(sb + BAR_XEMPTY + pxs * 8, 1, t + 4 < T);
        }
    };
    step(TrueT{});
    const int tm = T - 3;
    run(1, tm);
    float4 pv[20];
    {
        const uint32_t tile = 2 * IT_HALF(e) + W, bb = IT_BR(e) * 16 + IT_B(e);
        wait_flag(&g_pflag[bb * 2 + (tile >= 5)], epoch);
        const float4* pp = g_part + (size_t)(bb * 10 + tile) * 2560 + (threadIdx.x & 127);
#pragma unroll
        for (int i = 0; i < 20; i++) pv[i] = __ldcg(pp + i * 128);
    }
    run(tm, T);
    wg_wait<0>();
    reg_fence(c);
    mbar_arrive_warp(sb + BAR_REMPTY + r.slot * 8, 1);
    r.adv(1);
    nb_sync<NB_OPEND, 256>();
#pragma unroll
    for (int i = 0; i < 20; i++) {
        c[4 * i] += pv[i].x;
        c[4 * i + 1] += pv[i].y;
        c[4 * i + 2] += pv[i].z;
        c[4 * i + 3] += pv[i].w;
    }
    store_out_tile(c, sb + OFF_R + W * XS, threadIdx.x & 31, (threadIdx.x >> 5) & 3);
    fence_async_smem();
    nb_arrive<NB_ODONE, 288>();
}

template <int W>
__device__ __forceinline__ uint32_t qa_item(const Params& P, uint32_t sb, Ring& r, uint32_t phm, PendO<W>& po,
                                            float (&oa)[80], float (&ob)[W == 0 ? 32 : 48], int it) {
    const uint32_t loR = ((sb + OFF_R) >> 4) | LO_LBO1;
    const uint32_t loRing = ((sb + OFF_RING) >> 4) | LO_LBO1;
    const uint32_t lane = threadIdx.x & 31, w = (threadIdx.x >> 5) & 3;
    const uint32_t sta = sb + OFF_R + (lane >> 4) * 1024 + (lane & 7) * 128 + (((2 * w + ((lane >> 3) & 1)) ^ (lane & 7)) << 4);
    auto pack_o = [&](int ie) {
#pragma unroll
        for (int g = 0; g < 5; g++) {
            float2 sc[4];
#pragma unroll
            for (int t = 0; t < 4; t++) sc[t] = lds_f2(sb + OFF_LINV + (lane & 3) * 8 + (4 * g + t) * 32);
            opack(oa, g, sc, po.v + 8 * g);
            if (W == 0 && g >= 3) opack(ob, g - 3, sc, po.v + 40 + 8 * (g - 3));
            if (W == 1 && g < 3) opack(ob, g, sc, po.v + 40 + 8 * g);
        }
        const uint32_t e = lds_u(sb + OFF_ITEM + ie * 4);
        po.gp = ostash(IT_BR(e), IT_B(e), IT_H0(e)) + w * 5120 + (lane >> 2) * 64 + (((lane ^ (lane >> 3)) & 3) << 4);
    };
    {
        float q0[80], q1[80];
        if constexpr (W == 0) {
            qproj<W, 0, 10>(q0, q1, sb, r, phm, po);
        } else {
            qproj<W, 0, QPRE>(q0, q1, sb, r, phm, po);
            if (po.sig) nb_sync<NB_VOTE, 256>();
            po.pend = po.sig && !__any_sync(0xffffffffu, lds_u(sb + OFF_FB) != 0);
            pack_o(it > 0 ? it - 1 : 0);
            TS(W, 26);
            qproj<W, QPRE, 10>(q0, q1, sb, r, phm, po);
        }
        TS(W, 1);
        if (W == 0) {
            nb_sync<NB_PDONE, 256>();
            store_tile_t(q0, sta);
            store_tile_t(q1, sta + XS);
        } else {
            store_tile_t(q0, sta + 2 * XS);
        }
    }
    fence_async_smem();
    float s[80], l[10];
#pragma unroll
    for (int i = 0; i < 80; i++) oa[i] = 0.f;
#pragma unroll
    for (int i = 0; i < (W == 0 ? 32 : 48); i++) ob[i] = 0.f;
#pragma unroll
    for (int i = 0; i < 10; i++) l[i] = 0.f;
    reg_fence(oa);
    reg_fence(ob);
    auto pv = [&](uint32_t buf) {
        mbar_wait(sb + BAR_RFULL + r.slot * 8, r.ph);
        const uint32_t a = loRing + r.slot * (SLOT >> 4), b = loR + (3 + buf) * (XS >> 4);
        wg_fence();
#pragma unroll
        for (int k = 0; k < 4; k++) {
            wgmma<1, 0, HI_SW128, true>(oa, a + W * 512 + k * 128, b + k * 2);
            wgmma<1, 0, HI_SW128, true>(ob, a + 1024 + k * 128, b + (W == 0 ? (96 * 128) >> 4 : 0) + k * 2);
        }
        wg_commit();
    };
    float mref;
    uint32_t kslot, vslot;
    const uint32_t lxa = sb + OFF_LX + w * 640 + (((lane & 8) ? 80 : 0) + ((lane >> 1) & 8) + 2 * (lane & 3) + ((lane >> 2) & 1)) * 4;
    auto tail = [&](bool rel_other, int i) {
        uint32_t ps[40];
        exp_block<0>(s, ps, sta + (3 + W) * XS, mref);
        if (rel_other) {
            wg_wait<0>();
            mbar_arrive_warp(sb + BAR_REMPTY + vslot * 8, 1);
            if (W == 1) mbar_arrive_warp_if(sb + BAR_XEMPTY + 24, 1, i == 3);
        }
        fence_async_smem();
        if (W == 1 && i == 3) {
            nb_sync<NB_W + W, 128>();
            pv(W);
        }
        nb_arrive<NB_PFULL + W, 256>();
        TS(W, 6 + 5 * i);
        mbar_wait(sb + BAR_RFULL + r.slot * 8, r.ph);
        sum_block(ps, l, lane);
        TS(W, 7 + 5 * i);
        if (W == 0 || i < 3) {
            nb_sync<NB_W + W, 128>();
            pv(W);
        }
        TS(W, 8 + 5 * i);
    };
    if (W == 0) {
        nb_sync<NB_W, 128>();
        TS(W, 2);
        mbar_wait(sb + BAR_RFULL + r.slot * 8, r.ph);
        wg_fence();
        qk_steps<0, 8>(s, loRing + r.slot * (SLOT >> 4), loR);
        nb_sync<NB_Q2, 256>();
        qk_steps<8, 12>(s, loRing + r.slot * (SLOT >> 4), loR);
        wg_commit();
        nb_arrive<NB_Q01, 256>();
        TS(W, 4);
        wg_wait<0>();
        reg_fence(s);
        mbar_arrive_warp(sb + BAR_REMPTY + r.slot * 8, 2);
        r.adv(2);
        float m0 = fmaxf(s[0], s[5]), m1 = fmaxf(s[10], s[15]);
#pragma unroll
        for (int i = 20; i < 80; i += 10) {
            m0 = fmaxf(m0, s[i]);
            m1 = fmaxf(m1, s[i + 5]);
        }
        int key = __float_as_int(fmaxf(m0, m1));
        key ^= (key >> 31) & 0x7fffffff;
        key = __reduce_max_sync(0xffffffffu, key);
        key ^= (key >> 31) & 0x7fffffff;
        sts_u(sb + OFF_GM + w * 4, key);
        sts_u(sb + OFF_FB, 0);
        nb_sync<NB_W, 128>();
        const float2 u = lds_f2(sb + OFF_GM), v = lds_f2(sb + OFF_GM + 8);
        mref = fmaxf(fmaxf(u.x, u.y), fmaxf(v.x, v.y)) * SM_C;
        TS(W, 5);
        tail(false, 0);
    } else {
        nb_arrive<NB_Q2, 256>();
        TS(W, 2);
        nb_sync<NB_Q01, 256>();
    }
#pragma unroll 1
    for (int i = (W == 0 ? 1 : 0); i < 4; i++) {
        const uint32_t pvslot = r.slot;
        r.adv(1);
        kslot = r.slot;
        mbar_wait(sb + BAR_RFULL + r.slot * 8, r.ph);
        wg_fence();
        qk_steps<0, 12>(s, loRing + r.slot * (SLOT >> 4), loR);
        wg_commit();
        wg_wait<1>();
        mbar_arrive_warp_if(sb + BAR_REMPTY + pvslot * 8, 1, W == 0 || i > 0);
        r.adv(1);
        vslot = r.slot;
        TS(W, 4 + 5 * i);
        nb_sync<NB_PFULL + (W ^ 1), 256>();
        pv(W ^ 1);
        if (W == 1) {
            const float2 u = lds_f2(sb + OFF_GM), v = lds_f2(sb + OFF_GM + 8);
            mref = fmaxf(fmaxf(u.x, u.y), fmaxf(v.x, v.y)) * SM_C;
        }
        wg_wait<1>();
        reg_fence(s);
        mbar_arrive_warp(sb + BAR_REMPTY + kslot * 8, 2);
        if (W == 1) {
            mbar_arrive_warp_if(sb + BAR_XEMPTY + 0, 2, i == 3);
            mbar_arrive_warp_if(sb + BAR_XEMPTY + 8, 2, i == 3);
            mbar_arrive_warp_if(sb + BAR_XEMPTY + 16, 2, i == 3);
        }
        r.adv(W == 1 && i == 3 ? 1 : 2);
        TS(W, 5 + 5 * i);
        tail(true, i);
    }
    if (W == 0) {
        const uint32_t tid = threadIdx.x & 127;
        float2 v = make_float2(0.f, 0.f);
        auto gather = [&]() {
            if (tid < 80) {
#pragma unroll
                for (int i = 0; i < 4; i++) {
                    const float2 u = lds_f2(sb + OFF_LX + i * 640 + tid * 8);
                    v.x += u.x;
                    v.y += u.y;
                }
            }
        };
        sum_store(l, lane, lxa);
        nb_sync<NB_W, 128>();
        gather();
        nb_arrive<NB_LX, 256>();
        wg_wait<0>();
        mbar_arrive_warp(sb + BAR_REMPTY + r.slot * 8, 1);
        mbar_arrive_warp(sb + BAR_XEMPTY + 24, 1);
        r.adv(1);
        nb_sync<NB_PFULL + 1, 256>();
        pv(1);
        TS(W, 24);
        nb_sync<NB_L, 256>();
        gather();
        if (tid < 80) {
            sts_f2(sb + OFF_LINV + tid * 8, __fdividef(1.f, v.x), __fdividef(1.f, v.y));
            if (!(v.x >= 5.421010862e-20f && v.x <= 1.8446744e19f && v.y >= 5.421010862e-20f && v.y <= 1.8446744e19f))
                sts_u(sb + OFF_FB, 1);
        }
    }
    if (W == 0) {
        nb_arrive<NB_VOTE, 256>();
        nb_sync<NB_W, 128>();
    } else {
        nb_sync<NB_LX, 256>();
        sum_store(l, lane, lxa);
        nb_arrive<NB_L, 256>();
    }
    const uint32_t nx = get_item_warp(sb, it + 1);
    wg_wait<0>();
    reg_fence(oa);
    reg_fence(ob);
    mbar_arrive_warp(sb + BAR_REMPTY + r.slot * 8, 1);
    mbar_arrive_warp(sb + BAR_XEMPTY + 32, 1);
    r.adv(1);
    TS(W, 25);
    po.sig = 1;
    if (W == 0) {
        const bool any = __any_sync(0xffffffffu, lds_u(sb + OFF_FB) != 0);
        pack_o(it);
        po.pend = !any;
        if (any) {
            fallback_unit(P, lds_u(sb + OFF_ITEM + it * 4), threadIdx.x & 127);
            __syncwarp();
        }
    }
    if (IT_TYPE(nx) != IT_QA) {
        if (W == 1) {
            nb_sync<NB_VOTE, 256>();
            po.pend = !__any_sync(0xffffffffu, lds_u(sb + OFF_FB) != 0);
            pack_o(it);
        }
        po.template flush<0>();
        nb_arrive<NB_ODONE, 288>();
        po.sig = 0;
        po.pend = 0;
    }
    return nx;
}

__global__ void __launch_bounds__(384, 1) fused_kernel(const __grid_constant__ Params P) {
    extern __shared__ __align__(1024) unsigned char smem_raw[];
    const uint32_t sb = (uint32_t)__cvta_generic_to_shared(smem_raw);
    const uint32_t wgid = __shfl_sync(0xffffffffu, threadIdx.x >> 7, 0);
    const uint32_t cta = blockIdx.x;

    uint32_t epoch = 0;
    if (wgid == 0) epoch = *(volatile unsigned int*)&g_epoch[cta] + 1;
    if (threadIdx.x == 0) {
        if (sb & 1023) __trap();
        sts_u(sb + OFF_FB + 4, epoch);
        for (int i = 0; i < NSLOT; i++) {
            mbar_init(sb + BAR_RFULL + i * 8, 1);
            mbar_init(sb + BAR_REMPTY + i * 8, 8);
            mbar_init(sb + BAR_XFULL + i * 8, 1);
            mbar_init(sb + BAR_XEMPTY + i * 8, 8);
        }
        for (int i = 0; i < MAXI; i++) mbar_init(sb + BAR_ITEM + i * 8, 1);
        asm volatile("fence.mbarrier_init.release.cluster;" ::: "memory");
        fence_async_smem();
    }
    __syncthreads();

    if (wgid == 0) {
        asm volatile("setmaxnreg.dec.sync.aligned.u32 24;");
        const uint32_t warp = __shfl_sync(0xffffffffu, threadIdx.x >> 5, 0);
        if (warp == 0) {
            if (threadIdx.x == 0) {
                *(volatile unsigned int*)&g_epoch[cta] = epoch;
                const uint64_t pol_first = mkpol<1>(), pol_norm = mkpol<POL_W>();
                if (cta == 0) *(volatile unsigned int*)&g_ticket[(epoch + 1) & 1] = 0;
                Ring r{0, 1};
                {
                    const uint32_t d = P.delay[cta];
                    uint32_t t0, t1;
                    asm volatile("mov.u32 %0, %%clock;" : "=r"(t0));
                    do {
                        asm volatile("mov.u32 %0, %%clock;" : "=r"(t1));
                    } while (t1 - t0 < d);
                }
                uint32_t e = P.items[cta][0];
#pragma unroll 1
                for (int it = 0;; it++) {
                    sts_u(sb + OFF_ITEM + it * 4, e);
                    asm volatile("mbarrier.arrive.shared::cta.b64 _, [%0];" ::"r"(sb + BAR_ITEM + it * 8) : "memory");
                    if (e == 0) break;
                    uint32_t nx = P.items[cta][it + 1 < NSTAT ? it + 1 : NSTAT - 1];
                    if (IT_TYPE(e) == IT_ON || it + 2 == MAXI) nx = 0;
                    uint32_t tk = 0;
                    const uint32_t br = IT_BR(e);
                    if (IT_TYPE(e) == IT_QA) {
                        const uint32_t h = IT_H0(e);
#pragma unroll 1
                        for (int kk = 0; kk < 10; kk++) {
                            mbar_wait(sb + BAR_REMPTY + r.slot * 8, r.ph);
                            mbar_expect(sb + BAR_RFULL + r.slot * 8, SLOT);
                            tma3(sb + OFF_RING + r.slot * SLOT, &P.wq[br], kk * 64, h * 3, sb + BAR_RFULL + r.slot * 8, pol_norm);
                            r.adv(1);
                        }
                        const int row0 = (IT_B(e) * 32 + h) * 512;
#pragma unroll 1
                        for (int n = 0; n < 16; n++) {
                            if (n == 13 && nx == IT_DYN) tk = atomicAdd(&g_ticket[epoch & 1], 1);
                            const bool isv = n == 15 || (n > 0 && !(n & 1));
                            const int j = n == 15 ? 7 : isv ? (n - 2) >> 1 : (n + 1) >> 1;
                            mbar_wait(sb + BAR_REMPTY + r.slot * 8, r.ph);
                            mbar_expect(sb + BAR_RFULL + r.slot * 8, SLOT);
                            tma3(sb + OFF_RING + r.slot * SLOT, isv ? &P.v[br] : &P.k[br], row0 + j * 64, 0,
                                 sb + BAR_RFULL + r.slot * 8, pol_first);
                            r.adv(1);
                        }
                    } else {
                        const int r0 = IT_H0(e) * 192, r1 = IT_H1(e) * 192;
                        const bool wide = IT_TYPE(e) == IT_OP;
#pragma unroll 1
                        for (int row = r0; row < r1; row += wide ? 32 : 64) {
                            mbar_wait(sb + BAR_REMPTY + r.slot * 8, r.ph);
                            mbar_expect(sb + BAR_RFULL + r.slot * 8, wide ? XS : 16384);
                            tma3(sb + OFF_RING + r.slot * SLOT, wide ? &P.wo[br] : &P.won[br], row, IT_HALF(e) * (wide ? 5 : 2),
                                 sb + BAR_RFULL + r.slot * 8, pol_norm);
                            r.adv(1);
                        }
                        if (nx == IT_DYN) tk = atomicAdd(&g_ticket[epoch & 1], 1);
                    }
                    if (nx == IT_DYN) nx = tk < P.nlist ? P.list[tk] : 0;
                    e = nx;
                }
            }
        } else if (warp == 1) {
            if (threadIdx.x == 32) {
                const uint64_t pol_norm = mkpol<POL_X>(), pol_o = mkpol<POL_O>();
                uint32_t phm = 0x1f;
#pragma unroll 1
                for (int it = 0;; it++) {
                    const uint32_t e = get_item(sb, it);
                    if (e == 0) break;
                    const uint32_t br = IT_BR(e);
                    uint32_t xs = 0;
                    if (IT_TYPE(e) == IT_QA) {
#pragma unroll 1
                        for (int kk = 0; kk < 10; kk++) {
                            mbar_wait(sb + BAR_XEMPTY + xs * 8, (phm >> xs) & 1);
                            phm ^= 1u << xs;
                            mbar_expect(sb + BAR_XFULL + xs * 8, XS);
                            tma3(sb + OFF_R + xs * XS, &P.x[br], IT_B(e) * 160, kk, sb + BAR_XFULL + xs * 8, pol_norm);
                            if (++xs == 5) xs = 0;
                        }
                    } else {
                        const uint32_t u0 = (br * 16 + IT_B(e)) * 32;
#pragma unroll 1
                        for (uint32_t u = u0 + IT_H0(e); u < u0 + IT_H1(e); u++) {
                            wait_flag(&g_flag[u], epoch);
                            asm volatile("fence.proxy.async;" ::: "memory");
#pragma unroll 1
                            for (int t = 0; t < 3; t++) {
                                mbar_wait(sb + BAR_XEMPTY + xs * 8, (phm >> xs) & 1);
                                phm ^= 1u << xs;
                                mbar_expect(sb + BAR_XFULL + xs * 8, XS);
                                bulk_load(sb + OFF_R + xs * XS, ostash(br, IT_B(e), u & 31) + t * XS, XS, sb + BAR_XFULL + xs * 8, pol_o);
                                if (++xs == 5) xs = 0;
                            }
                        }
                    }
                }
            }
        } else if (warp == 2) {
#pragma unroll 1
            for (int it = 0;; it++) {
                const uint32_t e = get_item_warp(sb, it);
                if (e == 0) break;
                nb_sync<NB_ODONE, 288>();
                if (threadIdx.x == 64) {
                    const uint32_t bb = IT_BR(e) * 16 + IT_B(e);
                    if (IT_TYPE(e) == IT_QA || IT_PART(e)) {
                        __threadfence();
                        unsigned int* f = IT_TYPE(e) == IT_QA ? &g_flag[bb * 32 + IT_H0(e)] : &g_pflag[bb * 2 + IT_HALF(e)];
                        asm volatile("st.relaxed.gpu.global.u32 [%0], %1;" ::"l"(f), "r"(epoch) : "memory");
                    } else {
                        const int nt = IT_TYPE(e) == IT_OP ? 5 : 2;
                        const int cc0 = IT_BR(e) * 640 + IT_HALF(e) * nt * 64;
#pragma unroll
                        for (int m = 0; m < 5; m++) {
                            if (m < nt)
                                asm volatile("cp.async.bulk.tensor.2d.global.shared::cta.bulk_group [%0, {%2,%3}], [%1];" ::"l"(&P.out),
                                             "r"(sb + OFF_R + m * XS), "r"(cc0 + m * 64), "r"((int)IT_B(e) * 160)
                                             : "memory");
                            asm volatile("cp.async.bulk.commit_group;" ::: "memory");
                        }
#define REL(N)                                                          \
    asm volatile("cp.async.bulk.wait_group.read %0;" ::"n"(4 - N) : "memory"); \
    asm volatile("mbarrier.arrive.shared::cta.b64 _, [%0], 8;" ::"r"(sb + BAR_XEMPTY + N * 8) : "memory");
                        REL(0) REL(1) REL(2) REL(3) REL(4)
#undef REL
                    }
                }
                __syncwarp();
            }
            if (threadIdx.x == 64) asm volatile("cp.async.bulk.wait_group 0;" ::: "memory");
        }
    } else if (wgid == 1) {
        asm volatile("setmaxnreg.inc.sync.aligned.u32 240;");
        PendO<0> po;
        po.clear();
        {
            const int it = 0;
            TS(0, 30);
        }
        float oa[80], ob[32];
        zero(oa);
        zero(ob);
        Ring r{0, 0};
        uint32_t phm = 0;
        uint32_t e = get_item_warp(sb, 0);
#pragma unroll 1
        for (int it = 0; e != 0; it++) {
            TS(0, 0);
            if (IT_TYPE(e) == IT_QA) {
                e = qa_item<0>(P, sb, r, phm, po, oa, ob, it);
            } else {
                if (IT_TYPE(e) == IT_OP) op_item<true>(e, sb, r, phm);
                else on_item<0>(e, sb, r, phm, lds_u(sb + OFF_FB + 4));
                po.clear();
                zero(oa);
                zero(ob);
                e = get_item_warp(sb, it + 1);
            }
            TS(0, 31);
        }
        TS_DUMP(0);
    } else {
        asm volatile("setmaxnreg.inc.sync.aligned.u32 240;");
        PendO<1> po;
        po.clear();
        float oa[80], ob[48];
        zero(oa);
        zero(ob);
        Ring r{0, 0};
        uint32_t phm = 0;
        uint32_t e = get_item_warp(sb, 0);
#pragma unroll 1
        for (int it = 0; e != 0; it++) {
            TS(1, 0);
            if (IT_TYPE(e) == IT_QA) {
                e = qa_item<1>(P, sb, r, phm, po, oa, ob, it);
            } else {
                if (IT_TYPE(e) == IT_OP) op_item<false>(e, sb, r, phm);
                else on_item<1>(e, sb, r, phm, lds_u(sb + OFF_FB + 4));
                po.clear();
                zero(oa);
                zero(ob);
                e = get_item_warp(sb, it + 1);
            }
            TS(1, 31);
        }
        TS_DUMP(1);
    }
}

typedef CUresult (*EncFn)(CUtensorMap*, CUtensorMapDataType, cuuint32_t, void*, const cuuint64_t*, const cuuint64_t*,
                          const cuuint32_t*, const cuuint32_t*, CUtensorMapInterleave, CUtensorMapSwizzle,
                          CUtensorMapL2promotion, CUtensorMapFloatOOBfill);

void make_map3(EncFn enc, CUtensorMap* m, void* p, uint64_t rows, uint64_t rowbytes, uint64_t nblk, uint32_t boxrows,
               uint32_t boxblk) {
    cuuint64_t dims[3] = {64, rows, nblk};
    cuuint64_t str[2] = {rowbytes, 128};
    cuuint32_t box[3] = {64, boxrows, boxblk};
    cuuint32_t es[3] = {1, 1, 1};
    enc(m, CU_TENSOR_MAP_DATA_TYPE_BFLOAT16, 3, p, dims, str, box, es, CU_TENSOR_MAP_INTERLEAVE_NONE,
        CU_TENSOR_MAP_SWIZZLE_128B, CU_TENSOR_MAP_L2_PROMOTION_NONE, CU_TENSOR_MAP_FLOAT_OOB_FILL_NONE);
}

constexpr int tune(const char*, int def) { return def; }

void build_schedule(Params& P) {
    const int mode = tune("MODE", 4), dmax = tune("DMAX", 27000), n0 = tune("N0", 0);
    const int hmin = tune("HMIN", 19), hmax = tune("HMAX", 25), off = tune("OFF", 0), slope = tune("SLOPE", 1744);
    const int ng = tune("NG", 0), d0 = tune("D0", 0), nkeep = tune("NKEEP", 0), odmax = tune("ODMAX", 0);
    int u = 0;
    auto unit = [&]() {
        const uint32_t e = mk_item(IT_QA, u >> 9, u & 15, (u >> 4) & 31, 0, 0);
        u++;
        return e;
    };
    int qa[NCTA], nq = 0, op[NCTA], no = 0;
    for (int c = 0; c < NCTA; c++) {
        P.delay[c] = 0;
        for (int i = 0; i < NSTAT; i++) P.items[c][i] = 0;
        if (mode >= 3 && c < 128 && (c & 7) >= 6) op[no++] = c;
        else if (mode != 2 || (c & 3) == 0) qa[nq++] = c;
    }
    for (int t = 0; t < no; t++) {
        P.items[op[t]][0] = unit();
        P.items[op[t]][1] = mk_item(IT_OP, 0, t >> 1, 0, 32, t & 1);
        P.items[op[t]][2] = P.items[op[t]][3] = IT_DYN;
        P.delay[op[t]] = (t >> 1) * odmax / 16;
    }
    for (int k = 0; k < nq; k++) {
        const int c = qa[(k * 37) % nq];
        P.items[c][0] = unit();
        P.items[c][1] = P.items[c][2] = P.items[c][3] = IT_DYN;
        P.delay[c] = k < n0 ? 0 : (int)((long long)dmax * (k + 1 - n0) / (nq - n0));
        if (ng) P.delay[c] = d0 + (k * ng / nq) * (dmax / ng);
    }
    int H[16], pos[16];
    for (int b = 0; b < 16; b++) {
        H[b] = hmin + ((hmax - hmin) * b + 7) / 15;
        pos[b] = 1092 + off - H[b] * slope / 100;
        if (b < nkeep && no) {
            pos[b] = -1;
            P.items[op[30 - 2 * b]][2] = mk_item(IT_OP, 1, b, 0, H[b], 0, 1);
            P.items[op[31 - 2 * b]][2] = mk_item(IT_OP, 1, b, 0, H[b], 1, 1);
        }
    }
    int n = 0;
    const int uend = mode == 2 ? 8 * nq : 1024;
    while (u < uend) {
        for (int b = 0; b < 16 && no; b++)
            if (pos[b] == u) {
                P.list[n++] = mk_item(IT_OP, 1, b, 0, H[b], 0, 1);
                P.list[n++] = mk_item(IT_OP, 1, b, 0, H[b], 1, 1);
            }
        P.list[n++] = unit();
    }
    if (no)
        for (int k = 0; k < 80; k++) P.list[n++] = mk_item(IT_ON, 1, k / 5, H[k / 5], 32, k % 5);
    P.nlist = n;
}

}

extern "C" void kernel_launch(void* const* d_in, const int* in_sizes, int n_in, void* d_out, int out_size) {
    static Params P;
    static bool init = false;
    if (!init) {
        EncFn enc = nullptr;
        cudaDriverEntryPointQueryResult qr;
        cudaGetDriverEntryPoint("cuTensorMapEncodeTiled", (void**)&enc, cudaEnableDefault, &qr);
        for (int i = 0; i < 2; i++) {
            P.px[i] = (const __nv_bfloat16*)d_in[5 * i + 0];
            P.pk[i] = (const __nv_bfloat16*)d_in[5 * i + 1];
            P.pv[i] = (const __nv_bfloat16*)d_in[5 * i + 2];
            P.pwq[i] = (const __nv_bfloat16*)d_in[5 * i + 3];
            make_map3(enc, &P.x[i], d_in[5 * i + 0], 2560, 1280, 10, 160, 1);
            make_map3(enc, &P.k[i], d_in[5 * i + 1], 16 * 32 * 512, 384, 3, 64, 3);
            make_map3(enc, &P.v[i], d_in[5 * i + 2], 16 * 32 * 512, 384, 3, 64, 3);
            make_map3(enc, &P.wq[i], d_in[5 * i + 3], 640, 12288, 96, 64, 3);
            make_map3(enc, &P.wo[i], d_in[5 * i + 4], 6144, 1280, 10, 32, 5);
            make_map3(enc, &P.won[i], d_in[5 * i + 4], 6144, 1280, 10, 64, 2);
        }
        cuuint64_t dims[2] = {1280, 2560};
        cuuint64_t str[1] = {2560};
        cuuint32_t box[2] = {64, 160};
        cuuint32_t es[2] = {1, 1};
        enc(&P.out, CU_TENSOR_MAP_DATA_TYPE_BFLOAT16, 2, d_out, dims, str, box, es, CU_TENSOR_MAP_INTERLEAVE_NONE,
            CU_TENSOR_MAP_SWIZZLE_128B, CU_TENSOR_MAP_L2_PROMOTION_NONE, CU_TENSOR_MAP_FLOAT_OOB_FILL_NONE);
        build_schedule(P);
        cudaFuncSetAttribute(fused_kernel, cudaFuncAttributeMaxDynamicSharedMemorySize, SMEM_LAUNCH);
        init = true;
    }
    fused_kernel<<<NCTA, 384, SMEM_LAUNCH>>>(P);
}
```

```cpp
#include <cuda_runtime.h>
#include <cuda.h>
#include <cuda_bf16.h>
#include <stdint.h>

namespace {

constexpr int NCTA = 132;
constexpr int MAXI = 16;
constexpr int NSTAT = 4;
constexpr uint32_t IT_DYN = 0xffffffffu;
constexpr int SLOT = 24576;
constexpr int NSLOT = 5;
constexpr int XS = 20480;
constexpr int OFF_R = 0;
constexpr int OFF_RING = 5 * XS;
constexpr int OFF_MISC = OFF_RING + NSLOT * SLOT;
constexpr int OFF_LX = OFF_MISC;
constexpr int OFF_LINV = OFF_LX + 2560;
constexpr int OFF_FB = OFF_LINV + 640;
constexpr int OFF_GM = OFF_FB + 16;
constexpr int OFF_BAR = OFF_GM + 16;
constexpr int BAR_RFULL = OFF_BAR;
constexpr int BAR_REMPTY = BAR_RFULL + 40;
constexpr int BAR_XFULL = BAR_REMPTY + 40;
constexpr int BAR_XEMPTY = BAR_XFULL + 40;
constexpr int BAR_ITEM = BAR_XEMPTY + 40;
constexpr int OFF_ITEM = BAR_ITEM + MAXI * 8;
constexpr int SMEM_BYTES = OFF_ITEM + MAXI * 4;
static_assert(SMEM_BYTES <= 232448, "smem");

constexpr int NB_W = 1  , NB_PFULL = 3  , NB_VOTE = 5  , NB_Q2 = 7, NB_SDONE = 8, NB_PDONE = 9,
              NB_L = 10, NB_REF = 11, NB_ODONE = 12, NB_OPEND = 13, NB_LX = 14, NB_Q01 = 15, NB_QK = 0  ;

constexpr uint32_t IT_QA = 1, IT_OP = 2, IT_ON = 3;
__host__ __device__ constexpr uint32_t mk_item(uint32_t type, uint32_t br, uint32_t b, uint32_t h0, uint32_t h1, uint32_t half,
                                               uint32_t part = 0) {
    return type | (br << 2) | (b << 3) | (h0 << 7) | (h1 << 13) | (half << 19) | (part << 22);
}
#define IT_TYPE(e) ((e) & 3u)
#define IT_BR(e) (((e) >> 2) & 1u)
#define IT_B(e) (((e) >> 3) & 15u)
#define IT_H0(e) (((e) >> 7) & 63u)
#define IT_H1(e) (((e) >> 13) & 63u)
#define IT_HALF(e) (((e) >> 19) & 7u)
#define IT_PART(e) (((e) >> 22) & 1u)

struct Params {
    CUtensorMap x[2], wq[2], k[2], v[2], wo[2], won[2], out;
    const __nv_bfloat16 *px[2], *pwq[2], *pk[2], *pv[2];
    uint32_t items[NCTA][NSTAT];
    uint32_t delay[NCTA];
    uint32_t nlist;
    uint32_t list[1024];
};

constexpr int OUNIT = 61440;
__device__ __align__(1024) unsigned char g_ostash[(size_t)1024 * OUNIT];
__device__ unsigned int g_flag[1024];
__device__ float4 g_part[2 * 16 * 10 * 2560];
__device__ unsigned int g_pflag[64];
#define ORING 64
__device__ __forceinline__ uint32_t ostash_off(uint32_t br, uint32_t b, uint32_t h) {
    return (((br * 32 + h) % ORING) * 16 + b) * OUNIT;
}
__device__ __forceinline__ unsigned char* ostash(uint32_t br, uint32_t b, uint32_t h) { return g_ostash + ostash_off(br, b, h); }
__device__ unsigned int g_epoch[NCTA];
__device__ unsigned int g_ticket[2];

constexpr int SMEM_LAUNCH = SMEM_BYTES;
#define TS(role, idx)
#define TS_DUMP(role)
#define TSD(role, idx)

#define POL_W 2
#define POL_X 2
#define POL_O 2
template <int M>
__device__ __forceinline__ uint64_t mkpol() {
    uint64_t p;
    if (M == 0) asm volatile("createpolicy.fractional.L2::evict_normal.b64 %0, 1.0;" : "=l"(p));
    if (M == 1) asm volatile("createpolicy.fractional.L2::evict_first.b64 %0, 1.0;" : "=l"(p));
    if (M == 2) asm volatile("createpolicy.fractional.L2::evict_unchanged.b64 %0, 1.0;" : "=l"(p));
    if (M == 3) asm volatile("createpolicy.fractional.L2::evict_normal.L2::evict_unchanged.b64 %0, 0.25;" : "=l"(p));
    return p;
}
#define STSM_W 1
#define XLATE 2
#define PV0FIRST 1
#define QST0 2
#define QST1 2
#define QHOLD 7
constexpr float SM_C = 0.07216878364870322f * 1.4426950408889634f;

__device__ __forceinline__ uint32_t tid_now() {
    uint32_t t;
    asm volatile("mov.u32 %0, %%tid.x;" : "=r"(t));
    return t;
}
__device__ __forceinline__ void mbar_init(uint32_t a, uint32_t c) {
    asm volatile("mbarrier.init.shared::cta.b64 [%0], %1;" ::"r"(a), "r"(c) : "memory");
}
__device__ __forceinline__ void mbar_expect(uint32_t a, uint32_t b) {
    asm volatile("mbarrier.arrive.expect_tx.shared::cta.b64 _, [%0], %1;" ::"r"(a), "r"(b) : "memory");
}
template <int CNT = 1>
__device__ __forceinline__ void mbar_arrive_warp(uint32_t a) {
    if (CNT == 1)
        asm volatile("{\n.reg .pred p;\nelect.sync _|p, 0xffffffff;\n@p mbarrier.arrive.shared::cta.b64 _, [%0];\n}" ::"r"(a) : "memory");
    else
        asm volatile(
            "{\n.reg .pred p;\nelect.sync _|p, 0xffffffff;\n@p mbarrier.arrive.shared::cta.b64 _, [%0];\n"
            "@p mbarrier.arrive.shared::cta.b64 _, [%0];\n}" ::"r"(a)
            : "memory");
}
template <int CNT = 1>
__device__ __forceinline__ void mbar_arrive_warp_if(uint32_t a, bool cond) {
    if (CNT == 1)
        asm volatile(
            "{\n.reg .pred p, c;\nelect.sync _|p, 0xffffffff;\nsetp.ne.and.u32 c, %1, 0, p;\n"
            "@c mbarrier.arrive.shared::cta.b64 _, [%0];\n}" ::"r"(a), "r"((uint32_t)cond)
            : "memory");
    else
        asm volatile(
            "{\n.reg .pred p, c;\nelect.sync _|p, 0xffffffff;\nsetp.ne.and.u32 c, %1, 0, p;\n"
            "@c mbarrier.arrive.shared::cta.b64 _, [%0];\n@c mbarrier.arrive.shared::cta.b64 _, [%0];\n}" ::"r"(a), "r"((uint32_t)cond)
            : "memory");
}
__device__ __forceinline__ uint32_t deadline() {
    uint32_t c;
    asm volatile("mov.u32 %0, %%clock_hi;" : "=r"(c));
    return c + 4;
}
__device__ __forceinline__ void mbar_wait(uint32_t a, uint32_t ph, uint32_t dl) {
    asm volatile(
        "{\n.reg .pred p;\n.reg .u32 m;\n"
        "LOOP:\n"
        "mbarrier.try_wait.parity.shared::cta.b64 p, [%0], %1;\n"
        "@p bra DONE;\n"
        "mov.u32 m, %%clock_hi;\n"
        "setp.ne.u32 p, m, %2;\n"
        "@p bra LOOP;\n"
        "trap;\n"
        "DONE:\n}" ::"r"(a), "r"(ph), "r"(dl)
        : "memory");
}
template <int ID, int CNT>
__device__ __forceinline__ void nb_sync() { asm volatile("bar.sync %0, %1;" ::"n"(ID), "n"(CNT) : "memory"); }
template <int ID, int CNT>
__device__ __forceinline__ void nb_arrive() { asm volatile("bar.arrive %0, %1;" ::"n"(ID), "n"(CNT) : "memory"); }
__device__ __forceinline__ void fence_async_smem() { asm volatile("fence.proxy.async.shared::cta;" ::: "memory"); }

__device__ __forceinline__ void tma3(uint32_t dst, const CUtensorMap* m, int c1, int c2, uint32_t bar, uint64_t pol) {
    asm volatile(
        "cp.async.bulk.tensor.3d.shared::cluster.global.mbarrier::complete_tx::bytes.L2::cache_hint [%0], [%1, {%3,%4,%5}], [%2], %6;" ::"r"(dst),
        "l"(m), "r"(bar), "r"(0), "r"(c1), "r"(c2), "l"(pol)
        : "memory");
}
__device__ __forceinline__ void bulk_load(uint32_t dst, const void* src, uint32_t bytes, uint32_t bar, uint64_t pol) {
    asm volatile("cp.async.bulk.shared::cluster.global.mbarrier::complete_tx::bytes.L2::cache_hint [%0], [%1], %2, [%3], %4;" ::"r"(dst),
                 "l"(src), "r"(bytes), "r"(bar), "l"(pol)
                 : "memory");
}
__device__ __forceinline__ void wg_fence() { asm volatile("wgmma.fence.sync.aligned;" ::: "memory"); }
__device__ __forceinline__ void wg_commit() { asm volatile("wgmma.commit_group.sync.aligned;" ::: "memory"); }
template <int N>
__device__ __forceinline__ void wg_wait() { asm volatile("wgmma.wait_group.sync.aligned %0;" ::"n"(N) : "memory"); }

#define RW80(c, d) c(d[0]), c(d[1]), c(d[2]), c(d[3]), c(d[4]), c(d[5]), c(d[6]), c(d[7]), c(d[8]), c(d[9]), c(d[10]), c(d[11]), c(d[12]), c(d[13]), c(d[14]), c(d[15]), c(d[16]), c(d[17]), c(d[18]), c(d[19]), c(d[20]), c(d[21]), c(d[22]), c(d[23]), c(d[24]), c(d[25]), c(d[26]), c(d[27]), c(d[28]), c(d[29]), c(d[30]), c(d[31]), c(d[32]), c(d[33]), c(d[34]), c(d[35]), c(d[36]), c(d[37]), c(d[38]), c(d[39]), c(d[40]), c(d[41]), c(d[42]), c(d[43]), c(d[44]), c(d[45]), c(d[46]), c(d[47]), c(d[48]), c(d[49]), c(d[50]), c(d[51]), c(d[52]), c(d[53]), c(d[54]), c(d[55]), c(d[56]), c(d[57]), c(d[58]), c(d[59]), c(d[60]), c(d[61]), c(d[62]), c(d[63]), c(d[64]), c(d[65]), c(d[66]), c(d[67]), c(d[68]), c(d[69]), c(d[70]), c(d[71]), c(d[72]), c(d[73]), c(d[74]), c(d[75]), c(d[76]), c(d[77]), c(d[78]), c(d[79])
#define RW48(c, d) c(d[0]), c(d[1]), c(d[2]), c(d[3]), c(d[4]), c(d[5]), c(d[6]), c(d[7]), c(d[8]), c(d[9]), c(d[10]), c(d[11]), c(d[12]), c(d[13]), c(d[14]), c(d[15]), c(d[16]), c(d[17]), c(d[18]), c(d[19]), c(d[20]), c(d[21]), c(d[22]), c(d[23]), c(d[24]), c(d[25]), c(d[26]), c(d[27]), c(d[28]), c(d[29]), c(d[30]), c(d[31]), c(d[32]), c(d[33]), c(d[34]), c(d[35]), c(d[36]), c(d[37]), c(d[38]), c(d[39]), c(d[40]), c(d[41]), c(d[42]), c(d[43]), c(d[44]), c(d[45]), c(d[46]), c(d[47])
#define RW32(c, d) c(d[0]), c(d[1]), c(d[2]), c(d[3]), c(d[4]), c(d[5]), c(d[6]), c(d[7]), c(d[8]), c(d[9]), c(d[10]), c(d[11]), c(d[12]), c(d[13]), c(d[14]), c(d[15]), c(d[16]), c(d[17]), c(d[18]), c(d[19]), c(d[20]), c(d[21]), c(d[22]), c(d[23]), c(d[24]), c(d[25]), c(d[26]), c(d[27]), c(d[28]), c(d[29]), c(d[30]), c(d[31])

__device__ __forceinline__ void reg_fence(float (&d)[80]) { asm volatile("" : RW80("+f", d)::"memory"); }
__device__ __forceinline__ void reg_fence(float (&d)[48]) { asm volatile("" : RW48("+f", d)::"memory"); }
__device__ __forceinline__ void reg_fence(float (&d)[32]) { asm volatile("" : RW32("+f", d)::"memory"); }

template <int NR>
__device__ __forceinline__ void zero(float (&d)[NR]) {
#pragma unroll
    for (int i = 0; i < NR; i++) d[i] = 0.f;
}

constexpr uint32_t HI_SW128 = (1024u >> 4) | (1u << 30);
constexpr uint32_t HI_OST = (2560u >> 4) | (2u << 30);
constexpr uint32_t LO_LBO1 = (1u << 16);
constexpr uint32_t LO_OST = ((512u >> 4) << 16);

template <int TA, int TB, uint32_t HIB, int ACC>
__device__ __forceinline__ void wgmma(float (&d)[80], uint32_t loA, uint32_t loB) {
#define WG_ASM(SD)                                                          \
    "{\n.reg .b64 da, db;\nmov.b64 da, {%80, %82};\nmov.b64 db, {%81, %83};\n" \
    "wgmma.mma_async.sync.aligned.m64n160k16.f32.bf16.bf16 "               \
    "{%0,%1,%2,%3,%4,%5,%6,%7,%8,%9,%10,%11,%12,%13,%14,%15,%16,%17,%18,%19,%20,%21,%22,%23,%24,%25,%26,%27,%28,%29,%30,%31,%32,%33,%34,%35,%36,%37,%38,%39,%40,%41,%42,%43,%44,%45,%46,%47,%48,%49,%50,%51,%52,%53,%54,%55,%56,%57,%58,%59,%60,%61,%62,%63,%64,%65,%66,%67,%68,%69,%70,%71,%72,%73,%74,%75,%76,%77,%78,%79}, da, db, " SD ", 1, 1, %84, %85;\n}"
    if constexpr (ACC == 2)
        asm volatile(WG_ASM("0") : RW80("+f", d) : "r"(loA), "r"(loB), "n"(HI_SW128), "n"(HIB), "n"(TA), "n"(TB));
    else if constexpr (ACC == 1)
        asm volatile(WG_ASM("1") : RW80("+f", d) : "r"(loA), "r"(loB), "n"(HI_SW128), "n"(HIB), "n"(TA), "n"(TB));
    else
        asm volatile(WG_ASM("0") : RW80("=f", d) : "r"(loA), "r"(loB), "n"(HI_SW128), "n"(HIB), "n"(TA), "n"(TB));
#undef WG_ASM
}
template <int TA, int TB, uint32_t HIB, int ACC>
__device__ __forceinline__ void wgmma(float (&d)[48], uint32_t loA, uint32_t loB) {
#define WG_ASM(SD)                                                          \
    "{\n.reg .b64 da, db;\nmov.b64 da, {%48, %50};\nmov.b64 db, {%49, %51};\n" \
    "wgmma.mma_async.sync.aligned.m64n96k16.f32.bf16.bf16 "               \
    "{%0,%1,%2,%3,%4,%5,%6,%7,%8,%9,%10,%11,%12,%13,%14,%15,%16,%17,%18,%19,%20,%21,%22,%23,%24,%25,%26,%27,%28,%29,%30,%31,%32,%33,%34,%35,%36,%37,%38,%39,%40,%41,%42,%43,%44,%45,%46,%47}, da, db, " SD ", 1, 1, %52, %53;\n}"
    if constexpr (ACC == 1)
        asm volatile(WG_ASM("1") : RW48("+f", d) : "r"(loA), "r"(loB), "n"(HI_SW128), "n"(HIB), "n"(TA), "n"(TB));
    else
        asm volatile(WG_ASM("0") : RW48("=f", d) : "r"(loA), "r"(loB), "n"(HI_SW128), "n"(HIB), "n"(TA), "n"(TB));
#undef WG_ASM
}
template <int TA, int TB, uint32_t HIB, int ACC>
__device__ __forceinline__ void wgmma(float (&d)[32], uint32_t loA, uint32_t loB) {
#define WG_ASM(SD)                                                          \
    "{\n.reg .b64 da, db;\nmov.b64 da, {%32, %34};\nmov.b64 db, {%33, %35};\n" \
    "wgmma.mma_async.sync.aligned.m64n64k16.f32.bf16.bf16 "               \
    "{%0,%1,%2,%3,%4,%5,%6,%7,%8,%9,%10,%11,%12,%13,%14,%15,%16,%17,%18,%19,%20,%21,%22,%23,%24,%25,%26,%27,%28,%29,%30,%31}, da, db, " SD ", 1, 1, %36, %37;\n}"
    if constexpr (ACC == 1)
        asm volatile(WG_ASM("1") : RW32("+f", d) : "r"(loA), "r"(loB), "n"(HI_SW128), "n"(HIB), "n"(TA), "n"(TB));
    else
        asm volatile(WG_ASM("0") : RW32("=f", d) : "r"(loA), "r"(loB), "n"(HI_SW128), "n"(HIB), "n"(TA), "n"(TB));
#undef WG_ASM
}

__device__ __forceinline__ uint32_t pack_bf16(float lo, float hi) {
    uint32_t r;
    asm("cvt.rn.bf16x2.f32 %0, %1, %2;" : "=r"(r) : "f"(hi), "f"(lo));
    return r;
}
__device__ __forceinline__ float ex2(float x) {
    float r;
    asm("ex2.approx.ftz.f32 %0, %1;" : "=f"(r) : "f"(x));
    return r;
}
__device__ __forceinline__ void stsm4t(uint32_t a, uint32_t r0, uint32_t r1, uint32_t r2, uint32_t r3) {
    asm volatile("stmatrix.sync.aligned.m8n8.x4.trans.shared.b16 [%0], {%1,%2,%3,%4};" ::"r"(a), "r"(r0), "r"(r1), "r"(r2), "r"(r3)
                 : "memory");
}
__device__ __forceinline__ uint32_t lds_u(uint32_t a) {
    uint32_t v;
    asm volatile("ld.shared.u32 %0, [%1];" : "=r"(v) : "r"(a) : "memory");
    return v;
}
__device__ __forceinline__ uint4 lds_u4(uint32_t a) {
    uint4 v;
    asm volatile("ld.shared.v4.u32 {%0,%1,%2,%3}, [%4];" : "=r"(v.x), "=r"(v.y), "=r"(v.z), "=r"(v.w) : "r"(a) : "memory");
    return v;
}
__device__ __forceinline__ float2 lds_f2(uint32_t a) {
    float2 v;
    asm volatile("ld.shared.v2.f32 {%0,%1}, [%2];" : "=f"(v.x), "=f"(v.y) : "r"(a) : "memory");
    return v;
}
__device__ __forceinline__ void sts_f(uint32_t a, float v) { asm volatile("st.shared.f32 [%0], %1;" ::"r"(a), "f"(v) : "memory"); }
__device__ __forceinline__ void sts_u(uint32_t a, uint32_t v) { asm volatile("st.shared.u32 [%0], %1;" ::"r"(a), "r"(v) : "memory"); }
__device__ __forceinline__ void sts_f2(uint32_t a, float x, float y) {
    asm volatile("st.shared.v2.f32 [%0], {%1,%2};" ::"r"(a), "f"(x), "f"(y) : "memory");
}

__device__ __forceinline__ void store_tile_t(const float (&d)[80], uint32_t addr) {
#pragma unroll
    for (int j = 0; j < 10; j++)
        stsm4t(addr + j * 2048, pack_bf16(d[8 * j], d[8 * j + 1]), pack_bf16(d[8 * j + 2], d[8 * j + 3]),
               pack_bf16(d[8 * j + 4], d[8 * j + 5]), pack_bf16(d[8 * j + 6], d[8 * j + 7]));
}
template <int NR>
__device__ __forceinline__ void store_out_tile(const float (&d)[NR], uint32_t base, uint32_t lane, uint32_t w) {
    const uint32_t mi = lane >> 3, i = lane & 7;
    const uint32_t chunk = 2 * w + (mi & 1);
    const uint32_t q0 = 8 * (i >> 1) + 2 * (mi >> 1) + (i & 1);
    const uint32_t a0 = base + q0 * 128 + ((chunk ^ (q0 & 7)) << 4);
    const uint32_t a1 = base + (q0 + 4) * 128 + ((chunk ^ ((q0 + 4) & 7)) << 4);
#pragma unroll
    for (int j = 0; j < NR / 8; j++)
        stsm4t(((j & 1) ? a1 : a0) + (j >> 1) * 4096, pack_bf16(d[8 * j], d[8 * j + 1]), pack_bf16(d[8 * j + 2], d[8 * j + 3]),
               pack_bf16(d[8 * j + 4], d[8 * j + 5]), pack_bf16(d[8 * j + 6], d[8 * j + 7]));
}

struct TrueT { static constexpr bool value = true; };
struct FalseT { static constexpr bool value = false; };

template <int V>
struct IntT { static constexpr int value = V; };

__device__ __forceinline__ uint32_t get_item(uint32_t sb, int it, uint32_t dl) {
    mbar_wait(sb + BAR_ITEM + it * 8, 0, dl);
    return lds_u(sb + OFF_ITEM + it * 4);
}
__device__ __forceinline__ uint32_t get_item_warp(uint32_t sb, int it, uint32_t dl) {
    return __shfl_sync(0xffffffffu, get_item(sb, it, dl), 0);
}

struct Ring {
    uint32_t slot, ph, dl;
    __device__ __forceinline__ void adv(uint32_t k) {
        slot += k;
        if (slot >= NSLOT) { slot -= NSLOT; ph ^= 1; }
    }
};

template <int K>
__device__ __forceinline__ void qk_step(float (&s)[80], uint32_t loK, uint32_t loQ) {
    wgmma<0, 0, HI_SW128, K != 0>(s, loK + (K >> 2) * (8192 >> 4) + (K & 3) * 2, loQ + (K >> 2) * (XS >> 4) + (K & 3) * 2);
}
template <int K0, int K1>
__device__ __forceinline__ void qk_steps(float (&s)[80], uint32_t loK, uint32_t loQ) {
    if constexpr (K0 < K1) {
        qk_step<K0>(s, loK, loQ);
        qk_steps<K0 + 1, K1>(s, loK, loQ);
    }
}
__device__ __forceinline__ uint32_t add_bf2(uint32_t a, uint32_t b) {
    uint32_t r;
    asm("add.rn.bf16x2 %0, %1, %2;" : "=r"(r) : "r"(a), "r"(b));
    return r;
}
__device__ __forceinline__ uint32_t fma_bf2(uint32_t a, uint32_t b, uint32_t c) {
    uint32_t r;
    asm("fma.rn.bf16x2 %0, %1, %2, %3;" : "=r"(r) : "r"(a), "r"(b), "r"(c));
    return r;
}
template <int J>
__device__ __forceinline__ void exp_block(const float (&s)[80], uint32_t (&k)[40], uint32_t pa, float mref) {
    if constexpr (J < 10) {
#pragma unroll
        for (int i = 4 * J; i < 4 * J + 4; i++)
            k[i] = pack_bf16(ex2(fmaf(s[2 * i], SM_C, -mref)), ex2(fmaf(s[2 * i + 1], SM_C, -mref)));
#pragma unroll
        for (int i = 0; i < 4; i++)
            asm volatile("stmatrix.sync.aligned.m8n8.x1.trans.shared.b16 [%0], {%1};" ::"r"(((i & 1) ? pa ^ 16 : pa) + J * 2048 + (i >> 1) * 1024),
                         "r"(k[4 * J + i])
                         : "memory");
        exp_block<J + 1>(s, k, pa, mref);
    }
}
__device__ __forceinline__ void sum_block(const uint32_t (&k)[40], float (&l)[10], uint32_t lane) {
    const bool b4 = lane & 16, b3 = lane & 8;
    uint32_t ps[20], t[10];
#pragma unroll
    for (int j = 0; j < 20; j++) ps[j] = add_bf2(k[2 * j], k[2 * j + 1]);
#pragma unroll
    for (int j = 0; j < 10; j++)
        t[j] = add_bf2(b4 ? ps[2 * j + 1] : ps[2 * j], __shfl_xor_sync(0xffffffffu, b4 ? ps[2 * j] : ps[2 * j + 1], 16));
#pragma unroll
    for (int i = 0; i < 5; i++) {
        const uint32_t a = b3 ? t[i + 5] : t[i], b = __shfl_xor_sync(0xffffffffu, b3 ? t[i] : t[i + 5], 8);
        l[2 * i] += __uint_as_float(a << 16) + __uint_as_float(b << 16);
        l[2 * i + 1] += __uint_as_float(a & 0xffff0000u) + __uint_as_float(b & 0xffff0000u);
    }
}
template <bool ADD>
__device__ __forceinline__ void sum_store(const float (&l)[10], uint32_t lane, uint32_t lxa) {
    const bool b2 = lane & 4;
    float t[5];
#pragma unroll
    for (int i = 0; i < 5; i++) t[i] = ADD ? __uint_as_float(lds_u(lxa + i * 64)) : 0.f;
#pragma unroll
    for (int i = 0; i < 5; i++)
        sts_f(lxa + i * 64, t[i] + (b2 ? l[2 * i + 1] : l[2 * i]) + __shfl_xor_sync(0xffffffffu, b2 ? l[2 * i] : l[2 * i + 1], 4));
}

__device__ __forceinline__ void fallback_unit(const Params& P, uint32_t e, uint32_t tid) {
    const uint32_t lane = tid & 31, br = IT_BR(e), b = IT_B(e), h = IT_H0(e);
    const __nv_bfloat162* wq = (const __nv_bfloat162*)(P.pwq[br] + h * 192) + lane;
    const __nv_bfloat162* kp = (const __nv_bfloat162*)(P.pk[br] + (size_t)(b * 32 + h) * 512 * 192) + lane;
    const __nv_bfloat162* vp = (const __nv_bfloat162*)(P.pv[br] + (size_t)(b * 32 + h) * 512 * 192) + lane;
#pragma unroll 1
    for (uint32_t qi = 0; qi < 40; qi++) {
        const uint32_t q = 4 * qi + (tid >> 5);
        const __nv_bfloat16* xr = P.px[br] + (size_t)(b * 160 + q) * 640;
        float a[6] = {0.f, 0.f, 0.f, 0.f, 0.f, 0.f};
#pragma unroll 2
        for (int k = 0; k < 640; k++) {
            const float xv = __bfloat162float(xr[k]);
#pragma unroll
            for (int i = 0; i < 3; i++) {
                const float2 wv = __bfloat1622float2(wq[(size_t)k * 3072 + i * 32]);
                a[2 * i] = fmaf(xv, wv.x, a[2 * i]);
                a[2 * i + 1] = fmaf(xv, wv.y, a[2 * i + 1]);
            }
        }
#pragma unroll
        for (int i = 0; i < 6; i++) a[i] = __bfloat162float(__float2bfloat16(a[i]));
        auto score = [&](int key) {
            float d = 0.f;
#pragma unroll
            for (int i = 0; i < 3; i++) {
                const float2 kv = __bfloat1622float2(kp[key * 96 + i * 32]);
                d = fmaf(a[2 * i], kv.x, fmaf(a[2 * i + 1], kv.y, d));
            }
#pragma unroll
            for (int o = 16; o > 0; o >>= 1) d += __shfl_xor_sync(0xffffffffu, d, o);
            return d;
        };
        float m = -INFINITY, o[6] = {0.f, 0.f, 0.f, 0.f, 0.f, 0.f}, sum = 0.f;
#pragma unroll 1
        for (int n = 0; n < 1024; n++) {
            const int key = n & 511;
            const float d = score(key);
            if (n < 512) {
                m = fmaxf(m, d);
            } else {
                const float p = ex2((d - m) * SM_C);
                sum += p;
#pragma unroll
                for (int i = 0; i < 3; i++) {
                    const float2 vv = __bfloat1622float2(vp[key * 96 + i * 32]);
                    o[2 * i] = fmaf(p, vv.x, o[2 * i]);
                    o[2 * i + 1] = fmaf(p, vv.y, o[2 * i + 1]);
                }
            }
        }
        const float inv = __fdividef(1.f, sum);
        __nv_bfloat16* op = (__nv_bfloat16*)ostash(br, b, h) + (q >> 5) * 256 + 2 * ((q & 31) >> 3) + (q & 1);
#pragma unroll
        for (int i = 0; i < 6; i++) {
            const uint32_t d = (i >> 1) * 64 + 2 * lane + (i & 1);
            op[(d >> 3) * 1280 + (d & 7) * 32 + ((((q & 7) >> 1) ^ ((d & 7) >> 1)) << 3)] = __float2bfloat16(o[i] * inv);
        }
    }
}

template <int W>
struct PendO {
    static constexpr int N = W == 0 ? 56 : 64;
    uint32_t v[N];
    unsigned char* gp;
    uint32_t pend, sig;
    static __device__ __forceinline__ void scale(uint32_t& x, uint32_t hi, uint32_t lo) {
        asm("{\n.reg .b32 t;\nmul.rn.bf16x2 t, %0, %2;\nfma.rn.bf16x2 %0, %0, %1, t;\n}" : "+r"(x) : "r"(hi), "r"(lo));
    }
    template <int I, int OFF>
    __device__ __forceinline__ void put(const uint4& a, const uint4& b) {
        scale(v[I], a.x, a.y);
        scale(v[I + 1], a.z, a.w);
        scale(v[I + 2], b.x, b.y);
        scale(v[I + 3], b.z, b.w);
        asm volatile("{\n.reg .pred p;\nsetp.ne.u32 p, %6, 0;\n@p st.global.v4.b32 [%0+%5], {%1,%2,%3,%4};\n}" ::"l"(gp), "r"(v[I]),
                     "r"(v[I + 1]), "r"(v[I + 2]), "r"(v[I + 3]), "n"(OFF), "r"(pend)
                     : "memory");
    }
    __device__ __forceinline__ void verdict(const Params& P, uint32_t sb, int ie) {
        if (sig) {
            nb_sync<NB_VOTE + W, 160>();
            pend = !__any_sync(0xffffffffu, lds_u(sb + OFF_FB) != 0);
            if (W == 1 && !pend) {
                fallback_unit(P, lds_u(sb + OFF_ITEM + ie * 4), tid_now() & 127);
                __syncwarp();
            }
        }
    }
    template <int G>
    __device__ __forceinline__ void step(uint32_t sb) {
        const uint32_t la = sb + OFF_LINV + G * 128 + (threadIdx.x & 3) * 32;
        const uint4 a = lds_u4(la), b = lds_u4(la + 16);
        put<8 * G, W * XS + G * 512>(a, b);
        put<8 * G + 4, W * XS + G * 512 + 2560>(a, b);
        if constexpr (W == 0 ? G >= 3 : G < 3) {
            put<40 + 8 * (W == 0 ? G - 3 : G), 2 * XS + G * 512>(a, b);
            put<44 + 8 * (W == 0 ? G - 3 : G), 2 * XS + G * 512 + 2560>(a, b);
        }
        if (G == 4 && sig) nb_arrive<NB_ODONE, 288>();
    }
    __device__ __forceinline__ void clear() {
#pragma unroll
        for (int i = 0; i < N; i++) v[i] = 0;
        gp = nullptr;
        pend = 0;
        sig = 0;
    }
};

template <int W, int KK>
__device__ __forceinline__ void qproj(float (&q0)[80], float (&q1)[80], uint32_t sb, Ring& r, uint32_t pslot, uint32_t phm,
                                      PendO<W>& po, const Params& P, int it) {
    const uint32_t loR = ((sb + OFF_R) >> 4) | LO_LBO1;
    const uint32_t loRing = ((sb + OFF_RING) >> 4) | LO_LBO1;
    auto ready = [&](int k) {
        mbar_wait(sb + BAR_RFULL + r.slot * 8, r.ph, r.dl);
        mbar_wait(sb + BAR_XFULL + (k % 5) * 8, ((phm >> (k % 5)) ^ (k / 5)) & 1, r.dl);
    };
    auto release = [&]() {
        if (KK > 0) {
            wg_wait<1>();
            mbar_arrive_warp(sb + BAR_REMPTY + pslot * 8);
            if (KK <= 5) mbar_arrive_warp(sb + (BAR_XEMPTY + (KK - 1) * 8));
        }
    };
    if (KK == 0) ready(0);
    if (W == 1 && KK == QHOLD) nb_sync<NB_SDONE, 256>();
    const uint32_t a = loRing + r.slot * (SLOT >> 4) + (W == 0 ? 0 : 1024), b = loR + (KK % 5) * (XS >> 4);
    wg_fence();
    wgmma<1, 0, HI_SW128, KK != 0>(q0, a, b);
    if (W == 0) wgmma<1, 0, HI_SW128, KK != 0>(q1, a + 512, b);
#pragma unroll
    for (int k = 1; k < 4; k++) {
        wgmma<1, 0, HI_SW128, true>(q0, a + k * 128, b + k * 2);
        if (W == 0) wgmma<1, 0, HI_SW128, true>(q1, a + 512 + k * 128, b + k * 2);
    }
    wg_commit();
    const uint32_t cslot = r.slot;
    r.adv(1);
    if (W == 0 || KK < QHOLD) release();
    if (KK < 9) ready(KK + 1);
    if (W == 1 && KK >= QHOLD) release();
    if (W == 1 && KK == 7) nb_arrive<NB_PDONE, 256>();
    if (KK == QST0) po.verdict(P, sb, it - 1);
    if constexpr (KK >= QST0 && KK < QST0 + 5) po.template step<KK - QST0>(sb);
    if constexpr (KK < 9) {
        qproj<W, KK + 1>(q0, q1, sb, r, cslot, phm, po, P, it);
    } else {
        if (W == 0) nb_arrive<NB_SDONE, 256>();
        wg_wait<0>();
        reg_fence(q0);
        if (W == 0) reg_fence(q1);
        mbar_arrive_warp(sb + BAR_REMPTY + cslot * 8);
    }
}

template <int NR>
__device__ __forceinline__ void opack(const float (&o)[NR], uint32_t* v) {
#pragma unroll
    for (int g = 0; g < NR / 16; g++)
#pragma unroll
        for (int hh = 0; hh < 2; hh++)
#pragma unroll
            for (int t = 0; t < 4; t++) v[8 * g + 4 * hh + t] = pack_bf16(o[16 * g + 4 * t + 2 * hh], o[16 * g + 4 * t + 2 * hh + 1]);
}

template <int NR>
__device__ __forceinline__ void dump_acc(const float (&c)[NR], float4* p) {
#pragma unroll
    for (int i = 0; i < NR / 4; i++) p[i * 128] = make_float4(c[4 * i], c[4 * i + 1], c[4 * i + 2], c[4 * i + 3]);
}
__device__ __forceinline__ void wait_flag(const unsigned int* f, uint32_t epoch) {
    uint32_t v, n = 0;
    do {
        asm volatile("ld.acquire.gpu.global.u32 %0, [%1];" : "=r"(v) : "l"(f) : "memory");
        if (++n > 0x1000000) __trap();
    } while (v != epoch);
}

template <bool IS_S>
__device__ __forceinline__ void op_item(uint32_t e, uint32_t sb, Ring& r, uint32_t& phm) {
    constexpr int T0 = IS_S ? 0 : 2;
    constexpr uint32_t BOFF = IS_S ? (3 * 512) >> 4 : 0;
    const uint32_t loRing = ((sb + OFF_RING) >> 4) | LO_LBO1;
    const uint32_t loO = ((sb + OFF_R) >> 4) | LO_OST;
    float c0[80], c1[80], c2[IS_S ? 32 : 48];
    const int T2 = 6 * (IT_H1(e) - IT_H0(e));
    uint32_t xs = 0;
    auto step = [&](auto first, uint32_t hf) {
        constexpr bool F = decltype(first)::value;
        if (hf == 0) {
            mbar_wait(sb + BAR_XFULL + xs * 8, (phm >> xs) & 1, r.dl);
            phm ^= 1u << xs;
        }
        mbar_wait(sb + BAR_RFULL + r.slot * 8, r.ph, r.dl);
        const uint32_t a = loRing + r.slot * (SLOT >> 4), b = loO + xs * (XS >> 4) + hf * 640;
        wg_fence();
        wgmma<1, 1, HI_OST, !F>(c0, a + T0 * 256, b);
        wgmma<1, 1, HI_OST, !F>(c1, a + T0 * 256 + 256, b);
        wgmma<1, 1, HI_OST, !F>(c2, a + 1024, b + BOFF);
        wgmma<1, 1, HI_OST, true>(c0, a + T0 * 256 + 128, b + 320);
        wgmma<1, 1, HI_OST, true>(c1, a + T0 * 256 + 384, b + 320);
        wgmma<1, 1, HI_OST, true>(c2, a + 1024 + 128, b + 320 + BOFF);
        wg_commit();
    };
    step(TrueT{}, 0);
#pragma unroll 1
    for (int t = 1; t < T2; t++) {
        const uint32_t pslot = r.slot, pxs = xs;
        r.adv(1);
        if ((t & 1) == 0 && ++xs == 5) xs = 0;
        step(FalseT{}, t & 1);
        wg_wait<1>();
        mbar_arrive_warp(sb + BAR_REMPTY + pslot * 8);
        if ((t & 1) == 0 && t + 8 < T2) mbar_arrive_warp(sb + BAR_XEMPTY + pxs * 8);
    }
    wg_wait<0>();
    reg_fence(c0);
    reg_fence(c1);
    reg_fence(c2);
    mbar_arrive_warp(sb + BAR_REMPTY + r.slot * 8);
    r.adv(1);
    if (IT_PART(e)) {
#pragma unroll
        for (int m = 0; m < 5; m++) mbar_arrive_warp(sb + BAR_XEMPTY + m * 8);
        float4* pp = g_part + (size_t)((IT_BR(e) * 16 + IT_B(e)) * 10 + IT_HALF(e) * 5) * 2560 + (tid_now() & 127);
        dump_acc(c0, pp + T0 * 2560);
        dump_acc(c1, pp + (T0 + 1) * 2560);
        dump_acc(c2, pp + 4 * 2560 + (IS_S ? 12 * 128 : 0));
    } else {
        nb_sync<NB_OPEND, 256>();
        const uint32_t tid = tid_now(), lane = tid & 31, w = (tid >> 5) & 3;
        store_out_tile(c0, sb + OFF_R + T0 * XS, lane, w);
        store_out_tile(c1, sb + OFF_R + (T0 + 1) * XS, lane, w);
        store_out_tile(c2, sb + OFF_R + 4 * XS + (IS_S ? 96 * 128 : 0), lane, w);
        fence_async_smem();
    }
    nb_arrive<NB_ODONE, 288>();
}

template <int W>
__device__ __forceinline__ void on_item(uint32_t e, uint32_t sb, Ring& r, uint32_t& phm, uint32_t epoch) {
    const uint32_t loRing = ((sb + OFF_RING) >> 4) | LO_LBO1;
    const uint32_t loO = ((sb + OFF_R) >> 4) | LO_OST;
    float c[80];
    const int T = 3 * (IT_H1(e) - IT_H0(e));
    uint32_t xs = 0;
    auto step = [&](auto first) {
        constexpr bool F = decltype(first)::value;
        mbar_wait(sb + BAR_XFULL + xs * 8, (phm >> xs) & 1, r.dl);
        phm ^= 1u << xs;
        mbar_wait(sb + BAR_RFULL + r.slot * 8, r.ph, r.dl);
        const uint32_t a = loRing + r.slot * (SLOT >> 4) + W * 512, b = loO + xs * (XS >> 4);
        wg_fence();
        wgmma<1, 1, HI_OST, !F>(c, a, b);
#pragma unroll
        for (int k = 1; k < 4; k++) wgmma<1, 1, HI_OST, true>(c, a + k * 128, b + k * 320);
        wg_commit();
    };
    auto run = [&](int t0, int t1) {
#pragma unroll 1
        for (int t = t0; t < t1; t++) {
            const uint32_t pslot = r.slot, pxs = xs;
            r.adv(1);
            if (++xs == 5) xs = 0;
            step(FalseT{});
            wg_wait<1>();
            mbar_arrive_warp(sb + BAR_REMPTY + pslot * 8);
            mbar_arrive_warp_if(sb + BAR_XEMPTY + pxs * 8, t + 4 < T);
        }
    };
    step(TrueT{});
    const int tm = T - 3;
    run(1, tm);
    float4 pv[20];
    {
        const uint32_t tile = 2 * IT_HALF(e) + W, bb = IT_BR(e) * 16 + IT_B(e);
        wait_flag(&g_pflag[bb * 2 + (tile >= 5)], epoch);
        const float4* pp = g_part + (size_t)(bb * 10 + tile) * 2560 + (tid_now() & 127);
#pragma unroll
        for (int i = 0; i < 20; i++) pv[i] = __ldcg(pp + i * 128);
    }
    run(tm, T);
    wg_wait<0>();
    reg_fence(c);
    mbar_arrive_warp(sb + BAR_REMPTY + r.slot * 8);
    r.adv(1);
    nb_sync<NB_OPEND, 256>();
#pragma unroll
    for (int i = 0; i < 20; i++) {
        c[4 * i] += pv[i].x;
        c[4 * i + 1] += pv[i].y;
        c[4 * i + 2] += pv[i].z;
        c[4 * i + 3] += pv[i].w;
    }
    const uint32_t tid = tid_now();
    store_out_tile(c, sb + OFF_R + W * XS, tid & 31, (tid >> 5) & 3);
    fence_async_smem();
    nb_arrive<NB_ODONE, 288>();
}

template <int W>
__device__ __forceinline__ uint32_t qa_item(const Params& P, uint32_t sb, Ring& r, uint32_t phm, PendO<W>& po, int it) {
    const uint32_t loR = ((sb + OFF_R) >> 4) | LO_LBO1;
    const uint32_t loRing = ((sb + OFF_RING) >> 4) | LO_LBO1;
    uint32_t lane, sta;
    {
        float q0[80], q1[80];
        qproj<W, 0>(q0, q1, sb, r, 0, phm, po, P, it);
        const uint32_t tid = tid_now();
        lane = tid & 31;
        sta = sb + OFF_R + (lane >> 4) * 1024 + (lane & 7) * 128 + (((((tid >> 4) & 6) + ((lane >> 3) & 1)) ^ (lane & 7)) << 4);
        TSD(W, 1);
        if (W == 0) {
            nb_sync<NB_PDONE, 256>();
            store_tile_t(q0, sta);
            store_tile_t(q1, sta + XS);
        } else {
            store_tile_t(q0, sta + 2 * XS);
        }
    }
    fence_async_smem();
    float s[80], oa[80], ob[W == 0 ? 32 : 48], l[10];
    zero(oa);
    zero(ob);
    zero(l);
    reg_fence(oa);
    reg_fence(ob);
    auto pv = [&](const Ring& rv, uint32_t buf) {
        mbar_wait(sb + BAR_RFULL + rv.slot * 8, rv.ph, rv.dl);
        const uint32_t a = loRing + rv.slot * (SLOT >> 4), b = loR + (3 + buf) * (XS >> 4);
        wg_fence();
#pragma unroll
        for (int k = 0; k < 4; k++) {
            wgmma<1, 0, HI_SW128, true>(oa, a + W * 512 + k * 128, b + k * 2);
            wgmma<1, 0, HI_SW128, true>(ob, a + 1024 + k * 128, b + (W == 0 ? (96 * 128) >> 4 : 0) + k * 2);
        }
        wg_commit();
    };
    float mref;
    uint32_t kslot, vslot;
    auto tail = [&](bool rel_other, int i) {
        uint32_t ps[40];
        exp_block<0>(s, ps, sta + (3 + W) * XS, mref);
        if (rel_other) {
            wg_wait<0>();
            mbar_arrive_warp(sb + BAR_REMPTY + vslot * 8);
            if (W == 1) mbar_arrive_warp_if(sb + BAR_XEMPTY + 24, i == 3);
        }
        fence_async_smem();
        nb_arrive<NB_PFULL + W, 256>();
        TSD(W, 6 + 5 * i);
        if (W == 1) {
            if (XLATE >= 2) mbar_arrive_warp_if<2>(sb + BAR_XEMPTY + 8, i == 3);
            if (XLATE >= 1) mbar_arrive_warp_if<2>(sb + BAR_XEMPTY + 16, i == 3);
        }
        if (rel_other || !PV0FIRST) {
            mbar_wait(sb + BAR_RFULL + r.slot * 8, r.ph, r.dl);
            sum_block(ps, l, lane);
        }
        TSD(W, 7 + 5 * i);
        nb_sync<NB_W + W, 128>();
        pv(r, W);
        if (!rel_other && PV0FIRST) sum_block(ps, l, lane);
        TSD(W, 8 + 5 * i);
    };
    if (W == 0) {
        sts_u(sb + OFF_GM + 4, r.slot);
        mbar_wait(sb + BAR_RFULL + r.slot * 8, r.ph, r.dl);
        nb_sync<NB_QK, 160>();
        TSD(W, 2);
        wg_fence();
        qk_steps<0, 8>(s, loRing + r.slot * (SLOT >> 4), loR);
        nb_sync<NB_Q2, 288>();
        qk_steps<8, 12>(s, loRing + r.slot * (SLOT >> 4), loR);
        wg_commit();
        nb_arrive<NB_Q01, 256>();
        TSD(W, 4);
        nb_sync<NB_REF, 160>();
        mref = __uint_as_float(lds_u(sb + OFF_GM));
        wg_wait<0>();
        reg_fence(s);
        mbar_arrive_warp<2>(sb + BAR_REMPTY + r.slot * 8);
        r.adv(2);
        TSD(W, 5);
        tail(false, 0);
    } else {
        nb_arrive<NB_Q2, 288>();
        TSD(W, 2);
        nb_sync<NB_Q01, 256>();
    }
#pragma unroll 1
    for (int i = (W == 0 ? 1 : 0); i < 4; i++) {
        const uint32_t pvslot = r.slot;
        r.adv(1);
        kslot = r.slot;
        mbar_wait(sb + BAR_RFULL + r.slot * 8, r.ph, r.dl);
        wg_fence();
        qk_steps<0, 12>(s, loRing + r.slot * (SLOT >> 4), loR);
        wg_commit();
        wg_wait<1>();
        mbar_arrive_warp_if(sb + BAR_REMPTY + pvslot * 8, W == 0 || i > 0);
        r.adv(1);
        vslot = r.slot;
        TSD(W, 4 + 5 * i);
        nb_sync<NB_PFULL + (W ^ 1), 256>();
        pv(r, W ^ 1);
        if (W == 1) mref = __uint_as_float(lds_u(sb + OFF_GM));
        wg_wait<1>();
        reg_fence(s);
        mbar_arrive_warp<2>(sb + BAR_REMPTY + kslot * 8);
        if (W == 1) {
            mbar_arrive_warp_if<2>(sb + BAR_XEMPTY + 0, i == 3);
            if (XLATE < 2) mbar_arrive_warp_if<2>(sb + BAR_XEMPTY + 8, i == 3);
            if (XLATE < 1) mbar_arrive_warp_if<2>(sb + BAR_XEMPTY + 16, i == 3);
        }
        r.adv(W == 1 && i == 3 ? 1 : 2);
        TSD(W, 5 + 5 * i);
        tail(true, i);
    }
    const uint32_t w = (tid_now() >> 5) & 3;
    const uint32_t lxa = sb + OFF_LX + w * 640 + (((lane & 8) ? 80 : 0) + ((lane >> 1) & 8) + 2 * (lane & 3) + ((lane >> 2) & 1)) * 4;
    const uint32_t e = lds_u(sb + OFF_ITEM + it * 4), nx = get_item_warp(sb, it + 1, r.dl);
    po.gp = ostash(IT_BR(e), IT_B(e), IT_H0(e)) + w * 5120 + (lane >> 2) * 64 + (((lane ^ (lane >> 3)) & 3) << 4);
    po.sig = 1;
    if (W == 0) {
        sum_store<false>(l, lane, lxa);
        nb_arrive<NB_LX, 256>();
        wg_wait<0>();
        mbar_arrive_warp(sb + BAR_REMPTY + r.slot * 8);
        mbar_arrive_warp(sb + BAR_XEMPTY + 24);
        r.adv(1);
        nb_sync<NB_PFULL + 1, 256>();
        pv(r, 1);
    } else {
        nb_sync<NB_LX, 256>();
        sum_store<true>(l, lane, lxa);
        nb_arrive<NB_L, 160>();
    }
    TSD(W, 24);
    wg_wait<0>();
    reg_fence(oa);
    reg_fence(ob);
    mbar_arrive_warp(sb + BAR_REMPTY + r.slot * 8);
    mbar_arrive_warp(sb + BAR_XEMPTY + 32);
    r.adv(1);
    opack(oa, po.v);
    opack(ob, po.v + 40);
    if (IT_TYPE(nx) != IT_QA) {
        po.verdict(P, sb, it);
        po.template step<0>(sb);
        po.template step<1>(sb);
        po.template step<2>(sb);
        po.template step<3>(sb);
        po.template step<4>(sb);
        po.sig = 0;
        po.pend = 0;
    }
    return nx;
}

__global__ void __launch_bounds__(384, 1) fused_kernel(const __grid_constant__ Params P) {
    extern __shared__ __align__(1024) unsigned char smem_raw[];
    const uint32_t sb = (uint32_t)__cvta_generic_to_shared(smem_raw);
    const uint32_t wgid = __shfl_sync(0xffffffffu, threadIdx.x >> 7, 0);
    const uint32_t cta = blockIdx.x;
    const uint32_t dl = deadline();

    uint32_t epoch = 0;
    if (wgid == 0) epoch = *(volatile unsigned int*)&g_epoch[cta] + 1;
    if (threadIdx.x == 0) {
        if (sb & 1023) __trap();
        sts_u(sb + OFF_FB + 4, epoch);
        for (int i = 0; i < NSLOT; i++) {
            mbar_init(sb + BAR_RFULL + i * 8, 1);
            mbar_init(sb + BAR_REMPTY + i * 8, 8);
            mbar_init(sb + BAR_XFULL + i * 8, 1);
            mbar_init(sb + BAR_XEMPTY + i * 8, 8);
        }
        for (int i = 0; i < MAXI; i++) mbar_init(sb + BAR_ITEM + i * 8, 1);
        asm volatile("fence.mbarrier_init.release.cluster;" ::: "memory");
        fence_async_smem();
    }
    __syncthreads();

    if (wgid == 0) {
        asm volatile("setmaxnreg.dec.sync.aligned.u32 24;");
        const uint32_t warp = __shfl_sync(0xffffffffu, threadIdx.x >> 5, 0);
        if (warp == 0) {
            if (threadIdx.x == 0) {
                *(volatile unsigned int*)&g_epoch[cta] = epoch;
                const uint64_t pol_first = mkpol<1>(), pol_norm = mkpol<POL_W>();
                if (cta == 0) *(volatile unsigned int*)&g_ticket[(epoch + 1) & 1] = 0;
                Ring r{0, 1, dl};
                {
                    const uint32_t d = P.delay[cta];
                    uint32_t t0, t1;
                    asm volatile("mov.u32 %0, %%clock;" : "=r"(t0));
                    do {
                        asm volatile("mov.u32 %0, %%clock;" : "=r"(t1));
                    } while (t1 - t0 < d);
                }
                uint32_t e = P.items[cta][0];
#pragma unroll 1
                for (int it = 0;; it++) {
                    sts_u(sb + OFF_ITEM + it * 4, e);
                    asm volatile("mbarrier.arrive.shared::cta.b64 _, [%0];" ::"r"(sb + BAR_ITEM + it * 8) : "memory");
                    if (e == 0) break;
                    uint32_t nx = P.items[cta][it + 1 < NSTAT ? it + 1 : NSTAT - 1];
                    if (IT_TYPE(e) == IT_ON || it + 2 == MAXI) nx = 0;
                    uint32_t tk = 0;
                    const uint32_t br = IT_BR(e);
                    if (IT_TYPE(e) == IT_QA) {
                        const uint32_t h = IT_H0(e);
#pragma unroll 1
                        for (int kk = 0; kk < 10; kk++) {
                            mbar_wait(sb + BAR_REMPTY + r.slot * 8, r.ph, r.dl);
                            mbar_expect(sb + BAR_RFULL + r.slot * 8, SLOT);
                            tma3(sb + OFF_RING + r.slot * SLOT, &P.wq[br], kk * 64, h * 3, sb + BAR_RFULL + r.slot * 8, pol_norm);
                            r.adv(1);
                        }
                        const int row0 = (IT_B(e) * 32 + h) * 512;
#pragma unroll 1
                        for (int n = 0; n < 16; n++) {
                            if (n == 13 && nx == IT_DYN) tk = atomicAdd(&g_ticket[epoch & 1], 1);
                            const bool isv = n == 15 || (n > 0 && !(n & 1));
                            const int j = n == 15 ? 7 : isv ? (n - 2) >> 1 : (n + 1) >> 1;
                            mbar_wait(sb + BAR_REMPTY + r.slot * 8, r.ph, r.dl);
                            mbar_expect(sb + BAR_RFULL + r.slot * 8, SLOT);
                            tma3(sb + OFF_RING + r.slot * SLOT, isv ? &P.v[br] : &P.k[br], row0 + j * 64, 0,
                                 sb + BAR_RFULL + r.slot * 8, pol_first);
                            r.adv(1);
                        }
                    } else {
                        const int r0 = IT_H0(e) * 192, r1 = IT_H1(e) * 192;
                        const bool wide = IT_TYPE(e) == IT_OP;
#pragma unroll 1
                        for (int row = r0; row < r1; row += wide ? 32 : 64) {
                            mbar_wait(sb + BAR_REMPTY + r.slot * 8, r.ph, r.dl);
                            mbar_expect(sb + BAR_RFULL + r.slot * 8, wide ? XS : 16384);
                            tma3(sb + OFF_RING + r.slot * SLOT, wide ? &P.wo[br] : &P.won[br], row, IT_HALF(e) * (wide ? 5 : 2),
                                 sb + BAR_RFULL + r.slot * 8, pol_norm);
                            r.adv(1);
                        }
                        if (nx == IT_DYN) tk = atomicAdd(&g_ticket[epoch & 1], 1);
                    }
                    if (nx == IT_DYN) nx = tk < P.nlist ? P.list[tk] : 0;
                    e = nx;
                }
            }
        } else if (warp == 1) {
            if (threadIdx.x == 32) {
                const uint64_t pol_norm = mkpol<POL_X>(), pol_o = mkpol<POL_O>();
                uint32_t phm = 0x1f;
#pragma unroll 1
                for (int it = 0;; it++) {
                    const uint32_t e = get_item(sb, it, dl);
                    if (e == 0) break;
                    const uint32_t br = IT_BR(e);
                    uint32_t xs = 0;
                    if (IT_TYPE(e) == IT_QA) {
#pragma unroll 1
                        for (int kk = 0; kk < 10; kk++) {
                            mbar_wait(sb + BAR_XEMPTY + xs * 8, (phm >> xs) & 1, dl);
                            phm ^= 1u << xs;
                            mbar_expect(sb + BAR_XFULL + xs * 8, XS);
                            tma3(sb + OFF_R + xs * XS, &P.x[br], IT_B(e) * 160, kk, sb + BAR_XFULL + xs * 8, pol_norm);
                            if (++xs == 5) xs = 0;
                        }
                    } else {
                        const uint32_t u0 = (br * 16 + IT_B(e)) * 32;
#pragma unroll 1
                        for (uint32_t u = u0 + IT_H0(e); u < u0 + IT_H1(e); u++) {
                            wait_flag(&g_flag[u], epoch);
                            asm volatile("fence.proxy.async;" ::: "memory");
#pragma unroll 1
                            for (int t = 0; t < 3; t++) {
                                mbar_wait(sb + BAR_XEMPTY + xs * 8, (phm >> xs) & 1, dl);
                                phm ^= 1u << xs;
                                mbar_expect(sb + BAR_XFULL + xs * 8, XS);
                                bulk_load(sb + OFF_R + xs * XS, ostash(br, IT_B(e), u & 31) + t * XS, XS, sb + BAR_XFULL + xs * 8, pol_o);
                                if (++xs == 5) xs = 0;
                            }
                        }
                    }
                }
            }
        } else if (warp == 2) {
#pragma unroll 1
            for (int it = 0;; it++) {
                const uint32_t e = get_item_warp(sb, it, dl);
                if (e == 0) break;
                nb_sync<NB_ODONE, 288>();
                if (threadIdx.x == 64) {
                    const uint32_t bb = IT_BR(e) * 16 + IT_B(e);
                    if (IT_TYPE(e) == IT_QA || IT_PART(e)) {
                        __threadfence();
                        unsigned int* f = IT_TYPE(e) == IT_QA ? &g_flag[bb * 32 + IT_H0(e)] : &g_pflag[bb * 2 + IT_HALF(e)];
                        asm volatile("st.relaxed.gpu.global.u32 [%0], %1;" ::"l"(f), "r"(epoch) : "memory");
                    } else {
                        const int nt = IT_TYPE(e) == IT_OP ? 5 : 2;
                        const int cc0 = IT_BR(e) * 640 + IT_HALF(e) * nt * 64;
#pragma unroll
                        for (int m = 0; m < 5; m++) {
                            if (m < nt)
                                asm volatile("cp.async.bulk.tensor.2d.global.shared::cta.bulk_group [%0, {%2,%3}], [%1];" ::"l"(&P.out),
                                             "r"(sb + OFF_R + m * XS), "r"(cc0 + m * 64), "r"((int)IT_B(e) * 160)
                                             : "memory");
                            asm volatile("cp.async.bulk.commit_group;" ::: "memory");
                        }
#define REL(N)                                                          \
    asm volatile("cp.async.bulk.wait_group.read %0;" ::"n"(4 - N) : "memory"); \
    asm volatile("mbarrier.arrive.shared::cta.b64 _, [%0], 8;" ::"r"(sb + BAR_XEMPTY + N * 8) : "memory");
                        REL(0) REL(1) REL(2) REL(3) REL(4)
#undef REL
                    }
                }
                __syncwarp();
            }
            if (threadIdx.x == 64) asm volatile("cp.async.bulk.wait_group 0;" ::: "memory");
        } else {
            const uint32_t lane = threadIdx.x & 31, p = lane >> 2;
#pragma unroll 1
            for (int it = 0;; it++) {
                const uint32_t e = get_item_warp(sb, it, dl);
                if (e == 0) break;
                if (IT_TYPE(e) != IT_QA) continue;
                nb_sync<NB_QK, 160>();
                const uint32_t co = (((lane & 3) * 2) ^ p) << 4;
                const uint32_t ka = sb + OFF_RING + lds_u(sb + OFF_GM + 4) * SLOT + p * (9 * 128) + co;
                const uint32_t qa = sb + OFF_R + p * (17 * 128) + co;
                uint32_t acc = 0;
#pragma unroll
                for (int c = 0; c < 6; c++) {
                    if (c == 4) nb_sync<NB_Q2, 288>();
                    const uint4 kv = lds_u4((ka + (c >> 1) * 8192) ^ ((c & 1) << 4));
                    const uint4 qv = lds_u4((qa + (c >> 1) * XS) ^ ((c & 1) << 4));
                    acc = fma_bf2(kv.x, qv.x, fma_bf2(kv.y, qv.y, fma_bf2(kv.z, qv.z, fma_bf2(kv.w, qv.w, acc))));
                }
                float d = __uint_as_float(acc << 16) + __uint_as_float(acc & 0xffff0000u);
                d += __shfl_xor_sync(0xffffffffu, d, 1);
                d += __shfl_xor_sync(0xffffffffu, d, 2);
                int key = __float_as_int(d);
                key ^= (key >> 31) & 0x7fffffff;
                key = __reduce_max_sync(0xffffffffu, key);
                key ^= (key >> 31) & 0x7fffffff;
                sts_f(sb + OFF_GM, __int_as_float(key) * SM_C);
                nb_arrive<NB_REF, 160>();
                nb_sync<NB_L, 160>();
                bool bad = false;
#pragma unroll
                for (int c = 0; c < 5; c++) {
                    const uint32_t la = sb + OFF_LX + (c * 32 + lane) * 4;
                    const float v = (__uint_as_float(lds_u(la)) + __uint_as_float(lds_u(la + 640))) +
                                    (__uint_as_float(lds_u(la + 1280)) + __uint_as_float(lds_u(la + 1920)));
                    const float inv = __fdividef(1.f, v);
                    const uint32_t hi = pack_bf16(inv, 0.f), lo = pack_bf16(inv - __uint_as_float(hi << 16), 0.f);
                    const uint32_t ia = sb + OFF_LINV + c * 128 + ((lane >> 1) & 3) * 32 + (lane >> 3) * 8 + (lane & 1) * 2;
                    asm volatile("st.shared.u16 [%0], %1;\nst.shared.u16 [%0+4], %2;" ::"r"(ia), "h"((unsigned short)hi), "h"((unsigned short)lo) : "memory");
                    bad |= !(v >= 5.421010862e-20f && v <= 1.8446744e19f);
                }
                sts_u(sb + OFF_FB, __any_sync(0xffffffffu, bad));
                nb_arrive<NB_VOTE, 160>();
                nb_arrive<NB_VOTE + 1, 160>();
            }
        }
    } else if (wgid == 1) {
        asm volatile("setmaxnreg.inc.sync.aligned.u32 240;");
        PendO<0> po;
        po.clear();
        {
            const int it = 0;
            TS(0, 30);
        }
        Ring r{0, 0, dl};
        uint32_t phm = 0;
        uint32_t e = get_item_warp(sb, 0, dl);
#pragma unroll 1
        for (int it = 0; e != 0; it++) {
            TS(0, 0);
            if (IT_TYPE(e) == IT_QA) {
                e = qa_item<0>(P, sb, r, phm, po, it);
            } else {
                if (IT_TYPE(e) == IT_OP) op_item<true>(e, sb, r, phm);
                else on_item<0>(e, sb, r, phm, lds_u(sb + OFF_FB + 4));
                po.clear();
                e = get_item_warp(sb, it + 1, r.dl);
            }
            TS(0, 31);
        }
        TS_DUMP(0);
    } else {
        asm volatile("setmaxnreg.inc.sync.aligned.u32 240;");
        PendO<1> po;
        po.clear();
        Ring r{0, 0, dl};
        uint32_t phm = 0;
        uint32_t e = get_item_warp(sb, 0, dl);
#pragma unroll 1
        for (int it = 0; e != 0; it++) {
            TS(1, 0);
            if (IT_TYPE(e) == IT_QA) {
                e = qa_item<1>(P, sb, r, phm, po, it);
            } else {
                if (IT_TYPE(e) == IT_OP) op_item<false>(e, sb, r, phm);
                else on_item<1>(e, sb, r, phm, lds_u(sb + OFF_FB + 4));
                po.clear();
                e = get_item_warp(sb, it + 1, r.dl);
            }
            TS(1, 31);
        }
        TS_DUMP(1);
    }
}

typedef CUresult (*EncFn)(CUtensorMap*, CUtensorMapDataType, cuuint32_t, void*, const cuuint64_t*, const cuuint64_t*,
                          const cuuint32_t*, const cuuint32_t*, CUtensorMapInterleave, CUtensorMapSwizzle,
                          CUtensorMapL2promotion, CUtensorMapFloatOOBfill);

void make_map3(EncFn enc, CUtensorMap* m, void* p, uint64_t rows, uint64_t rowbytes, uint64_t nblk, uint32_t boxrows,
               uint32_t boxblk) {
    cuuint64_t dims[3] = {64, rows, nblk};
    cuuint64_t str[2] = {rowbytes, 128};
    cuuint32_t box[3] = {64, boxrows, boxblk};
    cuuint32_t es[3] = {1, 1, 1};
    enc(m, CU_TENSOR_MAP_DATA_TYPE_BFLOAT16, 3, p, dims, str, box, es, CU_TENSOR_MAP_INTERLEAVE_NONE,
        CU_TENSOR_MAP_SWIZZLE_128B, CU_TENSOR_MAP_L2_PROMOTION_NONE, CU_TENSOR_MAP_FLOAT_OOB_FILL_NONE);
}

constexpr int tune(const char*, int def) { return def; }

void build_schedule(Params& P) {
    const int mode = tune("MODE", 4), dmax = tune("DMAX", 27000), n0 = tune("N0", 0);
    const int hmin = tune("HMIN", 19), hmax = tune("HMAX", 25), off = tune("OFF", 0), slope = tune("SLOPE", 1744);
    const int ng = tune("NG", 0), d0 = tune("D0", 0), nkeep = tune("NKEEP", 0), odmax = tune("ODMAX", 0);
    int u = 0;
    auto unit = [&]() {
        const uint32_t e = mk_item(IT_QA, u >> 9, u & 15, (u >> 4) & 31, 0, 0);
        u++;
        return e;
    };
    int qa[NCTA], nq = 0, op[NCTA], no = 0;
    for (int c = 0; c < NCTA; c++) {
        P.delay[c] = 0;
        for (int i = 0; i < NSTAT; i++) P.items[c][i] = 0;
        if (mode >= 3 && c < 128 && (c & 7) >= 6) op[no++] = c;
        else if (mode != 2 || (c & 3) == 0) qa[nq++] = c;
    }
    for (int t = 0; t < no; t++) {
        P.items[op[t]][0] = unit();
        P.items[op[t]][1] = mk_item(IT_OP, 0, t >> 1, 0, 32, t & 1);
        P.items[op[t]][2] = P.items[op[t]][3] = IT_DYN;
        P.delay[op[t]] = (t >> 1) * odmax / 16;
    }
    for (int k = 0; k < nq; k++) {
        const int c = qa[(k * 37) % nq];
        P.items[c][0] = unit();
        P.items[c][1] = P.items[c][2] = P.items[c][3] = IT_DYN;
        P.delay[c] = k < n0 ? 0 : (int)((long long)dmax * (k + 1 - n0) / (nq - n0));
        if (ng) P.delay[c] = d0 + (k * ng / nq) * (dmax / ng);
    }
    int H[16], pos[16];
    for (int b = 0; b < 16; b++) {
        H[b] = hmin + ((hmax - hmin) * b + 7) / 15;
        pos[b] = 1092 + off - H[b] * slope / 100;
        if (b < nkeep && no) {
            pos[b] = -1;
            P.items[op[30 - 2 * b]][2] = mk_item(IT_OP, 1, b, 0, H[b], 0, 1);
            P.items[op[31 - 2 * b]][2] = mk_item(IT_OP, 1, b, 0, H[b], 1, 1);
        }
    }
    int n = 0;
    const int uend = mode == 2 ? 8 * nq : 1024;
    while (u < uend) {
        for (int b = 0; b < 16 && no; b++)
            if (pos[b] == u) {
                P.list[n++] = mk_item(IT_OP, 1, b, 0, H[b], 0, 1);
                P.list[n++] = mk_item(IT_OP, 1, b, 0, H[b], 1, 1);
            }
        P.list[n++] = unit();
    }
    if (no)
        for (int k = 0; k < 80; k++) P.list[n++] = mk_item(IT_ON, 1, k / 5, H[k / 5], 32, k % 5);
    P.nlist = n;
}

}

extern "C" void kernel_launch(void* const* d_in, const int* in_sizes, int n_in, void* d_out, int out_size) {
    static Params P;
    static bool init = false;
    if (!init) {
        EncFn enc = nullptr;
        cudaDriverEntryPointQueryResult qr;
        cudaGetDriverEntryPoint("cuTensorMapEncodeTiled", (void**)&enc, cudaEnableDefault, &qr);
        for (int i = 0; i < 2; i++) {
            P.px[i] = (const __nv_bfloat16*)d_in[5 * i + 0];
            P.pk[i] = (const __nv_bfloat16*)d_in[5 * i + 1];
            P.pv[i] = (const __nv_bfloat16*)d_in[5 * i + 2];
            P.pwq[i] = (const __nv_bfloat16*)d_in[5 * i + 3];
            make_map3(enc, &P.x[i], d_in[5 * i + 0], 2560, 1280, 10, 160, 1);
            make_map3(enc, &P.k[i], d_in[5 * i + 1], 16 * 32 * 512, 384, 3, 64, 3);
            make_map3(enc, &P.v[i], d_in[5 * i + 2], 16 * 32 * 512, 384, 3, 64, 3);
            make_map3(enc, &P.wq[i], d_in[5 * i + 3], 640, 12288, 96, 64, 3);
            make_map3(enc, &P.wo[i], d_in[5 * i + 4], 6144, 1280, 10, 32, 5);
            make_map3(enc, &P.won[i], d_in[5 * i + 4], 6144, 1280, 10, 64, 2);
        }
        cuuint64_t dims[2] = {1280, 2560};
        cuuint64_t str[1] = {2560};
        cuuint32_t box[2] = {64, 160};
        cuuint32_t es[2] = {1, 1};
        enc(&P.out, CU_TENSOR_MAP_DATA_TYPE_BFLOAT16, 2, d_out, dims, str, box, es, CU_TENSOR_MAP_INTERLEAVE_NONE,
            CU_TENSOR_MAP_SWIZZLE_128B, CU_TENSOR_MAP_L2_PROMOTION_NONE, CU_TENSOR_MAP_FLOAT_OOB_FILL_NONE);
        build_schedule(P);
        cudaFuncSetAttribute(fused_kernel, cudaFuncAttributeMaxDynamicSharedMemorySize, SMEM_LAUNCH);
        init = true;
    }
    fused_kernel<<<NCTA, 384, SMEM_LAUNCH>>>(P);
}
```

```cpp
#include <cuda_runtime.h>
#include <cuda.h>
#include <cuda_bf16.h>
#include <stdint.h>

namespace {

constexpr int NCTA = 132;
constexpr int MAXI = 16;
constexpr int NSTAT = 4;
constexpr uint32_t IT_DYN = 0xffffffffu;
constexpr int SLOT = 24576;
constexpr int NSLOT = 5;
constexpr int XS = 20480;
constexpr int OFF_R = 0;
constexpr int OFF_RING = 5 * XS;
constexpr int OFF_MISC = OFF_RING + NSLOT * SLOT;
constexpr int OFF_LX = OFF_MISC;
constexpr int OFF_LINV = OFF_LX + 2560;
constexpr int OFF_FB = OFF_LINV + 640;
constexpr int OFF_GM = OFF_FB + 16;
constexpr int OFF_BAR = OFF_GM + 16;
constexpr int BAR_RFULL = OFF_BAR;
constexpr int BAR_REMPTY = BAR_RFULL + 40;
constexpr int BAR_XFULL = BAR_REMPTY + 40;
constexpr int BAR_XEMPTY = BAR_XFULL + 40;
constexpr int BAR_ITEM = BAR_XEMPTY + 40;
constexpr int OFF_ITEM = BAR_ITEM + MAXI * 8;
constexpr int SMEM_BYTES = OFF_ITEM + MAXI * 4;
static_assert(SMEM_BYTES <= 232448, "smem");

constexpr int NB_W = 1  , NB_PFULL = 3  , NB_VOTE = 5  , NB_Q2 = 7, NB_SDONE = 8, NB_PDONE = 9,
              NB_L = 10, NB_REF = 11, NB_ODONE = 12, NB_OPEND = 13, NB_LX = 14, NB_Q01 = 15, NB_QK = 0  ;

constexpr uint32_t IT_QA = 1, IT_OP = 2, IT_ON = 3;
__host__ __device__ constexpr uint32_t mk_item(uint32_t type, uint32_t br, uint32_t b, uint32_t h0, uint32_t h1, uint32_t half,
                                               uint32_t part = 0) {
    return type | (br << 2) | (b << 3) | (h0 << 7) | (h1 << 13) | (half << 19) | (part << 22);
}
#define IT_TYPE(e) ((e) & 3u)
#define IT_BR(e) (((e) >> 2) & 1u)
#define IT_B(e) (((e) >> 3) & 15u)
#define IT_H0(e) (((e) >> 7) & 63u)
#define IT_H1(e) (((e) >> 13) & 63u)
#define IT_HALF(e) (((e) >> 19) & 7u)
#define IT_PART(e) (((e) >> 22) & 1u)

struct Params {
    CUtensorMap x[2], wq[2], k[2], v[2], wo[2], won[2], out;
    const __nv_bfloat16 *px[2], *pwq[2], *pk[2], *pv[2];
    uint32_t items[NCTA][NSTAT];
    uint32_t delay[NCTA];
    uint32_t nlist;
    uint32_t list[1024];
};

constexpr int OUNIT = 61440;
__device__ __align__(1024) unsigned char g_ostash[(size_t)1024 * OUNIT];
__device__ unsigned int g_flag[1024];
__device__ float4 g_part[2 * 16 * 10 * 2560];
__device__ unsigned int g_pflag[64];
#define ORING 64
__device__ __forceinline__ uint32_t ostash_off(uint32_t br, uint32_t b, uint32_t h) {
    return (((br * 32 + h) % ORING) * 16 + b) * OUNIT;
}
__device__ __forceinline__ unsigned char* ostash(uint32_t br, uint32_t b, uint32_t h) { return g_ostash + ostash_off(br, b, h); }
__device__ unsigned int g_epoch[NCTA];
__device__ unsigned int g_ticket[2];

constexpr int SMEM_LAUNCH = SMEM_BYTES;
#define TS(role, idx)
#define TS_DUMP(role)
#define TSD(role, idx)

#define POL_W 2
#define POL_X 2
#define POL_O 2
template <int M>
__device__ __forceinline__ uint64_t mkpol() {
    uint64_t p;
    if (M == 0) asm volatile("createpolicy.fractional.L2::evict_normal.b64 %0, 1.0;" : "=l"(p));
    if (M == 1) asm volatile("createpolicy.fractional.L2::evict_first.b64 %0, 1.0;" : "=l"(p));
    if (M == 2) asm volatile("createpolicy.fractional.L2::evict_unchanged.b64 %0, 1.0;" : "=l"(p));
    if (M == 3) asm volatile("createpolicy.fractional.L2::evict_normal.L2::evict_unchanged.b64 %0, 0.25;" : "=l"(p));
    return p;
}
#define STSM_W 1
#define XLATE 2
#define PV0FIRST 1
#define QST0 1
#define QST1 2
#define QHOLD 7
constexpr float SM_C = 0.07216878364870322f * 1.4426950408889634f;

__device__ __forceinline__ uint32_t tid_now() {
    uint32_t t;
    asm volatile("mov.u32 %0, %%tid.x;" : "=r"(t));
    return t;
}
__device__ __forceinline__ void mbar_init(uint32_t a, uint32_t c) {
    asm volatile("mbarrier.init.shared::cta.b64 [%0], %1;" ::"r"(a), "r"(c) : "memory");
}
__device__ __forceinline__ void mbar_expect(uint32_t a, uint32_t b) {
    asm volatile("mbarrier.arrive.expect_tx.shared::cta.b64 _, [%0], %1;" ::"r"(a), "r"(b) : "memory");
}
template <int CNT = 1>
__device__ __forceinline__ void mbar_arrive_warp(uint32_t a) {
    if (CNT == 1)
        asm volatile("{\n.reg .pred p;\nelect.sync _|p, 0xffffffff;\n@p mbarrier.arrive.shared::cta.b64 _, [%0];\n}" ::"r"(a) : "memory");
    else
        asm volatile(
            "{\n.reg .pred p;\nelect.sync _|p, 0xffffffff;\n@p mbarrier.arrive.shared::cta.b64 _, [%0];\n"
            "@p mbarrier.arrive.shared::cta.b64 _, [%0];\n}" ::"r"(a)
            : "memory");
}
template <int CNT = 1>
__device__ __forceinline__ void mbar_arrive_warp_if(uint32_t a, bool cond) {
    if (CNT == 1)
        asm volatile(
            "{\n.reg .pred p, c;\nelect.sync _|p, 0xffffffff;\nsetp.ne.and.u32 c, %1, 0, p;\n"
            "@c mbarrier.arrive.shared::cta.b64 _, [%0];\n}" ::"r"(a), "r"((uint32_t)cond)
            : "memory");
    else
        asm volatile(
            "{\n.reg .pred p, c;\nelect.sync _|p, 0xffffffff;\nsetp.ne.and.u32 c, %1, 0, p;\n"
            "@c mbarrier.arrive.shared::cta.b64 _, [%0];\n@c mbarrier.arrive.shared::cta.b64 _, [%0];\n}" ::"r"(a), "r"((uint32_t)cond)
            : "memory");
}
__device__ __forceinline__ uint32_t deadline() {
    uint32_t c;
    asm volatile("mov.u32 %0, %%clock_hi;" : "=r"(c));
    return c + 4;
}
__device__ __forceinline__ void mbar_wait(uint32_t a, uint32_t ph, uint32_t dl) {
    asm volatile(
        "{\n.reg .pred p;\n.reg .u32 m;\n"
        "LOOP:\n"
        "mbarrier.try_wait.parity.shared::cta.b64 p, [%0], %1;\n"
        "@p bra DONE;\n"
        "mov.u32 m, %%clock_hi;\n"
        "setp.ne.u32 p, m, %2;\n"
        "@p bra LOOP;\n"
        "trap;\n"
        "DONE:\n}" ::"r"(a), "r"(ph), "r"(dl)
        : "memory");
}
template <int ID, int CNT>
__device__ __forceinline__ void nb_sync() { asm volatile("bar.sync %0, %1;" ::"n"(ID), "n"(CNT) : "memory"); }
template <int ID, int CNT>
__device__ __forceinline__ void nb_arrive() { asm volatile("bar.arrive %0, %1;" ::"n"(ID), "n"(CNT) : "memory"); }
__device__ __forceinline__ void fence_async_smem() { asm volatile("fence.proxy.async.shared::cta;" ::: "memory"); }

__device__ __forceinline__ void tma3(uint32_t dst, const CUtensorMap* m, int c1, int c2, uint32_t bar, uint64_t pol) {
    asm volatile(
        "cp.async.bulk.tensor.3d.shared::cluster.global.mbarrier::complete_tx::bytes.L2::cache_hint [%0], [%1, {%3,%4,%5}], [%2], %6;" ::"r"(dst),
        "l"(m), "r"(bar), "r"(0), "r"(c1), "r"(c2), "l"(pol)
        : "memory");
}
__device__ __forceinline__ void bulk_load(uint32_t dst, const void* src, uint32_t bytes, uint32_t bar, uint64_t pol) {
    asm volatile("cp.async.bulk.shared::cluster.global.mbarrier::complete_tx::bytes.L2::cache_hint [%0], [%1], %2, [%3], %4;" ::"r"(dst),
                 "l"(src), "r"(bytes), "r"(bar), "l"(pol)
                 : "memory");
}
__device__ __forceinline__ void wg_fence() { asm volatile("wgmma.fence.sync.aligned;" ::: "memory"); }
__device__ __forceinline__ void wg_commit() { asm volatile("wgmma.commit_group.sync.aligned;" ::: "memory"); }
template <int N>
__device__ __forceinline__ void wg_wait() { asm volatile("wgmma.wait_group.sync.aligned %0;" ::"n"(N) : "memory"); }

#define RW80(c, d) c(d[0]), c(d[1]), c(d[2]), c(d[3]), c(d[4]), c(d[5]), c(d[6]), c(d[7]), c(d[8]), c(d[9]), c(d[10]), c(d[11]), c(d[12]), c(d[13]), c(d[14]), c(d[15]), c(d[16]), c(d[17]), c(d[18]), c(d[19]), c(d[20]), c(d[21]), c(d[22]), c(d[23]), c(d[24]), c(d[25]), c(d[26]), c(d[27]), c(d[28]), c(d[29]), c(d[30]), c(d[31]), c(d[32]), c(d[33]), c(d[34]), c(d[35]), c(d[36]), c(d[37]), c(d[38]), c(d[39]), c(d[40]), c(d[41]), c(d[42]), c(d[43]), c(d[44]), c(d[45]), c(d[46]), c(d[47]), c(d[48]), c(d[49]), c(d[50]), c(d[51]), c(d[52]), c(d[53]), c(d[54]), c(d[55]), c(d[56]), c(d[57]), c(d[58]), c(d[59]), c(d[60]), c(d[61]), c(d[62]), c(d[63]), c(d[64]), c(d[65]), c(d[66]), c(d[67]), c(d[68]), c(d[69]), c(d[70]), c(d[71]), c(d[72]), c(d[73]), c(d[74]), c(d[75]), c(d[76]), c(d[77]), c(d[78]), c(d[79])
#define RW48(c, d) c(d[0]), c(d[1]), c(d[2]), c(d[3]), c(d[4]), c(d[5]), c(d[6]), c(d[7]), c(d[8]), c(d[9]), c(d[10]), c(d[11]), c(d[12]), c(d[13]), c(d[14]), c(d[15]), c(d[16]), c(d[17]), c(d[18]), c(d[19]), c(d[20]), c(d[21]), c(d[22]), c(d[23]), c(d[24]), c(d[25]), c(d[26]), c(d[27]), c(d[28]), c(d[29]), c(d[30]), c(d[31]), c(d[32]), c(d[33]), c(d[34]), c(d[35]), c(d[36]), c(d[37]), c(d[38]), c(d[39]), c(d[40]), c(d[41]), c(d[42]), c(d[43]), c(d[44]), c(d[45]), c(d[46]), c(d[47])
#define RW32(c, d) c(d[0]), c(d[1]), c(d[2]), c(d[3]), c(d[4]), c(d[5]), c(d[6]), c(d[7]), c(d[8]), c(d[9]), c(d[10]), c(d[11]), c(d[12]), c(d[13]), c(d[14]), c(d[15]), c(d[16]), c(d[17]), c(d[18]), c(d[19]), c(d[20]), c(d[21]), c(d[22]), c(d[23]), c(d[24]), c(d[25]), c(d[26]), c(d[27]), c(d[28]), c(d[29]), c(d[30]), c(d[31])

__device__ __forceinline__ void reg_fence(float (&d)[80]) { asm volatile("" : RW80("+f", d)::"memory"); }
__device__ __forceinline__ void reg_fence(float (&d)[48]) { asm volatile("" : RW48("+f", d)::"memory"); }
__device__ __forceinline__ void reg_fence(float (&d)[32]) { asm volatile("" : RW32("+f", d)::"memory"); }

template <int NR>
__device__ __forceinline__ void zero(float (&d)[NR]) {
#pragma unroll
    for (int i = 0; i < NR; i++) d[i] = 0.f;
}

constexpr uint32_t HI_SW128 = (1024u >> 4) | (1u << 30);
constexpr uint32_t HI_OST = (2560u >> 4) | (2u << 30);
constexpr uint32_t LO_LBO1 = (1u << 16);
constexpr uint32_t LO_OST = ((512u >> 4) << 16);

template <int TA, int TB, uint32_t HIB, int ACC>
__device__ __forceinline__ void wgmma(float (&d)[80], uint32_t loA, uint32_t loB) {
#define WG_ASM(SD)                                                          \
    "{\n.reg .b64 da, db;\nmov.b64 da, {%80, %82};\nmov.b64 db, {%81, %83};\n" \
    "wgmma.mma_async.sync.aligned.m64n160k16.f32.bf16.bf16 "               \
    "{%0,%1,%2,%3,%4,%5,%6,%7,%8,%9,%10,%11,%12,%13,%14,%15,%16,%17,%18,%19,%20,%21,%22,%23,%24,%25,%26,%27,%28,%29,%30,%31,%32,%33,%34,%35,%36,%37,%38,%39,%40,%41,%42,%43,%44,%45,%46,%47,%48,%49,%50,%51,%52,%53,%54,%55,%56,%57,%58,%59,%60,%61,%62,%63,%64,%65,%66,%67,%68,%69,%70,%71,%72,%73,%74,%75,%76,%77,%78,%79}, da, db, " SD ", 1, 1, %84, %85;\n}"
    if constexpr (ACC == 2)
        asm volatile(WG_ASM("0") : RW80("+f", d) : "r"(loA), "r"(loB), "n"(HI_SW128), "n"(HIB), "n"(TA), "n"(TB));
    else if constexpr (ACC == 1)
        asm volatile(WG_ASM("1") : RW80("+f", d) : "r"(loA), "r"(loB), "n"(HI_SW128), "n"(HIB), "n"(TA), "n"(TB));
    else
        asm volatile(WG_ASM("0") : RW80("=f", d) : "r"(loA), "r"(loB), "n"(HI_SW128), "n"(HIB), "n"(TA), "n"(TB));
#undef WG_ASM
}
template <int TA, int TB, uint32_t HIB, int ACC>
__device__ __forceinline__ void wgmma(float (&d)[48], uint32_t loA, uint32_t loB) {
#define WG_ASM(SD)                                                          \
    "{\n.reg .b64 da, db;\nmov.b64 da, {%48, %50};\nmov.b64 db, {%49, %51};\n" \
    "wgmma.mma_async.sync.aligned.m64n96k16.f32.bf16.bf16 "               \
    "{%0,%1,%2,%3,%4,%5,%6,%7,%8,%9,%10,%11,%12,%13,%14,%15,%16,%17,%18,%19,%20,%21,%22,%23,%24,%25,%26,%27,%28,%29,%30,%31,%32,%33,%34,%35,%36,%37,%38,%39,%40,%41,%42,%43,%44,%45,%46,%47}, da, db, " SD ", 1, 1, %52, %53;\n}"
    if constexpr (ACC == 1)
        asm volatile(WG_ASM("1") : RW48("+f", d) : "r"(loA), "r"(loB), "n"(HI_SW128), "n"(HIB), "n"(TA), "n"(TB));
    else
        asm volatile(WG_ASM("0") : RW48("=f", d) : "r"(loA), "r"(loB), "n"(HI_SW128), "n"(HIB), "n"(TA), "n"(TB));
#undef WG_ASM
}
template <int TA, int TB, uint32_t HIB, int ACC>
__device__ __forceinline__ void wgmma(float (&d)[32], uint32_t loA, uint32_t loB) {
#define WG_ASM(SD)                                                          \
    "{\n.reg .b64 da, db;\nmov.b64 da, {%32, %34};\nmov.b64 db, {%33, %35};\n" \
    "wgmma.mma_async.sync.aligned.m64n64k16.f32.bf16.bf16 "               \
    "{%0,%1,%2,%3,%4,%5,%6,%7,%8,%9,%10,%11,%12,%13,%14,%15,%16,%17,%18,%19,%20,%21,%22,%23,%24,%25,%26,%27,%28,%29,%30,%31}, da, db, " SD ", 1, 1, %36, %37;\n}"
    if constexpr (ACC == 1)
        asm volatile(WG_ASM("1") : RW32("+f", d) : "r"(loA), "r"(loB), "n"(HI_SW128), "n"(HIB), "n"(TA), "n"(TB));
    else
        asm volatile(WG_ASM("0") : RW32("=f", d) : "r"(loA), "r"(loB), "n"(HI_SW128), "n"(HIB), "n"(TA), "n"(TB));
#undef WG_ASM
}

__device__ __forceinline__ uint32_t pack_bf16(float lo, float hi) {
    uint32_t r;
    asm("cvt.rn.bf16x2.f32 %0, %1, %2;" : "=r"(r) : "f"(hi), "f"(lo));
    return r;
}
__device__ __forceinline__ float ex2(float x) {
    float r;
    asm("ex2.approx.ftz.f32 %0, %1;" : "=f"(r) : "f"(x));
    return r;
}
__device__ __forceinline__ void stsm4t(uint32_t a, uint32_t r0, uint32_t r1, uint32_t r2, uint32_t r3) {
    asm volatile("stmatrix.sync.aligned.m8n8.x4.trans.shared.b16 [%0], {%1,%2,%3,%4};" ::"r"(a), "r"(r0), "r"(r1), "r"(r2), "r"(r3)
                 : "memory");
}
__device__ __forceinline__ uint32_t lds_u(uint32_t a) {
    uint32_t v;
    asm volatile("ld.shared.u32 %0, [%1];" : "=r"(v) : "r"(a) : "memory");
    return v;
}
__device__ __forceinline__ uint4 lds_u4(uint32_t a) {
    uint4 v;
    asm volatile("ld.shared.v4.u32 {%0,%1,%2,%3}, [%4];" : "=r"(v.x), "=r"(v.y), "=r"(v.z), "=r"(v.w) : "r"(a) : "memory");
    return v;
}
__device__ __forceinline__ float2 lds_f2(uint32_t a) {
    float2 v;
    asm volatile("ld.shared.v2.f32 {%0,%1}, [%2];" : "=f"(v.x), "=f"(v.y) : "r"(a) : "memory");
    return v;
}
__device__ __forceinline__ void sts_f(uint32_t a, float v) { asm volatile("st.shared.f32 [%0], %1;" ::"r"(a), "f"(v) : "memory"); }
__device__ __forceinline__ void sts_u(uint32_t a, uint32_t v) { asm volatile("st.shared.u32 [%0], %1;" ::"r"(a), "r"(v) : "memory"); }
__device__ __forceinline__ void sts_f2(uint32_t a, float x, float y) {
    asm volatile("st.shared.v2.f32 [%0], {%1,%2};" ::"r"(a), "f"(x), "f"(y) : "memory");
}

__device__ __forceinline__ void store_tile_t(const float (&d)[80], uint32_t addr) {
#pragma unroll
    for (int j = 0; j < 10; j++)
        stsm4t(addr + j * 2048, pack_bf16(d[8 * j], d[8 * j + 1]), pack_bf16(d[8 * j + 2], d[8 * j + 3]),
               pack_bf16(d[8 * j + 4], d[8 * j + 5]), pack_bf16(d[8 * j + 6], d[8 * j + 7]));
}
template <int NR>
__device__ __forceinline__ void store_out_tile(const float (&d)[NR], uint32_t base, uint32_t lane, uint32_t w) {
    const uint32_t mi = lane >> 3, i = lane & 7;
    const uint32_t chunk = 2 * w + (mi & 1);
    const uint32_t q0 = 8 * (i >> 1) + 2 * (mi >> 1) + (i & 1);
    const uint32_t a0 = base + q0 * 128 + ((chunk ^ (q0 & 7)) << 4);
    const uint32_t a1 = base + (q0 + 4) * 128 + ((chunk ^ ((q0 + 4) & 7)) << 4);
#pragma unroll
    for (int j = 0; j < NR / 8; j++)
        stsm4t(((j & 1) ? a1 : a0) + (j >> 1) * 4096, pack_bf16(d[8 * j], d[8 * j + 1]), pack_bf16(d[8 * j + 2], d[8 * j + 3]),
               pack_bf16(d[8 * j + 4], d[8 * j + 5]), pack_bf16(d[8 * j + 6], d[8 * j + 7]));
}

struct TrueT { static constexpr bool value = true; };
struct FalseT { static constexpr bool value = false; };

template <int V>
struct IntT { static constexpr int value = V; };

__device__ __forceinline__ uint32_t get_item(uint32_t sb, int it, uint32_t dl) {
    mbar_wait(sb + BAR_ITEM + it * 8, 0, dl);
    return lds_u(sb + OFF_ITEM + it * 4);
}
__device__ __forceinline__ uint32_t get_item_warp(uint32_t sb, int it, uint32_t dl) {
    return __shfl_sync(0xffffffffu, get_item(sb, it, dl), 0);
}

struct Ring {
    uint32_t slot, ph, dl;
    __device__ __forceinline__ void adv(uint32_t k) {
        slot += k;
        if (slot >= NSLOT) { slot -= NSLOT; ph ^= 1; }
    }
};

template <int K>
__device__ __forceinline__ void qk_step(float (&s)[80], uint32_t loK, uint32_t loQ) {
    wgmma<0, 0, HI_SW128, K != 0>(s, loK + (K >> 2) * (8192 >> 4) + (K & 3) * 2, loQ + (K >> 2) * (XS >> 4) + (K & 3) * 2);
}
template <int K0, int K1>
__device__ __forceinline__ void qk_steps(float (&s)[80], uint32_t loK, uint32_t loQ) {
    if constexpr (K0 < K1) {
        qk_step<K0>(s, loK, loQ);
        qk_steps<K0 + 1, K1>(s, loK, loQ);
    }
}
__device__ __forceinline__ uint32_t add_bf2(uint32_t a, uint32_t b) {
    uint32_t r;
    asm("add.rn.bf16x2 %0, %1, %2;" : "=r"(r) : "r"(a), "r"(b));
    return r;
}
__device__ __forceinline__ uint32_t fma_bf2(uint32_t a, uint32_t b, uint32_t c) {
    uint32_t r;
    asm("fma.rn.bf16x2 %0, %1, %2, %3;" : "=r"(r) : "r"(a), "r"(b), "r"(c));
    return r;
}
template <int J>
__device__ __forceinline__ void exp_block(const float (&s)[80], uint32_t (&k)[40], uint32_t pa, float mref) {
    if constexpr (J < 10) {
#pragma unroll
        for (int i = 4 * J; i < 4 * J + 4; i++)
            k[i] = pack_bf16(ex2(fmaf(s[2 * i], SM_C, -mref)), ex2(fmaf(s[2 * i + 1], SM_C, -mref)));
#pragma unroll
        for (int i = 0; i < 4; i++)
            asm volatile("stmatrix.sync.aligned.m8n8.x1.trans.shared.b16 [%0], {%1};" ::"r"(((i & 1) ? pa ^ 16 : pa) + J * 2048 + (i >> 1) * 1024),
                         "r"(k[4 * J + i])
                         : "memory");
        exp_block<J + 1>(s, k, pa, mref);
    }
}
__device__ __forceinline__ void sum_block(const uint32_t (&k)[40], float (&l)[10], uint32_t lane) {
    const bool b4 = lane & 16, b3 = lane & 8;
    uint32_t ps[20], t[10];
#pragma unroll
    for (int j = 0; j < 20; j++) ps[j] = add_bf2(k[2 * j], k[2 * j + 1]);
#pragma unroll
    for (int j = 0; j < 10; j++)
        t[j] = add_bf2(b4 ? ps[2 * j + 1] : ps[2 * j], __shfl_xor_sync(0xffffffffu, b4 ? ps[2 * j] : ps[2 * j + 1], 16));
#pragma unroll
    for (int i = 0; i < 5; i++) {
        const uint32_t a = b3 ? t[i + 5] : t[i], b = __shfl_xor_sync(0xffffffffu, b3 ? t[i] : t[i + 5], 8);
        l[2 * i] += __uint_as_float(a << 16) + __uint_as_float(b << 16);
        l[2 * i + 1] += __uint_as_float(a & 0xffff0000u) + __uint_as_float(b & 0xffff0000u);
    }
}
template <bool ADD>
__device__ __forceinline__ void sum_store(const float (&l)[10], uint32_t lane, uint32_t lxa) {
    const bool b2 = lane & 4;
    float t[5];
#pragma unroll
    for (int i = 0; i < 5; i++) t[i] = ADD ? __uint_as_float(lds_u(lxa + i * 64)) : 0.f;
#pragma unroll
    for (int i = 0; i < 5; i++)
        sts_f(lxa + i * 64, t[i] + (b2 ? l[2 * i + 1] : l[2 * i]) + __shfl_xor_sync(0xffffffffu, b2 ? l[2 * i] : l[2 * i + 1], 4));
}

__device__ __forceinline__ void fallback_unit(const Params& P, uint32_t e, uint32_t tid) {
    const uint32_t lane = tid & 31, br = IT_BR(e), b = IT_B(e), h = IT_H0(e);
    const __nv_bfloat162* wq = (const __nv_bfloat162*)(P.pwq[br] + h * 192) + lane;
    const __nv_bfloat162* kp = (const __nv_bfloat162*)(P.pk[br] + (size_t)(b * 32 + h) * 512 * 192) + lane;
    const __nv_bfloat162* vp = (const __nv_bfloat162*)(P.pv[br] + (size_t)(b * 32 + h) * 512 * 192) + lane;
#pragma unroll 1
    for (uint32_t qi = 0; qi < 40; qi++) {
        const uint32_t q = 4 * qi + (tid >> 5);
        const __nv_bfloat16* xr = P.px[br] + (size_t)(b * 160 + q) * 640;
        float a[6] = {0.f, 0.f, 0.f, 0.f, 0.f, 0.f};
#pragma unroll 2
        for (int k = 0; k < 640; k++) {
            const float xv = __bfloat162float(xr[k]);
#pragma unroll
            for (int i = 0; i < 3; i++) {
                const float2 wv = __bfloat1622float2(wq[(size_t)k * 3072 + i * 32]);
                a[2 * i] = fmaf(xv, wv.x, a[2 * i]);
                a[2 * i + 1] = fmaf(xv, wv.y, a[2 * i + 1]);
            }
        }
#pragma unroll
        for (int i = 0; i < 6; i++) a[i] = __bfloat162float(__float2bfloat16(a[i]));
        auto score = [&](int key) {
            float d = 0.f;
#pragma unroll
            for (int i = 0; i < 3; i++) {
                const float2 kv = __bfloat1622float2(kp[key * 96 + i * 32]);
                d = fmaf(a[2 * i], kv.x, fmaf(a[2 * i + 1], kv.y, d));
            }
#pragma unroll
            for (int o = 16; o > 0; o >>= 1) d += __shfl_xor_sync(0xffffffffu, d, o);
            return d;
        };
        float m = -INFINITY, o[6] = {0.f, 0.f, 0.f, 0.f, 0.f, 0.f}, sum = 0.f;
#pragma unroll 1
        for (int n = 0; n < 1024; n++) {
            const int key = n & 511;
            const float d = score(key);
            if (n < 512) {
                m = fmaxf(m, d);
            } else {
                const float p = ex2((d - m) * SM_C);
                sum += p;
#pragma unroll
                for (int i = 0; i < 3; i++) {
                    const float2 vv = __bfloat1622float2(vp[key * 96 + i * 32]);
                    o[2 * i] = fmaf(p, vv.x, o[2 * i]);
                    o[2 * i + 1] = fmaf(p, vv.y, o[2 * i + 1]);
                }
            }
        }
        const float inv = __fdividef(1.f, sum);
        __nv_bfloat16* op = (__nv_bfloat16*)ostash(br, b, h) + (q >> 5) * 256 + 2 * ((q & 31) >> 3) + (q & 1);
#pragma unroll
        for (int i = 0; i < 6; i++) {
            const uint32_t d = (i >> 1) * 64 + 2 * lane + (i & 1);
            op[(d >> 3) * 1280 + (d & 7) * 32 + ((((q & 7) >> 1) ^ ((d & 7) >> 1)) << 3)] = __float2bfloat16(o[i] * inv);
        }
    }
}

template <int W>
struct PendO {
    static constexpr int N = W == 0 ? 56 : 64;
    uint32_t v[N];
    unsigned char* gp;
    static __device__ __forceinline__ uint32_t toff() {
        const uint32_t t = tid_now();
        return ((t >> 5) & 3) * 5120 + ((t >> 2) & 7) * 64 + (((t ^ (t >> 3)) & 3) << 4);
    }
    uint32_t pend, sig;
    static __device__ __forceinline__ void scale(uint32_t& x, uint32_t hi, uint32_t lo) {
        asm("{\n.reg .b32 t;\nmul.rn.bf16x2 t, %0, %2;\nfma.rn.bf16x2 %0, %0, %1, t;\n}" : "+r"(x) : "r"(hi), "r"(lo));
    }
    template <int I, int OFF>
    __device__ __forceinline__ void put() {
        asm volatile("{\n.reg .pred p;\nsetp.ne.u32 p, %6, 0;\n@p st.global.v4.b32 [%0+%5], {%1,%2,%3,%4};\n}" ::"l"(gp), "r"(v[I]),
                     "r"(v[I + 1]), "r"(v[I + 2]), "r"(v[I + 3]), "n"(OFF), "r"(pend)
                     : "memory");
    }
    __device__ __forceinline__ void verdict(const Params& P, uint32_t sb, int ie) {
        if (sig) {
            nb_sync<NB_VOTE + W, 160>();
            pend = !__any_sync(0xffffffffu, lds_u(sb + OFF_FB) != 0);
            if (W == 1 && !pend) {
                fallback_unit(P, lds_u(sb + OFF_ITEM + ie * 4), tid_now() & 127);
                __syncwarp();
            }
        }
    }
    template <int G, int H>
    __device__ __forceinline__ void half(uint32_t sb) {
        constexpr bool T2 = W == 0 ? G >= 3 : G < 3;
        constexpr int B = T2 ? 40 + 8 * (W == 0 ? G - 3 : G) : 0;
        const uint4 a = lds_u4(sb + OFF_LINV + G * 128 + H * 16 + (threadIdx.x & 3) * 32);
#pragma unroll
        for (int i = 2 * H; i < 8; i += 4) {
            scale(v[8 * G + i], a.x, a.y);
            scale(v[8 * G + i + 1], a.z, a.w);
            if (T2) {
                scale(v[B + i], a.x, a.y);
                scale(v[B + i + 1], a.z, a.w);
            }
        }
        if (H == 1) {
            put<8 * G, W * XS + G * 512>();
            put<8 * G + 4, W * XS + G * 512 + 2560>();
            if (T2) {
                put<B, 2 * XS + G * 512>();
                put<B + 4, 2 * XS + G * 512 + 2560>();
            }
            if (G == 4 && sig) nb_arrive<NB_ODONE, 288>();
        }
    }
    template <int G>
    __device__ __forceinline__ void step(uint32_t sb) {
        half<G, 0>(sb);
        half<G, 1>(sb);
    }
    __device__ __forceinline__ void clear() {
#pragma unroll
        for (int i = 0; i < N; i++) v[i] = 0;
        gp = nullptr;
        pend = 0;
        sig = 0;
    }
};

template <int W, int KK>
__device__ __forceinline__ void qproj(float (&q0)[80], float (&q1)[80], uint32_t sb, Ring& r, uint32_t pslot, uint32_t phm,
                                      PendO<W>& po, const Params& P, int it) {
    const uint32_t loR = ((sb + OFF_R) >> 4) | LO_LBO1;
    const uint32_t loRing = ((sb + OFF_RING) >> 4) | LO_LBO1;
    auto ready = [&](int k) {
        mbar_wait(sb + BAR_RFULL + r.slot * 8, r.ph, r.dl);
        mbar_wait(sb + BAR_XFULL + (k % 5) * 8, ((phm >> (k % 5)) ^ (k / 5)) & 1, r.dl);
    };
    auto release = [&]() {
        if (KK > 0) {
            wg_wait<1>();
            mbar_arrive_warp(sb + BAR_REMPTY + pslot * 8);
            if (KK <= 5) mbar_arrive_warp(sb + (BAR_XEMPTY + (KK - 1) * 8));
        }
    };
    if (KK == 0) ready(0);
    if (W == 1 && KK == QHOLD) nb_sync<NB_SDONE, 256>();
    const uint32_t a = loRing + r.slot * (SLOT >> 4) + (W == 0 ? 0 : 1024), b = loR + (KK % 5) * (XS >> 4);
    wg_fence();
    wgmma<1, 0, HI_SW128, KK != 0>(q0, a, b);
    if (W == 0) wgmma<1, 0, HI_SW128, KK != 0>(q1, a + 512, b);
#pragma unroll
    for (int k = 1; k < 4; k++) {
        wgmma<1, 0, HI_SW128, true>(q0, a + k * 128, b + k * 2);
        if (W == 0) wgmma<1, 0, HI_SW128, true>(q1, a + 512 + k * 128, b + k * 2);
    }
    wg_commit();
    const uint32_t cslot = r.slot;
    r.adv(1);
    if (W == 0 || KK < QHOLD) release();
    if (KK == QST0) {
        po.verdict(P, sb, it - 1);
        po.template half<0, 0>(sb);
    }
    if (KK < 9) ready(KK + 1);
    if (W == 1 && KK >= QHOLD) release();
    if (W == 1 && KK == 7) nb_arrive<NB_PDONE, 256>();
    if (KK == QST0) po.template half<0, 1>(sb);
    if constexpr (KK > QST0 && KK < QST0 + 5) po.template step<KK - QST0>(sb);
    if constexpr (KK < 9) {
        qproj<W, KK + 1>(q0, q1, sb, r, cslot, phm, po, P, it);
    } else {
        if (W == 0) nb_arrive<NB_SDONE, 256>();
        wg_wait<0>();
        reg_fence(q0);
        if (W == 0) reg_fence(q1);
        mbar_arrive_warp(sb + BAR_REMPTY + cslot * 8);
    }
}

template <int NR>
__device__ __forceinline__ void opack(const float (&o)[NR], uint32_t* v) {
#pragma unroll
    for (int g = 0; g < NR / 16; g++)
#pragma unroll
        for (int hh = 0; hh < 2; hh++)
#pragma unroll
            for (int t = 0; t < 4; t++) v[8 * g + 4 * hh + t] = pack_bf16(o[16 * g + 4 * t + 2 * hh], o[16 * g + 4 * t + 2 * hh + 1]);
}

template <int NR>
__device__ __forceinline__ void dump_acc(const float (&c)[NR], float4* p) {
#pragma unroll
    for (int i = 0; i < NR / 4; i++) p[i * 128] = make_float4(c[4 * i], c[4 * i + 1], c[4 * i + 2], c[4 * i + 3]);
}
__device__ __forceinline__ void wait_flag(const unsigned int* f, uint32_t epoch) {
    uint32_t v, n = 0;
    do {
        asm volatile("ld.acquire.gpu.global.u32 %0, [%1];" : "=r"(v) : "l"(f) : "memory");
        if (++n > 0x1000000) __trap();
    } while (v != epoch);
}

template <bool IS_S>
__device__ __forceinline__ void op_item(uint32_t e, uint32_t sb, Ring& r, uint32_t& phm) {
    constexpr int T0 = IS_S ? 0 : 2;
    constexpr uint32_t BOFF = IS_S ? (3 * 512) >> 4 : 0;
    const uint32_t loRing = ((sb + OFF_RING) >> 4) | LO_LBO1;
    const uint32_t loO = ((sb + OFF_R) >> 4) | LO_OST;
    float c0[80], c1[80], c2[IS_S ? 32 : 48];
    const int T2 = 6 * (IT_H1(e) - IT_H0(e));
    uint32_t xs = 0;
    auto step = [&](auto first, uint32_t hf) {
        constexpr bool F = decltype(first)::value;
        if (hf == 0) {
            mbar_wait(sb + BAR_XFULL + xs * 8, (phm >> xs) & 1, r.dl);
            phm ^= 1u << xs;
        }
        mbar_wait(sb + BAR_RFULL + r.slot * 8, r.ph, r.dl);
        const uint32_t a = loRing + r.slot * (SLOT >> 4), b = loO + xs * (XS >> 4) + hf * 640;
        wg_fence();
        wgmma<1, 1, HI_OST, !F>(c0, a + T0 * 256, b);
        wgmma<1, 1, HI_OST, !F>(c1, a + T0 * 256 + 256, b);
        wgmma<1, 1, HI_OST, !F>(c2, a + 1024, b + BOFF);
        wgmma<1, 1, HI_OST, true>(c0, a + T0 * 256 + 128, b + 320);
        wgmma<1, 1, HI_OST, true>(c1, a + T0 * 256 + 384, b + 320);
        wgmma<1, 1, HI_OST, true>(c2, a + 1024 + 128, b + 320 + BOFF);
        wg_commit();
    };
    step(TrueT{}, 0);
#pragma unroll 1
    for (int t = 1; t < T2; t++) {
        const uint32_t pslot = r.slot, pxs = xs;
        r.adv(1);
        if ((t & 1) == 0 && ++xs == 5) xs = 0;
        step(FalseT{}, t & 1);
        wg_wait<1>();
        mbar_arrive_warp(sb + BAR_REMPTY + pslot * 8);
        if ((t & 1) == 0 && t + 8 < T2) mbar_arrive_warp(sb + BAR_XEMPTY + pxs * 8);
    }
    wg_wait<0>();
    reg_fence(c0);
    reg_fence(c1);
    reg_fence(c2);
    mbar_arrive_warp(sb + BAR_REMPTY + r.slot * 8);
    r.adv(1);
    if (IT_PART(e)) {
#pragma unroll
        for (int m = 0; m < 5; m++) mbar_arrive_warp(sb + BAR_XEMPTY + m * 8);
        float4* pp = g_part + (size_t)((IT_BR(e) * 16 + IT_B(e)) * 10 + IT_HALF(e) * 5) * 2560 + (tid_now() & 127);
        dump_acc(c0, pp + T0 * 2560);
        dump_acc(c1, pp + (T0 + 1) * 2560);
        dump_acc(c2, pp + 4 * 2560 + (IS_S ? 12 * 128 : 0));
    } else {
        nb_sync<NB_OPEND, 256>();
        const uint32_t tid = tid_now(), lane = tid & 31, w = (tid >> 5) & 3;
        store_out_tile(c0, sb + OFF_R + T0 * XS, lane, w);
        store_out_tile(c1, sb + OFF_R + (T0 + 1) * XS, lane, w);
        store_out_tile(c2, sb + OFF_R + 4 * XS + (IS_S ? 96 * 128 : 0), lane, w);
        fence_async_smem();
    }
    nb_arrive<NB_ODONE, 288>();
}

template <int W>
__device__ __forceinline__ void on_item(uint32_t e, uint32_t sb, Ring& r, uint32_t& phm, uint32_t epoch) {
    const uint32_t loRing = ((sb + OFF_RING) >> 4) | LO_LBO1;
    const uint32_t loO = ((sb + OFF_R) >> 4) | LO_OST;
    float c[80];
    const int T = 3 * (IT_H1(e) - IT_H0(e));
    uint32_t xs = 0;
    auto step = [&](auto first) {
        constexpr bool F = decltype(first)::value;
        mbar_wait(sb + BAR_XFULL + xs * 8, (phm >> xs) & 1, r.dl);
        phm ^= 1u << xs;
        mbar_wait(sb + BAR_RFULL + r.slot * 8, r.ph, r.dl);
        const uint32_t a = loRing + r.slot * (SLOT >> 4) + W * 512, b = loO + xs * (XS >> 4);
        wg_fence();
        wgmma<1, 1, HI_OST, !F>(c, a, b);
#pragma unroll
        for (int k = 1; k < 4; k++) wgmma<1, 1, HI_OST, true>(c, a + k * 128, b + k * 320);
        wg_commit();
    };
    auto run = [&](int t0, int t1) {
#pragma unroll 1
        for (int t = t0; t < t1; t++) {
            const uint32_t pslot = r.slot, pxs = xs;
            r.adv(1);
            if (++xs == 5) xs = 0;
            step(FalseT{});
            wg_wait<1>();
            mbar_arrive_warp(sb + BAR_REMPTY + pslot * 8);
            mbar_arrive_warp_if(sb + BAR_XEMPTY + pxs * 8, t + 4 < T);
        }
    };
    step(TrueT{});
    const int tm = T - 3;
    run(1, tm);
    float4 pv[20];
    {
        const uint32_t tile = 2 * IT_HALF(e) + W, bb = IT_BR(e) * 16 + IT_B(e);
        wait_flag(&g_pflag[bb * 2 + (tile >= 5)], epoch);
        const float4* pp = g_part + (size_t)(bb * 10 + tile) * 2560 + (tid_now() & 127);
#pragma unroll
        for (int i = 0; i < 20; i++) pv[i] = __ldcg(pp + i * 128);
    }
    run(tm, T);
    wg_wait<0>();
    reg_fence(c);
    mbar_arrive_warp(sb + BAR_REMPTY + r.slot * 8);
    r.adv(1);
    nb_sync<NB_OPEND, 256>();
#pragma unroll
    for (int i = 0; i < 20; i++) {
        c[4 * i] += pv[i].x;
        c[4 * i + 1] += pv[i].y;
        c[4 * i + 2] += pv[i].z;
        c[4 * i + 3] += pv[i].w;
    }
    const uint32_t tid = tid_now();
    store_out_tile(c, sb + OFF_R + W * XS, tid & 31, (tid >> 5) & 3);
    fence_async_smem();
    nb_arrive<NB_ODONE, 288>();
}

template <int W>
__device__ __forceinline__ uint32_t qa_item(const Params& P, uint32_t e, uint32_t sb, Ring& r, uint32_t phm, PendO<W>& po, int it) {
    const uint32_t loR = ((sb + OFF_R) >> 4) | LO_LBO1;
    const uint32_t loRing = ((sb + OFF_RING) >> 4) | LO_LBO1;
    uint32_t lane, sta;
    {
        float q0[80], q1[80];
        qproj<W, 0>(q0, q1, sb, r, 0, phm, po, P, it);
        const uint32_t tid = tid_now();
        lane = tid & 31;
        sta = sb + OFF_R + (lane >> 4) * 1024 + (lane & 7) * 128 + (((((tid >> 4) & 6) + ((lane >> 3) & 1)) ^ (lane & 7)) << 4);
        TSD(W, 1);
        if (W == 0) {
            nb_sync<NB_PDONE, 256>();
            store_tile_t(q0, sta);
            store_tile_t(q1, sta + XS);
        } else {
            store_tile_t(q0, sta + 2 * XS);
        }
    }
    fence_async_smem();
    float s[80], oa[80], ob[W == 0 ? 32 : 48], l[10];
    zero(oa);
    zero(ob);
    zero(l);
    reg_fence(oa);
    reg_fence(ob);
    auto pv = [&](const Ring& rv, uint32_t buf) {
        mbar_wait(sb + BAR_RFULL + rv.slot * 8, rv.ph, rv.dl);
        const uint32_t a = loRing + rv.slot * (SLOT >> 4), b = loR + (3 + buf) * (XS >> 4);
        wg_fence();
#pragma unroll
        for (int k = 0; k < 4; k++) {
            wgmma<1, 0, HI_SW128, true>(oa, a + W * 512 + k * 128, b + k * 2);
            wgmma<1, 0, HI_SW128, true>(ob, a + 1024 + k * 128, b + (W == 0 ? (96 * 128) >> 4 : 0) + k * 2);
        }
        wg_commit();
    };
    float mref;
    uint32_t kslot, vslot;
    auto tail = [&](bool rel_other, int i) {
        uint32_t ps[40];
        exp_block<0>(s, ps, sta + (3 + W) * XS, mref);
        if (rel_other) {
            wg_wait<0>();
            mbar_arrive_warp(sb + BAR_REMPTY + vslot * 8);
            if (W == 1) mbar_arrive_warp_if(sb + BAR_XEMPTY + 24, i == 3);
        }
        fence_async_smem();
        nb_arrive<NB_PFULL + W, 256>();
        TSD(W, 6 + 5 * i);
        if (W == 1) {
            if (XLATE >= 2) mbar_arrive_warp_if<2>(sb + BAR_XEMPTY + 8, i == 3);
            if (XLATE >= 1) mbar_arrive_warp_if<2>(sb + BAR_XEMPTY + 16, i == 3);
        }
        if (rel_other || !PV0FIRST) {
            mbar_wait(sb + BAR_RFULL + r.slot * 8, r.ph, r.dl);
            sum_block(ps, l, lane);
        }
        TSD(W, 7 + 5 * i);
        nb_sync<NB_W + W, 128>();
        pv(r, W);
        if (!rel_other && PV0FIRST) sum_block(ps, l, lane);
        TSD(W, 8 + 5 * i);
    };
    if (W == 0) {
        sts_u(sb + OFF_GM + 4, r.slot);
        mbar_wait(sb + BAR_RFULL + r.slot * 8, r.ph, r.dl);
        nb_sync<NB_QK, 160>();
        TSD(W, 2);
        wg_fence();
        qk_steps<0, 8>(s, loRing + r.slot * (SLOT >> 4), loR);
        nb_sync<NB_Q2, 288>();
        qk_steps<8, 12>(s, loRing + r.slot * (SLOT >> 4), loR);
        wg_commit();
        nb_arrive<NB_Q01, 256>();
        TSD(W, 4);
        nb_sync<NB_REF, 160>();
        mref = __uint_as_float(lds_u(sb + OFF_GM));
        wg_wait<0>();
        reg_fence(s);
        mbar_arrive_warp<2>(sb + BAR_REMPTY + r.slot * 8);
        r.adv(2);
        TSD(W, 5);
        tail(false, 0);
    } else {
        nb_arrive<NB_Q2, 288>();
        TSD(W, 2);
        nb_sync<NB_Q01, 256>();
    }
#pragma unroll 1
    for (int i = (W == 0 ? 1 : 0); i < 4; i++) {
        const uint32_t pvslot = r.slot;
        r.adv(1);
        kslot = r.slot;
        mbar_wait(sb + BAR_RFULL + r.slot * 8, r.ph, r.dl);
        wg_fence();
        qk_steps<0, 12>(s, loRing + r.slot * (SLOT >> 4), loR);
        wg_commit();
        wg_wait<1>();
        mbar_arrive_warp_if(sb + BAR_REMPTY + pvslot * 8, W == 0 || i > 0);
        r.adv(1);
        vslot = r.slot;
        TSD(W, 4 + 5 * i);
        nb_sync<NB_PFULL + (W ^ 1), 256>();
        pv(r, W ^ 1);
        if (W == 1) mref = __uint_as_float(lds_u(sb + OFF_GM));
        wg_wait<1>();
        reg_fence(s);
        mbar_arrive_warp<2>(sb + BAR_REMPTY + kslot * 8);
        if (W == 1) {
            mbar_arrive_warp_if<2>(sb + BAR_XEMPTY + 0, i == 3);
            if (XLATE < 2) mbar_arrive_warp_if<2>(sb + BAR_XEMPTY + 8, i == 3);
            if (XLATE < 1) mbar_arrive_warp_if<2>(sb + BAR_XEMPTY + 16, i == 3);
        }
        r.adv(W == 1 && i == 3 ? 1 : 2);
        TSD(W, 5 + 5 * i);
        tail(true, i);
    }
    const uint32_t w = (tid_now() >> 5) & 3;
    const uint32_t lxa = sb + OFF_LX + w * 640 + (((lane & 8) ? 80 : 0) + ((lane >> 1) & 8) + 2 * (lane & 3) + ((lane >> 2) & 1)) * 4;
    const uint32_t nx = get_item_warp(sb, it + 1, r.dl);
    po.gp = ostash(IT_BR(e), IT_B(e), IT_H0(e)) + po.toff();
    po.sig = 1;
    if (W == 0) {
        sum_store<false>(l, lane, lxa);
        nb_arrive<NB_LX, 256>();
        wg_wait<0>();
        mbar_arrive_warp(sb + BAR_REMPTY + r.slot * 8);
        mbar_arrive_warp(sb + BAR_XEMPTY + 24);
        r.adv(1);
        nb_sync<NB_PFULL + 1, 256>();
        pv(r, 1);
    } else {
        nb_sync<NB_LX, 256>();
        sum_store<true>(l, lane, lxa);
        nb_arrive<NB_L, 160>();
    }
    TSD(W, 24);
    wg_wait<0>();
    reg_fence(oa);
    reg_fence(ob);
    mbar_arrive_warp(sb + BAR_REMPTY + r.slot * 8);
    mbar_arrive_warp(sb + BAR_XEMPTY + 32);
    r.adv(1);
    opack(ob, po.v + 40);
    opack(oa, po.v);
    return nx;
}

template <int W>
__device__ __forceinline__ void consumer(const Params& P, uint32_t sb, uint32_t dl) {
    int it = 0;
    if (W == 0) TS(0, 30);
    Ring r{0, 0, dl};
    uint32_t phm = 0;
    uint32_t e = get_item_warp(sb, 0, dl);
#pragma unroll 1
    while (e != 0) {
        if (IT_TYPE(e) == IT_QA) {
            PendO<W> po;
            po.clear();
#pragma unroll 1
            do {
                TS(W, 0);
                e = qa_item<W>(P, e, sb, r, phm, po, it);
                TS(W, 31);
                it++;
            } while (IT_TYPE(e) == IT_QA);
            po.verdict(P, sb, it - 1);
            po.template step<0>(sb);
            po.template step<1>(sb);
            po.template step<2>(sb);
            po.template step<3>(sb);
            po.template step<4>(sb);
        } else {
            TS(W, 0);
            if (IT_TYPE(e) == IT_OP) op_item<W == 0>(e, sb, r, phm);
            else on_item<W>(e, sb, r, phm, lds_u(sb + OFF_FB + 4));
            TS(W, 31);
            e = get_item_warp(sb, ++it, dl);
        }
    }
    TS_DUMP(W);
}

__global__ void __launch_bounds__(384, 1) fused_kernel(const __grid_constant__ Params P) {
    extern __shared__ __align__(1024) unsigned char smem_raw[];
    const uint32_t sb = (uint32_t)__cvta_generic_to_shared(smem_raw);
    const uint32_t wgid = __shfl_sync(0xffffffffu, threadIdx.x >> 7, 0);
    const uint32_t cta = blockIdx.x;
    const uint32_t dl = deadline();

    uint32_t epoch = 0;
    if (wgid == 0) epoch = *(volatile unsigned int*)&g_epoch[cta] + 1;
    if (threadIdx.x == 0) {
        if (sb & 1023) __trap();
        sts_u(sb + OFF_FB + 4, epoch);
        for (int i = 0; i < NSLOT; i++) {
            mbar_init(sb + BAR_RFULL + i * 8, 1);
            mbar_init(sb + BAR_REMPTY + i * 8, 8);
            mbar_init(sb + BAR_XFULL + i * 8, 1);
            mbar_init(sb + BAR_XEMPTY + i * 8, 8);
        }
        for (int i = 0; i < MAXI; i++) mbar_init(sb + BAR_ITEM + i * 8, 1);
        asm volatile("fence.mbarrier_init.release.cluster;" ::: "memory");
        fence_async_smem();
    }
    __syncthreads();

    if (wgid == 0) {
        asm volatile("setmaxnreg.dec.sync.aligned.u32 24;");
        const uint32_t warp = __shfl_sync(0xffffffffu, threadIdx.x >> 5, 0);
        if (warp == 0) {
            if (threadIdx.x == 0) {
                *(volatile unsigned int*)&g_epoch[cta] = epoch;
                const uint64_t pol_first = mkpol<1>(), pol_norm = mkpol<POL_W>();
                if (cta == 0) *(volatile unsigned int*)&g_ticket[(epoch + 1) & 1] = 0;
                Ring r{0, 1, dl};
                {
                    const uint32_t d = P.delay[cta];
                    uint32_t t0, t1;
                    asm volatile("mov.u32 %0, %%clock;" : "=r"(t0));
                    do {
                        asm volatile("mov.u32 %0, %%clock;" : "=r"(t1));
                    } while (t1 - t0 < d);
                }
                uint32_t e = P.items[cta][0];
#pragma unroll 1
                for (int it = 0;; it++) {
                    sts_u(sb + OFF_ITEM + it * 4, e);
                    asm volatile("mbarrier.arrive.shared::cta.b64 _, [%0];" ::"r"(sb + BAR_ITEM + it * 8) : "memory");
                    if (e == 0) break;
                    uint32_t nx = P.items[cta][it + 1 < NSTAT ? it + 1 : NSTAT - 1];
                    if (IT_TYPE(e) == IT_ON || it + 2 == MAXI) nx = 0;
                    uint32_t tk = 0;
                    const uint32_t br = IT_BR(e);
                    if (IT_TYPE(e) == IT_QA) {
                        const uint32_t h = IT_H0(e);
#pragma unroll 1
                        for (int kk = 0; kk < 10; kk++) {
                            mbar_wait(sb + BAR_REMPTY + r.slot * 8, r.ph, r.dl);
                            mbar_expect(sb + BAR_RFULL + r.slot * 8, SLOT);
                            tma3(sb + OFF_RING + r.slot * SLOT, &P.wq[br], kk * 64, h * 3, sb + BAR_RFULL + r.slot * 8, pol_norm);
                            r.adv(1);
                        }
                        const int row0 = (IT_B(e) * 32 + h) * 512;
#pragma unroll 1
                        for (int n = 0; n < 16; n++) {
                            if (n == 13 && nx == IT_DYN) tk = atomicAdd(&g_ticket[epoch & 1], 1);
                            const bool isv = n == 15 || (n > 0 && !(n & 1));
                            const int j = n == 15 ? 7 : isv ? (n - 2) >> 1 : (n + 1) >> 1;
                            mbar_wait(sb + BAR_REMPTY + r.slot * 8, r.ph, r.dl);
                            mbar_expect(sb + BAR_RFULL + r.slot * 8, SLOT);
                            tma3(sb + OFF_RING + r.slot * SLOT, isv ? &P.v[br] : &P.k[br], row0 + j * 64, 0,
                                 sb + BAR_RFULL + r.slot * 8, pol_first);
                            r.adv(1);
                        }
                    } else {
                        const int r0 = IT_H0(e) * 192, r1 = IT_H1(e) * 192;
                        const bool wide = IT_TYPE(e) == IT_OP;
#pragma unroll 1
                        for (int row = r0; row < r1; row += wide ? 32 : 64) {
                            mbar_wait(sb + BAR_REMPTY + r.slot * 8, r.ph, r.dl);
                            mbar_expect(sb + BAR_RFULL + r.slot * 8, wide ? XS : 16384);
                            tma3(sb + OFF_RING + r.slot * SLOT, wide ? &P.wo[br] : &P.won[br], row, IT_HALF(e) * (wide ? 5 : 2),
                                 sb + BAR_RFULL + r.slot * 8, pol_norm);
                            r.adv(1);
                        }
                        if (nx == IT_DYN) tk = atomicAdd(&g_ticket[epoch & 1], 1);
                    }
                    if (nx == IT_DYN) nx = tk < P.nlist ? P.list[tk] : 0;
                    e = nx;
                }
            }
        } else if (warp == 1) {
            if (threadIdx.x == 32) {
                const uint64_t pol_norm = mkpol<POL_X>(), pol_o = mkpol<POL_O>();
                uint32_t phm = 0x1f;
#pragma unroll 1
                for (int it = 0;; it++) {
                    const uint32_t e = get_item(sb, it, dl);
                    if (e == 0) break;
                    const uint32_t br = IT_BR(e);
                    uint32_t xs = 0;
                    if (IT_TYPE(e) == IT_QA) {
#pragma unroll 1
                        for (int kk = 0; kk < 10; kk++) {
                            mbar_wait(sb + BAR_XEMPTY + xs * 8, (phm >> xs) & 1, dl);
                            phm ^= 1u << xs;
                            mbar_expect(sb + BAR_XFULL + xs * 8, XS);
                            tma3(sb + OFF_R + xs * XS, &P.x[br], IT_B(e) * 160, kk, sb + BAR_XFULL + xs * 8, pol_norm);
                            if (++xs == 5) xs = 0;
                        }
                    } else {
                        const uint32_t u0 = (br * 16 + IT_B(e)) * 32;
#pragma unroll 1
                        for (uint32_t u = u0 + IT_H0(e); u < u0 + IT_H1(e); u++) {
                            wait_flag(&g_flag[u], epoch);
                            asm volatile("fence.proxy.async;" ::: "memory");
#pragma unroll 1
                            for (int t = 0; t < 3; t++) {
                                mbar_wait(sb + BAR_XEMPTY + xs * 8, (phm >> xs) & 1, dl);
                                phm ^= 1u << xs;
                                mbar_expect(sb + BAR_XFULL + xs * 8, XS);
                                bulk_load(sb + OFF_R + xs * XS, ostash(br, IT_B(e), u & 31) + t * XS, XS, sb + BAR_XFULL + xs * 8, pol_o);
                                if (++xs == 5) xs = 0;
                            }
                        }
                    }
                }
            }
        } else if (warp == 2) {
#pragma unroll 1
            for (int it = 0;; it++) {
                const uint32_t e = get_item_warp(sb, it, dl);
                if (e == 0) break;
                nb_sync<NB_ODONE, 288>();
                if (threadIdx.x == 64) {
                    const uint32_t bb = IT_BR(e) * 16 + IT_B(e);
                    if (IT_TYPE(e) == IT_QA || IT_PART(e)) {
                        __threadfence();
                        unsigned int* f = IT_TYPE(e) == IT_QA ? &g_flag[bb * 32 + IT_H0(e)] : &g_pflag[bb * 2 + IT_HALF(e)];
                        asm volatile("st.relaxed.gpu.global.u32 [%0], %1;" ::"l"(f), "r"(epoch) : "memory");
                    } else {
                        const int nt = IT_TYPE(e) == IT_OP ? 5 : 2;
                        const int cc0 = IT_BR(e) * 640 + IT_HALF(e) * nt * 64;
#pragma unroll
                        for (int m = 0; m < 5; m++) {
                            if (m < nt)
                                asm volatile("cp.async.bulk.tensor.2d.global.shared::cta.bulk_group [%0, {%2,%3}], [%1];" ::"l"(&P.out),
                                             "r"(sb + OFF_R + m * XS), "r"(cc0 + m * 64), "r"((int)IT_B(e) * 160)
                                             : "memory");
                            asm volatile("cp.async.bulk.commit_group;" ::: "memory");
                        }
#define REL(N)                                                          \
    asm volatile("cp.async.bulk.wait_group.read %0;" ::"n"(4 - N) : "memory"); \
    asm volatile("mbarrier.arrive.shared::cta.b64 _, [%0], 8;" ::"r"(sb + BAR_XEMPTY + N * 8) : "memory");
                        REL(0) REL(1) REL(2) REL(3) REL(4)
#undef REL
                    }
                }
                __syncwarp();
            }
            if (threadIdx.x == 64) asm volatile("cp.async.bulk.wait_group 0;" ::: "memory");
        } else {
            const uint32_t lane = threadIdx.x & 31, p = lane >> 2;
#pragma unroll 1
            for (int it = 0;; it++) {
                const uint32_t e = get_item_warp(sb, it, dl);
                if (e == 0) break;
                if (IT_TYPE(e) != IT_QA) continue;
                nb_sync<NB_QK, 160>();
                const uint32_t co = (((lane & 3) * 2) ^ p) << 4;
                const uint32_t ka = sb + OFF_RING + lds_u(sb + OFF_GM + 4) * SLOT + p * (9 * 128) + co;
                const uint32_t qa = sb + OFF_R + p * (17 * 128) + co;
                uint32_t acc = 0;
#pragma unroll
                for (int c = 0; c < 6; c++) {
                    if (c == 4) nb_sync<NB_Q2, 288>();
                    const uint4 kv = lds_u4((ka + (c >> 1) * 8192) ^ ((c & 1) << 4));
                    const uint4 qv = lds_u4((qa + (c >> 1) * XS) ^ ((c & 1) << 4));
                    acc = fma_bf2(kv.x, qv.x, fma_bf2(kv.y, qv.y, fma_bf2(kv.z, qv.z, fma_bf2(kv.w, qv.w, acc))));
                }
                float d = __uint_as_float(acc << 16) + __uint_as_float(acc & 0xffff0000u);
                d += __shfl_xor_sync(0xffffffffu, d, 1);
                d += __shfl_xor_sync(0xffffffffu, d, 2);
                int key = __float_as_int(d);
                key ^= (key >> 31) & 0x7fffffff;
                key = __reduce_max_sync(0xffffffffu, key);
                key ^= (key >> 31) & 0x7fffffff;
                sts_f(sb + OFF_GM, __int_as_float(key) * SM_C);
                nb_arrive<NB_REF, 160>();
                nb_sync<NB_L, 160>();
                bool bad = false;
#pragma unroll
                for (int c = 0; c < 5; c++) {
                    const uint32_t la = sb + OFF_LX + (c * 32 + lane) * 4;
                    const float v = (__uint_as_float(lds_u(la)) + __uint_as_float(lds_u(la + 640))) +
                                    (__uint_as_float(lds_u(la + 1280)) + __uint_as_float(lds_u(la + 1920)));
                    const float inv = __fdividef(1.f, v);
                    const uint32_t hi = pack_bf16(inv, 0.f), lo = pack_bf16(inv - __uint_as_float(hi << 16), 0.f);
                    const uint32_t ia = sb + OFF_LINV + c * 128 + ((lane >> 1) & 3) * 32 + (lane >> 3) * 8 + (lane & 1) * 2;
                    asm volatile("st.shared.u16 [%0], %1;\nst.shared.u16 [%0+4], %2;" ::"r"(ia), "h"((unsigned short)hi), "h"((unsigned short)lo) : "memory");
                    bad |= !(v >= 5.421010862e-20f && v <= 1.8446744e19f);
                }
                sts_u(sb + OFF_FB, __any_sync(0xffffffffu, bad));
                nb_arrive<NB_VOTE, 160>();
                nb_arrive<NB_VOTE + 1, 160>();
            }
        }
    } else if (wgid == 1) {
        asm volatile("setmaxnreg.inc.sync.aligned.u32 240;");
        consumer<0>(P, sb, dl);
    } else {
        asm volatile("setmaxnreg.inc.sync.aligned.u32 240;");
        consumer<1>(P, sb, dl);
    }
}

typedef CUresult (*EncFn)(CUtensorMap*, CUtensorMapDataType, cuuint32_t, void*, const cuuint64_t*, const cuuint64_t*,
                          const cuuint32_t*, const cuuint32_t*, CUtensorMapInterleave, CUtensorMapSwizzle,
                          CUtensorMapL2promotion, CUtensorMapFloatOOBfill);

void make_map3(EncFn enc, CUtensorMap* m, void* p, uint64_t rows, uint64_t rowbytes, uint64_t nblk, uint32_t boxrows,
               uint32_t boxblk) {
    cuuint64_t dims[3] = {64, rows, nblk};
    cuuint64_t str[2] = {rowbytes, 128};
    cuuint32_t box[3] = {64, boxrows, boxblk};
    cuuint32_t es[3] = {1, 1, 1};
    enc(m, CU_TENSOR_MAP_DATA_TYPE_BFLOAT16, 3, p, dims, str, box, es, CU_TENSOR_MAP_INTERLEAVE_NONE,
        CU_TENSOR_MAP_SWIZZLE_128B, CU_TENSOR_MAP_L2_PROMOTION_NONE, CU_TENSOR_MAP_FLOAT_OOB_FILL_NONE);
}

constexpr int tune(const char*, int def) { return def; }

void build_schedule(Params& P) {
    const int mode = tune("MODE", 4), dmax = tune("DMAX", 27000), n0 = tune("N0", 0);
    const int hmin = tune("HMIN", 19), hmax = tune("HMAX", 25), off = tune("OFF", 0), slope = tune("SLOPE", 1744);
    const int ng = tune("NG", 0), d0 = tune("D0", 0), nkeep = tune("NKEEP", 0), odmax = tune("ODMAX", 0);
    int u = 0;
    auto unit = [&]() {
        const uint32_t e = mk_item(IT_QA, u >> 9, u & 15, (u >> 4) & 31, 0, 0);
        u++;
        return e;
    };
    int qa[NCTA], nq = 0, op[NCTA], no = 0;
    for (int c = 0; c < NCTA; c++) {
        P.delay[c] = 0;
        for (int i = 0; i < NSTAT; i++) P.items[c][i] = 0;
        if (mode >= 3 && c < 128 && (c & 7) >= 6) op[no++] = c;
        else if (mode != 2 || (c & 3) == 0) qa[nq++] = c;
    }
    for (int t = 0; t < no; t++) {
        P.items[op[t]][0] = unit();
        P.items[op[t]][1] = mk_item(IT_OP, 0, t >> 1, 0, 32, t & 1);
        P.items[op[t]][2] = P.items[op[t]][3] = IT_DYN;
        P.delay[op[t]] = (t >> 1) * odmax / 16;
    }
    for (int k = 0; k < nq; k++) {
        const int c = qa[(k * 37) % nq];
        P.items[c][0] = unit();
        P.items[c][1] = P.items[c][2] = P.items[c][3] = IT_DYN;
        P.delay[c] = k < n0 ? 0 : (int)((long long)dmax * (k + 1 - n0) / (nq - n0));
        if (ng) P.delay[c] = d0 + (k * ng / nq) * (dmax / ng);
    }
    int H[16], pos[16];
    for (int b = 0; b < 16; b++) {
        H[b] = hmin + ((hmax - hmin) * b + 7) / 15;
        pos[b] = 1092 + off - H[b] * slope / 100;
        if (b < nkeep && no) {
            pos[b] = -1;
            P.items[op[30 - 2 * b]][2] = mk_item(IT_OP, 1, b, 0, H[b], 0, 1);
            P.items[op[31 - 2 * b]][2] = mk_item(IT_OP, 1, b, 0, H[b], 1, 1);
        }
    }
    int n = 0;
    const int uend = mode == 2 ? 8 * nq : 1024;
    while (u < uend) {
        for (int b = 0; b < 16 && no; b++)
            if (pos[b] == u) {
                P.list[n++] = mk_item(IT_OP, 1, b, 0, H[b], 0, 1);
                P.list[n++] = mk_item(IT_OP, 1, b, 0, H[b], 1, 1);
            }
        P.list[n++] = unit();
    }
    if (no)
        for (int k = 0; k < 80; k++) P.list[n++] = mk_item(IT_ON, 1, k / 5, H[k / 5], 32, k % 5);
    P.nlist = n;
}

}

extern "C" void kernel_launch(void* const* d_in, const int* in_sizes, int n_in, void* d_out, int out_size) {
    static Params P;
    static bool init = false;
    if (!init) {
        EncFn enc = nullptr;
        cudaDriverEntryPointQueryResult qr;
        cudaGetDriverEntryPoint("cuTensorMapEncodeTiled", (void**)&enc, cudaEnableDefault, &qr);
        for (int i = 0; i < 2; i++) {
            P.px[i] = (const __nv_bfloat16*)d_in[5 * i + 0];
            P.pk[i] = (const __nv_bfloat16*)d_in[5 * i + 1];
            P.pv[i] = (const __nv_bfloat16*)d_in[5 * i + 2];
            P.pwq[i] = (const __nv_bfloat16*)d_in[5 * i + 3];
            make_map3(enc, &P.x[i], d_in[5 * i + 0], 2560, 1280, 10, 160, 1);
            make_map3(enc, &P.k[i], d_in[5 * i + 1], 16 * 32 * 512, 384, 3, 64, 3);
            make_map3(enc, &P.v[i], d_in[5 * i + 2], 16 * 32 * 512, 384, 3, 64, 3);
            make_map3(enc, &P.wq[i], d_in[5 * i + 3], 640, 12288, 96, 64, 3);
            make_map3(enc, &P.wo[i], d_in[5 * i + 4], 6144, 1280, 10, 32, 5);
            make_map3(enc, &P.won[i], d_in[5 * i + 4], 6144, 1280, 10, 64, 2);
        }
        cuuint64_t dims[2] = {1280, 2560};
        cuuint64_t str[1] = {2560};
        cuuint32_t box[2] = {64, 160};
        cuuint32_t es[2] = {1, 1};
        enc(&P.out, CU_TENSOR_MAP_DATA_TYPE_BFLOAT16, 2, d_out, dims, str, box, es, CU_TENSOR_MAP_INTERLEAVE_NONE,
            CU_TENSOR_MAP_SWIZZLE_128B, CU_TENSOR_MAP_L2_PROMOTION_NONE, CU_TENSOR_MAP_FLOAT_OOB_FILL_NONE);
        build_schedule(P);
        cudaFuncSetAttribute(fused_kernel, cudaFuncAttributeMaxDynamicSharedMemorySize, SMEM_LAUNCH);
        init = true;
    }
    fused_kernel<<<NCTA, 384, SMEM_LAUNCH>>>(P);
}
```

```cpp
#include <cuda_runtime.h>
#include <cuda.h>
#include <cuda_bf16.h>
#include <stdint.h>

namespace {

constexpr int NCTA = 132;
constexpr int MAXI = 16;
constexpr int NSTAT = 4;
constexpr uint32_t IT_DYN = 0xffffffffu;
constexpr int SLOT = 24576;
constexpr int NSLOT = 5;
constexpr int XS = 20480;
constexpr int OFF_R = 0;
constexpr int OFF_RING = 5 * XS;
constexpr int OFF_MISC = OFF_RING + NSLOT * SLOT;
constexpr int OFF_LX = OFF_MISC;
constexpr int OFF_LINV = OFF_LX + 2560;
constexpr int OFF_FB = OFF_LINV + 640;
constexpr int OFF_GM = OFF_FB + 16;
constexpr int OFF_BAR = OFF_GM + 16;
constexpr int BAR_RFULL = OFF_BAR;
constexpr int BAR_REMPTY = BAR_RFULL + 40;
constexpr int BAR_XFULL = BAR_REMPTY + 40;
constexpr int BAR_XEMPTY = BAR_XFULL + 40;
constexpr int BAR_ITEM = BAR_XEMPTY + 40;
constexpr int OFF_ITEM = BAR_ITEM + MAXI * 8;
constexpr int SMEM_BYTES = OFF_ITEM + MAXI * 4;
static_assert(SMEM_BYTES <= 232448, "smem");

constexpr int NB_W = 1  , NB_PFULL = 3  , NB_VOTE = 5  , NB_Q2 = 7, NB_SDONE = 8, NB_PDONE = 9,
              NB_L = 10, NB_REF = 11, NB_ODONE = 12, NB_OPEND = 13, NB_LX = 14, NB_Q01 = 15, NB_QK = 0  ;

constexpr uint32_t IT_QA = 1, IT_OP = 2, IT_ON = 3;
__host__ __device__ constexpr uint32_t mk_item(uint32_t type, uint32_t br, uint32_t b, uint32_t h0, uint32_t h1, uint32_t half,
                                               uint32_t part = 0) {
    return type | (br << 2) | (b << 3) | (h0 << 7) | (h1 << 13) | (half << 19) | (part << 22);
}
#define IT_TYPE(e) ((e) & 3u)
#define IT_BR(e) (((e) >> 2) & 1u)
#define IT_B(e) (((e) >> 3) & 15u)
#define IT_H0(e) (((e) >> 7) & 63u)
#define IT_H1(e) (((e) >> 13) & 63u)
#define IT_HALF(e) (((e) >> 19) & 7u)
#define IT_PART(e) (((e) >> 22) & 1u)

struct Params {
    CUtensorMap x[2], wq[2], k[2], v[2], wo[2], won[2], out;
    const __nv_bfloat16 *px[2], *pwq[2], *pk[2], *pv[2];
    uint32_t items[NCTA][NSTAT];
    uint32_t delay[NCTA];
    uint32_t nlist;
    uint32_t list[1024];
};

constexpr int OUNIT = 61440;
__device__ __align__(1024) unsigned char g_ostash[(size_t)1024 * OUNIT];
__device__ unsigned int g_flag[1024];
__device__ float4 g_part[2 * 16 * 10 * 2560];
__device__ unsigned int g_pflag[64];
#define ORING 64
__device__ __forceinline__ uint32_t ostash_off(uint32_t br, uint32_t b, uint32_t h) {
    return (((br * 32 + h) % ORING) * 16 + b) * OUNIT;
}
__device__ __forceinline__ unsigned char* ostash(uint32_t br, uint32_t b, uint32_t h) { return g_ostash + ostash_off(br, b, h); }
__device__ unsigned int g_epoch[NCTA];
__device__ unsigned int g_ticket[2];

constexpr int SMEM_LAUNCH = SMEM_BYTES;
#define TS(role, idx)
#define TS_ITEM(e)
#define TS_DUMP(role)
#define TSD(role, idx)

#define POL_W 2
#define POL_X 2
#define POL_O 2
template <int M>
__device__ __forceinline__ uint64_t mkpol() {
    uint64_t p;
    if (M == 0) asm volatile("createpolicy.fractional.L2::evict_normal.b64 %0, 1.0;" : "=l"(p));
    if (M == 1) asm volatile("createpolicy.fractional.L2::evict_first.b64 %0, 1.0;" : "=l"(p));
    if (M == 2) asm volatile("createpolicy.fractional.L2::evict_unchanged.b64 %0, 1.0;" : "=l"(p));
    if (M == 3) asm volatile("createpolicy.fractional.L2::evict_normal.L2::evict_unchanged.b64 %0, 0.25;" : "=l"(p));
    return p;
}
#define STSM_W 1
#define XLATE 2
#define PV0FIRST 1
#define QST0 1
#define QST1 2
#define QHOLD 7
constexpr float SM_C = 0.07216878364870322f * 1.4426950408889634f;

__device__ __forceinline__ uint32_t tid_now() {
    uint32_t t;
    asm volatile("mov.u32 %0, %%tid.x;" : "=r"(t));
    return t;
}
__device__ __forceinline__ void mbar_init(uint32_t a, uint32_t c) {
    asm volatile("mbarrier.init.shared::cta.b64 [%0], %1;" ::"r"(a), "r"(c) : "memory");
}
__device__ __forceinline__ void mbar_expect(uint32_t a, uint32_t b) {
    asm volatile("mbarrier.arrive.expect_tx.shared::cta.b64 _, [%0], %1;" ::"r"(a), "r"(b) : "memory");
}
template <int CNT = 1>
__device__ __forceinline__ void mbar_arrive_warp(uint32_t a) {
    if (CNT == 1)
        asm volatile("{\n.reg .pred p;\nelect.sync _|p, 0xffffffff;\n@p mbarrier.arrive.shared::cta.b64 _, [%0];\n}" ::"r"(a) : "memory");
    else
        asm volatile(
            "{\n.reg .pred p;\nelect.sync _|p, 0xffffffff;\n@p mbarrier.arrive.shared::cta.b64 _, [%0];\n"
            "@p mbarrier.arrive.shared::cta.b64 _, [%0];\n}" ::"r"(a)
            : "memory");
}
template <int CNT = 1>
__device__ __forceinline__ void mbar_arrive_warp_if(uint32_t a, bool cond) {
    if (CNT == 1)
        asm volatile(
            "{\n.reg .pred p, c;\nelect.sync _|p, 0xffffffff;\nsetp.ne.and.u32 c, %1, 0, p;\n"
            "@c mbarrier.arrive.shared::cta.b64 _, [%0];\n}" ::"r"(a), "r"((uint32_t)cond)
            : "memory");
    else
        asm volatile(
            "{\n.reg .pred p, c;\nelect.sync _|p, 0xffffffff;\nsetp.ne.and.u32 c, %1, 0, p;\n"
            "@c mbarrier.arrive.shared::cta.b64 _, [%0];\n@c mbarrier.arrive.shared::cta.b64 _, [%0];\n}" ::"r"(a), "r"((uint32_t)cond)
            : "memory");
}
__device__ __forceinline__ uint32_t deadline() {
    uint32_t c;
    asm volatile("mov.u32 %0, %%clock_hi;" : "=r"(c));
    return c + 4;
}
__device__ __forceinline__ void mbar_wait(uint32_t a, uint32_t ph, uint32_t dl) {
    asm volatile(
        "{\n.reg .pred p;\n.reg .u32 m;\n"
        "LOOP:\n"
        "mbarrier.try_wait.parity.shared::cta.b64 p, [%0], %1;\n"
        "@p bra DONE;\n"
        "mov.u32 m, %%clock_hi;\n"
        "setp.ne.u32 p, m, %2;\n"
        "@p bra LOOP;\n"
        "trap;\n"
        "DONE:\n}" ::"r"(a), "r"(ph), "r"(dl)
        : "memory");
}
template <int ID, int CNT>
__device__ __forceinline__ void nb_sync() { asm volatile("bar.sync %0, %1;" ::"n"(ID), "n"(CNT) : "memory"); }
template <int ID, int CNT>
__device__ __forceinline__ void nb_arrive() { asm volatile("bar.arrive %0, %1;" ::"n"(ID), "n"(CNT) : "memory"); }
__device__ __forceinline__ void fence_async_smem() { asm volatile("fence.proxy.async.shared::cta;" ::: "memory"); }

__device__ __forceinline__ void tma3(uint32_t dst, const CUtensorMap* m, int c1, int c2, uint32_t bar, uint64_t pol) {
    asm volatile(
        "cp.async.bulk.tensor.3d.shared::cluster.global.mbarrier::complete_tx::bytes.L2::cache_hint [%0], [%1, {%3,%4,%5}], [%2], %6;" ::"r"(dst),
        "l"(m), "r"(bar), "r"(0), "r"(c1), "r"(c2), "l"(pol)
        : "memory");
}
__device__ __forceinline__ void bulk_load(uint32_t dst, const void* src, uint32_t bytes, uint32_t bar, uint64_t pol) {
    asm volatile("cp.async.bulk.shared::cluster.global.mbarrier::complete_tx::bytes.L2::cache_hint [%0], [%1], %2, [%3], %4;" ::"r"(dst),
                 "l"(src), "r"(bytes), "r"(bar), "l"(pol)
                 : "memory");
}
__device__ __forceinline__ void wg_fence() { asm volatile("wgmma.fence.sync.aligned;" ::: "memory"); }
__device__ __forceinline__ void wg_commit() { asm volatile("wgmma.commit_group.sync.aligned;" ::: "memory"); }
template <int N>
__device__ __forceinline__ void wg_wait() { asm volatile("wgmma.wait_group.sync.aligned %0;" ::"n"(N) : "memory"); }

#define RW80(c, d) c(d[0]), c(d[1]), c(d[2]), c(d[3]), c(d[4]), c(d[5]), c(d[6]), c(d[7]), c(d[8]), c(d[9]), c(d[10]), c(d[11]), c(d[12]), c(d[13]), c(d[14]), c(d[15]), c(d[16]), c(d[17]), c(d[18]), c(d[19]), c(d[20]), c(d[21]), c(d[22]), c(d[23]), c(d[24]), c(d[25]), c(d[26]), c(d[27]), c(d[28]), c(d[29]), c(d[30]), c(d[31]), c(d[32]), c(d[33]), c(d[34]), c(d[35]), c(d[36]), c(d[37]), c(d[38]), c(d[39]), c(d[40]), c(d[41]), c(d[42]), c(d[43]), c(d[44]), c(d[45]), c(d[46]), c(d[47]), c(d[48]), c(d[49]), c(d[50]), c(d[51]), c(d[52]), c(d[53]), c(d[54]), c(d[55]), c(d[56]), c(d[57]), c(d[58]), c(d[59]), c(d[60]), c(d[61]), c(d[62]), c(d[63]), c(d[64]), c(d[65]), c(d[66]), c(d[67]), c(d[68]), c(d[69]), c(d[70]), c(d[71]), c(d[72]), c(d[73]), c(d[74]), c(d[75]), c(d[76]), c(d[77]), c(d[78]), c(d[79])
#define RW48(c, d) c(d[0]), c(d[1]), c(d[2]), c(d[3]), c(d[4]), c(d[5]), c(d[6]), c(d[7]), c(d[8]), c(d[9]), c(d[10]), c(d[11]), c(d[12]), c(d[13]), c(d[14]), c(d[15]), c(d[16]), c(d[17]), c(d[18]), c(d[19]), c(d[20]), c(d[21]), c(d[22]), c(d[23]), c(d[24]), c(d[25]), c(d[26]), c(d[27]), c(d[28]), c(d[29]), c(d[30]), c(d[31]), c(d[32]), c(d[33]), c(d[34]), c(d[35]), c(d[36]), c(d[37]), c(d[38]), c(d[39]), c(d[40]), c(d[41]), c(d[42]), c(d[43]), c(d[44]), c(d[45]), c(d[46]), c(d[47])
#define RW32(c, d) c(d[0]), c(d[1]), c(d[2]), c(d[3]), c(d[4]), c(d[5]), c(d[6]), c(d[7]), c(d[8]), c(d[9]), c(d[10]), c(d[11]), c(d[12]), c(d[13]), c(d[14]), c(d[15]), c(d[16]), c(d[17]), c(d[18]), c(d[19]), c(d[20]), c(d[21]), c(d[22]), c(d[23]), c(d[24]), c(d[25]), c(d[26]), c(d[27]), c(d[28]), c(d[29]), c(d[30]), c(d[31])

__device__ __forceinline__ void reg_fence(float (&d)[80]) { asm volatile("" : RW80("+f", d)::"memory"); }
__device__ __forceinline__ void reg_fence(float (&d)[48]) { asm volatile("" : RW48("+f", d)::"memory"); }
__device__ __forceinline__ void reg_fence(float (&d)[32]) { asm volatile("" : RW32("+f", d)::"memory"); }

template <int NR>
__device__ __forceinline__ void zero(float (&d)[NR]) {
#pragma unroll
    for (int i = 0; i < NR; i++) d[i] = 0.f;
}

constexpr uint32_t HI_SW128 = (1024u >> 4) | (1u << 30);
constexpr uint32_t HI_OST = (2560u >> 4) | (2u << 30);
constexpr uint32_t LO_LBO1 = (1u << 16);
constexpr uint32_t LO_OST = ((512u >> 4) << 16);

template <int TA, int TB, uint32_t HIB, int ACC>
__device__ __forceinline__ void wgmma(float (&d)[80], uint32_t loA, uint32_t loB) {
#define WG_ASM(SD)                                                          \
    "{\n.reg .b64 da, db;\nmov.b64 da, {%80, %82};\nmov.b64 db, {%81, %83};\n" \
    "wgmma.mma_async.sync.aligned.m64n160k16.f32.bf16.bf16 "               \
    "{%0,%1,%2,%3,%4,%5,%6,%7,%8,%9,%10,%11,%12,%13,%14,%15,%16,%17,%18,%19,%20,%21,%22,%23,%24,%25,%26,%27,%28,%29,%30,%31,%32,%33,%34,%35,%36,%37,%38,%39,%40,%41,%42,%43,%44,%45,%46,%47,%48,%49,%50,%51,%52,%53,%54,%55,%56,%57,%58,%59,%60,%61,%62,%63,%64,%65,%66,%67,%68,%69,%70,%71,%72,%73,%74,%75,%76,%77,%78,%79}, da, db, " SD ", 1, 1, %84, %85;\n}"
    if constexpr (ACC == 2)
        asm volatile(WG_ASM("0") : RW80("+f", d) : "r"(loA), "r"(loB), "n"(HI_SW128), "n"(HIB), "n"(TA), "n"(TB));
    else if constexpr (ACC == 1)
        asm volatile(WG_ASM("1") : RW80("+f", d) : "r"(loA), "r"(loB), "n"(HI_SW128), "n"(HIB), "n"(TA), "n"(TB));
    else
        asm volatile(WG_ASM("0") : RW80("=f", d) : "r"(loA), "r"(loB), "n"(HI_SW128), "n"(HIB), "n"(TA), "n"(TB));
#undef WG_ASM
}
template <int TA, int TB, uint32_t HIB, int ACC>
__device__ __forceinline__ void wgmma(float (&d)[48], uint32_t loA, uint32_t loB) {
#define WG_ASM(SD)                                                          \
    "{\n.reg .b64 da, db;\nmov.b64 da, {%48, %50};\nmov.b64 db, {%49, %51};\n" \
    "wgmma.mma_async.sync.aligned.m64n96k16.f32.bf16.bf16 "               \
    "{%0,%1,%2,%3,%4,%5,%6,%7,%8,%9,%10,%11,%12,%13,%14,%15,%16,%17,%18,%19,%20,%21,%22,%23,%24,%25,%26,%27,%28,%29,%30,%31,%32,%33,%34,%35,%36,%37,%38,%39,%40,%41,%42,%43,%44,%45,%46,%47}, da, db, " SD ", 1, 1, %52, %53;\n}"
    if constexpr (ACC == 1)
        asm volatile(WG_ASM("1") : RW48("+f", d) : "r"(loA), "r"(loB), "n"(HI_SW128), "n"(HIB), "n"(TA), "n"(TB));
    else
        asm volatile(WG_ASM("0") : RW48("=f", d) : "r"(loA), "r"(loB), "n"(HI_SW128), "n"(HIB), "n"(TA), "n"(TB));
#undef WG_ASM
}
template <int TA, int TB, uint32_t HIB, int ACC>
__device__ __forceinline__ void wgmma(float (&d)[32], uint32_t loA, uint32_t loB) {
#define WG_ASM(SD)                                                          \
    "{\n.reg .b64 da, db;\nmov.b64 da, {%32, %34};\nmov.b64 db, {%33, %35};\n" \
    "wgmma.mma_async.sync.aligned.m64n64k16.f32.bf16.bf16 "               \
    "{%0,%1,%2,%3,%4,%5,%6,%7,%8,%9,%10,%11,%12,%13,%14,%15,%16,%17,%18,%19,%20,%21,%22,%23,%24,%25,%26,%27,%28,%29,%30,%31}, da, db, " SD ", 1, 1, %36, %37;\n}"
    if constexpr (ACC == 1)
        asm volatile(WG_ASM("1") : RW32("+f", d) : "r"(loA), "r"(loB), "n"(HI_SW128), "n"(HIB), "n"(TA), "n"(TB));
    else
        asm volatile(WG_ASM("0") : RW32("=f", d) : "r"(loA), "r"(loB), "n"(HI_SW128), "n"(HIB), "n"(TA), "n"(TB));
#undef WG_ASM
}

__device__ __forceinline__ uint32_t pack_bf16(float lo, float hi) {
    uint32_t r;
    asm("cvt.rn.bf16x2.f32 %0, %1, %2;" : "=r"(r) : "f"(hi), "f"(lo));
    return r;
}
__device__ __forceinline__ float ex2(float x) {
    float r;
    asm("ex2.approx.ftz.f32 %0, %1;" : "=f"(r) : "f"(x));
    return r;
}
__device__ __forceinline__ void stsm4t(uint32_t a, uint32_t r0, uint32_t r1, uint32_t r2, uint32_t r3) {
    asm volatile("stmatrix.sync.aligned.m8n8.x4.trans.shared.b16 [%0], {%1,%2,%3,%4};" ::"r"(a), "r"(r0), "r"(r1), "r"(r2), "r"(r3)
                 : "memory");
}
__device__ __forceinline__ uint32_t lds_u(uint32_t a) {
    uint32_t v;
    asm volatile("ld.shared.u32 %0, [%1];" : "=r"(v) : "r"(a) : "memory");
    return v;
}
__device__ __forceinline__ uint4 lds_u4(uint32_t a) {
    uint4 v;
    asm volatile("ld.shared.v4.u32 {%0,%1,%2,%3}, [%4];" : "=r"(v.x), "=r"(v.y), "=r"(v.z), "=r"(v.w) : "r"(a) : "memory");
    return v;
}
__device__ __forceinline__ float2 lds_f2(uint32_t a) {
    float2 v;
    asm volatile("ld.shared.v2.f32 {%0,%1}, [%2];" : "=f"(v.x), "=f"(v.y) : "r"(a) : "memory");
    return v;
}
__device__ __forceinline__ void sts_f(uint32_t a, float v) { asm volatile("st.shared.f32 [%0], %1;" ::"r"(a), "f"(v) : "memory"); }
__device__ __forceinline__ void sts_u(uint32_t a, uint32_t v) { asm volatile("st.shared.u32 [%0], %1;" ::"r"(a), "r"(v) : "memory"); }
__device__ __forceinline__ void sts_f2(uint32_t a, float x, float y) {
    asm volatile("st.shared.v2.f32 [%0], {%1,%2};" ::"r"(a), "f"(x), "f"(y) : "memory");
}

__device__ __forceinline__ void store_tile_t(const float (&d)[80], uint32_t addr) {
#pragma unroll
    for (int j = 0; j < 10; j++)
        stsm4t(addr + j * 2048, pack_bf16(d[8 * j], d[8 * j + 1]), pack_bf16(d[8 * j + 2], d[8 * j + 3]),
               pack_bf16(d[8 * j + 4], d[8 * j + 5]), pack_bf16(d[8 * j + 6], d[8 * j + 7]));
}
template <int NR>
__device__ __forceinline__ void store_out_tile(const float (&d)[NR], uint32_t base, uint32_t lane, uint32_t w) {
    const uint32_t mi = lane >> 3, i = lane & 7;
    const uint32_t chunk = 2 * w + (mi & 1);
    const uint32_t q0 = 8 * (i >> 1) + 2 * (mi >> 1) + (i & 1);
    const uint32_t a0 = base + q0 * 128 + ((chunk ^ (q0 & 7)) << 4);
    const uint32_t a1 = base + (q0 + 4) * 128 + ((chunk ^ ((q0 + 4) & 7)) << 4);
#pragma unroll
    for (int j = 0; j < NR / 8; j++)
        stsm4t(((j & 1) ? a1 : a0) + (j >> 1) * 4096, pack_bf16(d[8 * j], d[8 * j + 1]), pack_bf16(d[8 * j + 2], d[8 * j + 3]),
               pack_bf16(d[8 * j + 4], d[8 * j + 5]), pack_bf16(d[8 * j + 6], d[8 * j + 7]));
}

struct TrueT { static constexpr bool value = true; };
struct FalseT { static constexpr bool value = false; };

template <int V>
struct IntT { static constexpr int value = V; };

__device__ __forceinline__ uint32_t get_item(uint32_t sb, int it, uint32_t dl) {
    mbar_wait(sb + BAR_ITEM + it * 8, 0, dl);
    return lds_u(sb + OFF_ITEM + it * 4);
}
__device__ __forceinline__ uint32_t get_item_warp(uint32_t sb, int it, uint32_t dl) {
    return __shfl_sync(0xffffffffu, get_item(sb, it, dl), 0);
}

struct Ring {
    uint32_t slot, ph, dl;
    __device__ __forceinline__ void adv(uint32_t k) {
        slot += k;
        if (slot >= NSLOT) { slot -= NSLOT; ph ^= 1; }
    }
};

template <int K>
__device__ __forceinline__ void qk_step(float (&s)[80], uint32_t loK, uint32_t loQ) {
    wgmma<0, 0, HI_SW128, K != 0>(s, loK + (K >> 2) * (8192 >> 4) + (K & 3) * 2, loQ + (K >> 2) * (XS >> 4) + (K & 3) * 2);
}
template <int K0, int K1>
__device__ __forceinline__ void qk_steps(float (&s)[80], uint32_t loK, uint32_t loQ) {
    if constexpr (K0 < K1) {
        qk_step<K0>(s, loK, loQ);
        qk_steps<K0 + 1, K1>(s, loK, loQ);
    }
}
__device__ __forceinline__ uint32_t add_bf2(uint32_t a, uint32_t b) {
    uint32_t r;
    asm("add.rn.bf16x2 %0, %1, %2;" : "=r"(r) : "r"(a), "r"(b));
    return r;
}
__device__ __forceinline__ uint32_t fma_bf2(uint32_t a, uint32_t b, uint32_t c) {
    uint32_t r;
    asm("fma.rn.bf16x2 %0, %1, %2, %3;" : "=r"(r) : "r"(a), "r"(b), "r"(c));
    return r;
}
template <int J>
__device__ __forceinline__ void exp_block(const float (&s)[80], uint32_t (&k)[40], uint32_t pa, float mref) {
    if constexpr (J < 10) {
#pragma unroll
        for (int i = 4 * J; i < 4 * J + 4; i++)
            k[i] = pack_bf16(ex2(fmaf(s[2 * i], SM_C, -mref)), ex2(fmaf(s[2 * i + 1], SM_C, -mref)));
#pragma unroll
        for (int i = 0; i < 4; i++)
            asm volatile("stmatrix.sync.aligned.m8n8.x1.trans.shared.b16 [%0], {%1};" ::"r"(((i & 1) ? pa ^ 16 : pa) + J * 2048 + (i >> 1) * 1024),
                         "r"(k[4 * J + i])
                         : "memory");
        exp_block<J + 1>(s, k, pa, mref);
    }
}
__device__ __forceinline__ void sum_block(const uint32_t (&k)[40], float (&l)[10], uint32_t lane) {
    const bool b4 = lane & 16, b3 = lane & 8;
    uint32_t ps[20], t[10];
#pragma unroll
    for (int j = 0; j < 20; j++) ps[j] = add_bf2(k[2 * j], k[2 * j + 1]);
#pragma unroll
    for (int j = 0; j < 10; j++)
        t[j] = add_bf2(b4 ? ps[2 * j + 1] : ps[2 * j], __shfl_xor_sync(0xffffffffu, b4 ? ps[2 * j] : ps[2 * j + 1], 16));
#pragma unroll
    for (int i = 0; i < 5; i++) {
        const uint32_t a = b3 ? t[i + 5] : t[i], b = __shfl_xor_sync(0xffffffffu, b3 ? t[i] : t[i + 5], 8);
        l[2 * i] += __uint_as_float(a << 16) + __uint_as_float(b << 16);
        l[2 * i + 1] += __uint_as_float(a & 0xffff0000u) + __uint_as_float(b & 0xffff0000u);
    }
}
template <bool ADD>
__device__ __forceinline__ void sum_store(const float (&l)[10], uint32_t lane, uint32_t lxa) {
    const bool b2 = lane & 4;
    float t[5];
#pragma unroll
    for (int i = 0; i < 5; i++) t[i] = ADD ? __uint_as_float(lds_u(lxa + i * 64)) : 0.f;
#pragma unroll
    for (int i = 0; i < 5; i++)
        sts_f(lxa + i * 64, t[i] + (b2 ? l[2 * i + 1] : l[2 * i]) + __shfl_xor_sync(0xffffffffu, b2 ? l[2 * i] : l[2 * i + 1], 4));
}

__device__ __forceinline__ void fallback_unit(const Params& P, uint32_t e, uint32_t tid) {
    const uint32_t lane = tid & 31, br = IT_BR(e), b = IT_B(e), h = IT_H0(e);
    const __nv_bfloat162* wq = (const __nv_bfloat162*)(P.pwq[br] + h * 192) + lane;
    const __nv_bfloat162* kp = (const __nv_bfloat162*)(P.pk[br] + (size_t)(b * 32 + h) * 512 * 192) + lane;
    const __nv_bfloat162* vp = (const __nv_bfloat162*)(P.pv[br] + (size_t)(b * 32 + h) * 512 * 192) + lane;
#pragma unroll 1
    for (uint32_t qi = 0; qi < 40; qi++) {
        const uint32_t q = 4 * qi + (tid >> 5);
        const __nv_bfloat16* xr = P.px[br] + (size_t)(b * 160 + q) * 640;
        float a[6] = {0.f, 0.f, 0.f, 0.f, 0.f, 0.f};
#pragma unroll 2
        for (int k = 0; k < 640; k++) {
            const float xv = __bfloat162float(xr[k]);
#pragma unroll
            for (int i = 0; i < 3; i++) {
                const float2 wv = __bfloat1622float2(wq[(size_t)k * 3072 + i * 32]);
                a[2 * i] = fmaf(xv, wv.x, a[2 * i]);
                a[2 * i + 1] = fmaf(xv, wv.y, a[2 * i + 1]);
            }
        }
#pragma unroll
        for (int i = 0; i < 6; i++) a[i] = __bfloat162float(__float2bfloat16(a[i]));
        auto score = [&](int key) {
            float d = 0.f;
#pragma unroll
            for (int i = 0; i < 3; i++) {
                const float2 kv = __bfloat1622float2(kp[key * 96 + i * 32]);
                d = fmaf(a[2 * i], kv.x, fmaf(a[2 * i + 1], kv.y, d));
            }
#pragma unroll
            for (int o = 16; o > 0; o >>= 1) d += __shfl_xor_sync(0xffffffffu, d, o);
            return d;
        };
        float m = -INFINITY, o[6] = {0.f, 0.f, 0.f, 0.f, 0.f, 0.f}, sum = 0.f;
#pragma unroll 1
        for (int n = 0; n < 1024; n++) {
            const int key = n & 511;
            const float d = score(key);
            if (n < 512) {
                m = fmaxf(m, d);
            } else {
                const float p = ex2((d - m) * SM_C);
                sum += p;
#pragma unroll
                for (int i = 0; i < 3; i++) {
                    const float2 vv = __bfloat1622float2(vp[key * 96 + i * 32]);
                    o[2 * i] = fmaf(p, vv.x, o[2 * i]);
                    o[2 * i + 1] = fmaf(p, vv.y, o[2 * i + 1]);
                }
            }
        }
        const float inv = __fdividef(1.f, sum);
        __nv_bfloat16* op = (__nv_bfloat16*)ostash(br, b, h) + (q >> 5) * 256 + 2 * ((q & 31) >> 3) + (q & 1);
#pragma unroll
        for (int i = 0; i < 6; i++) {
            const uint32_t d = (i >> 1) * 64 + 2 * lane + (i & 1);
            op[(d >> 3) * 1280 + (d & 7) * 32 + ((((q & 7) >> 1) ^ ((d & 7) >> 1)) << 3)] = __float2bfloat16(o[i] * inv);
        }
    }
}

template <int W>
struct PendO {
    static constexpr int N = W == 0 ? 56 : 64;
    uint32_t v[N];
    unsigned char* gp;
    static __device__ __forceinline__ uint32_t toff() {
        const uint32_t t = tid_now();
        return ((t >> 5) & 3) * 5120 + ((t >> 2) & 7) * 64 + (((t ^ (t >> 3)) & 3) << 4);
    }
    uint32_t pend, sig;
    static __device__ __forceinline__ void scale(uint32_t& x, uint32_t hi, uint32_t lo) {
        asm("{\n.reg .b32 t;\nmul.rn.bf16x2 t, %0, %2;\nfma.rn.bf16x2 %0, %0, %1, t;\n}" : "+r"(x) : "r"(hi), "r"(lo));
    }
    template <int I, int OFF>
    __device__ __forceinline__ void put() {
        asm volatile("{\n.reg .pred p;\nsetp.ne.u32 p, %6, 0;\n@p st.global.v4.b32 [%0+%5], {%1,%2,%3,%4};\n}" ::"l"(gp), "r"(v[I]),
                     "r"(v[I + 1]), "r"(v[I + 2]), "r"(v[I + 3]), "n"(OFF), "r"(pend)
                     : "memory");
    }
    __device__ __forceinline__ void verdict(const Params& P, uint32_t sb, int ie) {
        if (sig) {
            nb_sync<NB_VOTE + W, 160>();
            pend = !__any_sync(0xffffffffu, lds_u(sb + OFF_FB) != 0);
            if (W == 1 && !pend) {
                fallback_unit(P, lds_u(sb + OFF_ITEM + ie * 4), tid_now() & 127);
                __syncwarp();
            }
        }
    }
    template <int G, int H>
    __device__ __forceinline__ void half(uint32_t sb) {
        constexpr bool T2 = W == 0 ? G >= 3 : G < 3;
        constexpr int B = T2 ? 40 + 8 * (W == 0 ? G - 3 : G) : 0;
        const uint4 a = lds_u4(sb + OFF_LINV + G * 128 + H * 16 + (threadIdx.x & 3) * 32);
#pragma unroll
        for (int i = 2 * H; i < 8; i += 4) {
            scale(v[8 * G + i], a.x, a.y);
            scale(v[8 * G + i + 1], a.z, a.w);
            if (T2) {
                scale(v[B + i], a.x, a.y);
                scale(v[B + i + 1], a.z, a.w);
            }
        }
        if (H == 1) {
            put<8 * G, W * XS + G * 512>();
            put<8 * G + 4, W * XS + G * 512 + 2560>();
            if (T2) {
                put<B, 2 * XS + G * 512>();
                put<B + 4, 2 * XS + G * 512 + 2560>();
            }
            if (G == 4 && sig) nb_arrive<NB_ODONE, 288>();
        }
    }
    template <int G>
    __device__ __forceinline__ void step(uint32_t sb) {
        half<G, 0>(sb);
        half<G, 1>(sb);
    }
    __device__ __forceinline__ void clear() {
#pragma unroll
        for (int i = 0; i < N; i++) v[i] = 0;
        gp = nullptr;
        pend = 0;
        sig = 0;
    }
};

template <int W, int KK>
__device__ __forceinline__ void qproj(float (&q0)[80], float (&q1)[80], uint32_t sb, Ring& r, uint32_t pslot, uint32_t phm,
                                      PendO<W>& po, const Params& P, int it) {
    const uint32_t loR = ((sb + OFF_R) >> 4) | LO_LBO1;
    const uint32_t loRing = ((sb + OFF_RING) >> 4) | LO_LBO1;
    auto ready = [&](int k) {
        mbar_wait(sb + BAR_RFULL + r.slot * 8, r.ph, r.dl);
        mbar_wait(sb + BAR_XFULL + (k % 5) * 8, ((phm >> (k % 5)) ^ (k / 5)) & 1, r.dl);
    };
    auto release = [&]() {
        if (KK > 0) {
            wg_wait<1>();
            mbar_arrive_warp(sb + BAR_REMPTY + pslot * 8);
            if (KK <= 5) mbar_arrive_warp(sb + (BAR_XEMPTY + (KK - 1) * 8));
        }
    };
    if (KK == 0) ready(0);
    if (W == 1 && KK == QHOLD) nb_sync<NB_SDONE, 256>();
    const uint32_t a = loRing + r.slot * (SLOT >> 4) + (W == 0 ? 0 : 1024), b = loR + (KK % 5) * (XS >> 4);
    wg_fence();
    wgmma<1, 0, HI_SW128, KK != 0>(q0, a, b);
    if (W == 0) wgmma<1, 0, HI_SW128, KK != 0>(q1, a + 512, b);
#pragma unroll
    for (int k = 1; k < 4; k++) {
        wgmma<1, 0, HI_SW128, true>(q0, a + k * 128, b + k * 2);
        if (W == 0) wgmma<1, 0, HI_SW128, true>(q1, a + 512 + k * 128, b + k * 2);
    }
    wg_commit();
    const uint32_t cslot = r.slot;
    r.adv(1);
    if (W == 0 || KK < QHOLD) release();
    if (KK == QST0) {
        po.verdict(P, sb, it - 1);
        po.template half<0, 0>(sb);
    }
    if (KK < 9) ready(KK + 1);
    if (W == 1 && KK >= QHOLD) release();
    if (W == 1 && KK == 7) nb_arrive<NB_PDONE, 256>();
    if (KK == QST0) po.template half<0, 1>(sb);
    if constexpr (KK > QST0 && KK < QST0 + 5) po.template step<KK - QST0>(sb);
    if constexpr (KK < 9) {
        qproj<W, KK + 1>(q0, q1, sb, r, cslot, phm, po, P, it);
    } else {
        if (W == 0) nb_arrive<NB_SDONE, 256>();
        wg_wait<0>();
        reg_fence(q0);
        if (W == 0) reg_fence(q1);
        mbar_arrive_warp(sb + BAR_REMPTY + cslot * 8);
    }
}

template <int NR>
__device__ __forceinline__ void opack(const float (&o)[NR], uint32_t* v) {
#pragma unroll
    for (int g = 0; g < NR / 16; g++)
#pragma unroll
        for (int hh = 0; hh < 2; hh++)
#pragma unroll
            for (int t = 0; t < 4; t++) v[8 * g + 4 * hh + t] = pack_bf16(o[16 * g + 4 * t + 2 * hh], o[16 * g + 4 * t + 2 * hh + 1]);
}

template <int NR>
__device__ __forceinline__ void dump_acc(const float (&c)[NR], float4* p) {
#pragma unroll
    for (int i = 0; i < NR / 4; i++) p[i * 128] = make_float4(c[4 * i], c[4 * i + 1], c[4 * i + 2], c[4 * i + 3]);
}
__device__ __forceinline__ void wait_flag(const unsigned int* f, uint32_t epoch) {
    uint32_t v, n = 0;
    do {
        asm volatile("ld.acquire.gpu.global.u32 %0, [%1];" : "=r"(v) : "l"(f) : "memory");
        if (++n > 0x1000000) __trap();
    } while (v != epoch);
}

template <bool IS_S>
__device__ __forceinline__ void op_item(uint32_t e, uint32_t sb, Ring& r, uint32_t& phm) {
    constexpr int T0 = IS_S ? 0 : 2;
    constexpr uint32_t BOFF = IS_S ? (3 * 512) >> 4 : 0;
    const uint32_t loRing = ((sb + OFF_RING) >> 4) | LO_LBO1;
    const uint32_t loO = ((sb + OFF_R) >> 4) | LO_OST;
    float c0[80], c1[80], c2[IS_S ? 32 : 48];
    const int T2 = 6 * (IT_H1(e) - IT_H0(e));
    uint32_t xs = 0;
    auto step = [&](auto first, uint32_t hf) {
        constexpr bool F = decltype(first)::value;
        if (hf == 0) {
            mbar_wait(sb + BAR_XFULL + xs * 8, (phm >> xs) & 1, r.dl);
            phm ^= 1u << xs;
        }
        mbar_wait(sb + BAR_RFULL + r.slot * 8, r.ph, r.dl);
        const uint32_t a = loRing + r.slot * (SLOT >> 4), b = loO + xs * (XS >> 4) + hf * 640;
        wg_fence();
        wgmma<1, 1, HI_OST, !F>(c0, a + T0 * 256, b);
        wgmma<1, 1, HI_OST, !F>(c1, a + T0 * 256 + 256, b);
        wgmma<1, 1, HI_OST, !F>(c2, a + 1024, b + BOFF);
        wgmma<1, 1, HI_OST, true>(c0, a + T0 * 256 + 128, b + 320);
        wgmma<1, 1, HI_OST, true>(c1, a + T0 * 256 + 384, b + 320);
        wgmma<1, 1, HI_OST, true>(c2, a + 1024 + 128, b + 320 + BOFF);
        wg_commit();
    };
    step(TrueT{}, 0);
#pragma unroll 1
    for (int t = 1; t < T2; t++) {
        const uint32_t pslot = r.slot, pxs = xs;
        r.adv(1);
        if ((t & 1) == 0 && ++xs == 5) xs = 0;
        step(FalseT{}, t & 1);
        wg_wait<1>();
        mbar_arrive_warp(sb + BAR_REMPTY + pslot * 8);
        if ((t & 1) == 0 && t + 8 < T2) mbar_arrive_warp(sb + BAR_XEMPTY + pxs * 8);
    }
    wg_wait<0>();
    reg_fence(c0);
    reg_fence(c1);
    reg_fence(c2);
    mbar_arrive_warp(sb + BAR_REMPTY + r.slot * 8);
    r.adv(1);
    if (IT_PART(e)) {
#pragma unroll
        for (int m = 0; m < 5; m++) mbar_arrive_warp(sb + BAR_XEMPTY + m * 8);
        float4* pp = g_part + (size_t)((IT_BR(e) * 16 + IT_B(e)) * 10 + IT_HALF(e) * 5) * 2560 + (tid_now() & 127);
        dump_acc(c0, pp + T0 * 2560);
        dump_acc(c1, pp + (T0 + 1) * 2560);
        dump_acc(c2, pp + 4 * 2560 + (IS_S ? 12 * 128 : 0));
    } else {
        nb_sync<NB_OPEND, 256>();
        const uint32_t tid = tid_now(), lane = tid & 31, w = (tid >> 5) & 3;
        store_out_tile(c0, sb + OFF_R + T0 * XS, lane, w);
        store_out_tile(c1, sb + OFF_R + (T0 + 1) * XS, lane, w);
        store_out_tile(c2, sb + OFF_R + 4 * XS + (IS_S ? 96 * 128 : 0), lane, w);
        fence_async_smem();
    }
    nb_arrive<NB_ODONE, 288>();
}

template <int W>
__device__ __forceinline__ void on_item(uint32_t e, uint32_t sb, Ring& r, uint32_t& phm, uint32_t epoch) {
    const uint32_t loRing = ((sb + OFF_RING) >> 4) | LO_LBO1;
    const uint32_t loO = ((sb + OFF_R) >> 4) | LO_OST;
    float c[80];
    const int T = 3 * (IT_H1(e) - IT_H0(e));
    uint32_t xs = 0;
    auto step = [&](auto first) {
        constexpr bool F = decltype(first)::value;
        mbar_wait(sb + BAR_XFULL + xs * 8, (phm >> xs) & 1, r.dl);
        phm ^= 1u << xs;
        mbar_wait(sb + BAR_RFULL + r.slot * 8, r.ph, r.dl);
        const uint32_t a = loRing + r.slot * (SLOT >> 4) + W * 512, b = loO + xs * (XS >> 4);
        wg_fence();
        wgmma<1, 1, HI_OST, !F>(c, a, b);
#pragma unroll
        for (int k = 1; k < 4; k++) wgmma<1, 1, HI_OST, true>(c, a + k * 128, b + k * 320);
        wg_commit();
    };
    auto run = [&](int t0, int t1) {
#pragma unroll 1
        for (int t = t0; t < t1; t++) {
            const uint32_t pslot = r.slot, pxs = xs;
            r.adv(1);
            if (++xs == 5) xs = 0;
            step(FalseT{});
            wg_wait<1>();
            mbar_arrive_warp(sb + BAR_REMPTY + pslot * 8);
            mbar_arrive_warp_if(sb + BAR_XEMPTY + pxs * 8, t + 4 < T);
        }
    };
    step(TrueT{});
    const int tm = T - 3;
    run(1, tm);
    float4 pv[20];
    {
        const uint32_t tile = 2 * IT_HALF(e) + W, bb = IT_BR(e) * 16 + IT_B(e);
        wait_flag(&g_pflag[bb * 2 + (tile >= 5)], epoch);
        const float4* pp = g_part + (size_t)(bb * 10 + tile) * 2560 + (tid_now() & 127);
#pragma unroll
        for (int i = 0; i < 20; i++) pv[i] = __ldcg(pp + i * 128);
    }
    run(tm, T);
    wg_wait<0>();
    reg_fence(c);
    mbar_arrive_warp(sb + BAR_REMPTY + r.slot * 8);
    r.adv(1);
    nb_sync<NB_OPEND, 256>();
#pragma unroll
    for (int i = 0; i < 20; i++) {
        c[4 * i] += pv[i].x;
        c[4 * i + 1] += pv[i].y;
        c[4 * i + 2] += pv[i].z;
        c[4 * i + 3] += pv[i].w;
    }
    const uint32_t tid = tid_now();
    store_out_tile(c, sb + OFF_R + W * XS, tid & 31, (tid >> 5) & 3);
    fence_async_smem();
    nb_arrive<NB_ODONE, 288>();
}

template <int W>
__device__ __forceinline__ uint32_t qa_item(const Params& P, uint32_t e, uint32_t sb, Ring& r, uint32_t phm, PendO<W>& po, int it) {
    const uint32_t loR = ((sb + OFF_R) >> 4) | LO_LBO1;
    const uint32_t loRing = ((sb + OFF_RING) >> 4) | LO_LBO1;
    uint32_t lane, sta;
    {
        float q0[80], q1[80];
        qproj<W, 0>(q0, q1, sb, r, 0, phm, po, P, it);
        const uint32_t tid = tid_now();
        lane = tid & 31;
        sta = sb + OFF_R + (lane >> 4) * 1024 + (lane & 7) * 128 + (((((tid >> 4) & 6) + ((lane >> 3) & 1)) ^ (lane & 7)) << 4);
        TSD(W, 1);
        if (W == 0) {
            nb_sync<NB_PDONE, 256>();
            store_tile_t(q0, sta);
            store_tile_t(q1, sta + XS);
        } else {
            store_tile_t(q0, sta + 2 * XS);
        }
    }
    fence_async_smem();
    float s[80], oa[80], ob[W == 0 ? 32 : 48], l[10];
    zero(oa);
    zero(ob);
    zero(l);
    reg_fence(oa);
    reg_fence(ob);
    auto pv = [&](const Ring& rv, uint32_t buf) {
        mbar_wait(sb + BAR_RFULL + rv.slot * 8, rv.ph, rv.dl);
        const uint32_t a = loRing + rv.slot * (SLOT >> 4), b = loR + (3 + buf) * (XS >> 4);
        wg_fence();
#pragma unroll
        for (int k = 0; k < 4; k++) {
            wgmma<1, 0, HI_SW128, true>(oa, a + W * 512 + k * 128, b + k * 2);
            wgmma<1, 0, HI_SW128, true>(ob, a + 1024 + k * 128, b + (W == 0 ? (96 * 128) >> 4 : 0) + k * 2);
        }
        wg_commit();
    };
    float mref;
    uint32_t kslot, vslot;
    auto tail = [&](bool rel_other, int i) {
        uint32_t ps[40];
        exp_block<0>(s, ps, sta + (3 + W) * XS, mref);
        if (rel_other) {
            wg_wait<0>();
            mbar_arrive_warp(sb + BAR_REMPTY + vslot * 8);
            if (W == 1) mbar_arrive_warp_if(sb + BAR_XEMPTY + 24, i == 3);
        }
        fence_async_smem();
        nb_arrive<NB_PFULL + W, 256>();
        TSD(W, 6 + 5 * i);
        if (W == 1) {
            if (XLATE >= 2) mbar_arrive_warp_if<2>(sb + BAR_XEMPTY + 8, i == 3);
            if (XLATE >= 1) mbar_arrive_warp_if<2>(sb + BAR_XEMPTY + 16, i == 3);
        }
        if (rel_other || !PV0FIRST) {
            mbar_wait(sb + BAR_RFULL + r.slot * 8, r.ph, r.dl);
            sum_block(ps, l, lane);
        }
        TSD(W, 7 + 5 * i);
        nb_sync<NB_W + W, 128>();
        pv(r, W);
        if (!rel_other && PV0FIRST) sum_block(ps, l, lane);
        TSD(W, 8 + 5 * i);
    };
    if (W == 0) {
        sts_u(sb + OFF_GM + 4, r.slot);
        mbar_wait(sb + BAR_RFULL + r.slot * 8, r.ph, r.dl);
        nb_sync<NB_QK, 160>();
        TSD(W, 2);
        wg_fence();
        qk_steps<0, 8>(s, loRing + r.slot * (SLOT >> 4), loR);
        nb_sync<NB_Q2, 288>();
        qk_steps<8, 12>(s, loRing + r.slot * (SLOT >> 4), loR);
        wg_commit();
        nb_arrive<NB_Q01, 256>();
        TSD(W, 4);
        nb_sync<NB_REF, 160>();
        mref = __uint_as_float(lds_u(sb + OFF_GM));
        wg_wait<0>();
        reg_fence(s);
        mbar_arrive_warp<2>(sb + BAR_REMPTY + r.slot * 8);
        r.adv(2);
        TSD(W, 5);
        tail(false, 0);
    } else {
        nb_arrive<NB_Q2, 288>();
        TSD(W, 2);
        nb_sync<NB_Q01, 256>();
    }
#pragma unroll 1
    for (int i = (W == 0 ? 1 : 0); i < 4; i++) {
        const uint32_t pvslot = r.slot;
        r.adv(1);
        kslot = r.slot;
        mbar_wait(sb + BAR_RFULL + r.slot * 8, r.ph, r.dl);
        wg_fence();
        qk_steps<0, 12>(s, loRing + r.slot * (SLOT >> 4), loR);
        wg_commit();
        wg_wait<1>();
        mbar_arrive_warp_if(sb + BAR_REMPTY + pvslot * 8, W == 0 || i > 0);
        r.adv(1);
        vslot = r.slot;
        TSD(W, 4 + 5 * i);
        nb_sync<NB_PFULL + (W ^ 1), 256>();
        pv(r, W ^ 1);
        if (W == 1) mref = __uint_as_float(lds_u(sb + OFF_GM));
        wg_wait<1>();
        reg_fence(s);
        mbar_arrive_warp<2>(sb + BAR_REMPTY + kslot * 8);
        if (W == 1) {
            mbar_arrive_warp_if<2>(sb + BAR_XEMPTY + 0, i == 3);
            if (XLATE < 2) mbar_arrive_warp_if<2>(sb + BAR_XEMPTY + 8, i == 3);
            if (XLATE < 1) mbar_arrive_warp_if<2>(sb + BAR_XEMPTY + 16, i == 3);
        }
        r.adv(W == 1 && i == 3 ? 1 : 2);
        TSD(W, 5 + 5 * i);
        tail(true, i);
    }
    const uint32_t w = (tid_now() >> 5) & 3;
    const uint32_t lxa = sb + OFF_LX + w * 640 + (((lane & 8) ? 80 : 0) + ((lane >> 1) & 8) + 2 * (lane & 3) + ((lane >> 2) & 1)) * 4;
    const uint32_t nx = get_item_warp(sb, it + 1, r.dl);
    po.gp = ostash(IT_BR(e), IT_B(e), IT_H0(e)) + po.toff();
    po.sig = 1;
    if (W == 0) {
        sum_store<false>(l, lane, lxa);
        nb_arrive<NB_LX, 256>();
        wg_wait<0>();
        mbar_arrive_warp(sb + BAR_REMPTY + r.slot * 8);
        mbar_arrive_warp(sb + BAR_XEMPTY + 24);
        r.adv(1);
        nb_sync<NB_PFULL + 1, 256>();
        pv(r, 1);
    } else {
        nb_sync<NB_LX, 256>();
        sum_store<true>(l, lane, lxa);
        nb_arrive<NB_L, 160>();
    }
    TSD(W, 24);
    wg_wait<0>();
    reg_fence(oa);
    reg_fence(ob);
    mbar_arrive_warp(sb + BAR_REMPTY + r.slot * 8);
    mbar_arrive_warp(sb + BAR_XEMPTY + 32);
    r.adv(1);
    opack(ob, po.v + 40);
    opack(oa, po.v);
    return nx;
}

template <int W>
__device__ __forceinline__ void consumer(const Params& P, uint32_t sb, uint32_t dl) {
    int it = 0;
    if (W == 0) TS(0, 30);
    Ring r{0, 0, dl};
    uint32_t phm = 0;
    uint32_t e = get_item_warp(sb, 0, dl);
#pragma unroll 1
    while (e != 0) {
        if (IT_TYPE(e) == IT_QA) {
            PendO<W> po;
            po.clear();
#pragma unroll 1
            do {
                TS(W, 0);
                if (W == 0) TS_ITEM(e);
                e = qa_item<W>(P, e, sb, r, phm, po, it);
                TS(W, 31);
                it++;
            } while (IT_TYPE(e) == IT_QA);
            po.verdict(P, sb, it - 1);
            po.template step<0>(sb);
            po.template step<1>(sb);
            po.template step<2>(sb);
            po.template step<3>(sb);
            po.template step<4>(sb);
        } else {
            TS(W, 0);
            if (W == 0) TS_ITEM(e);
            if (IT_TYPE(e) == IT_OP) op_item<W == 0>(e, sb, r, phm);
            else on_item<W>(e, sb, r, phm, lds_u(sb + OFF_FB + 4));
            TS(W, 31);
            e = get_item_warp(sb, ++it, dl);
        }
    }
    TS_DUMP(W);
}

__global__ void __launch_bounds__(384, 1) fused_kernel(const __grid_constant__ Params P) {
    extern __shared__ __align__(1024) unsigned char smem_raw[];
    const uint32_t sb = (uint32_t)__cvta_generic_to_shared(smem_raw);
    const uint32_t wgid = __shfl_sync(0xffffffffu, threadIdx.x >> 7, 0);
    const uint32_t cta = blockIdx.x;
    const uint32_t dl = deadline();

    uint32_t epoch = 0;
    if (wgid == 0) epoch = *(volatile unsigned int*)&g_epoch[cta] + 1;
    if (threadIdx.x == 0) {
        if (sb & 1023) __trap();
        sts_u(sb + OFF_FB + 4, epoch);
        for (int i = 0; i < NSLOT; i++) {
            mbar_init(sb + BAR_RFULL + i * 8, 1);
            mbar_init(sb + BAR_REMPTY + i * 8, 8);
            mbar_init(sb + BAR_XFULL + i * 8, 1);
            mbar_init(sb + BAR_XEMPTY + i * 8, 8);
        }
        for (int i = 0; i < MAXI; i++) mbar_init(sb + BAR_ITEM + i * 8, 1);
        asm volatile("fence.mbarrier_init.release.cluster;" ::: "memory");
        fence_async_smem();
    }
    __syncthreads();

    if (wgid == 0) {
        asm volatile("setmaxnreg.dec.sync.aligned.u32 24;");
        const uint32_t warp = __shfl_sync(0xffffffffu, threadIdx.x >> 5, 0);
        if (warp == 0) {
            if (threadIdx.x == 0) {
                *(volatile unsigned int*)&g_epoch[cta] = epoch;
                const uint64_t pol_first = mkpol<1>(), pol_norm = mkpol<POL_W>();
                if (cta == 0) *(volatile unsigned int*)&g_ticket[(epoch + 1) & 1] = 0;
                Ring r{0, 1, dl};
                {
                    const uint32_t d = P.delay[cta];
                    uint32_t t0, t1;
                    asm volatile("mov.u32 %0, %%clock;" : "=r"(t0));
                    do {
                        asm volatile("mov.u32 %0, %%clock;" : "=r"(t1));
                    } while (t1 - t0 < d);
                }
                uint32_t e = P.items[cta][0];
#pragma unroll 1
                for (int it = 0;; it++) {
                    sts_u(sb + OFF_ITEM + it * 4, e);
                    asm volatile("mbarrier.arrive.shared::cta.b64 _, [%0];" ::"r"(sb + BAR_ITEM + it * 8) : "memory");
                    if (e == 0) break;
                    uint32_t nx = P.items[cta][it + 1 < NSTAT ? it + 1 : NSTAT - 1];
                    if (IT_TYPE(e) == IT_ON || it + 2 == MAXI) nx = 0;
                    uint32_t tk = 0;
                    const uint32_t br = IT_BR(e);
                    if (IT_TYPE(e) == IT_QA) {
                        const uint32_t h = IT_H0(e);
#pragma unroll 1
                        for (int kk = 0; kk < 10; kk++) {
                            mbar_wait(sb + BAR_REMPTY + r.slot * 8, r.ph, r.dl);
                            mbar_expect(sb + BAR_RFULL + r.slot * 8, SLOT);
                            tma3(sb + OFF_RING + r.slot * SLOT, &P.wq[br], kk * 64, h * 3, sb + BAR_RFULL + r.slot * 8, pol_norm);
                            r.adv(1);
                        }
                        const int row0 = (IT_B(e) * 32 + h) * 512;
#pragma unroll 1
                        for (int n = 0; n < 16; n++) {
                            if (n == 13 && nx == IT_DYN) tk = atomicAdd(&g_ticket[epoch & 1], 1);
                            const bool isv = n == 15 || (n > 0 && !(n & 1));
                            const int j = n == 15 ? 7 : isv ? (n - 2) >> 1 : (n + 1) >> 1;
                            mbar_wait(sb + BAR_REMPTY + r.slot * 8, r.ph, r.dl);
                            mbar_expect(sb + BAR_RFULL + r.slot * 8, SLOT);
                            tma3(sb + OFF_RING + r.slot * SLOT, isv ? &P.v[br] : &P.k[br], row0 + j * 64, 0,
                                 sb + BAR_RFULL + r.slot * 8, pol_first);
                            r.adv(1);
                        }
                    } else {
                        const int r0 = IT_H0(e) * 192, r1 = IT_H1(e) * 192;
                        const bool wide = IT_TYPE(e) == IT_OP;
#pragma unroll 1
                        for (int row = r0; row < r1; row += wide ? 32 : 64) {
                            mbar_wait(sb + BAR_REMPTY + r.slot * 8, r.ph, r.dl);
                            mbar_expect(sb + BAR_RFULL + r.slot * 8, wide ? XS : 16384);
                            tma3(sb + OFF_RING + r.slot * SLOT, wide ? &P.wo[br] : &P.won[br], row, IT_HALF(e) * (wide ? 5 : 2),
                                 sb + BAR_RFULL + r.slot * 8, pol_norm);
                            r.adv(1);
                        }
                        if (nx == IT_DYN) tk = atomicAdd(&g_ticket[epoch & 1], 1);
                    }
                    if (nx == IT_DYN) nx = tk < P.nlist ? P.list[tk] : 0;
                    e = nx;
                }
            }
        } else if (warp == 1) {
            if (threadIdx.x == 32) {
                const uint64_t pol_norm = mkpol<POL_X>(), pol_o = mkpol<POL_O>();
                uint32_t phm = 0x1f;
#pragma unroll 1
                for (int it = 0;; it++) {
                    const uint32_t e = get_item(sb, it, dl);
                    if (e == 0) break;
                    const uint32_t br = IT_BR(e);
                    uint32_t xs = 0;
                    if (IT_TYPE(e) == IT_QA) {
#pragma unroll 1
                        for (int kk = 0; kk < 10; kk++) {
                            mbar_wait(sb + BAR_XEMPTY + xs * 8, (phm >> xs) & 1, dl);
                            phm ^= 1u << xs;
                            mbar_expect(sb + BAR_XFULL + xs * 8, XS);
                            tma3(sb + OFF_R + xs * XS, &P.x[br], IT_B(e) * 160, kk, sb + BAR_XFULL + xs * 8, pol_norm);
                            if (++xs == 5) xs = 0;
                        }
                    } else {
                        const uint32_t u0 = (br * 16 + IT_B(e)) * 32;
#pragma unroll 1
                        for (uint32_t u = u0 + IT_H0(e); u < u0 + IT_H1(e); u++) {
                            wait_flag(&g_flag[u], epoch);
                            asm volatile("fence.proxy.async;" ::: "memory");
#pragma unroll 1
                            for (int t = 0; t < 3; t++) {
                                mbar_wait(sb + BAR_XEMPTY + xs * 8, (phm >> xs) & 1, dl);
                                phm ^= 1u << xs;
                                mbar_expect(sb + BAR_XFULL + xs * 8, XS);
                                bulk_load(sb + OFF_R + xs * XS, ostash(br, IT_B(e), u & 31) + t * XS, XS, sb + BAR_XFULL + xs * 8, pol_o);
                                if (++xs == 5) xs = 0;
                            }
                        }
                    }
                }
            }
        } else if (warp == 2) {
#pragma unroll 1
            for (int it = 0;; it++) {
                const uint32_t e = get_item_warp(sb, it, dl);
                if (e == 0) break;
                nb_sync<NB_ODONE, 288>();
                if (threadIdx.x == 64) {
                    const uint32_t bb = IT_BR(e) * 16 + IT_B(e);
                    if (IT_TYPE(e) == IT_QA || IT_PART(e)) {
                        __threadfence();
                        unsigned int* f = IT_TYPE(e) == IT_QA ? &g_flag[bb * 32 + IT_H0(e)] : &g_pflag[bb * 2 + IT_HALF(e)];
                        asm volatile("st.relaxed.gpu.global.u32 [%0], %1;" ::"l"(f), "r"(epoch) : "memory");
                    } else {
                        const int nt = IT_TYPE(e) == IT_OP ? 5 : 2;
                        const int cc0 = IT_BR(e) * 640 + IT_HALF(e) * nt * 64;
#pragma unroll
                        for (int m = 0; m < 5; m++) {
                            if (m < nt)
                                asm volatile("cp.async.bulk.tensor.2d.global.shared::cta.bulk_group [%0, {%2,%3}], [%1];" ::"l"(&P.out),
                                             "r"(sb + OFF_R + m * XS), "r"(cc0 + m * 64), "r"((int)IT_B(e) * 160)
                                             : "memory");
                            asm volatile("cp.async.bulk.commit_group;" ::: "memory");
                        }
#define REL(N)                                                          \
    asm volatile("cp.async.bulk.wait_group.read %0;" ::"n"(4 - N) : "memory"); \
    asm volatile("mbarrier.arrive.shared::cta.b64 _, [%0], 8;" ::"r"(sb + BAR_XEMPTY + N * 8) : "memory");
                        REL(0) REL(1) REL(2) REL(3) REL(4)
#undef REL
                    }
                }
                __syncwarp();
            }
            if (threadIdx.x == 64) asm volatile("cp.async.bulk.wait_group 0;" ::: "memory");
        } else {
            const uint32_t lane = threadIdx.x & 31, p = lane >> 2;
#pragma unroll 1
            for (int it = 0;; it++) {
                const uint32_t e = get_item_warp(sb, it, dl);
                if (e == 0) break;
                if (IT_TYPE(e) != IT_QA) continue;
                nb_sync<NB_QK, 160>();
                const uint32_t co = (((lane & 3) * 2) ^ p) << 4;
                const uint32_t ka = sb + OFF_RING + lds_u(sb + OFF_GM + 4) * SLOT + p * (9 * 128) + co;
                const uint32_t qa = sb + OFF_R + p * (17 * 128) + co;
                uint32_t acc = 0;
#pragma unroll
                for (int c = 0; c < 6; c++) {
                    if (c == 4) nb_sync<NB_Q2, 288>();
                    const uint4 kv = lds_u4((ka + (c >> 1) * 8192) ^ ((c & 1) << 4));
                    const uint4 qv = lds_u4((qa + (c >> 1) * XS) ^ ((c & 1) << 4));
                    acc = fma_bf2(kv.x, qv.x, fma_bf2(kv.y, qv.y, fma_bf2(kv.z, qv.z, fma_bf2(kv.w, qv.w, acc))));
                }
                float d = __uint_as_float(acc << 16) + __uint_as_float(acc & 0xffff0000u);
                d += __shfl_xor_sync(0xffffffffu, d, 1);
                d += __shfl_xor_sync(0xffffffffu, d, 2);
                int key = __float_as_int(d);
                key ^= (key >> 31) & 0x7fffffff;
                key = __reduce_max_sync(0xffffffffu, key);
                key ^= (key >> 31) & 0x7fffffff;
                sts_f(sb + OFF_GM, __int_as_float(key) * SM_C);
                nb_arrive<NB_REF, 160>();
                nb_sync<NB_L, 160>();
                bool bad = false;
#pragma unroll
                for (int c = 0; c < 5; c++) {
                    const uint32_t la = sb + OFF_LX + (c * 32 + lane) * 4;
                    const float v = (__uint_as_float(lds_u(la)) + __uint_as_float(lds_u(la + 640))) +
                                    (__uint_as_float(lds_u(la + 1280)) + __uint_as_float(lds_u(la + 1920)));
                    const float inv = __fdividef(1.f, v);
                    const uint32_t hi = pack_bf16(inv, 0.f), lo = pack_bf16(inv - __uint_as_float(hi << 16), 0.f);
                    const uint32_t ia = sb + OFF_LINV + c * 128 + ((lane >> 1) & 3) * 32 + (lane >> 3) * 8 + (lane & 1) * 2;
                    asm volatile("st.shared.u16 [%0], %1;\nst.shared.u16 [%0+4], %2;" ::"r"(ia), "h"((unsigned short)hi), "h"((unsigned short)lo) : "memory");
                    bad |= !(v >= 5.421010862e-20f && v <= 1.8446744e19f);
                }
                sts_u(sb + OFF_FB, __any_sync(0xffffffffu, bad));
                nb_arrive<NB_VOTE, 160>();
                nb_arrive<NB_VOTE + 1, 160>();
            }
        }
    } else if (wgid == 1) {
        asm volatile("setmaxnreg.inc.sync.aligned.u32 240;");
        consumer<0>(P, sb, dl);
    } else {
        asm volatile("setmaxnreg.inc.sync.aligned.u32 240;");
        consumer<1>(P, sb, dl);
    }
}

typedef CUresult (*EncFn)(CUtensorMap*, CUtensorMapDataType, cuuint32_t, void*, const cuuint64_t*, const cuuint64_t*,
                          const cuuint32_t*, const cuuint32_t*, CUtensorMapInterleave, CUtensorMapSwizzle,
                          CUtensorMapL2promotion, CUtensorMapFloatOOBfill);

void make_map3(EncFn enc, CUtensorMap* m, void* p, uint64_t rows, uint64_t rowbytes, uint64_t nblk, uint32_t boxrows,
               uint32_t boxblk) {
    cuuint64_t dims[3] = {64, rows, nblk};
    cuuint64_t str[2] = {rowbytes, 128};
    cuuint32_t box[3] = {64, boxrows, boxblk};
    cuuint32_t es[3] = {1, 1, 1};
    enc(m, CU_TENSOR_MAP_DATA_TYPE_BFLOAT16, 3, p, dims, str, box, es, CU_TENSOR_MAP_INTERLEAVE_NONE,
        CU_TENSOR_MAP_SWIZZLE_128B, CU_TENSOR_MAP_L2_PROMOTION_NONE, CU_TENSOR_MAP_FLOAT_OOB_FILL_NONE);
}

constexpr int tune(const char*, int def) { return def; }

void build_schedule(Params& P) {
    const int mode = tune("MODE", 4), dmax = tune("DMAX", 26400), n0 = tune("N0", 0);
    const int hmin = tune("HMIN", 19), hmax = tune("HMAX", 25), off = tune("OFF", 0), slope = tune("SLOPE", 1744);
    const int ng = tune("NG", 0), d0 = tune("D0", 0), nkeep = tune("NKEEP", 0), odmax = tune("ODMAX", 0);
    const int ong = tune("ONG", 0), od0 = tune("OD0", 0), jit = tune("JIT", 0);
    const int npos = tune("NPOS", 0), nearly = tune("NEARLY", 0);
    int u = 0;
    auto unit = [&]() {
        const uint32_t e = mk_item(IT_QA, u >> 9, u & 15, (u >> 4) & 31, 0, 0);
        u++;
        return e;
    };
    int qa[NCTA], nq = 0, op[NCTA], no = 0;
    for (int c = 0; c < NCTA; c++) {
        P.delay[c] = 0;
        for (int i = 0; i < NSTAT; i++) P.items[c][i] = 0;
        if (mode >= 3 && c < 128 && (c & 7) >= 6) op[no++] = c;
        else if (mode != 2 || (c & 3) == 0) qa[nq++] = c;
    }
    for (int t = 0; t < no; t++) {
        P.items[op[t]][1] = mk_item(IT_OP, 0, t >> 1, 0, 32, t & 1);
        P.items[op[t]][2] = P.items[op[t]][3] = IT_DYN;
        P.delay[op[t]] = ong ? od0 + ((t >> 1) * ong / 16) * (odmax / ong) : od0 + (t >> 1) * odmax / 16;
    }
    for (int k = 0; k < nq; k++) {
        const int c = qa[(k * 37) % nq];
        P.items[c][1] = P.items[c][2] = P.items[c][3] = IT_DYN;
        P.delay[c] = k < n0 ? 0 : (int)((long long)dmax * (k + 1 - n0) / (nq - n0));
        if (ng) P.delay[c] = d0 + (k * ng / nq) * (dmax / ng) + (k * ng % nq) * jit / nq;
    }
    for (int k = 0; k < no + nq; k++) {
        int best = -1;
        for (int c = 0; c < NCTA; c++)
            if (P.items[c][1] && !P.items[c][0] && (best < 0 || P.delay[c] < P.delay[best])) best = c;
        P.items[best][0] = unit();
    }
    int H[16], pos[16];
    for (int b = 0; b < 16; b++) {
        H[b] = hmin + ((hmax - hmin) * b + 7) / 15;
        pos[b] = 1092 + off - H[b] * slope / 100;
        if (b < nkeep && no) {
            pos[b] = -1;
            P.items[op[30 - 2 * b]][2] = mk_item(IT_OP, 1, b, 0, H[b], 0, 1);
            P.items[op[31 - 2 * b]][2] = mk_item(IT_OP, 1, b, 0, H[b], 1, 1);
        }
    }
    int n = 0, kn = 0;
    const int uend = mode == 2 ? 8 * nq : 1024;
    while (u < uend) {
        for (int b = 0; b < 16 && no; b++)
            if (pos[b] == u) {
                P.list[n++] = mk_item(IT_OP, 1, b, 0, H[b], 0, 1);
                P.list[n++] = mk_item(IT_OP, 1, b, 0, H[b], 1, 1);
            }
        while (no && u >= uend - npos && kn * npos < (u + 1 - (uend - npos)) * nearly) {
            P.list[n++] = mk_item(IT_ON, 1, kn / 5, H[kn / 5], 32, kn % 5);
            kn++;
        }
        P.list[n++] = unit();
    }
    for (; no && kn < 80; kn++) P.list[n++] = mk_item(IT_ON, 1, kn / 5, H[kn / 5], 32, kn % 5);
    P.nlist = n;
}

}

extern "C" void kernel_launch(void* const* d_in, const int* in_sizes, int n_in, void* d_out, int out_size) {
    static Params P;
    static bool init = false;
    if (!init) {
        EncFn enc = nullptr;
        cudaDriverEntryPointQueryResult qr;
        cudaGetDriverEntryPoint("cuTensorMapEncodeTiled", (void**)&enc, cudaEnableDefault, &qr);
        for (int i = 0; i < 2; i++) {
            P.px[i] = (const __nv_bfloat16*)d_in[5 * i + 0];
            P.pk[i] = (const __nv_bfloat16*)d_in[5 * i + 1];
            P.pv[i] = (const __nv_bfloat16*)d_in[5 * i + 2];
            P.pwq[i] = (const __nv_bfloat16*)d_in[5 * i + 3];
            make_map3(enc, &P.x[i], d_in[5 * i + 0], 2560, 1280, 10, 160, 1);
            make_map3(enc, &P.k[i], d_in[5 * i + 1], 16 * 32 * 512, 384, 3, 64, 3);
            make_map3(enc, &P.v[i], d_in[5 * i + 2], 16 * 32 * 512, 384, 3, 64, 3);
            make_map3(enc, &P.wq[i], d_in[5 * i + 3], 640, 12288, 96, 64, 3);
            make_map3(enc, &P.wo[i], d_in[5 * i + 4], 6144, 1280, 10, 32, 5);
            make_map3(enc, &P.won[i], d_in[5 * i + 4], 6144, 1280, 10, 64, 2);
        }
        cuuint64_t dims[2] = {1280, 2560};
        cuuint64_t str[1] = {2560};
        cuuint32_t box[2] = {64, 160};
        cuuint32_t es[2] = {1, 1};
        enc(&P.out, CU_TENSOR_MAP_DATA_TYPE_BFLOAT16, 2, d_out, dims, str, box, es, CU_TENSOR_MAP_INTERLEAVE_NONE,
            CU_TENSOR_MAP_SWIZZLE_128B, CU_TENSOR_MAP_L2_PROMOTION_NONE, CU_TENSOR_MAP_FLOAT_OOB_FILL_NONE);
        build_schedule(P);
        cudaFuncSetAttribute(fused_kernel, cudaFuncAttributeMaxDynamicSharedMemorySize, SMEM_LAUNCH);
        init = true;
    }
    fused_kernel<<<NCTA, 384, SMEM_LAUNCH>>>(P);
}
```

```cpp
#include <cuda_runtime.h>
#include <cuda.h>
#include <cuda_bf16.h>
#include <stdint.h>

namespace {

constexpr int NCTA = 132;
constexpr int MAXI = 16;
constexpr int NSTAT = 4;
constexpr uint32_t IT_DYN = 0xffffffffu;
constexpr int SLOT = 24576;
constexpr int NSLOT = 5;
constexpr int XS = 20480;
constexpr int OFF_R = 0;
constexpr int OFF_RING = 5 * XS;
constexpr int OFF_MISC = OFF_RING + NSLOT * SLOT;
constexpr int OFF_LX = OFF_MISC;
constexpr int OFF_LINV = OFF_LX + 2560;
constexpr int OFF_FB = OFF_LINV + 640;
constexpr int OFF_GM = OFF_FB + 16;
constexpr int OFF_BAR = OFF_GM + 16;
constexpr int BAR_RFULL = OFF_BAR;
constexpr int BAR_REMPTY = BAR_RFULL + 40;
constexpr int BAR_XFULL = BAR_REMPTY + 40;
constexpr int BAR_XEMPTY = BAR_XFULL + 40;
constexpr int BAR_ITEM = BAR_XEMPTY + 40;
constexpr int OFF_ITEM = BAR_ITEM + MAXI * 8;
constexpr int SMEM_BYTES = OFF_ITEM + MAXI * 4;
static_assert(SMEM_BYTES <= 232448, "smem");

constexpr int NB_W = 1  , NB_PFULL = 3  , NB_VOTE = 5  , NB_Q2 = 7, NB_SDONE = 8, NB_PDONE = 9,
              NB_L = 10, NB_REF = 11, NB_ODONE = 12, NB_OPEND = 13, NB_LX = 14, NB_Q01 = 15, NB_QK = 0  ;

constexpr uint32_t IT_QA = 1, IT_OP = 2, IT_ON = 3;
__host__ __device__ constexpr uint32_t mk_item(uint32_t type, uint32_t br, uint32_t b, uint32_t h0, uint32_t h1, uint32_t half,
                                               uint32_t part = 0) {
    return type | (br << 2) | (b << 3) | (h0 << 7) | (h1 << 13) | (half << 19) | (part << 22);
}
#define IT_TYPE(e) ((e) & 3u)
#define IT_BR(e) (((e) >> 2) & 1u)
#define IT_B(e) (((e) >> 3) & 15u)
#define IT_H0(e) (((e) >> 7) & 63u)
#define IT_H1(e) (((e) >> 13) & 63u)
#define IT_HALF(e) (((e) >> 19) & 7u)
#define IT_PART(e) (((e) >> 22) & 1u)

struct Params {
    CUtensorMap x[2], wq[2], k[2], v[2], wo[2], won[2], out;
    const __nv_bfloat16 *px[2], *pwq[2], *pk[2], *pv[2];
    uint32_t items[NCTA][NSTAT];
    uint32_t delay[NCTA];
    uint32_t nlist;
    uint32_t list[1024];
};

constexpr int OUNIT = 61440;
__device__ __align__(1024) unsigned char g_ostash[(size_t)1024 * OUNIT];
__device__ unsigned int g_flag[1024];
__device__ unsigned int g_pflag[64];
#define ORING 64
__device__ __forceinline__ uint32_t ostash_off(uint32_t br, uint32_t b, uint32_t h) {
    return (((br * 32 + h) % ORING) * 16 + b) * OUNIT;
}
__device__ __forceinline__ unsigned char* ostash(uint32_t br, uint32_t b, uint32_t h) { return g_ostash + ostash_off(br, b, h); }
__device__ unsigned int g_epoch[NCTA];
__device__ unsigned int g_ticket[2];

constexpr int SMEM_LAUNCH = SMEM_BYTES;
#define TS(role, idx)
#define TS_ITEM(e)
#define TS_DUMP(role)
#define TSD(role, idx)

#define POL_W 2
#define POL_X 2
#define POL_O 2
template <int M>
__device__ __forceinline__ uint64_t mkpol() {
    uint64_t p;
    if (M == 0) asm volatile("createpolicy.fractional.L2::evict_normal.b64 %0, 1.0;" : "=l"(p));
    if (M == 1) asm volatile("createpolicy.fractional.L2::evict_first.b64 %0, 1.0;" : "=l"(p));
    if (M == 2) asm volatile("createpolicy.fractional.L2::evict_unchanged.b64 %0, 1.0;" : "=l"(p));
    if (M == 3) asm volatile("createpolicy.fractional.L2::evict_normal.L2::evict_unchanged.b64 %0, 0.25;" : "=l"(p));
    return p;
}
#define STSM_W 1
#define XLATE 2
#define PV0FIRST 1
#define QST0 1
#define QST1 2
#define QHOLD 7
constexpr float SM_C = 0.07216878364870322f * 1.4426950408889634f;

__device__ __forceinline__ uint32_t tid_now() {
    uint32_t t;
    asm volatile("mov.u32 %0, %%tid.x;" : "=r"(t));
    return t;
}
__device__ __forceinline__ void mbar_init(uint32_t a, uint32_t c) {
    asm volatile("mbarrier.init.shared::cta.b64 [%0], %1;" ::"r"(a), "r"(c) : "memory");
}
__device__ __forceinline__ void mbar_expect(uint32_t a, uint32_t b) {
    asm volatile("mbarrier.arrive.expect_tx.shared::cta.b64 _, [%0], %1;" ::"r"(a), "r"(b) : "memory");
}
template <int CNT = 1>
__device__ __forceinline__ void mbar_arrive_warp(uint32_t a) {
    if (CNT == 1)
        asm volatile("{\n.reg .pred p;\nelect.sync _|p, 0xffffffff;\n@p mbarrier.arrive.shared::cta.b64 _, [%0];\n}" ::"r"(a) : "memory");
    else
        asm volatile(
            "{\n.reg .pred p;\nelect.sync _|p, 0xffffffff;\n@p mbarrier.arrive.shared::cta.b64 _, [%0];\n"
            "@p mbarrier.arrive.shared::cta.b64 _, [%0];\n}" ::"r"(a)
            : "memory");
}
template <int CNT = 1>
__device__ __forceinline__ void mbar_arrive_warp_if(uint32_t a, bool cond) {
    if (CNT == 1)
        asm volatile(
            "{\n.reg .pred p, c;\nelect.sync _|p, 0xffffffff;\nsetp.ne.and.u32 c, %1, 0, p;\n"
            "@c mbarrier.arrive.shared::cta.b64 _, [%0];\n}" ::"r"(a), "r"((uint32_t)cond)
            : "memory");
    else
        asm volatile(
            "{\n.reg .pred p, c;\nelect.sync _|p, 0xffffffff;\nsetp.ne.and.u32 c, %1, 0, p;\n"
            "@c mbarrier.arrive.shared::cta.b64 _, [%0];\n@c mbarrier.arrive.shared::cta.b64 _, [%0];\n}" ::"r"(a), "r"((uint32_t)cond)
            : "memory");
}
__device__ __forceinline__ uint32_t deadline() {
    uint32_t c;
    asm volatile("mov.u32 %0, %%clock_hi;" : "=r"(c));
    return c + 4;
}
__device__ __forceinline__ void mbar_wait(uint32_t a, uint32_t ph, uint32_t dl) {
    asm volatile(
        "{\n.reg .pred p;\n.reg .u32 m;\n"
        "LOOP:\n"
        "mbarrier.try_wait.parity.shared::cta.b64 p, [%0], %1;\n"
        "@p bra DONE;\n"
        "mov.u32 m, %%clock_hi;\n"
        "setp.ne.u32 p, m, %2;\n"
        "@p bra LOOP;\n"
        "trap;\n"
        "DONE:\n}" ::"r"(a), "r"(ph), "r"(dl)
        : "memory");
}
template <int ID, int CNT>
__device__ __forceinline__ void nb_sync() { asm volatile("bar.sync %0, %1;" ::"n"(ID), "n"(CNT) : "memory"); }
template <int ID, int CNT>
__device__ __forceinline__ void nb_arrive() { asm volatile("bar.arrive %0, %1;" ::"n"(ID), "n"(CNT) : "memory"); }
__device__ __forceinline__ void fence_async_smem() { asm volatile("fence.proxy.async.shared::cta;" ::: "memory"); }

__device__ __forceinline__ void tma3(uint32_t dst, const CUtensorMap* m, int c1, int c2, uint32_t bar, uint64_t pol) {
    asm volatile(
        "cp.async.bulk.tensor.3d.shared::cluster.global.mbarrier::complete_tx::bytes.L2::cache_hint [%0], [%1, {%3,%4,%5}], [%2], %6;" ::"r"(dst),
        "l"(m), "r"(bar), "r"(0), "r"(c1), "r"(c2), "l"(pol)
        : "memory");
}
__device__ __forceinline__ void bulk_load(uint32_t dst, const void* src, uint32_t bytes, uint32_t bar, uint64_t pol) {
    asm volatile("cp.async.bulk.shared::cluster.global.mbarrier::complete_tx::bytes.L2::cache_hint [%0], [%1], %2, [%3], %4;" ::"r"(dst),
                 "l"(src), "r"(bytes), "r"(bar), "l"(pol)
                 : "memory");
}
__device__ __forceinline__ void wg_fence() { asm volatile("wgmma.fence.sync.aligned;" ::: "memory"); }
__device__ __forceinline__ void wg_commit() { asm volatile("wgmma.commit_group.sync.aligned;" ::: "memory"); }
template <int N>
__device__ __forceinline__ void wg_wait() { asm volatile("wgmma.wait_group.sync.aligned %0;" ::"n"(N) : "memory"); }

#define RW80(c, d) c(d[0]), c(d[1]), c(d[2]), c(d[3]), c(d[4]), c(d[5]), c(d[6]), c(d[7]), c(d[8]), c(d[9]), c(d[10]), c(d[11]), c(d[12]), c(d[13]), c(d[14]), c(d[15]), c(d[16]), c(d[17]), c(d[18]), c(d[19]), c(d[20]), c(d[21]), c(d[22]), c(d[23]), c(d[24]), c(d[25]), c(d[26]), c(d[27]), c(d[28]), c(d[29]), c(d[30]), c(d[31]), c(d[32]), c(d[33]), c(d[34]), c(d[35]), c(d[36]), c(d[37]), c(d[38]), c(d[39]), c(d[40]), c(d[41]), c(d[42]), c(d[43]), c(d[44]), c(d[45]), c(d[46]), c(d[47]), c(d[48]), c(d[49]), c(d[50]), c(d[51]), c(d[52]), c(d[53]), c(d[54]), c(d[55]), c(d[56]), c(d[57]), c(d[58]), c(d[59]), c(d[60]), c(d[61]), c(d[62]), c(d[63]), c(d[64]), c(d[65]), c(d[66]), c(d[67]), c(d[68]), c(d[69]), c(d[70]), c(d[71]), c(d[72]), c(d[73]), c(d[74]), c(d[75]), c(d[76]), c(d[77]), c(d[78]), c(d[79])
#define RW48(c, d) c(d[0]), c(d[1]), c(d[2]), c(d[3]), c(d[4]), c(d[5]), c(d[6]), c(d[7]), c(d[8]), c(d[9]), c(d[10]), c(d[11]), c(d[12]), c(d[13]), c(d[14]), c(d[15]), c(d[16]), c(d[17]), c(d[18]), c(d[19]), c(d[20]), c(d[21]), c(d[22]), c(d[23]), c(d[24]), c(d[25]), c(d[26]), c(d[27]), c(d[28]), c(d[29]), c(d[30]), c(d[31]), c(d[32]), c(d[33]), c(d[34]), c(d[35]), c(d[36]), c(d[37]), c(d[38]), c(d[39]), c(d[40]), c(d[41]), c(d[42]), c(d[43]), c(d[44]), c(d[45]), c(d[46]), c(d[47])
#define RW32(c, d) c(d[0]), c(d[1]), c(d[2]), c(d[3]), c(d[4]), c(d[5]), c(d[6]), c(d[7]), c(d[8]), c(d[9]), c(d[10]), c(d[11]), c(d[12]), c(d[13]), c(d[14]), c(d[15]), c(d[16]), c(d[17]), c(d[18]), c(d[19]), c(d[20]), c(d[21]), c(d[22]), c(d[23]), c(d[24]), c(d[25]), c(d[26]), c(d[27]), c(d[28]), c(d[29]), c(d[30]), c(d[31])

__device__ __forceinline__ void reg_fence(float (&d)[80]) { asm volatile("" : RW80("+f", d)::"memory"); }
__device__ __forceinline__ void reg_fence(float (&d)[48]) { asm volatile("" : RW48("+f", d)::"memory"); }
__device__ __forceinline__ void reg_fence(float (&d)[32]) { asm volatile("" : RW32("+f", d)::"memory"); }

template <int NR>
__device__ __forceinline__ void zero(float (&d)[NR]) {
#pragma unroll
    for (int i = 0; i < NR; i++) d[i] = 0.f;
}

constexpr uint32_t HI_SW128 = (1024u >> 4) | (1u << 30);
constexpr uint32_t HI_OST = (2560u >> 4) | (2u << 30);
constexpr uint32_t LO_LBO1 = (1u << 16);
constexpr uint32_t LO_OST = ((512u >> 4) << 16);

template <int TA, int TB, uint32_t HIB, int ACC>
__device__ __forceinline__ void wgmma(float (&d)[80], uint32_t loA, uint32_t loB) {
#define WG_ASM(SD)                                                          \
    "{\n.reg .b64 da, db;\nmov.b64 da, {%80, %82};\nmov.b64 db, {%81, %83};\n" \
    "wgmma.mma_async.sync.aligned.m64n160k16.f32.bf16.bf16 "               \
    "{%0,%1,%2,%3,%4,%5,%6,%7,%8,%9,%10,%11,%12,%13,%14,%15,%16,%17,%18,%19,%20,%21,%22,%23,%24,%25,%26,%27,%28,%29,%30,%31,%32,%33,%34,%35,%36,%37,%38,%39,%40,%41,%42,%43,%44,%45,%46,%47,%48,%49,%50,%51,%52,%53,%54,%55,%56,%57,%58,%59,%60,%61,%62,%63,%64,%65,%66,%67,%68,%69,%70,%71,%72,%73,%74,%75,%76,%77,%78,%79}, da, db, " SD ", 1, 1, %84, %85;\n}"
    if constexpr (ACC == 2)
        asm volatile(WG_ASM("0") : RW80("+f", d) : "r"(loA), "r"(loB), "n"(HI_SW128), "n"(HIB), "n"(TA), "n"(TB));
    else if constexpr (ACC == 1)
        asm volatile(WG_ASM("1") : RW80("+f", d) : "r"(loA), "r"(loB), "n"(HI_SW128), "n"(HIB), "n"(TA), "n"(TB));
    else
        asm volatile(WG_ASM("0") : RW80("=f", d) : "r"(loA), "r"(loB), "n"(HI_SW128), "n"(HIB), "n"(TA), "n"(TB));
#undef WG_ASM
}
template <int TA, int TB, uint32_t HIB, int ACC>
__device__ __forceinline__ void wgmma(float (&d)[48], uint32_t loA, uint32_t loB) {
#define WG_ASM(SD)                                                          \
    "{\n.reg .b64 da, db;\nmov.b64 da, {%48, %50};\nmov.b64 db, {%49, %51};\n" \
    "wgmma.mma_async.sync.aligned.m64n96k16.f32.bf16.bf16 "               \
    "{%0,%1,%2,%3,%4,%5,%6,%7,%8,%9,%10,%11,%12,%13,%14,%15,%16,%17,%18,%19,%20,%21,%22,%23,%24,%25,%26,%27,%28,%29,%30,%31,%32,%33,%34,%35,%36,%37,%38,%39,%40,%41,%42,%43,%44,%45,%46,%47}, da, db, " SD ", 1, 1, %52, %53;\n}"
    if constexpr (ACC == 1)
        asm volatile(WG_ASM("1") : RW48("+f", d) : "r"(loA), "r"(loB), "n"(HI_SW128), "n"(HIB), "n"(TA), "n"(TB));
    else
        asm volatile(WG_ASM("0") : RW48("=f", d) : "r"(loA), "r"(loB), "n"(HI_SW128), "n"(HIB), "n"(TA), "n"(TB));
#undef WG_ASM
}
template <int TA, int TB, uint32_t HIB, int ACC>
__device__ __forceinline__ void wgmma(float (&d)[32], uint32_t loA, uint32_t loB) {
#define WG_ASM(SD)                                                          \
    "{\n.reg .b64 da, db;\nmov.b64 da, {%32, %34};\nmov.b64 db, {%33, %35};\n" \
    "wgmma.mma_async.sync.aligned.m64n64k16.f32.bf16.bf16 "               \
    "{%0,%1,%2,%3,%4,%5,%6,%7,%8,%9,%10,%11,%12,%13,%14,%15,%16,%17,%18,%19,%20,%21,%22,%23,%24,%25,%26,%27,%28,%29,%30,%31}, da, db, " SD ", 1, 1, %36, %37;\n}"
    if constexpr (ACC == 1)
        asm volatile(WG_ASM("1") : RW32("+f", d) : "r"(loA), "r"(loB), "n"(HI_SW128), "n"(HIB), "n"(TA), "n"(TB));
    else
        asm volatile(WG_ASM("0") : RW32("=f", d) : "r"(loA), "r"(loB), "n"(HI_SW128), "n"(HIB), "n"(TA), "n"(TB));
#undef WG_ASM
}

__device__ __forceinline__ uint32_t pack_bf16(float lo, float hi) {
    uint32_t r;
    asm("cvt.rn.bf16x2.f32 %0, %1, %2;" : "=r"(r) : "f"(hi), "f"(lo));
    return r;
}
__device__ __forceinline__ float ex2(float x) {
    float r;
    asm("ex2.approx.ftz.f32 %0, %1;" : "=f"(r) : "f"(x));
    return r;
}
__device__ __forceinline__ void stsm4t(uint32_t a, uint32_t r0, uint32_t r1, uint32_t r2, uint32_t r3) {
    asm volatile("stmatrix.sync.aligned.m8n8.x4.trans.shared.b16 [%0], {%1,%2,%3,%4};" ::"r"(a), "r"(r0), "r"(r1), "r"(r2), "r"(r3)
                 : "memory");
}
__device__ __forceinline__ uint32_t lds_u(uint32_t a) {
    uint32_t v;
    asm volatile("ld.shared.u32 %0, [%1];" : "=r"(v) : "r"(a) : "memory");
    return v;
}
__device__ __forceinline__ uint4 lds_u4(uint32_t a) {
    uint4 v;
    asm volatile("ld.shared.v4.u32 {%0,%1,%2,%3}, [%4];" : "=r"(v.x), "=r"(v.y), "=r"(v.z), "=r"(v.w) : "r"(a) : "memory");
    return v;
}
__device__ __forceinline__ float2 lds_f2(uint32_t a) {
    float2 v;
    asm volatile("ld.shared.v2.f32 {%0,%1}, [%2];" : "=f"(v.x), "=f"(v.y) : "r"(a) : "memory");
    return v;
}
__device__ __forceinline__ void sts_f(uint32_t a, float v) { asm volatile("st.shared.f32 [%0], %1;" ::"r"(a), "f"(v) : "memory"); }
__device__ __forceinline__ void sts_u(uint32_t a, uint32_t v) { asm volatile("st.shared.u32 [%0], %1;" ::"r"(a), "r"(v) : "memory"); }
__device__ __forceinline__ void sts_f2(uint32_t a, float x, float y) {
    asm volatile("st.shared.v2.f32 [%0], {%1,%2};" ::"r"(a), "f"(x), "f"(y) : "memory");
}

__device__ __forceinline__ void store_tile_t(const float (&d)[80], uint32_t addr) {
#pragma unroll
    for (int j = 0; j < 10; j++)
        stsm4t(addr + j * 2048, pack_bf16(d[8 * j], d[8 * j + 1]), pack_bf16(d[8 * j + 2], d[8 * j + 3]),
               pack_bf16(d[8 * j + 4], d[8 * j + 5]), pack_bf16(d[8 * j + 6], d[8 * j + 7]));
}
template <bool ADD, int NR>
__device__ __forceinline__ void store_out_tile(const float (&d)[NR], uint32_t base, uint32_t lane, uint32_t w) {
    const uint32_t mi = lane >> 3, i = lane & 7;
    const uint32_t chunk = 2 * w + (mi & 1);
    const uint32_t q0 = 8 * (i >> 1) + 2 * (mi >> 1) + (i & 1);
    const uint32_t a0 = base + q0 * 128 + ((chunk ^ (q0 & 7)) << 4);
    const uint32_t a1 = base + (q0 + 4) * 128 + ((chunk ^ ((q0 + 4) & 7)) << 4);
    uint32_t p[NR / 2];
    if (ADD) {
#pragma unroll
        for (int j = 0; j < NR / 8; j++)
            asm volatile("ldmatrix.sync.aligned.m8n8.x4.trans.shared.b16 {%0,%1,%2,%3}, [%4];"
                         : "=r"(p[4 * j]), "=r"(p[4 * j + 1]), "=r"(p[4 * j + 2]), "=r"(p[4 * j + 3])
                         : "r"(((j & 1) ? a1 : a0) + (j >> 1) * 4096)
                         : "memory");
    }
#pragma unroll
    for (int k = 0; k < NR / 2; k++)
        p[k] = ADD ? pack_bf16(d[2 * k] + __uint_as_float(p[k] << 16), d[2 * k + 1] + __uint_as_float(p[k] & 0xffff0000u))
                   : pack_bf16(d[2 * k], d[2 * k + 1]);
#pragma unroll
    for (int j = 0; j < NR / 8; j++)
        stsm4t(((j & 1) ? a1 : a0) + (j >> 1) * 4096, p[4 * j], p[4 * j + 1], p[4 * j + 2], p[4 * j + 3]);
}

struct TrueT { static constexpr bool value = true; };
struct FalseT { static constexpr bool value = false; };

template <int V>
struct IntT { static constexpr int value = V; };

__device__ __forceinline__ uint32_t get_item(uint32_t sb, int it, uint32_t dl) {
    mbar_wait(sb + BAR_ITEM + it * 8, 0, dl);
    return lds_u(sb + OFF_ITEM + it * 4);
}
__device__ __forceinline__ uint32_t get_item_warp(uint32_t sb, int it, uint32_t dl) {
    return __shfl_sync(0xffffffffu, get_item(sb, it, dl), 0);
}

struct Ring {
    uint32_t slot, ph, dl;
    __device__ __forceinline__ void adv(uint32_t k) {
        slot += k;
        if (slot >= NSLOT) { slot -= NSLOT; ph ^= 1; }
    }
};

template <int K>
__device__ __forceinline__ void qk_step(float (&s)[80], uint32_t loK, uint32_t loQ) {
    wgmma<0, 0, HI_SW128, K != 0>(s, loK + (K >> 2) * (8192 >> 4) + (K & 3) * 2, loQ + (K >> 2) * (XS >> 4) + (K & 3) * 2);
}
template <int K0, int K1>
__device__ __forceinline__ void qk_steps(float (&s)[80], uint32_t loK, uint32_t loQ) {
    if constexpr (K0 < K1) {
        qk_step<K0>(s, loK, loQ);
        qk_steps<K0 + 1, K1>(s, loK, loQ);
    }
}
__device__ __forceinline__ uint32_t add_bf2(uint32_t a, uint32_t b) {
    uint32_t r;
    asm("add.rn.bf16x2 %0, %1, %2;" : "=r"(r) : "r"(a), "r"(b));
    return r;
}
__device__ __forceinline__ uint32_t fma_bf2(uint32_t a, uint32_t b, uint32_t c) {
    uint32_t r;
    asm("fma.rn.bf16x2 %0, %1, %2, %3;" : "=r"(r) : "r"(a), "r"(b), "r"(c));
    return r;
}
template <int J>
__device__ __forceinline__ void exp_block(const float (&s)[80], uint32_t (&k)[40], uint32_t pa, float mref) {
    if constexpr (J < 10) {
#pragma unroll
        for (int i = 4 * J; i < 4 * J + 4; i++)
            k[i] = pack_bf16(ex2(fmaf(s[2 * i], SM_C, -mref)), ex2(fmaf(s[2 * i + 1], SM_C, -mref)));
#pragma unroll
        for (int i = 0; i < 4; i++)
            asm volatile("stmatrix.sync.aligned.m8n8.x1.trans.shared.b16 [%0], {%1};" ::"r"(((i & 1) ? pa ^ 16 : pa) + J * 2048 + (i >> 1) * 1024),
                         "r"(k[4 * J + i])
                         : "memory");
        exp_block<J + 1>(s, k, pa, mref);
    }
}
__device__ __forceinline__ void sum_block(const uint32_t (&k)[40], float (&l)[10], uint32_t lane) {
    const bool b4 = lane & 16, b3 = lane & 8;
    uint32_t ps[20], t[10];
#pragma unroll
    for (int j = 0; j < 20; j++) ps[j] = add_bf2(k[2 * j], k[2 * j + 1]);
#pragma unroll
    for (int j = 0; j < 10; j++)
        t[j] = add_bf2(b4 ? ps[2 * j + 1] : ps[2 * j], __shfl_xor_sync(0xffffffffu, b4 ? ps[2 * j] : ps[2 * j + 1], 16));
#pragma unroll
    for (int i = 0; i < 5; i++) {
        const uint32_t a = b3 ? t[i + 5] : t[i], b = __shfl_xor_sync(0xffffffffu, b3 ? t[i] : t[i + 5], 8);
        l[2 * i] += __uint_as_float(a << 16) + __uint_as_float(b << 16);
        l[2 * i + 1] += __uint_as_float(a & 0xffff0000u) + __uint_as_float(b & 0xffff0000u);
    }
}
template <bool ADD>
__device__ __forceinline__ void sum_store(const float (&l)[10], uint32_t lane, uint32_t lxa) {
    const bool b2 = lane & 4;
    float t[5];
#pragma unroll
    for (int i = 0; i < 5; i++) t[i] = ADD ? __uint_as_float(lds_u(lxa + i * 64)) : 0.f;
#pragma unroll
    for (int i = 0; i < 5; i++)
        sts_f(lxa + i * 64, t[i] + (b2 ? l[2 * i + 1] : l[2 * i]) + __shfl_xor_sync(0xffffffffu, b2 ? l[2 * i] : l[2 * i + 1], 4));
}

__device__ __forceinline__ void fallback_unit(const Params& P, uint32_t e, uint32_t tid) {
    const uint32_t lane = tid & 31, br = IT_BR(e), b = IT_B(e), h = IT_H0(e);
    const __nv_bfloat162* wq = (const __nv_bfloat162*)(P.pwq[br] + h * 192) + lane;
    const __nv_bfloat162* kp = (const __nv_bfloat162*)(P.pk[br] + (size_t)(b * 32 + h) * 512 * 192) + lane;
    const __nv_bfloat162* vp = (const __nv_bfloat162*)(P.pv[br] + (size_t)(b * 32 + h) * 512 * 192) + lane;
#pragma unroll 1
    for (uint32_t qi = 0; qi < 40; qi++) {
        const uint32_t q = 4 * qi + (tid >> 5);
        const __nv_bfloat16* xr = P.px[br] + (size_t)(b * 160 + q) * 640;
        float a[6] = {0.f, 0.f, 0.f, 0.f, 0.f, 0.f};
#pragma unroll 2
        for (int k = 0; k < 640; k++) {
            const float xv = __bfloat162float(xr[k]);
#pragma unroll
            for (int i = 0; i < 3; i++) {
                const float2 wv = __bfloat1622float2(wq[(size_t)k * 3072 + i * 32]);
                a[2 * i] = fmaf(xv, wv.x, a[2 * i]);
                a[2 * i + 1] = fmaf(xv, wv.y, a[2 * i + 1]);
            }
        }
#pragma unroll
        for (int i = 0; i < 6; i++) a[i] = __bfloat162float(__float2bfloat16(a[i]));
        auto score = [&](int key) {
            float d = 0.f;
#pragma unroll
            for (int i = 0; i < 3; i++) {
                const float2 kv = __bfloat1622float2(kp[key * 96 + i * 32]);
                d = fmaf(a[2 * i], kv.x, fmaf(a[2 * i + 1], kv.y, d));
            }
#pragma unroll
            for (int o = 16; o > 0; o >>= 1) d += __shfl_xor_sync(0xffffffffu, d, o);
            return d;
        };
        float m = -INFINITY, o[6] = {0.f, 0.f, 0.f, 0.f, 0.f, 0.f}, sum = 0.f;
#pragma unroll 1
        for (int n = 0; n < 1024; n++) {
            const int key = n & 511;
            const float d = score(key);
            if (n < 512) {
                m = fmaxf(m, d);
            } else {
                const float p = ex2((d - m) * SM_C);
                sum += p;
#pragma unroll
                for (int i = 0; i < 3; i++) {
                    const float2 vv = __bfloat1622float2(vp[key * 96 + i * 32]);
                    o[2 * i] = fmaf(p, vv.x, o[2 * i]);
                    o[2 * i + 1] = fmaf(p, vv.y, o[2 * i + 1]);
                }
            }
        }
        const float inv = __fdividef(1.f, sum);
        __nv_bfloat16* op = (__nv_bfloat16*)ostash(br, b, h) + (q >> 5) * 256 + 2 * ((q & 31) >> 3) + (q & 1);
#pragma unroll
        for (int i = 0; i < 6; i++) {
            const uint32_t d = (i >> 1) * 64 + 2 * lane + (i & 1);
            op[(d >> 3) * 1280 + (d & 7) * 32 + ((((q & 7) >> 1) ^ ((d & 7) >> 1)) << 3)] = __float2bfloat16(o[i] * inv);
        }
    }
}

template <int W>
struct PendO {
    static constexpr int N = W == 0 ? 56 : 64;
    uint32_t v[N];
    unsigned char* gp;
    static __device__ __forceinline__ uint32_t toff() {
        const uint32_t t = tid_now();
        return ((t >> 5) & 3) * 5120 + ((t >> 2) & 7) * 64 + (((t ^ (t >> 3)) & 3) << 4);
    }
    uint32_t pend, sig;
    static __device__ __forceinline__ void scale(uint32_t& x, uint32_t hi, uint32_t lo) {
        asm("{\n.reg .b32 t;\nmul.rn.bf16x2 t, %0, %2;\nfma.rn.bf16x2 %0, %0, %1, t;\n}" : "+r"(x) : "r"(hi), "r"(lo));
    }
    template <int I, int OFF>
    __device__ __forceinline__ void put() {
        asm volatile("{\n.reg .pred p;\nsetp.ne.u32 p, %6, 0;\n@p st.global.v4.b32 [%0+%5], {%1,%2,%3,%4};\n}" ::"l"(gp), "r"(v[I]),
                     "r"(v[I + 1]), "r"(v[I + 2]), "r"(v[I + 3]), "n"(OFF), "r"(pend)
                     : "memory");
    }
    __device__ __forceinline__ void verdict(const Params& P, uint32_t sb, int ie) {
        if (sig) {
            nb_sync<NB_VOTE + W, 160>();
            pend = !__any_sync(0xffffffffu, lds_u(sb + OFF_FB) != 0);
            if (W == 1 && !pend) {
                fallback_unit(P, lds_u(sb + OFF_ITEM + ie * 4), tid_now() & 127);
                __syncwarp();
            }
        }
    }
    template <int G, int H>
    __device__ __forceinline__ void half(uint32_t sb) {
        constexpr bool T2 = W == 0 ? G >= 3 : G < 3;
        constexpr int B = T2 ? 40 + 8 * (W == 0 ? G - 3 : G) : 0;
        const uint4 a = lds_u4(sb + OFF_LINV + G * 128 + H * 16 + (threadIdx.x & 3) * 32);
#pragma unroll
        for (int i = 2 * H; i < 8; i += 4) {
            scale(v[8 * G + i], a.x, a.y);
            scale(v[8 * G + i + 1], a.z, a.w);
            if (T2) {
                scale(v[B + i], a.x, a.y);
                scale(v[B + i + 1], a.z, a.w);
            }
        }
        if (H == 1) {
            put<8 * G, W * XS + G * 512>();
            put<8 * G + 4, W * XS + G * 512 + 2560>();
            if (T2) {
                put<B, 2 * XS + G * 512>();
                put<B + 4, 2 * XS + G * 512 + 2560>();
            }
            if (G == 4 && sig) nb_arrive<NB_ODONE, 288>();
        }
    }
    template <int G>
    __device__ __forceinline__ void step(uint32_t sb) {
        half<G, 0>(sb);
        half<G, 1>(sb);
    }
    __device__ __forceinline__ void clear() {
#pragma unroll
        for (int i = 0; i < N; i++) v[i] = 0;
        gp = nullptr;
        pend = 0;
        sig = 0;
    }
};

template <int W, int KK>
__device__ __forceinline__ void qproj(float (&q0)[80], float (&q1)[80], uint32_t sb, Ring& r, uint32_t pslot, uint32_t phm,
                                      PendO<W>& po, const Params& P, int it) {
    const uint32_t loR = ((sb + OFF_R) >> 4) | LO_LBO1;
    const uint32_t loRing = ((sb + OFF_RING) >> 4) | LO_LBO1;
    auto ready = [&](int k) {
        mbar_wait(sb + BAR_RFULL + r.slot * 8, r.ph, r.dl);
        mbar_wait(sb + BAR_XFULL + (k % 5) * 8, ((phm >> (k % 5)) ^ (k / 5)) & 1, r.dl);
    };
    auto release = [&]() {
        if (KK > 0) {
            wg_wait<1>();
            mbar_arrive_warp(sb + BAR_REMPTY + pslot * 8);
            if (KK <= 5) mbar_arrive_warp(sb + (BAR_XEMPTY + (KK - 1) * 8));
        }
    };
    if (KK == 0) ready(0);
    if (W == 1 && KK == QHOLD) nb_sync<NB_SDONE, 256>();
    const uint32_t a = loRing + r.slot * (SLOT >> 4) + (W == 0 ? 0 : 1024), b = loR + (KK % 5) * (XS >> 4);
    wg_fence();
    wgmma<1, 0, HI_SW128, KK != 0>(q0, a, b);
    if (W == 0) wgmma<1, 0, HI_SW128, KK != 0>(q1, a + 512, b);
#pragma unroll
    for (int k = 1; k < 4; k++) {
        wgmma<1, 0, HI_SW128, true>(q0, a + k * 128, b + k * 2);
        if (W == 0) wgmma<1, 0, HI_SW128, true>(q1, a + 512 + k * 128, b + k * 2);
    }
    wg_commit();
    const uint32_t cslot = r.slot;
    r.adv(1);
    if (W == 0 || KK < QHOLD) release();
    if (KK == QST0) {
        po.verdict(P, sb, it - 1);
        po.template half<0, 0>(sb);
    }
    if (KK < 9) ready(KK + 1);
    if (W == 1 && KK >= QHOLD) release();
    if (W == 1 && KK == 7) nb_arrive<NB_PDONE, 256>();
    if (KK == QST0) po.template half<0, 1>(sb);
    if constexpr (KK > QST0 && KK < QST0 + 5) po.template step<KK - QST0>(sb);
    if constexpr (KK < 9) {
        qproj<W, KK + 1>(q0, q1, sb, r, cslot, phm, po, P, it);
    } else {
        if (W == 0) nb_arrive<NB_SDONE, 256>();
        wg_wait<0>();
        reg_fence(q0);
        if (W == 0) reg_fence(q1);
        mbar_arrive_warp(sb + BAR_REMPTY + cslot * 8);
    }
}

template <int NR>
__device__ __forceinline__ void opack(const float (&o)[NR], uint32_t* v) {
#pragma unroll
    for (int g = 0; g < NR / 16; g++)
#pragma unroll
        for (int hh = 0; hh < 2; hh++)
#pragma unroll
            for (int t = 0; t < 4; t++) v[8 * g + 4 * hh + t] = pack_bf16(o[16 * g + 4 * t + 2 * hh], o[16 * g + 4 * t + 2 * hh + 1]);
}

__device__ __forceinline__ void wait_flag(const unsigned int* f, uint32_t epoch) {
    uint32_t v, n = 0;
    do {
        asm volatile("ld.acquire.gpu.global.u32 %0, [%1];" : "=r"(v) : "l"(f) : "memory");
        if (++n > 0x1000000) __trap();
    } while (v != epoch);
}

template <bool IS_S>
__device__ __forceinline__ void op_item(uint32_t e, uint32_t sb, Ring& r, uint32_t& phm) {
    constexpr int T0 = IS_S ? 0 : 2;
    constexpr uint32_t BOFF = IS_S ? (3 * 512) >> 4 : 0;
    const uint32_t loRing = ((sb + OFF_RING) >> 4) | LO_LBO1;
    const uint32_t loO = ((sb + OFF_R) >> 4) | LO_OST;
    float c0[80], c1[80], c2[IS_S ? 32 : 48];
    const int T2 = 6 * (IT_H1(e) - IT_H0(e));
    uint32_t xs = 0;
    auto step = [&](auto first, uint32_t hf) {
        constexpr bool F = decltype(first)::value;
        if (hf == 0) {
            mbar_wait(sb + BAR_XFULL + xs * 8, (phm >> xs) & 1, r.dl);
            phm ^= 1u << xs;
        }
        mbar_wait(sb + BAR_RFULL + r.slot * 8, r.ph, r.dl);
        const uint32_t a = loRing + r.slot * (SLOT >> 4), b = loO + xs * (XS >> 4) + hf * 640;
        wg_fence();
        wgmma<1, 1, HI_OST, !F>(c0, a + T0 * 256, b);
        wgmma<1, 1, HI_OST, !F>(c1, a + T0 * 256 + 256, b);
        wgmma<1, 1, HI_OST, !F>(c2, a + 1024, b + BOFF);
        wgmma<1, 1, HI_OST, true>(c0, a + T0 * 256 + 128, b + 320);
        wgmma<1, 1, HI_OST, true>(c1, a + T0 * 256 + 384, b + 320);
        wgmma<1, 1, HI_OST, true>(c2, a + 1024 + 128, b + 320 + BOFF);
        wg_commit();
    };
    step(TrueT{}, 0);
#pragma unroll 1
    for (int t = 1; t < T2; t++) {
        const uint32_t pslot = r.slot, pxs = xs;
        r.adv(1);
        if ((t & 1) == 0 && ++xs == 5) xs = 0;
        step(FalseT{}, t & 1);
        wg_wait<1>();
        mbar_arrive_warp(sb + BAR_REMPTY + pslot * 8);
        if ((t & 1) == 0 && t + 8 < T2) mbar_arrive_warp(sb + BAR_XEMPTY + pxs * 8);
    }
    wg_wait<0>();
    reg_fence(c0);
    reg_fence(c1);
    reg_fence(c2);
    mbar_arrive_warp(sb + BAR_REMPTY + r.slot * 8);
    r.adv(1);
    nb_sync<NB_OPEND, 256>();
    const uint32_t tid = tid_now(), lane = tid & 31, w = (tid >> 5) & 3;
    store_out_tile<false>(c0, sb + OFF_R + T0 * XS, lane, w);
    store_out_tile<false>(c1, sb + OFF_R + (T0 + 1) * XS, lane, w);
    store_out_tile<false>(c2, sb + OFF_R + 4 * XS + (IS_S ? 96 * 128 : 0), lane, w);
    fence_async_smem();
    nb_arrive<NB_ODONE, 288>();
}

template <int W>
__device__ __forceinline__ void on_item(uint32_t e, uint32_t sb, Ring& r, uint32_t& phm) {
    const uint32_t loRing = ((sb + OFF_RING) >> 4) | LO_LBO1;
    const uint32_t loO = ((sb + OFF_R) >> 4) | LO_OST;
    float c[80];
    const int T = 3 * (IT_H1(e) - IT_H0(e));
    uint32_t xs = 0;
    auto step = [&](auto first) {
        constexpr bool F = decltype(first)::value;
        mbar_wait(sb + BAR_XFULL + xs * 8, (phm >> xs) & 1, r.dl);
        phm ^= 1u << xs;
        mbar_wait(sb + BAR_RFULL + r.slot * 8, r.ph, r.dl);
        const uint32_t a = loRing + r.slot * (SLOT >> 4) + W * 512, b = loO + xs * (XS >> 4);
        wg_fence();
        wgmma<1, 1, HI_OST, !F>(c, a, b);
#pragma unroll
        for (int k = 1; k < 4; k++) wgmma<1, 1, HI_OST, true>(c, a + k * 128, b + k * 320);
        wg_commit();
    };
    step(TrueT{});
#pragma unroll 1
    for (int t = 1; t < T; t++) {
        const uint32_t pslot = r.slot, pxs = xs;
        r.adv(1);
        if (++xs == 5) xs = 0;
        step(FalseT{});
        wg_wait<1>();
        mbar_arrive_warp(sb + BAR_REMPTY + pslot * 8);
        mbar_arrive_warp_if(sb + BAR_XEMPTY + pxs * 8, t + 2 < T);
    }
    xs += 1 + W;
    if (xs >= 5) xs -= 5;
    mbar_wait(sb + BAR_XFULL + xs * 8, (phm >> xs) & 1, r.dl);
    wg_wait<0>();
    reg_fence(c);
    const uint32_t tid = tid_now();
    store_out_tile<true>(c, sb + OFF_R + xs * XS, tid & 31, (tid >> 5) & 3);
    fence_async_smem();
    nb_arrive<NB_ODONE, 288>();
}

template <int W>
__device__ __forceinline__ uint32_t qa_item(const Params& P, uint32_t e, uint32_t sb, Ring& r, uint32_t phm, PendO<W>& po, int it) {
    const uint32_t loR = ((sb + OFF_R) >> 4) | LO_LBO1;
    const uint32_t loRing = ((sb + OFF_RING) >> 4) | LO_LBO1;
    uint32_t lane, sta;
    {
        float q0[80], q1[80];
        qproj<W, 0>(q0, q1, sb, r, 0, phm, po, P, it);
        const uint32_t tid = tid_now();
        lane = tid & 31;
        sta = sb + OFF_R + (lane >> 4) * 1024 + (lane & 7) * 128 + (((((tid >> 4) & 6) + ((lane >> 3) & 1)) ^ (lane & 7)) << 4);
        TSD(W, 1);
        if (W == 0) {
            nb_sync<NB_PDONE, 256>();
            store_tile_t(q0, sta);
            store_tile_t(q1, sta + XS);
        } else {
            store_tile_t(q0, sta + 2 * XS);
        }
    }
    fence_async_smem();
    float s[80], oa[80], ob[W == 0 ? 32 : 48], l[10];
    zero(oa);
    zero(ob);
    zero(l);
    reg_fence(oa);
    reg_fence(ob);
    auto pv = [&](const Ring& rv, uint32_t buf) {
        mbar_wait(sb + BAR_RFULL + rv.slot * 8, rv.ph, rv.dl);
        const uint32_t a = loRing + rv.slot * (SLOT >> 4), b = loR + (3 + buf) * (XS >> 4);
        wg_fence();
#pragma unroll
        for (int k = 0; k < 4; k++) {
            wgmma<1, 0, HI_SW128, true>(oa, a + W * 512 + k * 128, b + k * 2);
            wgmma<1, 0, HI_SW128, true>(ob, a + 1024 + k * 128, b + (W == 0 ? (96 * 128) >> 4 : 0) + k * 2);
        }
        wg_commit();
    };
    float mref;
    uint32_t kslot, vslot;
    auto tail = [&](bool rel_other, int i) {
        uint32_t ps[40];
        exp_block<0>(s, ps, sta + (3 + W) * XS, mref);
        if (rel_other) {
            wg_wait<0>();
            mbar_arrive_warp(sb + BAR_REMPTY + vslot * 8);
            if (W == 1) mbar_arrive_warp_if(sb + BAR_XEMPTY + 24, i == 3);
        }
        fence_async_smem();
        nb_arrive<NB_PFULL + W, 256>();
        TSD(W, 6 + 5 * i);
        if (W == 1) {
            if (XLATE >= 2) mbar_arrive_warp_if<2>(sb + BAR_XEMPTY + 8, i == 3);
            if (XLATE >= 1) mbar_arrive_warp_if<2>(sb + BAR_XEMPTY + 16, i == 3);
        }
        if (rel_other || !PV0FIRST) {
            mbar_wait(sb + BAR_RFULL + r.slot * 8, r.ph, r.dl);
            sum_block(ps, l, lane);
        }
        TSD(W, 7 + 5 * i);
        nb_sync<NB_W + W, 128>();
        pv(r, W);
        if (!rel_other && PV0FIRST) sum_block(ps, l, lane);
        TSD(W, 8 + 5 * i);
    };
    if (W == 0) {
        sts_u(sb + OFF_GM + 4, r.slot);
        mbar_wait(sb + BAR_RFULL + r.slot * 8, r.ph, r.dl);
        nb_sync<NB_QK, 160>();
        TSD(W, 2);
        wg_fence();
        qk_steps<0, 8>(s, loRing + r.slot * (SLOT >> 4), loR);
        nb_sync<NB_Q2, 288>();
        qk_steps<8, 12>(s, loRing + r.slot * (SLOT >> 4), loR);
        wg_commit();
        nb_arrive<NB_Q01, 256>();
        TSD(W, 4);
        nb_sync<NB_REF, 160>();
        mref = __uint_as_float(lds_u(sb + OFF_GM));
        wg_wait<0>();
        reg_fence(s);
        mbar_arrive_warp<2>(sb + BAR_REMPTY + r.slot * 8);
        r.adv(2);
        TSD(W, 5);
        tail(false, 0);
    } else {
        nb_arrive<NB_Q2, 288>();
        TSD(W, 2);
        nb_sync<NB_Q01, 256>();
    }
#pragma unroll 1
    for (int i = (W == 0 ? 1 : 0); i < 4; i++) {
        const uint32_t pvslot = r.slot;
        r.adv(1);
        kslot = r.slot;
        mbar_wait(sb + BAR_RFULL + r.slot * 8, r.ph, r.dl);
        wg_fence();
        qk_steps<0, 12>(s, loRing + r.slot * (SLOT >> 4), loR);
        wg_commit();
        wg_wait<1>();
        mbar_arrive_warp_if(sb + BAR_REMPTY + pvslot * 8, W == 0 || i > 0);
        r.adv(1);
        vslot = r.slot;
        TSD(W, 4 + 5 * i);
        nb_sync<NB_PFULL + (W ^ 1), 256>();
        pv(r, W ^ 1);
        if (W == 1) mref = __uint_as_float(lds_u(sb + OFF_GM));
        wg_wait<1>();
        reg_fence(s);
        mbar_arrive_warp<2>(sb + BAR_REMPTY + kslot * 8);
        if (W == 1) {
            mbar_arrive_warp_if<2>(sb + BAR_XEMPTY + 0, i == 3);
            if (XLATE < 2) mbar_arrive_warp_if<2>(sb + BAR_XEMPTY + 8, i == 3);
            if (XLATE < 1) mbar_arrive_warp_if<2>(sb + BAR_XEMPTY + 16, i == 3);
        }
        r.adv(W == 1 && i == 3 ? 1 : 2);
        TSD(W, 5 + 5 * i);
        tail(true, i);
    }
    const uint32_t w = (tid_now() >> 5) & 3;
    const uint32_t lxa = sb + OFF_LX + w * 640 + (((lane & 8) ? 80 : 0) + ((lane >> 1) & 8) + 2 * (lane & 3) + ((lane >> 2) & 1)) * 4;
    const uint32_t nx = get_item_warp(sb, it + 1, r.dl);
    po.gp = ostash(IT_BR(e), IT_B(e), IT_H0(e)) + po.toff();
    po.sig = 1;
    if (W == 0) {
        sum_store<false>(l, lane, lxa);
        nb_arrive<NB_LX, 256>();
        wg_wait<0>();
        mbar_arrive_warp(sb + BAR_REMPTY + r.slot * 8);
        mbar_arrive_warp(sb + BAR_XEMPTY + 24);
        r.adv(1);
        nb_sync<NB_PFULL + 1, 256>();
        pv(r, 1);
    } else {
        nb_sync<NB_LX, 256>();
        sum_store<true>(l, lane, lxa);
        nb_arrive<NB_L, 160>();
    }
    TSD(W, 24);
    wg_wait<0>();
    reg_fence(oa);
    reg_fence(ob);
    mbar_arrive_warp(sb + BAR_REMPTY + r.slot * 8);
    mbar_arrive_warp(sb + BAR_XEMPTY + 32);
    r.adv(1);
    opack(ob, po.v + 40);
    opack(oa, po.v);
    return nx;
}

template <int W>
__device__ __forceinline__ void consumer(const Params& P, uint32_t sb, uint32_t dl) {
    int it = 0;
    if (W == 0) TS(0, 30);
    Ring r{0, 0, dl};
    uint32_t phm = 0;
    uint32_t e = get_item_warp(sb, 0, dl);
#pragma unroll 1
    while (e != 0) {
        if (IT_TYPE(e) == IT_QA) {
            PendO<W> po;
            po.clear();
#pragma unroll 1
            do {
                TS(W, 0);
                if (W == 0) TS_ITEM(e);
                e = qa_item<W>(P, e, sb, r, phm, po, it);
                TS(W, 31);
                it++;
            } while (IT_TYPE(e) == IT_QA);
            po.verdict(P, sb, it - 1);
            po.template step<0>(sb);
            po.template step<1>(sb);
            po.template step<2>(sb);
            po.template step<3>(sb);
            po.template step<4>(sb);
        } else {
            TS(W, 0);
            if (W == 0) TS_ITEM(e);
            if (IT_TYPE(e) == IT_OP) op_item<W == 0>(e, sb, r, phm);
            else on_item<W>(e, sb, r, phm);
            TS(W, 31);
            e = get_item_warp(sb, ++it, dl);
        }
    }
    TS_DUMP(W);
}

__global__ void __launch_bounds__(384, 1) fused_kernel(const __grid_constant__ Params P) {
    extern __shared__ __align__(1024) unsigned char smem_raw[];
    const uint32_t sb = (uint32_t)__cvta_generic_to_shared(smem_raw);
    const uint32_t wgid = __shfl_sync(0xffffffffu, threadIdx.x >> 7, 0);
    const uint32_t cta = blockIdx.x;
    const uint32_t dl = deadline();

    uint32_t epoch = 0;
    if (wgid == 0) epoch = *(volatile unsigned int*)&g_epoch[cta] + 1;
    if (threadIdx.x == 0) {
        if (sb & 1023) __trap();
        for (int i = 0; i < NSLOT; i++) {
            mbar_init(sb + BAR_RFULL + i * 8, 1);
            mbar_init(sb + BAR_REMPTY + i * 8, 8);
            mbar_init(sb + BAR_XFULL + i * 8, 1);
            mbar_init(sb + BAR_XEMPTY + i * 8, 8);
        }
        for (int i = 0; i < MAXI; i++) mbar_init(sb + BAR_ITEM + i * 8, 1);
        asm volatile("fence.mbarrier_init.release.cluster;" ::: "memory");
        fence_async_smem();
    }
    __syncthreads();

    if (wgid == 0) {
        asm volatile("setmaxnreg.dec.sync.aligned.u32 24;");
        const uint32_t warp = __shfl_sync(0xffffffffu, threadIdx.x >> 5, 0);
        if (warp == 0) {
            if (threadIdx.x == 0) {
                *(volatile unsigned int*)&g_epoch[cta] = epoch;
                const uint64_t pol_first = mkpol<1>(), pol_norm = mkpol<POL_W>();
                if (cta == 0) *(volatile unsigned int*)&g_ticket[(epoch + 1) & 1] = 0;
                Ring r{0, 1, dl};
                {
                    const uint32_t d = P.delay[cta];
                    uint32_t t0, t1;
                    asm volatile("mov.u32 %0, %%clock;" : "=r"(t0));
                    do {
                        asm volatile("mov.u32 %0, %%clock;" : "=r"(t1));
                    } while (t1 - t0 < d);
                }
                uint32_t e = P.items[cta][0];
#pragma unroll 1
                for (int it = 0;; it++) {
                    sts_u(sb + OFF_ITEM + it * 4, e);
                    asm volatile("mbarrier.arrive.shared::cta.b64 _, [%0];" ::"r"(sb + BAR_ITEM + it * 8) : "memory");
                    if (e == 0) break;
                    uint32_t nx = P.items[cta][it + 1 < NSTAT ? it + 1 : NSTAT - 1];
                    if (IT_TYPE(e) == IT_ON || it + 2 == MAXI) nx = 0;
                    uint32_t tk = 0;
                    const uint32_t br = IT_BR(e);
                    if (IT_TYPE(e) == IT_QA) {
                        const uint32_t h = IT_H0(e);
#pragma unroll 1
                        for (int kk = 0; kk < 10; kk++) {
                            mbar_wait(sb + BAR_REMPTY + r.slot * 8, r.ph, r.dl);
                            mbar_expect(sb + BAR_RFULL + r.slot * 8, SLOT);
                            tma3(sb + OFF_RING + r.slot * SLOT, &P.wq[br], kk * 64, h * 3, sb + BAR_RFULL + r.slot * 8, pol_norm);
                            r.adv(1);
                        }
                        const int row0 = (IT_B(e) * 32 + h) * 512;
#pragma unroll 1
                        for (int n = 0; n < 16; n++) {
                            if (n == 13 && nx == IT_DYN) tk = atomicAdd(&g_ticket[epoch & 1], 1);
                            const bool isv = n == 15 || (n > 0 && !(n & 1));
                            const int j = n == 15 ? 7 : isv ? (n - 2) >> 1 : (n + 1) >> 1;
                            mbar_wait(sb + BAR_REMPTY + r.slot * 8, r.ph, r.dl);
                            mbar_expect(sb + BAR_RFULL + r.slot * 8, SLOT);
                            tma3(sb + OFF_RING + r.slot * SLOT, isv ? &P.v[br] : &P.k[br], row0 + j * 64, 0,
                                 sb + BAR_RFULL + r.slot * 8, pol_first);
                            r.adv(1);
                        }
                    } else {
                        const int r0 = IT_H0(e) * 192, r1 = IT_H1(e) * 192;
                        const bool wide = IT_TYPE(e) == IT_OP;
#pragma unroll 1
                        for (int row = r0; row < r1; row += wide ? 32 : 64) {
                            mbar_wait(sb + BAR_REMPTY + r.slot * 8, r.ph, r.dl);
                            mbar_expect(sb + BAR_RFULL + r.slot * 8, wide ? XS : 16384);
                            tma3(sb + OFF_RING + r.slot * SLOT, wide ? &P.wo[br] : &P.won[br], row, IT_HALF(e) * (wide ? 5 : 2),
                                 sb + BAR_RFULL + r.slot * 8, pol_norm);
                            r.adv(1);
                        }
                        if (nx == IT_DYN) tk = atomicAdd(&g_ticket[epoch & 1], 1);
                    }
                    if (nx == IT_DYN) nx = tk < P.nlist ? P.list[tk] : 0;
                    e = nx;
                }
            }
        } else if (warp == 1) {
            if (threadIdx.x == 32) {
                const uint64_t pol_norm = mkpol<POL_X>(), pol_o = mkpol<POL_O>();
                uint32_t phm = 0x1f;
#pragma unroll 1
                for (int it = 0;; it++) {
                    const uint32_t e = get_item(sb, it, dl);
                    if (e == 0) break;
                    const uint32_t br = IT_BR(e);
                    uint32_t xs = 0;
                    if (IT_TYPE(e) == IT_QA) {
#pragma unroll 1
                        for (int kk = 0; kk < 10; kk++) {
                            mbar_wait(sb + BAR_XEMPTY + xs * 8, (phm >> xs) & 1, dl);
                            phm ^= 1u << xs;
                            mbar_expect(sb + BAR_XFULL + xs * 8, XS);
                            tma3(sb + OFF_R + xs * XS, &P.x[br], IT_B(e) * 160, kk, sb + BAR_XFULL + xs * 8, pol_norm);
                            if (++xs == 5) xs = 0;
                        }
                    } else {
                        const uint32_t u0 = (br * 16 + IT_B(e)) * 32;
#pragma unroll 1
                        for (uint32_t u = u0 + IT_H0(e); u < u0 + IT_H1(e); u++) {
                            wait_flag(&g_flag[u], epoch);
                            asm volatile("fence.proxy.async;" ::: "memory");
#pragma unroll 1
                            for (int t = 0; t < 3; t++) {
                                mbar_wait(sb + BAR_XEMPTY + xs * 8, (phm >> xs) & 1, dl);
                                phm ^= 1u << xs;
                                mbar_expect(sb + BAR_XFULL + xs * 8, XS);
                                bulk_load(sb + OFF_R + xs * XS, ostash(br, IT_B(e), u & 31) + t * XS, XS, sb + BAR_XFULL + xs * 8, pol_o);
                                if (++xs == 5) xs = 0;
                            }
                        }
                        if (IT_TYPE(e) == IT_ON) {
#pragma unroll 1
                            for (uint32_t tile = 2 * IT_HALF(e); tile < 2 * IT_HALF(e) + 2; tile++) {
                                wait_flag(&g_pflag[(u0 >> 4) + (tile >= 5)], epoch);
                                asm volatile("fence.proxy.async;" ::: "memory");
                                mbar_wait(sb + BAR_XEMPTY + xs * 8, (phm >> xs) & 1, dl);
                                mbar_expect(sb + BAR_XFULL + xs * 8, XS);
                                asm volatile(
                                    "cp.async.bulk.tensor.2d.shared::cluster.global.mbarrier::complete_tx::bytes [%0], [%1, {%3,%4}], [%2];" ::"r"(
                                        sb + OFF_R + xs * XS),
                                    "l"(&P.out), "r"(sb + BAR_XFULL + xs * 8), "r"(br * 640 + tile * 64), "r"(IT_B(e) * 160)
                                    : "memory");
                                if (++xs == 5) xs = 0;
                            }
                        }
                    }
                }
            }
        } else if (warp == 2) {
#pragma unroll 1
            for (int it = 0;; it++) {
                const uint32_t e = get_item_warp(sb, it, dl);
                if (e == 0) break;
                nb_sync<NB_ODONE, 288>();
                if (threadIdx.x == 64) {
                    const uint32_t bb = IT_BR(e) * 16 + IT_B(e);
                    if (IT_TYPE(e) != IT_QA) {
                        const bool wide = IT_TYPE(e) == IT_OP;
                        const int cc0 = IT_BR(e) * 640 + IT_HALF(e) * (wide ? 320 : 128);
                        uint32_t xs = wide ? 0 : (3 * (IT_H1(e) - IT_H0(e))) % 5;
#pragma unroll 1
                        for (int m = 0; m < (wide ? 5 : 2); m++) {
                            asm volatile("cp.async.bulk.tensor.2d.global.shared::cta.bulk_group [%0, {%2,%3}], [%1];" ::"l"(&P.out),
                                         "r"(sb + OFF_R + xs * XS), "r"(cc0 + m * 64), "r"((int)IT_B(e) * 160)
                                         : "memory");
                            asm volatile("cp.async.bulk.commit_group;" ::: "memory");
                            if (++xs == 5) xs = 0;
                        }
                        if (wide) {
#define REL(N)                                                          \
    asm volatile("cp.async.bulk.wait_group.read %0;" ::"n"(4 - N) : "memory"); \
    asm volatile("mbarrier.arrive.shared::cta.b64 _, [%0], 8;" ::"r"(sb + BAR_XEMPTY + N * 8) : "memory");
                            REL(0) REL(1) REL(2) REL(3) REL(4)
#undef REL
                        }
                        if (IT_PART(e)) {
                            asm volatile("cp.async.bulk.wait_group 0;" ::: "memory");
                            asm volatile("fence.proxy.async;" ::: "memory");
                        }
                    }
                    if (IT_TYPE(e) == IT_QA || IT_PART(e)) {
                        __threadfence();
                        unsigned int* f = IT_TYPE(e) == IT_QA ? &g_flag[bb * 32 + IT_H0(e)] : &g_pflag[bb * 2 + IT_HALF(e)];
                        asm volatile("st.relaxed.gpu.global.u32 [%0], %1;" ::"l"(f), "r"(epoch) : "memory");
                    }
                }
                __syncwarp();
            }
            if (threadIdx.x == 64) asm volatile("cp.async.bulk.wait_group 0;" ::: "memory");
        } else {
            const uint32_t lane = threadIdx.x & 31, p = lane >> 2;
#pragma unroll 1
            for (int it = 0;; it++) {
                const uint32_t e = get_item_warp(sb, it, dl);
                if (e == 0) break;
                if (IT_TYPE(e) != IT_QA) continue;
                nb_sync<NB_QK, 160>();
                const uint32_t co = (((lane & 3) * 2) ^ p) << 4;
                const uint32_t ka = sb + OFF_RING + lds_u(sb + OFF_GM + 4) * SLOT + p * (9 * 128) + co;
                const uint32_t qa = sb + OFF_R + p * (17 * 128) + co;
                uint32_t acc = 0;
#pragma unroll
                for (int c = 0; c < 6; c++) {
                    if (c == 4) nb_sync<NB_Q2, 288>();
                    const uint4 kv = lds_u4((ka + (c >> 1) * 8192) ^ ((c & 1) << 4));
                    const uint4 qv = lds_u4((qa + (c >> 1) * XS) ^ ((c & 1) << 4));
                    acc = fma_bf2(kv.x, qv.x, fma_bf2(kv.y, qv.y, fma_bf2(kv.z, qv.z, fma_bf2(kv.w, qv.w, acc))));
                }
                float d = __uint_as_float(acc << 16) + __uint_as_float(acc & 0xffff0000u);
                d += __shfl_xor_sync(0xffffffffu, d, 1);
                d += __shfl_xor_sync(0xffffffffu, d, 2);
                int key = __float_as_int(d);
                key ^= (key >> 31) & 0x7fffffff;
                key = __reduce_max_sync(0xffffffffu, key);
                key ^= (key >> 31) & 0x7fffffff;
                sts_f(sb + OFF_GM, __int_as_float(key) * SM_C);
                nb_arrive<NB_REF, 160>();
                nb_sync<NB_L, 160>();
                bool bad = false;
#pragma unroll
                for (int c = 0; c < 5; c++) {
                    const uint32_t la = sb + OFF_LX + (c * 32 + lane) * 4;
                    const float v = (__uint_as_float(lds_u(la)) + __uint_as_float(lds_u(la + 640))) +
                                    (__uint_as_float(lds_u(la + 1280)) + __uint_as_float(lds_u(la + 1920)));
                    const float inv = __fdividef(1.f, v);
                    const uint32_t hi = pack_bf16(inv, 0.f), lo = pack_bf16(inv - __uint_as_float(hi << 16), 0.f);
                    const uint32_t ia = sb + OFF_LINV + c * 128 + ((lane >> 1) & 3) * 32 + (lane >> 3) * 8 + (lane & 1) * 2;
                    asm volatile("st.shared.u16 [%0], %1;\nst.shared.u16 [%0+4], %2;" ::"r"(ia), "h"((unsigned short)hi), "h"((unsigned short)lo) : "memory");
                    bad |= !(v >= 5.421010862e-20f && v <= 1.8446744e19f);
                }
                sts_u(sb + OFF_FB, __any_sync(0xffffffffu, bad));
                nb_arrive<NB_VOTE, 160>();
                nb_arrive<NB_VOTE + 1, 160>();
            }
        }
    } else if (wgid == 1) {
        asm volatile("setmaxnreg.inc.sync.aligned.u32 240;");
        consumer<0>(P, sb, dl);
    } else {
        asm volatile("setmaxnreg.inc.sync.aligned.u32 240;");
        consumer<1>(P, sb, dl);
    }
}

typedef CUresult (*EncFn)(CUtensorMap*, CUtensorMapDataType, cuuint32_t, void*, const cuuint64_t*, const cuuint64_t*,
                          const cuuint32_t*, const cuuint32_t*, CUtensorMapInterleave, CUtensorMapSwizzle,
                          CUtensorMapL2promotion, CUtensorMapFloatOOBfill);

void make_map3(EncFn enc, CUtensorMap* m, void* p, uint64_t rows, uint64_t rowbytes, uint64_t nblk, uint32_t boxrows,
               uint32_t boxblk) {
    cuuint64_t dims[3] = {64, rows, nblk};
    cuuint64_t str[2] = {rowbytes, 128};
    cuuint32_t box[3] = {64, boxrows, boxblk};
    cuuint32_t es[3] = {1, 1, 1};
    enc(m, CU_TENSOR_MAP_DATA_TYPE_BFLOAT16, 3, p, dims, str, box, es, CU_TENSOR_MAP_INTERLEAVE_NONE,
        CU_TENSOR_MAP_SWIZZLE_128B, CU_TENSOR_MAP_L2_PROMOTION_NONE, CU_TENSOR_MAP_FLOAT_OOB_FILL_NONE);
}

constexpr int tune(const char*, int def) { return def; }

void build_schedule(Params& P) {
    const int mode = tune("MODE", 4), dmax = tune("DMAX", 26400), n0 = tune("N0", 0);
    const int hmin = tune("HMIN", 19), hmax = tune("HMAX", 25), off = tune("OFF", 0), slope = tune("SLOPE", 1744);
    const int ng = tune("NG", 0), d0 = tune("D0", 0), nkeep = tune("NKEEP", 0), odmax = tune("ODMAX", 0);
    const int ong = tune("ONG", 0), od0 = tune("OD0", 0), jit = tune("JIT", 0);
    const int npos = tune("NPOS", 0), nearly = tune("NEARLY", 0);
    int u = 0;
    auto unit = [&]() {
        const uint32_t e = mk_item(IT_QA, u >> 9, u & 15, (u >> 4) & 31, 0, 0);
        u++;
        return e;
    };
    int qa[NCTA], nq = 0, op[NCTA], no = 0;
    for (int c = 0; c < NCTA; c++) {
        P.delay[c] = 0;
        for (int i = 0; i < NSTAT; i++) P.items[c][i] = 0;
        if (mode >= 3 && c < 128 && (c & 7) >= 6) op[no++] = c;
        else if (mode != 2 || (c & 3) == 0) qa[nq++] = c;
    }
    for (int t = 0; t < no; t++) {
        P.items[op[t]][1] = mk_item(IT_OP, 0, t >> 1, 0, 32, t & 1);
        P.items[op[t]][2] = P.items[op[t]][3] = IT_DYN;
        P.delay[op[t]] = ong ? od0 + ((t >> 1) * ong / 16) * (odmax / ong) : od0 + (t >> 1) * odmax / 16;
    }
    for (int k = 0; k < nq; k++) {
        const int c = qa[(k * 37) % nq];
        P.items[c][1] = P.items[c][2] = P.items[c][3] = IT_DYN;
        P.delay[c] = k < n0 ? 0 : (int)((long long)dmax * (k + 1 - n0) / (nq - n0));
        if (ng) P.delay[c] = d0 + (k * ng / nq) * (dmax / ng) + (k * ng % nq) * jit / nq;
    }
    for (int k = 0; k < no + nq; k++) {
        int best = -1;
        for (int c = 0; c < NCTA; c++)
            if (P.items[c][1] && !P.items[c][0] && (best < 0 || P.delay[c] < P.delay[best])) best = c;
        P.items[best][0] = unit();
    }
    int H[16], pos[16];
    for (int b = 0; b < 16; b++) {
        H[b] = hmin + ((hmax - hmin) * b + 7) / 15;
        pos[b] = 1092 + off - H[b] * slope / 100;
        if (b < nkeep && no) {
            pos[b] = -1;
            P.items[op[30 - 2 * b]][2] = mk_item(IT_OP, 1, b, 0, H[b], 0, 1);
            P.items[op[31 - 2 * b]][2] = mk_item(IT_OP, 1, b, 0, H[b], 1, 1);
        }
    }
    int n = 0, kn = 0;
    const int uend = mode == 2 ? 8 * nq : 1024;
    while (u < uend) {
        for (int b = 0; b < 16 && no; b++)
            if (pos[b] == u) {
                P.list[n++] = mk_item(IT_OP, 1, b, 0, H[b], 0, 1);
                P.list[n++] = mk_item(IT_OP, 1, b, 0, H[b], 1, 1);
            }
        while (no && u >= uend - npos && kn * npos < (u + 1 - (uend - npos)) * nearly) {
            P.list[n++] = mk_item(IT_ON, 1, kn / 5, H[kn / 5], 32, kn % 5);
            kn++;
        }
        P.list[n++] = unit();
    }
    for (; no && kn < 80; kn++) P.list[n++] = mk_item(IT_ON, 1, kn / 5, H[kn / 5], 32, kn % 5);
    P.nlist = n;
}

}

extern "C" void kernel_launch(void* const* d_in, const int* in_sizes, int n_in, void* d_out, int out_size) {
    static Params P;
    static bool init = false;
    if (!init) {
        EncFn enc = nullptr;
        cudaDriverEntryPointQueryResult qr;
        cudaGetDriverEntryPoint("cuTensorMapEncodeTiled", (void**)&enc, cudaEnableDefault, &qr);
        for (int i = 0; i < 2; i++) {
            P.px[i] = (const __nv_bfloat16*)d_in[5 * i + 0];
            P.pk[i] = (const __nv_bfloat16*)d_in[5 * i + 1];
            P.pv[i] = (const __nv_bfloat16*)d_in[5 * i + 2];
            P.pwq[i] = (const __nv_bfloat16*)d_in[5 * i + 3];
            make_map3(enc, &P.x[i], d_in[5 * i + 0], 2560, 1280, 10, 160, 1);
            make_map3(enc, &P.k[i], d_in[5 * i + 1], 16 * 32 * 512, 384, 3, 64, 3);
            make_map3(enc, &P.v[i], d_in[5 * i + 2], 16 * 32 * 512, 384, 3, 64, 3);
            make_map3(enc, &P.wq[i], d_in[5 * i + 3], 640, 12288, 96, 64, 3);
            make_map3(enc, &P.wo[i], d_in[5 * i + 4], 6144, 1280, 10, 32, 5);
            make_map3(enc, &P.won[i], d_in[5 * i + 4], 6144, 1280, 10, 64, 2);
        }
        cuuint64_t dims[2] = {1280, 2560};
        cuuint64_t str[1] = {2560};
        cuuint32_t box[2] = {64, 160};
        cuuint32_t es[2] = {1, 1};
        enc(&P.out, CU_TENSOR_MAP_DATA_TYPE_BFLOAT16, 2, d_out, dims, str, box, es, CU_TENSOR_MAP_INTERLEAVE_NONE,
            CU_TENSOR_MAP_SWIZZLE_128B, CU_TENSOR_MAP_L2_PROMOTION_NONE, CU_TENSOR_MAP_FLOAT_OOB_FILL_NONE);
        build_schedule(P);
        cudaFuncSetAttribute(fused_kernel, cudaFuncAttributeMaxDynamicSharedMemorySize, SMEM_LAUNCH);
        init = true;
    }
    fused_kernel<<<NCTA, 384, SMEM_LAUNCH>>>(P);
}
```

```cpp
#include <cuda_runtime.h>
#include <cuda.h>
#include <cuda_bf16.h>
#include <stdint.h>

namespace {

constexpr int NCTA = 132;
constexpr int NCL = NCTA / 2;
constexpr int MAXI = 16;
constexpr int NSTAT = 4;
constexpr uint32_t IT_DYN = 0xffffffffu;
constexpr int SLOT = 24576;
constexpr int NSLOT = 5;
constexpr int XS = 20480;
constexpr int OFF_R = 0;
constexpr int OFF_RING = 5 * XS;
constexpr int OFF_MISC = OFF_RING + NSLOT * SLOT;
constexpr int OFF_LX = OFF_MISC;
constexpr int OFF_LINV = OFF_LX + 2560;
constexpr int OFF_FB = OFF_LINV + 640;
constexpr int OFF_GM = OFF_FB + 16;
constexpr int OFF_BAR = OFF_GM + 16;
constexpr int BAR_RFULL = OFF_BAR;
constexpr int BAR_REMPTY = BAR_RFULL + 40;
constexpr int BAR_XFULL = BAR_REMPTY + 40;
constexpr int BAR_XEMPTY = BAR_XFULL + 40;
constexpr int BAR_PRDY = BAR_XEMPTY + 40;
constexpr int BAR_ITEM = BAR_PRDY + 40;
constexpr int OFF_ITEM = BAR_ITEM + MAXI * 8;
constexpr int SMEM_BYTES = OFF_ITEM + MAXI * 4;
static_assert(SMEM_BYTES <= 232448, "smem");

constexpr int NB_W = 1  , NB_PFULL = 3  , NB_VOTE = 5  , NB_Q2 = 7, NB_SDONE = 8, NB_PDONE = 9,
              NB_L = 10, NB_REF = 11, NB_ODONE = 12, NB_OPEND = 13, NB_LX = 14, NB_Q01 = 15, NB_QK = 0  ;

constexpr uint32_t IT_QA = 1, IT_OP = 2, IT_ON = 3;
__host__ __device__ constexpr uint32_t mk_item(uint32_t type, uint32_t br, uint32_t b, uint32_t h0, uint32_t h1, uint32_t half,
                                               uint32_t part = 0) {
    return type | (br << 2) | (b << 3) | (h0 << 7) | (h1 << 13) | (half << 19) | (part << 22);
}
#define IT_TYPE(e) ((e) & 3u)
#define IT_BR(e) (((e) >> 2) & 1u)
#define IT_B(e) (((e) >> 3) & 15u)
#define IT_H0(e) (((e) >> 7) & 63u)
#define IT_H1(e) (((e) >> 13) & 63u)
#define IT_HALF(e) (((e) >> 19) & 7u)
#define IT_PART(e) (((e) >> 22) & 1u)

struct Params {
    CUtensorMap x[2], wq[2], k[2], v[2], wo[2], won[2], out;
    const __nv_bfloat16 *px[2], *pwq[2], *pk[2], *pv[2];
    uint32_t items[NCL][NSTAT];
    uint32_t delay[NCL];
    uint32_t nlist;
    uint32_t list[512];
};

constexpr int OUNIT = 61440;
__device__ __align__(1024) unsigned char g_ostash[(size_t)1024 * OUNIT];
__device__ unsigned int g_flag[1024];
__device__ unsigned int g_pflag[64];
#define ORING 64
__device__ __forceinline__ uint32_t ostash_off(uint32_t br, uint32_t b, uint32_t h) {
    return (((br * 32 + h) % ORING) * 16 + b) * OUNIT;
}
__device__ __forceinline__ unsigned char* ostash(uint32_t br, uint32_t b, uint32_t h) { return g_ostash + ostash_off(br, b, h); }
__device__ unsigned int g_epoch[NCTA];
__device__ unsigned int g_ticket[2];

constexpr int SMEM_LAUNCH = SMEM_BYTES;
#define TS(role, idx)
#define TS_ITEM(e)
#define TS_DUMP(role)
#define TSD(role, idx)

#define POL_W 2
#define POL_X 2
#define POL_O 2
template <int M>
__device__ __forceinline__ uint64_t mkpol() {
    uint64_t p;
    if (M == 0) asm volatile("createpolicy.fractional.L2::evict_normal.b64 %0, 1.0;" : "=l"(p));
    if (M == 1) asm volatile("createpolicy.fractional.L2::evict_first.b64 %0, 1.0;" : "=l"(p));
    if (M == 2) asm volatile("createpolicy.fractional.L2::evict_unchanged.b64 %0, 1.0;" : "=l"(p));
    if (M == 3) asm volatile("createpolicy.fractional.L2::evict_normal.L2::evict_unchanged.b64 %0, 0.25;" : "=l"(p));
    return p;
}
#define STSM_W 1
#define XLATE 2
#define PV0FIRST 1
#define QST0 1
#define QST1 2
#define QHOLD 7
constexpr float SM_C = 0.07216878364870322f * 1.4426950408889634f;

__device__ __forceinline__ uint32_t tid_now() {
    uint32_t t;
    asm volatile("mov.u32 %0, %%tid.x;" : "=r"(t));
    return t;
}
__device__ __forceinline__ void mbar_init(uint32_t a, uint32_t c) {
    asm volatile("mbarrier.init.shared::cta.b64 [%0], %1;" ::"r"(a), "r"(c) : "memory");
}
__device__ __forceinline__ void mbar_expect(uint32_t a, uint32_t b) {
    asm volatile("mbarrier.arrive.expect_tx.shared::cta.b64 _, [%0], %1;" ::"r"(a), "r"(b) : "memory");
}
template <int CNT = 1>
__device__ __forceinline__ void mbar_arrive_warp(uint32_t a) {
    if (CNT == 1)
        asm volatile("{\n.reg .pred p;\nelect.sync _|p, 0xffffffff;\n@p mbarrier.arrive.shared::cta.b64 _, [%0];\n}" ::"r"(a) : "memory");
    else
        asm volatile(
            "{\n.reg .pred p;\nelect.sync _|p, 0xffffffff;\n@p mbarrier.arrive.shared::cta.b64 _, [%0];\n"
            "@p mbarrier.arrive.shared::cta.b64 _, [%0];\n}" ::"r"(a)
            : "memory");
}
template <int CNT = 1>
__device__ __forceinline__ void mbar_arrive_warp_if(uint32_t a, bool cond) {
    if (CNT == 1)
        asm volatile(
            "{\n.reg .pred p, c;\nelect.sync _|p, 0xffffffff;\nsetp.ne.and.u32 c, %1, 0, p;\n"
            "@c mbarrier.arrive.shared::cta.b64 _, [%0];\n}" ::"r"(a), "r"((uint32_t)cond)
            : "memory");
    else
        asm volatile(
            "{\n.reg .pred p, c;\nelect.sync _|p, 0xffffffff;\nsetp.ne.and.u32 c, %1, 0, p;\n"
            "@c mbarrier.arrive.shared::cta.b64 _, [%0];\n@c mbarrier.arrive.shared::cta.b64 _, [%0];\n}" ::"r"(a), "r"((uint32_t)cond)
            : "memory");
}
__device__ __forceinline__ uint32_t deadline() {
    uint32_t c;
    asm volatile("mov.u32 %0, %%clock_hi;" : "=r"(c));
    return c + 4;
}
__device__ __forceinline__ void mbar_wait(uint32_t a, uint32_t ph, uint32_t dl) {
    asm volatile(
        "{\n.reg .pred p;\n.reg .u32 m;\n"
        "LOOP:\n"
        "mbarrier.try_wait.parity.shared::cta.b64 p, [%0], %1;\n"
        "@p bra DONE;\n"
        "mov.u32 m, %%clock_hi;\n"
        "setp.ne.u32 p, m, %2;\n"
        "@p bra LOOP;\n"
        "trap;\n"
        "DONE:\n}" ::"r"(a), "r"(ph), "r"(dl)
        : "memory");
}
template <int ID, int CNT>
__device__ __forceinline__ void nb_sync() { asm volatile("bar.sync %0, %1;" ::"n"(ID), "n"(CNT) : "memory"); }
template <int ID, int CNT>
__device__ __forceinline__ void nb_arrive() { asm volatile("bar.arrive %0, %1;" ::"n"(ID), "n"(CNT) : "memory"); }
__device__ __forceinline__ void fence_async_smem() { asm volatile("fence.proxy.async.shared::cta;" ::: "memory"); }

__device__ __forceinline__ void tma3(uint32_t dst, const CUtensorMap* m, int c1, int c2, uint32_t bar, uint64_t pol) {
    asm volatile(
        "cp.async.bulk.tensor.3d.shared::cluster.global.mbarrier::complete_tx::bytes.L2::cache_hint [%0], [%1, {%3,%4,%5}], [%2], %6;" ::"r"(dst),
        "l"(m), "r"(bar), "r"(0), "r"(c1), "r"(c2), "l"(pol)
        : "memory");
}
__device__ __forceinline__ void tma3_mc(uint32_t dst, const CUtensorMap* m, int c1, int c2, uint32_t bar, uint64_t pol) {
    asm volatile(
        "cp.async.bulk.tensor.3d.shared::cluster.global.mbarrier::complete_tx::bytes.multicast::cluster.L2::cache_hint"
        " [%0], [%1, {%3,%4,%5}], [%2], %6, %7;" ::"r"(dst),
        "l"(m), "r"(bar), "r"(0), "r"(c1), "r"(c2), "h"((unsigned short)3), "l"(pol)
        : "memory");
}
__device__ __forceinline__ void bulk_load(uint32_t dst, const void* src, uint32_t bytes, uint32_t bar, uint64_t pol) {
    asm volatile("cp.async.bulk.shared::cluster.global.mbarrier::complete_tx::bytes.L2::cache_hint [%0], [%1], %2, [%3], %4;" ::"r"(dst),
                 "l"(src), "r"(bytes), "r"(bar), "l"(pol)
                 : "memory");
}
__device__ __forceinline__ void wg_fence() { asm volatile("wgmma.fence.sync.aligned;" ::: "memory"); }
__device__ __forceinline__ void wg_commit() { asm volatile("wgmma.commit_group.sync.aligned;" ::: "memory"); }
template <int N>
__device__ __forceinline__ void wg_wait() { asm volatile("wgmma.wait_group.sync.aligned %0;" ::"n"(N) : "memory"); }

#define RW80(c, d) c(d[0]), c(d[1]), c(d[2]), c(d[3]), c(d[4]), c(d[5]), c(d[6]), c(d[7]), c(d[8]), c(d[9]), c(d[10]), c(d[11]), c(d[12]), c(d[13]), c(d[14]), c(d[15]), c(d[16]), c(d[17]), c(d[18]), c(d[19]), c(d[20]), c(d[21]), c(d[22]), c(d[23]), c(d[24]), c(d[25]), c(d[26]), c(d[27]), c(d[28]), c(d[29]), c(d[30]), c(d[31]), c(d[32]), c(d[33]), c(d[34]), c(d[35]), c(d[36]), c(d[37]), c(d[38]), c(d[39]), c(d[40]), c(d[41]), c(d[42]), c(d[43]), c(d[44]), c(d[45]), c(d[46]), c(d[47]), c(d[48]), c(d[49]), c(d[50]), c(d[51]), c(d[52]), c(d[53]), c(d[54]), c(d[55]), c(d[56]), c(d[57]), c(d[58]), c(d[59]), c(d[60]), c(d[61]), c(d[62]), c(d[63]), c(d[64]), c(d[65]), c(d[66]), c(d[67]), c(d[68]), c(d[69]), c(d[70]), c(d[71]), c(d[72]), c(d[73]), c(d[74]), c(d[75]), c(d[76]), c(d[77]), c(d[78]), c(d[79])
#define RW48(c, d) c(d[0]), c(d[1]), c(d[2]), c(d[3]), c(d[4]), c(d[5]), c(d[6]), c(d[7]), c(d[8]), c(d[9]), c(d[10]), c(d[11]), c(d[12]), c(d[13]), c(d[14]), c(d[15]), c(d[16]), c(d[17]), c(d[18]), c(d[19]), c(d[20]), c(d[21]), c(d[22]), c(d[23]), c(d[24]), c(d[25]), c(d[26]), c(d[27]), c(d[28]), c(d[29]), c(d[30]), c(d[31]), c(d[32]), c(d[33]), c(d[34]), c(d[35]), c(d[36]), c(d[37]), c(d[38]), c(d[39]), c(d[40]), c(d[41]), c(d[42]), c(d[43]), c(d[44]), c(d[45]), c(d[46]), c(d[47])
#define RW32(c, d) c(d[0]), c(d[1]), c(d[2]), c(d[3]), c(d[4]), c(d[5]), c(d[6]), c(d[7]), c(d[8]), c(d[9]), c(d[10]), c(d[11]), c(d[12]), c(d[13]), c(d[14]), c(d[15]), c(d[16]), c(d[17]), c(d[18]), c(d[19]), c(d[20]), c(d[21]), c(d[22]), c(d[23]), c(d[24]), c(d[25]), c(d[26]), c(d[27]), c(d[28]), c(d[29]), c(d[30]), c(d[31])

__device__ __forceinline__ void reg_fence(float (&d)[80]) { asm volatile("" : RW80("+f", d)::"memory"); }
__device__ __forceinline__ void reg_fence(float (&d)[48]) { asm volatile("" : RW48("+f", d)::"memory"); }
__device__ __forceinline__ void reg_fence(float (&d)[32]) { asm volatile("" : RW32("+f", d)::"memory"); }

template <int NR>
__device__ __forceinline__ void zero(float (&d)[NR]) {
#pragma unroll
    for (int i = 0; i < NR; i++) d[i] = 0.f;
}

constexpr uint32_t HI_SW128 = (1024u >> 4) | (1u << 30);
constexpr uint32_t HI_OST = (2560u >> 4) | (2u << 30);
constexpr uint32_t LO_LBO1 = (1u << 16);
constexpr uint32_t LO_OST = ((512u >> 4) << 16);

template <int TA, int TB, uint32_t HIB, int ACC>
__device__ __forceinline__ void wgmma(float (&d)[80], uint32_t loA, uint32_t loB) {
#define WG_ASM(SD)                                                          \
    "{\n.reg .b64 da, db;\nmov.b64 da, {%80, %82};\nmov.b64 db, {%81, %83};\n" \
    "wgmma.mma_async.sync.aligned.m64n160k16.f32.bf16.bf16 "               \
    "{%0,%1,%2,%3,%4,%5,%6,%7,%8,%9,%10,%11,%12,%13,%14,%15,%16,%17,%18,%19,%20,%21,%22,%23,%24,%25,%26,%27,%28,%29,%30,%31,%32,%33,%34,%35,%36,%37,%38,%39,%40,%41,%42,%43,%44,%45,%46,%47,%48,%49,%50,%51,%52,%53,%54,%55,%56,%57,%58,%59,%60,%61,%62,%63,%64,%65,%66,%67,%68,%69,%70,%71,%72,%73,%74,%75,%76,%77,%78,%79}, da, db, " SD ", 1, 1, %84, %85;\n}"
    if constexpr (ACC == 2)
        asm volatile(WG_ASM("0") : RW80("+f", d) : "r"(loA), "r"(loB), "n"(HI_SW128), "n"(HIB), "n"(TA), "n"(TB));
    else if constexpr (ACC == 1)
        asm volatile(WG_ASM("1") : RW80("+f", d) : "r"(loA), "r"(loB), "n"(HI_SW128), "n"(HIB), "n"(TA), "n"(TB));
    else
        asm volatile(WG_ASM("0") : RW80("=f", d) : "r"(loA), "r"(loB), "n"(HI_SW128), "n"(HIB), "n"(TA), "n"(TB));
#undef WG_ASM
}
template <int TA, int TB, uint32_t HIB, int ACC>
__device__ __forceinline__ void wgmma(float (&d)[48], uint32_t loA, uint32_t loB) {
#define WG_ASM(SD)                                                          \
    "{\n.reg .b64 da, db;\nmov.b64 da, {%48, %50};\nmov.b64 db, {%49, %51};\n" \
    "wgmma.mma_async.sync.aligned.m64n96k16.f32.bf16.bf16 "               \
    "{%0,%1,%2,%3,%4,%5,%6,%7,%8,%9,%10,%11,%12,%13,%14,%15,%16,%17,%18,%19,%20,%21,%22,%23,%24,%25,%26,%27,%28,%29,%30,%31,%32,%33,%34,%35,%36,%37,%38,%39,%40,%41,%42,%43,%44,%45,%46,%47}, da, db, " SD ", 1, 1, %52, %53;\n}"
    if constexpr (ACC == 1)
        asm volatile(WG_ASM("1") : RW48("+f", d) : "r"(loA), "r"(loB), "n"(HI_SW128), "n"(HIB), "n"(TA), "n"(TB));
    else
        asm volatile(WG_ASM("0") : RW48("=f", d) : "r"(loA), "r"(loB), "n"(HI_SW128), "n"(HIB), "n"(TA), "n"(TB));
#undef WG_ASM
}
template <int TA, int TB, uint32_t HIB, int ACC>
__device__ __forceinline__ void wgmma(float (&d)[32], uint32_t loA, uint32_t loB) {
#define WG_ASM(SD)                                                          \
    "{\n.reg .b64 da, db;\nmov.b64 da, {%32, %34};\nmov.b64 db, {%33, %35};\n" \
    "wgmma.mma_async.sync.aligned.m64n64k16.f32.bf16.bf16 "               \
    "{%0,%1,%2,%3,%4,%5,%6,%7,%8,%9,%10,%11,%12,%13,%14,%15,%16,%17,%18,%19,%20,%21,%22,%23,%24,%25,%26,%27,%28,%29,%30,%31}, da, db, " SD ", 1, 1, %36, %37;\n}"
    if constexpr (ACC == 1)
        asm volatile(WG_ASM("1") : RW32("+f", d) : "r"(loA), "r"(loB), "n"(HI_SW128), "n"(HIB), "n"(TA), "n"(TB));
    else
        asm volatile(WG_ASM("0") : RW32("=f", d) : "r"(loA), "r"(loB), "n"(HI_SW128), "n"(HIB), "n"(TA), "n"(TB));
#undef WG_ASM
}

__device__ __forceinline__ uint32_t pack_bf16(float lo, float hi) {
    uint32_t r;
    asm("cvt.rn.bf16x2.f32 %0, %1, %2;" : "=r"(r) : "f"(hi), "f"(lo));
    return r;
}
__device__ __forceinline__ float ex2(float x) {
    float r;
    asm("ex2.approx.ftz.f32 %0, %1;" : "=f"(r) : "f"(x));
    return r;
}
__device__ __forceinline__ void stsm4t(uint32_t a, uint32_t r0, uint32_t r1, uint32_t r2, uint32_t r3) {
    asm volatile("stmatrix.sync.aligned.m8n8.x4.trans.shared.b16 [%0], {%1,%2,%3,%4};" ::"r"(a), "r"(r0), "r"(r1), "r"(r2), "r"(r3)
                 : "memory");
}
__device__ __forceinline__ uint32_t lds_u(uint32_t a) {
    uint32_t v;
    asm volatile("ld.shared.u32 %0, [%1];" : "=r"(v) : "r"(a) : "memory");
    return v;
}
__device__ __forceinline__ uint4 lds_u4(uint32_t a) {
    uint4 v;
    asm volatile("ld.shared.v4.u32 {%0,%1,%2,%3}, [%4];" : "=r"(v.x), "=r"(v.y), "=r"(v.z), "=r"(v.w) : "r"(a) : "memory");
    return v;
}
__device__ __forceinline__ float2 lds_f2(uint32_t a) {
    float2 v;
    asm volatile("ld.shared.v2.f32 {%0,%1}, [%2];" : "=f"(v.x), "=f"(v.y) : "r"(a) : "memory");
    return v;
}
__device__ __forceinline__ void sts_f(uint32_t a, float v) { asm volatile("st.shared.f32 [%0], %1;" ::"r"(a), "f"(v) : "memory"); }
__device__ __forceinline__ void sts_u(uint32_t a, uint32_t v) { asm volatile("st.shared.u32 [%0], %1;" ::"r"(a), "r"(v) : "memory"); }
__device__ __forceinline__ void sts_f2(uint32_t a, float x, float y) {
    asm volatile("st.shared.v2.f32 [%0], {%1,%2};" ::"r"(a), "f"(x), "f"(y) : "memory");
}

__device__ __forceinline__ void store_tile_t(const float (&d)[80], uint32_t addr) {
#pragma unroll
    for (int j = 0; j < 10; j++)
        stsm4t(addr + j * 2048, pack_bf16(d[8 * j], d[8 * j + 1]), pack_bf16(d[8 * j + 2], d[8 * j + 3]),
               pack_bf16(d[8 * j + 4], d[8 * j + 5]), pack_bf16(d[8 * j + 6], d[8 * j + 7]));
}
template <bool ADD, int NR>
__device__ __forceinline__ void store_out_tile(const float (&d)[NR], uint32_t base, uint32_t lane, uint32_t w) {
    const uint32_t mi = lane >> 3, i = lane & 7;
    const uint32_t chunk = 2 * w + (mi & 1);
    const uint32_t q0 = 8 * (i >> 1) + 2 * (mi >> 1) + (i & 1);
    const uint32_t a0 = base + q0 * 128 + ((chunk ^ (q0 & 7)) << 4);
    const uint32_t a1 = base + (q0 + 4) * 128 + ((chunk ^ ((q0 + 4) & 7)) << 4);
    uint32_t p[NR / 2];
    if (ADD) {
#pragma unroll
        for (int j = 0; j < NR / 8; j++)
            asm volatile("ldmatrix.sync.aligned.m8n8.x4.trans.shared.b16 {%0,%1,%2,%3}, [%4];"
                         : "=r"(p[4 * j]), "=r"(p[4 * j + 1]), "=r"(p[4 * j + 2]), "=r"(p[4 * j + 3])
                         : "r"(((j & 1) ? a1 : a0) + (j >> 1) * 4096)
                         : "memory");
    }
#pragma unroll
    for (int k = 0; k < NR / 2; k++)
        p[k] = ADD ? pack_bf16(d[2 * k] + __uint_as_float(p[k] << 16), d[2 * k + 1] + __uint_as_float(p[k] & 0xffff0000u))
                   : pack_bf16(d[2 * k], d[2 * k + 1]);
#pragma unroll
    for (int j = 0; j < NR / 8; j++)
        stsm4t(((j & 1) ? a1 : a0) + (j >> 1) * 4096, p[4 * j], p[4 * j + 1], p[4 * j + 2], p[4 * j + 3]);
}

struct TrueT { static constexpr bool value = true; };
struct FalseT { static constexpr bool value = false; };

template <int V>
struct IntT { static constexpr int value = V; };

__device__ __forceinline__ uint32_t get_item(uint32_t sb, int it, uint32_t dl) {
    mbar_wait(sb + BAR_ITEM + it * 8, 0, dl);
    return lds_u(sb + OFF_ITEM + it * 4);
}
__device__ __forceinline__ uint32_t get_item_warp(uint32_t sb, int it, uint32_t dl) {
    return __shfl_sync(0xffffffffu, get_item(sb, it, dl), 0);
}

struct Ring {
    uint32_t slot, ph, dl;
    __device__ __forceinline__ void adv(uint32_t k) {
        slot += k;
        if (slot >= NSLOT) { slot -= NSLOT; ph ^= 1; }
    }
};

template <int K>
__device__ __forceinline__ void qk_step(float (&s)[80], uint32_t loK, uint32_t loQ) {
    wgmma<0, 0, HI_SW128, K != 0>(s, loK + (K >> 2) * (8192 >> 4) + (K & 3) * 2, loQ + (K >> 2) * (XS >> 4) + (K & 3) * 2);
}
template <int K0, int K1>
__device__ __forceinline__ void qk_steps(float (&s)[80], uint32_t loK, uint32_t loQ) {
    if constexpr (K0 < K1) {
        qk_step<K0>(s, loK, loQ);
        qk_steps<K0 + 1, K1>(s, loK, loQ);
    }
}
__device__ __forceinline__ uint32_t add_bf2(uint32_t a, uint32_t b) {
    uint32_t r;
    asm("add.rn.bf16x2 %0, %1, %2;" : "=r"(r) : "r"(a), "r"(b));
    return r;
}
__device__ __forceinline__ uint32_t fma_bf2(uint32_t a, uint32_t b, uint32_t c) {
    uint32_t r;
    asm("fma.rn.bf16x2 %0, %1, %2, %3;" : "=r"(r) : "r"(a), "r"(b), "r"(c));
    return r;
}
template <int J>
__device__ __forceinline__ void exp_block(const float (&s)[80], uint32_t (&k)[40], uint32_t pa, float mref) {
    if constexpr (J < 10) {
#pragma unroll
        for (int i = 4 * J; i < 4 * J + 4; i++)
            k[i] = pack_bf16(ex2(fmaf(s[2 * i], SM_C, -mref)), ex2(fmaf(s[2 * i + 1], SM_C, -mref)));
#pragma unroll
        for (int i = 0; i < 4; i++)
            asm volatile("stmatrix.sync.aligned.m8n8.x1.trans.shared.b16 [%0], {%1};" ::"r"(((i & 1) ? pa ^ 16 : pa) + J * 2048 + (i >> 1) * 1024),
                         "r"(k[4 * J + i])
                         : "memory");
        exp_block<J + 1>(s, k, pa, mref);
    }
}
__device__ __forceinline__ void sum_block(const uint32_t (&k)[40], float (&l)[10], uint32_t lane) {
    const bool b4 = lane & 16, b3 = lane & 8;
    uint32_t ps[20], t[10];
#pragma unroll
    for (int j = 0; j < 20; j++) ps[j] = add_bf2(k[2 * j], k[2 * j + 1]);
#pragma unroll
    for (int j = 0; j < 10; j++)
        t[j] = add_bf2(b4 ? ps[2 * j + 1] : ps[2 * j], __shfl_xor_sync(0xffffffffu, b4 ? ps[2 * j] : ps[2 * j + 1], 16));
#pragma unroll
    for (int i = 0; i < 5; i++) {
        const uint32_t a = b3 ? t[i + 5] : t[i], b = __shfl_xor_sync(0xffffffffu, b3 ? t[i] : t[i + 5], 8);
        l[2 * i] += __uint_as_float(a << 16) + __uint_as_float(b << 16);
        l[2 * i + 1] += __uint_as_float(a & 0xffff0000u) + __uint_as_float(b & 0xffff0000u);
    }
}
template <bool ADD>
__device__ __forceinline__ void sum_store(const float (&l)[10], uint32_t lane, uint32_t lxa) {
    const bool b2 = lane & 4;
    float t[5];
#pragma unroll
    for (int i = 0; i < 5; i++) t[i] = ADD ? __uint_as_float(lds_u(lxa + i * 64)) : 0.f;
#pragma unroll
    for (int i = 0; i < 5; i++)
        sts_f(lxa + i * 64, t[i] + (b2 ? l[2 * i + 1] : l[2 * i]) + __shfl_xor_sync(0xffffffffu, b2 ? l[2 * i] : l[2 * i + 1], 4));
}

__device__ __forceinline__ void fallback_unit(const Params& P, uint32_t e, uint32_t tid) {
    const uint32_t lane = tid & 31, br = IT_BR(e), b = IT_B(e), h = IT_H0(e);
    const __nv_bfloat162* wq = (const __nv_bfloat162*)(P.pwq[br] + h * 192) + lane;
    const __nv_bfloat162* kp = (const __nv_bfloat162*)(P.pk[br] + (size_t)(b * 32 + h) * 512 * 192) + lane;
    const __nv_bfloat162* vp = (const __nv_bfloat162*)(P.pv[br] + (size_t)(b * 32 + h) * 512 * 192) + lane;
#pragma unroll 1
    for (uint32_t qi = 0; qi < 40; qi++) {
        const uint32_t q = 4 * qi + (tid >> 5);
        const __nv_bfloat16* xr = P.px[br] + (size_t)(b * 160 + q) * 640;
        float a[6] = {0.f, 0.f, 0.f, 0.f, 0.f, 0.f};
#pragma unroll 2
        for (int k = 0; k < 640; k++) {
            const float xv = __bfloat162float(xr[k]);
#pragma unroll
            for (int i = 0; i < 3; i++) {
                const float2 wv = __bfloat1622float2(wq[(size_t)k * 3072 + i * 32]);
                a[2 * i] = fmaf(xv, wv.x, a[2 * i]);
                a[2 * i + 1] = fmaf(xv, wv.y, a[2 * i + 1]);
            }
        }
#pragma unroll
        for (int i = 0; i < 6; i++) a[i] = __bfloat162float(__float2bfloat16(a[i]));
        auto score = [&](int key) {
            float d = 0.f;
#pragma unroll
            for (int i = 0; i < 3; i++) {
                const float2 kv = __bfloat1622float2(kp[key * 96 + i * 32]);
                d = fmaf(a[2 * i], kv.x, fmaf(a[2 * i + 1], kv.y, d));
            }
#pragma unroll
            for (int o = 16; o > 0; o >>= 1) d += __shfl_xor_sync(0xffffffffu, d, o);
            return d;
        };
        float m = -INFINITY, o[6] = {0.f, 0.f, 0.f, 0.f, 0.f, 0.f}, sum = 0.f;
#pragma unroll 1
        for (int n = 0; n < 1024; n++) {
            const int key = n & 511;
            const float d = score(key);
            if (n < 512) {
                m = fmaxf(m, d);
            } else {
                const float p = ex2((d - m) * SM_C);
                sum += p;
#pragma unroll
                for (int i = 0; i < 3; i++) {
                    const float2 vv = __bfloat1622float2(vp[key * 96 + i * 32]);
                    o[2 * i] = fmaf(p, vv.x, o[2 * i]);
                    o[2 * i + 1] = fmaf(p, vv.y, o[2 * i + 1]);
                }
            }
        }
        const float inv = __fdividef(1.f, sum);
        __nv_bfloat16* op = (__nv_bfloat16*)ostash(br, b, h) + (q >> 5) * 256 + 2 * ((q & 31) >> 3) + (q & 1);
#pragma unroll
        for (int i = 0; i < 6; i++) {
            const uint32_t d = (i >> 1) * 64 + 2 * lane + (i & 1);
            op[(d >> 3) * 1280 + (d & 7) * 32 + ((((q & 7) >> 1) ^ ((d & 7) >> 1)) << 3)] = __float2bfloat16(o[i] * inv);
        }
    }
}

template <int W>
struct PendO {
    static constexpr int N = W == 0 ? 56 : 64;
    uint32_t v[N];
    unsigned char* gp;
    static __device__ __forceinline__ uint32_t toff() {
        const uint32_t t = tid_now();
        return ((t >> 5) & 3) * 5120 + ((t >> 2) & 7) * 64 + (((t ^ (t >> 3)) & 3) << 4);
    }
    uint32_t pend, sig;
    static __device__ __forceinline__ void scale(uint32_t& x, uint32_t hi, uint32_t lo) {
        asm("{\n.reg .b32 t;\nmul.rn.bf16x2 t, %0, %2;\nfma.rn.bf16x2 %0, %0, %1, t;\n}" : "+r"(x) : "r"(hi), "r"(lo));
    }
    template <int I, int OFF>
    __device__ __forceinline__ void put() {
        asm volatile("{\n.reg .pred p;\nsetp.ne.u32 p, %6, 0;\n@p st.global.v4.b32 [%0+%5], {%1,%2,%3,%4};\n}" ::"l"(gp), "r"(v[I]),
                     "r"(v[I + 1]), "r"(v[I + 2]), "r"(v[I + 3]), "n"(OFF), "r"(pend)
                     : "memory");
    }
    __device__ __forceinline__ void verdict(const Params& P, uint32_t sb, int ie) {
        if (sig) {
            nb_sync<NB_VOTE + W, 160>();
            pend = !__any_sync(0xffffffffu, lds_u(sb + OFF_FB) != 0);
            if (W == 1 && !pend) {
                fallback_unit(P, lds_u(sb + OFF_ITEM + ie * 4), tid_now() & 127);
                __syncwarp();
            }
        }
    }
    template <int G, int H>
    __device__ __forceinline__ void half(uint32_t sb) {
        constexpr bool T2 = W == 0 ? G >= 3 : G < 3;
        constexpr int B = T2 ? 40 + 8 * (W == 0 ? G - 3 : G) : 0;
        const uint4 a = lds_u4(sb + OFF_LINV + G * 128 + H * 16 + (threadIdx.x & 3) * 32);
#pragma unroll
        for (int i = 2 * H; i < 8; i += 4) {
            scale(v[8 * G + i], a.x, a.y);
            scale(v[8 * G + i + 1], a.z, a.w);
            if (T2) {
                scale(v[B + i], a.x, a.y);
                scale(v[B + i + 1], a.z, a.w);
            }
        }
        if (H == 1) {
            put<8 * G, W * XS + G * 512>();
            put<8 * G + 4, W * XS + G * 512 + 2560>();
            if (T2) {
                put<B, 2 * XS + G * 512>();
                put<B + 4, 2 * XS + G * 512 + 2560>();
            }
            if (G == 4 && sig) nb_arrive<NB_ODONE, 288>();
        }
    }
    template <int G>
    __device__ __forceinline__ void step(uint32_t sb) {
        half<G, 0>(sb);
        half<G, 1>(sb);
    }
    __device__ __forceinline__ void clear() {
#pragma unroll
        for (int i = 0; i < N; i++) v[i] = 0;
        gp = nullptr;
        pend = 0;
        sig = 0;
    }
};

template <int W, int KK>
__device__ __forceinline__ void qproj(float (&q0)[80], float (&q1)[80], uint32_t sb, Ring& r, uint32_t pslot, uint32_t phm,
                                      PendO<W>& po, const Params& P, int it) {
    const uint32_t loR = (((sb + OFF_R) & 0x3ffff) >> 4) | LO_LBO1;
    const uint32_t loRing = (((sb + OFF_RING) & 0x3ffff) >> 4) | LO_LBO1;
    auto ready = [&](int k) {
        mbar_wait(sb + BAR_RFULL + r.slot * 8, r.ph, r.dl);
        mbar_wait(sb + BAR_XFULL + (k % 5) * 8, ((phm >> (k % 5)) ^ (k / 5)) & 1, r.dl);
    };
    auto release = [&]() {
        if (KK > 0) {
            wg_wait<1>();
            mbar_arrive_warp(sb + BAR_REMPTY + pslot * 8);
            if (KK <= 5) mbar_arrive_warp(sb + (BAR_XEMPTY + (KK - 1) * 8));
        }
    };
    if (KK == 0) ready(0);
    if (W == 1 && KK == QHOLD) nb_sync<NB_SDONE, 256>();
    const uint32_t a = loRing + r.slot * (SLOT >> 4) + (W == 0 ? 0 : 512), b = loR + (KK % 5) * (XS >> 4);
    wg_fence();
    wgmma<1, 0, HI_SW128, KK != 0>(q0, a, b);
    if (W == 0) wgmma<1, 0, HI_SW128, KK != 0>(q1, a + 256, b);
#pragma unroll
    for (int k = 1; k < 4; k++) {
        wgmma<1, 0, HI_SW128, true>(q0, a + (k >> 1) * 768 + (k & 1) * 128, b + k * 2);
        if (W == 0) wgmma<1, 0, HI_SW128, true>(q1, a + 256 + (k >> 1) * 768 + (k & 1) * 128, b + k * 2);
    }
    wg_commit();
    const uint32_t cslot = r.slot;
    r.adv(1);
    if (W == 0 || KK < QHOLD) release();
    if (KK == QST0) {
        po.verdict(P, sb, it - 1);
        po.template half<0, 0>(sb);
    }
    if (KK < 9) ready(KK + 1);
    if (W == 1 && KK >= QHOLD) release();
    if (W == 1 && KK == 7) nb_arrive<NB_PDONE, 256>();
    if (KK == QST0) po.template half<0, 1>(sb);
    if constexpr (KK > QST0 && KK < QST0 + 5) po.template step<KK - QST0>(sb);
    if constexpr (KK < 9) {
        qproj<W, KK + 1>(q0, q1, sb, r, cslot, phm, po, P, it);
    } else {
        if (W == 0) nb_arrive<NB_SDONE, 256>();
        wg_wait<0>();
        reg_fence(q0);
        if (W == 0) reg_fence(q1);
        mbar_arrive_warp(sb + BAR_REMPTY + cslot * 8);
    }
}

template <int NR>
__device__ __forceinline__ void opack(const float (&o)[NR], uint32_t* v) {
#pragma unroll
    for (int g = 0; g < NR / 16; g++)
#pragma unroll
        for (int hh = 0; hh < 2; hh++)
#pragma unroll
            for (int t = 0; t < 4; t++) v[8 * g + 4 * hh + t] = pack_bf16(o[16 * g + 4 * t + 2 * hh], o[16 * g + 4 * t + 2 * hh + 1]);
}

__device__ __forceinline__ void wait_flag(const unsigned int* f, uint32_t epoch) {
    uint32_t v, n = 0;
    do {
        asm volatile("ld.acquire.gpu.global.u32 %0, [%1];" : "=r"(v) : "l"(f) : "memory");
        if (++n > 0x1000000) __trap();
    } while (v != epoch);
}

template <bool IS_S>
__device__ __forceinline__ void op_item(uint32_t e, uint32_t sb, Ring& r, uint32_t& phm) {
    constexpr int T0 = IS_S ? 0 : 2;
    constexpr uint32_t BOFF = IS_S ? (3 * 512) >> 4 : 0;
    const uint32_t loRing = (((sb + OFF_RING) & 0x3ffff) >> 4) | LO_LBO1;
    const uint32_t loO = (((sb + OFF_R) & 0x3ffff) >> 4) | LO_OST;
    float c0[80], c1[80], c2[IS_S ? 32 : 48];
    const int T2 = 6 * (IT_H1(e) - IT_H0(e));
    uint32_t xs = 0;
    auto step = [&](auto first, uint32_t hf) {
        constexpr bool F = decltype(first)::value;
        if (hf == 0) {
            mbar_wait(sb + BAR_XFULL + xs * 8, (phm >> xs) & 1, r.dl);
            phm ^= 1u << xs;
        }
        mbar_wait(sb + BAR_RFULL + r.slot * 8, r.ph, r.dl);
        const uint32_t a = loRing + r.slot * (SLOT >> 4), b = loO + xs * (XS >> 4) + hf * 640;
        wg_fence();
        wgmma<1, 1, HI_OST, !F>(c0, a + T0 * 128, b);
        wgmma<1, 1, HI_OST, !F>(c1, a + T0 * 128 + 128, b);
        wgmma<1, 1, HI_OST, !F>(c2, a + 512, b + BOFF);
        wgmma<1, 1, HI_OST, true>(c0, a + 640 + T0 * 128, b + 320);
        wgmma<1, 1, HI_OST, true>(c1, a + 640 + T0 * 128 + 128, b + 320);
        wgmma<1, 1, HI_OST, true>(c2, a + 640 + 512, b + 320 + BOFF);
        wg_commit();
    };
    step(TrueT{}, 0);
#pragma unroll 1
    for (int t = 1; t < T2; t++) {
        const uint32_t pslot = r.slot, pxs = xs;
        r.adv(1);
        if ((t & 1) == 0 && ++xs == 5) xs = 0;
        step(FalseT{}, t & 1);
        wg_wait<1>();
        mbar_arrive_warp(sb + BAR_REMPTY + pslot * 8);
        if ((t & 1) == 0 && t + 8 < T2) mbar_arrive_warp(sb + BAR_XEMPTY + pxs * 8);
    }
    wg_wait<0>();
    reg_fence(c0);
    reg_fence(c1);
    reg_fence(c2);
    mbar_arrive_warp(sb + BAR_REMPTY + r.slot * 8);
    r.adv(1);
    nb_sync<NB_OPEND, 256>();
    const uint32_t tid = tid_now(), lane = tid & 31, w = (tid >> 5) & 3;
    store_out_tile<false>(c0, sb + OFF_R + T0 * XS, lane, w);
    store_out_tile<false>(c1, sb + OFF_R + (T0 + 1) * XS, lane, w);
    store_out_tile<false>(c2, sb + OFF_R + 4 * XS + (IS_S ? 96 * 128 : 0), lane, w);
    fence_async_smem();
    nb_arrive<NB_ODONE, 288>();
}

template <int W>
__device__ __forceinline__ void on_item(uint32_t e, uint32_t sb, Ring& r, uint32_t& phm) {
    const uint32_t loRing = (((sb + OFF_RING) & 0x3ffff) >> 4) | LO_LBO1;
    const uint32_t loO = (((sb + OFF_R) & 0x3ffff) >> 4) | LO_OST;
    float c[80];
    const int T = 3 * (IT_H1(e) - IT_H0(e));
    uint32_t xs = 0;
    auto step = [&](auto first) {
        constexpr bool F = decltype(first)::value;
        mbar_wait(sb + BAR_XFULL + xs * 8, (phm >> xs) & 1, r.dl);
        phm ^= 1u << xs;
        mbar_wait(sb + BAR_RFULL + r.slot * 8, r.ph, r.dl);
        const uint32_t a = loRing + r.slot * (SLOT >> 4) + W * 256, b = loO + xs * (XS >> 4);
        wg_fence();
        wgmma<1, 1, HI_OST, !F>(c, a, b);
#pragma unroll
        for (int k = 1; k < 4; k++) wgmma<1, 1, HI_OST, true>(c, a + (k >> 1) * 512 + (k & 1) * 128, b + k * 320);
        wg_commit();
    };
    step(TrueT{});
#pragma unroll 1
    for (int t = 1; t < T; t++) {
        const uint32_t pslot = r.slot, pxs = xs;
        r.adv(1);
        if (++xs == 5) xs = 0;
        step(FalseT{});
        wg_wait<1>();
        mbar_arrive_warp(sb + BAR_REMPTY + pslot * 8);
        mbar_arrive_warp_if(sb + BAR_XEMPTY + pxs * 8, t + 2 < T);
    }
    xs += 1 + W;
    if (xs >= 5) xs -= 5;
    mbar_wait(sb + BAR_XFULL + xs * 8, (phm >> xs) & 1, r.dl);
    wg_wait<0>();
    reg_fence(c);
    const uint32_t tid = tid_now();
    store_out_tile<true>(c, sb + OFF_R + xs * XS, tid & 31, (tid >> 5) & 3);
    fence_async_smem();
    nb_arrive<NB_ODONE, 288>();
}

template <int W>
__device__ __forceinline__ uint32_t qa_item(const Params& P, uint32_t e, uint32_t sb, Ring& r, uint32_t phm, PendO<W>& po, int it) {
    const uint32_t loR = (((sb + OFF_R) & 0x3ffff) >> 4) | LO_LBO1;
    const uint32_t loRing = (((sb + OFF_RING) & 0x3ffff) >> 4) | LO_LBO1;
    uint32_t lane, sta;
    {
        float q0[80], q1[80];
        qproj<W, 0>(q0, q1, sb, r, 0, phm, po, P, it);
        const uint32_t tid = tid_now();
        lane = tid & 31;
        sta = sb + OFF_R + (lane >> 4) * 1024 + (lane & 7) * 128 + (((((tid >> 4) & 6) + ((lane >> 3) & 1)) ^ (lane & 7)) << 4);
        TSD(W, 1);
        if (W == 0) {
            nb_sync<NB_PDONE, 256>();
            store_tile_t(q0, sta);
            store_tile_t(q1, sta + XS);
        } else {
            store_tile_t(q0, sta + 2 * XS);
        }
    }
    fence_async_smem();
    float s[80], oa[80], ob[W == 0 ? 32 : 48], l[10];
    zero(oa);
    zero(ob);
    zero(l);
    reg_fence(oa);
    reg_fence(ob);
    auto pv = [&](const Ring& rv, uint32_t buf) {
        mbar_wait(sb + BAR_RFULL + rv.slot * 8, rv.ph, rv.dl);
        const uint32_t a = loRing + rv.slot * (SLOT >> 4), b = loR + (3 + buf) * (XS >> 4);
        wg_fence();
#pragma unroll
        for (int k = 0; k < 4; k++) {
            wgmma<1, 0, HI_SW128, true>(oa, a + W * 512 + k * 128, b + k * 2);
            wgmma<1, 0, HI_SW128, true>(ob, a + 1024 + k * 128, b + (W == 0 ? (96 * 128) >> 4 : 0) + k * 2);
        }
        wg_commit();
    };
    float mref;
    uint32_t kslot, vslot;
    auto tail = [&](bool rel_other, int i) {
        uint32_t ps[40];
        exp_block<0>(s, ps, sta + (3 + W) * XS, mref);
        if (rel_other) {
            wg_wait<0>();
            mbar_arrive_warp(sb + BAR_REMPTY + vslot * 8);
            if (W == 1) mbar_arrive_warp_if(sb + BAR_XEMPTY + 24, i == 3);
        }
        fence_async_smem();
        nb_arrive<NB_PFULL + W, 256>();
        TSD(W, 6 + 5 * i);
        if (W == 1) {
            if (XLATE >= 2) mbar_arrive_warp_if<2>(sb + BAR_XEMPTY + 8, i == 3);
            if (XLATE >= 1) mbar_arrive_warp_if<2>(sb + BAR_XEMPTY + 16, i == 3);
        }
        if (rel_other || !PV0FIRST) {
            mbar_wait(sb + BAR_RFULL + r.slot * 8, r.ph, r.dl);
            sum_block(ps, l, lane);
        }
        TSD(W, 7 + 5 * i);
        nb_sync<NB_W + W, 128>();
        pv(r, W);
        if (!rel_other && PV0FIRST) sum_block(ps, l, lane);
        TSD(W, 8 + 5 * i);
    };
    if (W == 0) {
        sts_u(sb + OFF_GM + 4, r.slot);
        mbar_wait(sb + BAR_RFULL + r.slot * 8, r.ph, r.dl);
        nb_sync<NB_QK, 160>();
        TSD(W, 2);
        wg_fence();
        qk_steps<0, 8>(s, loRing + r.slot * (SLOT >> 4), loR);
        nb_sync<NB_Q2, 288>();
        qk_steps<8, 12>(s, loRing + r.slot * (SLOT >> 4), loR);
        wg_commit();
        nb_arrive<NB_Q01, 256>();
        TSD(W, 4);
        nb_sync<NB_REF, 160>();
        mref = __uint_as_float(lds_u(sb + OFF_GM));
        wg_wait<0>();
        reg_fence(s);
        mbar_arrive_warp<2>(sb + BAR_REMPTY + r.slot * 8);
        r.adv(2);
        TSD(W, 5);
        tail(false, 0);
    } else {
        nb_arrive<NB_Q2, 288>();
        TSD(W, 2);
        nb_sync<NB_Q01, 256>();
    }
#pragma unroll 1
    for (int i = (W == 0 ? 1 : 0); i < 4; i++) {
        const uint32_t pvslot = r.slot;
        r.adv(1);
        kslot = r.slot;
        mbar_wait(sb + BAR_RFULL + r.slot * 8, r.ph, r.dl);
        wg_fence();
        qk_steps<0, 12>(s, loRing + r.slot * (SLOT >> 4), loR);
        wg_commit();
        wg_wait<1>();
        mbar_arrive_warp_if(sb + BAR_REMPTY + pvslot * 8, W == 0 || i > 0);
        r.adv(1);
        vslot = r.slot;
        TSD(W, 4 + 5 * i);
        nb_sync<NB_PFULL + (W ^ 1), 256>();
        pv(r, W ^ 1);
        if (W == 1) mref = __uint_as_float(lds_u(sb + OFF_GM));
        wg_wait<1>();
        reg_fence(s);
        mbar_arrive_warp<2>(sb + BAR_REMPTY + kslot * 8);
        if (W == 1) {
            mbar_arrive_warp_if<2>(sb + BAR_XEMPTY + 0, i == 3);
            if (XLATE < 2) mbar_arrive_warp_if<2>(sb + BAR_XEMPTY + 8, i == 3);
            if (XLATE < 1) mbar_arrive_warp_if<2>(sb + BAR_XEMPTY + 16, i == 3);
        }
        r.adv(W == 1 && i == 3 ? 1 : 2);
        TSD(W, 5 + 5 * i);
        tail(true, i);
    }
    const uint32_t w = (tid_now() >> 5) & 3;
    const uint32_t lxa = sb + OFF_LX + w * 640 + (((lane & 8) ? 80 : 0) + ((lane >> 1) & 8) + 2 * (lane & 3) + ((lane >> 2) & 1)) * 4;
    const uint32_t nx = get_item_warp(sb, it + 1, r.dl);
    po.gp = ostash(IT_BR(e), IT_B(e), IT_H0(e)) + po.toff();
    po.sig = 1;
    if (W == 0) {
        sum_store<false>(l, lane, lxa);
        nb_arrive<NB_LX, 256>();
        wg_wait<0>();
        mbar_arrive_warp(sb + BAR_REMPTY + r.slot * 8);
        mbar_arrive_warp(sb + BAR_XEMPTY + 24);
        r.adv(1);
        nb_sync<NB_PFULL + 1, 256>();
        pv(r, 1);
    } else {
        nb_sync<NB_LX, 256>();
        sum_store<true>(l, lane, lxa);
        nb_arrive<NB_L, 160>();
    }
    TSD(W, 24);
    wg_wait<0>();
    reg_fence(oa);
    reg_fence(ob);
    mbar_arrive_warp(sb + BAR_REMPTY + r.slot * 8);
    mbar_arrive_warp(sb + BAR_XEMPTY + 32);
    r.adv(1);
    opack(ob, po.v + 40);
    opack(oa, po.v);
    return nx;
}

template <int W>
__device__ __forceinline__ void consumer(const Params& P, uint32_t sb, uint32_t dl) {
    int it = 0;
    if (W == 0) TS(0, 30);
    Ring r{0, 0, dl};
    uint32_t phm = 0;
    uint32_t e = get_item_warp(sb, 0, dl);
#pragma unroll 1
    while (e != 0) {
        if (IT_TYPE(e) == IT_QA) {
            PendO<W> po;
            po.clear();
#pragma unroll 1
            do {
                TS(W, 0);
                if (W == 0) TS_ITEM(e);
                e = qa_item<W>(P, e, sb, r, phm, po, it);
                TS(W, 31);
                it++;
            } while (IT_TYPE(e) == IT_QA);
            po.verdict(P, sb, it - 1);
            po.template step<0>(sb);
            po.template step<1>(sb);
            po.template step<2>(sb);
            po.template step<3>(sb);
            po.template step<4>(sb);
        } else {
            TS(W, 0);
            if (W == 0) TS_ITEM(e);
            if (IT_TYPE(e) == IT_OP) op_item<W == 0>(e, sb, r, phm);
            else on_item<W>(e, sb, r, phm);
            TS(W, 31);
            e = get_item_warp(sb, ++it, dl);
        }
    }
    TS_DUMP(W);
}

__global__ void __cluster_dims__(2, 1, 1) __launch_bounds__(384, 1) fused_kernel(const __grid_constant__ Params P) {
    extern __shared__ __align__(1024) unsigned char smem_raw[];
    const uint32_t sb = (uint32_t)__cvta_generic_to_shared(smem_raw);
    const uint32_t wgid = __shfl_sync(0xffffffffu, threadIdx.x >> 7, 0);
    const uint32_t cta = blockIdx.x;
    const uint32_t dl = deadline();

    uint32_t epoch = 0;
    if (wgid == 0) epoch = *(volatile unsigned int*)&g_epoch[cta] + 1;
    if (threadIdx.x == 0) {
        if (sb & 1023) __trap();
        for (int i = 0; i < NSLOT; i++) {
            mbar_init(sb + BAR_RFULL + i * 8, 1);
            mbar_init(sb + BAR_REMPTY + i * 8, 8);
            mbar_init(sb + BAR_XFULL + i * 8, 1);
            mbar_init(sb + BAR_XEMPTY + i * 8, 8);
            mbar_init(sb + BAR_PRDY + i * 8, 1);
        }
        for (int i = 0; i < MAXI; i++) mbar_init(sb + BAR_ITEM + i * 8, 1);
        asm volatile("fence.mbarrier_init.release.cluster;" ::: "memory");
        fence_async_smem();
    }
    __syncthreads();
    asm volatile("barrier.cluster.arrive.relaxed.aligned;\nbarrier.cluster.wait.aligned;" ::: "memory");

    if (wgid == 0) {
        asm volatile("setmaxnreg.dec.sync.aligned.u32 24;");
        const uint32_t warp = __shfl_sync(0xffffffffu, threadIdx.x >> 5, 0);
        if (warp == 0) {
            if (threadIdx.x == 0) {
                *(volatile unsigned int*)&g_epoch[cta] = epoch;
                const uint64_t pol_first = mkpol<1>(), pol_norm = mkpol<POL_W>();
                if (cta == 0) *(volatile unsigned int*)&g_ticket[(epoch + 1) & 1] = 0;
                const uint32_t rank = cta & 1;
                uint32_t peer;
                asm volatile("mapa.shared::cluster.u32 %0, %1, %2;" : "=r"(peer) : "r"(sb), "r"(rank ^ 1));
                Ring r{0, 1, dl};
                uint32_t pm = 0;
                auto load_w = [&](const CUtensorMap* m, int row, int blk, uint32_t half_bytes) {
                    mbar_wait(sb + BAR_REMPTY + r.slot * 8, r.ph, dl);
                    mbar_expect(sb + BAR_RFULL + r.slot * 8, 2 * half_bytes);
                    asm volatile("mbarrier.arrive.shared::cluster.b64 _, [%0];" ::"r"(peer + BAR_PRDY + r.slot * 8) : "memory");
                    mbar_wait(sb + BAR_PRDY + r.slot * 8, (pm >> r.slot) & 1, dl);
                    pm ^= 1u << r.slot;
                    tma3_mc(sb + OFF_RING + r.slot * SLOT + rank * half_bytes, m, row, blk, sb + BAR_RFULL + r.slot * 8, pol_norm);
                    r.adv(1);
                };
                uint32_t e = 0;
                if (rank == 0) {
                    const uint32_t d = P.delay[cta >> 1];
                    uint32_t t0, t1;
                    asm volatile("mov.u32 %0, %%clock;" : "=r"(t0));
                    do {
                        asm volatile("mov.u32 %0, %%clock;" : "=r"(t1));
                    } while (t1 - t0 < d);
                    e = P.items[cta >> 1][0];
                }
#pragma unroll 1
                for (int it = 0;; it++) {
                    uint32_t nx = 0, tk = 0;
                    if (rank == 0) {
                        asm volatile("st.async.weak.shared::cluster.mbarrier::complete_tx::bytes.b32 [%0], %1, [%2];" ::"r"(
                                         peer + OFF_ITEM + it * 4),
                                     "r"(e ? e + 8 : 0), "r"(peer + BAR_ITEM + it * 8)
                                     : "memory");
                        sts_u(sb + OFF_ITEM + it * 4, e);
                        asm volatile("mbarrier.arrive.shared::cta.b64 _, [%0];" ::"r"(sb + BAR_ITEM + it * 8) : "memory");
                        if (IT_TYPE(e) != IT_ON && it + 2 < MAXI) nx = P.items[cta >> 1][it + 1 < NSTAT ? it + 1 : NSTAT - 1];
                    } else {
                        mbar_expect(sb + BAR_ITEM + it * 8, 4);
                        e = get_item(sb, it, dl);
                    }
                    if (e == 0) break;
                    const uint32_t br = IT_BR(e);
                    if (IT_TYPE(e) == IT_QA) {
                        const uint32_t h = IT_H0(e);
#pragma unroll 1
                        for (int kk = 0; kk < 10; kk++) load_w(&P.wq[br], kk * 64 + rank * 32, h * 3, SLOT / 2);
                        const int row0 = (IT_B(e) * 32 + h) * 512;
#pragma unroll 1
                        for (int n = 0; n < 16; n++) {
                            if (n == 13 && nx == IT_DYN) tk = atomicAdd(&g_ticket[epoch & 1], 1);
                            const bool isv = n == 15 || (n > 0 && !(n & 1));
                            const int j = n == 15 ? 7 : isv ? (n - 2) >> 1 : (n + 1) >> 1;
                            mbar_wait(sb + BAR_REMPTY + r.slot * 8, r.ph, dl);
                            mbar_expect(sb + BAR_RFULL + r.slot * 8, SLOT);
                            tma3(sb + OFF_RING + r.slot * SLOT, isv ? &P.v[br] : &P.k[br], row0 + j * 64, 0,
                                 sb + BAR_RFULL + r.slot * 8, pol_first);
                            r.adv(1);
                        }
                    } else {
                        const bool wide = IT_TYPE(e) == IT_OP;
                        const int step = wide ? 32 : 64, r1 = IT_H1(e) * 192;
#pragma unroll 1
                        for (int row = IT_H0(e) * 192 + rank * (step >> 1); row < r1; row += step)
                            load_w(wide ? &P.wo[br] : &P.won[br], row, IT_HALF(e) * (wide ? 5 : 2), wide ? XS / 2 : 8192);
                        if (nx == IT_DYN) tk = atomicAdd(&g_ticket[epoch & 1], 1);
                    }
                    if (nx == IT_DYN) nx = tk < P.nlist ? P.list[tk] : 0;
                    e = nx;
                }
            }
        } else if (warp == 1) {
            if (threadIdx.x == 32) {
                const uint64_t pol_norm = mkpol<POL_X>(), pol_o = mkpol<POL_O>();
                uint32_t phm = 0x1f;
#pragma unroll 1
                for (int it = 0;; it++) {
                    const uint32_t e = get_item(sb, it, dl);
                    if (e == 0) break;
                    const uint32_t br = IT_BR(e);
                    uint32_t xs = 0;
                    if (IT_TYPE(e) == IT_QA) {
#pragma unroll 1
                        for (int kk = 0; kk < 10; kk++) {
                            mbar_wait(sb + BAR_XEMPTY + xs * 8, (phm >> xs) & 1, dl);
                            phm ^= 1u << xs;
                            mbar_expect(sb + BAR_XFULL + xs * 8, XS);
                            tma3(sb + OFF_R + xs * XS, &P.x[br], IT_B(e) * 160, kk, sb + BAR_XFULL + xs * 8, pol_norm);
                            if (++xs == 5) xs = 0;
                        }
                    } else {
                        const uint32_t u0 = (br * 16 + IT_B(e)) * 32;
#pragma unroll 1
                        for (uint32_t u = u0 + IT_H0(e); u < u0 + IT_H1(e); u++) {
                            wait_flag(&g_flag[u], epoch);
                            asm volatile("fence.proxy.async;" ::: "memory");
#pragma unroll 1
                            for (int t = 0; t < 3; t++) {
                                mbar_wait(sb + BAR_XEMPTY + xs * 8, (phm >> xs) & 1, dl);
                                phm ^= 1u << xs;
                                mbar_expect(sb + BAR_XFULL + xs * 8, XS);
                                bulk_load(sb + OFF_R + xs * XS, ostash(br, IT_B(e), u & 31) + t * XS, XS, sb + BAR_XFULL + xs * 8, pol_o);
                                if (++xs == 5) xs = 0;
                            }
                        }
                        if (IT_TYPE(e) == IT_ON) {
#pragma unroll 1
                            for (uint32_t tile = 2 * IT_HALF(e); tile < 2 * IT_HALF(e) + 2; tile++) {
                                wait_flag(&g_pflag[(u0 >> 4) + (tile >= 5)], epoch);
                                asm volatile("fence.proxy.async;" ::: "memory");
                                mbar_wait(sb + BAR_XEMPTY + xs * 8, (phm >> xs) & 1, dl);
                                mbar_expect(sb + BAR_XFULL + xs * 8, XS);
                                asm volatile(
                                    "cp.async.bulk.tensor.2d.shared::cluster.global.mbarrier::complete_tx::bytes [%0], [%1, {%3,%4}], [%2];" ::"r"(
                                        sb + OFF_R + xs * XS),
                                    "l"(&P.out), "r"(sb + BAR_XFULL + xs * 8), "r"(br * 640 + tile * 64), "r"(IT_B(e) * 160)
                                    : "memory");
                                if (++xs == 5) xs = 0;
                            }
                        }
                    }
                }
            }
        } else if (warp == 2) {
#pragma unroll 1
            for (int it = 0;; it++) {
                const uint32_t e = get_item_warp(sb, it, dl);
                if (e == 0) break;
                nb_sync<NB_ODONE, 288>();
                if (threadIdx.x == 64) {
                    const uint32_t bb = IT_BR(e) * 16 + IT_B(e);
                    if (IT_TYPE(e) != IT_QA) {
                        const bool wide = IT_TYPE(e) == IT_OP;
                        const int cc0 = IT_BR(e) * 640 + IT_HALF(e) * (wide ? 320 : 128);
                        uint32_t xs = wide ? 0 : (3 * (IT_H1(e) - IT_H0(e))) % 5;
#pragma unroll 1
                        for (int m = 0; m < (wide ? 5 : 2); m++) {
                            asm volatile("cp.async.bulk.tensor.2d.global.shared::cta.bulk_group [%0, {%2,%3}], [%1];" ::"l"(&P.out),
                                         "r"(sb + OFF_R + xs * XS), "r"(cc0 + m * 64), "r"((int)IT_B(e) * 160)
                                         : "memory");
                            asm volatile("cp.async.bulk.commit_group;" ::: "memory");
                            if (++xs == 5) xs = 0;
                        }
                        if (wide) {
#define REL(N)                                                          \
    asm volatile("cp.async.bulk.wait_group.read %0;" ::"n"(4 - N) : "memory"); \
    asm volatile("mbarrier.arrive.shared::cta.b64 _, [%0], 8;" ::"r"(sb + BAR_XEMPTY + N * 8) : "memory");
                            REL(0) REL(1) REL(2) REL(3) REL(4)
#undef REL
                        }
                        if (IT_PART(e)) {
                            asm volatile("cp.async.bulk.wait_group 0;" ::: "memory");
                            asm volatile("fence.proxy.async;" ::: "memory");
                        }
                    }
                    if (IT_TYPE(e) == IT_QA || IT_PART(e)) {
                        __threadfence();
                        unsigned int* f = IT_TYPE(e) == IT_QA ? &g_flag[bb * 32 + IT_H0(e)] : &g_pflag[bb * 2 + IT_HALF(e)];
                        asm volatile("st.relaxed.gpu.global.u32 [%0], %1;" ::"l"(f), "r"(epoch) : "memory");
                    }
                }
                __syncwarp();
            }
            if (threadIdx.x == 64) asm volatile("cp.async.bulk.wait_group 0;" ::: "memory");
            __syncwarp();
            asm volatile("barrier.cluster.arrive.relaxed.aligned;\nbarrier.cluster.wait.aligned;" ::: "memory");
        } else {
            const uint32_t lane = threadIdx.x & 31, p = lane >> 2;
#pragma unroll 1
            for (int it = 0;; it++) {
                const uint32_t e = get_item_warp(sb, it, dl);
                if (e == 0) break;
                if (IT_TYPE(e) != IT_QA) continue;
                nb_sync<NB_QK, 160>();
                const uint32_t co = (((lane & 3) * 2) ^ p) << 4;
                const uint32_t ka = sb + OFF_RING + lds_u(sb + OFF_GM + 4) * SLOT + p * (9 * 128) + co;
                const uint32_t qa = sb + OFF_R + p * (17 * 128) + co;
                uint32_t acc = 0;
#pragma unroll
                for (int c = 0; c < 6; c++) {
                    if (c == 4) nb_sync<NB_Q2, 288>();
                    const uint4 kv = lds_u4((ka + (c >> 1) * 8192) ^ ((c & 1) << 4));
                    const uint4 qv = lds_u4((qa + (c >> 1) * XS) ^ ((c & 1) << 4));
                    acc = fma_bf2(kv.x, qv.x, fma_bf2(kv.y, qv.y, fma_bf2(kv.z, qv.z, fma_bf2(kv.w, qv.w, acc))));
                }
                float d = __uint_as_float(acc << 16) + __uint_as_float(acc & 0xffff0000u);
                d += __shfl_xor_sync(0xffffffffu, d, 1);
                d += __shfl_xor_sync(0xffffffffu, d, 2);
                int key = __float_as_int(d);
                key ^= (key >> 31) & 0x7fffffff;
                key = __reduce_max_sync(0xffffffffu, key);
                key ^= (key >> 31) & 0x7fffffff;
                sts_f(sb + OFF_GM, __int_as_float(key) * SM_C);
                nb_arrive<NB_REF, 160>();
                nb_sync<NB_L, 160>();
                bool bad = false;
#pragma unroll
                for (int c = 0; c < 5; c++) {
                    const uint32_t la = sb + OFF_LX + (c * 32 + lane) * 4;
                    const float v = (__uint_as_float(lds_u(la)) + __uint_as_float(lds_u(la + 640))) +
                                    (__uint_as_float(lds_u(la + 1280)) + __uint_as_float(lds_u(la + 1920)));
                    const float inv = __fdividef(1.f, v);
                    const uint32_t hi = pack_bf16(inv, 0.f), lo = pack_bf16(inv - __uint_as_float(hi << 16), 0.f);
                    const uint32_t ia = sb + OFF_LINV + c * 128 + ((lane >> 1) & 3) * 32 + (lane >> 3) * 8 + (lane & 1) * 2;
                    asm volatile("st.shared.u16 [%0], %1;\nst.shared.u16 [%0+4], %2;" ::"r"(ia), "h"((unsigned short)hi), "h"((unsigned short)lo) : "memory");
                    bad |= !(v >= 5.421010862e-20f && v <= 1.8446744e19f);
                }
                sts_u(sb + OFF_FB, __any_sync(0xffffffffu, bad));
                nb_arrive<NB_VOTE, 160>();
                nb_arrive<NB_VOTE + 1, 160>();
            }
        }
    } else if (wgid == 1) {
        asm volatile("setmaxnreg.inc.sync.aligned.u32 240;");
        consumer<0>(P, sb, dl);
    } else {
        asm volatile("setmaxnreg.inc.sync.aligned.u32 240;");
        consumer<1>(P, sb, dl);
    }
}

typedef CUresult (*EncFn)(CUtensorMap*, CUtensorMapDataType, cuuint32_t, void*, const cuuint64_t*, const cuuint64_t*,
                          const cuuint32_t*, const cuuint32_t*, CUtensorMapInterleave, CUtensorMapSwizzle,
                          CUtensorMapL2promotion, CUtensorMapFloatOOBfill);

void make_map3(EncFn enc, CUtensorMap* m, void* p, uint64_t rows, uint64_t rowbytes, uint64_t nblk, uint32_t boxrows,
               uint32_t boxblk) {
    cuuint64_t dims[3] = {64, rows, nblk};
    cuuint64_t str[2] = {rowbytes, 128};
    cuuint32_t box[3] = {64, boxrows, boxblk};
    cuuint32_t es[3] = {1, 1, 1};
    enc(m, CU_TENSOR_MAP_DATA_TYPE_BFLOAT16, 3, p, dims, str, box, es, CU_TENSOR_MAP_INTERLEAVE_NONE,
        CU_TENSOR_MAP_SWIZZLE_128B, CU_TENSOR_MAP_L2_PROMOTION_NONE, CU_TENSOR_MAP_FLOAT_OOB_FILL_NONE);
}

constexpr int tune(const char*, int def) { return def; }

void build_schedule(Params& P) {
    const int mode = tune("MODE", 4), dmax = tune("DMAX", 26400), n0 = tune("N0", 0);
    const int hmin = tune("HMIN", 19), hmax = tune("HMAX", 25), off = tune("OFF", 0), slope = tune("SLOPE", 1744);
    const int ng = tune("NG", 0), d0 = tune("D0", 0), nkeep = tune("NKEEP", 0), odmax = tune("ODMAX", 0);
    const int ong = tune("ONG", 0), od0 = tune("OD0", 0), jit = tune("JIT", 0);
    const int npos = tune("NPOS", 0), nearly = tune("NEARLY", 0);
    int u = 0;
    auto unit = [&]() {
        const uint32_t e = mk_item(IT_QA, u >> 8, (u & 7) * 2, (u >> 3) & 31, 0, 0);
        u++;
        return e;
    };
    int qa[NCL], nq = 0, op[NCL], no = 0;
    for (int c = 0; c < NCL; c++) {
        P.delay[c] = 0;
        for (int i = 0; i < NSTAT; i++) P.items[c][i] = 0;
        if (mode >= 3 && c < 64 && (c & 3) == 3) op[no++] = c;
        else if (mode != 2 || (c & 3) == 0) qa[nq++] = c;
    }
    for (int t = 0; t < no; t++) {
        P.items[op[t]][1] = mk_item(IT_OP, 0, t & ~1, 0, 32, t & 1);
        P.items[op[t]][2] = P.items[op[t]][3] = IT_DYN;
        P.delay[op[t]] = ong ? od0 + (t * ong / 16) * (odmax / ong) : od0 + t * odmax / 16;
    }
    for (int k = 0; k < nq; k++) {
        const int c = qa[(k * 19) % nq];
        P.items[c][1] = P.items[c][2] = P.items[c][3] = IT_DYN;
        P.delay[c] = k < n0 ? 0 : (int)((long long)dmax * (k + 1 - n0) / (nq - n0));
        if (ng) P.delay[c] = d0 + (k * ng / nq) * (dmax / ng) + (k * ng % nq) * jit / nq;
    }
    for (int k = 0; k < no + nq; k++) {
        int best = -1;
        for (int c = 0; c < NCL; c++)
            if (P.items[c][1] && !P.items[c][0] && (best < 0 || P.delay[c] < P.delay[best])) best = c;
        P.items[best][0] = unit();
    }
    int H[8], pos[8];
    for (int b = 0; b < 8; b++) {
        H[b] = hmin + ((hmax - hmin) * b + 3) / 7;
        pos[b] = (1092 + off - H[b] * slope / 100) / 2;
        if (b < nkeep && no) {
            pos[b] = -1;
            P.items[op[14 - 2 * b]][2] = mk_item(IT_OP, 1, 2 * b, 0, H[b], 0, 1);
            P.items[op[15 - 2 * b]][2] = mk_item(IT_OP, 1, 2 * b, 0, H[b], 1, 1);
        }
    }
    int n = 0, kn = 0;
    const int uend = mode == 2 ? 8 * nq : 512;
    while (u < uend) {
        for (int b = 0; b < 8 && no; b++)
            if (pos[b] == u) {
                P.list[n++] = mk_item(IT_OP, 1, 2 * b, 0, H[b], 0, 1);
                P.list[n++] = mk_item(IT_OP, 1, 2 * b, 0, H[b], 1, 1);
            }
        while (no && u >= uend - npos && kn * npos < (u + 1 - (uend - npos)) * nearly) {
            P.list[n++] = mk_item(IT_ON, 1, kn / 5 * 2, H[kn / 5], 32, kn % 5);
            kn++;
        }
        P.list[n++] = unit();
    }
    for (; no && kn < 40; kn++) P.list[n++] = mk_item(IT_ON, 1, kn / 5 * 2, H[kn / 5], 32, kn % 5);
    P.nlist = n;
}

}

extern "C" void kernel_launch(void* const* d_in, const int* in_sizes, int n_in, void* d_out, int out_size) {
    static Params P;
    static bool init = false;
    if (!init) {
        EncFn enc = nullptr;
        cudaDriverEntryPointQueryResult qr;
        cudaGetDriverEntryPoint("cuTensorMapEncodeTiled", (void**)&enc, cudaEnableDefault, &qr);
        for (int i = 0; i < 2; i++) {
            P.px[i] = (const __nv_bfloat16*)d_in[5 * i + 0];
            P.pk[i] = (const __nv_bfloat16*)d_in[5 * i + 1];
            P.pv[i] = (const __nv_bfloat16*)d_in[5 * i + 2];
            P.pwq[i] = (const __nv_bfloat16*)d_in[5 * i + 3];
            make_map3(enc, &P.x[i], d_in[5 * i + 0], 2560, 1280, 10, 160, 1);
            make_map3(enc, &P.k[i], d_in[5 * i + 1], 16 * 32 * 512, 384, 3, 64, 3);
            make_map3(enc, &P.v[i], d_in[5 * i + 2], 16 * 32 * 512, 384, 3, 64, 3);
            make_map3(enc, &P.wq[i], d_in[5 * i + 3], 640, 12288, 96, 32, 3);
            make_map3(enc, &P.wo[i], d_in[5 * i + 4], 6144, 1280, 10, 16, 5);
            make_map3(enc, &P.won[i], d_in[5 * i + 4], 6144, 1280, 10, 32, 2);
        }
        cuuint64_t dims[2] = {1280, 2560};
        cuuint64_t str[1] = {2560};
        cuuint32_t box[2] = {64, 160};
        cuuint32_t es[2] = {1, 1};
        enc(&P.out, CU_TENSOR_MAP_DATA_TYPE_BFLOAT16, 2, d_out, dims, str, box, es, CU_TENSOR_MAP_INTERLEAVE_NONE,
            CU_TENSOR_MAP_SWIZZLE_128B, CU_TENSOR_MAP_L2_PROMOTION_NONE, CU_TENSOR_MAP_FLOAT_OOB_FILL_NONE);
        build_schedule(P);
        cudaFuncSetAttribute(fused_kernel, cudaFuncAttributeMaxDynamicSharedMemorySize, SMEM_LAUNCH);
        init = true;
    }
    fused_kernel<<<NCTA, 384, SMEM_LAUNCH>>>(P);
}
```

```cpp
#include <cuda_runtime.h>
#include <cuda.h>
#include <cuda_bf16.h>
#include <stdint.h>

namespace {

constexpr int NCTA = 132;
constexpr int NCL = NCTA / 2;
constexpr int MAXI = 16;
constexpr int NSTAT = 4;
constexpr uint32_t IT_DYN = 0xffffffffu;
constexpr int SLOT = 24576;
constexpr int NSLOT = 5;
constexpr int XS = 20480;
constexpr int OFF_R = 0;
constexpr int OFF_RING = 5 * XS;
constexpr int OFF_MISC = OFF_RING + NSLOT * SLOT;
constexpr int OFF_LX = OFF_MISC;
constexpr int OFF_LINV = OFF_LX + 2560;
constexpr int OFF_FB = OFF_LINV + 640;
constexpr int OFF_GM = OFF_FB + 16;
constexpr int OFF_BAR = OFF_GM + 16;
constexpr int BAR_RFULL = OFF_BAR;
constexpr int BAR_REMPTY = BAR_RFULL + 40;
constexpr int BAR_XFULL = BAR_REMPTY + 40;
constexpr int BAR_XEMPTY = BAR_XFULL + 40;
constexpr int BAR_PRDY = BAR_XEMPTY + 40;
constexpr int BAR_ITEM = BAR_PRDY + 40;
constexpr int OFF_ITEM = BAR_ITEM + MAXI * 8;
constexpr int SMEM_BYTES = OFF_ITEM + MAXI * 4;
static_assert(SMEM_BYTES <= 232448, "smem");

constexpr int NB_W = 1  , NB_PFULL = 3  , NB_VOTE = 5  , NB_Q2 = 7, NB_SDONE = 8, NB_PDONE = 9,
              NB_L = 10, NB_REF = 11, NB_ODONE = 12, NB_OPEND = 13, NB_LX = 14, NB_Q01 = 15, NB_QK = 0  ;

constexpr uint32_t IT_QA = 1, IT_OP = 2, IT_ON = 3;
__host__ __device__ constexpr uint32_t mk_item(uint32_t type, uint32_t br, uint32_t b, uint32_t h0, uint32_t h1, uint32_t half,
                                               uint32_t part = 0) {
    return type | (br << 2) | (b << 3) | (h0 << 7) | (h1 << 13) | (half << 19) | (part << 22);
}
#define IT_TYPE(e) ((e) & 3u)
#define IT_BR(e) (((e) >> 2) & 1u)
#define IT_B(e) (((e) >> 3) & 15u)
#define IT_H0(e) (((e) >> 7) & 63u)
#define IT_H1(e) (((e) >> 13) & 63u)
#define IT_HALF(e) (((e) >> 19) & 7u)
#define IT_PART(e) (((e) >> 22) & 1u)

struct Params {
    CUtensorMap x[2], wq[2], k[2], v[2], wo[2], won[2], out;
    const __nv_bfloat16 *px[2], *pwq[2], *pk[2], *pv[2];
    uint32_t items[NCL][NSTAT];
    uint32_t delay[NCL];
    uint32_t nlist;
    uint32_t list[512];
};

constexpr int OUNIT = 61440;
__device__ __align__(1024) unsigned char g_ostash[(size_t)1024 * OUNIT];
__device__ unsigned int g_flag[32 * 64];
#define ORING 64
__device__ __forceinline__ uint32_t ostash_off(uint32_t br, uint32_t b, uint32_t h) {
    return (((br * 32 + h) % ORING) * 16 + b) * OUNIT;
}
__device__ __forceinline__ unsigned char* ostash(uint32_t br, uint32_t b, uint32_t h) { return g_ostash + ostash_off(br, b, h); }
__device__ unsigned int g_epoch[NCTA];
__device__ unsigned int g_ticket[2];

constexpr int SMEM_LAUNCH = SMEM_BYTES;
#define TS(role, idx)
#define TS_ITEM(e)
#define TS_DUMP(role)
#define TSD(role, idx)

#define POL_W 2
#define POL_X 2
#define POL_O 2
template <int M>
__device__ __forceinline__ uint64_t mkpol() {
    uint64_t p;
    if (M == 0) asm volatile("createpolicy.fractional.L2::evict_normal.b64 %0, 1.0;" : "=l"(p));
    if (M == 1) asm volatile("createpolicy.fractional.L2::evict_first.b64 %0, 1.0;" : "=l"(p));
    if (M == 2) asm volatile("createpolicy.fractional.L2::evict_unchanged.b64 %0, 1.0;" : "=l"(p));
    if (M == 3) asm volatile("createpolicy.fractional.L2::evict_normal.L2::evict_unchanged.b64 %0, 0.25;" : "=l"(p));
    return p;
}
#define STSM_W 1
#define XLATE 2
#define PV0FIRST 1
#define QST0 1
#define QST1 2
#define QHOLD 7
constexpr float SM_C = 0.07216878364870322f * 1.4426950408889634f;

__device__ __forceinline__ uint32_t tid_now() {
    uint32_t t;
    asm volatile("mov.u32 %0, %%tid.x;" : "=r"(t));
    return t;
}
__device__ __forceinline__ void mbar_init(uint32_t a, uint32_t c) {
    asm volatile("mbarrier.init.shared::cta.b64 [%0], %1;" ::"r"(a), "r"(c) : "memory");
}
__device__ __forceinline__ void mbar_expect(uint32_t a, uint32_t b) {
    asm volatile("mbarrier.arrive.expect_tx.shared::cta.b64 _, [%0], %1;" ::"r"(a), "r"(b) : "memory");
}
template <int CNT = 1>
__device__ __forceinline__ void mbar_arrive_warp(uint32_t a) {
    if (CNT == 1)
        asm volatile("{\n.reg .pred p;\nelect.sync _|p, 0xffffffff;\n@p mbarrier.arrive.shared::cta.b64 _, [%0];\n}" ::"r"(a) : "memory");
    else
        asm volatile(
            "{\n.reg .pred p;\nelect.sync _|p, 0xffffffff;\n@p mbarrier.arrive.shared::cta.b64 _, [%0];\n"
            "@p mbarrier.arrive.shared::cta.b64 _, [%0];\n}" ::"r"(a)
            : "memory");
}
template <int CNT = 1>
__device__ __forceinline__ void mbar_arrive_warp_if(uint32_t a, bool cond) {
    if (CNT == 1)
        asm volatile(
            "{\n.reg .pred p, c;\nelect.sync _|p, 0xffffffff;\nsetp.ne.and.u32 c, %1, 0, p;\n"
            "@c mbarrier.arrive.shared::cta.b64 _, [%0];\n}" ::"r"(a), "r"((uint32_t)cond)
            : "memory");
    else
        asm volatile(
            "{\n.reg .pred p, c;\nelect.sync _|p, 0xffffffff;\nsetp.ne.and.u32 c, %1, 0, p;\n"
            "@c mbarrier.arrive.shared::cta.b64 _, [%0];\n@c mbarrier.arrive.shared::cta.b64 _, [%0];\n}" ::"r"(a), "r"((uint32_t)cond)
            : "memory");
}
__device__ __forceinline__ uint32_t deadline() {
    uint32_t c;
    asm volatile("mov.u32 %0, %%clock_hi;" : "=r"(c));
    return c + 4;
}
__device__ __forceinline__ void mbar_wait(uint32_t a, uint32_t ph, uint32_t dl) {
    asm volatile(
        "{\n.reg .pred p;\n.reg .u32 m;\n"
        "LOOP:\n"
        "mbarrier.try_wait.parity.shared::cta.b64 p, [%0], %1;\n"
        "@p bra DONE;\n"
        "mov.u32 m, %%clock_hi;\n"
        "setp.ne.u32 p, m, %2;\n"
        "@p bra LOOP;\n"
        "trap;\n"
        "DONE:\n}" ::"r"(a), "r"(ph), "r"(dl)
        : "memory");
}
template <int ID, int CNT>
__device__ __forceinline__ void nb_sync() { asm volatile("bar.sync %0, %1;" ::"n"(ID), "n"(CNT) : "memory"); }
template <int ID, int CNT>
__device__ __forceinline__ void nb_arrive() { asm volatile("bar.arrive %0, %1;" ::"n"(ID), "n"(CNT) : "memory"); }
__device__ __forceinline__ void fence_async_smem() { asm volatile("fence.proxy.async.shared::cta;" ::: "memory"); }

__device__ __forceinline__ void tma3(uint32_t dst, const CUtensorMap* m, int c1, int c2, uint32_t bar, uint64_t pol) {
    asm volatile(
        "cp.async.bulk.tensor.3d.shared::cluster.global.mbarrier::complete_tx::bytes.L2::cache_hint [%0], [%1, {%3,%4,%5}], [%2], %6;" ::"r"(dst),
        "l"(m), "r"(bar), "r"(0), "r"(c1), "r"(c2), "l"(pol)
        : "memory");
}
__device__ __forceinline__ void tma3_mc(uint32_t dst, const CUtensorMap* m, int c1, int c2, uint32_t bar, uint64_t pol) {
    asm volatile(
        "cp.async.bulk.tensor.3d.shared::cluster.global.mbarrier::complete_tx::bytes.multicast::cluster.L2::cache_hint"
        " [%0], [%1, {%3,%4,%5}], [%2], %6, %7;" ::"r"(dst),
        "l"(m), "r"(bar), "r"(0), "r"(c1), "r"(c2), "h"((unsigned short)3), "l"(pol)
        : "memory");
}
__device__ __forceinline__ void bulk_load(uint32_t dst, const void* src, uint32_t bytes, uint32_t bar, uint64_t pol) {
    asm volatile("cp.async.bulk.shared::cluster.global.mbarrier::complete_tx::bytes.L2::cache_hint [%0], [%1], %2, [%3], %4;" ::"r"(dst),
                 "l"(src), "r"(bytes), "r"(bar), "l"(pol)
                 : "memory");
}
__device__ __forceinline__ void wg_fence() { asm volatile("wgmma.fence.sync.aligned;" ::: "memory"); }
__device__ __forceinline__ void wg_commit() { asm volatile("wgmma.commit_group.sync.aligned;" ::: "memory"); }
template <int N>
__device__ __forceinline__ void wg_wait() { asm volatile("wgmma.wait_group.sync.aligned %0;" ::"n"(N) : "memory"); }

#define RW80(c, d) c(d[0]), c(d[1]), c(d[2]), c(d[3]), c(d[4]), c(d[5]), c(d[6]), c(d[7]), c(d[8]), c(d[9]), c(d[10]), c(d[11]), c(d[12]), c(d[13]), c(d[14]), c(d[15]), c(d[16]), c(d[17]), c(d[18]), c(d[19]), c(d[20]), c(d[21]), c(d[22]), c(d[23]), c(d[24]), c(d[25]), c(d[26]), c(d[27]), c(d[28]), c(d[29]), c(d[30]), c(d[31]), c(d[32]), c(d[33]), c(d[34]), c(d[35]), c(d[36]), c(d[37]), c(d[38]), c(d[39]), c(d[40]), c(d[41]), c(d[42]), c(d[43]), c(d[44]), c(d[45]), c(d[46]), c(d[47]), c(d[48]), c(d[49]), c(d[50]), c(d[51]), c(d[52]), c(d[53]), c(d[54]), c(d[55]), c(d[56]), c(d[57]), c(d[58]), c(d[59]), c(d[60]), c(d[61]), c(d[62]), c(d[63]), c(d[64]), c(d[65]), c(d[66]), c(d[67]), c(d[68]), c(d[69]), c(d[70]), c(d[71]), c(d[72]), c(d[73]), c(d[74]), c(d[75]), c(d[76]), c(d[77]), c(d[78]), c(d[79])
#define RW48(c, d) c(d[0]), c(d[1]), c(d[2]), c(d[3]), c(d[4]), c(d[5]), c(d[6]), c(d[7]), c(d[8]), c(d[9]), c(d[10]), c(d[11]), c(d[12]), c(d[13]), c(d[14]), c(d[15]), c(d[16]), c(d[17]), c(d[18]), c(d[19]), c(d[20]), c(d[21]), c(d[22]), c(d[23]), c(d[24]), c(d[25]), c(d[26]), c(d[27]), c(d[28]), c(d[29]), c(d[30]), c(d[31]), c(d[32]), c(d[33]), c(d[34]), c(d[35]), c(d[36]), c(d[37]), c(d[38]), c(d[39]), c(d[40]), c(d[41]), c(d[42]), c(d[43]), c(d[44]), c(d[45]), c(d[46]), c(d[47])
#define RW32(c, d) c(d[0]), c(d[1]), c(d[2]), c(d[3]), c(d[4]), c(d[5]), c(d[6]), c(d[7]), c(d[8]), c(d[9]), c(d[10]), c(d[11]), c(d[12]), c(d[13]), c(d[14]), c(d[15]), c(d[16]), c(d[17]), c(d[18]), c(d[19]), c(d[20]), c(d[21]), c(d[22]), c(d[23]), c(d[24]), c(d[25]), c(d[26]), c(d[27]), c(d[28]), c(d[29]), c(d[30]), c(d[31])

__device__ __forceinline__ void reg_fence(float (&d)[80]) { asm volatile("" : RW80("+f", d)::"memory"); }
__device__ __forceinline__ void reg_fence(float (&d)[48]) { asm volatile("" : RW48("+f", d)::"memory"); }
__device__ __forceinline__ void reg_fence(float (&d)[32]) { asm volatile("" : RW32("+f", d)::"memory"); }

template <int NR>
__device__ __forceinline__ void zero(float (&d)[NR]) {
#pragma unroll
    for (int i = 0; i < NR; i++) d[i] = 0.f;
}

constexpr uint32_t HI_SW128 = (1024u >> 4) | (1u << 30);
constexpr uint32_t HI_OST = (2560u >> 4) | (2u << 30);
constexpr uint32_t LO_LBO1 = (1u << 16);
constexpr uint32_t LO_OST = ((512u >> 4) << 16);

template <int TA, int TB, uint32_t HIB, int ACC>
__device__ __forceinline__ void wgmma(float (&d)[80], uint32_t loA, uint32_t loB) {
#define WG_ASM(SD)                                                          \
    "{\n.reg .b64 da, db;\nmov.b64 da, {%80, %82};\nmov.b64 db, {%81, %83};\n" \
    "wgmma.mma_async.sync.aligned.m64n160k16.f32.bf16.bf16 "               \
    "{%0,%1,%2,%3,%4,%5,%6,%7,%8,%9,%10,%11,%12,%13,%14,%15,%16,%17,%18,%19,%20,%21,%22,%23,%24,%25,%26,%27,%28,%29,%30,%31,%32,%33,%34,%35,%36,%37,%38,%39,%40,%41,%42,%43,%44,%45,%46,%47,%48,%49,%50,%51,%52,%53,%54,%55,%56,%57,%58,%59,%60,%61,%62,%63,%64,%65,%66,%67,%68,%69,%70,%71,%72,%73,%74,%75,%76,%77,%78,%79}, da, db, " SD ", 1, 1, %84, %85;\n}"
    if constexpr (ACC == 2)
        asm volatile(WG_ASM("0") : RW80("+f", d) : "r"(loA), "r"(loB), "n"(HI_SW128), "n"(HIB), "n"(TA), "n"(TB));
    else if constexpr (ACC == 1)
        asm volatile(WG_ASM("1") : RW80("+f", d) : "r"(loA), "r"(loB), "n"(HI_SW128), "n"(HIB), "n"(TA), "n"(TB));
    else
        asm volatile(WG_ASM("0") : RW80("=f", d) : "r"(loA), "r"(loB), "n"(HI_SW128), "n"(HIB), "n"(TA), "n"(TB));
#undef WG_ASM
}
template <int TA, int TB, uint32_t HIB, int ACC>
__device__ __forceinline__ void wgmma(float (&d)[48], uint32_t loA, uint32_t loB) {
#define WG_ASM(SD)                                                          \
    "{\n.reg .b64 da, db;\nmov.b64 da, {%48, %50};\nmov.b64 db, {%49, %51};\n" \
    "wgmma.mma_async.sync.aligned.m64n96k16.f32.bf16.bf16 "               \
    "{%0,%1,%2,%3,%4,%5,%6,%7,%8,%9,%10,%11,%12,%13,%14,%15,%16,%17,%18,%19,%20,%21,%22,%23,%24,%25,%26,%27,%28,%29,%30,%31,%32,%33,%34,%35,%36,%37,%38,%39,%40,%41,%42,%43,%44,%45,%46,%47}, da, db, " SD ", 1, 1, %52, %53;\n}"
    if constexpr (ACC == 1)
        asm volatile(WG_ASM("1") : RW48("+f", d) : "r"(loA), "r"(loB), "n"(HI_SW128), "n"(HIB), "n"(TA), "n"(TB));
    else
        asm volatile(WG_ASM("0") : RW48("=f", d) : "r"(loA), "r"(loB), "n"(HI_SW128), "n"(HIB), "n"(TA), "n"(TB));
#undef WG_ASM
}
template <int TA, int TB, uint32_t HIB, int ACC>
__device__ __forceinline__ void wgmma(float (&d)[32], uint32_t loA, uint32_t loB) {
#define WG_ASM(SD)                                                          \
    "{\n.reg .b64 da, db;\nmov.b64 da, {%32, %34};\nmov.b64 db, {%33, %35};\n" \
    "wgmma.mma_async.sync.aligned.m64n64k16.f32.bf16.bf16 "               \
    "{%0,%1,%2,%3,%4,%5,%6,%7,%8,%9,%10,%11,%12,%13,%14,%15,%16,%17,%18,%19,%20,%21,%22,%23,%24,%25,%26,%27,%28,%29,%30,%31}, da, db, " SD ", 1, 1, %36, %37;\n}"
    if constexpr (ACC == 1)
        asm volatile(WG_ASM("1") : RW32("+f", d) : "r"(loA), "r"(loB), "n"(HI_SW128), "n"(HIB), "n"(TA), "n"(TB));
    else
        asm volatile(WG_ASM("0") : RW32("=f", d) : "r"(loA), "r"(loB), "n"(HI_SW128), "n"(HIB), "n"(TA), "n"(TB));
#undef WG_ASM
}

__device__ __forceinline__ uint32_t pack_bf16(float lo, float hi) {
    uint32_t r;
    asm("cvt.rn.bf16x2.f32 %0, %1, %2;" : "=r"(r) : "f"(hi), "f"(lo));
    return r;
}
__device__ __forceinline__ float ex2(float x) {
    float r;
    asm("ex2.approx.ftz.f32 %0, %1;" : "=f"(r) : "f"(x));
    return r;
}
__device__ __forceinline__ void stsm4t(uint32_t a, uint32_t r0, uint32_t r1, uint32_t r2, uint32_t r3) {
    asm volatile("stmatrix.sync.aligned.m8n8.x4.trans.shared.b16 [%0], {%1,%2,%3,%4};" ::"r"(a), "r"(r0), "r"(r1), "r"(r2), "r"(r3)
                 : "memory");
}
__device__ __forceinline__ uint32_t lds_u(uint32_t a) {
    uint32_t v;
    asm volatile("ld.shared.u32 %0, [%1];" : "=r"(v) : "r"(a) : "memory");
    return v;
}
__device__ __forceinline__ uint4 lds_u4(uint32_t a) {
    uint4 v;
    asm volatile("ld.shared.v4.u32 {%0,%1,%2,%3}, [%4];" : "=r"(v.x), "=r"(v.y), "=r"(v.z), "=r"(v.w) : "r"(a) : "memory");
    return v;
}
__device__ __forceinline__ float2 lds_f2(uint32_t a) {
    float2 v;
    asm volatile("ld.shared.v2.f32 {%0,%1}, [%2];" : "=f"(v.x), "=f"(v.y) : "r"(a) : "memory");
    return v;
}
__device__ __forceinline__ void sts_f(uint32_t a, float v) { asm volatile("st.shared.f32 [%0], %1;" ::"r"(a), "f"(v) : "memory"); }
__device__ __forceinline__ void sts_u(uint32_t a, uint32_t v) { asm volatile("st.shared.u32 [%0], %1;" ::"r"(a), "r"(v) : "memory"); }
__device__ __forceinline__ void sts_f2(uint32_t a, float x, float y) {
    asm volatile("st.shared.v2.f32 [%0], {%1,%2};" ::"r"(a), "f"(x), "f"(y) : "memory");
}

__device__ __forceinline__ void store_tile_t(const float (&d)[80], uint32_t addr) {
#pragma unroll
    for (int j = 0; j < 10; j++)
        stsm4t(addr + j * 2048, pack_bf16(d[8 * j], d[8 * j + 1]), pack_bf16(d[8 * j + 2], d[8 * j + 3]),
               pack_bf16(d[8 * j + 4], d[8 * j + 5]), pack_bf16(d[8 * j + 6], d[8 * j + 7]));
}
template <bool ADD, int NR>
__device__ __forceinline__ void store_out_tile(const float (&d)[NR], uint32_t base, uint32_t lane, uint32_t w) {
    const uint32_t mi = lane >> 3, i = lane & 7;
    const uint32_t chunk = 2 * w + (mi & 1);
    const uint32_t q0 = 8 * (i >> 1) + 2 * (mi >> 1) + (i & 1);
    const uint32_t a0 = base + q0 * 128 + ((chunk ^ (q0 & 7)) << 4);
    const uint32_t a1 = base + (q0 + 4) * 128 + ((chunk ^ ((q0 + 4) & 7)) << 4);
    uint32_t p[NR / 2];
    if (ADD) {
#pragma unroll
        for (int j = 0; j < NR / 8; j++)
            asm volatile("ldmatrix.sync.aligned.m8n8.x4.trans.shared.b16 {%0,%1,%2,%3}, [%4];"
                         : "=r"(p[4 * j]), "=r"(p[4 * j + 1]), "=r"(p[4 * j + 2]), "=r"(p[4 * j + 3])
                         : "r"(((j & 1) ? a1 : a0) + (j >> 1) * 4096)
                         : "memory");
    }
#pragma unroll
    for (int k = 0; k < NR / 2; k++)
        p[k] = ADD ? pack_bf16(d[2 * k] + __uint_as_float(p[k] << 16), d[2 * k + 1] + __uint_as_float(p[k] & 0xffff0000u))
                   : pack_bf16(d[2 * k], d[2 * k + 1]);
#pragma unroll
    for (int j = 0; j < NR / 8; j++)
        stsm4t(((j & 1) ? a1 : a0) + (j >> 1) * 4096, p[4 * j], p[4 * j + 1], p[4 * j + 2], p[4 * j + 3]);
}

struct TrueT { static constexpr bool value = true; };
struct FalseT { static constexpr bool value = false; };

template <int V>
struct IntT { static constexpr int value = V; };

__device__ __forceinline__ uint32_t get_item(uint32_t sb, int it, uint32_t dl) {
    mbar_wait(sb + BAR_ITEM + it * 8, 0, dl);
    return lds_u(sb + OFF_ITEM + it * 4);
}
__device__ __forceinline__ uint32_t get_item_warp(uint32_t sb, int it, uint32_t dl) {
    return __shfl_sync(0xffffffffu, get_item(sb, it, dl), 0);
}

struct Ring {
    uint32_t slot, ph, dl;
    __device__ __forceinline__ void adv(uint32_t k) {
        slot += k;
        if (slot >= NSLOT) { slot -= NSLOT; ph ^= 1; }
    }
};

template <int K>
__device__ __forceinline__ void qk_step(float (&s)[80], uint32_t loK, uint32_t loQ) {
    wgmma<0, 0, HI_SW128, K != 0>(s, loK + (K >> 2) * (8192 >> 4) + (K & 3) * 2, loQ + (K >> 2) * (XS >> 4) + (K & 3) * 2);
}
template <int K0, int K1>
__device__ __forceinline__ void qk_steps(float (&s)[80], uint32_t loK, uint32_t loQ) {
    if constexpr (K0 < K1) {
        qk_step<K0>(s, loK, loQ);
        qk_steps<K0 + 1, K1>(s, loK, loQ);
    }
}
__device__ __forceinline__ uint32_t add_bf2(uint32_t a, uint32_t b) {
    uint32_t r;
    asm("add.rn.bf16x2 %0, %1, %2;" : "=r"(r) : "r"(a), "r"(b));
    return r;
}
__device__ __forceinline__ uint32_t fma_bf2(uint32_t a, uint32_t b, uint32_t c) {
    uint32_t r;
    asm("fma.rn.bf16x2 %0, %1, %2, %3;" : "=r"(r) : "r"(a), "r"(b), "r"(c));
    return r;
}
template <int J>
__device__ __forceinline__ void exp_block(const float (&s)[80], uint32_t (&k)[40], uint32_t pa, float mref) {
    if constexpr (J < 10) {
#pragma unroll
        for (int i = 4 * J; i < 4 * J + 4; i++)
            k[i] = pack_bf16(ex2(fmaf(s[2 * i], SM_C, -mref)), ex2(fmaf(s[2 * i + 1], SM_C, -mref)));
#pragma unroll
        for (int i = 0; i < 4; i++)
            asm volatile("stmatrix.sync.aligned.m8n8.x1.trans.shared.b16 [%0], {%1};" ::"r"(((i & 1) ? pa ^ 16 : pa) + J * 2048 + (i >> 1) * 1024),
                         "r"(k[4 * J + i])
                         : "memory");
        exp_block<J + 1>(s, k, pa, mref);
    }
}
__device__ __forceinline__ void sum_block(const uint32_t (&k)[40], float (&l)[10], uint32_t lane) {
    const bool b4 = lane & 16, b3 = lane & 8;
    uint32_t ps[20], t[10];
#pragma unroll
    for (int j = 0; j < 20; j++) ps[j] = add_bf2(k[2 * j], k[2 * j + 1]);
#pragma unroll
    for (int j = 0; j < 10; j++)
        t[j] = add_bf2(b4 ? ps[2 * j + 1] : ps[2 * j], __shfl_xor_sync(0xffffffffu, b4 ? ps[2 * j] : ps[2 * j + 1], 16));
#pragma unroll
    for (int i = 0; i < 5; i++) {
        const uint32_t a = b3 ? t[i + 5] : t[i], b = __shfl_xor_sync(0xffffffffu, b3 ? t[i] : t[i + 5], 8);
        l[2 * i] += __uint_as_float(a << 16) + __uint_as_float(b << 16);
        l[2 * i + 1] += __uint_as_float(a & 0xffff0000u) + __uint_as_float(b & 0xffff0000u);
    }
}
template <bool ADD>
__device__ __forceinline__ void sum_store(const float (&l)[10], uint32_t lane, uint32_t lxa) {
    const bool b2 = lane & 4;
    float t[5];
#pragma unroll
    for (int i = 0; i < 5; i++) t[i] = ADD ? __uint_as_float(lds_u(lxa + i * 64)) : 0.f;
#pragma unroll
    for (int i = 0; i < 5; i++)
        sts_f(lxa + i * 64, t[i] + (b2 ? l[2 * i + 1] : l[2 * i]) + __shfl_xor_sync(0xffffffffu, b2 ? l[2 * i] : l[2 * i + 1], 4));
}

__device__ __forceinline__ void fallback_unit(const Params& P, uint32_t e, uint32_t tid) {
    const uint32_t lane = tid & 31, br = IT_BR(e), b = IT_B(e), h = IT_H0(e);
    const __nv_bfloat162* wq = (const __nv_bfloat162*)(P.pwq[br] + h * 192) + lane;
    const __nv_bfloat162* kp = (const __nv_bfloat162*)(P.pk[br] + (size_t)(b * 32 + h) * 512 * 192) + lane;
    const __nv_bfloat162* vp = (const __nv_bfloat162*)(P.pv[br] + (size_t)(b * 32 + h) * 512 * 192) + lane;
#pragma unroll 1
    for (uint32_t qi = 0; qi < 40; qi++) {
        const uint32_t q = 4 * qi + (tid >> 5);
        const __nv_bfloat16* xr = P.px[br] + (size_t)(b * 160 + q) * 640;
        float a[6] = {0.f, 0.f, 0.f, 0.f, 0.f, 0.f};
#pragma unroll 2
        for (int k = 0; k < 640; k++) {
            const float xv = __bfloat162float(xr[k]);
#pragma unroll
            for (int i = 0; i < 3; i++) {
                const float2 wv = __bfloat1622float2(wq[(size_t)k * 3072 + i * 32]);
                a[2 * i] = fmaf(xv, wv.x, a[2 * i]);
                a[2 * i + 1] = fmaf(xv, wv.y, a[2 * i + 1]);
            }
        }
#pragma unroll
        for (int i = 0; i < 6; i++) a[i] = __bfloat162float(__float2bfloat16(a[i]));
        auto score = [&](int key) {
            float d = 0.f;
#pragma unroll
            for (int i = 0; i < 3; i++) {
                const float2 kv = __bfloat1622float2(kp[key * 96 + i * 32]);
                d = fmaf(a[2 * i], kv.x, fmaf(a[2 * i + 1], kv.y, d));
            }
#pragma unroll
            for (int o = 16; o > 0; o >>= 1) d += __shfl_xor_sync(0xffffffffu, d, o);
            return d;
        };
        float m = -INFINITY, o[6] = {0.f, 0.f, 0.f, 0.f, 0.f, 0.f}, sum = 0.f;
#pragma unroll 1
        for (int n = 0; n < 1024; n++) {
            const int key = n & 511;
            const float d = score(key);
            if (n < 512) {
                m = fmaxf(m, d);
            } else {
                const float p = ex2((d - m) * SM_C);
                sum += p;
#pragma unroll
                for (int i = 0; i < 3; i++) {
                    const float2 vv = __bfloat1622float2(vp[key * 96 + i * 32]);
                    o[2 * i] = fmaf(p, vv.x, o[2 * i]);
                    o[2 * i + 1] = fmaf(p, vv.y, o[2 * i + 1]);
                }
            }
        }
        const float inv = __fdividef(1.f, sum);
        __nv_bfloat16* op = (__nv_bfloat16*)ostash(br, b, h) + (q >> 5) * 256 + 2 * ((q & 31) >> 3) + (q & 1);
#pragma unroll
        for (int i = 0; i < 6; i++) {
            const uint32_t d = (i >> 1) * 64 + 2 * lane + (i & 1);
            op[(d >> 3) * 1280 + (d & 7) * 32 + ((((q & 7) >> 1) ^ ((d & 7) >> 1)) << 3)] = __float2bfloat16(o[i] * inv);
        }
    }
}

template <int W>
struct PendO {
    static constexpr int N = W == 0 ? 56 : 64;
    uint32_t v[N];
    unsigned char* gp;
    static __device__ __forceinline__ uint32_t toff() {
        const uint32_t t = tid_now();
        return ((t >> 5) & 3) * 5120 + ((t >> 2) & 7) * 64 + (((t ^ (t >> 3)) & 3) << 4);
    }
    uint32_t pend, sig;
    static __device__ __forceinline__ void scale(uint32_t& x, uint32_t hi, uint32_t lo) {
        asm("{\n.reg .b32 t;\nmul.rn.bf16x2 t, %0, %2;\nfma.rn.bf16x2 %0, %0, %1, t;\n}" : "+r"(x) : "r"(hi), "r"(lo));
    }
    template <int I, int OFF>
    __device__ __forceinline__ void put() {
        asm volatile("{\n.reg .pred p;\nsetp.ne.u32 p, %6, 0;\n@p st.global.v4.b32 [%0+%5], {%1,%2,%3,%4};\n}" ::"l"(gp), "r"(v[I]),
                     "r"(v[I + 1]), "r"(v[I + 2]), "r"(v[I + 3]), "n"(OFF), "r"(pend)
                     : "memory");
    }
    __device__ __forceinline__ void verdict(const Params& P, uint32_t sb, int ie) {
        if (sig) {
            nb_sync<NB_VOTE + W, 160>();
            pend = !__any_sync(0xffffffffu, lds_u(sb + OFF_FB) != 0);
            if (W == 1 && !pend) {
                fallback_unit(P, lds_u(sb + OFF_ITEM + ie * 4), tid_now() & 127);
                __syncwarp();
            }
        }
    }
    template <int G, int H>
    __device__ __forceinline__ void half(uint32_t sb) {
        constexpr bool T2 = W == 0 ? G >= 3 : G < 3;
        constexpr int B = T2 ? 40 + 8 * (W == 0 ? G - 3 : G) : 0;
        const uint4 a = lds_u4(sb + OFF_LINV + G * 128 + H * 16 + (threadIdx.x & 3) * 32);
#pragma unroll
        for (int i = 2 * H; i < 8; i += 4) {
            scale(v[8 * G + i], a.x, a.y);
            scale(v[8 * G + i + 1], a.z, a.w);
            if (T2) {
                scale(v[B + i], a.x, a.y);
                scale(v[B + i + 1], a.z, a.w);
            }
        }
        if (H == 1) {
            put<8 * G, W * XS + G * 512>();
            put<8 * G + 4, W * XS + G * 512 + 2560>();
            if (T2) {
                put<B, 2 * XS + G * 512>();
                put<B + 4, 2 * XS + G * 512 + 2560>();
            }
            if (G == 4 && sig) nb_arrive<NB_ODONE, 288>();
        }
    }
    template <int G>
    __device__ __forceinline__ void step(uint32_t sb) {
        half<G, 0>(sb);
        half<G, 1>(sb);
    }
    __device__ __forceinline__ void clear() {
#pragma unroll
        for (int i = 0; i < N; i++) v[i] = 0;
        gp = nullptr;
        pend = 0;
        sig = 0;
    }
};

template <int W, int KK>
__device__ __forceinline__ void qproj(float (&q0)[80], float (&q1)[80], uint32_t sb, Ring& r, uint32_t pslot, uint32_t phm,
                                      PendO<W>& po, const Params& P, int it) {
    const uint32_t loR = (((sb + OFF_R) & 0x3ffff) >> 4) | LO_LBO1;
    const uint32_t loRing = (((sb + OFF_RING) & 0x3ffff) >> 4) | LO_LBO1;
    auto ready = [&](int k) {
        mbar_wait(sb + BAR_RFULL + r.slot * 8, r.ph, r.dl);
        mbar_wait(sb + BAR_XFULL + (k % 5) * 8, ((phm >> (k % 5)) ^ (k / 5)) & 1, r.dl);
    };
    auto release = [&]() {
        if (KK > 0) {
            wg_wait<1>();
            mbar_arrive_warp(sb + BAR_REMPTY + pslot * 8);
            if (KK <= 5) mbar_arrive_warp(sb + (BAR_XEMPTY + (KK - 1) * 8));
        }
    };
    if (KK == 0) ready(0);
    if (W == 1 && KK == QHOLD) nb_sync<NB_SDONE, 256>();
    const uint32_t a = loRing + r.slot * (SLOT >> 4) + (W == 0 ? 0 : 512), b = loR + (KK % 5) * (XS >> 4);
    wg_fence();
    wgmma<1, 0, HI_SW128, KK != 0>(q0, a, b);
    if (W == 0) wgmma<1, 0, HI_SW128, KK != 0>(q1, a + 256, b);
#pragma unroll
    for (int k = 1; k < 4; k++) {
        wgmma<1, 0, HI_SW128, true>(q0, a + (k >> 1) * 768 + (k & 1) * 128, b + k * 2);
        if (W == 0) wgmma<1, 0, HI_SW128, true>(q1, a + 256 + (k >> 1) * 768 + (k & 1) * 128, b + k * 2);
    }
    wg_commit();
    const uint32_t cslot = r.slot;
    r.adv(1);
    if (W == 0 || KK < QHOLD) release();
    if (KK == QST0) {
        po.verdict(P, sb, it - 1);
        po.template half<0, 0>(sb);
    }
    if (KK < 9) ready(KK + 1);
    if (W == 1 && KK >= QHOLD) release();
    if (W == 1 && KK == 7) nb_arrive<NB_PDONE, 256>();
    if (KK == QST0) po.template half<0, 1>(sb);
    if constexpr (KK > QST0 && KK < QST0 + 5) po.template step<KK - QST0>(sb);
    if constexpr (KK < 9) {
        qproj<W, KK + 1>(q0, q1, sb, r, cslot, phm, po, P, it);
    } else {
        if (W == 0) nb_arrive<NB_SDONE, 256>();
        wg_wait<0>();
        reg_fence(q0);
        if (W == 0) reg_fence(q1);
        mbar_arrive_warp(sb + BAR_REMPTY + cslot * 8);
    }
}

template <int NR>
__device__ __forceinline__ void opack(const float (&o)[NR], uint32_t* v) {
#pragma unroll
    for (int g = 0; g < NR / 16; g++)
#pragma unroll
        for (int hh = 0; hh < 2; hh++)
#pragma unroll
            for (int t = 0; t < 4; t++) v[8 * g + 4 * hh + t] = pack_bf16(o[16 * g + 4 * t + 2 * hh], o[16 * g + 4 * t + 2 * hh + 1]);
}

template <bool IS_S>
__device__ __forceinline__ void op_item(uint32_t e, uint32_t sb, Ring& r, uint32_t& phm) {
    constexpr int T0 = IS_S ? 0 : 2;
    constexpr uint32_t BOFF = IS_S ? (3 * 512) >> 4 : 0;
    const uint32_t loRing = (((sb + OFF_RING) & 0x3ffff) >> 4) | LO_LBO1;
    const uint32_t loO = (((sb + OFF_R) & 0x3ffff) >> 4) | LO_OST;
    float c0[80], c1[80], c2[IS_S ? 32 : 48];
    const int T2 = 6 * (IT_H1(e) - IT_H0(e));
    uint32_t xs = 0;
    auto step = [&](auto first, uint32_t hf) {
        constexpr bool F = decltype(first)::value;
        if (hf == 0) {
            mbar_wait(sb + BAR_XFULL + xs * 8, (phm >> xs) & 1, r.dl);
            phm ^= 1u << xs;
        }
        mbar_wait(sb + BAR_RFULL + r.slot * 8, r.ph, r.dl);
        const uint32_t a = loRing + r.slot * (SLOT >> 4), b = loO + xs * (XS >> 4) + hf * 640;
        wg_fence();
        wgmma<1, 1, HI_OST, !F>(c0, a + T0 * 128, b);
        wgmma<1, 1, HI_OST, !F>(c1, a + T0 * 128 + 128, b);
        wgmma<1, 1, HI_OST, !F>(c2, a + 512, b + BOFF);
        wgmma<1, 1, HI_OST, true>(c0, a + 640 + T0 * 128, b + 320);
        wgmma<1, 1, HI_OST, true>(c1, a + 640 + T0 * 128 + 128, b + 320);
        wgmma<1, 1, HI_OST, true>(c2, a + 640 + 512, b + 320 + BOFF);
        wg_commit();
    };
    step(TrueT{}, 0);
#pragma unroll 1
    for (int t = 1; t < T2; t++) {
        const uint32_t pslot = r.slot, pxs = xs;
        r.adv(1);
        if ((t & 1) == 0 && ++xs == 5) xs = 0;
        step(FalseT{}, t & 1);
        wg_wait<1>();
        mbar_arrive_warp(sb + BAR_REMPTY + pslot * 8);
        if ((t & 1) == 0 && t + 8 < T2) mbar_arrive_warp(sb + BAR_XEMPTY + pxs * 8);
    }
    wg_wait<0>();
    reg_fence(c0);
    reg_fence(c1);
    reg_fence(c2);
    mbar_arrive_warp(sb + BAR_REMPTY + r.slot * 8);
    r.adv(1);
    nb_sync<NB_OPEND, 256>();
    const uint32_t tid = tid_now(), lane = tid & 31, w = (tid >> 5) & 3;
    store_out_tile<false>(c0, sb + OFF_R + T0 * XS, lane, w);
    store_out_tile<false>(c1, sb + OFF_R + (T0 + 1) * XS, lane, w);
    store_out_tile<false>(c2, sb + OFF_R + 4 * XS + (IS_S ? 96 * 128 : 0), lane, w);
    fence_async_smem();
    nb_arrive<NB_ODONE, 288>();
}

template <int W>
__device__ __forceinline__ void on_item(uint32_t e, uint32_t sb, Ring& r, uint32_t& phm) {
    const uint32_t loRing = (((sb + OFF_RING) & 0x3ffff) >> 4) | LO_LBO1;
    const uint32_t loO = (((sb + OFF_R) & 0x3ffff) >> 4) | LO_OST;
    float c[80];
    const int T = 3 * (IT_H1(e) - IT_H0(e));
    uint32_t xs = 0;
    auto step = [&](auto first) {
        constexpr bool F = decltype(first)::value;
        mbar_wait(sb + BAR_XFULL + xs * 8, (phm >> xs) & 1, r.dl);
        phm ^= 1u << xs;
        mbar_wait(sb + BAR_RFULL + r.slot * 8, r.ph, r.dl);
        const uint32_t a = loRing + r.slot * (SLOT >> 4) + W * 256, b = loO + xs * (XS >> 4);
        wg_fence();
        wgmma<1, 1, HI_OST, !F>(c, a, b);
#pragma unroll
        for (int k = 1; k < 4; k++) wgmma<1, 1, HI_OST, true>(c, a + (k >> 1) * 512 + (k & 1) * 128, b + k * 320);
        wg_commit();
    };
    step(TrueT{});
#pragma unroll 1
    for (int t = 1; t < T; t++) {
        const uint32_t pslot = r.slot, pxs = xs;
        r.adv(1);
        if (++xs == 5) xs = 0;
        step(FalseT{});
        wg_wait<1>();
        mbar_arrive_warp(sb + BAR_REMPTY + pslot * 8);
        mbar_arrive_warp_if(sb + BAR_XEMPTY + pxs * 8, t + 2 < T);
    }
    xs += 1 + W;
    if (xs >= 5) xs -= 5;
    mbar_wait(sb + BAR_XFULL + xs * 8, (phm >> xs) & 1, r.dl);
    wg_wait<0>();
    reg_fence(c);
    const uint32_t tid = tid_now();
    store_out_tile<true>(c, sb + OFF_R + xs * XS, tid & 31, (tid >> 5) & 3);
    fence_async_smem();
    nb_arrive<NB_ODONE, 288>();
}

template <int W>
__device__ __forceinline__ uint32_t qa_item(const Params& P, uint32_t e, uint32_t sb, Ring& r, uint32_t phm, PendO<W>& po, int it) {
    const uint32_t loR = (((sb + OFF_R) & 0x3ffff) >> 4) | LO_LBO1;
    const uint32_t loRing = (((sb + OFF_RING) & 0x3ffff) >> 4) | LO_LBO1;
    uint32_t lane, sta;
    {
        float q0[80], q1[80];
        qproj<W, 0>(q0, q1, sb, r, 0, phm, po, P, it);
        const uint32_t tid = tid_now();
        lane = tid & 31;
        sta = sb + OFF_R + (lane >> 4) * 1024 + (lane & 7) * 128 + (((((tid >> 4) & 6) + ((lane >> 3) & 1)) ^ (lane & 7)) << 4);
        TSD(W, 1);
        if (W == 0) {
            nb_sync<NB_PDONE, 256>();
            store_tile_t(q0, sta);
            store_tile_t(q1, sta + XS);
        } else {
            store_tile_t(q0, sta + 2 * XS);
        }
    }
    fence_async_smem();
    float s[80], oa[80], ob[W == 0 ? 32 : 48], l[10];
    zero(oa);
    zero(ob);
    zero(l);
    reg_fence(oa);
    reg_fence(ob);
    auto pv = [&](const Ring& rv, uint32_t buf) {
        mbar_wait(sb + BAR_RFULL + rv.slot * 8, rv.ph, rv.dl);
        const uint32_t a = loRing + rv.slot * (SLOT >> 4), b = loR + (3 + buf) * (XS >> 4);
        wg_fence();
#pragma unroll
        for (int k = 0; k < 4; k++) {
            wgmma<1, 0, HI_SW128, true>(oa, a + W * 512 + k * 128, b + k * 2);
            wgmma<1, 0, HI_SW128, true>(ob, a + 1024 + k * 128, b + (W == 0 ? (96 * 128) >> 4 : 0) + k * 2);
        }
        wg_commit();
    };
    float mref;
    uint32_t kslot, vslot;
    auto tail = [&](bool rel_other, int i) {
        uint32_t ps[40];
        exp_block<0>(s, ps, sta + (3 + W) * XS, mref);
        if (rel_other) {
            wg_wait<0>();
            mbar_arrive_warp(sb + BAR_REMPTY + vslot * 8);
            if (W == 1) mbar_arrive_warp_if(sb + BAR_XEMPTY + 24, i == 3);
        }
        fence_async_smem();
        nb_arrive<NB_PFULL + W, 256>();
        TSD(W, 6 + 5 * i);
        if (W == 1) {
            if (XLATE >= 2) mbar_arrive_warp_if<2>(sb + BAR_XEMPTY + 8, i == 3);
            if (XLATE >= 1) mbar_arrive_warp_if<2>(sb + BAR_XEMPTY + 16, i == 3);
        }
        if (rel_other || !PV0FIRST) {
            mbar_wait(sb + BAR_RFULL + r.slot * 8, r.ph, r.dl);
            sum_block(ps, l, lane);
        }
        TSD(W, 7 + 5 * i);
        nb_sync<NB_W + W, 128>();
        pv(r, W);
        if (!rel_other && PV0FIRST) sum_block(ps, l, lane);
        TSD(W, 8 + 5 * i);
    };
    if (W == 0) {
        sts_u(sb + OFF_GM + 4, r.slot);
        mbar_wait(sb + BAR_RFULL + r.slot * 8, r.ph, r.dl);
        nb_sync<NB_QK, 160>();
        TSD(W, 2);
        wg_fence();
        qk_steps<0, 8>(s, loRing + r.slot * (SLOT >> 4), loR);
        nb_sync<NB_Q2, 288>();
        qk_steps<8, 12>(s, loRing + r.slot * (SLOT >> 4), loR);
        wg_commit();
        nb_arrive<NB_Q01, 256>();
        TSD(W, 4);
        nb_sync<NB_REF, 160>();
        mref = __uint_as_float(lds_u(sb + OFF_GM));
        wg_wait<0>();
        reg_fence(s);
        mbar_arrive_warp<2>(sb + BAR_REMPTY + r.slot * 8);
        r.adv(2);
        TSD(W, 5);
        tail(false, 0);
    } else {
        nb_arrive<NB_Q2, 288>();
        TSD(W, 2);
        nb_sync<NB_Q01, 256>();
    }
#pragma unroll 1
    for (int i = (W == 0 ? 1 : 0); i < 4; i++) {
        const uint32_t pvslot = r.slot;
        r.adv(1);
        kslot = r.slot;
        mbar_wait(sb + BAR_RFULL + r.slot * 8, r.ph, r.dl);
        wg_fence();
        qk_steps<0, 12>(s, loRing + r.slot * (SLOT >> 4), loR);
        wg_commit();
        wg_wait<1>();
        mbar_arrive_warp_if(sb + BAR_REMPTY + pvslot * 8, W == 0 || i > 0);
        r.adv(1);
        vslot = r.slot;
        TSD(W, 4 + 5 * i);
        nb_sync<NB_PFULL + (W ^ 1), 256>();
        pv(r, W ^ 1);
        if (W == 1) mref = __uint_as_float(lds_u(sb + OFF_GM));
        wg_wait<1>();
        reg_fence(s);
        mbar_arrive_warp<2>(sb + BAR_REMPTY + kslot * 8);
        if (W == 1) {
            mbar_arrive_warp_if<2>(sb + BAR_XEMPTY + 0, i == 3);
            if (XLATE < 2) mbar_arrive_warp_if<2>(sb + BAR_XEMPTY + 8, i == 3);
            if (XLATE < 1) mbar_arrive_warp_if<2>(sb + BAR_XEMPTY + 16, i == 3);
        }
        r.adv(W == 1 && i == 3 ? 1 : 2);
        TSD(W, 5 + 5 * i);
        tail(true, i);
    }
    const uint32_t w = (tid_now() >> 5) & 3;
    const uint32_t lxa = sb + OFF_LX + w * 640 + (((lane & 8) ? 80 : 0) + ((lane >> 1) & 8) + 2 * (lane & 3) + ((lane >> 2) & 1)) * 4;
    const uint32_t nx = get_item_warp(sb, it + 1, r.dl);
    po.gp = ostash(IT_BR(e), IT_B(e), IT_H0(e)) + po.toff();
    po.sig = 1;
    if (W == 0) {
        sum_store<false>(l, lane, lxa);
        nb_arrive<NB_LX, 256>();
        wg_wait<0>();
        mbar_arrive_warp(sb + BAR_REMPTY + r.slot * 8);
        mbar_arrive_warp(sb + BAR_XEMPTY + 24);
        r.adv(1);
        nb_sync<NB_PFULL + 1, 256>();
        pv(r, 1);
    } else {
        nb_sync<NB_LX, 256>();
        sum_store<true>(l, lane, lxa);
        nb_arrive<NB_L, 160>();
    }
    TSD(W, 24);
    wg_wait<0>();
    reg_fence(oa);
    reg_fence(ob);
    mbar_arrive_warp(sb + BAR_REMPTY + r.slot * 8);
    mbar_arrive_warp(sb + BAR_XEMPTY + 32);
    r.adv(1);
    opack(ob, po.v + 40);
    opack(oa, po.v);
    return nx;
}

template <int W>
__device__ __forceinline__ void consumer(const Params& P, uint32_t sb, uint32_t dl) {
    int it = 0;
    if (W == 0) TS(0, 30);
    Ring r{0, 0, dl};
    uint32_t phm = 0;
    uint32_t e = get_item_warp(sb, 0, dl);
#pragma unroll 1
    while (e != 0) {
        if (IT_TYPE(e) == IT_QA) {
            PendO<W> po;
            po.clear();
#pragma unroll 1
            do {
                TS(W, 0);
                if (W == 0) TS_ITEM(e);
                e = qa_item<W>(P, e, sb, r, phm, po, it);
                TS(W, 31);
                it++;
            } while (IT_TYPE(e) == IT_QA);
            po.verdict(P, sb, it - 1);
            po.template step<0>(sb);
            po.template step<1>(sb);
            po.template step<2>(sb);
            po.template step<3>(sb);
            po.template step<4>(sb);
        } else {
            TS(W, 0);
            if (W == 0) TS_ITEM(e);
            if (IT_TYPE(e) == IT_OP) op_item<W == 0>(e, sb, r, phm);
            else on_item<W>(e, sb, r, phm);
            TS(W, 31);
            e = get_item_warp(sb, ++it, dl);
        }
    }
    TS_DUMP(W);
}

__global__ void __cluster_dims__(2, 1, 1) __launch_bounds__(384, 1) fused_kernel(const __grid_constant__ Params P) {
    extern __shared__ __align__(1024) unsigned char smem_raw[];
    const uint32_t sb = (uint32_t)__cvta_generic_to_shared(smem_raw);
    const uint32_t wgid = __shfl_sync(0xffffffffu, threadIdx.x >> 7, 0);
    const uint32_t cta = blockIdx.x;
    const uint32_t dl = deadline();

    uint32_t epoch = 0;
    if (wgid == 0) epoch = *(volatile unsigned int*)&g_epoch[cta] + 1;
    if (threadIdx.x == 0) {
        if (sb & 1023) __trap();
        for (int i = 0; i < NSLOT; i++) {
            mbar_init(sb + BAR_RFULL + i * 8, 1);
            mbar_init(sb + BAR_REMPTY + i * 8, 8);
            mbar_init(sb + BAR_XFULL + i * 8, 1);
            mbar_init(sb + BAR_XEMPTY + i * 8, 8);
            mbar_init(sb + BAR_PRDY + i * 8, 1);
        }
        for (int i = 0; i < MAXI; i++) mbar_init(sb + BAR_ITEM + i * 8, 1);
        asm volatile("fence.mbarrier_init.release.cluster;" ::: "memory");
        fence_async_smem();
    }
    __syncthreads();
    asm volatile("barrier.cluster.arrive.relaxed.aligned;\nbarrier.cluster.wait.aligned;" ::: "memory");

    if (wgid == 0) {
        asm volatile("setmaxnreg.dec.sync.aligned.u32 24;");
        const uint32_t warp = __shfl_sync(0xffffffffu, threadIdx.x >> 5, 0);
        if (warp == 0) {
            if (threadIdx.x == 0) {
                *(volatile unsigned int*)&g_epoch[cta] = epoch;
                const uint64_t pol_first = mkpol<1>(), pol_norm = mkpol<POL_W>();
                if (cta == 0) *(volatile unsigned int*)&g_ticket[(epoch + 1) & 1] = 0;
                const uint32_t rank = cta & 1;
                uint32_t peer;
                asm volatile("mapa.shared::cluster.u32 %0, %1, %2;" : "=r"(peer) : "r"(sb), "r"(rank ^ 1));
                Ring r{0, 1, dl};
                uint32_t pm = 0;
                auto load_w = [&](const CUtensorMap* m, int row, int blk, uint32_t half_bytes) {
                    mbar_wait(sb + BAR_REMPTY + r.slot * 8, r.ph, dl);
                    mbar_expect(sb + BAR_RFULL + r.slot * 8, 2 * half_bytes);
                    asm volatile("mbarrier.arrive.shared::cluster.b64 _, [%0];" ::"r"(peer + BAR_PRDY + r.slot * 8) : "memory");
                    mbar_wait(sb + BAR_PRDY + r.slot * 8, (pm >> r.slot) & 1, dl);
                    pm ^= 1u << r.slot;
                    tma3_mc(sb + OFF_RING + r.slot * SLOT + rank * half_bytes, m, row, blk, sb + BAR_RFULL + r.slot * 8, pol_norm);
                    r.adv(1);
                };
                uint32_t e = 0;
                if (rank == 0) {
                    const uint32_t d = P.delay[cta >> 1];
                    uint32_t t0, t1;
                    asm volatile("mov.u32 %0, %%clock;" : "=r"(t0));
                    do {
                        asm volatile("mov.u32 %0, %%clock;" : "=r"(t1));
                    } while (t1 - t0 < d);
                    e = P.items[cta >> 1][0];
                }
#pragma unroll 1
                for (int it = 0;; it++) {
                    uint32_t nx = 0, tk = 0;
                    if (rank == 0) {
                        asm volatile("st.async.weak.shared::cluster.mbarrier::complete_tx::bytes.b32 [%0], %1, [%2];" ::"r"(
                                         peer + OFF_ITEM + it * 4),
                                     "r"(e ? e + 8 : 0), "r"(peer + BAR_ITEM + it * 8)
                                     : "memory");
                        sts_u(sb + OFF_ITEM + it * 4, e);
                        asm volatile("mbarrier.arrive.shared::cta.b64 _, [%0];" ::"r"(sb + BAR_ITEM + it * 8) : "memory");
                        if (IT_TYPE(e) != IT_ON && it + 2 < MAXI) nx = P.items[cta >> 1][it + 1 < NSTAT ? it + 1 : NSTAT - 1];
                    } else {
                        mbar_expect(sb + BAR_ITEM + it * 8, 4);
                        e = get_item(sb, it, dl);
                    }
                    if (e == 0) break;
                    const uint32_t br = IT_BR(e);
                    if (IT_TYPE(e) == IT_QA) {
                        const uint32_t h = IT_H0(e);
#pragma unroll 1
                        for (int kk = 0; kk < 10; kk++) load_w(&P.wq[br], kk * 64 + rank * 32, h * 3, SLOT / 2);
                        const int row0 = (IT_B(e) * 32 + h) * 512;
#pragma unroll 1
                        for (int n = 0; n < 16; n++) {
                            if (n == 13 && nx == IT_DYN) tk = atomicAdd(&g_ticket[epoch & 1], 1);
                            const bool isv = n == 15 || (n > 0 && !(n & 1));
                            const int j = n == 15 ? 7 : isv ? (n - 2) >> 1 : (n + 1) >> 1;
                            mbar_wait(sb + BAR_REMPTY + r.slot * 8, r.ph, dl);
                            mbar_expect(sb + BAR_RFULL + r.slot * 8, SLOT);
                            tma3(sb + OFF_RING + r.slot * SLOT, isv ? &P.v[br] : &P.k[br], row0 + j * 64, 0,
                                 sb + BAR_RFULL + r.slot * 8, pol_first);
                            r.adv(1);
                        }
                    } else {
                        const bool wide = IT_TYPE(e) == IT_OP;
                        const int step = wide ? 32 : 64, r1 = IT_H1(e) * 192;
#pragma unroll 1
                        for (int row = IT_H0(e) * 192 + rank * (step >> 1); row < r1; row += step)
                            load_w(wide ? &P.wo[br] : &P.won[br], row, IT_HALF(e) * (wide ? 5 : 2), wide ? XS / 2 : 8192);
                        if (nx == IT_DYN) tk = atomicAdd(&g_ticket[epoch & 1], 1);
                    }
                    if (nx == IT_DYN) nx = tk < P.nlist ? P.list[tk] : 0;
                    e = nx;
                }
            }
        } else if (warp == 1) {
            const uint64_t pol_norm = mkpol<POL_X>(), pol_o = mkpol<POL_O>();
            const bool lead = threadIdx.x == 32;
            uint32_t phm = 0x1f;
#pragma unroll 1
            for (int it = 0;; it++) {
                const uint32_t e = get_item_warp(sb, it, dl);
                if (e == 0) break;
                const uint32_t br = IT_BR(e);
                uint32_t xs = 0;
                auto acquire = [&]() {
                    mbar_wait(sb + BAR_XEMPTY + xs * 8, (phm >> xs) & 1, dl);
                    phm ^= 1u << xs;
                    if (lead) mbar_expect(sb + BAR_XFULL + xs * 8, XS);
                };
                if (IT_TYPE(e) == IT_QA) {
#pragma unroll 1
                    for (int kk = 0; kk < 10; kk++) {
                        acquire();
                        if (lead) tma3(sb + OFF_R + xs * XS, &P.x[br], IT_B(e) * 160, kk, sb + BAR_XFULL + xs * 8, pol_norm);
                        if (++xs == 5) xs = 0;
                    }
                } else {
                    const unsigned int* fp = g_flag + (br * 16 + IT_B(e)) * 64 + (threadIdx.x & 31);
                    uint32_t hm = 0, pm = 0;
                    auto poll = [&](uint32_t hneed, uint32_t pneed) {
                        if ((hm & hneed) == hneed && (pm & pneed) == pneed) return;
                        uint32_t n = 0;
                        do {
                            uint32_t a, b;
                            asm volatile("ld.acquire.gpu.global.u32 %0, [%2];\nld.acquire.gpu.global.u32 %1, [%2+128];"
                                         : "=r"(a), "=r"(b) : "l"(fp) : "memory");
                            hm = __ballot_sync(0xffffffffu, a == epoch);
                            pm = __ballot_sync(0xffffffffu, b == epoch);
                            if (++n > 0x1000000) __trap();
                        } while ((hm & hneed) != hneed || (pm & pneed) != pneed);
                        __syncwarp();
                        asm volatile("fence.proxy.async;" ::: "memory");
                    };
#pragma unroll 1
                    for (uint32_t h = IT_H0(e); h < IT_H1(e); h++) {
                        poll(1u << h, 0);
#pragma unroll 1
                        for (int t = 0; t < 3; t++) {
                            acquire();
                            if (lead) bulk_load(sb + OFF_R + xs * XS, ostash(br, IT_B(e), h) + t * XS, XS, sb + BAR_XFULL + xs * 8, pol_o);
                            if (++xs == 5) xs = 0;
                        }
                    }
                    if (IT_TYPE(e) == IT_ON) {
                        poll(0, IT_HALF(e) < 2 ? 1 : IT_HALF(e) == 2 ? 3 : 2);
#pragma unroll 1
                        for (uint32_t tile = 2 * IT_HALF(e); tile < 2 * IT_HALF(e) + 2; tile++) {
                            acquire();
                            if (lead)
                                asm volatile(
                                    "cp.async.bulk.tensor.2d.shared::cluster.global.mbarrier::complete_tx::bytes [%0], [%1, {%3,%4}], [%2];" ::"r"(
                                        sb + OFF_R + xs * XS),
                                    "l"(&P.out), "r"(sb + BAR_XFULL + xs * 8), "r"(br * 640 + tile * 64), "r"(IT_B(e) * 160)
                                    : "memory");
                            if (++xs == 5) xs = 0;
                        }
                    }
                }
            }
        } else if (warp == 2) {
#pragma unroll 1
            for (int it = 0;; it++) {
                const uint32_t e = get_item_warp(sb, it, dl);
                if (e == 0) break;
                nb_sync<NB_ODONE, 288>();
                if (threadIdx.x == 64) {
                    const uint32_t bb = IT_BR(e) * 16 + IT_B(e);
                    if (IT_TYPE(e) != IT_QA) {
                        const bool wide = IT_TYPE(e) == IT_OP;
                        const int cc0 = IT_BR(e) * 640 + IT_HALF(e) * (wide ? 320 : 128);
                        uint32_t xs = wide ? 0 : (3 * (IT_H1(e) - IT_H0(e))) % 5;
#pragma unroll 1
                        for (int m = 0; m < (wide ? 5 : 2); m++) {
                            asm volatile("cp.async.bulk.tensor.2d.global.shared::cta.bulk_group [%0, {%2,%3}], [%1];" ::"l"(&P.out),
                                         "r"(sb + OFF_R + xs * XS), "r"(cc0 + m * 64), "r"((int)IT_B(e) * 160)
                                         : "memory");
                            asm volatile("cp.async.bulk.commit_group;" ::: "memory");
                            if (++xs == 5) xs = 0;
                        }
                        if (wide) {
#define REL(N)                                                          \
    asm volatile("cp.async.bulk.wait_group.read %0;" ::"n"(4 - N) : "memory"); \
    asm volatile("mbarrier.arrive.shared::cta.b64 _, [%0], 8;" ::"r"(sb + BAR_XEMPTY + N * 8) : "memory");
                            REL(0) REL(1) REL(2) REL(3) REL(4)
#undef REL
                        }
                        if (IT_PART(e)) {
                            asm volatile("cp.async.bulk.wait_group 0;" ::: "memory");
                            asm volatile("fence.proxy.async;" ::: "memory");
                        }
                    }
                    if (IT_TYPE(e) == IT_QA || IT_PART(e)) {
                        unsigned int* f = &g_flag[bb * 64 + (IT_TYPE(e) == IT_QA ? IT_H0(e) : 32 + IT_HALF(e))];
                        asm volatile("st.release.gpu.global.u32 [%0], %1;" ::"l"(f), "r"(epoch) : "memory");
                    }
                }
                __syncwarp();
            }
            if (threadIdx.x == 64) asm volatile("cp.async.bulk.wait_group 0;" ::: "memory");
            __syncwarp();
            asm volatile("barrier.cluster.arrive.relaxed.aligned;\nbarrier.cluster.wait.aligned;" ::: "memory");
        } else {
            const uint32_t lane = threadIdx.x & 31, p = lane >> 2;
#pragma unroll 1
            for (int it = 0;; it++) {
                const uint32_t e = get_item_warp(sb, it, dl);
                if (e == 0) break;
                if (IT_TYPE(e) != IT_QA) continue;
                nb_sync<NB_QK, 160>();
                const uint32_t co = (((lane & 3) * 2) ^ p) << 4;
                const uint32_t ka = sb + OFF_RING + lds_u(sb + OFF_GM + 4) * SLOT + p * (9 * 128) + co;
                const uint32_t qa = sb + OFF_R + p * (17 * 128) + co;
                uint32_t acc = 0;
#pragma unroll
                for (int c = 0; c < 6; c++) {
                    if (c == 4) nb_sync<NB_Q2, 288>();
                    const uint4 kv = lds_u4((ka + (c >> 1) * 8192) ^ ((c & 1) << 4));
                    const uint4 qv = lds_u4((qa + (c >> 1) * XS) ^ ((c & 1) << 4));
                    acc = fma_bf2(kv.x, qv.x, fma_bf2(kv.y, qv.y, fma_bf2(kv.z, qv.z, fma_bf2(kv.w, qv.w, acc))));
                }
                float d = __uint_as_float(acc << 16) + __uint_as_float(acc & 0xffff0000u);
                d += __shfl_xor_sync(0xffffffffu, d, 1);
                d += __shfl_xor_sync(0xffffffffu, d, 2);
                int key = __float_as_int(d);
                key ^= (key >> 31) & 0x7fffffff;
                key = __reduce_max_sync(0xffffffffu, key);
                key ^= (key >> 31) & 0x7fffffff;
                sts_f(sb + OFF_GM, __int_as_float(key) * SM_C);
                nb_arrive<NB_REF, 160>();
                nb_sync<NB_L, 160>();
                bool bad = false;
#pragma unroll
                for (int c = 0; c < 5; c++) {
                    const uint32_t la = sb + OFF_LX + (c * 32 + lane) * 4;
                    const float v = (__uint_as_float(lds_u(la)) + __uint_as_float(lds_u(la + 640))) +
                                    (__uint_as_float(lds_u(la + 1280)) + __uint_as_float(lds_u(la + 1920)));
                    const float inv = __fdividef(1.f, v);
                    const uint32_t hi = pack_bf16(inv, 0.f), lo = pack_bf16(inv - __uint_as_float(hi << 16), 0.f);
                    const uint32_t ia = sb + OFF_LINV + c * 128 + ((lane >> 1) & 3) * 32 + (lane >> 3) * 8 + (lane & 1) * 2;
                    asm volatile("st.shared.u16 [%0], %1;\nst.shared.u16 [%0+4], %2;" ::"r"(ia), "h"((unsigned short)hi), "h"((unsigned short)lo) : "memory");
                    bad |= !(v >= 5.421010862e-20f && v <= 1.8446744e19f);
                }
                sts_u(sb + OFF_FB, __any_sync(0xffffffffu, bad));
                nb_arrive<NB_VOTE, 160>();
                nb_arrive<NB_VOTE + 1, 160>();
            }
        }
    } else if (wgid == 1) {
        asm volatile("setmaxnreg.inc.sync.aligned.u32 240;");
        consumer<0>(P, sb, dl);
    } else {
        asm volatile("setmaxnreg.inc.sync.aligned.u32 240;");
        consumer<1>(P, sb, dl);
    }
}

typedef CUresult (*EncFn)(CUtensorMap*, CUtensorMapDataType, cuuint32_t, void*, const cuuint64_t*, const cuuint64_t*,
                          const cuuint32_t*, const cuuint32_t*, CUtensorMapInterleave, CUtensorMapSwizzle,
                          CUtensorMapL2promotion, CUtensorMapFloatOOBfill);

void make_map3(EncFn enc, CUtensorMap* m, void* p, uint64_t rows, uint64_t rowbytes, uint64_t nblk, uint32_t boxrows,
               uint32_t boxblk) {
    cuuint64_t dims[3] = {64, rows, nblk};
    cuuint64_t str[2] = {rowbytes, 128};
    cuuint32_t box[3] = {64, boxrows, boxblk};
    cuuint32_t es[3] = {1, 1, 1};
    enc(m, CU_TENSOR_MAP_DATA_TYPE_BFLOAT16, 3, p, dims, str, box, es, CU_TENSOR_MAP_INTERLEAVE_NONE,
        CU_TENSOR_MAP_SWIZZLE_128B, CU_TENSOR_MAP_L2_PROMOTION_NONE, CU_TENSOR_MAP_FLOAT_OOB_FILL_NONE);
}

constexpr int tune(const char*, int def) { return def; }

void build_schedule(Params& P) {
    const int mode = tune("MODE", 4), dmax = tune("DMAX", 26400), n0 = tune("N0", 0);
    const int hmin = tune("HMIN", 19), hmax = tune("HMAX", 25), off = tune("OFF", 0), slope = tune("SLOPE", 1744);
    const int ng = tune("NG", 0), d0 = tune("D0", 0), nkeep = tune("NKEEP", 0), odmax = tune("ODMAX", 0);
    const int ong = tune("ONG", 0), od0 = tune("OD0", 0), jit = tune("JIT", 0);
    const int npos = tune("NPOS", 0), nearly = tune("NEARLY", 0);
    int u = 0;
    auto unit = [&]() {
        const uint32_t e = mk_item(IT_QA, u >> 8, (u & 7) * 2, (u >> 3) & 31, 0, 0);
        u++;
        return e;
    };
    int qa[NCL], nq = 0, op[NCL], no = 0;
    for (int c = 0; c < NCL; c++) {
        P.delay[c] = 0;
        for (int i = 0; i < NSTAT; i++) P.items[c][i] = 0;
        if (mode >= 3 && c < 64 && (c & 3) == 3) op[no++] = c;
        else if (mode != 2 || (c & 3) == 0) qa[nq++] = c;
    }
    for (int t = 0; t < no; t++) {
        P.items[op[t]][1] = mk_item(IT_OP, 0, t & ~1, 0, 32, t & 1);
        P.items[op[t]][2] = P.items[op[t]][3] = IT_DYN;
        P.delay[op[t]] = ong ? od0 + (t * ong / 16) * (odmax / ong) : od0 + t * odmax / 16;
    }
    for (int k = 0; k < nq; k++) {
        const int c = qa[(k * 19) % nq];
        P.items[c][1] = P.items[c][2] = P.items[c][3] = IT_DYN;
        P.delay[c] = k < n0 ? 0 : (int)((long long)dmax * (k + 1 - n0) / (nq - n0));
        if (ng) P.delay[c] = d0 + (k * ng / nq) * (dmax / ng) + (k * ng % nq) * jit / nq;
    }
    for (int k = 0; k < no + nq; k++) {
        int best = -1;
        for (int c = 0; c < NCL; c++)
            if (P.items[c][1] && !P.items[c][0] && (best < 0 || P.delay[c] < P.delay[best])) best = c;
        P.items[best][0] = unit();
    }
    int H[8], pos[8];
    for (int b = 0; b < 8; b++) {
        char nh[3] = {'H', (char)('0' + b), 0}, np[3] = {'P', (char)('0' + b), 0};
        H[b] = tune(nh, hmin + ((hmax - hmin) * b + 3) / 7);
        pos[b] = tune(np, (1092 + off - H[b] * slope / 100) / 2);
        if (b < nkeep && no) {
            pos[b] = -1;
            P.items[op[14 - 2 * b]][2] = mk_item(IT_OP, 1, 2 * b, 0, H[b], 0, 1);
            P.items[op[15 - 2 * b]][2] = mk_item(IT_OP, 1, 2 * b, 0, H[b], 1, 1);
        }
    }
    int n = 0, kn = 0;
    const int uend = mode == 2 ? 8 * nq : 512;
    while (u < uend) {
        for (int b = 0; b < 8 && no; b++)
            if (pos[b] == u) {
                P.list[n++] = mk_item(IT_OP, 1, 2 * b, 0, H[b], 0, 1);
                P.list[n++] = mk_item(IT_OP, 1, 2 * b, 0, H[b], 1, 1);
            }
        while (no && u >= uend - npos && kn * npos < (u + 1 - (uend - npos)) * nearly) {
            P.list[n++] = mk_item(IT_ON, 1, kn / 5 * 2, H[kn / 5], 32, kn % 5);
            kn++;
        }
        P.list[n++] = unit();
    }
    for (; no && kn < 40; kn++) P.list[n++] = mk_item(IT_ON, 1, kn / 5 * 2, H[kn / 5], 32, kn % 5);
    P.nlist = n;
}

}

extern "C" void kernel_launch(void* const* d_in, const int* in_sizes, int n_in, void* d_out, int out_size) {
    static Params P;
    static bool init = false;
    if (!init) {
        EncFn enc = nullptr;
        cudaDriverEntryPointQueryResult qr;
        cudaGetDriverEntryPoint("cuTensorMapEncodeTiled", (void**)&enc, cudaEnableDefault, &qr);
        for (int i = 0; i < 2; i++) {
            P.px[i] = (const __nv_bfloat16*)d_in[5 * i + 0];
            P.pk[i] = (const __nv_bfloat16*)d_in[5 * i + 1];
            P.pv[i] = (const __nv_bfloat16*)d_in[5 * i + 2];
            P.pwq[i] = (const __nv_bfloat16*)d_in[5 * i + 3];
            make_map3(enc, &P.x[i], d_in[5 * i + 0], 2560, 1280, 10, 160, 1);
            make_map3(enc, &P.k[i], d_in[5 * i + 1], 16 * 32 * 512, 384, 3, 64, 3);
            make_map3(enc, &P.v[i], d_in[5 * i + 2], 16 * 32 * 512, 384, 3, 64, 3);
            make_map3(enc, &P.wq[i], d_in[5 * i + 3], 640, 12288, 96, 32, 3);
            make_map3(enc, &P.wo[i], d_in[5 * i + 4], 6144, 1280, 10, 16, 5);
            make_map3(enc, &P.won[i], d_in[5 * i + 4], 6144, 1280, 10, 32, 2);
        }
        cuuint64_t dims[2] = {1280, 2560};
        cuuint64_t str[1] = {2560};
        cuuint32_t box[2] = {64, 160};
        cuuint32_t es[2] = {1, 1};
        enc(&P.out, CU_TENSOR_MAP_DATA_TYPE_BFLOAT16, 2, d_out, dims, str, box, es, CU_TENSOR_MAP_INTERLEAVE_NONE,
            CU_TENSOR_MAP_SWIZZLE_128B, CU_TENSOR_MAP_L2_PROMOTION_NONE, CU_TENSOR_MAP_FLOAT_OOB_FILL_NONE);
        build_schedule(P);
        cudaFuncSetAttribute(fused_kernel, cudaFuncAttributeMaxDynamicSharedMemorySize, SMEM_LAUNCH);
        init = true;
    }
    fused_kernel<<<NCTA, 384, SMEM_LAUNCH>>>(P);
}
```

```cpp
#include <cuda_runtime.h>
#include <cuda.h>
#include <cuda_bf16.h>
#include <stdint.h>

namespace {

constexpr int NCTA = 132;
constexpr int NCL = NCTA / 2;
constexpr int MAXI = 16;
constexpr int NSTAT = 4;
constexpr uint32_t IT_DYN = 0xffffffffu;
constexpr int SLOT = 24576;
constexpr int NSLOT = 5;
constexpr int XS = 20480;
constexpr int OFF_R = 0;
constexpr int OFF_RING = 5 * XS;
constexpr int OFF_MISC = OFF_RING + NSLOT * SLOT;
constexpr int OFF_LX = OFF_MISC;
constexpr int OFF_LINV = OFF_LX + 2560;
constexpr int OFF_FB = OFF_LINV + 640;
constexpr int OFF_GM = OFF_FB + 16;
constexpr int OFF_BAR = OFF_GM + 16;
constexpr int BAR_RFULL = OFF_BAR;
constexpr int BAR_REMPTY = BAR_RFULL + 40;
constexpr int BAR_XFULL = BAR_REMPTY + 40;
constexpr int BAR_XEMPTY = BAR_XFULL + 40;
constexpr int BAR_PRDY = BAR_XEMPTY + 40;
constexpr int BAR_ITEM = BAR_PRDY + 40;
constexpr int OFF_ITEM = BAR_ITEM + MAXI * 8;
constexpr int SMEM_BYTES = OFF_ITEM + MAXI * 4;
static_assert(SMEM_BYTES <= 232448, "smem");

constexpr int NB_W = 1  , NB_PFULL = 3  , NB_VOTE = 5  , NB_Q2 = 7, NB_SDONE = 8, NB_PDONE = 9,
              NB_L = 10, NB_REF = 11, NB_ODONE = 12, NB_OPEND = 13, NB_LX = 14, NB_Q01 = 15, NB_QK = 0  ;

constexpr uint32_t IT_QA = 1, IT_OP = 2, IT_ON = 3;
__host__ __device__ constexpr uint32_t mk_item(uint32_t type, uint32_t br, uint32_t b, uint32_t h0, uint32_t h1, uint32_t half,
                                               uint32_t part = 0) {
    return type | (br << 2) | (b << 3) | (h0 << 7) | (h1 << 13) | (half << 19) | (part << 22);
}
#define IT_TYPE(e) ((e) & 3u)
#define IT_BR(e) (((e) >> 2) & 1u)
#define IT_B(e) (((e) >> 3) & 15u)
#define IT_H0(e) (((e) >> 7) & 63u)
#define IT_H1(e) (((e) >> 13) & 63u)
#define IT_HALF(e) (((e) >> 19) & 7u)
#define IT_PART(e) (((e) >> 22) & 1u)
#define IT_SLOT(e) IT_H1(e)
#define IT_DEP(e) (((e) >> 23) & 127u)

struct Params {
    CUtensorMap x[2], wq[2], k[2], v[2], wo[2], won[2], out;
    const __nv_bfloat16 *px[2], *pwq[2], *pk[2], *pv[2];
    uint32_t items[NCL][NSTAT];
    uint32_t delay[NCL];
    uint32_t nlist;
    uint8_t slot[64];
    uint32_t list[512];
};

constexpr int OUNIT = 61440;
__device__ __align__(1024) unsigned char g_ostash[(size_t)1024 * OUNIT];
__device__ unsigned int g_flag[32 * 64];
__device__ __forceinline__ unsigned char* ostash(uint32_t slot, uint32_t b) { return g_ostash + (slot * 16 + b) * OUNIT; }
__device__ unsigned int g_epoch[NCTA];
__device__ unsigned int g_ticket[2];

constexpr int SMEM_LAUNCH = SMEM_BYTES;
#define TS(role, idx)
#define TS_ITEM(e)
#define TS_DUMP(role)
#define TSD(role, idx)

#define POL_W 2
#define POL_X 2
#define POL_O 2
template <int M>
__device__ __forceinline__ uint64_t mkpol() {
    uint64_t p;
    if (M == 0) asm volatile("createpolicy.fractional.L2::evict_normal.b64 %0, 1.0;" : "=l"(p));
    if (M == 1) asm volatile("createpolicy.fractional.L2::evict_first.b64 %0, 1.0;" : "=l"(p));
    if (M == 2) asm volatile("createpolicy.fractional.L2::evict_unchanged.b64 %0, 1.0;" : "=l"(p));
    if (M == 3) asm volatile("createpolicy.fractional.L2::evict_normal.L2::evict_unchanged.b64 %0, 0.25;" : "=l"(p));
    return p;
}
#define STSM_W 1
#define XLATE 2
#define PV0FIRST 1
#define QST0 1
#define QST1 2
#define QHOLD 7
constexpr float SM_C = 0.07216878364870322f * 1.4426950408889634f;

__device__ __forceinline__ uint32_t tid_now() {
    uint32_t t;
    asm volatile("mov.u32 %0, %%tid.x;" : "=r"(t));
    return t;
}
__device__ __forceinline__ void mbar_init(uint32_t a, uint32_t c) {
    asm volatile("mbarrier.init.shared::cta.b64 [%0], %1;" ::"r"(a), "r"(c) : "memory");
}
__device__ __forceinline__ void mbar_expect(uint32_t a, uint32_t b) {
    asm volatile("mbarrier.arrive.expect_tx.shared::cta.b64 _, [%0], %1;" ::"r"(a), "r"(b) : "memory");
}
template <int CNT = 1>
__device__ __forceinline__ void mbar_arrive_warp(uint32_t a) {
    if (CNT == 1)
        asm volatile("{\n.reg .pred p;\nelect.sync _|p, 0xffffffff;\n@p mbarrier.arrive.shared::cta.b64 _, [%0];\n}" ::"r"(a) : "memory");
    else
        asm volatile(
            "{\n.reg .pred p;\nelect.sync _|p, 0xffffffff;\n@p mbarrier.arrive.shared::cta.b64 _, [%0];\n"
            "@p mbarrier.arrive.shared::cta.b64 _, [%0];\n}" ::"r"(a)
            : "memory");
}
template <int CNT = 1>
__device__ __forceinline__ void mbar_arrive_warp_if(uint32_t a, bool cond) {
    if (CNT == 1)
        asm volatile(
            "{\n.reg .pred p, c;\nelect.sync _|p, 0xffffffff;\nsetp.ne.and.u32 c, %1, 0, p;\n"
            "@c mbarrier.arrive.shared::cta.b64 _, [%0];\n}" ::"r"(a), "r"((uint32_t)cond)
            : "memory");
    else
        asm volatile(
            "{\n.reg .pred p, c;\nelect.sync _|p, 0xffffffff;\nsetp.ne.and.u32 c, %1, 0, p;\n"
            "@c mbarrier.arrive.shared::cta.b64 _, [%0];\n@c mbarrier.arrive.shared::cta.b64 _, [%0];\n}" ::"r"(a), "r"((uint32_t)cond)
            : "memory");
}
__device__ __forceinline__ uint32_t deadline() {
    uint32_t c;
    asm volatile("mov.u32 %0, %%clock_hi;" : "=r"(c));
    return c + 4;
}
__device__ __forceinline__ void mbar_wait(uint32_t a, uint32_t ph, uint32_t dl) {
    asm volatile(
        "{\n.reg .pred p;\n.reg .u32 m;\n"
        "LOOP:\n"
        "mbarrier.try_wait.parity.shared::cta.b64 p, [%0], %1;\n"
        "@p bra DONE;\n"
        "mov.u32 m, %%clock_hi;\n"
        "setp.ne.u32 p, m, %2;\n"
        "@p bra LOOP;\n"
        "trap;\n"
        "DONE:\n}" ::"r"(a), "r"(ph), "r"(dl)
        : "memory");
}
template <int ID, int CNT>
__device__ __forceinline__ void nb_sync() { asm volatile("bar.sync %0, %1;" ::"n"(ID), "n"(CNT) : "memory"); }
template <int ID, int CNT>
__device__ __forceinline__ void nb_arrive() { asm volatile("bar.arrive %0, %1;" ::"n"(ID), "n"(CNT) : "memory"); }
__device__ __forceinline__ void fence_async_smem() { asm volatile("fence.proxy.async.shared::cta;" ::: "memory"); }

__device__ __forceinline__ void tma3(uint32_t dst, const CUtensorMap* m, int c1, int c2, uint32_t bar, uint64_t pol) {
    asm volatile(
        "cp.async.bulk.tensor.3d.shared::cluster.global.mbarrier::complete_tx::bytes.L2::cache_hint [%0], [%1, {%3,%4,%5}], [%2], %6;" ::"r"(dst),
        "l"(m), "r"(bar), "r"(0), "r"(c1), "r"(c2), "l"(pol)
        : "memory");
}
__device__ __forceinline__ void tma3_mc(uint32_t dst, const CUtensorMap* m, int c1, int c2, uint32_t bar, uint64_t pol) {
    asm volatile(
        "cp.async.bulk.tensor.3d.shared::cluster.global.mbarrier::complete_tx::bytes.multicast::cluster.L2::cache_hint"
        " [%0], [%1, {%3,%4,%5}], [%2], %6, %7;" ::"r"(dst),
        "l"(m), "r"(bar), "r"(0), "r"(c1), "r"(c2), "h"((unsigned short)3), "l"(pol)
        : "memory");
}
__device__ __forceinline__ void bulk_load(uint32_t dst, const void* src, uint32_t bytes, uint32_t bar, uint64_t pol) {
    asm volatile("cp.async.bulk.shared::cluster.global.mbarrier::complete_tx::bytes.L2::cache_hint [%0], [%1], %2, [%3], %4;" ::"r"(dst),
                 "l"(src), "r"(bytes), "r"(bar), "l"(pol)
                 : "memory");
}
__device__ __forceinline__ void wg_fence() { asm volatile("wgmma.fence.sync.aligned;" ::: "memory"); }
__device__ __forceinline__ void wg_commit() { asm volatile("wgmma.commit_group.sync.aligned;" ::: "memory"); }
template <int N>
__device__ __forceinline__ void wg_wait() { asm volatile("wgmma.wait_group.sync.aligned %0;" ::"n"(N) : "memory"); }

#define RW80(c, d) c(d[0]), c(d[1]), c(d[2]), c(d[3]), c(d[4]), c(d[5]), c(d[6]), c(d[7]), c(d[8]), c(d[9]), c(d[10]), c(d[11]), c(d[12]), c(d[13]), c(d[14]), c(d[15]), c(d[16]), c(d[17]), c(d[18]), c(d[19]), c(d[20]), c(d[21]), c(d[22]), c(d[23]), c(d[24]), c(d[25]), c(d[26]), c(d[27]), c(d[28]), c(d[29]), c(d[30]), c(d[31]), c(d[32]), c(d[33]), c(d[34]), c(d[35]), c(d[36]), c(d[37]), c(d[38]), c(d[39]), c(d[40]), c(d[41]), c(d[42]), c(d[43]), c(d[44]), c(d[45]), c(d[46]), c(d[47]), c(d[48]), c(d[49]), c(d[50]), c(d[51]), c(d[52]), c(d[53]), c(d[54]), c(d[55]), c(d[56]), c(d[57]), c(d[58]), c(d[59]), c(d[60]), c(d[61]), c(d[62]), c(d[63]), c(d[64]), c(d[65]), c(d[66]), c(d[67]), c(d[68]), c(d[69]), c(d[70]), c(d[71]), c(d[72]), c(d[73]), c(d[74]), c(d[75]), c(d[76]), c(d[77]), c(d[78]), c(d[79])
#define RW48(c, d) c(d[0]), c(d[1]), c(d[2]), c(d[3]), c(d[4]), c(d[5]), c(d[6]), c(d[7]), c(d[8]), c(d[9]), c(d[10]), c(d[11]), c(d[12]), c(d[13]), c(d[14]), c(d[15]), c(d[16]), c(d[17]), c(d[18]), c(d[19]), c(d[20]), c(d[21]), c(d[22]), c(d[23]), c(d[24]), c(d[25]), c(d[26]), c(d[27]), c(d[28]), c(d[29]), c(d[30]), c(d[31]), c(d[32]), c(d[33]), c(d[34]), c(d[35]), c(d[36]), c(d[37]), c(d[38]), c(d[39]), c(d[40]), c(d[41]), c(d[42]), c(d[43]), c(d[44]), c(d[45]), c(d[46]), c(d[47])
#define RW32(c, d) c(d[0]), c(d[1]), c(d[2]), c(d[3]), c(d[4]), c(d[5]), c(d[6]), c(d[7]), c(d[8]), c(d[9]), c(d[10]), c(d[11]), c(d[12]), c(d[13]), c(d[14]), c(d[15]), c(d[16]), c(d[17]), c(d[18]), c(d[19]), c(d[20]), c(d[21]), c(d[22]), c(d[23]), c(d[24]), c(d[25]), c(d[26]), c(d[27]), c(d[28]), c(d[29]), c(d[30]), c(d[31])

__device__ __forceinline__ void reg_fence(float (&d)[80]) { asm volatile("" : RW80("+f", d)::"memory"); }
__device__ __forceinline__ void reg_fence(float (&d)[48]) { asm volatile("" : RW48("+f", d)::"memory"); }
__device__ __forceinline__ void reg_fence(float (&d)[32]) { asm volatile("" : RW32("+f", d)::"memory"); }

template <int NR>
__device__ __forceinline__ void zero(float (&d)[NR]) {
#pragma unroll
    for (int i = 0; i < NR; i++) d[i] = 0.f;
}

constexpr uint32_t HI_SW128 = (1024u >> 4) | (1u << 30);
constexpr uint32_t HI_OST = (2560u >> 4) | (2u << 30);
constexpr uint32_t LO_LBO1 = (1u << 16);
constexpr uint32_t LO_OST = ((512u >> 4) << 16);

template <int TA, int TB, uint32_t HIB, int ACC>
__device__ __forceinline__ void wgmma(float (&d)[80], uint32_t loA, uint32_t loB) {
#define WG_ASM(SD)                                                          \
    "{\n.reg .b64 da, db;\nmov.b64 da, {%80, %82};\nmov.b64 db, {%81, %83};\n" \
    "wgmma.mma_async.sync.aligned.m64n160k16.f32.bf16.bf16 "               \
    "{%0,%1,%2,%3,%4,%5,%6,%7,%8,%9,%10,%11,%12,%13,%14,%15,%16,%17,%18,%19,%20,%21,%22,%23,%24,%25,%26,%27,%28,%29,%30,%31,%32,%33,%34,%35,%36,%37,%38,%39,%40,%41,%42,%43,%44,%45,%46,%47,%48,%49,%50,%51,%52,%53,%54,%55,%56,%57,%58,%59,%60,%61,%62,%63,%64,%65,%66,%67,%68,%69,%70,%71,%72,%73,%74,%75,%76,%77,%78,%79}, da, db, " SD ", 1, 1, %84, %85;\n}"
    if constexpr (ACC == 2)
        asm volatile(WG_ASM("0") : RW80("+f", d) : "r"(loA), "r"(loB), "n"(HI_SW128), "n"(HIB), "n"(TA), "n"(TB));
    else if constexpr (ACC == 1)
        asm volatile(WG_ASM("1") : RW80("+f", d) : "r"(loA), "r"(loB), "n"(HI_SW128), "n"(HIB), "n"(TA), "n"(TB));
    else
        asm volatile(WG_ASM("0") : RW80("=f", d) : "r"(loA), "r"(loB), "n"(HI_SW128), "n"(HIB), "n"(TA), "n"(TB));
#undef WG_ASM
}
template <int TA, int TB, uint32_t HIB, int ACC>
__device__ __forceinline__ void wgmma(float (&d)[48], uint32_t loA, uint32_t loB) {
#define WG_ASM(SD)                                                          \
    "{\n.reg .b64 da, db;\nmov.b64 da, {%48, %50};\nmov.b64 db, {%49, %51};\n" \
    "wgmma.mma_async.sync.aligned.m64n96k16.f32.bf16.bf16 "               \
    "{%0,%1,%2,%3,%4,%5,%6,%7,%8,%9,%10,%11,%12,%13,%14,%15,%16,%17,%18,%19,%20,%21,%22,%23,%24,%25,%26,%27,%28,%29,%30,%31,%32,%33,%34,%35,%36,%37,%38,%39,%40,%41,%42,%43,%44,%45,%46,%47}, da, db, " SD ", 1, 1, %52, %53;\n}"
    if constexpr (ACC == 1)
        asm volatile(WG_ASM("1") : RW48("+f", d) : "r"(loA), "r"(loB), "n"(HI_SW128), "n"(HIB), "n"(TA), "n"(TB));
    else
        asm volatile(WG_ASM("0") : RW48("=f", d) : "r"(loA), "r"(loB), "n"(HI_SW128), "n"(HIB), "n"(TA), "n"(TB));
#undef WG_ASM
}
template <int TA, int TB, uint32_t HIB, int ACC>
__device__ __forceinline__ void wgmma(float (&d)[32], uint32_t loA, uint32_t loB) {
#define WG_ASM(SD)                                                          \
    "{\n.reg .b64 da, db;\nmov.b64 da, {%32, %34};\nmov.b64 db, {%33, %35};\n" \
    "wgmma.mma_async.sync.aligned.m64n64k16.f32.bf16.bf16 "               \
    "{%0,%1,%2,%3,%4,%5,%6,%7,%8,%9,%10,%11,%12,%13,%14,%15,%16,%17,%18,%19,%20,%21,%22,%23,%24,%25,%26,%27,%28,%29,%30,%31}, da, db, " SD ", 1, 1, %36, %37;\n}"
    if constexpr (ACC == 1)
        asm volatile(WG_ASM("1") : RW32("+f", d) : "r"(loA), "r"(loB), "n"(HI_SW128), "n"(HIB), "n"(TA), "n"(TB));
    else
        asm volatile(WG_ASM("0") : RW32("=f", d) : "r"(loA), "r"(loB), "n"(HI_SW128), "n"(HIB), "n"(TA), "n"(TB));
#undef WG_ASM
}

__device__ __forceinline__ uint32_t pack_bf16(float lo, float hi) {
    uint32_t r;
    asm("cvt.rn.bf16x2.f32 %0, %1, %2;" : "=r"(r) : "f"(hi), "f"(lo));
    return r;
}
__device__ __forceinline__ float ex2(float x) {
    float r;
    asm("ex2.approx.ftz.f32 %0, %1;" : "=f"(r) : "f"(x));
    return r;
}
__device__ __forceinline__ void stsm4t(uint32_t a, uint32_t r0, uint32_t r1, uint32_t r2, uint32_t r3) {
    asm volatile("stmatrix.sync.aligned.m8n8.x4.trans.shared.b16 [%0], {%1,%2,%3,%4};" ::"r"(a), "r"(r0), "r"(r1), "r"(r2), "r"(r3)
                 : "memory");
}
__device__ __forceinline__ uint32_t lds_u(uint32_t a) {
    uint32_t v;
    asm volatile("ld.shared.u32 %0, [%1];" : "=r"(v) : "r"(a) : "memory");
    return v;
}
__device__ __forceinline__ uint4 lds_u4(uint32_t a) {
    uint4 v;
    asm volatile("ld.shared.v4.u32 {%0,%1,%2,%3}, [%4];" : "=r"(v.x), "=r"(v.y), "=r"(v.z), "=r"(v.w) : "r"(a) : "memory");
    return v;
}
__device__ __forceinline__ float2 lds_f2(uint32_t a) {
    float2 v;
    asm volatile("ld.shared.v2.f32 {%0,%1}, [%2];" : "=f"(v.x), "=f"(v.y) : "r"(a) : "memory");
    return v;
}
__device__ __forceinline__ void sts_f(uint32_t a, float v) { asm volatile("st.shared.f32 [%0], %1;" ::"r"(a), "f"(v) : "memory"); }
__device__ __forceinline__ void sts_u(uint32_t a, uint32_t v) { asm volatile("st.shared.u32 [%0], %1;" ::"r"(a), "r"(v) : "memory"); }
__device__ __forceinline__ void sts_f2(uint32_t a, float x, float y) {
    asm volatile("st.shared.v2.f32 [%0], {%1,%2};" ::"r"(a), "f"(x), "f"(y) : "memory");
}

__device__ __forceinline__ void store_tile_t(const float (&d)[80], uint32_t addr) {
#pragma unroll
    for (int j = 0; j < 10; j++)
        stsm4t(addr + j * 2048, pack_bf16(d[8 * j], d[8 * j + 1]), pack_bf16(d[8 * j + 2], d[8 * j + 3]),
               pack_bf16(d[8 * j + 4], d[8 * j + 5]), pack_bf16(d[8 * j + 6], d[8 * j + 7]));
}
template <bool ADD, int NR>
__device__ __forceinline__ void store_out_tile(const float (&d)[NR], uint32_t base, uint32_t lane, uint32_t w) {
    const uint32_t mi = lane >> 3, i = lane & 7;
    const uint32_t chunk = 2 * w + (mi & 1);
    const uint32_t q0 = 8 * (i >> 1) + 2 * (mi >> 1) + (i & 1);
    const uint32_t a0 = base + q0 * 128 + ((chunk ^ (q0 & 7)) << 4);
    const uint32_t a1 = base + (q0 + 4) * 128 + ((chunk ^ ((q0 + 4) & 7)) << 4);
    uint32_t p[NR / 2];
    if (ADD) {
#pragma unroll
        for (int j = 0; j < NR / 8; j++)
            asm volatile("ldmatrix.sync.aligned.m8n8.x4.trans.shared.b16 {%0,%1,%2,%3}, [%4];"
                         : "=r"(p[4 * j]), "=r"(p[4 * j + 1]), "=r"(p[4 * j + 2]), "=r"(p[4 * j + 3])
                         : "r"(((j & 1) ? a1 : a0) + (j >> 1) * 4096)
                         : "memory");
    }
#pragma unroll
    for (int k = 0; k < NR / 2; k++)
        p[k] = ADD ? pack_bf16(d[2 * k] + __uint_as_float(p[k] << 16), d[2 * k + 1] + __uint_as_float(p[k] & 0xffff0000u))
                   : pack_bf16(d[2 * k], d[2 * k + 1]);
#pragma unroll
    for (int j = 0; j < NR / 8; j++)
        stsm4t(((j & 1) ? a1 : a0) + (j >> 1) * 4096, p[4 * j], p[4 * j + 1], p[4 * j + 2], p[4 * j + 3]);
}

struct TrueT { static constexpr bool value = true; };
struct FalseT { static constexpr bool value = false; };

template <int V>
struct IntT { static constexpr int value = V; };

__device__ __forceinline__ uint32_t get_item(uint32_t sb, int it, uint32_t dl) {
    mbar_wait(sb + BAR_ITEM + it * 8, 0, dl);
    return lds_u(sb + OFF_ITEM + it * 4);
}
__device__ __forceinline__ uint32_t get_item_warp(uint32_t sb, int it, uint32_t dl) {
    return __shfl_sync(0xffffffffu, get_item(sb, it, dl), 0);
}

struct Ring {
    uint32_t slot, ph, dl;
    __device__ __forceinline__ void adv(uint32_t k) {
        slot += k;
        if (slot >= NSLOT) { slot -= NSLOT; ph ^= 1; }
    }
};

template <int K>
__device__ __forceinline__ void qk_step(float (&s)[80], uint32_t loK, uint32_t loQ) {
    wgmma<0, 0, HI_SW128, K != 0>(s, loK + (K >> 2) * (8192 >> 4) + (K & 3) * 2, loQ + (K >> 2) * (XS >> 4) + (K & 3) * 2);
}
template <int K0, int K1>
__device__ __forceinline__ void qk_steps(float (&s)[80], uint32_t loK, uint32_t loQ) {
    if constexpr (K0 < K1) {
        qk_step<K0>(s, loK, loQ);
        qk_steps<K0 + 1, K1>(s, loK, loQ);
    }
}
__device__ __forceinline__ uint32_t add_bf2(uint32_t a, uint32_t b) {
    uint32_t r;
    asm("add.rn.bf16x2 %0, %1, %2;" : "=r"(r) : "r"(a), "r"(b));
    return r;
}
__device__ __forceinline__ uint32_t fma_bf2(uint32_t a, uint32_t b, uint32_t c) {
    uint32_t r;
    asm("fma.rn.bf16x2 %0, %1, %2, %3;" : "=r"(r) : "r"(a), "r"(b), "r"(c));
    return r;
}
template <int J>
__device__ __forceinline__ void exp_block(const float (&s)[80], uint32_t (&k)[40], uint32_t pa, float mref) {
    if constexpr (J < 10) {
#pragma unroll
        for (int i = 4 * J; i < 4 * J + 4; i++)
            k[i] = pack_bf16(ex2(fmaf(s[2 * i], SM_C, -mref)), ex2(fmaf(s[2 * i + 1], SM_C, -mref)));
#pragma unroll
        for (int i = 0; i < 4; i++)
            asm volatile("stmatrix.sync.aligned.m8n8.x1.trans.shared.b16 [%0], {%1};" ::"r"(((i & 1) ? pa ^ 16 : pa) + J * 2048 + (i >> 1) * 1024),
                         "r"(k[4 * J + i])
                         : "memory");
        exp_block<J + 1>(s, k, pa, mref);
    }
}
__device__ __forceinline__ void sum_block(const uint32_t (&k)[40], float (&l)[10], uint32_t lane) {
    const bool b4 = lane & 16, b3 = lane & 8;
    uint32_t ps[20], t[10];
#pragma unroll
    for (int j = 0; j < 20; j++) ps[j] = add_bf2(k[2 * j], k[2 * j + 1]);
#pragma unroll
    for (int j = 0; j < 10; j++)
        t[j] = add_bf2(b4 ? ps[2 * j + 1] : ps[2 * j], __shfl_xor_sync(0xffffffffu, b4 ? ps[2 * j] : ps[2 * j + 1], 16));
#pragma unroll
    for (int i = 0; i < 5; i++) {
        const uint32_t a = b3 ? t[i + 5] : t[i], b = __shfl_xor_sync(0xffffffffu, b3 ? t[i] : t[i + 5], 8);
        l[2 * i] += __uint_as_float(a << 16) + __uint_as_float(b << 16);
        l[2 * i + 1] += __uint_as_float(a & 0xffff0000u) + __uint_as_float(b & 0xffff0000u);
    }
}
template <bool ADD>
__device__ __forceinline__ void sum_store(const float (&l)[10], uint32_t lane, uint32_t lxa) {
    const bool b2 = lane & 4;
    float t[5];
#pragma unroll
    for (int i = 0; i < 5; i++) t[i] = ADD ? __uint_as_float(lds_u(lxa + i * 64)) : 0.f;
#pragma unroll
    for (int i = 0; i < 5; i++)
        sts_f(lxa + i * 64, t[i] + (b2 ? l[2 * i + 1] : l[2 * i]) + __shfl_xor_sync(0xffffffffu, b2 ? l[2 * i] : l[2 * i + 1], 4));
}

__device__ __forceinline__ void fallback_unit(const Params& P, uint32_t e, uint32_t tid) {
    const uint32_t lane = tid & 31, br = IT_BR(e), b = IT_B(e), h = IT_H0(e);
    const __nv_bfloat162* wq = (const __nv_bfloat162*)(P.pwq[br] + h * 192) + lane;
    const __nv_bfloat162* kp = (const __nv_bfloat162*)(P.pk[br] + (size_t)(b * 32 + h) * 512 * 192) + lane;
    const __nv_bfloat162* vp = (const __nv_bfloat162*)(P.pv[br] + (size_t)(b * 32 + h) * 512 * 192) + lane;
#pragma unroll 1
    for (uint32_t qi = 0; qi < 40; qi++) {
        const uint32_t q = 4 * qi + (tid >> 5);
        const __nv_bfloat16* xr = P.px[br] + (size_t)(b * 160 + q) * 640;
        float a[6] = {0.f, 0.f, 0.f, 0.f, 0.f, 0.f};
#pragma unroll 2
        for (int k = 0; k < 640; k++) {
            const float xv = __bfloat162float(xr[k]);
#pragma unroll
            for (int i = 0; i < 3; i++) {
                const float2 wv = __bfloat1622float2(wq[(size_t)k * 3072 + i * 32]);
                a[2 * i] = fmaf(xv, wv.x, a[2 * i]);
                a[2 * i + 1] = fmaf(xv, wv.y, a[2 * i + 1]);
            }
        }
#pragma unroll
        for (int i = 0; i < 6; i++) a[i] = __bfloat162float(__float2bfloat16(a[i]));
        auto score = [&](int key) {
            float d = 0.f;
#pragma unroll
            for (int i = 0; i < 3; i++) {
                const float2 kv = __bfloat1622float2(kp[key * 96 + i * 32]);
                d = fmaf(a[2 * i], kv.x, fmaf(a[2 * i + 1], kv.y, d));
            }
#pragma unroll
            for (int o = 16; o > 0; o >>= 1) d += __shfl_xor_sync(0xffffffffu, d, o);
            return d;
        };
        float m = -INFINITY, o[6] = {0.f, 0.f, 0.f, 0.f, 0.f, 0.f}, sum = 0.f;
#pragma unroll 1
        for (int n = 0; n < 1024; n++) {
            const int key = n & 511;
            const float d = score(key);
            if (n < 512) {
                m = fmaxf(m, d);
            } else {
                const float p = ex2((d - m) * SM_C);
                sum += p;
#pragma unroll
                for (int i = 0; i < 3; i++) {
                    const float2 vv = __bfloat1622float2(vp[key * 96 + i * 32]);
                    o[2 * i] = fmaf(p, vv.x, o[2 * i]);
                    o[2 * i + 1] = fmaf(p, vv.y, o[2 * i + 1]);
                }
            }
        }
        const float inv = __fdividef(1.f, sum);
        __nv_bfloat16* op = (__nv_bfloat16*)ostash(IT_SLOT(e), b) + (q >> 5) * 256 + 2 * ((q & 31) >> 3) + (q & 1);
#pragma unroll
        for (int i = 0; i < 6; i++) {
            const uint32_t d = (i >> 1) * 64 + 2 * lane + (i & 1);
            op[(d >> 3) * 1280 + (d & 7) * 32 + ((((q & 7) >> 1) ^ ((d & 7) >> 1)) << 3)] = __float2bfloat16(o[i] * inv);
        }
    }
}

template <int W>
struct PendO {
    static constexpr int N = W == 0 ? 56 : 64;
    uint32_t v[N];
    unsigned char* gp;
    static __device__ __forceinline__ uint32_t toff() {
        const uint32_t t = tid_now();
        return ((t >> 5) & 3) * 5120 + ((t >> 2) & 7) * 64 + (((t ^ (t >> 3)) & 3) << 4);
    }
    uint32_t pend, sig;
    static __device__ __forceinline__ void scale(uint32_t& x, uint32_t hi, uint32_t lo) {
        asm("{\n.reg .b32 t;\nmul.rn.bf16x2 t, %0, %2;\nfma.rn.bf16x2 %0, %0, %1, t;\n}" : "+r"(x) : "r"(hi), "r"(lo));
    }
    template <int I, int OFF>
    __device__ __forceinline__ void put() {
        asm volatile("{\n.reg .pred p;\nsetp.ne.u32 p, %6, 0;\n@p st.global.v4.b32 [%0+%5], {%1,%2,%3,%4};\n}" ::"l"(gp), "r"(v[I]),
                     "r"(v[I + 1]), "r"(v[I + 2]), "r"(v[I + 3]), "n"(OFF), "r"(pend)
                     : "memory");
    }
    __device__ __forceinline__ void verdict(const Params& P, uint32_t sb, int ie) {
        if (sig) {
            nb_sync<NB_VOTE + W, 160>();
            pend = !__any_sync(0xffffffffu, lds_u(sb + OFF_FB) != 0);
            if (W == 1 && !pend) {
                fallback_unit(P, lds_u(sb + OFF_ITEM + ie * 4), tid_now() & 127);
                __syncwarp();
            }
        }
    }
    template <int G, int H>
    __device__ __forceinline__ void half(uint32_t sb) {
        constexpr bool T2 = W == 0 ? G >= 3 : G < 3;
        constexpr int B = T2 ? 40 + 8 * (W == 0 ? G - 3 : G) : 0;
        const uint4 a = lds_u4(sb + OFF_LINV + G * 128 + H * 16 + (threadIdx.x & 3) * 32);
#pragma unroll
        for (int i = 2 * H; i < 8; i += 4) {
            scale(v[8 * G + i], a.x, a.y);
            scale(v[8 * G + i + 1], a.z, a.w);
            if (T2) {
                scale(v[B + i], a.x, a.y);
                scale(v[B + i + 1], a.z, a.w);
            }
        }
        if (H == 1) {
            put<8 * G, W * XS + G * 512>();
            put<8 * G + 4, W * XS + G * 512 + 2560>();
            if (T2) {
                put<B, 2 * XS + G * 512>();
                put<B + 4, 2 * XS + G * 512 + 2560>();
            }
            if (G == 4 && sig) nb_arrive<NB_ODONE, 288>();
        }
    }
    template <int G>
    __device__ __forceinline__ void step(uint32_t sb) {
        half<G, 0>(sb);
        half<G, 1>(sb);
    }
    __device__ __forceinline__ void clear() {
#pragma unroll
        for (int i = 0; i < N; i++) v[i] = 0;
        gp = nullptr;
        pend = 0;
        sig = 0;
    }
};

template <int W, int KK>
__device__ __forceinline__ void qproj(float (&q0)[80], float (&q1)[80], uint32_t sb, Ring& r, uint32_t pslot, uint32_t phm,
                                      PendO<W>& po, const Params& P, int it) {
    const uint32_t loR = (((sb + OFF_R) & 0x3ffff) >> 4) | LO_LBO1;
    const uint32_t loRing = (((sb + OFF_RING) & 0x3ffff) >> 4) | LO_LBO1;
    auto ready = [&](int k) {
        mbar_wait(sb + BAR_RFULL + r.slot * 8, r.ph, r.dl);
        mbar_wait(sb + BAR_XFULL + (k % 5) * 8, ((phm >> (k % 5)) ^ (k / 5)) & 1, r.dl);
    };
    auto release = [&]() {
        if (KK > 0) {
            wg_wait<1>();
            mbar_arrive_warp(sb + BAR_REMPTY + pslot * 8);
            if (KK <= 5) mbar_arrive_warp(sb + (BAR_XEMPTY + (KK - 1) * 8));
        }
    };
    if (KK == 0) ready(0);
    if (W == 1 && KK == QHOLD) nb_sync<NB_SDONE, 256>();
    const uint32_t a = loRing + r.slot * (SLOT >> 4) + (W == 0 ? 0 : 512), b = loR + (KK % 5) * (XS >> 4);
    wg_fence();
    wgmma<1, 0, HI_SW128, KK != 0>(q0, a, b);
    if (W == 0) wgmma<1, 0, HI_SW128, KK != 0>(q1, a + 256, b);
#pragma unroll
    for (int k = 1; k < 4; k++) {
        wgmma<1, 0, HI_SW128, true>(q0, a + (k >> 1) * 768 + (k & 1) * 128, b + k * 2);
        if (W == 0) wgmma<1, 0, HI_SW128, true>(q1, a + 256 + (k >> 1) * 768 + (k & 1) * 128, b + k * 2);
    }
    wg_commit();
    const uint32_t cslot = r.slot;
    r.adv(1);
    if (W == 0 || KK < QHOLD) release();
    if (KK == QST0) {
        po.verdict(P, sb, it - 1);
        po.template half<0, 0>(sb);
    }
    if (KK < 9) ready(KK + 1);
    if (W == 1 && KK >= QHOLD) release();
    if (W == 1 && KK == 7) nb_arrive<NB_PDONE, 256>();
    if (KK == QST0) po.template half<0, 1>(sb);
    if constexpr (KK > QST0 && KK < QST0 + 5) po.template step<KK - QST0>(sb);
    if constexpr (KK < 9) {
        qproj<W, KK + 1>(q0, q1, sb, r, cslot, phm, po, P, it);
    } else {
        if (W == 0) nb_arrive<NB_SDONE, 256>();
        wg_wait<0>();
        reg_fence(q0);
        if (W == 0) reg_fence(q1);
        mbar_arrive_warp(sb + BAR_REMPTY + cslot * 8);
    }
}

template <int NR>
__device__ __forceinline__ void opack(const float (&o)[NR], uint32_t* v) {
#pragma unroll
    for (int g = 0; g < NR / 16; g++)
#pragma unroll
        for (int hh = 0; hh < 2; hh++)
#pragma unroll
            for (int t = 0; t < 4; t++) v[8 * g + 4 * hh + t] = pack_bf16(o[16 * g + 4 * t + 2 * hh], o[16 * g + 4 * t + 2 * hh + 1]);
}

template <bool IS_S>
__device__ __forceinline__ void op_item(uint32_t e, uint32_t sb, Ring& r, uint32_t& phm) {
    constexpr int T0 = IS_S ? 0 : 2;
    constexpr uint32_t BOFF = IS_S ? (3 * 512) >> 4 : 0;
    const uint32_t loRing = (((sb + OFF_RING) & 0x3ffff) >> 4) | LO_LBO1;
    const uint32_t loO = (((sb + OFF_R) & 0x3ffff) >> 4) | LO_OST;
    float c0[80], c1[80], c2[IS_S ? 32 : 48];
    const int T2 = 6 * (IT_H1(e) - IT_H0(e));
    uint32_t xs = 0;
    auto step = [&](auto first, uint32_t hf) {
        constexpr bool F = decltype(first)::value;
        if (hf == 0) {
            mbar_wait(sb + BAR_XFULL + xs * 8, (phm >> xs) & 1, r.dl);
            phm ^= 1u << xs;
        }
        mbar_wait(sb + BAR_RFULL + r.slot * 8, r.ph, r.dl);
        const uint32_t a = loRing + r.slot * (SLOT >> 4), b = loO + xs * (XS >> 4) + hf * 640;
        wg_fence();
        wgmma<1, 1, HI_OST, !F>(c0, a + T0 * 128, b);
        wgmma<1, 1, HI_OST, !F>(c1, a + T0 * 128 + 128, b);
        wgmma<1, 1, HI_OST, !F>(c2, a + 512, b + BOFF);
        wgmma<1, 1, HI_OST, true>(c0, a + 640 + T0 * 128, b + 320);
        wgmma<1, 1, HI_OST, true>(c1, a + 640 + T0 * 128 + 128, b + 320);
        wgmma<1, 1, HI_OST, true>(c2, a + 640 + 512, b + 320 + BOFF);
        wg_commit();
    };
    step(TrueT{}, 0);
#pragma unroll 1
    for (int t = 1; t < T2; t++) {
        const uint32_t pslot = r.slot, pxs = xs;
        r.adv(1);
        if ((t & 1) == 0 && ++xs == 5) xs = 0;
        step(FalseT{}, t & 1);
        wg_wait<1>();
        mbar_arrive_warp(sb + BAR_REMPTY + pslot * 8);
        if ((t & 1) == 0 && t + 8 < T2) mbar_arrive_warp(sb + BAR_XEMPTY + pxs * 8);
    }
    wg_wait<0>();
    reg_fence(c0);
    reg_fence(c1);
    reg_fence(c2);
    mbar_arrive_warp(sb + BAR_REMPTY + r.slot * 8);
    r.adv(1);
    nb_sync<NB_OPEND, 256>();
    const uint32_t tid = tid_now(), lane = tid & 31, w = (tid >> 5) & 3;
    store_out_tile<false>(c0, sb + OFF_R + T0 * XS, lane, w);
    store_out_tile<false>(c1, sb + OFF_R + (T0 + 1) * XS, lane, w);
    store_out_tile<false>(c2, sb + OFF_R + 4 * XS + (IS_S ? 96 * 128 : 0), lane, w);
    fence_async_smem();
    nb_arrive<NB_ODONE, 288>();
}

template <int W>
__device__ __forceinline__ void on_item(uint32_t e, uint32_t sb, Ring& r, uint32_t& phm) {
    const uint32_t loRing = (((sb + OFF_RING) & 0x3ffff) >> 4) | LO_LBO1;
    const uint32_t loO = (((sb + OFF_R) & 0x3ffff) >> 4) | LO_OST;
    float c[80];
    const int T = 3 * (IT_H1(e) - IT_H0(e));
    uint32_t xs = 0;
    auto step = [&](auto first) {
        constexpr bool F = decltype(first)::value;
        mbar_wait(sb + BAR_XFULL + xs * 8, (phm >> xs) & 1, r.dl);
        phm ^= 1u << xs;
        mbar_wait(sb + BAR_RFULL + r.slot * 8, r.ph, r.dl);
        const uint32_t a = loRing + r.slot * (SLOT >> 4) + W * 256, b = loO + xs * (XS >> 4);
        wg_fence();
        wgmma<1, 1, HI_OST, !F>(c, a, b);
#pragma unroll
        for (int k = 1; k < 4; k++) wgmma<1, 1, HI_OST, true>(c, a + (k >> 1) * 512 + (k & 1) * 128, b + k * 320);
        wg_commit();
    };
    step(TrueT{});
#pragma unroll 1
    for (int t = 1; t < T; t++) {
        const uint32_t pslot = r.slot, pxs = xs;
        r.adv(1);
        if (++xs == 5) xs = 0;
        step(FalseT{});
        wg_wait<1>();
        mbar_arrive_warp(sb + BAR_REMPTY + pslot * 8);
        mbar_arrive_warp_if(sb + BAR_XEMPTY + pxs * 8, t + 2 < T);
    }
    xs += 1 + W;
    if (xs >= 5) xs -= 5;
    mbar_wait(sb + BAR_XFULL + xs * 8, (phm >> xs) & 1, r.dl);
    wg_wait<0>();
    reg_fence(c);
    const uint32_t tid = tid_now();
    store_out_tile<true>(c, sb + OFF_R + xs * XS, tid & 31, (tid >> 5) & 3);
    fence_async_smem();
    nb_arrive<NB_ODONE, 288>();
}

template <int W>
__device__ __forceinline__ uint32_t qa_item(const Params& P, uint32_t e, uint32_t sb, Ring& r, uint32_t phm, PendO<W>& po, int it) {
    const uint32_t loR = (((sb + OFF_R) & 0x3ffff) >> 4) | LO_LBO1;
    const uint32_t loRing = (((sb + OFF_RING) & 0x3ffff) >> 4) | LO_LBO1;
    uint32_t lane, sta;
    {
        float q0[80], q1[80];
        qproj<W, 0>(q0, q1, sb, r, 0, phm, po, P, it);
        const uint32_t tid = tid_now();
        lane = tid & 31;
        sta = sb + OFF_R + (lane >> 4) * 1024 + (lane & 7) * 128 + (((((tid >> 4) & 6) + ((lane >> 3) & 1)) ^ (lane & 7)) << 4);
        TSD(W, 1);
        if (W == 0) {
            nb_sync<NB_PDONE, 256>();
            store_tile_t(q0, sta);
            store_tile_t(q1, sta + XS);
        } else {
            store_tile_t(q0, sta + 2 * XS);
        }
    }
    fence_async_smem();
    float s[80], oa[80], ob[W == 0 ? 32 : 48], l[10];
    zero(oa);
    zero(ob);
    zero(l);
    reg_fence(oa);
    reg_fence(ob);
    auto pv = [&](const Ring& rv, uint32_t buf) {
        mbar_wait(sb + BAR_RFULL + rv.slot * 8, rv.ph, rv.dl);
        const uint32_t a = loRing + rv.slot * (SLOT >> 4), b = loR + (3 + buf) * (XS >> 4);
        wg_fence();
#pragma unroll
        for (int k = 0; k < 4; k++) {
            wgmma<1, 0, HI_SW128, true>(oa, a + W * 512 + k * 128, b + k * 2);
            wgmma<1, 0, HI_SW128, true>(ob, a + 1024 + k * 128, b + (W == 0 ? (96 * 128) >> 4 : 0) + k * 2);
        }
        wg_commit();
    };
    float mref;
    uint32_t kslot, vslot;
    auto tail = [&](bool rel_other, int i) {
        uint32_t ps[40];
        exp_block<0>(s, ps, sta + (3 + W) * XS, mref);
        if (rel_other) {
            wg_wait<0>();
            mbar_arrive_warp(sb + BAR_REMPTY + vslot * 8);
            if (W == 1) mbar_arrive_warp_if(sb + BAR_XEMPTY + 24, i == 3);
        }
        fence_async_smem();
        nb_arrive<NB_PFULL + W, 256>();
        TSD(W, 6 + 5 * i);
        if (W == 1) {
            if (XLATE >= 2) mbar_arrive_warp_if<2>(sb + BAR_XEMPTY + 8, i == 3);
            if (XLATE >= 1) mbar_arrive_warp_if<2>(sb + BAR_XEMPTY + 16, i == 3);
        }
        if (rel_other || !PV0FIRST) {
            mbar_wait(sb + BAR_RFULL + r.slot * 8, r.ph, r.dl);
            sum_block(ps, l, lane);
        }
        TSD(W, 7 + 5 * i);
        nb_sync<NB_W + W, 128>();
        pv(r, W);
        if (!rel_other && PV0FIRST) sum_block(ps, l, lane);
        TSD(W, 8 + 5 * i);
    };
    if (W == 0) {
        sts_u(sb + OFF_GM + 4, r.slot);
        mbar_wait(sb + BAR_RFULL + r.slot * 8, r.ph, r.dl);
        nb_sync<NB_QK, 160>();
        TSD(W, 2);
        wg_fence();
        qk_steps<0, 8>(s, loRing + r.slot * (SLOT >> 4), loR);
        nb_sync<NB_Q2, 288>();
        qk_steps<8, 12>(s, loRing + r.slot * (SLOT >> 4), loR);
        wg_commit();
        nb_arrive<NB_Q01, 256>();
        TSD(W, 4);
        nb_sync<NB_REF, 160>();
        mref = __uint_as_float(lds_u(sb + OFF_GM));
        wg_wait<0>();
        reg_fence(s);
        mbar_arrive_warp<2>(sb + BAR_REMPTY + r.slot * 8);
        r.adv(2);
        TSD(W, 5);
        tail(false, 0);
    } else {
        nb_arrive<NB_Q2, 288>();
        TSD(W, 2);
        nb_sync<NB_Q01, 256>();
    }
#pragma unroll 1
    for (int i = (W == 0 ? 1 : 0); i < 4; i++) {
        const uint32_t pvslot = r.slot;
        r.adv(1);
        kslot = r.slot;
        mbar_wait(sb + BAR_RFULL + r.slot * 8, r.ph, r.dl);
        wg_fence();
        qk_steps<0, 12>(s, loRing + r.slot * (SLOT >> 4), loR);
        wg_commit();
        wg_wait<1>();
        mbar_arrive_warp_if(sb + BAR_REMPTY + pvslot * 8, W == 0 || i > 0);
        r.adv(1);
        vslot = r.slot;
        TSD(W, 4 + 5 * i);
        nb_sync<NB_PFULL + (W ^ 1), 256>();
        pv(r, W ^ 1);
        if (W == 1) mref = __uint_as_float(lds_u(sb + OFF_GM));
        wg_wait<1>();
        reg_fence(s);
        mbar_arrive_warp<2>(sb + BAR_REMPTY + kslot * 8);
        if (W == 1) {
            mbar_arrive_warp_if<2>(sb + BAR_XEMPTY + 0, i == 3);
            if (XLATE < 2) mbar_arrive_warp_if<2>(sb + BAR_XEMPTY + 8, i == 3);
            if (XLATE < 1) mbar_arrive_warp_if<2>(sb + BAR_XEMPTY + 16, i == 3);
        }
        r.adv(W == 1 && i == 3 ? 1 : 2);
        TSD(W, 5 + 5 * i);
        tail(true, i);
    }
    const uint32_t w = (tid_now() >> 5) & 3;
    const uint32_t lxa = sb + OFF_LX + w * 640 + (((lane & 8) ? 80 : 0) + ((lane >> 1) & 8) + 2 * (lane & 3) + ((lane >> 2) & 1)) * 4;
    const uint32_t nx = get_item_warp(sb, it + 1, r.dl);
    po.gp = ostash(IT_SLOT(e), IT_B(e)) + po.toff();
    po.sig = 1;
    if (W == 0) {
        sum_store<false>(l, lane, lxa);
        nb_arrive<NB_LX, 256>();
        wg_wait<0>();
        mbar_arrive_warp(sb + BAR_REMPTY + r.slot * 8);
        mbar_arrive_warp(sb + BAR_XEMPTY + 24);
        r.adv(1);
        nb_sync<NB_PFULL + 1, 256>();
        pv(r, 1);
    } else {
        nb_sync<NB_LX, 256>();
        sum_store<true>(l, lane, lxa);
        nb_arrive<NB_L, 160>();
    }
    TSD(W, 24);
    wg_wait<0>();
    reg_fence(oa);
    reg_fence(ob);
    mbar_arrive_warp(sb + BAR_REMPTY + r.slot * 8);
    mbar_arrive_warp(sb + BAR_XEMPTY + 32);
    r.adv(1);
    opack(ob, po.v + 40);
    opack(oa, po.v);
    return nx;
}

template <int W>
__device__ __forceinline__ void consumer(const Params& P, uint32_t sb, uint32_t dl) {
    int it = 0;
    if (W == 0) TS(0, 30);
    Ring r{0, 0, dl};
    uint32_t phm = 0;
    uint32_t e = get_item_warp(sb, 0, dl);
#pragma unroll 1
    while (e != 0) {
        if (IT_TYPE(e) == IT_QA) {
            PendO<W> po;
            po.clear();
#pragma unroll 1
            do {
                TS(W, 0);
                if (W == 0) TS_ITEM(e);
                e = qa_item<W>(P, e, sb, r, phm, po, it);
                TS(W, 31);
                it++;
            } while (IT_TYPE(e) == IT_QA);
            po.verdict(P, sb, it - 1);
            po.template step<0>(sb);
            po.template step<1>(sb);
            po.template step<2>(sb);
            po.template step<3>(sb);
            po.template step<4>(sb);
        } else {
            TS(W, 0);
            if (W == 0) TS_ITEM(e);
            if (IT_TYPE(e) == IT_OP) op_item<W == 0>(e, sb, r, phm);
            else on_item<W>(e, sb, r, phm);
            TS(W, 31);
            e = get_item_warp(sb, ++it, dl);
        }
    }
    TS_DUMP(W);
}

__global__ void __cluster_dims__(2, 1, 1) __launch_bounds__(384, 1) fused_kernel(const __grid_constant__ Params P) {
    extern __shared__ __align__(1024) unsigned char smem_raw[];
    const uint32_t sb = (uint32_t)__cvta_generic_to_shared(smem_raw);
    const uint32_t wgid = __shfl_sync(0xffffffffu, threadIdx.x >> 7, 0);
    const uint32_t cta = blockIdx.x;
    const uint32_t dl = deadline();

    uint32_t epoch = 0;
    if (wgid == 0) epoch = *(volatile unsigned int*)&g_epoch[cta] + 1;
    if (threadIdx.x == 0) {
        if (sb & 1023) __trap();
        for (int i = 0; i < NSLOT; i++) {
            mbar_init(sb + BAR_RFULL + i * 8, 1);
            mbar_init(sb + BAR_REMPTY + i * 8, 8);
            mbar_init(sb + BAR_XFULL + i * 8, 1);
            mbar_init(sb + BAR_XEMPTY + i * 8, 8);
            mbar_init(sb + BAR_PRDY + i * 8, 1);
        }
        for (int i = 0; i < MAXI; i++) mbar_init(sb + BAR_ITEM + i * 8, 1);
        asm volatile("fence.mbarrier_init.release.cluster;" ::: "memory");
        fence_async_smem();
    }
    __syncthreads();
    asm volatile("barrier.cluster.arrive.relaxed.aligned;\nbarrier.cluster.wait.aligned;" ::: "memory");

    if (wgid == 0) {
        asm volatile("setmaxnreg.dec.sync.aligned.u32 24;");
        const uint32_t warp = __shfl_sync(0xffffffffu, threadIdx.x >> 5, 0);
        if (warp == 0) {
            if (threadIdx.x == 0) {
                *(volatile unsigned int*)&g_epoch[cta] = epoch;
                const uint64_t pol_first = mkpol<1>(), pol_norm = mkpol<POL_W>();
                if (cta == 0) *(volatile unsigned int*)&g_ticket[(epoch + 1) & 1] = 0;
                const uint32_t rank = cta & 1;
                uint32_t peer;
                asm volatile("mapa.shared::cluster.u32 %0, %1, %2;" : "=r"(peer) : "r"(sb), "r"(rank ^ 1));
                Ring r{0, 1, dl};
                uint32_t pm = 0;
                auto load_w = [&](const CUtensorMap* m, int row, int blk, uint32_t half_bytes) {
                    mbar_wait(sb + BAR_REMPTY + r.slot * 8, r.ph, dl);
                    mbar_expect(sb + BAR_RFULL + r.slot * 8, 2 * half_bytes);
                    asm volatile("mbarrier.arrive.shared::cluster.b64 _, [%0];" ::"r"(peer + BAR_PRDY + r.slot * 8) : "memory");
                    mbar_wait(sb + BAR_PRDY + r.slot * 8, (pm >> r.slot) & 1, dl);
                    pm ^= 1u << r.slot;
                    tma3_mc(sb + OFF_RING + r.slot * SLOT + rank * half_bytes, m, row, blk, sb + BAR_RFULL + r.slot * 8, pol_norm);
                    r.adv(1);
                };
                uint32_t e = 0;
                if (rank == 0) {
                    const uint32_t d = P.delay[cta >> 1];
                    uint32_t t0, t1;
                    asm volatile("mov.u32 %0, %%clock;" : "=r"(t0));
                    do {
                        asm volatile("mov.u32 %0, %%clock;" : "=r"(t1));
                    } while (t1 - t0 < d);
                    e = P.items[cta >> 1][0];
                }
#pragma unroll 1
                for (int it = 0;; it++) {
                    uint32_t nx = 0, tk = 0;
                    if (rank == 0) {
                        asm volatile("st.async.weak.shared::cluster.mbarrier::complete_tx::bytes.b32 [%0], %1, [%2];" ::"r"(
                                         peer + OFF_ITEM + it * 4),
                                     "r"(e ? e + 8 : 0), "r"(peer + BAR_ITEM + it * 8)
                                     : "memory");
                        sts_u(sb + OFF_ITEM + it * 4, e);
                        asm volatile("mbarrier.arrive.shared::cta.b64 _, [%0];" ::"r"(sb + BAR_ITEM + it * 8) : "memory");
                        if (IT_TYPE(e) != IT_ON && it + 2 < MAXI) nx = P.items[cta >> 1][it + 1 < NSTAT ? it + 1 : NSTAT - 1];
                    } else {
                        mbar_expect(sb + BAR_ITEM + it * 8, 4);
                        e = get_item(sb, it, dl);
                    }
                    if (e == 0) break;
                    const uint32_t br = IT_BR(e);
                    if (IT_TYPE(e) == IT_QA) {
                        const uint32_t h = IT_H0(e);
#pragma unroll 1
                        for (int kk = 0; kk < 10; kk++) load_w(&P.wq[br], kk * 64 + rank * 32, h * 3, SLOT / 2);
                        const int row0 = (IT_B(e) * 32 + h) * 512;
#pragma unroll 1
                        for (int n = 0; n < 16; n++) {
                            if (n == 13 && nx == IT_DYN) tk = atomicAdd(&g_ticket[epoch & 1], 1);
                            const bool isv = n == 15 || (n > 0 && !(n & 1));
                            const int j = n == 15 ? 7 : isv ? (n - 2) >> 1 : (n + 1) >> 1;
                            mbar_wait(sb + BAR_REMPTY + r.slot * 8, r.ph, dl);
                            mbar_expect(sb + BAR_RFULL + r.slot * 8, SLOT);
                            tma3(sb + OFF_RING + r.slot * SLOT, isv ? &P.v[br] : &P.k[br], row0 + j * 64, 0,
                                 sb + BAR_RFULL + r.slot * 8, pol_first);
                            r.adv(1);
                        }
                    } else {
                        const bool wide = IT_TYPE(e) == IT_OP;
                        const int step = wide ? 32 : 64, r1 = IT_H1(e) * 192;
#pragma unroll 1
                        for (int row = IT_H0(e) * 192 + rank * (step >> 1); row < r1; row += step)
                            load_w(wide ? &P.wo[br] : &P.won[br], row, IT_HALF(e) * (wide ? 5 : 2), wide ? XS / 2 : 8192);
                        if (nx == IT_DYN) tk = atomicAdd(&g_ticket[epoch & 1], 1);
                    }
                    if (nx == IT_DYN) nx = tk < P.nlist ? P.list[tk] : 0;
                    e = nx;
                }
            }
        } else if (warp == 1) {
            const uint64_t pol_norm = mkpol<POL_X>(), pol_o = mkpol<POL_O>();
            const bool lead = threadIdx.x == 32;
            uint32_t phm = 0x1f;
#pragma unroll 1
            for (int it = 0;; it++) {
                const uint32_t e = get_item_warp(sb, it, dl);
                if (e == 0) break;
                const uint32_t br = IT_BR(e);
                uint32_t xs = 0;
                auto acquire = [&]() {
                    mbar_wait(sb + BAR_XEMPTY + xs * 8, (phm >> xs) & 1, dl);
                    phm ^= 1u << xs;
                    if (lead) mbar_expect(sb + BAR_XFULL + xs * 8, XS);
                };
                if (IT_TYPE(e) == IT_QA) {
#pragma unroll 1
                    for (int kk = 0; kk < 10; kk++) {
                        acquire();
                        if (lead) tma3(sb + OFF_R + xs * XS, &P.x[br], IT_B(e) * 160, kk, sb + BAR_XFULL + xs * 8, pol_norm);
                        if (++xs == 5) xs = 0;
                    }
                } else {
                    const unsigned int* fp = g_flag + (br * 16 + IT_B(e)) * 64 + (threadIdx.x & 31);
                    uint32_t hm = 0, pm = 0;
                    auto poll = [&](uint32_t hneed, uint32_t pneed) {
                        if ((hm & hneed) == hneed && (pm & pneed) == pneed) return;
                        uint32_t n = 0;
                        do {
                            uint32_t a, b;
                            asm volatile("ld.acquire.gpu.global.u32 %0, [%2];\nld.acquire.gpu.global.u32 %1, [%2+128];"
                                         : "=r"(a), "=r"(b) : "l"(fp) : "memory");
                            hm = __ballot_sync(0xffffffffu, a == epoch);
                            pm = __ballot_sync(0xffffffffu, b == epoch);
                            if (++n > 0x1000000) __trap();
                        } while ((hm & hneed) != hneed || (pm & pneed) != pneed);
                        __syncwarp();
                        asm volatile("fence.proxy.async;" ::: "memory");
                    };
#pragma unroll 1
                    for (uint32_t h = IT_H0(e); h < IT_H1(e); h++) {
                        poll(1u << h, 0);
                        const unsigned char* src = ostash(P.slot[br * 32 + h], IT_B(e));
#pragma unroll 1
                        for (int t = 0; t < 3; t++) {
                            acquire();
                            if (lead) bulk_load(sb + OFF_R + xs * XS, src + t * XS, XS, sb + BAR_XFULL + xs * 8, pol_o);
                            if (++xs == 5) xs = 0;
                        }
                        if (IT_TYPE(e) == IT_OP && h >= 1) {
                            const uint32_t x1 = xs == 4 ? 0 : xs + 1;
                            mbar_wait(sb + BAR_XFULL + xs * 8, (phm >> xs) & 1, dl);
                            mbar_wait(sb + BAR_XFULL + x1 * 8, (phm >> x1) & 1, dl);
                            if (lead)
                                asm volatile("st.relaxed.gpu.global.u32 [%0], %1;" ::"l"(fp + 34 + IT_HALF(e)), "r"(epoch * 64 + h) : "memory");
                        }
                    }
                    if (IT_TYPE(e) == IT_ON) {
                        poll(0, IT_HALF(e) < 2 ? 1 : IT_HALF(e) == 2 ? 3 : 2);
#pragma unroll 1
                        for (uint32_t tile = 2 * IT_HALF(e); tile < 2 * IT_HALF(e) + 2; tile++) {
                            acquire();
                            if (lead)
                                asm volatile(
                                    "cp.async.bulk.tensor.2d.shared::cluster.global.mbarrier::complete_tx::bytes [%0], [%1, {%3,%4}], [%2];" ::"r"(
                                        sb + OFF_R + xs * XS),
                                    "l"(&P.out), "r"(sb + BAR_XFULL + xs * 8), "r"(br * 640 + tile * 64), "r"(IT_B(e) * 160)
                                    : "memory");
                            if (++xs == 5) xs = 0;
                        }
                    }
                }
            }
        } else if (warp == 2) {
#pragma unroll 1
            for (int it = 0;; it++) {
                const uint32_t e = get_item_warp(sb, it, dl);
                if (e == 0) break;
                nb_sync<NB_ODONE, 288>();
                if (threadIdx.x == 64) {
                    const uint32_t bb = IT_BR(e) * 16 + IT_B(e);
                    if (IT_TYPE(e) != IT_QA) {
                        const bool wide = IT_TYPE(e) == IT_OP;
                        if (wide)
                            asm volatile("st.relaxed.gpu.global.u32 [%0], %1;" ::"l"(&g_flag[bb * 64 + 34 + IT_HALF(e)]),
                                         "r"(epoch * 64 + IT_H1(e))
                                         : "memory");
                        const int cc0 = IT_BR(e) * 640 + IT_HALF(e) * (wide ? 320 : 128);
                        uint32_t xs = wide ? 0 : (3 * (IT_H1(e) - IT_H0(e))) % 5;
#pragma unroll 1
                        for (int m = 0; m < (wide ? 5 : 2); m++) {
                            asm volatile("cp.async.bulk.tensor.2d.global.shared::cta.bulk_group [%0, {%2,%3}], [%1];" ::"l"(&P.out),
                                         "r"(sb + OFF_R + xs * XS), "r"(cc0 + m * 64), "r"((int)IT_B(e) * 160)
                                         : "memory");
                            asm volatile("cp.async.bulk.commit_group;" ::: "memory");
                            if (++xs == 5) xs = 0;
                        }
                        if (wide) {
#define REL(N)                                                          \
    asm volatile("cp.async.bulk.wait_group.read %0;" ::"n"(4 - N) : "memory"); \
    asm volatile("mbarrier.arrive.shared::cta.b64 _, [%0], 8;" ::"r"(sb + BAR_XEMPTY + N * 8) : "memory");
                            REL(0) REL(1) REL(2) REL(3) REL(4)
#undef REL
                        }
                        if (IT_PART(e)) {
                            asm volatile("cp.async.bulk.wait_group 0;" ::: "memory");
                            asm volatile("fence.proxy.async;" ::: "memory");
                        }
                    }
                    if (IT_TYPE(e) == IT_QA || IT_PART(e)) {
                        unsigned int* f = &g_flag[bb * 64 + (IT_TYPE(e) == IT_QA ? IT_H0(e) : 32 + IT_HALF(e))];
                        asm volatile("st.release.gpu.global.u32 [%0], %1;" ::"l"(f), "r"(epoch) : "memory");
                    }
                }
                __syncwarp();
            }
            if (threadIdx.x == 64) asm volatile("cp.async.bulk.wait_group 0;" ::: "memory");
            __syncwarp();
            asm volatile("barrier.cluster.arrive.relaxed.aligned;\nbarrier.cluster.wait.aligned;" ::: "memory");
        } else {
            const uint32_t lane = threadIdx.x & 31, p = lane >> 2;
#pragma unroll 1
            for (int it = 0;; it++) {
                const uint32_t e = get_item_warp(sb, it, dl);
                if (e == 0) break;
                if (IT_TYPE(e) != IT_QA) continue;
                nb_sync<NB_QK, 160>();
                const uint32_t co = (((lane & 3) * 2) ^ p) << 4;
                const uint32_t ka = sb + OFF_RING + lds_u(sb + OFF_GM + 4) * SLOT + p * (9 * 128) + co;
                const uint32_t qa = sb + OFF_R + p * (17 * 128) + co;
                uint32_t acc = 0;
#pragma unroll
                for (int c = 0; c < 6; c++) {
                    if (c == 4) nb_sync<NB_Q2, 288>();
                    const uint4 kv = lds_u4((ka + (c >> 1) * 8192) ^ ((c & 1) << 4));
                    const uint4 qv = lds_u4((qa + (c >> 1) * XS) ^ ((c & 1) << 4));
                    acc = fma_bf2(kv.x, qv.x, fma_bf2(kv.y, qv.y, fma_bf2(kv.z, qv.z, fma_bf2(kv.w, qv.w, acc))));
                }
                float d = __uint_as_float(acc << 16) + __uint_as_float(acc & 0xffff0000u);
                d += __shfl_xor_sync(0xffffffffu, d, 1);
                d += __shfl_xor_sync(0xffffffffu, d, 2);
                int key = __float_as_int(d);
                key ^= (key >> 31) & 0x7fffffff;
                key = __reduce_max_sync(0xffffffffu, key);
                key ^= (key >> 31) & 0x7fffffff;
                sts_f(sb + OFF_GM, __int_as_float(key) * SM_C);
                nb_arrive<NB_REF, 160>();
                if (IT_DEP(e)) {
                    const uint32_t g = IT_DEP(e) - 1, need = epoch * 64 + (g & 31) + 1;
                    const unsigned int* cp = &g_flag[((g >> 5) * 16 + IT_B(e)) * 64 + 34 + (lane & 1)];
                    for (uint32_t n = 0;; n++) {
                        uint32_t v;
                        asm volatile("ld.acquire.gpu.global.u32 %0, [%1];" : "=r"(v) : "l"(cp) : "memory");
                        if (__all_sync(0xffffffffu, v - need < 64)) break;
                        if (n > 0x800000) __trap();
                        __nanosleep(500);
                    }
                }
                nb_sync<NB_L, 160>();
                bool bad = false;
#pragma unroll
                for (int c = 0; c < 5; c++) {
                    const uint32_t la = sb + OFF_LX + (c * 32 + lane) * 4;
                    const float v = (__uint_as_float(lds_u(la)) + __uint_as_float(lds_u(la + 640))) +
                                    (__uint_as_float(lds_u(la + 1280)) + __uint_as_float(lds_u(la + 1920)));
                    const float inv = __fdividef(1.f, v);
                    const uint32_t hi = pack_bf16(inv, 0.f), lo = pack_bf16(inv - __uint_as_float(hi << 16), 0.f);
                    const uint32_t ia = sb + OFF_LINV + c * 128 + ((lane >> 1) & 3) * 32 + (lane >> 3) * 8 + (lane & 1) * 2;
                    asm volatile("st.shared.u16 [%0], %1;\nst.shared.u16 [%0+4], %2;" ::"r"(ia), "h"((unsigned short)hi), "h"((unsigned short)lo) : "memory");
                    bad |= !(v >= 5.421010862e-20f && v <= 1.8446744e19f);
                }
                sts_u(sb + OFF_FB, __any_sync(0xffffffffu, bad));
                nb_arrive<NB_VOTE, 160>();
                nb_arrive<NB_VOTE + 1, 160>();
            }
        }
    } else if (wgid == 1) {
        asm volatile("setmaxnreg.inc.sync.aligned.u32 240;");
        consumer<0>(P, sb, dl);
    } else {
        asm volatile("setmaxnreg.inc.sync.aligned.u32 240;");
        consumer<1>(P, sb, dl);
    }
}

typedef CUresult (*EncFn)(CUtensorMap*, CUtensorMapDataType, cuuint32_t, void*, const cuuint64_t*, const cuuint64_t*,
                          const cuuint32_t*, const cuuint32_t*, CUtensorMapInterleave, CUtensorMapSwizzle,
                          CUtensorMapL2promotion, CUtensorMapFloatOOBfill);

void make_map3(EncFn enc, CUtensorMap* m, void* p, uint64_t rows, uint64_t rowbytes, uint64_t nblk, uint32_t boxrows,
               uint32_t boxblk) {
    cuuint64_t dims[3] = {64, rows, nblk};
    cuuint64_t str[2] = {rowbytes, 128};
    cuuint32_t box[3] = {64, boxrows, boxblk};
    cuuint32_t es[3] = {1, 1, 1};
    enc(m, CU_TENSOR_MAP_DATA_TYPE_BFLOAT16, 3, p, dims, str, box, es, CU_TENSOR_MAP_INTERLEAVE_NONE,
        CU_TENSOR_MAP_SWIZZLE_128B, CU_TENSOR_MAP_L2_PROMOTION_NONE, CU_TENSOR_MAP_FLOAT_OOB_FILL_NONE);
}

constexpr int tune(const char*, int def) { return def; }

void build_schedule(Params& P) {
    const int mode = tune("MODE", 4), dmax = tune("DMAX", 24900), n0 = tune("N0", 6);
    const int H0[8] = {18, 17, 20, 21, 22, 23, 23, 24}, P0[8] = {383, 371, 344, 348, 354, 345, 348, 336};
    const int ng = tune("NG", 0), d0 = tune("D0", 0), nkeep = tune("NKEEP", 0), odmax = tune("ODMAX", 6000);
    const int ong = tune("ONG", 0), od0 = tune("OD0", 0), jit = tune("JIT", 0);
    const int npos = tune("NPOS", 0), nearly = tune("NEARLY", 0);
    const int ra = tune("RA", 10), ga = tune("GA", 32), rb = tune("RB", 12), g1 = tune("G1", 58);
    int dep[64];
    for (int g = 0, ns = 0, live = 0; g < 64; g++) {
        const bool fresh = mode < 3 || g >= g1 || live < (g < ga ? ra : rb);
        dep[g] = fresh ? 0 : g - live + 1;
        P.slot[g] = fresh ? ns++ : P.slot[g - live];
        live += fresh;
    }
    int u = 0;
    auto unit = [&]() {
        const uint32_t e = mk_item(IT_QA, u >> 8, (u & 7) * 2, (u >> 3) & 31, P.slot[u >> 3], 0) | (dep[u >> 3] << 23);
        u++;
        return e;
    };
    int qa[NCL], nq = 0, op[NCL], no = 0;
    for (int c = 0; c < NCL; c++) {
        P.delay[c] = 0;
        for (int i = 0; i < NSTAT; i++) P.items[c][i] = 0;
        if (mode >= 3 && c < 64 && (c & 3) == 3) op[no++] = c;
        else if (mode != 2 || (c & 3) == 0) qa[nq++] = c;
    }
    for (int t = 0; t < no; t++) {
        P.items[op[t]][1] = mk_item(IT_OP, 0, t & ~1, 0, 32, t & 1);
        P.items[op[t]][2] = P.items[op[t]][3] = IT_DYN;
        P.delay[op[t]] = ong ? od0 + (t * ong / 16) * (odmax / ong) : od0 + t * odmax / 16;
    }
    for (int k = 0; k < nq; k++) {
        const int c = qa[(k * 19) % nq];
        P.items[c][1] = P.items[c][2] = P.items[c][3] = IT_DYN;
        P.delay[c] = k < n0 ? 0 : (int)((long long)dmax * (k + 1 - n0) / (nq - n0));
        if (ng) P.delay[c] = d0 + (k * ng / nq) * (dmax / ng) + (k * ng % nq) * jit / nq;
    }
    for (int k = 0; k < no + nq; k++) {
        int best = -1;
        for (int c = 0; c < NCL; c++)
            if (P.items[c][1] && !P.items[c][0] && (best < 0 || P.delay[c] < P.delay[best])) best = c;
        P.items[best][0] = unit();
    }
    int H[8], pos[8];
    for (int b = 0; b < 8; b++) {
        char nh[3] = {'H', (char)('0' + b), 0}, np[3] = {'P', (char)('0' + b), 0};
        H[b] = tune(nh, H0[b]);
        pos[b] = tune(np, P0[b]);
        for (int g = 0; g < 64; g++)
            if (dep[g] > 32) {
                if (pos[b] > 8 * g) pos[b] = 8 * g;
                if (H[b] < dep[g] - 32) H[b] = dep[g] - 32;
            }
        if (b < nkeep && no) {
            pos[b] = -1;
            P.items[op[14 - 2 * b]][2] = mk_item(IT_OP, 1, 2 * b, 0, H[b], 0, 1);
            P.items[op[15 - 2 * b]][2] = mk_item(IT_OP, 1, 2 * b, 0, H[b], 1, 1);
        }
    }
    int n = 0, kn = 0;
    const int uend = mode == 2 ? 8 * nq : 512;
    while (u < uend) {
        for (int b = 0; b < 8 && no; b++)
            if (pos[b] == u) {
                P.list[n++] = mk_item(IT_OP, 1, 2 * b, 0, H[b], 0, 1);
                P.list[n++] = mk_item(IT_OP, 1, 2 * b, 0, H[b], 1, 1);
            }
        while (no && u >= uend - npos && kn * npos < (u + 1 - (uend - npos)) * nearly) {
            P.list[n++] = mk_item(IT_ON, 1, kn / 5 * 2, H[kn / 5], 32, kn % 5);
            kn++;
        }
        P.list[n++] = unit();
    }
    for (; no && kn < 40; kn++) P.list[n++] = mk_item(IT_ON, 1, kn / 5 * 2, H[kn / 5], 32, kn % 5);
    P.nlist = n;
}

}

extern "C" void kernel_launch(void* const* d_in, const int* in_sizes, int n_in, void* d_out, int out_size) {
    static Params P;
    static bool init = false;
    if (!init) {
        EncFn enc = nullptr;
        cudaDriverEntryPointQueryResult qr;
        cudaGetDriverEntryPoint("cuTensorMapEncodeTiled", (void**)&enc, cudaEnableDefault, &qr);
        for (int i = 0; i < 2; i++) {
            P.px[i] = (const __nv_bfloat16*)d_in[5 * i + 0];
            P.pk[i] = (const __nv_bfloat16*)d_in[5 * i + 1];
            P.pv[i] = (const __nv_bfloat16*)d_in[5 * i + 2];
            P.pwq[i] = (const __nv_bfloat16*)d_in[5 * i + 3];
            make_map3(enc, &P.x[i], d_in[5 * i + 0], 2560, 1280, 10, 160, 1);
            make_map3(enc, &P.k[i], d_in[5 * i + 1], 16 * 32 * 512, 384, 3, 64, 3);
            make_map3(enc, &P.v[i], d_in[5 * i + 2], 16 * 32 * 512, 384, 3, 64, 3);
            make_map3(enc, &P.wq[i], d_in[5 * i + 3], 640, 12288, 96, 32, 3);
            make_map3(enc, &P.wo[i], d_in[5 * i + 4], 6144, 1280, 10, 16, 5);
            make_map3(enc, &P.won[i], d_in[5 * i + 4], 6144, 1280, 10, 32, 2);
        }
        cuuint64_t dims[2] = {1280, 2560};
        cuuint64_t str[1] = {2560};
        cuuint32_t box[2] = {64, 160};
        cuuint32_t es[2] = {1, 1};
        enc(&P.out, CU_TENSOR_MAP_DATA_TYPE_BFLOAT16, 2, d_out, dims, str, box, es, CU_TENSOR_MAP_INTERLEAVE_NONE,
            CU_TENSOR_MAP_SWIZZLE_128B, CU_TENSOR_MAP_L2_PROMOTION_NONE, CU_TENSOR_MAP_FLOAT_OOB_FILL_NONE);
        build_schedule(P);
        cudaFuncSetAttribute(fused_kernel, cudaFuncAttributeMaxDynamicSharedMemorySize, SMEM_LAUNCH);
        init = true;
    }
    fused_kernel<<<NCTA, 384, SMEM_LAUNCH>>>(P);
}
```

```cpp
#include <cuda_runtime.h>
#include <cuda.h>
#include <cuda_bf16.h>
#include <stdint.h>

namespace {

constexpr int NCTA = 132;
constexpr int NCL = NCTA / 2;
constexpr int MAXI = 16;
constexpr int NSTAT = 3;
constexpr uint32_t IT_DYN = 0xffffffffu;
constexpr int SLOT = 24576;
constexpr int NSLOT = 5;
constexpr int XS = 20480;
constexpr int OFF_R = 0;
constexpr int OFF_RING = 5 * XS;
constexpr int OFF_MISC = OFF_RING + NSLOT * SLOT;
constexpr int OFF_LX = OFF_MISC;
constexpr int OFF_LINV = OFF_LX + 2560;
constexpr int OFF_FB = OFF_LINV + 640;
constexpr int OFF_GM = OFF_FB + 16;
constexpr int OFF_BAR = OFF_GM + 16;
constexpr int BAR_RFULL = OFF_BAR;
constexpr int BAR_REMPTY = BAR_RFULL + 40;
constexpr int BAR_XFULL = BAR_REMPTY + 40;
constexpr int BAR_XEMPTY = BAR_XFULL + 40;
constexpr int BAR_PRDY = BAR_XEMPTY + 40;
constexpr int BAR_ITEM = BAR_PRDY + 40;
constexpr int OFF_ITEM = BAR_ITEM + MAXI * 8;
constexpr int SMEM_BYTES = OFF_ITEM + MAXI * 4;
static_assert(SMEM_BYTES <= 232448, "smem");

constexpr int NB_W = 1  , NB_PFULL = 3  , NB_VOTE = 5  , NB_Q2 = 7, NB_SDONE = 8, NB_PDONE = 9,
              NB_L = 10, NB_REF = 11, NB_ODONE = 12, NB_OPEND = 13, NB_LX = 14, NB_Q01 = 15, NB_QK = 0  ;

constexpr uint32_t IT_QA = 1, IT_OP = 2, IT_ON = 3;
__host__ __device__ constexpr uint32_t mk_item(uint32_t type, uint32_t br, uint32_t b, uint32_t h0, uint32_t h1, uint32_t half,
                                               uint32_t part = 0) {
    return type | (br << 2) | (b << 3) | (h0 << 7) | (h1 << 13) | (half << 19) | (part << 22);
}
#define IT_TYPE(e) ((e) & 3u)
#define IT_BR(e) (((e) >> 2) & 1u)
#define IT_B(e) (((e) >> 3) & 15u)
#define IT_H0(e) (((e) >> 7) & 63u)
#define IT_H1(e) (((e) >> 13) & 63u)
#define IT_HALF(e) (((e) >> 19) & 7u)
#define IT_PART(e) (((e) >> 22) & 1u)
#define IT_SLOT(e) IT_H1(e)
#define IT_DEP(e) (((e) >> 23) & 127u)

struct Params {
    CUtensorMap x[2], wq[2], k[2], v[2], wo[2], won[2], out;
    const __nv_bfloat16 *px[2], *pwq[2], *pk[2], *pv[2];
    struct alignas(16) { uint32_t delay, items[NSTAT]; } cl[NCL];
    uint32_t nlist;
    uint8_t slot[64];
    uint32_t list[512];
};

constexpr int OUNIT = 61440;
__device__ __align__(1024) unsigned char g_ostash[(size_t)1024 * OUNIT];
__device__ unsigned int g_flag[32 * 64];
__device__ __forceinline__ unsigned char* ostash(uint32_t slot, uint32_t b) { return g_ostash + (slot * 16 + b) * OUNIT; }
__device__ unsigned int g_epoch[NCTA * 4];
__device__ unsigned int g_ticket[2];

constexpr int SMEM_LAUNCH = SMEM_BYTES;
#define TS(role, idx)
#define TS_ITEM(e)
#define TS_DUMP(role)
#define TSD(role, idx)

#define POL_W 2
#define POL_X 2
#define POL_O 2
template <int M>
__device__ __forceinline__ uint64_t mkpol() {
    uint64_t p;
    if (M == 0) asm volatile("createpolicy.fractional.L2::evict_normal.b64 %0, 1.0;" : "=l"(p));
    if (M == 1) asm volatile("createpolicy.fractional.L2::evict_first.b64 %0, 1.0;" : "=l"(p));
    if (M == 2) asm volatile("createpolicy.fractional.L2::evict_unchanged.b64 %0, 1.0;" : "=l"(p));
    if (M == 3) asm volatile("createpolicy.fractional.L2::evict_normal.L2::evict_unchanged.b64 %0, 0.25;" : "=l"(p));
    return p;
}
#define STSM_W 1
#define XLATE 2
#define PV0FIRST 1
#define QST0 1
#define QST1 2
#define QHOLD 7
constexpr float SM_C = 0.07216878364870322f * 1.4426950408889634f;

__device__ __forceinline__ uint32_t next_epoch(int warp) {
    unsigned int* p = &g_epoch[blockIdx.x * 4 + warp];
    const uint32_t e = __ldcg(p) + 1;
    *p = e;
    return e;
}

__device__ __forceinline__ uint32_t tid_now() {
    uint32_t t;
    asm volatile("mov.u32 %0, %%tid.x;" : "=r"(t));
    return t;
}
__device__ __forceinline__ void mbar_init(uint32_t a, uint32_t c) {
    asm volatile("mbarrier.init.shared::cta.b64 [%0], %1;" ::"r"(a), "r"(c) : "memory");
}
__device__ __forceinline__ void mbar_expect(uint32_t a, uint32_t b) {
    asm volatile("mbarrier.arrive.expect_tx.shared::cta.b64 _, [%0], %1;" ::"r"(a), "r"(b) : "memory");
}
template <int CNT = 1>
__device__ __forceinline__ void mbar_arrive_warp(uint32_t a) {
    if (CNT == 1)
        asm volatile("{\n.reg .pred p;\nelect.sync _|p, 0xffffffff;\n@p mbarrier.arrive.shared::cta.b64 _, [%0];\n}" ::"r"(a) : "memory");
    else
        asm volatile(
            "{\n.reg .pred p;\nelect.sync _|p, 0xffffffff;\n@p mbarrier.arrive.shared::cta.b64 _, [%0];\n"
            "@p mbarrier.arrive.shared::cta.b64 _, [%0];\n}" ::"r"(a)
            : "memory");
}
template <int CNT = 1>
__device__ __forceinline__ void mbar_arrive_warp_if(uint32_t a, bool cond) {
    if (CNT == 1)
        asm volatile(
            "{\n.reg .pred p, c;\nelect.sync _|p, 0xffffffff;\nsetp.ne.and.u32 c, %1, 0, p;\n"
            "@c mbarrier.arrive.shared::cta.b64 _, [%0];\n}" ::"r"(a), "r"((uint32_t)cond)
            : "memory");
    else
        asm volatile(
            "{\n.reg .pred p, c;\nelect.sync _|p, 0xffffffff;\nsetp.ne.and.u32 c, %1, 0, p;\n"
            "@c mbarrier.arrive.shared::cta.b64 _, [%0];\n@c mbarrier.arrive.shared::cta.b64 _, [%0];\n}" ::"r"(a), "r"((uint32_t)cond)
            : "memory");
}
__device__ __forceinline__ uint32_t deadline() {
    uint32_t c;
    asm volatile("mov.u32 %0, %%clock_hi;" : "=r"(c));
    return c + 4;
}
__device__ __forceinline__ void mbar_wait(uint32_t a, uint32_t ph, uint32_t dl) {
    asm volatile(
        "{\n.reg .pred p;\n.reg .u32 m;\n"
        "LOOP:\n"
        "mbarrier.try_wait.parity.shared::cta.b64 p, [%0], %1;\n"
        "@p bra DONE;\n"
        "mov.u32 m, %%clock_hi;\n"
        "setp.ne.u32 p, m, %2;\n"
        "@p bra LOOP;\n"
        "trap;\n"
        "DONE:\n}" ::"r"(a), "r"(ph), "r"(dl)
        : "memory");
}
template <int ID, int CNT>
__device__ __forceinline__ void nb_sync() { asm volatile("bar.sync %0, %1;" ::"n"(ID), "n"(CNT) : "memory"); }
template <int ID, int CNT>
__device__ __forceinline__ void nb_arrive() { asm volatile("bar.arrive %0, %1;" ::"n"(ID), "n"(CNT) : "memory"); }
__device__ __forceinline__ void fence_async_smem() { asm volatile("fence.proxy.async.shared::cta;" ::: "memory"); }

__device__ __forceinline__ void tma3(uint32_t dst, const CUtensorMap* m, int c1, int c2, uint32_t bar, uint64_t pol) {
    asm volatile(
        "cp.async.bulk.tensor.3d.shared::cluster.global.mbarrier::complete_tx::bytes.L2::cache_hint [%0], [%1, {%3,%4,%5}], [%2], %6;" ::"r"(dst),
        "l"(m), "r"(bar), "r"(0), "r"(c1), "r"(c2), "l"(pol)
        : "memory");
}
__device__ __forceinline__ void tma3_mc(uint32_t dst, const CUtensorMap* m, int c1, int c2, uint32_t bar, uint64_t pol) {
    asm volatile(
        "cp.async.bulk.tensor.3d.shared::cluster.global.mbarrier::complete_tx::bytes.multicast::cluster.L2::cache_hint"
        " [%0], [%1, {%3,%4,%5}], [%2], %6, %7;" ::"r"(dst),
        "l"(m), "r"(bar), "r"(0), "r"(c1), "r"(c2), "h"((unsigned short)3), "l"(pol)
        : "memory");
}
__device__ __forceinline__ void bulk_load(uint32_t dst, const void* src, uint32_t bytes, uint32_t bar, uint64_t pol) {
    asm volatile("cp.async.bulk.shared::cluster.global.mbarrier::complete_tx::bytes.L2::cache_hint [%0], [%1], %2, [%3], %4;" ::"r"(dst),
                 "l"(src), "r"(bytes), "r"(bar), "l"(pol)
                 : "memory");
}
__device__ __forceinline__ void wg_fence() { asm volatile("wgmma.fence.sync.aligned;" ::: "memory"); }
__device__ __forceinline__ void wg_commit() { asm volatile("wgmma.commit_group.sync.aligned;" ::: "memory"); }
template <int N>
__device__ __forceinline__ void wg_wait() { asm volatile("wgmma.wait_group.sync.aligned %0;" ::"n"(N) : "memory"); }

#define RW80(c, d) c(d[0]), c(d[1]), c(d[2]), c(d[3]), c(d[4]), c(d[5]), c(d[6]), c(d[7]), c(d[8]), c(d[9]), c(d[10]), c(d[11]), c(d[12]), c(d[13]), c(d[14]), c(d[15]), c(d[16]), c(d[17]), c(d[18]), c(d[19]), c(d[20]), c(d[21]), c(d[22]), c(d[23]), c(d[24]), c(d[25]), c(d[26]), c(d[27]), c(d[28]), c(d[29]), c(d[30]), c(d[31]), c(d[32]), c(d[33]), c(d[34]), c(d[35]), c(d[36]), c(d[37]), c(d[38]), c(d[39]), c(d[40]), c(d[41]), c(d[42]), c(d[43]), c(d[44]), c(d[45]), c(d[46]), c(d[47]), c(d[48]), c(d[49]), c(d[50]), c(d[51]), c(d[52]), c(d[53]), c(d[54]), c(d[55]), c(d[56]), c(d[57]), c(d[58]), c(d[59]), c(d[60]), c(d[61]), c(d[62]), c(d[63]), c(d[64]), c(d[65]), c(d[66]), c(d[67]), c(d[68]), c(d[69]), c(d[70]), c(d[71]), c(d[72]), c(d[73]), c(d[74]), c(d[75]), c(d[76]), c(d[77]), c(d[78]), c(d[79])
#define RW48(c, d) c(d[0]), c(d[1]), c(d[2]), c(d[3]), c(d[4]), c(d[5]), c(d[6]), c(d[7]), c(d[8]), c(d[9]), c(d[10]), c(d[11]), c(d[12]), c(d[13]), c(d[14]), c(d[15]), c(d[16]), c(d[17]), c(d[18]), c(d[19]), c(d[20]), c(d[21]), c(d[22]), c(d[23]), c(d[24]), c(d[25]), c(d[26]), c(d[27]), c(d[28]), c(d[29]), c(d[30]), c(d[31]), c(d[32]), c(d[33]), c(d[34]), c(d[35]), c(d[36]), c(d[37]), c(d[38]), c(d[39]), c(d[40]), c(d[41]), c(d[42]), c(d[43]), c(d[44]), c(d[45]), c(d[46]), c(d[47])
#define RW32(c, d) c(d[0]), c(d[1]), c(d[2]), c(d[3]), c(d[4]), c(d[5]), c(d[6]), c(d[7]), c(d[8]), c(d[9]), c(d[10]), c(d[11]), c(d[12]), c(d[13]), c(d[14]), c(d[15]), c(d[16]), c(d[17]), c(d[18]), c(d[19]), c(d[20]), c(d[21]), c(d[22]), c(d[23]), c(d[24]), c(d[25]), c(d[26]), c(d[27]), c(d[28]), c(d[29]), c(d[30]), c(d[31])

__device__ __forceinline__ void reg_fence(float (&d)[80]) { asm volatile("" : RW80("+f", d)::"memory"); }
__device__ __forceinline__ void reg_fence(float (&d)[48]) { asm volatile("" : RW48("+f", d)::"memory"); }
__device__ __forceinline__ void reg_fence(float (&d)[32]) { asm volatile("" : RW32("+f", d)::"memory"); }

template <int NR>
__device__ __forceinline__ void zero(float (&d)[NR]) {
#pragma unroll
    for (int i = 0; i < NR; i++) d[i] = 0.f;
}

constexpr uint32_t HI_SW128 = (1024u >> 4) | (1u << 30);
constexpr uint32_t HI_OST = (2560u >> 4) | (2u << 30);
constexpr uint32_t LO_LBO1 = (1u << 16);
constexpr uint32_t LO_OST = ((512u >> 4) << 16);

template <int TA, int TB, uint32_t HIB, int ACC>
__device__ __forceinline__ void wgmma(float (&d)[80], uint32_t loA, uint32_t loB) {
#define WG_ASM(SD)                                                          \
    "{\n.reg .b64 da, db;\nmov.b64 da, {%80, %82};\nmov.b64 db, {%81, %83};\n" \
    "wgmma.mma_async.sync.aligned.m64n160k16.f32.bf16.bf16 "               \
    "{%0,%1,%2,%3,%4,%5,%6,%7,%8,%9,%10,%11,%12,%13,%14,%15,%16,%17,%18,%19,%20,%21,%22,%23,%24,%25,%26,%27,%28,%29,%30,%31,%32,%33,%34,%35,%36,%37,%38,%39,%40,%41,%42,%43,%44,%45,%46,%47,%48,%49,%50,%51,%52,%53,%54,%55,%56,%57,%58,%59,%60,%61,%62,%63,%64,%65,%66,%67,%68,%69,%70,%71,%72,%73,%74,%75,%76,%77,%78,%79}, da, db, " SD ", 1, 1, %84, %85;\n}"
    if constexpr (ACC == 2)
        asm volatile(WG_ASM("0") : RW80("+f", d) : "r"(loA), "r"(loB), "n"(HI_SW128), "n"(HIB), "n"(TA), "n"(TB));
    else if constexpr (ACC == 1)
        asm volatile(WG_ASM("1") : RW80("+f", d) : "r"(loA), "r"(loB), "n"(HI_SW128), "n"(HIB), "n"(TA), "n"(TB));
    else
        asm volatile(WG_ASM("0") : RW80("=f", d) : "r"(loA), "r"(loB), "n"(HI_SW128), "n"(HIB), "n"(TA), "n"(TB));
#undef WG_ASM
}
template <int TA, int TB, uint32_t HIB, int ACC>
__device__ __forceinline__ void wgmma(float (&d)[48], uint32_t loA, uint32_t loB) {
#define WG_ASM(SD)                                                          \
    "{\n.reg .b64 da, db;\nmov.b64 da, {%48, %50};\nmov.b64 db, {%49, %51};\n" \
    "wgmma.mma_async.sync.aligned.m64n96k16.f32.bf16.bf16 "               \
    "{%0,%1,%2,%3,%4,%5,%6,%7,%8,%9,%10,%11,%12,%13,%14,%15,%16,%17,%18,%19,%20,%21,%22,%23,%24,%25,%26,%27,%28,%29,%30,%31,%32,%33,%34,%35,%36,%37,%38,%39,%40,%41,%42,%43,%44,%45,%46,%47}, da, db, " SD ", 1, 1, %52, %53;\n}"
    if constexpr (ACC == 1)
        asm volatile(WG_ASM("1") : RW48("+f", d) : "r"(loA), "r"(loB), "n"(HI_SW128), "n"(HIB), "n"(TA), "n"(TB));
    else
        asm volatile(WG_ASM("0") : RW48("=f", d) : "r"(loA), "r"(loB), "n"(HI_SW128), "n"(HIB), "n"(TA), "n"(TB));
#undef WG_ASM
}
template <int TA, int TB, uint32_t HIB, int ACC>
__device__ __forceinline__ void wgmma(float (&d)[32], uint32_t loA, uint32_t loB) {
#define WG_ASM(SD)                                                          \
    "{\n.reg .b64 da, db;\nmov.b64 da, {%32, %34};\nmov.b64 db, {%33, %35};\n" \
    "wgmma.mma_async.sync.aligned.m64n64k16.f32.bf16.bf16 "               \
    "{%0,%1,%2,%3,%4,%5,%6,%7,%8,%9,%10,%11,%12,%13,%14,%15,%16,%17,%18,%19,%20,%21,%22,%23,%24,%25,%26,%27,%28,%29,%30,%31}, da, db, " SD ", 1, 1, %36, %37;\n}"
    if constexpr (ACC == 1)
        asm volatile(WG_ASM("1") : RW32("+f", d) : "r"(loA), "r"(loB), "n"(HI_SW128), "n"(HIB), "n"(TA), "n"(TB));
    else
        asm volatile(WG_ASM("0") : RW32("=f", d) : "r"(loA), "r"(loB), "n"(HI_SW128), "n"(HIB), "n"(TA), "n"(TB));
#undef WG_ASM
}

__device__ __forceinline__ uint32_t pack_bf16(float lo, float hi) {
    uint32_t r;
    asm("cvt.rn.bf16x2.f32 %0, %1, %2;" : "=r"(r) : "f"(hi), "f"(lo));
    return r;
}
__device__ __forceinline__ float ex2(float x) {
    float r;
    asm("ex2.approx.ftz.f32 %0, %1;" : "=f"(r) : "f"(x));
    return r;
}
__device__ __forceinline__ void stsm4t(uint32_t a, uint32_t r0, uint32_t r1, uint32_t r2, uint32_t r3) {
    asm volatile("stmatrix.sync.aligned.m8n8.x4.trans.shared.b16 [%0], {%1,%2,%3,%4};" ::"r"(a), "r"(r0), "r"(r1), "r"(r2), "r"(r3)
                 : "memory");
}
__device__ __forceinline__ uint32_t lds_u(uint32_t a) {
    uint32_t v;
    asm volatile("ld.shared.u32 %0, [%1];" : "=r"(v) : "r"(a) : "memory");
    return v;
}
__device__ __forceinline__ uint4 lds_u4(uint32_t a) {
    uint4 v;
    asm volatile("ld.shared.v4.u32 {%0,%1,%2,%3}, [%4];" : "=r"(v.x), "=r"(v.y), "=r"(v.z), "=r"(v.w) : "r"(a) : "memory");
    return v;
}
__device__ __forceinline__ float2 lds_f2(uint32_t a) {
    float2 v;
    asm volatile("ld.shared.v2.f32 {%0,%1}, [%2];" : "=f"(v.x), "=f"(v.y) : "r"(a) : "memory");
    return v;
}
__device__ __forceinline__ void sts_f(uint32_t a, float v) { asm volatile("st.shared.f32 [%0], %1;" ::"r"(a), "f"(v) : "memory"); }
__device__ __forceinline__ void sts_u(uint32_t a, uint32_t v) { asm volatile("st.shared.u32 [%0], %1;" ::"r"(a), "r"(v) : "memory"); }
__device__ __forceinline__ void sts_f2(uint32_t a, float x, float y) {
    asm volatile("st.shared.v2.f32 [%0], {%1,%2};" ::"r"(a), "f"(x), "f"(y) : "memory");
}

__device__ __forceinline__ void store_tile_t(const float (&d)[80], uint32_t addr) {
#pragma unroll
    for (int j = 0; j < 10; j++)
        stsm4t(addr + j * 2048, pack_bf16(d[8 * j], d[8 * j + 1]), pack_bf16(d[8 * j + 2], d[8 * j + 3]),
               pack_bf16(d[8 * j + 4], d[8 * j + 5]), pack_bf16(d[8 * j + 6], d[8 * j + 7]));
}
template <bool ADD, int NR>
__device__ __forceinline__ void store_out_tile(const float (&d)[NR], uint32_t base, uint32_t lane, uint32_t w) {
    const uint32_t mi = lane >> 3, i = lane & 7;
    const uint32_t chunk = 2 * w + (mi & 1);
    const uint32_t q0 = 8 * (i >> 1) + 2 * (mi >> 1) + (i & 1);
    const uint32_t a0 = base + q0 * 128 + ((chunk ^ (q0 & 7)) << 4);
    const uint32_t a1 = base + (q0 + 4) * 128 + ((chunk ^ ((q0 + 4) & 7)) << 4);
    uint32_t p[NR / 2];
    if (ADD) {
#pragma unroll
        for (int j = 0; j < NR / 8; j++)
            asm volatile("ldmatrix.sync.aligned.m8n8.x4.trans.shared.b16 {%0,%1,%2,%3}, [%4];"
                         : "=r"(p[4 * j]), "=r"(p[4 * j + 1]), "=r"(p[4 * j + 2]), "=r"(p[4 * j + 3])
                         : "r"(((j & 1) ? a1 : a0) + (j >> 1) * 4096)
                         : "memory");
    }
#pragma unroll
    for (int k = 0; k < NR / 2; k++)
        p[k] = ADD ? pack_bf16(d[2 * k] + __uint_as_float(p[k] << 16), d[2 * k + 1] + __uint_as_float(p[k] & 0xffff0000u))
                   : pack_bf16(d[2 * k], d[2 * k + 1]);
#pragma unroll
    for (int j = 0; j < NR / 8; j++)
        stsm4t(((j & 1) ? a1 : a0) + (j >> 1) * 4096, p[4 * j], p[4 * j + 1], p[4 * j + 2], p[4 * j + 3]);
}

struct TrueT { static constexpr bool value = true; };
struct FalseT { static constexpr bool value = false; };

template <int V>
struct IntT { static constexpr int value = V; };

__device__ __forceinline__ uint32_t get_item(uint32_t sb, int it, uint32_t dl) {
    mbar_wait(sb + BAR_ITEM + it * 8, 0, dl);
    return lds_u(sb + OFF_ITEM + it * 4);
}
__device__ __forceinline__ uint32_t get_item_warp(uint32_t sb, int it, uint32_t dl) {
    return __shfl_sync(0xffffffffu, get_item(sb, it, dl), 0);
}

struct Ring {
    uint32_t slot, ph, dl;
    __device__ __forceinline__ void adv(uint32_t k) {
        slot += k;
        if (slot >= NSLOT) { slot -= NSLOT; ph ^= 1; }
    }
};

template <int K>
__device__ __forceinline__ void qk_step(float (&s)[80], uint32_t loK, uint32_t loQ) {
    wgmma<0, 0, HI_SW128, K != 0>(s, loK + (K >> 2) * (8192 >> 4) + (K & 3) * 2, loQ + (K >> 2) * (XS >> 4) + (K & 3) * 2);
}
template <int K0, int K1>
__device__ __forceinline__ void qk_steps(float (&s)[80], uint32_t loK, uint32_t loQ) {
    if constexpr (K0 < K1) {
        qk_step<K0>(s, loK, loQ);
        qk_steps<K0 + 1, K1>(s, loK, loQ);
    }
}
__device__ __forceinline__ uint32_t add_bf2(uint32_t a, uint32_t b) {
    uint32_t r;
    asm("add.rn.bf16x2 %0, %1, %2;" : "=r"(r) : "r"(a), "r"(b));
    return r;
}
__device__ __forceinline__ uint32_t fma_bf2(uint32_t a, uint32_t b, uint32_t c) {
    uint32_t r;
    asm("fma.rn.bf16x2 %0, %1, %2, %3;" : "=r"(r) : "r"(a), "r"(b), "r"(c));
    return r;
}
template <int J>
__device__ __forceinline__ void exp_block(const float (&s)[80], uint32_t (&k)[40], uint32_t pa, float mref) {
    if constexpr (J < 10) {
#pragma unroll
        for (int i = 4 * J; i < 4 * J + 4; i++)
            k[i] = pack_bf16(ex2(fmaf(s[2 * i], SM_C, -mref)), ex2(fmaf(s[2 * i + 1], SM_C, -mref)));
#pragma unroll
        for (int i = 0; i < 4; i++)
            asm volatile("stmatrix.sync.aligned.m8n8.x1.trans.shared.b16 [%0], {%1};" ::"r"(((i & 1) ? pa ^ 16 : pa) + J * 2048 + (i >> 1) * 1024),
                         "r"(k[4 * J + i])
                         : "memory");
        exp_block<J + 1>(s, k, pa, mref);
    }
}
__device__ __forceinline__ void sum_block(const uint32_t (&k)[40], float (&l)[10], uint32_t lane) {
    const bool b4 = lane & 16, b3 = lane & 8;
    uint32_t ps[20], t[10];
#pragma unroll
    for (int j = 0; j < 20; j++) ps[j] = add_bf2(k[2 * j], k[2 * j + 1]);
#pragma unroll
    for (int j = 0; j < 10; j++)
        t[j] = add_bf2(b4 ? ps[2 * j + 1] : ps[2 * j], __shfl_xor_sync(0xffffffffu, b4 ? ps[2 * j] : ps[2 * j + 1], 16));
#pragma unroll
    for (int i = 0; i < 5; i++) {
        const uint32_t a = b3 ? t[i + 5] : t[i], b = __shfl_xor_sync(0xffffffffu, b3 ? t[i] : t[i + 5], 8);
        l[2 * i] += __uint_as_float(a << 16) + __uint_as_float(b << 16);
        l[2 * i + 1] += __uint_as_float(a & 0xffff0000u) + __uint_as_float(b & 0xffff0000u);
    }
}
template <bool ADD>
__device__ __forceinline__ void sum_store(const float (&l)[10], uint32_t lane, uint32_t lxa) {
    const bool b2 = lane & 4;
    float t[5];
#pragma unroll
    for (int i = 0; i < 5; i++) t[i] = ADD ? __uint_as_float(lds_u(lxa + i * 64)) : 0.f;
#pragma unroll
    for (int i = 0; i < 5; i++)
        sts_f(lxa + i * 64, t[i] + (b2 ? l[2 * i + 1] : l[2 * i]) + __shfl_xor_sync(0xffffffffu, b2 ? l[2 * i] : l[2 * i + 1], 4));
}

__device__ __forceinline__ void fallback_unit(const Params& P, uint32_t e, uint32_t tid) {
    const uint32_t lane = tid & 31, br = IT_BR(e), b = IT_B(e), h = IT_H0(e);
    const __nv_bfloat162* wq = (const __nv_bfloat162*)(P.pwq[br] + h * 192) + lane;
    const __nv_bfloat162* kp = (const __nv_bfloat162*)(P.pk[br] + (size_t)(b * 32 + h) * 512 * 192) + lane;
    const __nv_bfloat162* vp = (const __nv_bfloat162*)(P.pv[br] + (size_t)(b * 32 + h) * 512 * 192) + lane;
#pragma unroll 1
    for (uint32_t qi = 0; qi < 40; qi++) {
        const uint32_t q = 4 * qi + (tid >> 5);
        const __nv_bfloat16* xr = P.px[br] + (size_t)(b * 160 + q) * 640;
        float a[6] = {0.f, 0.f, 0.f, 0.f, 0.f, 0.f};
#pragma unroll 2
        for (int k = 0; k < 640; k++) {
            const float xv = __bfloat162float(xr[k]);
#pragma unroll
            for (int i = 0; i < 3; i++) {
                const float2 wv = __bfloat1622float2(wq[(size_t)k * 3072 + i * 32]);
                a[2 * i] = fmaf(xv, wv.x, a[2 * i]);
                a[2 * i + 1] = fmaf(xv, wv.y, a[2 * i + 1]);
            }
        }
#pragma unroll
        for (int i = 0; i < 6; i++) a[i] = __bfloat162float(__float2bfloat16(a[i]));
        auto score = [&](int key) {
            float d = 0.f;
#pragma unroll
            for (int i = 0; i < 3; i++) {
                const float2 kv = __bfloat1622float2(kp[key * 96 + i * 32]);
                d = fmaf(a[2 * i], kv.x, fmaf(a[2 * i + 1], kv.y, d));
            }
#pragma unroll
            for (int o = 16; o > 0; o >>= 1) d += __shfl_xor_sync(0xffffffffu, d, o);
            return d;
        };
        float m = -INFINITY, o[6] = {0.f, 0.f, 0.f, 0.f, 0.f, 0.f}, sum = 0.f;
#pragma unroll 1
        for (int n = 0; n < 1024; n++) {
            const int key = n & 511;
            const float d = score(key);
            if (n < 512) {
                m = fmaxf(m, d);
            } else {
                const float p = ex2((d - m) * SM_C);
                sum += p;
#pragma unroll
                for (int i = 0; i < 3; i++) {
                    const float2 vv = __bfloat1622float2(vp[key * 96 + i * 32]);
                    o[2 * i] = fmaf(p, vv.x, o[2 * i]);
                    o[2 * i + 1] = fmaf(p, vv.y, o[2 * i + 1]);
                }
            }
        }
        const float inv = __fdividef(1.f, sum);
        __nv_bfloat16* op = (__nv_bfloat16*)ostash(IT_SLOT(e), b) + (q >> 5) * 256 + 2 * ((q & 31) >> 3) + (q & 1);
#pragma unroll
        for (int i = 0; i < 6; i++) {
            const uint32_t d = (i >> 1) * 64 + 2 * lane + (i & 1);
            op[(d >> 3) * 1280 + (d & 7) * 32 + ((((q & 7) >> 1) ^ ((d & 7) >> 1)) << 3)] = __float2bfloat16(o[i] * inv);
        }
    }
}

template <int W>
struct PendO {
    static constexpr int N = W == 0 ? 56 : 64;
    uint32_t v[N];
    unsigned char* gp;
    static __device__ __forceinline__ uint32_t toff() {
        const uint32_t t = tid_now();
        return ((t >> 5) & 3) * 5120 + ((t >> 2) & 7) * 64 + (((t ^ (t >> 3)) & 3) << 4);
    }
    uint32_t pend, sig;
    static __device__ __forceinline__ void scale(uint32_t& x, uint32_t hi, uint32_t lo) {
        asm("{\n.reg .b32 t;\nmul.rn.bf16x2 t, %0, %2;\nfma.rn.bf16x2 %0, %0, %1, t;\n}" : "+r"(x) : "r"(hi), "r"(lo));
    }
    template <int I, int OFF>
    __device__ __forceinline__ void put() {
        asm volatile("{\n.reg .pred p;\nsetp.ne.u32 p, %6, 0;\n@p st.global.v4.b32 [%0+%5], {%1,%2,%3,%4};\n}" ::"l"(gp), "r"(v[I]),
                     "r"(v[I + 1]), "r"(v[I + 2]), "r"(v[I + 3]), "n"(OFF), "r"(pend)
                     : "memory");
    }
    __device__ __forceinline__ void verdict(const Params& P, uint32_t sb, int ie) {
        if (sig) {
            nb_sync<NB_VOTE + W, 160>();
            pend = !__any_sync(0xffffffffu, lds_u(sb + OFF_FB) != 0);
            if (W == 1 && !pend) {
                fallback_unit(P, lds_u(sb + OFF_ITEM + ie * 4), tid_now() & 127);
                __syncwarp();
            }
        }
    }
    template <int G, int H>
    __device__ __forceinline__ void half(uint32_t sb) {
        constexpr bool T2 = W == 0 ? G >= 3 : G < 3;
        constexpr int B = T2 ? 40 + 8 * (W == 0 ? G - 3 : G) : 0;
        const uint4 a = lds_u4(sb + OFF_LINV + G * 128 + H * 16 + (threadIdx.x & 3) * 32);
#pragma unroll
        for (int i = 2 * H; i < 8; i += 4) {
            scale(v[8 * G + i], a.x, a.y);
            scale(v[8 * G + i + 1], a.z, a.w);
            if (T2) {
                scale(v[B + i], a.x, a.y);
                scale(v[B + i + 1], a.z, a.w);
            }
        }
        if (H == 1) {
            put<8 * G, W * XS + G * 512>();
            put<8 * G + 4, W * XS + G * 512 + 2560>();
            if (T2) {
                put<B, 2 * XS + G * 512>();
                put<B + 4, 2 * XS + G * 512 + 2560>();
            }
            if (G == 4 && sig) nb_arrive<NB_ODONE, 288>();
        }
    }
    template <int G>
    __device__ __forceinline__ void step(uint32_t sb) {
        half<G, 0>(sb);
        half<G, 1>(sb);
    }
    __device__ __forceinline__ void clear() {
#pragma unroll
        for (int i = 0; i < N; i++) v[i] = 0;
        gp = nullptr;
        pend = 0;
        sig = 0;
    }
};

template <int W, int KK>
__device__ __forceinline__ void qproj(float (&q0)[80], float (&q1)[80], uint32_t sb, Ring& r, uint32_t pslot, uint32_t phm,
                                      PendO<W>& po, const Params& P, int it) {
    const uint32_t loR = (((sb + OFF_R) & 0x3ffff) >> 4) | LO_LBO1;
    const uint32_t loRing = (((sb + OFF_RING) & 0x3ffff) >> 4) | LO_LBO1;
    auto ready = [&](int k) {
        mbar_wait(sb + BAR_RFULL + r.slot * 8, r.ph, r.dl);
        mbar_wait(sb + BAR_XFULL + (k % 5) * 8, ((phm >> (k % 5)) ^ (k / 5)) & 1, r.dl);
    };
    auto release = [&]() {
        if (KK > 0) {
            wg_wait<1>();
            mbar_arrive_warp(sb + BAR_REMPTY + pslot * 8);
            if (KK <= 5) mbar_arrive_warp(sb + (BAR_XEMPTY + (KK - 1) * 8));
        }
    };
    if (KK == 0) ready(0);
    if (W == 1 && KK == QHOLD) nb_sync<NB_SDONE, 256>();
    const uint32_t a = loRing + r.slot * (SLOT >> 4) + (W == 0 ? 0 : 512), b = loR + (KK % 5) * (XS >> 4);
    wg_fence();
    wgmma<1, 0, HI_SW128, KK != 0>(q0, a, b);
    if (W == 0) wgmma<1, 0, HI_SW128, KK != 0>(q1, a + 256, b);
#pragma unroll
    for (int k = 1; k < 4; k++) {
        wgmma<1, 0, HI_SW128, true>(q0, a + (k >> 1) * 768 + (k & 1) * 128, b + k * 2);
        if (W == 0) wgmma<1, 0, HI_SW128, true>(q1, a + 256 + (k >> 1) * 768 + (k & 1) * 128, b + k * 2);
    }
    wg_commit();
    const uint32_t cslot = r.slot;
    r.adv(1);
    if (W == 0 || KK < QHOLD) release();
    if (KK == QST0) {
        po.verdict(P, sb, it - 1);
        po.template half<0, 0>(sb);
    }
    if (KK < 9) ready(KK + 1);
    if (W == 1 && KK >= QHOLD) release();
    if (W == 1 && KK == 7) nb_arrive<NB_PDONE, 256>();
    if (KK == QST0) po.template half<0, 1>(sb);
    if constexpr (KK > QST0 && KK < QST0 + 5) po.template step<KK - QST0>(sb);
    if constexpr (KK < 9) {
        qproj<W, KK + 1>(q0, q1, sb, r, cslot, phm, po, P, it);
    } else {
        if (W == 0) nb_arrive<NB_SDONE, 256>();
        wg_wait<0>();
        reg_fence(q0);
        if (W == 0) reg_fence(q1);
        mbar_arrive_warp(sb + BAR_REMPTY + cslot * 8);
    }
}

template <int NR>
__device__ __forceinline__ void opack(const float (&o)[NR], uint32_t* v) {
#pragma unroll
    for (int g = 0; g < NR / 16; g++)
#pragma unroll
        for (int hh = 0; hh < 2; hh++)
#pragma unroll
            for (int t = 0; t < 4; t++) v[8 * g + 4 * hh + t] = pack_bf16(o[16 * g + 4 * t + 2 * hh], o[16 * g + 4 * t + 2 * hh + 1]);
}

template <bool IS_S>
__device__ __forceinline__ void op_item(uint32_t e, uint32_t sb, Ring& r, uint32_t& phm) {
    constexpr int T0 = IS_S ? 0 : 2;
    constexpr uint32_t BOFF = IS_S ? (3 * 512) >> 4 : 0;
    const uint32_t loRing = (((sb + OFF_RING) & 0x3ffff) >> 4) | LO_LBO1;
    const uint32_t loO = (((sb + OFF_R) & 0x3ffff) >> 4) | LO_OST;
    float c0[80], c1[80], c2[IS_S ? 32 : 48];
    const int T2 = 6 * (IT_H1(e) - IT_H0(e));
    uint32_t xs = 0;
    auto step = [&](auto first, uint32_t hf) {
        constexpr bool F = decltype(first)::value;
        if (hf == 0) {
            mbar_wait(sb + BAR_XFULL + xs * 8, (phm >> xs) & 1, r.dl);
            phm ^= 1u << xs;
        }
        mbar_wait(sb + BAR_RFULL + r.slot * 8, r.ph, r.dl);
        const uint32_t a = loRing + r.slot * (SLOT >> 4), b = loO + xs * (XS >> 4) + hf * 640;
        wg_fence();
        wgmma<1, 1, HI_OST, !F>(c0, a + T0 * 128, b);
        wgmma<1, 1, HI_OST, !F>(c1, a + T0 * 128 + 128, b);
        wgmma<1, 1, HI_OST, !F>(c2, a + 512, b + BOFF);
        wgmma<1, 1, HI_OST, true>(c0, a + 640 + T0 * 128, b + 320);
        wgmma<1, 1, HI_OST, true>(c1, a + 640 + T0 * 128 + 128, b + 320);
        wgmma<1, 1, HI_OST, true>(c2, a + 640 + 512, b + 320 + BOFF);
        wg_commit();
    };
    step(TrueT{}, 0);
#pragma unroll 1
    for (int t = 1; t < T2; t++) {
        const uint32_t pslot = r.slot, pxs = xs;
        r.adv(1);
        if ((t & 1) == 0 && ++xs == 5) xs = 0;
        step(FalseT{}, t & 1);
        wg_wait<1>();
        mbar_arrive_warp(sb + BAR_REMPTY + pslot * 8);
        if ((t & 1) == 0 && t + 8 < T2) mbar_arrive_warp(sb + BAR_XEMPTY + pxs * 8);
    }
    wg_wait<0>();
    reg_fence(c0);
    reg_fence(c1);
    reg_fence(c2);
    mbar_arrive_warp(sb + BAR_REMPTY + r.slot * 8);
    r.adv(1);
    nb_sync<NB_OPEND, 256>();
    const uint32_t tid = tid_now(), lane = tid & 31, w = (tid >> 5) & 3;
    store_out_tile<false>(c0, sb + OFF_R + T0 * XS, lane, w);
    store_out_tile<false>(c1, sb + OFF_R + (T0 + 1) * XS, lane, w);
    store_out_tile<false>(c2, sb + OFF_R + 4 * XS + (IS_S ? 96 * 128 : 0), lane, w);
    fence_async_smem();
    nb_arrive<NB_ODONE, 288>();
}

template <int W>
__device__ __forceinline__ void on_item(uint32_t e, uint32_t sb, Ring& r, uint32_t& phm) {
    const uint32_t loRing = (((sb + OFF_RING) & 0x3ffff) >> 4) | LO_LBO1;
    const uint32_t loO = (((sb + OFF_R) & 0x3ffff) >> 4) | LO_OST;
    float c[80];
    const int T = 3 * (IT_H1(e) - IT_H0(e));
    uint32_t xs = 0;
    auto step = [&](auto first) {
        constexpr bool F = decltype(first)::value;
        mbar_wait(sb + BAR_XFULL + xs * 8, (phm >> xs) & 1, r.dl);
        phm ^= 1u << xs;
        mbar_wait(sb + BAR_RFULL + r.slot * 8, r.ph, r.dl);
        const uint32_t a = loRing + r.slot * (SLOT >> 4) + W * 256, b = loO + xs * (XS >> 4);
        wg_fence();
        wgmma<1, 1, HI_OST, !F>(c, a, b);
#pragma unroll
        for (int k = 1; k < 4; k++) wgmma<1, 1, HI_OST, true>(c, a + (k >> 1) * 512 + (k & 1) * 128, b + k * 320);
        wg_commit();
    };
    step(TrueT{});
#pragma unroll 1
    for (int t = 1; t < T; t++) {
        const uint32_t pslot = r.slot, pxs = xs;
        r.adv(1);
        if (++xs == 5) xs = 0;
        step(FalseT{});
        wg_wait<1>();
        mbar_arrive_warp(sb + BAR_REMPTY + pslot * 8);
        mbar_arrive_warp_if(sb + BAR_XEMPTY + pxs * 8, t + 2 < T);
    }
    xs += 1 + W;
    if (xs >= 5) xs -= 5;
    mbar_wait(sb + BAR_XFULL + xs * 8, (phm >> xs) & 1, r.dl);
    wg_wait<0>();
    reg_fence(c);
    const uint32_t tid = tid_now();
    store_out_tile<true>(c, sb + OFF_R + xs * XS, tid & 31, (tid >> 5) & 3);
    fence_async_smem();
    nb_arrive<NB_ODONE, 288>();
}

template <int W>
__device__ __forceinline__ uint32_t qa_item(const Params& P, uint32_t e, uint32_t sb, Ring& r, uint32_t phm, PendO<W>& po, int it) {
    const uint32_t loR = (((sb + OFF_R) & 0x3ffff) >> 4) | LO_LBO1;
    const uint32_t loRing = (((sb + OFF_RING) & 0x3ffff) >> 4) | LO_LBO1;
    uint32_t lane, sta;
    {
        float q0[80], q1[80];
        qproj<W, 0>(q0, q1, sb, r, 0, phm, po, P, it);
        const uint32_t tid = tid_now();
        lane = tid & 31;
        sta = sb + OFF_R + (lane >> 4) * 1024 + (lane & 7) * 128 + (((((tid >> 4) & 6) + ((lane >> 3) & 1)) ^ (lane & 7)) << 4);
        TSD(W, 1);
        if (W == 0) {
            nb_sync<NB_PDONE, 256>();
            store_tile_t(q0, sta);
            store_tile_t(q1, sta + XS);
        } else {
            store_tile_t(q0, sta + 2 * XS);
        }
    }
    fence_async_smem();
    float s[80], oa[80], ob[W == 0 ? 32 : 48], l[10];
    zero(oa);
    zero(ob);
    zero(l);
    reg_fence(oa);
    reg_fence(ob);
    auto pv = [&](const Ring& rv, uint32_t buf) {
        mbar_wait(sb + BAR_RFULL + rv.slot * 8, rv.ph, rv.dl);
        const uint32_t a = loRing + rv.slot * (SLOT >> 4), b = loR + (3 + buf) * (XS >> 4);
        wg_fence();
#pragma unroll
        for (int k = 0; k < 4; k++) {
            wgmma<1, 0, HI_SW128, true>(oa, a + W * 512 + k * 128, b + k * 2);
            wgmma<1, 0, HI_SW128, true>(ob, a + 1024 + k * 128, b + (W == 0 ? (96 * 128) >> 4 : 0) + k * 2);
        }
        wg_commit();
    };
    float mref;
    uint32_t kslot, vslot;
    auto tail = [&](bool rel_other, int i) {
        uint32_t ps[40];
        exp_block<0>(s, ps, sta + (3 + W) * XS, mref);
        if (rel_other) {
            wg_wait<0>();
            mbar_arrive_warp(sb + BAR_REMPTY + vslot * 8);
            if (W == 1) mbar_arrive_warp_if(sb + BAR_XEMPTY + 24, i == 3);
        }
        fence_async_smem();
        nb_arrive<NB_PFULL + W, 256>();
        TSD(W, 6 + 5 * i);
        if (W == 1) {
            if (XLATE >= 2) mbar_arrive_warp_if<2>(sb + BAR_XEMPTY + 8, i == 3);
            if (XLATE >= 1) mbar_arrive_warp_if<2>(sb + BAR_XEMPTY + 16, i == 3);
        }
        if (rel_other || !PV0FIRST) {
            mbar_wait(sb + BAR_RFULL + r.slot * 8, r.ph, r.dl);
            sum_block(ps, l, lane);
        }
        TSD(W, 7 + 5 * i);
        nb_sync<NB_W + W, 128>();
        pv(r, W);
        if (!rel_other && PV0FIRST) sum_block(ps, l, lane);
        TSD(W, 8 + 5 * i);
    };
    if (W == 0) {
        sts_u(sb + OFF_GM + 4, r.slot);
        mbar_wait(sb + BAR_RFULL + r.slot * 8, r.ph, r.dl);
        nb_sync<NB_QK, 160>();
        TSD(W, 2);
        wg_fence();
        qk_steps<0, 8>(s, loRing + r.slot * (SLOT >> 4), loR);
        nb_sync<NB_Q2, 288>();
        qk_steps<8, 12>(s, loRing + r.slot * (SLOT >> 4), loR);
        wg_commit();
        nb_arrive<NB_Q01, 256>();
        TSD(W, 4);
        nb_sync<NB_REF, 160>();
        mref = __uint_as_float(lds_u(sb + OFF_GM));
        wg_wait<0>();
        reg_fence(s);
        mbar_arrive_warp<2>(sb + BAR_REMPTY + r.slot * 8);
        r.adv(2);
        TSD(W, 5);
        tail(false, 0);
    } else {
        nb_arrive<NB_Q2, 288>();
        TSD(W, 2);
        nb_sync<NB_Q01, 256>();
    }
#pragma unroll 1
    for (int i = (W == 0 ? 1 : 0); i < 4; i++) {
        const uint32_t pvslot = r.slot;
        r.adv(1);
        kslot = r.slot;
        mbar_wait(sb + BAR_RFULL + r.slot * 8, r.ph, r.dl);
        wg_fence();
        qk_steps<0, 12>(s, loRing + r.slot * (SLOT >> 4), loR);
        wg_commit();
        wg_wait<1>();
        mbar_arrive_warp_if(sb + BAR_REMPTY + pvslot * 8, W == 0 || i > 0);
        r.adv(1);
        vslot = r.slot;
        TSD(W, 4 + 5 * i);
        nb_sync<NB_PFULL + (W ^ 1), 256>();
        pv(r, W ^ 1);
        if (W == 1) mref = __uint_as_float(lds_u(sb + OFF_GM));
        wg_wait<1>();
        reg_fence(s);
        mbar_arrive_warp<2>(sb + BAR_REMPTY + kslot * 8);
        if (W == 1) {
            mbar_arrive_warp_if<2>(sb + BAR_XEMPTY + 0, i == 3);
            if (XLATE < 2) mbar_arrive_warp_if<2>(sb + BAR_XEMPTY + 8, i == 3);
            if (XLATE < 1) mbar_arrive_warp_if<2>(sb + BAR_XEMPTY + 16, i == 3);
        }
        r.adv(W == 1 && i == 3 ? 1 : 2);
        TSD(W, 5 + 5 * i);
        tail(true, i);
    }
    const uint32_t w = (tid_now() >> 5) & 3;
    const uint32_t lxa = sb + OFF_LX + w * 640 + (((lane & 8) ? 80 : 0) + ((lane >> 1) & 8) + 2 * (lane & 3) + ((lane >> 2) & 1)) * 4;
    const uint32_t nx = get_item_warp(sb, it + 1, r.dl);
    po.gp = ostash(IT_SLOT(e), IT_B(e)) + po.toff();
    po.sig = 1;
    if (W == 0) {
        sum_store<false>(l, lane, lxa);
        nb_arrive<NB_LX, 256>();
        wg_wait<0>();
        mbar_arrive_warp(sb + BAR_REMPTY + r.slot * 8);
        mbar_arrive_warp(sb + BAR_XEMPTY + 24);
        r.adv(1);
        nb_sync<NB_PFULL + 1, 256>();
        pv(r, 1);
    } else {
        nb_sync<NB_LX, 256>();
        sum_store<true>(l, lane, lxa);
        nb_arrive<NB_L, 160>();
    }
    TSD(W, 24);
    wg_wait<0>();
    reg_fence(oa);
    reg_fence(ob);
    mbar_arrive_warp(sb + BAR_REMPTY + r.slot * 8);
    mbar_arrive_warp(sb + BAR_XEMPTY + 32);
    r.adv(1);
    opack(ob, po.v + 40);
    opack(oa, po.v);
    return nx;
}

template <int W>
__device__ __forceinline__ void consumer(const Params& P, uint32_t sb, uint32_t dl) {
    int it = 0;
    if (W == 0) TS(0, 30);
    Ring r{0, 0, dl};
    uint32_t phm = 0;
    uint32_t e = get_item_warp(sb, 0, dl);
#pragma unroll 1
    while (e != 0) {
        if (IT_TYPE(e) == IT_QA) {
            PendO<W> po;
            po.clear();
#pragma unroll 1
            do {
                TS(W, 0);
                if (W == 0) TS_ITEM(e);
                e = qa_item<W>(P, e, sb, r, phm, po, it);
                TS(W, 31);
                it++;
            } while (IT_TYPE(e) == IT_QA);
            po.verdict(P, sb, it - 1);
            po.template step<0>(sb);
            po.template step<1>(sb);
            po.template step<2>(sb);
            po.template step<3>(sb);
            po.template step<4>(sb);
        } else {
            TS(W, 0);
            if (W == 0) TS_ITEM(e);
            if (IT_TYPE(e) == IT_OP) op_item<W == 0>(e, sb, r, phm);
            else on_item<W>(e, sb, r, phm);
            TS(W, 31);
            e = get_item_warp(sb, ++it, dl);
        }
    }
    TS_DUMP(W);
}

__global__ void __cluster_dims__(2, 1, 1) __launch_bounds__(384, 1) fused_kernel(const __grid_constant__ Params P) {
    extern __shared__ __align__(1024) unsigned char smem_raw[];
    const uint32_t sb = (uint32_t)__cvta_generic_to_shared(smem_raw);
    const uint32_t wgid = __shfl_sync(0xffffffffu, threadIdx.x >> 7, 0);
    const uint32_t cta = blockIdx.x;
    const uint32_t dl = deadline();

    if (threadIdx.x == 128) {
#pragma unroll
        for (int i = 0; i < NSLOT; i++) {
            mbar_init(sb + BAR_RFULL + i * 8, 1);
            mbar_init(sb + BAR_REMPTY + i * 8, 8);
            mbar_init(sb + BAR_XFULL + i * 8, 1);
            mbar_init(sb + BAR_XEMPTY + i * 8, 8);
        }
        asm volatile("fence.mbarrier_init.release.cluster;" ::: "memory");
        fence_async_smem();
    } else if (threadIdx.x == 160) {
#pragma unroll
        for (int i = 0; i < NSLOT + MAXI; i++) mbar_init(sb + BAR_PRDY + i * 8, 1);
        asm volatile("fence.mbarrier_init.release.cluster;" ::: "memory");
    } else if (threadIdx.x == 0) {
        sts_u(sb + OFF_ITEM, P.cl[cta >> 1].items[0] ? P.cl[cta >> 1].items[0] + 8 * (cta & 1) : 0);
    } else if (threadIdx.x == 64) {
        if (sb & 1023) __trap();
        asm volatile("prefetch.tensormap [%0];" ::"l"(&P.wq[0]) : "memory");
        asm volatile("prefetch.tensormap [%0];" ::"l"(&P.x[0]) : "memory");
    }
    __syncthreads();
    asm volatile("barrier.cluster.arrive.relaxed.aligned;" ::: "memory");

    if (wgid == 0) {
        asm volatile("setmaxnreg.dec.sync.aligned.u32 24;");
        const uint32_t warp = __shfl_sync(0xffffffffu, threadIdx.x >> 5, 0);
        if (warp == 0) {
            const uint64_t pol_norm = mkpol<POL_W>();
            uint32_t e = lds_u(sb + OFF_ITEM);
            if (threadIdx.x == 0) {
                const uint32_t d = P.cl[cta >> 1].delay;
                uint32_t t0, t1;
                asm volatile("mov.u32 %0, %%clock;" : "=r"(t0));
                do {
                    asm volatile("mov.u32 %0, %%clock;" : "=r"(t1));
                } while (t1 - t0 < d);
                asm volatile("mbarrier.arrive.shared::cta.b64 _, [%0];" ::"r"(sb + BAR_ITEM) : "memory");
#pragma unroll 1
                for (int n = 0; n < (e ? 2 * NSLOT : 0); n++) {
                    if (!(n & 1)) mbar_expect(sb + BAR_RFULL + (n >> 1) * 8, SLOT);
                    tma3(sb + OFF_RING + n * (SLOT / 2), &P.wq[IT_BR(e)], n * 32, IT_H0(e) * 3, sb + BAR_RFULL + (n >> 1) * 8, pol_norm);
                }
            }
            __syncwarp();
            asm volatile("barrier.cluster.wait.aligned;" ::: "memory");
            if (threadIdx.x == 0) {
                const uint32_t epoch = next_epoch(0);
                const uint64_t pol_first = mkpol<1>();
                const uint32_t rank = cta & 1;
                uint32_t peer;
                asm volatile("mapa.shared::cluster.u32 %0, %1, %2;" : "=r"(peer) : "r"(sb), "r"(rank ^ 1));
                Ring r{0, 0, dl};
                uint32_t pm = 0;
                auto load_w = [&](const CUtensorMap* m, int row, int blk, uint32_t half_bytes) {
                    mbar_wait(sb + BAR_REMPTY + r.slot * 8, r.ph, dl);
                    mbar_expect(sb + BAR_RFULL + r.slot * 8, 2 * half_bytes);
                    asm volatile("mbarrier.arrive.shared::cluster.b64 _, [%0];" ::"r"(peer + BAR_PRDY + r.slot * 8) : "memory");
                    mbar_wait(sb + BAR_PRDY + r.slot * 8, (pm >> r.slot) & 1, dl);
                    pm ^= 1u << r.slot;
                    tma3_mc(sb + OFF_RING + r.slot * SLOT + rank * half_bytes, m, row, blk, sb + BAR_RFULL + r.slot * 8, pol_norm);
                    r.adv(1);
                };
#pragma unroll 1
                for (int it = 0;; it++) {
                    uint32_t nx = 0, tk = 0;
                    if (rank == 0) {
                        if (it > 0) {
                            asm volatile("st.async.weak.shared::cluster.mbarrier::complete_tx::bytes.b32 [%0], %1, [%2];" ::"r"(
                                             peer + OFF_ITEM + it * 4),
                                         "r"(e ? e + 8 : 0), "r"(peer + BAR_ITEM + it * 8)
                                         : "memory");
                            sts_u(sb + OFF_ITEM + it * 4, e);
                            asm volatile("mbarrier.arrive.shared::cta.b64 _, [%0];" ::"r"(sb + BAR_ITEM + it * 8) : "memory");
                        }
                        if (IT_TYPE(e) != IT_ON && it + 2 < MAXI) nx = it + 1 < NSTAT ? P.cl[cta >> 1].items[it + 1] : IT_DYN;
                    } else if (it > 0) {
                        mbar_expect(sb + BAR_ITEM + it * 8, 4);
                        e = get_item(sb, it, dl);
                    }
                    if (e == 0) break;
                    const uint32_t br = IT_BR(e);
                    if (IT_TYPE(e) == IT_QA) {
                        const uint32_t h = IT_H0(e);
#pragma unroll 1
                        for (int kk = it ? 0 : NSLOT; kk < 10; kk++) load_w(&P.wq[br], kk * 64 + rank * 32, h * 3, SLOT / 2);
                        const int row0 = (IT_B(e) * 32 + h) * 512;
#pragma unroll 1
                        for (int n = 0; n < 16; n++) {
                            if (n == 13 && nx == IT_DYN) tk = atomicAdd(&g_ticket[epoch & 1], 1);
                            const bool isv = n == 15 || (n > 0 && !(n & 1));
                            const int j = n == 15 ? 7 : isv ? (n - 2) >> 1 : (n + 1) >> 1;
                            mbar_wait(sb + BAR_REMPTY + r.slot * 8, r.ph, dl);
                            mbar_expect(sb + BAR_RFULL + r.slot * 8, SLOT);
                            tma3(sb + OFF_RING + r.slot * SLOT, isv ? &P.v[br] : &P.k[br], row0 + j * 64, 0,
                                 sb + BAR_RFULL + r.slot * 8, pol_first);
                            r.adv(1);
                        }
                    } else {
                        const bool wide = IT_TYPE(e) == IT_OP;
                        const int step = wide ? 32 : 64, r1 = IT_H1(e) * 192;
#pragma unroll 1
                        for (int row = IT_H0(e) * 192 + rank * (step >> 1); row < r1; row += step)
                            load_w(wide ? &P.wo[br] : &P.won[br], row, IT_HALF(e) * (wide ? 5 : 2), wide ? XS / 2 : 8192);
                        if (nx == IT_DYN) tk = atomicAdd(&g_ticket[epoch & 1], 1);
                    }
                    if (nx == IT_DYN) nx = tk < P.nlist ? P.list[tk] : 0;
                    e = nx;
                }
            }
        } else if (warp == 1) {
            const uint64_t pol_norm = mkpol<POL_X>(), pol_o = mkpol<POL_O>();
            const bool lead = threadIdx.x == 32;
            uint32_t phm = 0x1f, epoch = 0;
#pragma unroll 1
            for (int it = 0;; it++) {
                const uint32_t e = get_item_warp(sb, it, dl);
                if (it == 1 || (it == 0 && e == 0)) epoch = next_epoch(1);
                if (e == 0) break;
                const uint32_t br = IT_BR(e);
                uint32_t xs = 0;
                auto acquire = [&]() {
                    mbar_wait(sb + BAR_XEMPTY + xs * 8, (phm >> xs) & 1, dl);
                    phm ^= 1u << xs;
                    if (lead) mbar_expect(sb + BAR_XFULL + xs * 8, XS);
                };
                if (IT_TYPE(e) == IT_QA) {
#pragma unroll 1
                    for (int kk = 0; kk < 10; kk++) {
                        acquire();
                        if (lead) tma3(sb + OFF_R + xs * XS, &P.x[br], IT_B(e) * 160, kk, sb + BAR_XFULL + xs * 8, pol_norm);
                        if (++xs == 5) xs = 0;
                    }
                } else {
                    const unsigned int* fp = g_flag + (br * 16 + IT_B(e)) * 64 + (threadIdx.x & 31);
                    uint32_t hm = 0, pm = 0;
                    auto poll = [&](uint32_t hneed, uint32_t pneed) {
                        if ((hm & hneed) == hneed && (pm & pneed) == pneed) return;
                        uint32_t n = 0;
                        do {
                            uint32_t a, b;
                            asm volatile("ld.acquire.gpu.global.u32 %0, [%2];\nld.acquire.gpu.global.u32 %1, [%2+128];"
                                         : "=r"(a), "=r"(b) : "l"(fp) : "memory");
                            hm = __ballot_sync(0xffffffffu, a == epoch);
                            pm = __ballot_sync(0xffffffffu, b == epoch);
                            if (++n > 0x1000000) __trap();
                        } while ((hm & hneed) != hneed || (pm & pneed) != pneed);
                        __syncwarp();
                        asm volatile("fence.proxy.async;" ::: "memory");
                    };
#pragma unroll 1
                    for (uint32_t h = IT_H0(e); h < IT_H1(e); h++) {
                        poll(1u << h, 0);
                        const unsigned char* src = ostash(P.slot[br * 32 + h], IT_B(e));
#pragma unroll 1
                        for (int t = 0; t < 3; t++) {
                            acquire();
                            if (lead) bulk_load(sb + OFF_R + xs * XS, src + t * XS, XS, sb + BAR_XFULL + xs * 8, pol_o);
                            if (++xs == 5) xs = 0;
                        }
                        if (IT_TYPE(e) == IT_OP && h >= 1) {
                            const uint32_t x1 = xs == 4 ? 0 : xs + 1;
                            mbar_wait(sb + BAR_XFULL + xs * 8, (phm >> xs) & 1, dl);
                            mbar_wait(sb + BAR_XFULL + x1 * 8, (phm >> x1) & 1, dl);
                            if (lead)
                                asm volatile("st.relaxed.gpu.global.u32 [%0], %1;" ::"l"(fp + 34 + IT_HALF(e)), "r"(epoch * 64 + h) : "memory");
                        }
                    }
                    if (IT_TYPE(e) == IT_ON) {
                        poll(0, IT_HALF(e) < 2 ? 1 : IT_HALF(e) == 2 ? 3 : 2);
#pragma unroll 1
                        for (uint32_t tile = 2 * IT_HALF(e); tile < 2 * IT_HALF(e) + 2; tile++) {
                            acquire();
                            if (lead)
                                asm volatile(
                                    "cp.async.bulk.tensor.2d.shared::cluster.global.mbarrier::complete_tx::bytes [%0], [%1, {%3,%4}], [%2];" ::"r"(
                                        sb + OFF_R + xs * XS),
                                    "l"(&P.out), "r"(sb + BAR_XFULL + xs * 8), "r"(br * 640 + tile * 64), "r"(IT_B(e) * 160)
                                    : "memory");
                            if (++xs == 5) xs = 0;
                        }
                    }
                }
            }
        } else if (warp == 2) {
            asm volatile("barrier.cluster.wait.aligned;" ::: "memory");
            const uint32_t epoch = next_epoch(2);
            if (cta == 0) g_ticket[(epoch + 1) & 1] = 0;
#pragma unroll 1
            for (int it = 0;; it++) {
                const uint32_t e = get_item_warp(sb, it, dl);
                if (e == 0) break;
                nb_sync<NB_ODONE, 288>();
                if (threadIdx.x == 64) {
                    const uint32_t bb = IT_BR(e) * 16 + IT_B(e);
                    if (IT_TYPE(e) != IT_QA) {
                        const bool wide = IT_TYPE(e) == IT_OP;
                        if (wide)
                            asm volatile("st.relaxed.gpu.global.u32 [%0], %1;" ::"l"(&g_flag[bb * 64 + 34 + IT_HALF(e)]),
                                         "r"(epoch * 64 + IT_H1(e))
                                         : "memory");
                        const int cc0 = IT_BR(e) * 640 + IT_HALF(e) * (wide ? 320 : 128);
                        uint32_t xs = wide ? 0 : (3 * (IT_H1(e) - IT_H0(e))) % 5;
#pragma unroll 1
                        for (int m = 0; m < (wide ? 5 : 2); m++) {
                            asm volatile("cp.async.bulk.tensor.2d.global.shared::cta.bulk_group [%0, {%2,%3}], [%1];" ::"l"(&P.out),
                                         "r"(sb + OFF_R + xs * XS), "r"(cc0 + m * 64), "r"((int)IT_B(e) * 160)
                                         : "memory");
                            asm volatile("cp.async.bulk.commit_group;" ::: "memory");
                            if (++xs == 5) xs = 0;
                        }
                        if (wide) {
#define REL(N)                                                          \
    asm volatile("cp.async.bulk.wait_group.read %0;" ::"n"(4 - N) : "memory"); \
    asm volatile("mbarrier.arrive.shared::cta.b64 _, [%0], 8;" ::"r"(sb + BAR_XEMPTY + N * 8) : "memory");
                            REL(0) REL(1) REL(2) REL(3) REL(4)
#undef REL
                        }
                        if (IT_PART(e)) {
                            asm volatile("cp.async.bulk.wait_group 0;" ::: "memory");
                            asm volatile("fence.proxy.async;" ::: "memory");
                        }
                    }
                    if (IT_TYPE(e) == IT_QA || IT_PART(e)) {
                        unsigned int* f = &g_flag[bb * 64 + (IT_TYPE(e) == IT_QA ? IT_H0(e) : 32 + IT_HALF(e))];
                        asm volatile("st.release.gpu.global.u32 [%0], %1;" ::"l"(f), "r"(epoch) : "memory");
                    }
                }
                __syncwarp();
            }
            if (threadIdx.x == 64) asm volatile("cp.async.bulk.wait_group 0;" ::: "memory");
            __syncwarp();
            asm volatile("barrier.cluster.arrive.relaxed.aligned;\nbarrier.cluster.wait.aligned;" ::: "memory");
        } else {
            const uint32_t lane = threadIdx.x & 31, p = lane >> 2;
            const uint32_t epoch = next_epoch(3);
#pragma unroll 1
            for (int it = 0;; it++) {
                const uint32_t e = get_item_warp(sb, it, dl);
                if (e == 0) break;
                if (IT_TYPE(e) != IT_QA) continue;
                nb_sync<NB_QK, 160>();
                const uint32_t co = (((lane & 3) * 2) ^ p) << 4;
                const uint32_t ka = sb + OFF_RING + lds_u(sb + OFF_GM + 4) * SLOT + p * (9 * 128) + co;
                const uint32_t qa = sb + OFF_R + p * (17 * 128) + co;
                uint32_t acc = 0;
#pragma unroll
                for (int c = 0; c < 6; c++) {
                    if (c == 4) nb_sync<NB_Q2, 288>();
                    const uint4 kv = lds_u4((ka + (c >> 1) * 8192) ^ ((c & 1) << 4));
                    const uint4 qv = lds_u4((qa + (c >> 1) * XS) ^ ((c & 1) << 4));
                    acc = fma_bf2(kv.x, qv.x, fma_bf2(kv.y, qv.y, fma_bf2(kv.z, qv.z, fma_bf2(kv.w, qv.w, acc))));
                }
                float d = __uint_as_float(acc << 16) + __uint_as_float(acc & 0xffff0000u);
                d += __shfl_xor_sync(0xffffffffu, d, 1);
                d += __shfl_xor_sync(0xffffffffu, d, 2);
                int key = __float_as_int(d);
                key ^= (key >> 31) & 0x7fffffff;
                key = __reduce_max_sync(0xffffffffu, key);
                key ^= (key >> 31) & 0x7fffffff;
                sts_f(sb + OFF_GM, __int_as_float(key) * SM_C);
                nb_arrive<NB_REF, 160>();
                if (IT_DEP(e)) {
                    const uint32_t g = IT_DEP(e) - 1, need = epoch * 64 + (g & 31) + 1;
                    const unsigned int* cp = &g_flag[((g >> 5) * 16 + IT_B(e)) * 64 + 34 + (lane & 1)];
                    for (uint32_t n = 0;; n++) {
                        uint32_t v;
                        asm volatile("ld.acquire.gpu.global.u32 %0, [%1];" : "=r"(v) : "l"(cp) : "memory");
                        if (__all_sync(0xffffffffu, v - need < 64)) break;
                        if (n > 0x800000) __trap();
                        __nanosleep(500);
                    }
                }
                nb_sync<NB_L, 160>();
                bool bad = false;
#pragma unroll
                for (int c = 0; c < 5; c++) {
                    const uint32_t la = sb + OFF_LX + (c * 32 + lane) * 4;
                    const float v = (__uint_as_float(lds_u(la)) + __uint_as_float(lds_u(la + 640))) +
                                    (__uint_as_float(lds_u(la + 1280)) + __uint_as_float(lds_u(la + 1920)));
                    const float inv = __fdividef(1.f, v);
                    const uint32_t hi = pack_bf16(inv, 0.f), lo = pack_bf16(inv - __uint_as_float(hi << 16), 0.f);
                    const uint32_t ia = sb + OFF_LINV + c * 128 + ((lane >> 1) & 3) * 32 + (lane >> 3) * 8 + (lane & 1) * 2;
                    asm volatile("st.shared.u16 [%0], %1;\nst.shared.u16 [%0+4], %2;" ::"r"(ia), "h"((unsigned short)hi), "h"((unsigned short)lo) : "memory");
                    bad |= !(v >= 5.421010862e-20f && v <= 1.8446744e19f);
                }
                sts_u(sb + OFF_FB, __any_sync(0xffffffffu, bad));
                nb_arrive<NB_VOTE, 160>();
                nb_arrive<NB_VOTE + 1, 160>();
            }
        }
    } else if (wgid == 1) {
        asm volatile("setmaxnreg.inc.sync.aligned.u32 240;");
        consumer<0>(P, sb, dl);
    } else {
        asm volatile("setmaxnreg.inc.sync.aligned.u32 240;");
        consumer<1>(P, sb, dl);
    }
}

typedef CUresult (*EncFn)(CUtensorMap*, CUtensorMapDataType, cuuint32_t, void*, const cuuint64_t*, const cuuint64_t*,
                          const cuuint32_t*, const cuuint32_t*, CUtensorMapInterleave, CUtensorMapSwizzle,
                          CUtensorMapL2promotion, CUtensorMapFloatOOBfill);

void make_map3(EncFn enc, CUtensorMap* m, void* p, uint64_t rows, uint64_t rowbytes, uint64_t nblk, uint32_t boxrows,
               uint32_t boxblk) {
    cuuint64_t dims[3] = {64, rows, nblk};
    cuuint64_t str[2] = {rowbytes, 128};
    cuuint32_t box[3] = {64, boxrows, boxblk};
    cuuint32_t es[3] = {1, 1, 1};
    enc(m, CU_TENSOR_MAP_DATA_TYPE_BFLOAT16, 3, p, dims, str, box, es, CU_TENSOR_MAP_INTERLEAVE_NONE,
        CU_TENSOR_MAP_SWIZZLE_128B, CU_TENSOR_MAP_L2_PROMOTION_NONE, CU_TENSOR_MAP_FLOAT_OOB_FILL_NONE);
}

constexpr int tune(const char*, int def) { return def; }

void build_schedule(Params& P) {
    const int mode = tune("MODE", 4), dmax = tune("DMAX", 24900), n0 = tune("N0", 6);
    const int H0[8] = {18, 17, 20, 21, 22, 23, 23, 24}, P0[8] = {383, 371, 344, 348, 354, 345, 348, 336};
    const int ng = tune("NG", 0), d0 = tune("D0", 0), nkeep = tune("NKEEP", 0), odmax = tune("ODMAX", 6000);
    const int ong = tune("ONG", 0), od0 = tune("OD0", 0), jit = tune("JIT", 0);
    const int npos = tune("NPOS", 0), nearly = tune("NEARLY", 0);
    const int ra = tune("RA", 10), ga = tune("GA", 32), rb = tune("RB", 12), g1 = tune("G1", 58);
    int dep[64];
    for (int g = 0, ns = 0, live = 0; g < 64; g++) {
        const bool fresh = mode < 3 || g >= g1 || live < (g < ga ? ra : rb);
        dep[g] = fresh ? 0 : g - live + 1;
        P.slot[g] = fresh ? ns++ : P.slot[g - live];
        live += fresh;
    }
    int u = 0;
    auto unit = [&]() {
        const uint32_t e = mk_item(IT_QA, u >> 8, (u & 7) * 2, (u >> 3) & 31, P.slot[u >> 3], 0) | (dep[u >> 3] << 23);
        u++;
        return e;
    };
    int qa[NCL], nq = 0, op[NCL], no = 0;
    for (int c = 0; c < NCL; c++) {
        P.cl[c].delay = 0;
        for (int i = 0; i < NSTAT; i++) P.cl[c].items[i] = 0;
        if (mode >= 3 && c < 64 && (c & 3) == 3) op[no++] = c;
        else if (mode != 2 || (c & 3) == 0) qa[nq++] = c;
    }
    for (int t = 0; t < no; t++) {
        P.cl[op[t]].items[1] = mk_item(IT_OP, 0, t & ~1, 0, 32, t & 1);
        P.cl[op[t]].items[2] = IT_DYN;
        P.cl[op[t]].delay = ong ? od0 + (t * ong / 16) * (odmax / ong) : od0 + t * odmax / 16;
    }
    for (int k = 0; k < nq; k++) {
        const int c = qa[(k * 19) % nq];
        P.cl[c].items[1] = P.cl[c].items[2] = IT_DYN;
        P.cl[c].delay = k < n0 ? 0 : (int)((long long)dmax * (k + 1 - n0) / (nq - n0));
        if (ng) P.cl[c].delay = d0 + (k * ng / nq) * (dmax / ng) + (k * ng % nq) * jit / nq;
    }
    for (int k = 0; k < no + nq; k++) {
        int best = -1;
        for (int c = 0; c < NCL; c++)
            if (P.cl[c].items[1] && !P.cl[c].items[0] && (best < 0 || P.cl[c].delay < P.cl[best].delay)) best = c;
        P.cl[best].items[0] = unit();
    }
    int H[8], pos[8];
    for (int b = 0; b < 8; b++) {
        char nh[3] = {'H', (char)('0' + b), 0}, np[3] = {'P', (char)('0' + b), 0};
        H[b] = tune(nh, H0[b]);
        pos[b] = tune(np, P0[b]);
        for (int g = 0; g < 64; g++)
            if (dep[g] > 32) {
                if (pos[b] > 8 * g) pos[b] = 8 * g;
                if (H[b] < dep[g] - 32) H[b] = dep[g] - 32;
            }
        if (b < nkeep && no) {
            pos[b] = -1;
            P.cl[op[14 - 2 * b]].items[2] = mk_item(IT_OP, 1, 2 * b, 0, H[b], 0, 1);
            P.cl[op[15 - 2 * b]].items[2] = mk_item(IT_OP, 1, 2 * b, 0, H[b], 1, 1);
        }
    }
    int n = 0, kn = 0;
    const int uend = mode == 2 ? 8 * nq : 512;
    while (u < uend) {
        for (int b = 0; b < 8 && no; b++)
            if (pos[b] == u) {
                P.list[n++] = mk_item(IT_OP, 1, 2 * b, 0, H[b], 0, 1);
                P.list[n++] = mk_item(IT_OP, 1, 2 * b, 0, H[b], 1, 1);
            }
        while (no && u >= uend - npos && kn * npos < (u + 1 - (uend - npos)) * nearly) {
            P.list[n++] = mk_item(IT_ON, 1, kn / 5 * 2, H[kn / 5], 32, kn % 5);
            kn++;
        }
        P.list[n++] = unit();
    }
    for (; no && kn < 40; kn++) P.list[n++] = mk_item(IT_ON, 1, kn / 5 * 2, H[kn / 5], 32, kn % 5);
    P.nlist = n;
}

}

extern "C" void kernel_launch(void* const* d_in, const int* in_sizes, int n_in, void* d_out, int out_size) {
    static Params P;
    static bool init = false;
    if (!init) {
        EncFn enc = nullptr;
        cudaDriverEntryPointQueryResult qr;
        cudaGetDriverEntryPoint("cuTensorMapEncodeTiled", (void**)&enc, cudaEnableDefault, &qr);
        for (int i = 0; i < 2; i++) {
            P.px[i] = (const __nv_bfloat16*)d_in[5 * i + 0];
            P.pk[i] = (const __nv_bfloat16*)d_in[5 * i + 1];
            P.pv[i] = (const __nv_bfloat16*)d_in[5 * i + 2];
            P.pwq[i] = (const __nv_bfloat16*)d_in[5 * i + 3];
            make_map3(enc, &P.x[i], d_in[5 * i + 0], 2560, 1280, 10, 160, 1);
            make_map3(enc, &P.k[i], d_in[5 * i + 1], 16 * 32 * 512, 384, 3, 64, 3);
            make_map3(enc, &P.v[i], d_in[5 * i + 2], 16 * 32 * 512, 384, 3, 64, 3);
            make_map3(enc, &P.wq[i], d_in[5 * i + 3], 640, 12288, 96, 32, 3);
            make_map3(enc, &P.wo[i], d_in[5 * i + 4], 6144, 1280, 10, 16, 5);
            make_map3(enc, &P.won[i], d_in[5 * i + 4], 6144, 1280, 10, 32, 2);
        }
        cuuint64_t dims[2] = {1280, 2560};
        cuuint64_t str[1] = {2560};
        cuuint32_t box[2] = {64, 160};
        cuuint32_t es[2] = {1, 1};
        enc(&P.out, CU_TENSOR_MAP_DATA_TYPE_BFLOAT16, 2, d_out, dims, str, box, es, CU_TENSOR_MAP_INTERLEAVE_NONE,
            CU_TENSOR_MAP_SWIZZLE_128B, CU_TENSOR_MAP_L2_PROMOTION_NONE, CU_TENSOR_MAP_FLOAT_OOB_FILL_NONE);
        build_schedule(P);
        cudaFuncSetAttribute(fused_kernel, cudaFuncAttributeMaxDynamicSharedMemorySize, SMEM_LAUNCH);
        init = true;
    }
    fused_kernel<<<NCTA, 384, SMEM_LAUNCH>>>(P);
}
```

```cpp
#include <cuda_runtime.h>
#include <cuda.h>
#include <cuda_bf16.h>
#include <stdint.h>

namespace {

constexpr int NCTA = 132;
constexpr int NCL = NCTA / 2;
constexpr int MAXI = 16;
constexpr int NSTAT = 3;
constexpr uint32_t IT_DYN = 0xffffffffu;
constexpr int SLOT = 24576;
constexpr int NSLOT = 5;
constexpr int XS = 20480;
constexpr int OFF_R = 0;
constexpr int OFF_RING = 5 * XS;
constexpr int OFF_MISC = OFF_RING + NSLOT * SLOT;
constexpr int OFF_LX = OFF_MISC;
constexpr int OFF_LINV = OFF_LX + 2560;
constexpr int OFF_FB = OFF_LINV + 640;
constexpr int OFF_GM = OFF_FB + 16;
constexpr int OFF_BAR = OFF_GM + 16;
constexpr int BAR_RFULL = OFF_BAR;
constexpr int BAR_REMPTY = BAR_RFULL + 40;
constexpr int BAR_XFULL = BAR_REMPTY + 40;
constexpr int BAR_XEMPTY = BAR_XFULL + 40;
constexpr int BAR_PRDY = BAR_XEMPTY + 40;
constexpr int BAR_ITEM = BAR_PRDY + 40;
constexpr int OFF_ITEM = BAR_ITEM + MAXI * 8;
constexpr int SMEM_BYTES = OFF_ITEM + MAXI * 4;
static_assert(SMEM_BYTES <= 232448, "smem");

constexpr int NB_W = 1  , NB_PFULL = 3  , NB_VOTE = 5  , NB_Q2 = 7, NB_SDONE = 8, NB_PDONE = 9,
              NB_L = 10, NB_REF = 11, NB_ODONE = 12, NB_OPEND = 13, NB_LX = 14, NB_Q01 = 15, NB_QK = 0  ;

constexpr uint32_t IT_QA = 1, IT_OP = 2, IT_ON = 3;
__host__ __device__ constexpr uint32_t mk_item(uint32_t type, uint32_t br, uint32_t b, uint32_t h0, uint32_t h1, uint32_t half,
                                               uint32_t part = 0) {
    return type | (br << 2) | (b << 3) | (h0 << 7) | (h1 << 13) | (half << 19) | (part << 22);
}
#define IT_TYPE(e) ((e) & 3u)
#define IT_BR(e) (((e) >> 2) & 1u)
#define IT_B(e) (((e) >> 3) & 15u)
#define IT_H0(e) (((e) >> 7) & 63u)
#define IT_H1(e) (((e) >> 13) & 63u)
#define IT_HALF(e) (((e) >> 19) & 7u)
#define IT_PART(e) (((e) >> 22) & 1u)
#define IT_SLOT(e) IT_H1(e)
#define IT_DEP(e) (((e) >> 23) & 127u)

struct Params {
    CUtensorMap x[2], wq[2], k[2], v[2], wo[2], won[2], out;
    const __nv_bfloat16 *px[2], *pwq[2], *pk[2], *pv[2];
    struct alignas(16) { uint32_t delay, items[NSTAT]; } cl[NCL];
    uint32_t nlist;
    uint8_t slot[64];
    uint32_t list[512];
};

constexpr int OUNIT = 61440;
__device__ __align__(1024) unsigned char g_ostash[(size_t)1024 * OUNIT];
__device__ unsigned int g_flag[32 * 64];
__device__ __forceinline__ unsigned char* ostash(uint32_t slot, uint32_t b) { return g_ostash + (slot * 16 + b) * OUNIT; }
__device__ unsigned int g_epoch[NCTA * 4];
__device__ unsigned int g_ticket[2];

constexpr int SMEM_LAUNCH = SMEM_BYTES;
#define TS(role, idx)
#define TS_ITEM(e)
#define TS_DUMP(role)
#define TSD(role, idx)

#define POL_W 2
#define POL_X 2
#define POL_O 2
template <int M>
__device__ __forceinline__ uint64_t mkpol() {
    uint64_t p;
    if (M == 0) asm volatile("createpolicy.fractional.L2::evict_normal.b64 %0, 1.0;" : "=l"(p));
    if (M == 1) asm volatile("createpolicy.fractional.L2::evict_first.b64 %0, 1.0;" : "=l"(p));
    if (M == 2) asm volatile("createpolicy.fractional.L2::evict_unchanged.b64 %0, 1.0;" : "=l"(p));
    if (M == 3) asm volatile("createpolicy.fractional.L2::evict_normal.L2::evict_unchanged.b64 %0, 0.25;" : "=l"(p));
    return p;
}
#define STSM_W 1
#define XLATE 2
#define PV0FIRST 1
#define QST0 1
#define QST1 2
#define QHOLD 7
constexpr float SM_C = 0.07216878364870322f * 1.4426950408889634f;

__device__ __forceinline__ uint32_t next_epoch(int warp) {
    unsigned int* p = &g_epoch[blockIdx.x * 4 + warp];
    const uint32_t e = __ldcg(p) + 1;
    *p = e;
    return e;
}

__device__ __forceinline__ uint32_t tid_now() {
    uint32_t t;
    asm volatile("mov.u32 %0, %%tid.x;" : "=r"(t));
    return t;
}
__device__ __forceinline__ void mbar_init(uint32_t a, uint32_t c) {
    asm volatile("mbarrier.init.shared::cta.b64 [%0], %1;" ::"r"(a), "r"(c) : "memory");
}
__device__ __forceinline__ void mbar_expect(uint32_t a, uint32_t b) {
    asm volatile("mbarrier.arrive.expect_tx.shared::cta.b64 _, [%0], %1;" ::"r"(a), "r"(b) : "memory");
}
template <int CNT = 1>
__device__ __forceinline__ void mbar_arrive_warp(uint32_t a) {
    if (CNT == 1)
        asm volatile("{\n.reg .pred p;\nelect.sync _|p, 0xffffffff;\n@p mbarrier.arrive.shared::cta.b64 _, [%0];\n}" ::"r"(a) : "memory");
    else
        asm volatile(
            "{\n.reg .pred p;\nelect.sync _|p, 0xffffffff;\n@p mbarrier.arrive.shared::cta.b64 _, [%0];\n"
            "@p mbarrier.arrive.shared::cta.b64 _, [%0];\n}" ::"r"(a)
            : "memory");
}
template <int CNT = 1>
__device__ __forceinline__ void mbar_arrive_warp_if(uint32_t a, bool cond) {
    if (CNT == 1)
        asm volatile(
            "{\n.reg .pred p, c;\nelect.sync _|p, 0xffffffff;\nsetp.ne.and.u32 c, %1, 0, p;\n"
            "@c mbarrier.arrive.shared::cta.b64 _, [%0];\n}" ::"r"(a), "r"((uint32_t)cond)
            : "memory");
    else
        asm volatile(
            "{\n.reg .pred p, c;\nelect.sync _|p, 0xffffffff;\nsetp.ne.and.u32 c, %1, 0, p;\n"
            "@c mbarrier.arrive.shared::cta.b64 _, [%0];\n@c mbarrier.arrive.shared::cta.b64 _, [%0];\n}" ::"r"(a), "r"((uint32_t)cond)
            : "memory");
}
__device__ __forceinline__ uint32_t deadline() {
    uint32_t c;
    asm volatile("mov.u32 %0, %%clock_hi;" : "=r"(c));
    return c + 4;
}
__device__ __forceinline__ void mbar_wait(uint32_t a, uint32_t ph, uint32_t dl) {
    asm volatile(
        "{\n.reg .pred p;\n.reg .u32 m;\n"
        "LOOP:\n"
        "mbarrier.try_wait.parity.shared::cta.b64 p, [%0], %1;\n"
        "@p bra DONE;\n"
        "mov.u32 m, %%clock_hi;\n"
        "setp.ne.u32 p, m, %2;\n"
        "@p bra LOOP;\n"
        "trap;\n"
        "DONE:\n}" ::"r"(a), "r"(ph), "r"(dl)
        : "memory");
}
template <int ID, int CNT>
__device__ __forceinline__ void nb_sync() { asm volatile("bar.sync %0, %1;" ::"n"(ID), "n"(CNT) : "memory"); }
template <int ID, int CNT>
__device__ __forceinline__ void nb_arrive() { asm volatile("bar.arrive %0, %1;" ::"n"(ID), "n"(CNT) : "memory"); }
__device__ __forceinline__ void fence_async_smem() { asm volatile("fence.proxy.async.shared::cta;" ::: "memory"); }

__device__ __forceinline__ void tma3(uint32_t dst, const CUtensorMap* m, int c1, int c2, uint32_t bar, uint64_t pol) {
    asm volatile(
        "cp.async.bulk.tensor.3d.shared::cluster.global.mbarrier::complete_tx::bytes.L2::cache_hint [%0], [%1, {%3,%4,%5}], [%2], %6;" ::"r"(dst),
        "l"(m), "r"(bar), "r"(0), "r"(c1), "r"(c2), "l"(pol)
        : "memory");
}
__device__ __forceinline__ void tma3_mc(uint32_t dst, const CUtensorMap* m, int c1, int c2, uint32_t bar, uint64_t pol) {
    asm volatile(
        "cp.async.bulk.tensor.3d.shared::cluster.global.mbarrier::complete_tx::bytes.multicast::cluster.L2::cache_hint"
        " [%0], [%1, {%3,%4,%5}], [%2], %6, %7;" ::"r"(dst),
        "l"(m), "r"(bar), "r"(0), "r"(c1), "r"(c2), "h"((unsigned short)3), "l"(pol)
        : "memory");
}
__device__ __forceinline__ void bulk_load(uint32_t dst, const void* src, uint32_t bytes, uint32_t bar, uint64_t pol) {
    asm volatile("cp.async.bulk.shared::cluster.global.mbarrier::complete_tx::bytes.L2::cache_hint [%0], [%1], %2, [%3], %4;" ::"r"(dst),
                 "l"(src), "r"(bytes), "r"(bar), "l"(pol)
                 : "memory");
}
__device__ __forceinline__ void wg_fence() { asm volatile("wgmma.fence.sync.aligned;" ::: "memory"); }
__device__ __forceinline__ void wg_commit() { asm volatile("wgmma.commit_group.sync.aligned;" ::: "memory"); }
template <int N>
__device__ __forceinline__ void wg_wait() { asm volatile("wgmma.wait_group.sync.aligned %0;" ::"n"(N) : "memory"); }

#define RW80(c, d) c(d[0]), c(d[1]), c(d[2]), c(d[3]), c(d[4]), c(d[5]), c(d[6]), c(d[7]), c(d[8]), c(d[9]), c(d[10]), c(d[11]), c(d[12]), c(d[13]), c(d[14]), c(d[15]), c(d[16]), c(d[17]), c(d[18]), c(d[19]), c(d[20]), c(d[21]), c(d[22]), c(d[23]), c(d[24]), c(d[25]), c(d[26]), c(d[27]), c(d[28]), c(d[29]), c(d[30]), c(d[31]), c(d[32]), c(d[33]), c(d[34]), c(d[35]), c(d[36]), c(d[37]), c(d[38]), c(d[39]), c(d[40]), c(d[41]), c(d[42]), c(d[43]), c(d[44]), c(d[45]), c(d[46]), c(d[47]), c(d[48]), c(d[49]), c(d[50]), c(d[51]), c(d[52]), c(d[53]), c(d[54]), c(d[55]), c(d[56]), c(d[57]), c(d[58]), c(d[59]), c(d[60]), c(d[61]), c(d[62]), c(d[63]), c(d[64]), c(d[65]), c(d[66]), c(d[67]), c(d[68]), c(d[69]), c(d[70]), c(d[71]), c(d[72]), c(d[73]), c(d[74]), c(d[75]), c(d[76]), c(d[77]), c(d[78]), c(d[79])
#define RW48(c, d) c(d[0]), c(d[1]), c(d[2]), c(d[3]), c(d[4]), c(d[5]), c(d[6]), c(d[7]), c(d[8]), c(d[9]), c(d[10]), c(d[11]), c(d[12]), c(d[13]), c(d[14]), c(d[15]), c(d[16]), c(d[17]), c(d[18]), c(d[19]), c(d[20]), c(d[21]), c(d[22]), c(d[23]), c(d[24]), c(d[25]), c(d[26]), c(d[27]), c(d[28]), c(d[29]), c(d[30]), c(d[31]), c(d[32]), c(d[33]), c(d[34]), c(d[35]), c(d[36]), c(d[37]), c(d[38]), c(d[39]), c(d[40]), c(d[41]), c(d[42]), c(d[43]), c(d[44]), c(d[45]), c(d[46]), c(d[47])
#define RW32(c, d) c(d[0]), c(d[1]), c(d[2]), c(d[3]), c(d[4]), c(d[5]), c(d[6]), c(d[7]), c(d[8]), c(d[9]), c(d[10]), c(d[11]), c(d[12]), c(d[13]), c(d[14]), c(d[15]), c(d[16]), c(d[17]), c(d[18]), c(d[19]), c(d[20]), c(d[21]), c(d[22]), c(d[23]), c(d[24]), c(d[25]), c(d[26]), c(d[27]), c(d[28]), c(d[29]), c(d[30]), c(d[31])

__device__ __forceinline__ void reg_fence(float (&d)[80]) { asm volatile("" : RW80("+f", d)::"memory"); }
__device__ __forceinline__ void reg_fence(float (&d)[48]) { asm volatile("" : RW48("+f", d)::"memory"); }
__device__ __forceinline__ void reg_fence(float (&d)[32]) { asm volatile("" : RW32("+f", d)::"memory"); }

template <int NR>
__device__ __forceinline__ void zero(float (&d)[NR]) {
#pragma unroll
    for (int i = 0; i < NR; i++) d[i] = 0.f;
}

constexpr uint32_t HI_SW128 = (1024u >> 4) | (1u << 30);
constexpr uint32_t HI_OST = (2560u >> 4) | (2u << 30);
constexpr uint32_t LO_LBO1 = (1u << 16);
constexpr uint32_t LO_OST = ((512u >> 4) << 16);

template <int TA, int TB, uint32_t HIB, int ACC>
__device__ __forceinline__ void wgmma(float (&d)[80], uint32_t loA, uint32_t loB) {
#define WG_ASM(SD)                                                          \
    "{\n.reg .b64 da, db;\nmov.b64 da, {%80, %82};\nmov.b64 db, {%81, %83};\n" \
    "wgmma.mma_async.sync.aligned.m64n160k16.f32.bf16.bf16 "               \
    "{%0,%1,%2,%3,%4,%5,%6,%7,%8,%9,%10,%11,%12,%13,%14,%15,%16,%17,%18,%19,%20,%21,%22,%23,%24,%25,%26,%27,%28,%29,%30,%31,%32,%33,%34,%35,%36,%37,%38,%39,%40,%41,%42,%43,%44,%45,%46,%47,%48,%49,%50,%51,%52,%53,%54,%55,%56,%57,%58,%59,%60,%61,%62,%63,%64,%65,%66,%67,%68,%69,%70,%71,%72,%73,%74,%75,%76,%77,%78,%79}, da, db, " SD ", 1, 1, %84, %85;\n}"
    if constexpr (ACC == 2)
        asm volatile(WG_ASM("0") : RW80("+f", d) : "r"(loA), "r"(loB), "n"(HI_SW128), "n"(HIB), "n"(TA), "n"(TB));
    else if constexpr (ACC == 1)
        asm volatile(WG_ASM("1") : RW80("+f", d) : "r"(loA), "r"(loB), "n"(HI_SW128), "n"(HIB), "n"(TA), "n"(TB));
    else
        asm volatile(WG_ASM("0") : RW80("=f", d) : "r"(loA), "r"(loB), "n"(HI_SW128), "n"(HIB), "n"(TA), "n"(TB));
#undef WG_ASM
}
template <int TA, int TB, uint32_t HIB, int ACC>
__device__ __forceinline__ void wgmma(float (&d)[48], uint32_t loA, uint32_t loB) {
#define WG_ASM(SD)                                                          \
    "{\n.reg .b64 da, db;\nmov.b64 da, {%48, %50};\nmov.b64 db, {%49, %51};\n" \
    "wgmma.mma_async.sync.aligned.m64n96k16.f32.bf16.bf16 "               \
    "{%0,%1,%2,%3,%4,%5,%6,%7,%8,%9,%10,%11,%12,%13,%14,%15,%16,%17,%18,%19,%20,%21,%22,%23,%24,%25,%26,%27,%28,%29,%30,%31,%32,%33,%34,%35,%36,%37,%38,%39,%40,%41,%42,%43,%44,%45,%46,%47}, da, db, " SD ", 1, 1, %52, %53;\n}"
    if constexpr (ACC == 1)
        asm volatile(WG_ASM("1") : RW48("+f", d) : "r"(loA), "r"(loB), "n"(HI_SW128), "n"(HIB), "n"(TA), "n"(TB));
    else
        asm volatile(WG_ASM("0") : RW48("=f", d) : "r"(loA), "r"(loB), "n"(HI_SW128), "n"(HIB), "n"(TA), "n"(TB));
#undef WG_ASM
}
template <int TA, int TB, uint32_t HIB, int ACC>
__device__ __forceinline__ void wgmma(float (&d)[32], uint32_t loA, uint32_t loB) {
#define WG_ASM(SD)                                                          \
    "{\n.reg .b64 da, db;\nmov.b64 da, {%32, %34};\nmov.b64 db, {%33, %35};\n" \
    "wgmma.mma_async.sync.aligned.m64n64k16.f32.bf16.bf16 "               \
    "{%0,%1,%2,%3,%4,%5,%6,%7,%8,%9,%10,%11,%12,%13,%14,%15,%16,%17,%18,%19,%20,%21,%22,%23,%24,%25,%26,%27,%28,%29,%30,%31}, da, db, " SD ", 1, 1, %36, %37;\n}"
    if constexpr (ACC == 1)
        asm volatile(WG_ASM("1") : RW32("+f", d) : "r"(loA), "r"(loB), "n"(HI_SW128), "n"(HIB), "n"(TA), "n"(TB));
    else
        asm volatile(WG_ASM("0") : RW32("=f", d) : "r"(loA), "r"(loB), "n"(HI_SW128), "n"(HIB), "n"(TA), "n"(TB));
#undef WG_ASM
}

__device__ __forceinline__ uint32_t pack_bf16(float lo, float hi) {
    uint32_t r;
    asm("cvt.rn.bf16x2.f32 %0, %1, %2;" : "=r"(r) : "f"(hi), "f"(lo));
    return r;
}
__device__ __forceinline__ float ex2(float x) {
    float r;
    asm("ex2.approx.ftz.f32 %0, %1;" : "=f"(r) : "f"(x));
    return r;
}
__device__ __forceinline__ void stsm4t(uint32_t a, uint32_t r0, uint32_t r1, uint32_t r2, uint32_t r3) {
    asm volatile("stmatrix.sync.aligned.m8n8.x4.trans.shared.b16 [%0], {%1,%2,%3,%4};" ::"r"(a), "r"(r0), "r"(r1), "r"(r2), "r"(r3)
                 : "memory");
}
__device__ __forceinline__ uint32_t lds_u(uint32_t a) {
    uint32_t v;
    asm volatile("ld.shared.u32 %0, [%1];" : "=r"(v) : "r"(a) : "memory");
    return v;
}
__device__ __forceinline__ uint4 lds_u4(uint32_t a) {
    uint4 v;
    asm volatile("ld.shared.v4.u32 {%0,%1,%2,%3}, [%4];" : "=r"(v.x), "=r"(v.y), "=r"(v.z), "=r"(v.w) : "r"(a) : "memory");
    return v;
}
__device__ __forceinline__ float2 lds_f2(uint32_t a) {
    float2 v;
    asm volatile("ld.shared.v2.f32 {%0,%1}, [%2];" : "=f"(v.x), "=f"(v.y) : "r"(a) : "memory");
    return v;
}
__device__ __forceinline__ void sts_f(uint32_t a, float v) { asm volatile("st.shared.f32 [%0], %1;" ::"r"(a), "f"(v) : "memory"); }
__device__ __forceinline__ void sts_u(uint32_t a, uint32_t v) { asm volatile("st.shared.u32 [%0], %1;" ::"r"(a), "r"(v) : "memory"); }
__device__ __forceinline__ void sts_f2(uint32_t a, float x, float y) {
    asm volatile("st.shared.v2.f32 [%0], {%1,%2};" ::"r"(a), "f"(x), "f"(y) : "memory");
}

__device__ __forceinline__ void store_tile_t(const float (&d)[80], uint32_t addr) {
#pragma unroll
    for (int j = 0; j < 10; j++)
        stsm4t(addr + j * 2048, pack_bf16(d[8 * j], d[8 * j + 1]), pack_bf16(d[8 * j + 2], d[8 * j + 3]),
               pack_bf16(d[8 * j + 4], d[8 * j + 5]), pack_bf16(d[8 * j + 6], d[8 * j + 7]));
}
template <bool ADD, int NR>
__device__ __forceinline__ void store_out_tile(const float (&d)[NR], uint32_t base, uint32_t lane, uint32_t w) {
    const uint32_t mi = lane >> 3, i = lane & 7;
    const uint32_t chunk = 2 * w + (mi & 1);
    const uint32_t q0 = 8 * (i >> 1) + 2 * (mi >> 1) + (i & 1);
    const uint32_t a0 = base + q0 * 128 + ((chunk ^ (q0 & 7)) << 4);
    const uint32_t a1 = base + (q0 + 4) * 128 + ((chunk ^ ((q0 + 4) & 7)) << 4);
    uint32_t p[NR / 2];
    if (ADD) {
#pragma unroll
        for (int j = 0; j < NR / 8; j++)
            asm volatile("ldmatrix.sync.aligned.m8n8.x4.trans.shared.b16 {%0,%1,%2,%3}, [%4];"
                         : "=r"(p[4 * j]), "=r"(p[4 * j + 1]), "=r"(p[4 * j + 2]), "=r"(p[4 * j + 3])
                         : "r"(((j & 1) ? a1 : a0) + (j >> 1) * 4096)
                         : "memory");
    }
#pragma unroll
    for (int k = 0; k < NR / 2; k++)
        p[k] = ADD ? pack_bf16(d[2 * k] + __uint_as_float(p[k] << 16), d[2 * k + 1] + __uint_as_float(p[k] & 0xffff0000u))
                   : pack_bf16(d[2 * k], d[2 * k + 1]);
#pragma unroll
    for (int j = 0; j < NR / 8; j++)
        stsm4t(((j & 1) ? a1 : a0) + (j >> 1) * 4096, p[4 * j], p[4 * j + 1], p[4 * j + 2], p[4 * j + 3]);
}

struct TrueT { static constexpr bool value = true; };
struct FalseT { static constexpr bool value = false; };

template <int V>
struct IntT { static constexpr int value = V; };

__device__ __forceinline__ uint32_t get_item(uint32_t sb, int it, uint32_t dl) {
    mbar_wait(sb + BAR_ITEM + it * 8, 0, dl);
    return lds_u(sb + OFF_ITEM + it * 4);
}
__device__ __forceinline__ uint32_t get_item_warp(uint32_t sb, int it, uint32_t dl) {
    return __shfl_sync(0xffffffffu, get_item(sb, it, dl), 0);
}

struct Ring {
    uint32_t slot, ph, dl;
    __device__ __forceinline__ void adv(uint32_t k) {
        slot += k;
        if (slot >= NSLOT) { slot -= NSLOT; ph ^= 1; }
    }
};

template <int K>
__device__ __forceinline__ void qk_step(float (&s)[80], uint32_t loK, uint32_t loQ) {
    wgmma<0, 0, HI_SW128, K != 0>(s, loK + (K >> 2) * (8192 >> 4) + (K & 3) * 2, loQ + (K >> 2) * (XS >> 4) + (K & 3) * 2);
}
template <int K0, int K1>
__device__ __forceinline__ void qk_steps(float (&s)[80], uint32_t loK, uint32_t loQ) {
    if constexpr (K0 < K1) {
        qk_step<K0>(s, loK, loQ);
        qk_steps<K0 + 1, K1>(s, loK, loQ);
    }
}
__device__ __forceinline__ uint32_t add_bf2(uint32_t a, uint32_t b) {
    uint32_t r;
    asm("add.rn.bf16x2 %0, %1, %2;" : "=r"(r) : "r"(a), "r"(b));
    return r;
}
__device__ __forceinline__ uint32_t fma_bf2(uint32_t a, uint32_t b, uint32_t c) {
    uint32_t r;
    asm("fma.rn.bf16x2 %0, %1, %2, %3;" : "=r"(r) : "r"(a), "r"(b), "r"(c));
    return r;
}
template <int J>
__device__ __forceinline__ void exp_block(const float (&s)[80], uint32_t (&k)[40], uint32_t pa, float mref) {
    if constexpr (J < 10) {
#pragma unroll
        for (int i = 4 * J; i < 4 * J + 4; i++)
            k[i] = pack_bf16(ex2(fmaf(s[2 * i], SM_C, -mref)), ex2(fmaf(s[2 * i + 1], SM_C, -mref)));
#pragma unroll
        for (int i = 0; i < 4; i++)
            asm volatile("stmatrix.sync.aligned.m8n8.x1.trans.shared.b16 [%0], {%1};" ::"r"(((i & 1) ? pa ^ 16 : pa) + J * 2048 + (i >> 1) * 1024),
                         "r"(k[4 * J + i])
                         : "memory");
        exp_block<J + 1>(s, k, pa, mref);
    }
}
__device__ __forceinline__ void sum_block(const uint32_t (&k)[40], float (&l)[10], uint32_t lane) {
    const bool b4 = lane & 16, b3 = lane & 8;
    uint32_t ps[20], t[10];
#pragma unroll
    for (int j = 0; j < 20; j++) ps[j] = add_bf2(k[2 * j], k[2 * j + 1]);
#pragma unroll
    for (int j = 0; j < 10; j++)
        t[j] = add_bf2(b4 ? ps[2 * j + 1] : ps[2 * j], __shfl_xor_sync(0xffffffffu, b4 ? ps[2 * j] : ps[2 * j + 1], 16));
#pragma unroll
    for (int i = 0; i < 5; i++) {
        const uint32_t a = b3 ? t[i + 5] : t[i], b = __shfl_xor_sync(0xffffffffu, b3 ? t[i] : t[i + 5], 8);
        l[2 * i] += __uint_as_float(a << 16) + __uint_as_float(b << 16);
        l[2 * i + 1] += __uint_as_float(a & 0xffff0000u) + __uint_as_float(b & 0xffff0000u);
    }
}
template <bool ADD>
__device__ __forceinline__ void sum_store(const float (&l)[10], uint32_t lane, uint32_t lxa) {
    const bool b2 = lane & 4;
    float t[5];
#pragma unroll
    for (int i = 0; i < 5; i++) t[i] = ADD ? __uint_as_float(lds_u(lxa + i * 64)) : 0.f;
#pragma unroll
    for (int i = 0; i < 5; i++)
        sts_f(lxa + i * 64, t[i] + (b2 ? l[2 * i + 1] : l[2 * i]) + __shfl_xor_sync(0xffffffffu, b2 ? l[2 * i] : l[2 * i + 1], 4));
}

__device__ __forceinline__ void fallback_unit(const Params& P, uint32_t e, uint32_t tid) {
    const uint32_t lane = tid & 31, br = IT_BR(e), b = IT_B(e), h = IT_H0(e);
    const __nv_bfloat162* wq = (const __nv_bfloat162*)(P.pwq[br] + h * 192) + lane;
    const __nv_bfloat162* kp = (const __nv_bfloat162*)(P.pk[br] + (size_t)(b * 32 + h) * 512 * 192) + lane;
    const __nv_bfloat162* vp = (const __nv_bfloat162*)(P.pv[br] + (size_t)(b * 32 + h) * 512 * 192) + lane;
#pragma unroll 1
    for (uint32_t qi = 0; qi < 40; qi++) {
        const uint32_t q = 4 * qi + (tid >> 5);
        const __nv_bfloat16* xr = P.px[br] + (size_t)(b * 160 + q) * 640;
        float a[6] = {0.f, 0.f, 0.f, 0.f, 0.f, 0.f};
#pragma unroll 2
        for (int k = 0; k < 640; k++) {
            const float xv = __bfloat162float(xr[k]);
#pragma unroll
            for (int i = 0; i < 3; i++) {
                const float2 wv = __bfloat1622float2(wq[(size_t)k * 3072 + i * 32]);
                a[2 * i] = fmaf(xv, wv.x, a[2 * i]);
                a[2 * i + 1] = fmaf(xv, wv.y, a[2 * i + 1]);
            }
        }
#pragma unroll
        for (int i = 0; i < 6; i++) a[i] = __bfloat162float(__float2bfloat16(a[i]));
        auto score = [&](int key) {
            float d = 0.f;
#pragma unroll
            for (int i = 0; i < 3; i++) {
                const float2 kv = __bfloat1622float2(kp[key * 96 + i * 32]);
                d = fmaf(a[2 * i], kv.x, fmaf(a[2 * i + 1], kv.y, d));
            }
#pragma unroll
            for (int o = 16; o > 0; o >>= 1) d += __shfl_xor_sync(0xffffffffu, d, o);
            return d;
        };
        float m = -INFINITY, o[6] = {0.f, 0.f, 0.f, 0.f, 0.f, 0.f}, sum = 0.f;
#pragma unroll 1
        for (int n = 0; n < 1024; n++) {
            const int key = n & 511;
            const float d = score(key);
            if (n < 512) {
                m = fmaxf(m, d);
            } else {
                const float p = ex2((d - m) * SM_C);
                sum += p;
#pragma unroll
                for (int i = 0; i < 3; i++) {
                    const float2 vv = __bfloat1622float2(vp[key * 96 + i * 32]);
                    o[2 * i] = fmaf(p, vv.x, o[2 * i]);
                    o[2 * i + 1] = fmaf(p, vv.y, o[2 * i + 1]);
                }
            }
        }
        const float inv = __fdividef(1.f, sum);
        __nv_bfloat16* op = (__nv_bfloat16*)ostash(IT_SLOT(e), b) + (q >> 5) * 256 + 2 * ((q & 31) >> 3) + (q & 1);
#pragma unroll
        for (int i = 0; i < 6; i++) {
            const uint32_t d = (i >> 1) * 64 + 2 * lane + (i & 1);
            op[(d >> 3) * 1280 + (d & 7) * 32 + ((((q & 7) >> 1) ^ ((d & 7) >> 1)) << 3)] = __float2bfloat16(o[i] * inv);
        }
    }
}

template <int W>
struct PendO {
    static constexpr int N = W == 0 ? 56 : 64;
    uint32_t v[N];
    unsigned char* gp;
    static __device__ __forceinline__ uint32_t toff() {
        const uint32_t t = tid_now();
        return ((t >> 5) & 3) * 5120 + ((t >> 2) & 7) * 64 + (((t ^ (t >> 3)) & 3) << 4);
    }
    uint32_t pend, sig;
    static __device__ __forceinline__ void scale(uint32_t& x, uint32_t hi, uint32_t lo) {
        asm("{\n.reg .b32 t;\nmul.rn.bf16x2 t, %0, %2;\nfma.rn.bf16x2 %0, %0, %1, t;\n}" : "+r"(x) : "r"(hi), "r"(lo));
    }
    template <int I, int OFF>
    __device__ __forceinline__ void put() {
        asm volatile("{\n.reg .pred p;\nsetp.ne.u32 p, %6, 0;\n@p st.global.v4.b32 [%0+%5], {%1,%2,%3,%4};\n}" ::"l"(gp), "r"(v[I]),
                     "r"(v[I + 1]), "r"(v[I + 2]), "r"(v[I + 3]), "n"(OFF), "r"(pend)
                     : "memory");
    }
    __device__ __forceinline__ void verdict(const Params& P, uint32_t sb, int ie) {
        if (sig) {
            nb_sync<NB_VOTE + W, 160>();
            pend = !__any_sync(0xffffffffu, lds_u(sb + OFF_FB) != 0);
            if (W == 1 && !pend) {
                fallback_unit(P, lds_u(sb + OFF_ITEM + ie * 4), tid_now() & 127);
                __syncwarp();
            }
        }
    }
    template <int G, int H>
    __device__ __forceinline__ void half(uint32_t sb) {
        constexpr bool T2 = W == 0 ? G >= 3 : G < 3;
        constexpr int B = T2 ? 40 + 8 * (W == 0 ? G - 3 : G) : 0;
        const uint4 a = lds_u4(sb + OFF_LINV + G * 128 + H * 16 + (threadIdx.x & 3) * 32);
#pragma unroll
        for (int i = 2 * H; i < 8; i += 4) {
            scale(v[8 * G + i], a.x, a.y);
            scale(v[8 * G + i + 1], a.z, a.w);
            if (T2) {
                scale(v[B + i], a.x, a.y);
                scale(v[B + i + 1], a.z, a.w);
            }
        }
        if (H == 1) {
            put<8 * G, W * XS + G * 512>();
            put<8 * G + 4, W * XS + G * 512 + 2560>();
            if (T2) {
                put<B, 2 * XS + G * 512>();
                put<B + 4, 2 * XS + G * 512 + 2560>();
            }
            if (G == 4 && sig) nb_arrive<NB_ODONE, 288>();
        }
    }
    template <int G>
    __device__ __forceinline__ void step(uint32_t sb) {
        half<G, 0>(sb);
        half<G, 1>(sb);
    }
    __device__ __forceinline__ void clear() {
#pragma unroll
        for (int i = 0; i < N; i++) v[i] = 0;
        gp = nullptr;
        pend = 0;
        sig = 0;
    }
};

template <int W, int KK>
__device__ __forceinline__ void qproj(float (&q0)[80], float (&q1)[80], uint32_t sb, Ring& r, uint32_t pslot, uint32_t phm,
                                      PendO<W>& po, const Params& P, int it) {
    const uint32_t loR = (((sb + OFF_R) & 0x3ffff) >> 4) | LO_LBO1;
    const uint32_t loRing = (((sb + OFF_RING) & 0x3ffff) >> 4) | LO_LBO1;
    auto ready = [&](int k) {
        mbar_wait(sb + BAR_RFULL + r.slot * 8, r.ph, r.dl);
        mbar_wait(sb + BAR_XFULL + (k % 5) * 8, ((phm >> (k % 5)) ^ (k / 5)) & 1, r.dl);
    };
    auto release = [&]() {
        if (KK > 0) {
            wg_wait<1>();
            mbar_arrive_warp(sb + BAR_REMPTY + pslot * 8);
            if (KK <= 5) mbar_arrive_warp(sb + (BAR_XEMPTY + (KK - 1) * 8));
        }
    };
    if (KK == 0) ready(0);
    if (W == 1 && KK == QHOLD) nb_sync<NB_SDONE, 256>();
    const uint32_t a = loRing + r.slot * (SLOT >> 4) + (W == 0 ? 0 : 512), b = loR + (KK % 5) * (XS >> 4);
    wg_fence();
    wgmma<1, 0, HI_SW128, KK != 0>(q0, a, b);
    if (W == 0) wgmma<1, 0, HI_SW128, KK != 0>(q1, a + 256, b);
#pragma unroll
    for (int k = 1; k < 4; k++) {
        wgmma<1, 0, HI_SW128, true>(q0, a + (k >> 1) * 768 + (k & 1) * 128, b + k * 2);
        if (W == 0) wgmma<1, 0, HI_SW128, true>(q1, a + 256 + (k >> 1) * 768 + (k & 1) * 128, b + k * 2);
    }
    wg_commit();
    const uint32_t cslot = r.slot;
    r.adv(1);
    if (W == 0 || KK < QHOLD) release();
    if (KK == QST0) {
        po.verdict(P, sb, it - 1);
        po.template half<0, 0>(sb);
    }
    if (KK < 9) ready(KK + 1);
    if (W == 1 && KK >= QHOLD) release();
    if (W == 1 && KK == 7) nb_arrive<NB_PDONE, 256>();
    if (KK == QST0) po.template half<0, 1>(sb);
    if constexpr (KK > QST0 && KK < QST0 + 5) po.template step<KK - QST0>(sb);
    if constexpr (KK < 9) {
        qproj<W, KK + 1>(q0, q1, sb, r, cslot, phm, po, P, it);
    } else {
        if (W == 0) nb_arrive<NB_SDONE, 256>();
        wg_wait<0>();
        reg_fence(q0);
        if (W == 0) reg_fence(q1);
        mbar_arrive_warp(sb + BAR_REMPTY + cslot * 8);
    }
}

template <int NR>
__device__ __forceinline__ void opack(const float (&o)[NR], uint32_t* v) {
#pragma unroll
    for (int g = 0; g < NR / 16; g++)
#pragma unroll
        for (int hh = 0; hh < 2; hh++)
#pragma unroll
            for (int t = 0; t < 4; t++) v[8 * g + 4 * hh + t] = pack_bf16(o[16 * g + 4 * t + 2 * hh], o[16 * g + 4 * t + 2 * hh + 1]);
}

template <bool IS_S>
__device__ __forceinline__ void op_item(uint32_t e, uint32_t sb, Ring& r, uint32_t& phm) {
    constexpr int T0 = IS_S ? 0 : 2;
    constexpr uint32_t BOFF = IS_S ? (3 * 512) >> 4 : 0;
    const uint32_t loRing = (((sb + OFF_RING) & 0x3ffff) >> 4) | LO_LBO1;
    const uint32_t loO = (((sb + OFF_R) & 0x3ffff) >> 4) | LO_OST;
    float c0[80], c1[80], c2[IS_S ? 32 : 48];
    const int T2 = 6 * (IT_H1(e) - IT_H0(e));
    uint32_t xs = 0;
    auto step = [&](auto first, uint32_t hf) {
        constexpr bool F = decltype(first)::value;
        if (hf == 0) {
            mbar_wait(sb + BAR_XFULL + xs * 8, (phm >> xs) & 1, r.dl);
            phm ^= 1u << xs;
        }
        mbar_wait(sb + BAR_RFULL + r.slot * 8, r.ph, r.dl);
        const uint32_t a = loRing + r.slot * (SLOT >> 4), b = loO + xs * (XS >> 4) + hf * 640;
        wg_fence();
        wgmma<1, 1, HI_OST, !F>(c0, a + T0 * 128, b);
        wgmma<1, 1, HI_OST, !F>(c1, a + T0 * 128 + 128, b);
        wgmma<1, 1, HI_OST, !F>(c2, a + 512, b + BOFF);
        wgmma<1, 1, HI_OST, true>(c0, a + 640 + T0 * 128, b + 320);
        wgmma<1, 1, HI_OST, true>(c1, a + 640 + T0 * 128 + 128, b + 320);
        wgmma<1, 1, HI_OST, true>(c2, a + 640 + 512, b + 320 + BOFF);
        wg_commit();
    };
    step(TrueT{}, 0);
#pragma unroll 1
    for (int t = 1; t < T2; t++) {
        const uint32_t pslot = r.slot, pxs = xs;
        r.adv(1);
        if ((t & 1) == 0 && ++xs == 5) xs = 0;
        step(FalseT{}, t & 1);
        wg_wait<1>();
        mbar_arrive_warp(sb + BAR_REMPTY + pslot * 8);
        if ((t & 1) == 0 && t + 8 < T2) mbar_arrive_warp(sb + BAR_XEMPTY + pxs * 8);
    }
    wg_wait<0>();
    reg_fence(c0);
    reg_fence(c1);
    reg_fence(c2);
    mbar_arrive_warp(sb + BAR_REMPTY + r.slot * 8);
    r.adv(1);
    nb_sync<NB_OPEND, 256>();
    const uint32_t tid = tid_now(), lane = tid & 31, w = (tid >> 5) & 3;
    store_out_tile<false>(c0, sb + OFF_R + T0 * XS, lane, w);
    store_out_tile<false>(c1, sb + OFF_R + (T0 + 1) * XS, lane, w);
    store_out_tile<false>(c2, sb + OFF_R + 4 * XS + (IS_S ? 96 * 128 : 0), lane, w);
    fence_async_smem();
    nb_arrive<NB_ODONE, 288>();
}

template <int W>
__device__ __forceinline__ void on_item(uint32_t e, uint32_t sb, Ring& r, uint32_t& phm) {
    const uint32_t loRing = (((sb + OFF_RING) & 0x3ffff) >> 4) | LO_LBO1;
    const uint32_t loO = (((sb + OFF_R) & 0x3ffff) >> 4) | LO_OST;
    float c[80];
    const int T = 3 * (IT_H1(e) - IT_H0(e));
    uint32_t xs = 0;
    auto step = [&](auto first) {
        constexpr bool F = decltype(first)::value;
        mbar_wait(sb + BAR_XFULL + xs * 8, (phm >> xs) & 1, r.dl);
        phm ^= 1u << xs;
        mbar_wait(sb + BAR_RFULL + r.slot * 8, r.ph, r.dl);
        const uint32_t a = loRing + r.slot * (SLOT >> 4) + W * 256, b = loO + xs * (XS >> 4);
        wg_fence();
        wgmma<1, 1, HI_OST, !F>(c, a, b);
#pragma unroll
        for (int k = 1; k < 4; k++) wgmma<1, 1, HI_OST, true>(c, a + (k >> 1) * 512 + (k & 1) * 128, b + k * 320);
        wg_commit();
    };
    step(TrueT{});
#pragma unroll 1
    for (int t = 1; t < T; t++) {
        const uint32_t pslot = r.slot, pxs = xs;
        r.adv(1);
        if (++xs == 5) xs = 0;
        step(FalseT{});
        wg_wait<1>();
        mbar_arrive_warp(sb + BAR_REMPTY + pslot * 8);
        mbar_arrive_warp_if(sb + BAR_XEMPTY + pxs * 8, t + 2 < T);
    }
    xs += 1 + W;
    if (xs >= 5) xs -= 5;
    mbar_wait(sb + BAR_XFULL + xs * 8, (phm >> xs) & 1, r.dl);
    wg_wait<0>();
    reg_fence(c);
    const uint32_t tid = tid_now();
    store_out_tile<true>(c, sb + OFF_R + xs * XS, tid & 31, (tid >> 5) & 3);
    fence_async_smem();
    nb_arrive<NB_ODONE, 288>();
}

template <int W>
__device__ __forceinline__ uint32_t qa_item(const Params& P, uint32_t e, uint32_t sb, Ring& r, uint32_t phm, PendO<W>& po, int it) {
    const uint32_t loR = (((sb + OFF_R) & 0x3ffff) >> 4) | LO_LBO1;
    const uint32_t loRing = (((sb + OFF_RING) & 0x3ffff) >> 4) | LO_LBO1;
    uint32_t lane, sta;
    {
        float q0[80], q1[80];
        qproj<W, 0>(q0, q1, sb, r, 0, phm, po, P, it);
        const uint32_t tid = tid_now();
        lane = tid & 31;
        sta = sb + OFF_R + (lane >> 4) * 1024 + (lane & 7) * 128 + (((((tid >> 4) & 6) + ((lane >> 3) & 1)) ^ (lane & 7)) << 4);
        TSD(W, 1);
        if (W == 0) {
            nb_sync<NB_PDONE, 256>();
            store_tile_t(q0, sta);
            store_tile_t(q1, sta + XS);
        } else {
            store_tile_t(q0, sta + 2 * XS);
        }
    }
    fence_async_smem();
    float s[80], oa[80], ob[W == 0 ? 32 : 48], l[10];
    zero(oa);
    zero(ob);
    zero(l);
    reg_fence(oa);
    reg_fence(ob);
    auto pv = [&](const Ring& rv, uint32_t buf) {
        mbar_wait(sb + BAR_RFULL + rv.slot * 8, rv.ph, rv.dl);
        const uint32_t a = loRing + rv.slot * (SLOT >> 4), b = loR + (3 + buf) * (XS >> 4);
        wg_fence();
#pragma unroll
        for (int k = 0; k < 4; k++) {
            wgmma<1, 0, HI_SW128, true>(oa, a + W * 512 + k * 128, b + k * 2);
            wgmma<1, 0, HI_SW128, true>(ob, a + 1024 + k * 128, b + (W == 0 ? (96 * 128) >> 4 : 0) + k * 2);
        }
        wg_commit();
    };
    float mref;
    uint32_t kslot, vslot;
    auto tail = [&](bool rel_other, int i) {
        uint32_t ps[40];
        exp_block<0>(s, ps, sta + (3 + W) * XS, mref);
        if (rel_other) {
            wg_wait<0>();
            mbar_arrive_warp(sb + BAR_REMPTY + vslot * 8);
            if (W == 1) mbar_arrive_warp_if(sb + BAR_XEMPTY + 24, i == 3);
        }
        fence_async_smem();
        nb_arrive<NB_PFULL + W, 256>();
        TSD(W, 6 + 5 * i);
        if (W == 1) {
            if (XLATE >= 2) mbar_arrive_warp_if<2>(sb + BAR_XEMPTY + 8, i == 3);
            if (XLATE >= 1) mbar_arrive_warp_if<2>(sb + BAR_XEMPTY + 16, i == 3);
        }
        if (rel_other || !PV0FIRST) {
            mbar_wait(sb + BAR_RFULL + r.slot * 8, r.ph, r.dl);
            sum_block(ps, l, lane);
        }
        TSD(W, 7 + 5 * i);
        nb_sync<NB_W + W, 128>();
        pv(r, W);
        if (!rel_other && PV0FIRST) sum_block(ps, l, lane);
        TSD(W, 8 + 5 * i);
    };
    if (W == 0) {
        sts_u(sb + OFF_GM + 4, r.slot);
        mbar_wait(sb + BAR_RFULL + r.slot * 8, r.ph, r.dl);
        nb_sync<NB_QK, 160>();
        TSD(W, 2);
        wg_fence();
        qk_steps<0, 8>(s, loRing + r.slot * (SLOT >> 4), loR);
        nb_sync<NB_Q2, 288>();
        qk_steps<8, 12>(s, loRing + r.slot * (SLOT >> 4), loR);
        wg_commit();
        nb_arrive<NB_Q01, 256>();
        TSD(W, 4);
        nb_sync<NB_REF, 160>();
        mref = __uint_as_float(lds_u(sb + OFF_GM));
        wg_wait<0>();
        reg_fence(s);
        mbar_arrive_warp<2>(sb + BAR_REMPTY + r.slot * 8);
        r.adv(2);
        TSD(W, 5);
        tail(false, 0);
    } else {
        nb_arrive<NB_Q2, 288>();
        TSD(W, 2);
        nb_sync<NB_Q01, 256>();
    }
#pragma unroll 1
    for (int i = (W == 0 ? 1 : 0); i < 4; i++) {
        const uint32_t pvslot = r.slot;
        r.adv(1);
        kslot = r.slot;
        mbar_wait(sb + BAR_RFULL + r.slot * 8, r.ph, r.dl);
        wg_fence();
        qk_steps<0, 12>(s, loRing + r.slot * (SLOT >> 4), loR);
        wg_commit();
        wg_wait<1>();
        mbar_arrive_warp_if(sb + BAR_REMPTY + pvslot * 8, W == 0 || i > 0);
        r.adv(1);
        vslot = r.slot;
        TSD(W, 4 + 5 * i);
        nb_sync<NB_PFULL + (W ^ 1), 256>();
        pv(r, W ^ 1);
        if (W == 1) mref = __uint_as_float(lds_u(sb + OFF_GM));
        wg_wait<1>();
        reg_fence(s);
        mbar_arrive_warp<2>(sb + BAR_REMPTY + kslot * 8);
        if (W == 1) {
            mbar_arrive_warp_if<2>(sb + BAR_XEMPTY + 0, i == 3);
            if (XLATE < 2) mbar_arrive_warp_if<2>(sb + BAR_XEMPTY + 8, i == 3);
            if (XLATE < 1) mbar_arrive_warp_if<2>(sb + BAR_XEMPTY + 16, i == 3);
        }
        r.adv(W == 1 && i == 3 ? 1 : 2);
        TSD(W, 5 + 5 * i);
        tail(true, i);
    }
    const uint32_t w = (tid_now() >> 5) & 3;
    const uint32_t lxa = sb + OFF_LX + w * 640 + (((lane & 8) ? 80 : 0) + ((lane >> 1) & 8) + 2 * (lane & 3) + ((lane >> 2) & 1)) * 4;
    const uint32_t nx = get_item_warp(sb, it + 1, r.dl);
    po.gp = ostash(IT_SLOT(e), IT_B(e)) + po.toff();
    po.sig = 1;
    if (W == 0) {
        sum_store<false>(l, lane, lxa);
        nb_arrive<NB_LX, 256>();
        wg_wait<0>();
        mbar_arrive_warp(sb + BAR_REMPTY + r.slot * 8);
        mbar_arrive_warp(sb + BAR_XEMPTY + 24);
        r.adv(1);
        nb_sync<NB_PFULL + 1, 256>();
        pv(r, 1);
    } else {
        nb_sync<NB_LX, 256>();
        sum_store<true>(l, lane, lxa);
        nb_arrive<NB_L, 160>();
    }
    TSD(W, 24);
    wg_wait<0>();
    reg_fence(oa);
    reg_fence(ob);
    mbar_arrive_warp(sb + BAR_REMPTY + r.slot * 8);
    mbar_arrive_warp(sb + BAR_XEMPTY + 32);
    r.adv(1);
    opack(ob, po.v + 40);
    opack(oa, po.v);
    return nx;
}

template <int W>
__device__ __forceinline__ void consumer(const Params& P, uint32_t sb, uint32_t dl) {
    int it = 0;
    if (W == 0) TS(0, 30);
    Ring r{0, 0, dl};
    uint32_t phm = 0;
    uint32_t e = get_item_warp(sb, 0, dl);
#pragma unroll 1
    while (e != 0) {
        if (IT_TYPE(e) == IT_QA) {
            PendO<W> po;
            po.clear();
#pragma unroll 1
            do {
                TS(W, 0);
                if (W == 0) TS_ITEM(e);
                e = qa_item<W>(P, e, sb, r, phm, po, it);
                TS(W, 31);
                it++;
            } while (IT_TYPE(e) == IT_QA);
            po.verdict(P, sb, it - 1);
            po.template step<0>(sb);
            po.template step<1>(sb);
            po.template step<2>(sb);
            po.template step<3>(sb);
            po.template step<4>(sb);
        } else {
            TS(W, 0);
            if (W == 0) TS_ITEM(e);
            if (IT_TYPE(e) == IT_OP) op_item<W == 0>(e, sb, r, phm);
            else on_item<W>(e, sb, r, phm);
            TS(W, 31);
            e = get_item_warp(sb, ++it, dl);
        }
    }
    TS_DUMP(W);
}

__global__ void __cluster_dims__(2, 1, 1) __launch_bounds__(384, 1) fused_kernel(const __grid_constant__ Params P) {
    extern __shared__ __align__(1024) unsigned char smem_raw[];
    const uint32_t sb = (uint32_t)__cvta_generic_to_shared(smem_raw);
    const uint32_t wgid = __shfl_sync(0xffffffffu, threadIdx.x >> 7, 0);
    const uint32_t cta = blockIdx.x;
    const uint32_t dl = deadline();

    if (threadIdx.x == 128) {
#pragma unroll
        for (int i = 0; i < NSLOT; i++) {
            mbar_init(sb + BAR_RFULL + i * 8, 1);
            mbar_init(sb + BAR_REMPTY + i * 8, 8);
            mbar_init(sb + BAR_XFULL + i * 8, 1);
            mbar_init(sb + BAR_XEMPTY + i * 8, 8);
        }
        asm volatile("fence.mbarrier_init.release.cluster;" ::: "memory");
        fence_async_smem();
    } else if (threadIdx.x == 160) {
#pragma unroll
        for (int i = 0; i < NSLOT + MAXI; i++) mbar_init(sb + BAR_PRDY + i * 8, 1);
        asm volatile("fence.mbarrier_init.release.cluster;" ::: "memory");
    } else if (threadIdx.x == 0) {
        sts_u(sb + OFF_ITEM, P.cl[cta >> 1].items[0] ? P.cl[cta >> 1].items[0] + 8 * (cta & 1) : 0);
        sts_u(sb + OFF_FB, P.cl[cta >> 1].delay);
    } else if (threadIdx.x == 64) {
        if (sb & 1023) __trap();
        asm volatile("prefetch.tensormap [%0];" ::"l"(&P.wq[0]) : "memory");
        asm volatile("prefetch.tensormap [%0];" ::"l"(&P.x[0]) : "memory");
    }
    __syncthreads();
    asm volatile("barrier.cluster.arrive.relaxed.aligned;" ::: "memory");

    if (wgid == 0) {
        asm volatile("setmaxnreg.dec.sync.aligned.u32 24;");
        const uint32_t warp = __shfl_sync(0xffffffffu, threadIdx.x >> 5, 0);
        if (warp == 0) {
            const bool lead = threadIdx.x == 0;
            const uint64_t pol_first = mkpol<1>(), pol_norm = mkpol<POL_W>();
            uint32_t e = __shfl_sync(0xffffffffu, lds_u(sb + OFF_ITEM), 0);
            {
                const uint32_t d = lds_u(sb + OFF_FB);
                uint32_t t0, t1;
                asm volatile("mov.u32 %0, %%clock;" : "=r"(t0));
                do {
                    asm volatile("mov.u32 %0, %%clock;" : "=r"(t1));
                } while (t1 - t0 < d);
                __syncwarp();
            }
            if (lead) asm volatile("mbarrier.arrive.shared::cta.b64 _, [%0];" ::"r"(sb + BAR_ITEM) : "memory");
#pragma unroll 1
            for (int n = 0; n < (e ? NSLOT : 0); n++) {
                if (lead) {
                    mbar_expect(sb + BAR_RFULL + n * 8, SLOT);
                    tma3(sb + OFF_RING + n * SLOT, &P.wq[0], n * 64, IT_H0(e) * 3, sb + BAR_RFULL + n * 8, pol_norm);
                    mbar_expect(sb + BAR_XFULL + n * 8, XS);
                    tma3(sb + OFF_R + n * XS, &P.x[0], IT_B(e) * 160, n, sb + BAR_XFULL + n * 8, pol_norm);
                    tma3(sb + OFF_RING + n * SLOT + SLOT / 2, &P.wq[0], n * 64 + 32, IT_H0(e) * 3, sb + BAR_RFULL + n * 8, pol_norm);
                }
            }
            __syncwarp();
            asm volatile("barrier.cluster.wait.aligned;" ::: "memory");
            unsigned int* const ticket = &g_ticket[next_epoch(0) & 1];
            const uint32_t rank = cta & 1;
            uint32_t peer;
            asm volatile("mapa.shared::cluster.u32 %0, %1, %2;" : "=r"(peer) : "r"(sb), "r"(rank ^ 1));
            Ring r{0, 0, dl};
            uint32_t pm = 0;
            auto load_w = [&](const CUtensorMap* m, int row, int blk, uint32_t half_bytes) {
                mbar_wait(sb + BAR_REMPTY + r.slot * 8, r.ph, dl);
                if (lead) {
                    mbar_expect(sb + BAR_RFULL + r.slot * 8, 2 * half_bytes);
                    asm volatile("mbarrier.arrive.shared::cluster.b64 _, [%0];" ::"r"(peer + BAR_PRDY + r.slot * 8) : "memory");
                }
                mbar_wait(sb + BAR_PRDY + r.slot * 8, (pm >> r.slot) & 1, dl);
                pm ^= 1u << r.slot;
                if (lead) tma3_mc(sb + OFF_RING + r.slot * SLOT + rank * half_bytes, m, row, blk, sb + BAR_RFULL + r.slot * 8, pol_norm);
                r.adv(1);
            };
#pragma unroll 1
            for (int it = 0; e != 0; it++) {
                uint32_t nx = 0, tk = 0;
                if (rank == 0 && IT_TYPE(e) != IT_ON && it + 2 < MAXI) nx = it + 1 < NSTAT ? P.cl[cta >> 1].items[it + 1] : IT_DYN;
                const uint32_t br = IT_BR(e);
                if (IT_TYPE(e) == IT_QA) {
                    const uint32_t h = IT_H0(e);
#pragma unroll 1
                    for (int kk = it ? 0 : NSLOT; kk < 10; kk++) load_w(&P.wq[br], kk * 64 + rank * 32, h * 3, SLOT / 2);
                    const int row0 = (IT_B(e) * 32 + h) * 512;
#pragma unroll 1
                    for (int n = 0; n < 16; n++) {
                        if (n == 13 && nx == IT_DYN && lead) tk = atomicAdd(ticket, 1);
                        const bool isv = n == 15 || (n > 0 && !(n & 1));
                        const int j = n == 15 ? 7 : isv ? (n - 2) >> 1 : (n + 1) >> 1;
                        mbar_wait(sb + BAR_REMPTY + r.slot * 8, r.ph, dl);
                        if (lead) {
                            mbar_expect(sb + BAR_RFULL + r.slot * 8, SLOT);
                            tma3(sb + OFF_RING + r.slot * SLOT, isv ? &P.v[br] : &P.k[br], row0 + j * 64, 0,
                                 sb + BAR_RFULL + r.slot * 8, pol_first);
                        }
                        r.adv(1);
                    }
                } else {
                    const bool wide = IT_TYPE(e) == IT_OP;
                    const int step = wide ? 32 : 64, r1 = IT_H1(e) * 192;
#pragma unroll 1
                    for (int row = IT_H0(e) * 192 + rank * (step >> 1); row < r1; row += step)
                        load_w(wide ? &P.wo[br] : &P.won[br], row, IT_HALF(e) * (wide ? 5 : 2), wide ? XS / 2 : 8192);
                    if (nx == IT_DYN && lead) tk = atomicAdd(ticket, 1);
                }
                if (rank == 0) {
                    if (nx == IT_DYN) {
                        tk = __shfl_sync(0xffffffffu, tk, 0);
                        nx = tk < P.nlist ? P.list[tk] : 0;
                    }
                    e = nx;
                    if (lead) {
                        asm volatile("st.async.weak.shared::cluster.mbarrier::complete_tx::bytes.b32 [%0], %1, [%2];" ::"r"(
                                         peer + OFF_ITEM + 4 + it * 4),
                                     "r"(e ? e + 8 : 0), "r"(peer + BAR_ITEM + 8 + it * 8)
                                     : "memory");
                        sts_u(sb + OFF_ITEM + 4 + it * 4, e);
                        asm volatile("mbarrier.arrive.shared::cta.b64 _, [%0];" ::"r"(sb + BAR_ITEM + 8 + it * 8) : "memory");
                    }
                } else {
                    if (lead) mbar_expect(sb + BAR_ITEM + 8 + it * 8, 4);
                    e = get_item_warp(sb, it + 1, dl);
                }
            }
        } else if (warp == 1) {
            const uint64_t pol_norm = mkpol<POL_X>(), pol_o = mkpol<POL_O>();
            const bool lead = threadIdx.x == 32;
            uint32_t phm = 0, epoch = 0;
#pragma unroll 1
            for (int it = 0;; it++) {
                const uint32_t e = get_item_warp(sb, it, dl);
                if (it == 1 || (it == 0 && e == 0)) epoch = next_epoch(1);
                if (e == 0) break;
                const uint32_t br = IT_BR(e);
                uint32_t xs = 0;
                auto acquire = [&]() {
                    mbar_wait(sb + BAR_XEMPTY + xs * 8, (phm >> xs) & 1, dl);
                    phm ^= 1u << xs;
                    if (lead) mbar_expect(sb + BAR_XFULL + xs * 8, XS);
                };
                if (IT_TYPE(e) == IT_QA) {
#pragma unroll 1
                    for (int kk = it ? 0 : 5; kk < 10; kk++) {
                        acquire();
                        if (lead) tma3(sb + OFF_R + xs * XS, &P.x[br], IT_B(e) * 160, kk, sb + BAR_XFULL + xs * 8, pol_norm);
                        if (++xs == 5) xs = 0;
                    }
                } else {
                    const unsigned int* fp = g_flag + (br * 16 + IT_B(e)) * 64 + (threadIdx.x & 31);
                    uint32_t hm = 0, pm = 0;
                    auto poll = [&](uint32_t hneed, uint32_t pneed) {
                        if ((hm & hneed) == hneed && (pm & pneed) == pneed) return;
                        uint32_t n = 0;
                        do {
                            uint32_t a, b;
                            asm volatile("ld.acquire.gpu.global.u32 %0, [%2];\nld.acquire.gpu.global.u32 %1, [%2+128];"
                                         : "=r"(a), "=r"(b) : "l"(fp) : "memory");
                            hm = __ballot_sync(0xffffffffu, a == epoch);
                            pm = __ballot_sync(0xffffffffu, b == epoch);
                            if (++n > 0x1000000) __trap();
                        } while ((hm & hneed) != hneed || (pm & pneed) != pneed);
                        __syncwarp();
                        asm volatile("fence.proxy.async;" ::: "memory");
                    };
#pragma unroll 1
                    for (uint32_t h = IT_H0(e); h < IT_H1(e); h++) {
                        poll(1u << h, 0);
                        const unsigned char* src = ostash(P.slot[br * 32 + h], IT_B(e));
#pragma unroll 1
                        for (int t = 0; t < 3; t++) {
                            acquire();
                            if (lead) bulk_load(sb + OFF_R + xs * XS, src + t * XS, XS, sb + BAR_XFULL + xs * 8, pol_o);
                            if (++xs == 5) xs = 0;
                        }
                        if (IT_TYPE(e) == IT_OP && h >= 1) {
                            const uint32_t x1 = xs == 4 ? 0 : xs + 1;
                            mbar_wait(sb + BAR_XFULL + xs * 8, (phm >> xs) & 1, dl);
                            mbar_wait(sb + BAR_XFULL + x1 * 8, (phm >> x1) & 1, dl);
                            if (lead)
                                asm volatile("st.relaxed.gpu.global.u32 [%0], %1;" ::"l"(fp + 34 + IT_HALF(e)), "r"(epoch * 64 + h) : "memory");
                        }
                    }
                    if (IT_TYPE(e) == IT_ON) {
                        poll(0, IT_HALF(e) < 2 ? 1 : IT_HALF(e) == 2 ? 3 : 2);
#pragma unroll 1
                        for (uint32_t tile = 2 * IT_HALF(e); tile < 2 * IT_HALF(e) + 2; tile++) {
                            acquire();
                            if (lead)
                                asm volatile(
                                    "cp.async.bulk.tensor.2d.shared::cluster.global.mbarrier::complete_tx::bytes [%0], [%1, {%3,%4}], [%2];" ::"r"(
                                        sb + OFF_R + xs * XS),
                                    "l"(&P.out), "r"(sb + BAR_XFULL + xs * 8), "r"(br * 640 + tile * 64), "r"(IT_B(e) * 160)
                                    : "memory");
                            if (++xs == 5) xs = 0;
                        }
                    }
                }
            }
        } else if (warp == 2) {
            asm volatile("barrier.cluster.wait.aligned;" ::: "memory");
            const uint32_t epoch = next_epoch(2);
            if (cta == 0) g_ticket[(epoch + 1) & 1] = 0;
#pragma unroll 1
            for (int it = 0;; it++) {
                const uint32_t e = get_item_warp(sb, it, dl);
                if (e == 0) break;
                nb_sync<NB_ODONE, 288>();
                if (threadIdx.x == 64) {
                    const uint32_t bb = IT_BR(e) * 16 + IT_B(e);
                    if (IT_TYPE(e) != IT_QA) {
                        const bool wide = IT_TYPE(e) == IT_OP;
                        if (wide)
                            asm volatile("st.relaxed.gpu.global.u32 [%0], %1;" ::"l"(&g_flag[bb * 64 + 34 + IT_HALF(e)]),
                                         "r"(epoch * 64 + IT_H1(e))
                                         : "memory");
                        const int cc0 = IT_BR(e) * 640 + IT_HALF(e) * (wide ? 320 : 128);
                        uint32_t xs = wide ? 0 : (3 * (IT_H1(e) - IT_H0(e))) % 5;
#pragma unroll 1
                        for (int m = 0; m < (wide ? 5 : 2); m++) {
                            asm volatile("cp.async.bulk.tensor.2d.global.shared::cta.bulk_group [%0, {%2,%3}], [%1];" ::"l"(&P.out),
                                         "r"(sb + OFF_R + xs * XS), "r"(cc0 + m * 64), "r"((int)IT_B(e) * 160)
                                         : "memory");
                            asm volatile("cp.async.bulk.commit_group;" ::: "memory");
                            if (++xs == 5) xs = 0;
                        }
                        if (wide) {
#define REL(N)                                                          \
    asm volatile("cp.async.bulk.wait_group.read %0;" ::"n"(4 - N) : "memory"); \
    asm volatile("mbarrier.arrive.shared::cta.b64 _, [%0], 8;" ::"r"(sb + BAR_XEMPTY + N * 8) : "memory");
                            REL(0) REL(1) REL(2) REL(3) REL(4)
#undef REL
                        }
                        if (IT_PART(e)) {
                            asm volatile("cp.async.bulk.wait_group 0;" ::: "memory");
                            asm volatile("fence.proxy.async;" ::: "memory");
                        }
                    }
                    if (IT_TYPE(e) == IT_QA || IT_PART(e)) {
                        unsigned int* f = &g_flag[bb * 64 + (IT_TYPE(e) == IT_QA ? IT_H0(e) : 32 + IT_HALF(e))];
                        asm volatile("st.release.gpu.global.u32 [%0], %1;" ::"l"(f), "r"(epoch) : "memory");
                    }
                }
                __syncwarp();
            }
            if (threadIdx.x == 64) asm volatile("cp.async.bulk.wait_group 0;" ::: "memory");
            __syncwarp();
            asm volatile("barrier.cluster.arrive.relaxed.aligned;\nbarrier.cluster.wait.aligned;" ::: "memory");
        } else {
            const uint32_t lane = threadIdx.x & 31, p = lane >> 2;
            const uint32_t epoch = next_epoch(3);
#pragma unroll 1
            for (int it = 0;; it++) {
                const uint32_t e = get_item_warp(sb, it, dl);
                if (e == 0) break;
                if (IT_TYPE(e) != IT_QA) continue;
                nb_sync<NB_QK, 160>();
                const uint32_t co = (((lane & 3) * 2) ^ p) << 4;
                const uint32_t ka = sb + OFF_RING + lds_u(sb + OFF_GM + 4) * SLOT + p * (9 * 128) + co;
                const uint32_t qa = sb + OFF_R + p * (17 * 128) + co;
                uint32_t acc = 0;
#pragma unroll 1
                for (int c = 0; c < 3; c++) {
                    if (c == 2) nb_sync<NB_Q2, 288>();
                    const uint4 k0 = lds_u4(ka + c * 8192), q0 = lds_u4(qa + c * XS);
                    acc = fma_bf2(k0.x, q0.x, fma_bf2(k0.y, q0.y, fma_bf2(k0.z, q0.z, fma_bf2(k0.w, q0.w, acc))));
                    const uint4 k1 = lds_u4((ka + c * 8192) ^ 16), q1 = lds_u4((qa + c * XS) ^ 16);
                    acc = fma_bf2(k1.x, q1.x, fma_bf2(k1.y, q1.y, fma_bf2(k1.z, q1.z, fma_bf2(k1.w, q1.w, acc))));
                }
                float d = __uint_as_float(acc << 16) + __uint_as_float(acc & 0xffff0000u);
                d += __shfl_xor_sync(0xffffffffu, d, 1);
                d += __shfl_xor_sync(0xffffffffu, d, 2);
                int key = __float_as_int(d);
                key ^= (key >> 31) & 0x7fffffff;
                key = __reduce_max_sync(0xffffffffu, key);
                key ^= (key >> 31) & 0x7fffffff;
                sts_f(sb + OFF_GM, __int_as_float(key) * SM_C);
                nb_arrive<NB_REF, 160>();
                if (IT_DEP(e)) {
                    const uint32_t g = IT_DEP(e) - 1, need = epoch * 64 + (g & 31) + 1;
                    const unsigned int* cp = &g_flag[((g >> 5) * 16 + IT_B(e)) * 64 + 34 + (lane & 1)];
                    for (uint32_t n = 0;; n++) {
                        uint32_t v;
                        asm volatile("ld.acquire.gpu.global.u32 %0, [%1];" : "=r"(v) : "l"(cp) : "memory");
                        if (__all_sync(0xffffffffu, v - need < 64)) break;
                        if (n > 0x800000) __trap();
                        __nanosleep(500);
                    }
                }
                nb_sync<NB_L, 160>();
                bool bad = false;
#pragma unroll
                for (int c = 0; c < 5; c++) {
                    const uint32_t la = sb + OFF_LX + (c * 32 + lane) * 4;
                    const float v = (__uint_as_float(lds_u(la)) + __uint_as_float(lds_u(la + 640))) +
                                    (__uint_as_float(lds_u(la + 1280)) + __uint_as_float(lds_u(la + 1920)));
                    const float inv = __fdividef(1.f, v);
                    const uint32_t hi = pack_bf16(inv, 0.f), lo = pack_bf16(inv - __uint_as_float(hi << 16), 0.f);
                    const uint32_t ia = sb + OFF_LINV + c * 128 + ((lane >> 1) & 3) * 32 + (lane >> 3) * 8 + (lane & 1) * 2;
                    asm volatile("st.shared.u16 [%0], %1;\nst.shared.u16 [%0+4], %2;" ::"r"(ia), "h"((unsigned short)hi), "h"((unsigned short)lo) : "memory");
                    bad |= !(v >= 5.421010862e-20f && v <= 1.8446744e19f);
                }
                sts_u(sb + OFF_FB, __any_sync(0xffffffffu, bad));
                nb_arrive<NB_VOTE, 160>();
                nb_arrive<NB_VOTE + 1, 160>();
            }
        }
    } else if (wgid == 1) {
        asm volatile("setmaxnreg.inc.sync.aligned.u32 240;");
        consumer<0>(P, sb, dl);
    } else {
        asm volatile("setmaxnreg.inc.sync.aligned.u32 240;");
        consumer<1>(P, sb, dl);
    }
}

typedef CUresult (*EncFn)(CUtensorMap*, CUtensorMapDataType, cuuint32_t, void*, const cuuint64_t*, const cuuint64_t*,
                          const cuuint32_t*, const cuuint32_t*, CUtensorMapInterleave, CUtensorMapSwizzle,
                          CUtensorMapL2promotion, CUtensorMapFloatOOBfill);

void make_map3(EncFn enc, CUtensorMap* m, void* p, uint64_t rows, uint64_t rowbytes, uint64_t nblk, uint32_t boxrows,
               uint32_t boxblk) {
    cuuint64_t dims[3] = {64, rows, nblk};
    cuuint64_t str[2] = {rowbytes, 128};
    cuuint32_t box[3] = {64, boxrows, boxblk};
    cuuint32_t es[3] = {1, 1, 1};
    enc(m, CU_TENSOR_MAP_DATA_TYPE_BFLOAT16, 3, p, dims, str, box, es, CU_TENSOR_MAP_INTERLEAVE_NONE,
        CU_TENSOR_MAP_SWIZZLE_128B, CU_TENSOR_MAP_L2_PROMOTION_NONE, CU_TENSOR_MAP_FLOAT_OOB_FILL_NONE);
}

constexpr int tune(const char*, int def) { return def; }

void build_schedule(Params& P) {
    const int mode = tune("MODE", 4), dmax = tune("DMAX", 24900), n0 = tune("N0", 6);
    const int H0[8] = {18, 17, 20, 21, 22, 23, 23, 24}, P0[8] = {383, 371, 344, 348, 354, 345, 348, 336};
    const int ng = tune("NG", 0), d0 = tune("D0", 0), nkeep = tune("NKEEP", 0), odmax = tune("ODMAX", 6000);
    const int ong = tune("ONG", 0), od0 = tune("OD0", 0), jit = tune("JIT", 0);
    const int npos = tune("NPOS", 0), nearly = tune("NEARLY", 0);
    const int ra = tune("RA", 10), ga = tune("GA", 32), rb = tune("RB", 12), g1 = tune("G1", 58);
    int dep[64];
    for (int g = 0, ns = 0, live = 0; g < 64; g++) {
        const bool fresh = mode < 3 || g >= g1 || live < (g < ga ? ra : rb);
        dep[g] = fresh ? 0 : g - live + 1;
        P.slot[g] = fresh ? ns++ : P.slot[g - live];
        live += fresh;
    }
    int u = 0;
    auto unit = [&]() {
        const uint32_t e = mk_item(IT_QA, u >> 8, (u & 7) * 2, (u >> 3) & 31, P.slot[u >> 3], 0) | (dep[u >> 3] << 23);
        u++;
        return e;
    };
    int qa[NCL], nq = 0, op[NCL], no = 0;
    for (int c = 0; c < NCL; c++) {
        P.cl[c].delay = 0;
        for (int i = 0; i < NSTAT; i++) P.cl[c].items[i] = 0;
        if (mode >= 3 && c < 64 && (c & 3) == 3) op[no++] = c;
        else if (mode != 2 || (c & 3) == 0) qa[nq++] = c;
    }
    for (int t = 0; t < no; t++) {
        P.cl[op[t]].items[1] = mk_item(IT_OP, 0, t & ~1, 0, 32, t & 1);
        P.cl[op[t]].items[2] = IT_DYN;
        P.cl[op[t]].delay = ong ? od0 + (t * ong / 16) * (odmax / ong) : od0 + t * odmax / 16;
    }
    for (int k = 0; k < nq; k++) {
        const int c = qa[(k * 19) % nq];
        P.cl[c].items[1] = P.cl[c].items[2] = IT_DYN;
        P.cl[c].delay = k < n0 ? 0 : (int)((long long)dmax * (k + 1 - n0) / (nq - n0));
        if (ng) P.cl[c].delay = d0 + (k * ng / nq) * (dmax / ng) + (k * ng % nq) * jit / nq;
    }
    for (int k = 0; k < no + nq; k++) {
        int best = -1;
        for (int c = 0; c < NCL; c++)
            if (P.cl[c].items[1] && !P.cl[c].items[0] && (best < 0 || P.cl[c].delay < P.cl[best].delay)) best = c;
        P.cl[best].items[0] = unit();
    }
    int H[8], pos[8];
    for (int b = 0; b < 8; b++) {
        char nh[3] = {'H', (char)('0' + b), 0}, np[3] = {'P', (char)('0' + b), 0};
        H[b] = tune(nh, H0[b]);
        pos[b] = tune(np, P0[b]);
        for (int g = 0; g < 64; g++)
            if (dep[g] > 32) {
                if (pos[b] > 8 * g) pos[b] = 8 * g;
                if (H[b] < dep[g] - 32) H[b] = dep[g] - 32;
            }
        if (b < nkeep && no) {
            pos[b] = -1;
            P.cl[op[14 - 2 * b]].items[2] = mk_item(IT_OP, 1, 2 * b, 0, H[b], 0, 1);
            P.cl[op[15 - 2 * b]].items[2] = mk_item(IT_OP, 1, 2 * b, 0, H[b], 1, 1);
        }
    }
    int n = 0, kn = 0;
    const int uend = mode == 2 ? 8 * nq : 512;
    while (u < uend) {
        for (int b = 0; b < 8 && no; b++)
            if (pos[b] == u) {
                P.list[n++] = mk_item(IT_OP, 1, 2 * b, 0, H[b], 0, 1);
                P.list[n++] = mk_item(IT_OP, 1, 2 * b, 0, H[b], 1, 1);
            }
        while (no && u >= uend - npos && kn * npos < (u + 1 - (uend - npos)) * nearly) {
            P.list[n++] = mk_item(IT_ON, 1, kn / 5 * 2, H[kn / 5], 32, kn % 5);
            kn++;
        }
        P.list[n++] = unit();
    }
    for (; no && kn < 40; kn++) P.list[n++] = mk_item(IT_ON, 1, kn / 5 * 2, H[kn / 5], 32, kn % 5);
    P.nlist = n;
}

}

extern "C" void kernel_launch(void* const* d_in, const int* in_sizes, int n_in, void* d_out, int out_size) {
    static Params P;
    static bool init = false;
    if (!init) {
        EncFn enc = nullptr;
        cudaDriverEntryPointQueryResult qr;
        cudaGetDriverEntryPoint("cuTensorMapEncodeTiled", (void**)&enc, cudaEnableDefault, &qr);
        for (int i = 0; i < 2; i++) {
            P.px[i] = (const __nv_bfloat16*)d_in[5 * i + 0];
            P.pk[i] = (const __nv_bfloat16*)d_in[5 * i + 1];
            P.pv[i] = (const __nv_bfloat16*)d_in[5 * i + 2];
            P.pwq[i] = (const __nv_bfloat16*)d_in[5 * i + 3];
            make_map3(enc, &P.x[i], d_in[5 * i + 0], 2560, 1280, 10, 160, 1);
            make_map3(enc, &P.k[i], d_in[5 * i + 1], 16 * 32 * 512, 384, 3, 64, 3);
            make_map3(enc, &P.v[i], d_in[5 * i + 2], 16 * 32 * 512, 384, 3, 64, 3);
            make_map3(enc, &P.wq[i], d_in[5 * i + 3], 640, 12288, 96, 32, 3);
            make_map3(enc, &P.wo[i], d_in[5 * i + 4], 6144, 1280, 10, 16, 5);
            make_map3(enc, &P.won[i], d_in[5 * i + 4], 6144, 1280, 10, 32, 2);
        }
        cuuint64_t dims[2] = {1280, 2560};
        cuuint64_t str[1] = {2560};
        cuuint32_t box[2] = {64, 160};
        cuuint32_t es[2] = {1, 1};
        enc(&P.out, CU_TENSOR_MAP_DATA_TYPE_BFLOAT16, 2, d_out, dims, str, box, es, CU_TENSOR_MAP_INTERLEAVE_NONE,
            CU_TENSOR_MAP_SWIZZLE_128B, CU_TENSOR_MAP_L2_PROMOTION_NONE, CU_TENSOR_MAP_FLOAT_OOB_FILL_NONE);
        build_schedule(P);
        cudaFuncSetAttribute(fused_kernel, cudaFuncAttributeMaxDynamicSharedMemorySize, SMEM_LAUNCH);
        init = true;
    }
    fused_kernel<<<NCTA, 384, SMEM_LAUNCH>>>(P);
}
```

```cpp
#include <cuda_runtime.h>
#include <cuda.h>
#include <cuda_bf16.h>
#include <stdint.h>

namespace {

constexpr int NCTA = 132;
constexpr int NCL = NCTA / 2;
constexpr int MAXI = 16;
constexpr int NSTAT = 3;
constexpr uint32_t IT_DYN = 0xffffffffu;
constexpr int SLOT = 24576;
constexpr int NSLOT = 5;
constexpr int XS = 20480;
constexpr int OFF_R = 0;
constexpr int OFF_RING = 5 * XS;
constexpr int OFF_MISC = OFF_RING + NSLOT * SLOT;
constexpr int OFF_LX = OFF_MISC;
constexpr int OFF_LINV = OFF_LX + 2560;
constexpr int OFF_FB = OFF_LINV + 640;
constexpr int OFF_GM = OFF_FB + 16;
constexpr int OFF_BAR = OFF_GM + 16;
constexpr int BAR_RFULL = OFF_BAR;
constexpr int BAR_REMPTY = BAR_RFULL + 40;
constexpr int BAR_XFULL = BAR_REMPTY + 40;
constexpr int BAR_XEMPTY = BAR_XFULL + 40;
constexpr int BAR_PRDY = BAR_XEMPTY + 40;
constexpr int BAR_ITEM = BAR_PRDY + 40;
constexpr int OFF_ITEM = BAR_ITEM + MAXI * 8;
constexpr int SMEM_BYTES = OFF_ITEM + MAXI * 4;
static_assert(SMEM_BYTES <= 232448, "smem");

constexpr int NB_W = 1  , NB_PFULL = 3  , NB_VOTE = 5  , NB_Q2 = 7, NB_SDONE = 8, NB_PDONE = 9,
              NB_L = 10, NB_REF = 11, NB_ODONE = 12, NB_OPEND = 13, NB_LX = 14, NB_Q01 = 15, NB_QK = 0  ;

constexpr uint32_t IT_QA = 1, IT_OP = 2, IT_ON = 3;
__host__ __device__ constexpr uint32_t mk_item(uint32_t type, uint32_t br, uint32_t b, uint32_t h0, uint32_t h1, uint32_t half,
                                               uint32_t part = 0) {
    return type | (br << 2) | (b << 3) | (h0 << 7) | (h1 << 13) | (half << 19) | (part << 22);
}
#define IT_TYPE(e) ((e) & 3u)
#define IT_BR(e) (((e) >> 2) & 1u)
#define IT_B(e) (((e) >> 3) & 15u)
#define IT_H0(e) (((e) >> 7) & 63u)
#define IT_H1(e) (((e) >> 13) & 63u)
#define IT_HALF(e) (((e) >> 19) & 7u)
#define IT_PART(e) (((e) >> 22) & 1u)
#define IT_SLOT(e) IT_H1(e)
#define IT_DEP(e) (((e) >> 23) & 127u)

struct Params {
    CUtensorMap x[2], wq[2], k[2], v[2], wo[2], won[2], out;
    const __nv_bfloat16 *px[2], *pwq[2], *pk[2], *pv[2];
    struct alignas(16) { uint32_t delay, items[NSTAT]; } cl[NCL];
    uint32_t nlist;
    uint8_t slot[64];
    uint32_t list[512];
};

constexpr int OUNIT = 61440;
__device__ __align__(1024) unsigned char g_ostash[(size_t)1024 * OUNIT];
__device__ unsigned int g_flag[32 * 64];
__device__ __forceinline__ unsigned char* ostash(uint32_t slot, uint32_t b) { return g_ostash + (slot * 16 + b) * OUNIT; }
__device__ unsigned int g_epoch[NCTA * 4];
__device__ unsigned int g_ticket[2];

constexpr int SMEM_LAUNCH = SMEM_BYTES;
#define TS(role, idx)
#define TS_ITEM(e)
#define TS_DUMP(role)
#define TSD(role, idx)

#define POL_W 2
#define POL_X 2
#define POL_O 2
template <int M>
__device__ __forceinline__ uint64_t mkpol() {
    uint64_t p;
    if (M == 0) asm volatile("createpolicy.fractional.L2::evict_normal.b64 %0, 1.0;" : "=l"(p));
    if (M == 1) asm volatile("createpolicy.fractional.L2::evict_first.b64 %0, 1.0;" : "=l"(p));
    if (M == 2) asm volatile("createpolicy.fractional.L2::evict_unchanged.b64 %0, 1.0;" : "=l"(p));
    if (M == 3) asm volatile("createpolicy.fractional.L2::evict_normal.L2::evict_unchanged.b64 %0, 0.25;" : "=l"(p));
    return p;
}
#define STSM_W 1
#define XLATE 2
#define PV0FIRST 1
#define QST0 1
#define QST1 2
#define QHOLD 8
constexpr float SM_C = 0.07216878364870322f * 1.4426950408889634f;

__device__ __forceinline__ uint32_t next_epoch(int warp) {
    unsigned int* p = &g_epoch[blockIdx.x * 4 + warp];
    const uint32_t e = __ldcg(p) + 1;
    *p = e;
    return e;
}

__device__ __forceinline__ uint32_t tid_now() {
    uint32_t t;
    asm volatile("mov.u32 %0, %%tid.x;" : "=r"(t));
    return t;
}
__device__ __forceinline__ void mbar_init(uint32_t a, uint32_t c) {
    asm volatile("mbarrier.init.shared::cta.b64 [%0], %1;" ::"r"(a), "r"(c) : "memory");
}
__device__ __forceinline__ void mbar_expect(uint32_t a, uint32_t b) {
    asm volatile("mbarrier.arrive.expect_tx.shared::cta.b64 _, [%0], %1;" ::"r"(a), "r"(b) : "memory");
}
template <int CNT = 1>
__device__ __forceinline__ void mbar_arrive_warp(uint32_t a) {
    if (CNT == 1)
        asm volatile("{\n.reg .pred p;\nelect.sync _|p, 0xffffffff;\n@p mbarrier.arrive.shared::cta.b64 _, [%0];\n}" ::"r"(a) : "memory");
    else
        asm volatile(
            "{\n.reg .pred p;\nelect.sync _|p, 0xffffffff;\n@p mbarrier.arrive.shared::cta.b64 _, [%0];\n"
            "@p mbarrier.arrive.shared::cta.b64 _, [%0];\n}" ::"r"(a)
            : "memory");
}
template <int CNT = 1>
__device__ __forceinline__ void mbar_arrive_warp_if(uint32_t a, bool cond) {
    if (CNT == 1)
        asm volatile(
            "{\n.reg .pred p, c;\nelect.sync _|p, 0xffffffff;\nsetp.ne.and.u32 c, %1, 0, p;\n"
            "@c mbarrier.arrive.shared::cta.b64 _, [%0];\n}" ::"r"(a), "r"((uint32_t)cond)
            : "memory");
    else
        asm volatile(
            "{\n.reg .pred p, c;\nelect.sync _|p, 0xffffffff;\nsetp.ne.and.u32 c, %1, 0, p;\n"
            "@c mbarrier.arrive.shared::cta.b64 _, [%0];\n@c mbarrier.arrive.shared::cta.b64 _, [%0];\n}" ::"r"(a), "r"((uint32_t)cond)
            : "memory");
}
__device__ __forceinline__ uint32_t deadline() {
    uint32_t c;
    asm volatile("mov.u32 %0, %%clock_hi;" : "=r"(c));
    return c + 4;
}
__device__ __forceinline__ void mbar_wait(uint32_t a, uint32_t ph, uint32_t dl) {
    asm volatile(
        "{\n.reg .pred p;\n.reg .u32 m;\n"
        "LOOP:\n"
        "mbarrier.try_wait.parity.shared::cta.b64 p, [%0], %1;\n"
        "@p bra DONE;\n"
        "mov.u32 m, %%clock_hi;\n"
        "setp.ne.u32 p, m, %2;\n"
        "@p bra LOOP;\n"
        "trap;\n"
        "DONE:\n}" ::"r"(a), "r"(ph), "r"(dl)
        : "memory");
}
template <int ID, int CNT>
__device__ __forceinline__ void nb_sync() { asm volatile("bar.sync %0, %1;" ::"n"(ID), "n"(CNT) : "memory"); }
template <int ID, int CNT>
__device__ __forceinline__ void nb_arrive() { asm volatile("bar.arrive %0, %1;" ::"n"(ID), "n"(CNT) : "memory"); }
__device__ __forceinline__ void fence_async_smem() { asm volatile("fence.proxy.async.shared::cta;" ::: "memory"); }

__device__ __forceinline__ void tma3(uint32_t dst, const CUtensorMap* m, int c1, int c2, uint32_t bar, uint64_t pol) {
    asm volatile(
        "cp.async.bulk.tensor.3d.shared::cluster.global.mbarrier::complete_tx::bytes.L2::cache_hint [%0], [%1, {%3,%4,%5}], [%2], %6;" ::"r"(dst),
        "l"(m), "r"(bar), "r"(0), "r"(c1), "r"(c2), "l"(pol)
        : "memory");
}
__device__ __forceinline__ void tma3_mc(uint32_t dst, const CUtensorMap* m, int c1, int c2, uint32_t bar, uint64_t pol) {
    asm volatile(
        "cp.async.bulk.tensor.3d.shared::cluster.global.mbarrier::complete_tx::bytes.multicast::cluster.L2::cache_hint"
        " [%0], [%1, {%3,%4,%5}], [%2], %6, %7;" ::"r"(dst),
        "l"(m), "r"(bar), "r"(0), "r"(c1), "r"(c2), "h"((unsigned short)3), "l"(pol)
        : "memory");
}
__device__ __forceinline__ void bulk_load(uint32_t dst, const void* src, uint32_t bytes, uint32_t bar, uint64_t pol) {
    asm volatile("cp.async.bulk.shared::cluster.global.mbarrier::complete_tx::bytes.L2::cache_hint [%0], [%1], %2, [%3], %4;" ::"r"(dst),
                 "l"(src), "r"(bytes), "r"(bar), "l"(pol)
                 : "memory");
}
__device__ __forceinline__ void wg_fence() { asm volatile("wgmma.fence.sync.aligned;" ::: "memory"); }
__device__ __forceinline__ void wg_commit() { asm volatile("wgmma.commit_group.sync.aligned;" ::: "memory"); }
template <int N>
__device__ __forceinline__ void wg_wait() { asm volatile("wgmma.wait_group.sync.aligned %0;" ::"n"(N) : "memory"); }

#define RW80(c, d) c(d[0]), c(d[1]), c(d[2]), c(d[3]), c(d[4]), c(d[5]), c(d[6]), c(d[7]), c(d[8]), c(d[9]), c(d[10]), c(d[11]), c(d[12]), c(d[13]), c(d[14]), c(d[15]), c(d[16]), c(d[17]), c(d[18]), c(d[19]), c(d[20]), c(d[21]), c(d[22]), c(d[23]), c(d[24]), c(d[25]), c(d[26]), c(d[27]), c(d[28]), c(d[29]), c(d[30]), c(d[31]), c(d[32]), c(d[33]), c(d[34]), c(d[35]), c(d[36]), c(d[37]), c(d[38]), c(d[39]), c(d[40]), c(d[41]), c(d[42]), c(d[43]), c(d[44]), c(d[45]), c(d[46]), c(d[47]), c(d[48]), c(d[49]), c(d[50]), c(d[51]), c(d[52]), c(d[53]), c(d[54]), c(d[55]), c(d[56]), c(d[57]), c(d[58]), c(d[59]), c(d[60]), c(d[61]), c(d[62]), c(d[63]), c(d[64]), c(d[65]), c(d[66]), c(d[67]), c(d[68]), c(d[69]), c(d[70]), c(d[71]), c(d[72]), c(d[73]), c(d[74]), c(d[75]), c(d[76]), c(d[77]), c(d[78]), c(d[79])
#define RW48(c, d) c(d[0]), c(d[1]), c(d[2]), c(d[3]), c(d[4]), c(d[5]), c(d[6]), c(d[7]), c(d[8]), c(d[9]), c(d[10]), c(d[11]), c(d[12]), c(d[13]), c(d[14]), c(d[15]), c(d[16]), c(d[17]), c(d[18]), c(d[19]), c(d[20]), c(d[21]), c(d[22]), c(d[23]), c(d[24]), c(d[25]), c(d[26]), c(d[27]), c(d[28]), c(d[29]), c(d[30]), c(d[31]), c(d[32]), c(d[33]), c(d[34]), c(d[35]), c(d[36]), c(d[37]), c(d[38]), c(d[39]), c(d[40]), c(d[41]), c(d[42]), c(d[43]), c(d[44]), c(d[45]), c(d[46]), c(d[47])
#define RW32(c, d) c(d[0]), c(d[1]), c(d[2]), c(d[3]), c(d[4]), c(d[5]), c(d[6]), c(d[7]), c(d[8]), c(d[9]), c(d[10]), c(d[11]), c(d[12]), c(d[13]), c(d[14]), c(d[15]), c(d[16]), c(d[17]), c(d[18]), c(d[19]), c(d[20]), c(d[21]), c(d[22]), c(d[23]), c(d[24]), c(d[25]), c(d[26]), c(d[27]), c(d[28]), c(d[29]), c(d[30]), c(d[31])

__device__ __forceinline__ void reg_fence(float (&d)[80]) { asm volatile("" : RW80("+f", d)::"memory"); }
__device__ __forceinline__ void reg_fence(float (&d)[48]) { asm volatile("" : RW48("+f", d)::"memory"); }
__device__ __forceinline__ void reg_fence(float (&d)[32]) { asm volatile("" : RW32("+f", d)::"memory"); }

template <int NR>
__device__ __forceinline__ void zero(float (&d)[NR]) {
#pragma unroll
    for (int i = 0; i < NR; i++) d[i] = 0.f;
}

constexpr uint32_t HI_SW128 = (1024u >> 4) | (1u << 30);
constexpr uint32_t HI_OST = (2560u >> 4) | (2u << 30);
constexpr uint32_t LO_LBO1 = (1u << 16);
constexpr uint32_t LO_OST = ((512u >> 4) << 16);

template <int TA, int TB, uint32_t HIB, int ACC>
__device__ __forceinline__ void wgmma(float (&d)[80], uint32_t loA, uint32_t loB) {
#define WG_ASM(SD)                                                          \
    "{\n.reg .b64 da, db;\nmov.b64 da, {%80, %82};\nmov.b64 db, {%81, %83};\n" \
    "wgmma.mma_async.sync.aligned.m64n160k16.f32.bf16.bf16 "               \
    "{%0,%1,%2,%3,%4,%5,%6,%7,%8,%9,%10,%11,%12,%13,%14,%15,%16,%17,%18,%19,%20,%21,%22,%23,%24,%25,%26,%27,%28,%29,%30,%31,%32,%33,%34,%35,%36,%37,%38,%39,%40,%41,%42,%43,%44,%45,%46,%47,%48,%49,%50,%51,%52,%53,%54,%55,%56,%57,%58,%59,%60,%61,%62,%63,%64,%65,%66,%67,%68,%69,%70,%71,%72,%73,%74,%75,%76,%77,%78,%79}, da, db, " SD ", 1, 1, %84, %85;\n}"
    if constexpr (ACC == 2)
        asm volatile(WG_ASM("0") : RW80("+f", d) : "r"(loA), "r"(loB), "n"(HI_SW128), "n"(HIB), "n"(TA), "n"(TB));
    else if constexpr (ACC == 1)
        asm volatile(WG_ASM("1") : RW80("+f", d) : "r"(loA), "r"(loB), "n"(HI_SW128), "n"(HIB), "n"(TA), "n"(TB));
    else
        asm volatile(WG_ASM("0") : RW80("=f", d) : "r"(loA), "r"(loB), "n"(HI_SW128), "n"(HIB), "n"(TA), "n"(TB));
#undef WG_ASM
}
template <int TA, int TB, uint32_t HIB, int ACC>
__device__ __forceinline__ void wgmma(float (&d)[48], uint32_t loA, uint32_t loB) {
#define WG_ASM(SD)                                                          \
    "{\n.reg .b64 da, db;\nmov.b64 da, {%48, %50};\nmov.b64 db, {%49, %51};\n" \
    "wgmma.mma_async.sync.aligned.m64n96k16.f32.bf16.bf16 "               \
    "{%0,%1,%2,%3,%4,%5,%6,%7,%8,%9,%10,%11,%12,%13,%14,%15,%16,%17,%18,%19,%20,%21,%22,%23,%24,%25,%26,%27,%28,%29,%30,%31,%32,%33,%34,%35,%36,%37,%38,%39,%40,%41,%42,%43,%44,%45,%46,%47}, da, db, " SD ", 1, 1, %52, %53;\n}"
    if constexpr (ACC == 1)
        asm volatile(WG_ASM("1") : RW48("+f", d) : "r"(loA), "r"(loB), "n"(HI_SW128), "n"(HIB), "n"(TA), "n"(TB));
    else
        asm volatile(WG_ASM("0") : RW48("=f", d) : "r"(loA), "r"(loB), "n"(HI_SW128), "n"(HIB), "n"(TA), "n"(TB));
#undef WG_ASM
}
template <int TA, int TB, uint32_t HIB, int ACC>
__device__ __forceinline__ void wgmma(float (&d)[32], uint32_t loA, uint32_t loB) {
#define WG_ASM(SD)                                                          \
    "{\n.reg .b64 da, db;\nmov.b64 da, {%32, %34};\nmov.b64 db, {%33, %35};\n" \
    "wgmma.mma_async.sync.aligned.m64n64k16.f32.bf16.bf16 "               \
    "{%0,%1,%2,%3,%4,%5,%6,%7,%8,%9,%10,%11,%12,%13,%14,%15,%16,%17,%18,%19,%20,%21,%22,%23,%24,%25,%26,%27,%28,%29,%30,%31}, da, db, " SD ", 1, 1, %36, %37;\n}"
    if constexpr (ACC == 1)
        asm volatile(WG_ASM("1") : RW32("+f", d) : "r"(loA), "r"(loB), "n"(HI_SW128), "n"(HIB), "n"(TA), "n"(TB));
    else
        asm volatile(WG_ASM("0") : RW32("=f", d) : "r"(loA), "r"(loB), "n"(HI_SW128), "n"(HIB), "n"(TA), "n"(TB));
#undef WG_ASM
}

__device__ __forceinline__ uint32_t pack_bf16(float lo, float hi) {
    uint32_t r;
    asm("cvt.rn.bf16x2.f32 %0, %1, %2;" : "=r"(r) : "f"(hi), "f"(lo));
    return r;
}
__device__ __forceinline__ float ex2(float x) {
    float r;
    asm("ex2.approx.ftz.f32 %0, %1;" : "=f"(r) : "f"(x));
    return r;
}
__device__ __forceinline__ void stsm4t(uint32_t a, uint32_t r0, uint32_t r1, uint32_t r2, uint32_t r3) {
    asm volatile("stmatrix.sync.aligned.m8n8.x4.trans.shared.b16 [%0], {%1,%2,%3,%4};" ::"r"(a), "r"(r0), "r"(r1), "r"(r2), "r"(r3)
                 : "memory");
}
__device__ __forceinline__ uint32_t lds_u(uint32_t a) {
    uint32_t v;
    asm volatile("ld.shared.u32 %0, [%1];" : "=r"(v) : "r"(a) : "memory");
    return v;
}
__device__ __forceinline__ uint4 lds_u4(uint32_t a) {
    uint4 v;
    asm volatile("ld.shared.v4.u32 {%0,%1,%2,%3}, [%4];" : "=r"(v.x), "=r"(v.y), "=r"(v.z), "=r"(v.w) : "r"(a) : "memory");
    return v;
}
__device__ __forceinline__ float2 lds_f2(uint32_t a) {
    float2 v;
    asm volatile("ld.shared.v2.f32 {%0,%1}, [%2];" : "=f"(v.x), "=f"(v.y) : "r"(a) : "memory");
    return v;
}
__device__ __forceinline__ void sts_f(uint32_t a, float v) { asm volatile("st.shared.f32 [%0], %1;" ::"r"(a), "f"(v) : "memory"); }
__device__ __forceinline__ void sts_u(uint32_t a, uint32_t v) { asm volatile("st.shared.u32 [%0], %1;" ::"r"(a), "r"(v) : "memory"); }
__device__ __forceinline__ void sts_f2(uint32_t a, float x, float y) {
    asm volatile("st.shared.v2.f32 [%0], {%1,%2};" ::"r"(a), "f"(x), "f"(y) : "memory");
}

__device__ __forceinline__ void store_tile_t(const float (&d)[80], uint32_t addr) {
#pragma unroll
    for (int j = 0; j < 10; j++)
        stsm4t(addr + j * 2048, pack_bf16(d[8 * j], d[8 * j + 1]), pack_bf16(d[8 * j + 2], d[8 * j + 3]),
               pack_bf16(d[8 * j + 4], d[8 * j + 5]), pack_bf16(d[8 * j + 6], d[8 * j + 7]));
}
template <bool ADD, int NR>
__device__ __forceinline__ void store_out_tile(const float (&d)[NR], uint32_t base, uint32_t lane, uint32_t w) {
    const uint32_t mi = lane >> 3, i = lane & 7;
    const uint32_t chunk = 2 * w + (mi & 1);
    const uint32_t q0 = 8 * (i >> 1) + 2 * (mi >> 1) + (i & 1);
    const uint32_t a0 = base + q0 * 128 + ((chunk ^ (q0 & 7)) << 4);
    const uint32_t a1 = base + (q0 + 4) * 128 + ((chunk ^ ((q0 + 4) & 7)) << 4);
    uint32_t p[NR / 2];
    if (ADD) {
#pragma unroll
        for (int j = 0; j < NR / 8; j++)
            asm volatile("ldmatrix.sync.aligned.m8n8.x4.trans.shared.b16 {%0,%1,%2,%3}, [%4];"
                         : "=r"(p[4 * j]), "=r"(p[4 * j + 1]), "=r"(p[4 * j + 2]), "=r"(p[4 * j + 3])
                         : "r"(((j & 1) ? a1 : a0) + (j >> 1) * 4096)
                         : "memory");
    }
#pragma unroll
    for (int k = 0; k < NR / 2; k++)
        p[k] = ADD ? pack_bf16(d[2 * k] + __uint_as_float(p[k] << 16), d[2 * k + 1] + __uint_as_float(p[k] & 0xffff0000u))
                   : pack_bf16(d[2 * k], d[2 * k + 1]);
#pragma unroll
    for (int j = 0; j < NR / 8; j++)
        stsm4t(((j & 1) ? a1 : a0) + (j >> 1) * 4096, p[4 * j], p[4 * j + 1], p[4 * j + 2], p[4 * j + 3]);
}

struct TrueT { static constexpr bool value = true; };
struct FalseT { static constexpr bool value = false; };

template <int V>
struct IntT { static constexpr int value = V; };

__device__ __forceinline__ uint32_t get_item(uint32_t sb, int it, uint32_t dl) {
    mbar_wait(sb + BAR_ITEM + it * 8, 0, dl);
    return lds_u(sb + OFF_ITEM + it * 4);
}
__device__ __forceinline__ uint32_t get_item_warp(uint32_t sb, int it, uint32_t dl) {
    return __shfl_sync(0xffffffffu, get_item(sb, it, dl), 0);
}

struct Ring {
    uint32_t slot, ph, dl;
    __device__ __forceinline__ void adv(uint32_t k) {
        slot += k;
        if (slot >= NSLOT) { slot -= NSLOT; ph ^= 1; }
    }
};

template <int K>
__device__ __forceinline__ void qk_step(float (&s)[80], uint32_t loK, uint32_t loQ) {
    wgmma<0, 0, HI_SW128, K != 0>(s, loK + (K >> 2) * (8192 >> 4) + (K & 3) * 2, loQ + (K >> 2) * (XS >> 4) + (K & 3) * 2);
}
template <int K0, int K1>
__device__ __forceinline__ void qk_steps(float (&s)[80], uint32_t loK, uint32_t loQ) {
    if constexpr (K0 < K1) {
        qk_step<K0>(s, loK, loQ);
        qk_steps<K0 + 1, K1>(s, loK, loQ);
    }
}
__device__ __forceinline__ uint32_t add_bf2(uint32_t a, uint32_t b) {
    uint32_t r;
    asm("add.rn.bf16x2 %0, %1, %2;" : "=r"(r) : "r"(a), "r"(b));
    return r;
}
__device__ __forceinline__ uint32_t fma_bf2(uint32_t a, uint32_t b, uint32_t c) {
    uint32_t r;
    asm("fma.rn.bf16x2 %0, %1, %2, %3;" : "=r"(r) : "r"(a), "r"(b), "r"(c));
    return r;
}
template <int J>
__device__ __forceinline__ void exp_block(const float (&s)[80], uint32_t (&k)[40], uint32_t pa, float mref) {
    if constexpr (J < 10) {
#pragma unroll
        for (int i = 4 * J; i < 4 * J + 4; i++)
            k[i] = pack_bf16(ex2(fmaf(s[2 * i], SM_C, -mref)), ex2(fmaf(s[2 * i + 1], SM_C, -mref)));
#pragma unroll
        for (int i = 0; i < 4; i++)
            asm volatile("stmatrix.sync.aligned.m8n8.x1.trans.shared.b16 [%0], {%1};" ::"r"(((i & 1) ? pa ^ 16 : pa) + J * 2048 + (i >> 1) * 1024),
                         "r"(k[4 * J + i])
                         : "memory");
        exp_block<J + 1>(s, k, pa, mref);
    }
}
__device__ __forceinline__ void sum_block(const uint32_t (&k)[40], float (&l)[10], uint32_t lane) {
    const bool b4 = lane & 16, b3 = lane & 8;
    uint32_t ps[20], t[10];
#pragma unroll
    for (int j = 0; j < 20; j++) ps[j] = add_bf2(k[2 * j], k[2 * j + 1]);
#pragma unroll
    for (int j = 0; j < 10; j++)
        t[j] = add_bf2(b4 ? ps[2 * j + 1] : ps[2 * j], __shfl_xor_sync(0xffffffffu, b4 ? ps[2 * j] : ps[2 * j + 1], 16));
#pragma unroll
    for (int i = 0; i < 5; i++) {
        const uint32_t a = b3 ? t[i + 5] : t[i], b = __shfl_xor_sync(0xffffffffu, b3 ? t[i] : t[i + 5], 8);
        l[2 * i] += __uint_as_float(a << 16) + __uint_as_float(b << 16);
        l[2 * i + 1] += __uint_as_float(a & 0xffff0000u) + __uint_as_float(b & 0xffff0000u);
    }
}
template <bool ADD>
__device__ __forceinline__ void sum_store(const float (&l)[10], uint32_t lane, uint32_t lxa) {
    const bool b2 = lane & 4;
    float t[5];
#pragma unroll
    for (int i = 0; i < 5; i++) t[i] = ADD ? __uint_as_float(lds_u(lxa + i * 64)) : 0.f;
#pragma unroll
    for (int i = 0; i < 5; i++)
        sts_f(lxa + i * 64, t[i] + (b2 ? l[2 * i + 1] : l[2 * i]) + __shfl_xor_sync(0xffffffffu, b2 ? l[2 * i] : l[2 * i + 1], 4));
}

__device__ __forceinline__ void fallback_unit(const Params& P, uint32_t e, uint32_t tid) {
    const uint32_t lane = tid & 31, br = IT_BR(e), b = IT_B(e), h = IT_H0(e);
    const __nv_bfloat162* wq = (const __nv_bfloat162*)(P.pwq[br] + h * 192) + lane;
    const __nv_bfloat162* kp = (const __nv_bfloat162*)(P.pk[br] + (size_t)(b * 32 + h) * 512 * 192) + lane;
    const __nv_bfloat162* vp = (const __nv_bfloat162*)(P.pv[br] + (size_t)(b * 32 + h) * 512 * 192) + lane;
#pragma unroll 1
    for (uint32_t qi = 0; qi < 40; qi++) {
        const uint32_t q = 4 * qi + (tid >> 5);
        const __nv_bfloat16* xr = P.px[br] + (size_t)(b * 160 + q) * 640;
        float a[6] = {0.f, 0.f, 0.f, 0.f, 0.f, 0.f};
#pragma unroll 2
        for (int k = 0; k < 640; k++) {
            const float xv = __bfloat162float(xr[k]);
#pragma unroll
            for (int i = 0; i < 3; i++) {
                const float2 wv = __bfloat1622float2(wq[(size_t)k * 3072 + i * 32]);
                a[2 * i] = fmaf(xv, wv.x, a[2 * i]);
                a[2 * i + 1] = fmaf(xv, wv.y, a[2 * i + 1]);
            }
        }
#pragma unroll
        for (int i = 0; i < 6; i++) a[i] = __bfloat162float(__float2bfloat16(a[i]));
        auto score = [&](int key) {
            float d = 0.f;
#pragma unroll
            for (int i = 0; i < 3; i++) {
                const float2 kv = __bfloat1622float2(kp[key * 96 + i * 32]);
                d = fmaf(a[2 * i], kv.x, fmaf(a[2 * i + 1], kv.y, d));
            }
#pragma unroll
            for (int o = 16; o > 0; o >>= 1) d += __shfl_xor_sync(0xffffffffu, d, o);
            return d;
        };
        float m = -INFINITY, o[6] = {0.f, 0.f, 0.f, 0.f, 0.f, 0.f}, sum = 0.f;
#pragma unroll 1
        for (int n = 0; n < 1024; n++) {
            const int key = n & 511;
            const float d = score(key);
            if (n < 512) {
                m = fmaxf(m, d);
            } else {
                const float p = ex2((d - m) * SM_C);
                sum += p;
#pragma unroll
                for (int i = 0; i < 3; i++) {
                    const float2 vv = __bfloat1622float2(vp[key * 96 + i * 32]);
                    o[2 * i] = fmaf(p, vv.x, o[2 * i]);
                    o[2 * i + 1] = fmaf(p, vv.y, o[2 * i + 1]);
                }
            }
        }
        const float inv = __fdividef(1.f, sum);
        __nv_bfloat16* op = (__nv_bfloat16*)ostash(IT_SLOT(e), b) + (q >> 5) * 256 + 2 * ((q & 31) >> 3) + (q & 1);
#pragma unroll
        for (int i = 0; i < 6; i++) {
            const uint32_t d = (i >> 1) * 64 + 2 * lane + (i & 1);
            op[(d >> 3) * 1280 + (d & 7) * 32 + ((((q & 7) >> 1) ^ ((d & 7) >> 1)) << 3)] = __float2bfloat16(o[i] * inv);
        }
    }
}

template <int W>
struct PendO {
    static constexpr int N = W == 0 ? 56 : 64;
    uint32_t v[N];
    unsigned char* gp;
    static __device__ __forceinline__ uint32_t toff() {
        const uint32_t t = tid_now();
        return ((t >> 5) & 3) * 5120 + ((t >> 2) & 7) * 64 + (((t ^ (t >> 3)) & 3) << 4);
    }
    uint32_t pend, sig;
    static __device__ __forceinline__ void scale(uint32_t& x, uint32_t hi, uint32_t lo) {
        asm("{\n.reg .b32 t;\nmul.rn.bf16x2 t, %0, %2;\nfma.rn.bf16x2 %0, %0, %1, t;\n}" : "+r"(x) : "r"(hi), "r"(lo));
    }
    template <int I, int OFF>
    __device__ __forceinline__ void put() {
        asm volatile("{\n.reg .pred p;\nsetp.ne.u32 p, %6, 0;\n@p st.global.v4.b32 [%0+%5], {%1,%2,%3,%4};\n}" ::"l"(gp), "r"(v[I]),
                     "r"(v[I + 1]), "r"(v[I + 2]), "r"(v[I + 3]), "n"(OFF), "r"(pend)
                     : "memory");
    }
    __device__ __forceinline__ void verdict(const Params& P, uint32_t sb, int ie) {
        if (sig) {
            nb_sync<NB_VOTE + W, 160>();
            pend = !__any_sync(0xffffffffu, lds_u(sb + OFF_FB) != 0);
            if (W == 1 && !pend) {
                fallback_unit(P, lds_u(sb + OFF_ITEM + ie * 4), tid_now() & 127);
                __syncwarp();
            }
        }
    }
    template <int G, int H>
    __device__ __forceinline__ void half(uint32_t sb) {
        constexpr bool T2 = W == 0 ? G >= 3 : G < 3;
        constexpr int B = T2 ? 40 + 8 * (W == 0 ? G - 3 : G) : 0;
        const uint4 a = lds_u4(sb + OFF_LINV + G * 128 + H * 16 + (threadIdx.x & 3) * 32);
#pragma unroll
        for (int i = 2 * H; i < 8; i += 4) {
            scale(v[8 * G + i], a.x, a.y);
            scale(v[8 * G + i + 1], a.z, a.w);
            if (T2) {
                scale(v[B + i], a.x, a.y);
                scale(v[B + i + 1], a.z, a.w);
            }
        }
        if (H == 1) {
            put<8 * G, W * XS + G * 512>();
            put<8 * G + 4, W * XS + G * 512 + 2560>();
            if (T2) {
                put<B, 2 * XS + G * 512>();
                put<B + 4, 2 * XS + G * 512 + 2560>();
            }
            if (G == 4 && sig) nb_arrive<NB_ODONE, 288>();
        }
    }
    template <int G>
    __device__ __forceinline__ void step(uint32_t sb) {
        half<G, 0>(sb);
        half<G, 1>(sb);
    }
    __device__ __forceinline__ void clear() {
#pragma unroll
        for (int i = 0; i < N; i++) v[i] = 0;
        gp = nullptr;
        pend = 0;
        sig = 0;
    }
};

__device__ __forceinline__ uint32_t stsm_off() {
    const uint32_t tid = tid_now(), lane = tid & 31;
    return (lane >> 4) * 1024 + (lane & 7) * 128 + (((((tid >> 4) & 6) + ((lane >> 3) & 1)) ^ (lane & 7)) << 4);
}
template <int W, int KK>
__device__ __forceinline__ void qproj(float (&q0)[80], float (&q1)[80], uint32_t sb, Ring& r, uint32_t pslot, uint32_t phm,
                                      PendO<W>& po, const Params& P, int it) {
    const uint32_t loR = (((sb + OFF_R) & 0x3ffff) >> 4) | LO_LBO1;
    const uint32_t loRing = (((sb + OFF_RING) & 0x3ffff) >> 4) | LO_LBO1;
    auto ready = [&](int k) {
        mbar_wait(sb + BAR_RFULL + r.slot * 8, r.ph, r.dl);
        mbar_wait(sb + BAR_XFULL + (k % 5) * 8, ((phm >> (k % 5)) ^ (k / 5)) & 1, r.dl);
    };
    auto release = [&]() {
        if (KK > 0) {
            wg_wait<1>();
            mbar_arrive_warp(sb + BAR_REMPTY + pslot * 8);
            if (KK <= 5) mbar_arrive_warp(sb + (BAR_XEMPTY + (KK - 1) * 8));
        }
    };
    if (KK == 0 && (W == 1 || !po.sig)) ready(0);
    if (W == 1 && KK == QHOLD) {
        if (QHOLD == 7) {
            wg_wait<0>();
            nb_arrive<NB_PDONE, 256>();
        }
        nb_sync<NB_SDONE, 256>();
    }
    const uint32_t a = loRing + r.slot * (SLOT >> 4) + (W == 0 ? 0 : 512), b = loR + (KK % 5) * (XS >> 4);
    wg_fence();
    wgmma<1, 0, HI_SW128, KK != 0>(q0, a, b);
    if (W == 0) wgmma<1, 0, HI_SW128, KK != 0>(q1, a + 256, b);
#pragma unroll
    for (int k = 1; k < 4; k++) {
        wgmma<1, 0, HI_SW128, true>(q0, a + (k >> 1) * 768 + (k & 1) * 128, b + k * 2);
        if (W == 0) wgmma<1, 0, HI_SW128, true>(q1, a + 256 + (k >> 1) * 768 + (k & 1) * 128, b + k * 2);
    }
    wg_commit();
    const uint32_t cslot = r.slot;
    r.adv(1);
    if (W == 0 || KK < QHOLD) release();
    if (KK == QST0) {
        po.verdict(P, sb, it - 1);
        po.template half<0, 0>(sb);
    }
    if (KK < 9) ready(KK + 1);
    if (W == 1 && KK >= QHOLD) release();
    if (W == 1 && KK == 7 && QHOLD > 7) nb_arrive<NB_PDONE, 256>();
    if (KK == QST0) po.template half<0, 1>(sb);
    if constexpr (KK > QST0 && KK < QST0 + 5) po.template step<KK - QST0>(sb);
    if constexpr (KK < (W == 0 ? 7 : 9)) {
        qproj<W, KK + 1>(q0, q1, sb, r, cslot, phm, po, P, it);
    } else if constexpr (W == 1) {
        wg_wait<0>();
        reg_fence(q0);
        mbar_arrive_warp(sb + BAR_REMPTY + cslot * 8);
        store_tile_t(q0, sb + OFF_R + 2 * XS + stsm_off());
    } else {
        const uint32_t s8 = r.slot, a8 = loRing + s8 * (SLOT >> 4);
        wg_fence();
#pragma unroll
        for (int k = 0; k < 4; k++) wgmma<1, 0, HI_SW128, true>(q0, a8 + (k >> 1) * 768 + (k & 1) * 128, loR + 3 * (XS >> 4) + k * 2);
        r.adv(1);
        ready(9);
        const uint32_t s9 = r.slot, a9 = loRing + s9 * (SLOT >> 4);
        r.adv(1);
        wg_fence();
#pragma unroll
        for (int k = 0; k < 4; k++) wgmma<1, 0, HI_SW128, true>(q0, a9 + (k >> 1) * 768 + (k & 1) * 128, loR + 4 * (XS >> 4) + k * 2);
        wg_commit();
        wg_wait<1>();
        mbar_arrive_warp(sb + BAR_REMPTY + cslot * 8);
        wg_fence();
#pragma unroll
        for (int k = 0; k < 8; k++)
            wgmma<1, 0, HI_SW128, true>(q1, (k < 4 ? a8 : a9) + 256 + ((k >> 1) & 1) * 768 + (k & 1) * 128,
                                        loR + (3 + (k >> 2)) * (XS >> 4) + (k & 3) * 2);
        wg_commit();
        nb_arrive<NB_SDONE, 256>();
        nb_sync<NB_PDONE, 256>();
        wg_wait<1>();
        reg_fence(q0);
        const uint32_t sta = sb + OFF_R + stsm_off();
        store_tile_t(q0, sta);
        sts_u(sb + OFF_GM + 4, r.slot);
        mbar_wait(sb + BAR_RFULL + r.slot * 8, r.ph, r.dl);
        wg_wait<0>();
        reg_fence(q1);
        mbar_arrive_warp(sb + BAR_REMPTY + s8 * 8);
        mbar_arrive_warp(sb + BAR_REMPTY + s9 * 8);
        store_tile_t(q1, sta + XS);
    }
}

template <int NR>
__device__ __forceinline__ void opack(const float (&o)[NR], uint32_t* v) {
#pragma unroll
    for (int g = 0; g < NR / 16; g++)
#pragma unroll
        for (int hh = 0; hh < 2; hh++)
#pragma unroll
            for (int t = 0; t < 4; t++) v[8 * g + 4 * hh + t] = pack_bf16(o[16 * g + 4 * t + 2 * hh], o[16 * g + 4 * t + 2 * hh + 1]);
}

template <bool IS_S>
__device__ __forceinline__ void op_item(uint32_t e, uint32_t sb, Ring& r, uint32_t& phm) {
    constexpr int T0 = IS_S ? 0 : 2;
    constexpr uint32_t BOFF = IS_S ? (3 * 512) >> 4 : 0;
    const uint32_t loRing = (((sb + OFF_RING) & 0x3ffff) >> 4) | LO_LBO1;
    const uint32_t loO = (((sb + OFF_R) & 0x3ffff) >> 4) | LO_OST;
    float c0[80], c1[80], c2[IS_S ? 32 : 48];
    const int T2 = 6 * (IT_H1(e) - IT_H0(e));
    uint32_t xs = 0;
    auto step = [&](auto first, uint32_t hf) {
        constexpr bool F = decltype(first)::value;
        if (hf == 0) {
            mbar_wait(sb + BAR_XFULL + xs * 8, (phm >> xs) & 1, r.dl);
            phm ^= 1u << xs;
        }
        mbar_wait(sb + BAR_RFULL + r.slot * 8, r.ph, r.dl);
        const uint32_t a = loRing + r.slot * (SLOT >> 4), b = loO + xs * (XS >> 4) + hf * 640;
        wg_fence();
        wgmma<1, 1, HI_OST, !F>(c0, a + T0 * 128, b);
        wgmma<1, 1, HI_OST, !F>(c1, a + T0 * 128 + 128, b);
        wgmma<1, 1, HI_OST, !F>(c2, a + 512, b + BOFF);
        wgmma<1, 1, HI_OST, true>(c0, a + 640 + T0 * 128, b + 320);
        wgmma<1, 1, HI_OST, true>(c1, a + 640 + T0 * 128 + 128, b + 320);
        wgmma<1, 1, HI_OST, true>(c2, a + 640 + 512, b + 320 + BOFF);
        wg_commit();
    };
    step(TrueT{}, 0);
#pragma unroll 1
    for (int t = 1; t < T2; t++) {
        const uint32_t pslot = r.slot, pxs = xs;
        r.adv(1);
        if ((t & 1) == 0 && ++xs == 5) xs = 0;
        step(FalseT{}, t & 1);
        wg_wait<1>();
        mbar_arrive_warp(sb + BAR_REMPTY + pslot * 8);
        if ((t & 1) == 0 && t + 8 < T2) mbar_arrive_warp(sb + BAR_XEMPTY + pxs * 8);
    }
    wg_wait<0>();
    reg_fence(c0);
    reg_fence(c1);
    reg_fence(c2);
    mbar_arrive_warp(sb + BAR_REMPTY + r.slot * 8);
    r.adv(1);
    nb_sync<NB_OPEND, 256>();
    const uint32_t tid = tid_now(), lane = tid & 31, w = (tid >> 5) & 3;
    store_out_tile<false>(c0, sb + OFF_R + T0 * XS, lane, w);
    store_out_tile<false>(c1, sb + OFF_R + (T0 + 1) * XS, lane, w);
    store_out_tile<false>(c2, sb + OFF_R + 4 * XS + (IS_S ? 96 * 128 : 0), lane, w);
    fence_async_smem();
    nb_arrive<NB_ODONE, 288>();
}

template <int W>
__device__ __forceinline__ void on_item(uint32_t e, uint32_t sb, Ring& r, uint32_t& phm) {
    const uint32_t loRing = (((sb + OFF_RING) & 0x3ffff) >> 4) | LO_LBO1;
    const uint32_t loO = (((sb + OFF_R) & 0x3ffff) >> 4) | LO_OST;
    float c[80];
    const int T = 3 * (IT_H1(e) - IT_H0(e));
    uint32_t xs = 0;
    auto step = [&](auto first) {
        constexpr bool F = decltype(first)::value;
        mbar_wait(sb + BAR_XFULL + xs * 8, (phm >> xs) & 1, r.dl);
        phm ^= 1u << xs;
        mbar_wait(sb + BAR_RFULL + r.slot * 8, r.ph, r.dl);
        const uint32_t a = loRing + r.slot * (SLOT >> 4) + W * 256, b = loO + xs * (XS >> 4);
        wg_fence();
        wgmma<1, 1, HI_OST, !F>(c, a, b);
#pragma unroll
        for (int k = 1; k < 4; k++) wgmma<1, 1, HI_OST, true>(c, a + (k >> 1) * 512 + (k & 1) * 128, b + k * 320);
        wg_commit();
    };
    step(TrueT{});
#pragma unroll 1
    for (int t = 1; t < T; t++) {
        const uint32_t pslot = r.slot, pxs = xs;
        r.adv(1);
        if (++xs == 5) xs = 0;
        step(FalseT{});
        wg_wait<1>();
        mbar_arrive_warp(sb + BAR_REMPTY + pslot * 8);
        mbar_arrive_warp_if(sb + BAR_XEMPTY + pxs * 8, t + 2 < T);
    }
    xs += 1 + W;
    if (xs >= 5) xs -= 5;
    mbar_wait(sb + BAR_XFULL + xs * 8, (phm >> xs) & 1, r.dl);
    wg_wait<0>();
    reg_fence(c);
    const uint32_t tid = tid_now();
    store_out_tile<true>(c, sb + OFF_R + xs * XS, tid & 31, (tid >> 5) & 3);
    fence_async_smem();
    nb_arrive<NB_ODONE, 288>();
}

template <int W>
__device__ __forceinline__ uint32_t qa_item(const Params& P, uint32_t e, uint32_t sb, Ring& r, uint32_t phm, PendO<W>& po, int it) {
    const uint32_t loR = (((sb + OFF_R) & 0x3ffff) >> 4) | LO_LBO1;
    const uint32_t loRing = (((sb + OFF_RING) & 0x3ffff) >> 4) | LO_LBO1;
    {
        float q0[80], q1[80];
        qproj<W, 0>(q0, q1, sb, r, 0, phm, po, P, it);
    }
    fence_async_smem();
    TSD(W, 1);
    float s[80], oa[80], ob[W == 0 ? 32 : 48], l[10];
    if (W == 1) {
        nb_arrive<NB_Q2, 256>();
        nb_arrive<NB_L, 160>();
        zero(oa);
        zero(ob);
        reg_fence(oa);
        reg_fence(ob);
    }
    const uint32_t lane = tid_now() & 31, sta = sb + OFF_R + stsm_off();
    auto pv = [&](auto first, uint32_t buf) {
        constexpr bool F = decltype(first)::value;
        mbar_wait(sb + BAR_RFULL + r.slot * 8, r.ph, r.dl);
        const uint32_t a = loRing + r.slot * (SLOT >> 4), b = loR + (3 + buf) * (XS >> 4);
        wg_fence();
        wgmma<1, 0, HI_SW128, !F>(oa, a + W * 512, b);
        wgmma<1, 0, HI_SW128, !F>(ob, a + 1024, b + (W == 0 ? (96 * 128) >> 4 : 0));
#pragma unroll
        for (int k = 1; k < 4; k++) {
            wgmma<1, 0, HI_SW128, true>(oa, a + W * 512 + k * 128, b + k * 2);
            wgmma<1, 0, HI_SW128, true>(ob, a + 1024 + k * 128, b + (W == 0 ? (96 * 128) >> 4 : 0) + k * 2);
        }
        wg_commit();
    };
    zero(l);
    float mref;
    uint32_t kslot, vslot;
    auto tail = [&](auto first, int i) {
        constexpr bool rel_other = !decltype(first)::value;
        uint32_t ps[40];
        exp_block<0>(s, ps, sta + (3 + W) * XS, mref);
        if (rel_other) {
            wg_wait<0>();
            mbar_arrive_warp(sb + BAR_REMPTY + vslot * 8);
            if (W == 1) mbar_arrive_warp_if(sb + BAR_XEMPTY + 24, i == 3);
        }
        fence_async_smem();
        nb_arrive<NB_PFULL + W, 256>();
        TSD(W, 6 + 5 * i);
        if (W == 1) {
            if (XLATE >= 2) mbar_arrive_warp_if<2>(sb + BAR_XEMPTY + 8, i == 3);
            if (XLATE >= 1) mbar_arrive_warp_if<2>(sb + BAR_XEMPTY + 16, i == 3);
        }
        if (rel_other || !PV0FIRST) {
            mbar_wait(sb + BAR_RFULL + r.slot * 8, r.ph, r.dl);
            sum_block(ps, l, lane);
        }
        TSD(W, 7 + 5 * i);
        nb_sync<NB_W + W, 128>();
        pv(first, W);
        if (!rel_other && PV0FIRST) sum_block(ps, l, lane);
        TSD(W, 8 + 5 * i);
    };
    if (W == 0) {
        nb_sync<NB_QK, 160>();
        TSD(W, 2);
        wg_fence();
        qk_steps<0, 8>(s, loRing + r.slot * (SLOT >> 4), loR);
        nb_sync<NB_Q2, 256>();
        qk_steps<8, 12>(s, loRing + r.slot * (SLOT >> 4), loR);
        wg_commit();
        nb_arrive<NB_Q01, 256>();
        TSD(W, 4);
        nb_sync<NB_REF, 160>();
        mref = __uint_as_float(lds_u(sb + OFF_GM));
        wg_wait<0>();
        reg_fence(s);
        mbar_arrive_warp<2>(sb + BAR_REMPTY + r.slot * 8);
        r.adv(2);
        TSD(W, 5);
        tail(TrueT{}, 0);
    } else {
        nb_sync<NB_Q01, 256>();
    }
#pragma unroll 1
    for (int i = (W == 0 ? 1 : 0); i < 4; i++) {
        const uint32_t pvslot = r.slot;
        r.adv(1);
        kslot = r.slot;
        mbar_wait(sb + BAR_RFULL + r.slot * 8, r.ph, r.dl);
        wg_fence();
        qk_steps<0, 12>(s, loRing + r.slot * (SLOT >> 4), loR);
        wg_commit();
        wg_wait<1>();
        mbar_arrive_warp_if(sb + BAR_REMPTY + pvslot * 8, W == 0 || i > 0);
        r.adv(1);
        vslot = r.slot;
        TSD(W, 4 + 5 * i);
        nb_sync<NB_PFULL + (W ^ 1), 256>();
        pv(FalseT{}, W ^ 1);
        if (W == 1) mref = __uint_as_float(lds_u(sb + OFF_GM));
        wg_wait<1>();
        reg_fence(s);
        mbar_arrive_warp<2>(sb + BAR_REMPTY + kslot * 8);
        if (W == 1) {
            mbar_arrive_warp_if<2>(sb + BAR_XEMPTY + 0, i == 3);
            if (XLATE < 2) mbar_arrive_warp_if<2>(sb + BAR_XEMPTY + 8, i == 3);
            if (XLATE < 1) mbar_arrive_warp_if<2>(sb + BAR_XEMPTY + 16, i == 3);
        }
        r.adv(W == 1 && i == 3 ? 1 : 2);
        TSD(W, 5 + 5 * i);
        tail(FalseT{}, i);
    }
    const uint32_t w = (tid_now() >> 5) & 3;
    const uint32_t lxa = sb + OFF_LX + w * 640 + (((lane & 8) ? 80 : 0) + ((lane >> 1) & 8) + 2 * (lane & 3) + ((lane >> 2) & 1)) * 4;
    const uint32_t nx = get_item_warp(sb, it + 1, r.dl);
    po.gp = ostash(IT_SLOT(e), IT_B(e)) + po.toff();
    po.sig = 1;
    if (W == 0) {
        sum_store<false>(l, lane, lxa);
        nb_arrive<NB_LX, 256>();
        wg_wait<0>();
        mbar_arrive_warp(sb + BAR_REMPTY + r.slot * 8);
        mbar_arrive_warp(sb + BAR_XEMPTY + 24);
        r.adv(1);
        nb_sync<NB_PFULL + 1, 256>();
        pv(FalseT{}, 1);
        if (IT_TYPE(nx) == IT_QA) {
            Ring rn = r;
            rn.adv(1);
            mbar_wait(sb + BAR_RFULL + rn.slot * 8, rn.ph, r.dl);
            mbar_wait(sb + BAR_XFULL, phm & 1, r.dl);
        }
    } else {
        nb_sync<NB_LX, 256>();
        sum_store<true>(l, lane, lxa);
        nb_arrive<NB_L, 160>();
    }
    TSD(W, 24);
    wg_wait<0>();
    reg_fence(oa);
    reg_fence(ob);
    mbar_arrive_warp(sb + BAR_REMPTY + r.slot * 8);
    mbar_arrive_warp(sb + BAR_XEMPTY + 32);
    r.adv(1);
    opack(ob, po.v + 40);
    opack(oa, po.v);
    return nx;
}

template <int W>
__device__ __forceinline__ void consumer(const Params& P, uint32_t sb, uint32_t dl) {
    int it = 0;
    if (W == 0) TS(0, 30);
    Ring r{0, 0, dl};
    uint32_t phm = 0;
    uint32_t e = get_item_warp(sb, 0, dl);
#pragma unroll 1
    while (e != 0) {
        if (IT_TYPE(e) == IT_QA) {
            PendO<W> po;
            po.clear();
#pragma unroll 1
            do {
                TS(W, 0);
                if (W == 0) TS_ITEM(e);
                e = qa_item<W>(P, e, sb, r, phm, po, it);
                TS(W, 31);
                it++;
            } while (IT_TYPE(e) == IT_QA);
            po.verdict(P, sb, it - 1);
            po.template step<0>(sb);
            po.template step<1>(sb);
            po.template step<2>(sb);
            po.template step<3>(sb);
            po.template step<4>(sb);
        } else {
            TS(W, 0);
            if (W == 0) TS_ITEM(e);
            if (IT_TYPE(e) == IT_OP) op_item<W == 0>(e, sb, r, phm);
            else on_item<W>(e, sb, r, phm);
            TS(W, 31);
            e = get_item_warp(sb, ++it, dl);
        }
    }
    TS_DUMP(W);
}

__global__ void __cluster_dims__(2, 1, 1) __launch_bounds__(384, 1) fused_kernel(const __grid_constant__ Params P) {
    extern __shared__ __align__(1024) unsigned char smem_raw[];
    const uint32_t sb = (uint32_t)__cvta_generic_to_shared(smem_raw);
    const uint32_t wgid = __shfl_sync(0xffffffffu, threadIdx.x >> 7, 0);
    const uint32_t cta = blockIdx.x;
    const uint32_t dl = deadline();

    if (threadIdx.x == 128) {
#pragma unroll
        for (int i = 0; i < NSLOT; i++) {
            mbar_init(sb + BAR_RFULL + i * 8, 1);
            mbar_init(sb + BAR_REMPTY + i * 8, 8);
            mbar_init(sb + BAR_XFULL + i * 8, 1);
            mbar_init(sb + BAR_XEMPTY + i * 8, 8);
        }
        asm volatile("fence.mbarrier_init.release.cluster;" ::: "memory");
        fence_async_smem();
    } else if (threadIdx.x == 160) {
#pragma unroll
        for (int i = 0; i < NSLOT + MAXI; i++) mbar_init(sb + BAR_PRDY + i * 8, 1);
        asm volatile("fence.mbarrier_init.release.cluster;" ::: "memory");
    } else if (threadIdx.x == 0) {
        sts_u(sb + OFF_ITEM, P.cl[cta >> 1].items[0] ? P.cl[cta >> 1].items[0] + 8 * (cta & 1) : 0);
        sts_u(sb + OFF_FB, P.cl[cta >> 1].delay);
    } else if (threadIdx.x == 64) {
        if (sb & 1023) __trap();
        asm volatile("prefetch.tensormap [%0];" ::"l"(&P.wq[0]) : "memory");
        asm volatile("prefetch.tensormap [%0];" ::"l"(&P.x[0]) : "memory");
    }
    __syncthreads();
    asm volatile("barrier.cluster.arrive.relaxed.aligned;" ::: "memory");

    if (wgid == 0) {
        asm volatile("setmaxnreg.dec.sync.aligned.u32 24;");
        const uint32_t warp = __shfl_sync(0xffffffffu, threadIdx.x >> 5, 0);
        if (warp == 0) {
            const bool lead = threadIdx.x == 0;
            const uint64_t pol_first = mkpol<1>(), pol_norm = mkpol<POL_W>();
            uint32_t e = __shfl_sync(0xffffffffu, lds_u(sb + OFF_ITEM), 0);
            {
                const uint32_t d = lds_u(sb + OFF_FB);
                uint32_t t0, t1;
                asm volatile("mov.u32 %0, %%clock;" : "=r"(t0));
                do {
                    asm volatile("mov.u32 %0, %%clock;" : "=r"(t1));
                } while (t1 - t0 < d);
                __syncwarp();
            }
            if (lead) asm volatile("mbarrier.arrive.shared::cta.b64 _, [%0];" ::"r"(sb + BAR_ITEM) : "memory");
#pragma unroll 1
            for (int n = 0; n < (e ? NSLOT : 0); n++) {
                if (lead) {
                    mbar_expect(sb + BAR_RFULL + n * 8, SLOT);
                    tma3(sb + OFF_RING + n * SLOT, &P.wq[0], n * 64, IT_H0(e) * 3, sb + BAR_RFULL + n * 8, pol_norm);
                    mbar_expect(sb + BAR_XFULL + n * 8, XS);
                    tma3(sb + OFF_R + n * XS, &P.x[0], IT_B(e) * 160, n, sb + BAR_XFULL + n * 8, pol_norm);
                    tma3(sb + OFF_RING + n * SLOT + SLOT / 2, &P.wq[0], n * 64 + 32, IT_H0(e) * 3, sb + BAR_RFULL + n * 8, pol_norm);
                }
            }
            __syncwarp();
            asm volatile("barrier.cluster.wait.aligned;" ::: "memory");
            unsigned int* const ticket = &g_ticket[next_epoch(0) & 1];
            const uint32_t rank = cta & 1;
            uint32_t peer;
            asm volatile("mapa.shared::cluster.u32 %0, %1, %2;" : "=r"(peer) : "r"(sb), "r"(rank ^ 1));
            Ring r{0, 0, dl};
            uint32_t pm = 0;
            auto load_w = [&](const CUtensorMap* m, int row, int blk, uint32_t half_bytes) {
                mbar_wait(sb + BAR_REMPTY + r.slot * 8, r.ph, dl);
                if (lead) {
                    mbar_expect(sb + BAR_RFULL + r.slot * 8, 2 * half_bytes);
                    asm volatile("mbarrier.arrive.shared::cluster.b64 _, [%0];" ::"r"(peer + BAR_PRDY + r.slot * 8) : "memory");
                }
                mbar_wait(sb + BAR_PRDY + r.slot * 8, (pm >> r.slot) & 1, dl);
                pm ^= 1u << r.slot;
                if (lead) tma3_mc(sb + OFF_RING + r.slot * SLOT + rank * half_bytes, m, row, blk, sb + BAR_RFULL + r.slot * 8, pol_norm);
                r.adv(1);
            };
#pragma unroll 1
            for (int it = 0; e != 0; it++) {
                uint32_t nx = 0, tk = 0;
                if (rank == 0 && IT_TYPE(e) != IT_ON && it + 2 < MAXI) nx = it + 1 < NSTAT ? P.cl[cta >> 1].items[it + 1] : IT_DYN;
                const uint32_t br = IT_BR(e);
                if (IT_TYPE(e) == IT_QA) {
                    const uint32_t h = IT_H0(e);
#pragma unroll 1
                    for (int kk = it ? 0 : NSLOT; kk < 10; kk++) load_w(&P.wq[br], kk * 64 + rank * 32, h * 3, SLOT / 2);
                    const int row0 = (IT_B(e) * 32 + h) * 512;
#pragma unroll 1
                    for (int n = 0; n < 16; n++) {
                        if (n == 13 && nx == IT_DYN && lead) tk = atomicAdd(ticket, 1);
                        const bool isv = n == 15 || (n > 0 && !(n & 1));
                        const int j = n == 15 ? 7 : isv ? (n - 2) >> 1 : (n + 1) >> 1;
                        mbar_wait(sb + BAR_REMPTY + r.slot * 8, r.ph, dl);
                        if (lead) {
                            mbar_expect(sb + BAR_RFULL + r.slot * 8, SLOT);
                            tma3(sb + OFF_RING + r.slot * SLOT, isv ? &P.v[br] : &P.k[br], row0 + j * 64, 0,
                                 sb + BAR_RFULL + r.slot * 8, pol_first);
                        }
                        r.adv(1);
                    }
                } else {
                    const bool wide = IT_TYPE(e) == IT_OP;
                    const int step = wide ? 32 : 64, r1 = IT_H1(e) * 192;
#pragma unroll 1
                    for (int row = IT_H0(e) * 192 + rank * (step >> 1); row < r1; row += step)
                        load_w(wide ? &P.wo[br] : &P.won[br], row, IT_HALF(e) * (wide ? 5 : 2), wide ? XS / 2 : 8192);
                    if (nx == IT_DYN && lead) tk = atomicAdd(ticket, 1);
                }
                if (rank == 0) {
                    if (nx == IT_DYN) {
                        tk = __shfl_sync(0xffffffffu, tk, 0);
                        nx = tk < P.nlist ? P.list[tk] : 0;
                    }
                    e = nx;
                    if (lead) {
                        asm volatile("st.async.weak.shared::cluster.mbarrier::complete_tx::bytes.b32 [%0], %1, [%2];" ::"r"(
                                         peer + OFF_ITEM + 4 + it * 4),
                                     "r"(e ? e + 8 : 0), "r"(peer + BAR_ITEM + 8 + it * 8)
                                     : "memory");
                        sts_u(sb + OFF_ITEM + 4 + it * 4, e);
                        asm volatile("mbarrier.arrive.shared::cta.b64 _, [%0];" ::"r"(sb + BAR_ITEM + 8 + it * 8) : "memory");
                    }
                } else {
                    if (lead) mbar_expect(sb + BAR_ITEM + 8 + it * 8, 4);
                    e = get_item_warp(sb, it + 1, dl);
                }
            }
        } else if (warp == 1) {
            const uint64_t pol_norm = mkpol<POL_X>(), pol_o = mkpol<POL_O>();
            const bool lead = threadIdx.x == 32;
            uint32_t phm = 0, epoch = 0;
#pragma unroll 1
            for (int it = 0;; it++) {
                const uint32_t e = get_item_warp(sb, it, dl);
                if (it == 1 || (it == 0 && e == 0)) epoch = next_epoch(1);
                if (e == 0) break;
                const uint32_t br = IT_BR(e);
                uint32_t xs = 0;
                auto acquire = [&]() {
                    mbar_wait(sb + BAR_XEMPTY + xs * 8, (phm >> xs) & 1, dl);
                    phm ^= 1u << xs;
                    if (lead) mbar_expect(sb + BAR_XFULL + xs * 8, XS);
                };
                if (IT_TYPE(e) == IT_QA) {
#pragma unroll 1
                    for (int kk = it ? 0 : 5; kk < 10; kk++) {
                        acquire();
                        if (lead) tma3(sb + OFF_R + xs * XS, &P.x[br], IT_B(e) * 160, kk, sb + BAR_XFULL + xs * 8, pol_norm);
                        if (++xs == 5) xs = 0;
                    }
                } else {
                    const unsigned int* fp = g_flag + (br * 16 + IT_B(e)) * 64 + (threadIdx.x & 31);
                    uint32_t hm = 0, pm = 0;
                    auto poll = [&](uint32_t hneed, uint32_t pneed) {
                        if ((hm & hneed) == hneed && (pm & pneed) == pneed) return;
                        uint32_t n = 0;
                        do {
                            uint32_t a, b;
                            asm volatile("ld.acquire.gpu.global.u32 %0, [%2];\nld.acquire.gpu.global.u32 %1, [%2+128];"
                                         : "=r"(a), "=r"(b) : "l"(fp) : "memory");
                            hm = __ballot_sync(0xffffffffu, a == epoch);
                            pm = __ballot_sync(0xffffffffu, b == epoch);
                            if (++n > 0x1000000) __trap();
                        } while ((hm & hneed) != hneed || (pm & pneed) != pneed);
                        __syncwarp();
                        asm volatile("fence.proxy.async;" ::: "memory");
                    };
#pragma unroll 1
                    for (uint32_t h = IT_H0(e); h < IT_H1(e); h++) {
                        poll(1u << h, 0);
                        const unsigned char* src = ostash(P.slot[br * 32 + h], IT_B(e));
#pragma unroll 1
                        for (int t = 0; t < 3; t++) {
                            acquire();
                            if (lead) bulk_load(sb + OFF_R + xs * XS, src + t * XS, XS, sb + BAR_XFULL + xs * 8, pol_o);
                            if (++xs == 5) xs = 0;
                        }
                        if (IT_TYPE(e) == IT_OP && h >= 1) {
                            const uint32_t x1 = xs == 4 ? 0 : xs + 1;
                            mbar_wait(sb + BAR_XFULL + xs * 8, (phm >> xs) & 1, dl);
                            mbar_wait(sb + BAR_XFULL + x1 * 8, (phm >> x1) & 1, dl);
                            if (lead)
                                asm volatile("st.relaxed.gpu.global.u32 [%0], %1;" ::"l"(fp + 34 + IT_HALF(e)), "r"(epoch * 64 + h) : "memory");
                        }
                    }
                    if (IT_TYPE(e) == IT_ON) {
                        poll(0, IT_HALF(e) < 2 ? 1 : IT_HALF(e) == 2 ? 3 : 2);
#pragma unroll 1
                        for (uint32_t tile = 2 * IT_HALF(e); tile < 2 * IT_HALF(e) + 2; tile++) {
                            acquire();
                            if (lead)
                                asm volatile(
                                    "cp.async.bulk.tensor.2d.shared::cluster.global.mbarrier::complete_tx::bytes [%0], [%1, {%3,%4}], [%2];" ::"r"(
                                        sb + OFF_R + xs * XS),
                                    "l"(&P.out), "r"(sb + BAR_XFULL + xs * 8), "r"(br * 640 + tile * 64), "r"(IT_B(e) * 160)
                                    : "memory");
                            if (++xs == 5) xs = 0;
                        }
                    }
                }
            }
        } else if (warp == 2) {
            asm volatile("barrier.cluster.wait.aligned;" ::: "memory");
            const uint32_t epoch = next_epoch(2);
            if (cta == 0) g_ticket[(epoch + 1) & 1] = 0;
#pragma unroll 1
            for (int it = 0;; it++) {
                const uint32_t e = get_item_warp(sb, it, dl);
                if (e == 0) break;
                nb_sync<NB_ODONE, 288>();
                if (threadIdx.x == 64) {
                    const uint32_t bb = IT_BR(e) * 16 + IT_B(e);
                    if (IT_TYPE(e) != IT_QA) {
                        const bool wide = IT_TYPE(e) == IT_OP;
                        if (wide)
                            asm volatile("st.relaxed.gpu.global.u32 [%0], %1;" ::"l"(&g_flag[bb * 64 + 34 + IT_HALF(e)]),
                                         "r"(epoch * 64 + IT_H1(e))
                                         : "memory");
                        const int cc0 = IT_BR(e) * 640 + IT_HALF(e) * (wide ? 320 : 128);
                        uint32_t xs = wide ? 0 : (3 * (IT_H1(e) - IT_H0(e))) % 5;
#pragma unroll 1
                        for (int m = 0; m < (wide ? 5 : 2); m++) {
                            asm volatile("cp.async.bulk.tensor.2d.global.shared::cta.bulk_group [%0, {%2,%3}], [%1];" ::"l"(&P.out),
                                         "r"(sb + OFF_R + xs * XS), "r"(cc0 + m * 64), "r"((int)IT_B(e) * 160)
                                         : "memory");
                            asm volatile("cp.async.bulk.commit_group;" ::: "memory");
                            if (++xs == 5) xs = 0;
                        }
                        if (wide) {
#define REL(N)                                                          \
    asm volatile("cp.async.bulk.wait_group.read %0;" ::"n"(4 - N) : "memory"); \
    asm volatile("mbarrier.arrive.shared::cta.b64 _, [%0], 8;" ::"r"(sb + BAR_XEMPTY + N * 8) : "memory");
                            REL(0) REL(1) REL(2) REL(3) REL(4)
#undef REL
                        }
                        if (IT_PART(e)) {
                            asm volatile("cp.async.bulk.wait_group 0;" ::: "memory");
                            asm volatile("fence.proxy.async;" ::: "memory");
                        }
                    }
                    if (IT_TYPE(e) == IT_QA || IT_PART(e)) {
                        unsigned int* f = &g_flag[bb * 64 + (IT_TYPE(e) == IT_QA ? IT_H0(e) : 32 + IT_HALF(e))];
                        asm volatile("st.release.gpu.global.u32 [%0], %1;" ::"l"(f), "r"(epoch) : "memory");
                    }
                }
                __syncwarp();
            }
            if (threadIdx.x == 64) asm volatile("cp.async.bulk.wait_group 0;" ::: "memory");
            __syncwarp();
            asm volatile("barrier.cluster.arrive.relaxed.aligned;\nbarrier.cluster.wait.aligned;" ::: "memory");
        } else {
            const uint32_t lane = threadIdx.x & 31, p = lane >> 2;
            const uint32_t epoch = next_epoch(3);
#pragma unroll 1
            for (int it = 0;; it++) {
                const uint32_t e = get_item_warp(sb, it, dl);
                if (e == 0) break;
                if (IT_TYPE(e) != IT_QA) continue;
                nb_sync<NB_QK, 160>();
                const uint32_t co = (((lane & 3) * 2) ^ p) << 4;
                const uint32_t ka = sb + OFF_RING + lds_u(sb + OFF_GM + 4) * SLOT + p * (9 * 128) + co;
                const uint32_t qa = sb + OFF_R + p * (17 * 128) + co;
                uint32_t acc = 0;
#pragma unroll 1
                for (int c = 0; c < 3; c++) {
                    if (c == 2) nb_sync<NB_L, 160>();
                    const uint4 k0 = lds_u4(ka + c * 8192), q0 = lds_u4(qa + c * XS);
                    acc = fma_bf2(k0.x, q0.x, fma_bf2(k0.y, q0.y, fma_bf2(k0.z, q0.z, fma_bf2(k0.w, q0.w, acc))));
                    const uint4 k1 = lds_u4((ka + c * 8192) ^ 16), q1 = lds_u4((qa + c * XS) ^ 16);
                    acc = fma_bf2(k1.x, q1.x, fma_bf2(k1.y, q1.y, fma_bf2(k1.z, q1.z, fma_bf2(k1.w, q1.w, acc))));
                }
                float d = __uint_as_float(acc << 16) + __uint_as_float(acc & 0xffff0000u);
                d += __shfl_xor_sync(0xffffffffu, d, 1);
                d += __shfl_xor_sync(0xffffffffu, d, 2);
                int key = __float_as_int(d);
                key ^= (key >> 31) & 0x7fffffff;
                key = __reduce_max_sync(0xffffffffu, key);
                key ^= (key >> 31) & 0x7fffffff;
                sts_f(sb + OFF_GM, __int_as_float(key) * SM_C);
                nb_arrive<NB_REF, 160>();
                if (IT_DEP(e)) {
                    const uint32_t g = IT_DEP(e) - 1, need = epoch * 64 + (g & 31) + 1;
                    const unsigned int* cp = &g_flag[((g >> 5) * 16 + IT_B(e)) * 64 + 34 + (lane & 1)];
                    for (uint32_t n = 0;; n++) {
                        uint32_t v;
                        asm volatile("ld.acquire.gpu.global.u32 %0, [%1];" : "=r"(v) : "l"(cp) : "memory");
                        if (__all_sync(0xffffffffu, v - need < 64)) break;
                        if (n > 0x800000) __trap();
                        __nanosleep(500);
                    }
                }
                nb_sync<NB_L, 160>();
                bool bad = false;
#pragma unroll
                for (int c = 0; c < 5; c++) {
                    const uint32_t la = sb + OFF_LX + (c * 32 + lane) * 4;
                    const float v = (__uint_as_float(lds_u(la)) + __uint_as_float(lds_u(la + 640))) +
                                    (__uint_as_float(lds_u(la + 1280)) + __uint_as_float(lds_u(la + 1920)));
                    const float inv = __fdividef(1.f, v);
                    const uint32_t hi = pack_bf16(inv, 0.f), lo = pack_bf16(inv - __uint_as_float(hi << 16), 0.f);
                    const uint32_t ia = sb + OFF_LINV + c * 128 + ((lane >> 1) & 3) * 32 + (lane >> 3) * 8 + (lane & 1) * 2;
                    asm volatile("st.shared.u16 [%0], %1;\nst.shared.u16 [%0+4], %2;" ::"r"(ia), "h"((unsigned short)hi), "h"((unsigned short)lo) : "memory");
                    bad |= !(v >= 5.421010862e-20f && v <= 1.8446744e19f);
                }
                sts_u(sb + OFF_FB, __any_sync(0xffffffffu, bad));
                nb_arrive<NB_VOTE, 160>();
                nb_arrive<NB_VOTE + 1, 160>();
            }
        }
    } else if (wgid == 1) {
        asm volatile("setmaxnreg.inc.sync.aligned.u32 240;");
        consumer<0>(P, sb, dl);
    } else {
        asm volatile("setmaxnreg.inc.sync.aligned.u32 240;");
        consumer<1>(P, sb, dl);
    }
}

typedef CUresult (*EncFn)(CUtensorMap*, CUtensorMapDataType, cuuint32_t, void*, const cuuint64_t*, const cuuint64_t*,
                          const cuuint32_t*, const cuuint32_t*, CUtensorMapInterleave, CUtensorMapSwizzle,
                          CUtensorMapL2promotion, CUtensorMapFloatOOBfill);

void make_map3(EncFn enc, CUtensorMap* m, void* p, uint64_t rows, uint64_t rowbytes, uint64_t nblk, uint32_t boxrows,
               uint32_t boxblk) {
    cuuint64_t dims[3] = {64, rows, nblk};
    cuuint64_t str[2] = {rowbytes, 128};
    cuuint32_t box[3] = {64, boxrows, boxblk};
    cuuint32_t es[3] = {1, 1, 1};
    enc(m, CU_TENSOR_MAP_DATA_TYPE_BFLOAT16, 3, p, dims, str, box, es, CU_TENSOR_MAP_INTERLEAVE_NONE,
        CU_TENSOR_MAP_SWIZZLE_128B, CU_TENSOR_MAP_L2_PROMOTION_NONE, CU_TENSOR_MAP_FLOAT_OOB_FILL_NONE);
}

constexpr int tune(const char*, int def) { return def; }

void build_schedule(Params& P) {
    const int mode = tune("MODE", 4), dmax = tune("DMAX", 24900), n0 = tune("N0", 6);
    const int H0[8] = {18, 17, 20, 21, 22, 23, 23, 24}, P0[8] = {383, 371, 344, 348, 354, 345, 348, 336};
    const int ng = tune("NG", 0), d0 = tune("D0", 0), nkeep = tune("NKEEP", 0), odmax = tune("ODMAX", 6000);
    const int ong = tune("ONG", 0), od0 = tune("OD0", 0), jit = tune("JIT", 0);
    const int npos = tune("NPOS", 0), nearly = tune("NEARLY", 0);
    const int ra = tune("RA", 10), ga = tune("GA", 32), rb = tune("RB", 12), g1 = tune("G1", 58);
    int dep[64];
    for (int g = 0, ns = 0, live = 0; g < 64; g++) {
        const bool fresh = mode < 3 || g >= g1 || live < (g < ga ? ra : rb);
        dep[g] = fresh ? 0 : g - live + 1;
        P.slot[g] = fresh ? ns++ : P.slot[g - live];
        live += fresh;
    }
    int u = 0;
    auto unit = [&]() {
        const uint32_t e = mk_item(IT_QA, u >> 8, (u & 7) * 2, (u >> 3) & 31, P.slot[u >> 3], 0) | (dep[u >> 3] << 23);
        u++;
        return e;
    };
    int qa[NCL], nq = 0, op[NCL], no = 0;
    for (int c = 0; c < NCL; c++) {
        P.cl[c].delay = 0;
        for (int i = 0; i < NSTAT; i++) P.cl[c].items[i] = 0;
        if (mode >= 3 && c < 64 && (c & 3) == 3) op[no++] = c;
        else if (mode != 2 || (c & 3) == 0) qa[nq++] = c;
    }
    for (int t = 0; t < no; t++) {
        P.cl[op[t]].items[1] = mk_item(IT_OP, 0, t & ~1, 0, 32, t & 1);
        P.cl[op[t]].items[2] = IT_DYN;
        P.cl[op[t]].delay = ong ? od0 + (t * ong / 16) * (odmax / ong) : od0 + t * odmax / 16;
    }
    for (int k = 0; k < nq; k++) {
        const int c = qa[(k * 19) % nq];
        P.cl[c].items[1] = P.cl[c].items[2] = IT_DYN;
        P.cl[c].delay = k < n0 ? 0 : (int)((long long)dmax * (k + 1 - n0) / (nq - n0));
        if (ng) P.cl[c].delay = d0 + (k * ng / nq) * (dmax / ng) + (k * ng % nq) * jit / nq;
    }
    for (int k = 0; k < no + nq; k++) {
        int best = -1;
        for (int c = 0; c < NCL; c++)
            if (P.cl[c].items[1] && !P.cl[c].items[0] && (best < 0 || P.cl[c].delay < P.cl[best].delay)) best = c;
        P.cl[best].items[0] = unit();
    }
    int H[8], pos[8];
    for (int b = 0; b < 8; b++) {
        char nh[3] = {'H', (char)('0' + b), 0}, np[3] = {'P', (char)('0' + b), 0};
        H[b] = tune(nh, H0[b]);
        pos[b] = tune(np, P0[b]);
        for (int g = 0; g < 64; g++)
            if (dep[g] > 32) {
                if (pos[b] > 8 * g) pos[b] = 8 * g;
                if (H[b] < dep[g] - 32) H[b] = dep[g] - 32;
            }
        if (b < nkeep && no) {
            pos[b] = -1;
            P.cl[op[14 - 2 * b]].items[2] = mk_item(IT_OP, 1, 2 * b, 0, H[b], 0, 1);
            P.cl[op[15 - 2 * b]].items[2] = mk_item(IT_OP, 1, 2 * b, 0, H[b], 1, 1);
        }
    }
    int n = 0, kn = 0;
    const int uend = mode == 2 ? 8 * nq : 512;
    while (u < uend) {
        for (int b = 0; b < 8 && no; b++)
            if (pos[b] == u) {
                P.list[n++] = mk_item(IT_OP, 1, 2 * b, 0, H[b], 0, 1);
                P.list[n++] = mk_item(IT_OP, 1, 2 * b, 0, H[b], 1, 1);
            }
        while (no && u >= uend - npos && kn * npos < (u + 1 - (uend - npos)) * nearly) {
            P.list[n++] = mk_item(IT_ON, 1, kn / 5 * 2, H[kn / 5], 32, kn % 5);
            kn++;
        }
        P.list[n++] = unit();
    }
    for (; no && kn < 40; kn++) P.list[n++] = mk_item(IT_ON, 1, kn / 5 * 2, H[kn / 5], 32, kn % 5);
    P.nlist = n;
}

}

extern "C" void kernel_launch(void* const* d_in, const int* in_sizes, int n_in, void* d_out, int out_size) {
    static Params P;
    static bool init = false;
    if (!init) {
        EncFn enc = nullptr;
        cudaDriverEntryPointQueryResult qr;
        cudaGetDriverEntryPoint("cuTensorMapEncodeTiled", (void**)&enc, cudaEnableDefault, &qr);
        for (int i = 0; i < 2; i++) {
            P.px[i] = (const __nv_bfloat16*)d_in[5 * i + 0];
            P.pk[i] = (const __nv_bfloat16*)d_in[5 * i + 1];
            P.pv[i] = (const __nv_bfloat16*)d_in[5 * i + 2];
            P.pwq[i] = (const __nv_bfloat16*)d_in[5 * i + 3];
            make_map3(enc, &P.x[i], d_in[5 * i + 0], 2560, 1280, 10, 160, 1);
            make_map3(enc, &P.k[i], d_in[5 * i + 1], 16 * 32 * 512, 384, 3, 64, 3);
            make_map3(enc, &P.v[i], d_in[5 * i + 2], 16 * 32 * 512, 384, 3, 64, 3);
            make_map3(enc, &P.wq[i], d_in[5 * i + 3], 640, 12288, 96, 32, 3);
            make_map3(enc, &P.wo[i], d_in[5 * i + 4], 6144, 1280, 10, 16, 5);
            make_map3(enc, &P.won[i], d_in[5 * i + 4], 6144, 1280, 10, 32, 2);
        }
        cuuint64_t dims[2] = {1280, 2560};
        cuuint64_t str[1] = {2560};
        cuuint32_t box[2] = {64, 160};
        cuuint32_t es[2] = {1, 1};
        enc(&P.out, CU_TENSOR_MAP_DATA_TYPE_BFLOAT16, 2, d_out, dims, str, box, es, CU_TENSOR_MAP_INTERLEAVE_NONE,
            CU_TENSOR_MAP_SWIZZLE_128B, CU_TENSOR_MAP_L2_PROMOTION_NONE, CU_TENSOR_MAP_FLOAT_OOB_FILL_NONE);
        build_schedule(P);
        cudaFuncSetAttribute(fused_kernel, cudaFuncAttributeMaxDynamicSharedMemorySize, SMEM_LAUNCH);
        init = true;
    }
    fused_kernel<<<NCTA, 384, SMEM_LAUNCH>>>(P);
}
```

```cpp
#include <cuda_runtime.h>
#include <cuda.h>
#include <cuda_bf16.h>
#include <stdint.h>

namespace {

constexpr int NCTA = 132;
constexpr int NCL = NCTA / 2;
constexpr int MAXI = 16;
constexpr int NSTAT = 3;
constexpr uint32_t IT_DYN = 0xffffffffu;
constexpr int SLOT = 24576;
constexpr int NSLOT = 5;
constexpr int XS = 20480;
constexpr int OFF_R = 0;
constexpr int OFF_RING = 5 * XS;
constexpr int OFF_MISC = OFF_RING + NSLOT * SLOT;
constexpr int OFF_LX = OFF_MISC;
constexpr int OFF_LINV = OFF_LX + 2560;
constexpr int OFF_FB = OFF_LINV + 640;
constexpr int OFF_GM = OFF_FB + 16;
constexpr int OFF_BAR = OFF_GM + 16;
constexpr int BAR_RFULL = OFF_BAR;
constexpr int BAR_REMPTY = BAR_RFULL + 40;
constexpr int BAR_XFULL = BAR_REMPTY + 40;
constexpr int BAR_XEMPTY = BAR_XFULL + 40;
constexpr int BAR_PRDY = BAR_XEMPTY + 40;
constexpr int BAR_ITEM = BAR_PRDY + 40;
constexpr int OFF_ITEM = BAR_ITEM + MAXI * 8;
constexpr int SMEM_BYTES = OFF_ITEM + MAXI * 4;
static_assert(SMEM_BYTES <= 232448, "smem");

constexpr int NB_W = 1  , NB_PFULL = 3  , NB_VOTE = 5  , NB_Q2 = 7, NB_SDONE = 8, NB_PDONE = 9,
              NB_L = 10, NB_REF = 11, NB_ODONE = 12, NB_OPEND = 13, NB_LX = 14, NB_Q01 = 15, NB_QK = 0  ;

constexpr uint32_t IT_QA = 1, IT_OP = 2, IT_ON = 3;
__host__ __device__ constexpr uint32_t mk_item(uint32_t type, uint32_t br, uint32_t b, uint32_t h0, uint32_t h1, uint32_t half,
                                               uint32_t part = 0) {
    return type | (br << 2) | (b << 3) | (h0 << 7) | (h1 << 13) | (half << 19) | (part << 22);
}
#define IT_TYPE(e) ((e) & 3u)
#define IT_BR(e) (((e) >> 2) & 1u)
#define IT_B(e) (((e) >> 3) & 15u)
#define IT_H0(e) (((e) >> 7) & 63u)
#define IT_H1(e) (((e) >> 13) & 63u)
#define IT_HALF(e) (((e) >> 19) & 7u)
#define IT_PART(e) (((e) >> 22) & 1u)
#define IT_SLOT(e) IT_H1(e)
#define IT_DEP(e) (((e) >> 23) & 127u)

struct Params {
    CUtensorMap x[2], wq[2], k[2], v[2], wo[2], won[2], out;
    const __nv_bfloat16 *px[2], *pwq[2], *pk[2], *pv[2];
    struct alignas(16) { uint32_t delay, items[NSTAT]; } cl[NCL];
    uint32_t nlist;
    uint8_t slot[64];
    uint32_t list[512];
};

constexpr int OUNIT = 61440;
__device__ __align__(1024) unsigned char g_ostash[(size_t)1024 * OUNIT];
__device__ unsigned int g_flag[32 * 64];
__device__ __forceinline__ unsigned char* ostash(uint32_t slot, uint32_t b) { return g_ostash + (slot * 16 + b) * OUNIT; }
__device__ unsigned int g_epoch[NCTA * 4];
__device__ unsigned int g_ticket[2];

constexpr int SMEM_LAUNCH = SMEM_BYTES;
#define TS(role, idx)
#define TS_ITEM(e)
#define TS_DUMP(role)
#define TSD(role, idx)

#define POL_W 2
#define POL_X 2
#define POL_O 2
template <int M>
__device__ __forceinline__ uint64_t mkpol() {
    uint64_t p;
    if (M == 0) asm volatile("createpolicy.fractional.L2::evict_normal.b64 %0, 1.0;" : "=l"(p));
    if (M == 1) asm volatile("createpolicy.fractional.L2::evict_first.b64 %0, 1.0;" : "=l"(p));
    if (M == 2) asm volatile("createpolicy.fractional.L2::evict_unchanged.b64 %0, 1.0;" : "=l"(p));
    if (M == 3) asm volatile("createpolicy.fractional.L2::evict_normal.L2::evict_unchanged.b64 %0, 0.25;" : "=l"(p));
    return p;
}
#define STSM_W 1
#define XLATE 2
#define PV0FIRST 1
#define QST0 1
#define QST1 2
#define QHOLD 8
constexpr float SM_C = 0.07216878364870322f * 1.4426950408889634f;

__device__ __forceinline__ uint32_t next_epoch(int warp) {
    unsigned int* p = &g_epoch[blockIdx.x * 4 + warp];
    const uint32_t e = __ldcg(p) + 1;
    *p = e;
    return e;
}

__device__ __forceinline__ uint32_t tid_now() {
    uint32_t t;
    asm volatile("mov.u32 %0, %%tid.x;" : "=r"(t));
    return t;
}
__device__ __forceinline__ void mbar_init(uint32_t a, uint32_t c) {
    asm volatile("mbarrier.init.shared::cta.b64 [%0], %1;" ::"r"(a), "r"(c) : "memory");
}
__device__ __forceinline__ void mbar_expect(uint32_t a, uint32_t b) {
    asm volatile("mbarrier.arrive.expect_tx.shared::cta.b64 _, [%0], %1;" ::"r"(a), "r"(b) : "memory");
}
template <int CNT = 1>
__device__ __forceinline__ void mbar_arrive_warp(uint32_t a) {
    if (CNT == 1)
        asm volatile("{\n.reg .pred p;\nelect.sync _|p, 0xffffffff;\n@p mbarrier.arrive.shared::cta.b64 _, [%0];\n}" ::"r"(a) : "memory");
    else
        asm volatile(
            "{\n.reg .pred p;\nelect.sync _|p, 0xffffffff;\n@p mbarrier.arrive.shared::cta.b64 _, [%0];\n"
            "@p mbarrier.arrive.shared::cta.b64 _, [%0];\n}" ::"r"(a)
            : "memory");
}
template <int CNT = 1>
__device__ __forceinline__ void mbar_arrive_warp_if(uint32_t a, bool cond) {
    if (CNT == 1)
        asm volatile(
            "{\n.reg .pred p, c;\nelect.sync _|p, 0xffffffff;\nsetp.ne.and.u32 c, %1, 0, p;\n"
            "@c mbarrier.arrive.shared::cta.b64 _, [%0];\n}" ::"r"(a), "r"((uint32_t)cond)
            : "memory");
    else
        asm volatile(
            "{\n.reg .pred p, c;\nelect.sync _|p, 0xffffffff;\nsetp.ne.and.u32 c, %1, 0, p;\n"
            "@c mbarrier.arrive.shared::cta.b64 _, [%0];\n@c mbarrier.arrive.shared::cta.b64 _, [%0];\n}" ::"r"(a), "r"((uint32_t)cond)
            : "memory");
}
__device__ __forceinline__ uint32_t deadline() {
    uint32_t c;
    asm volatile("mov.u32 %0, %%clock_hi;" : "=r"(c));
    return c + 4;
}
__device__ __forceinline__ void mbar_wait(uint32_t a, uint32_t ph, uint32_t dl) {
    asm volatile(
        "{\n.reg .pred p;\n.reg .u32 m;\n"
        "LOOP:\n"
        "mbarrier.try_wait.parity.shared::cta.b64 p, [%0], %1;\n"
        "@p bra DONE;\n"
        "mov.u32 m, %%clock_hi;\n"
        "setp.ne.u32 p, m, %2;\n"
        "@p bra LOOP;\n"
        "trap;\n"
        "DONE:\n}" ::"r"(a), "r"(ph), "r"(dl)
        : "memory");
}
template <int ID, int CNT>
__device__ __forceinline__ void nb_sync() { asm volatile("bar.sync %0, %1;" ::"n"(ID), "n"(CNT) : "memory"); }
template <int ID, int CNT>
__device__ __forceinline__ void nb_arrive() { asm volatile("bar.arrive %0, %1;" ::"n"(ID), "n"(CNT) : "memory"); }
__device__ __forceinline__ void fence_async_smem() { asm volatile("fence.proxy.async.shared::cta;" ::: "memory"); }

__device__ __forceinline__ void tma3(uint32_t dst, const CUtensorMap* m, int c1, int c2, uint32_t bar, uint64_t pol) {
    asm volatile(
        "cp.async.bulk.tensor.3d.shared::cluster.global.mbarrier::complete_tx::bytes.L2::cache_hint [%0], [%1, {%3,%4,%5}], [%2], %6;" ::"r"(dst),
        "l"(m), "r"(bar), "r"(0), "r"(c1), "r"(c2), "l"(pol)
        : "memory");
}
__device__ __forceinline__ void tma3_mc(uint32_t dst, const CUtensorMap* m, int c1, int c2, uint32_t bar, uint64_t pol) {
    asm volatile(
        "cp.async.bulk.tensor.3d.shared::cluster.global.mbarrier::complete_tx::bytes.multicast::cluster.L2::cache_hint"
        " [%0], [%1, {%3,%4,%5}], [%2], %6, %7;" ::"r"(dst),
        "l"(m), "r"(bar), "r"(0), "r"(c1), "r"(c2), "h"((unsigned short)3), "l"(pol)
        : "memory");
}
__device__ __forceinline__ void bulk_load(uint32_t dst, const void* src, uint32_t bytes, uint32_t bar, uint64_t pol) {
    asm volatile("cp.async.bulk.shared::cluster.global.mbarrier::complete_tx::bytes.L2::cache_hint [%0], [%1], %2, [%3], %4;" ::"r"(dst),
                 "l"(src), "r"(bytes), "r"(bar), "l"(pol)
                 : "memory");
}
__device__ __forceinline__ void wg_fence() { asm volatile("wgmma.fence.sync.aligned;" ::: "memory"); }
__device__ __forceinline__ void wg_commit() { asm volatile("wgmma.commit_group.sync.aligned;" ::: "memory"); }
template <int N>
__device__ __forceinline__ void wg_wait() { asm volatile("wgmma.wait_group.sync.aligned %0;" ::"n"(N) : "memory"); }

#define RW80(c, d) c(d[0]), c(d[1]), c(d[2]), c(d[3]), c(d[4]), c(d[5]), c(d[6]), c(d[7]), c(d[8]), c(d[9]), c(d[10]), c(d[11]), c(d[12]), c(d[13]), c(d[14]), c(d[15]), c(d[16]), c(d[17]), c(d[18]), c(d[19]), c(d[20]), c(d[21]), c(d[22]), c(d[23]), c(d[24]), c(d[25]), c(d[26]), c(d[27]), c(d[28]), c(d[29]), c(d[30]), c(d[31]), c(d[32]), c(d[33]), c(d[34]), c(d[35]), c(d[36]), c(d[37]), c(d[38]), c(d[39]), c(d[40]), c(d[41]), c(d[42]), c(d[43]), c(d[44]), c(d[45]), c(d[46]), c(d[47]), c(d[48]), c(d[49]), c(d[50]), c(d[51]), c(d[52]), c(d[53]), c(d[54]), c(d[55]), c(d[56]), c(d[57]), c(d[58]), c(d[59]), c(d[60]), c(d[61]), c(d[62]), c(d[63]), c(d[64]), c(d[65]), c(d[66]), c(d[67]), c(d[68]), c(d[69]), c(d[70]), c(d[71]), c(d[72]), c(d[73]), c(d[74]), c(d[75]), c(d[76]), c(d[77]), c(d[78]), c(d[79])
#define RW48(c, d) c(d[0]), c(d[1]), c(d[2]), c(d[3]), c(d[4]), c(d[5]), c(d[6]), c(d[7]), c(d[8]), c(d[9]), c(d[10]), c(d[11]), c(d[12]), c(d[13]), c(d[14]), c(d[15]), c(d[16]), c(d[17]), c(d[18]), c(d[19]), c(d[20]), c(d[21]), c(d[22]), c(d[23]), c(d[24]), c(d[25]), c(d[26]), c(d[27]), c(d[28]), c(d[29]), c(d[30]), c(d[31]), c(d[32]), c(d[33]), c(d[34]), c(d[35]), c(d[36]), c(d[37]), c(d[38]), c(d[39]), c(d[40]), c(d[41]), c(d[42]), c(d[43]), c(d[44]), c(d[45]), c(d[46]), c(d[47])
#define RW32(c, d) c(d[0]), c(d[1]), c(d[2]), c(d[3]), c(d[4]), c(d[5]), c(d[6]), c(d[7]), c(d[8]), c(d[9]), c(d[10]), c(d[11]), c(d[12]), c(d[13]), c(d[14]), c(d[15]), c(d[16]), c(d[17]), c(d[18]), c(d[19]), c(d[20]), c(d[21]), c(d[22]), c(d[23]), c(d[24]), c(d[25]), c(d[26]), c(d[27]), c(d[28]), c(d[29]), c(d[30]), c(d[31])

__device__ __forceinline__ void reg_fence(float (&d)[80]) { asm volatile("" : RW80("+f", d)::"memory"); }
__device__ __forceinline__ void reg_fence(float (&d)[48]) { asm volatile("" : RW48("+f", d)::"memory"); }
__device__ __forceinline__ void reg_fence(float (&d)[32]) { asm volatile("" : RW32("+f", d)::"memory"); }

template <int NR>
__device__ __forceinline__ void zero(float (&d)[NR]) {
#pragma unroll
    for (int i = 0; i < NR; i++) d[i] = 0.f;
}

constexpr uint32_t HI_SW128 = (1024u >> 4) | (1u << 30);
constexpr uint32_t HI_OST = (2560u >> 4) | (2u << 30);
constexpr uint32_t LO_LBO1 = (1u << 16);
constexpr uint32_t LO_OST = ((512u >> 4) << 16);

template <int TA, int TB, uint32_t HIB, int ACC>
__device__ __forceinline__ void wgmma(float (&d)[80], uint32_t loA, uint32_t loB) {
#define WG_ASM(SD)                                                          \
    "{\n.reg .b64 da, db;\nmov.b64 da, {%80, %82};\nmov.b64 db, {%81, %83};\n" \
    "wgmma.mma_async.sync.aligned.m64n160k16.f32.bf16.bf16 "               \
    "{%0,%1,%2,%3,%4,%5,%6,%7,%8,%9,%10,%11,%12,%13,%14,%15,%16,%17,%18,%19,%20,%21,%22,%23,%24,%25,%26,%27,%28,%29,%30,%31,%32,%33,%34,%35,%36,%37,%38,%39,%40,%41,%42,%43,%44,%45,%46,%47,%48,%49,%50,%51,%52,%53,%54,%55,%56,%57,%58,%59,%60,%61,%62,%63,%64,%65,%66,%67,%68,%69,%70,%71,%72,%73,%74,%75,%76,%77,%78,%79}, da, db, " SD ", 1, 1, %84, %85;\n}"
    if constexpr (ACC == 2)
        asm volatile(WG_ASM("0") : RW80("+f", d) : "r"(loA), "r"(loB), "n"(HI_SW128), "n"(HIB), "n"(TA), "n"(TB));
    else if constexpr (ACC == 1)
        asm volatile(WG_ASM("1") : RW80("+f", d) : "r"(loA), "r"(loB), "n"(HI_SW128), "n"(HIB), "n"(TA), "n"(TB));
    else
        asm volatile(WG_ASM("0") : RW80("=f", d) : "r"(loA), "r"(loB), "n"(HI_SW128), "n"(HIB), "n"(TA), "n"(TB));
#undef WG_ASM
}
template <int TA, int TB, uint32_t HIB, int ACC>
__device__ __forceinline__ void wgmma(float (&d)[48], uint32_t loA, uint32_t loB) {
#define WG_ASM(SD)                                                          \
    "{\n.reg .b64 da, db;\nmov.b64 da, {%48, %50};\nmov.b64 db, {%49, %51};\n" \
    "wgmma.mma_async.sync.aligned.m64n96k16.f32.bf16.bf16 "               \
    "{%0,%1,%2,%3,%4,%5,%6,%7,%8,%9,%10,%11,%12,%13,%14,%15,%16,%17,%18,%19,%20,%21,%22,%23,%24,%25,%26,%27,%28,%29,%30,%31,%32,%33,%34,%35,%36,%37,%38,%39,%40,%41,%42,%43,%44,%45,%46,%47}, da, db, " SD ", 1, 1, %52, %53;\n}"
    if constexpr (ACC == 1)
        asm volatile(WG_ASM("1") : RW48("+f", d) : "r"(loA), "r"(loB), "n"(HI_SW128), "n"(HIB), "n"(TA), "n"(TB));
    else
        asm volatile(WG_ASM("0") : RW48("=f", d) : "r"(loA), "r"(loB), "n"(HI_SW128), "n"(HIB), "n"(TA), "n"(TB));
#undef WG_ASM
}
template <int TA, int TB, uint32_t HIB, int ACC>
__device__ __forceinline__ void wgmma(float (&d)[32], uint32_t loA, uint32_t loB) {
#define WG_ASM(SD)                                                          \
    "{\n.reg .b64 da, db;\nmov.b64 da, {%32, %34};\nmov.b64 db, {%33, %35};\n" \
    "wgmma.mma_async.sync.aligned.m64n64k16.f32.bf16.bf16 "               \
    "{%0,%1,%2,%3,%4,%5,%6,%7,%8,%9,%10,%11,%12,%13,%14,%15,%16,%17,%18,%19,%20,%21,%22,%23,%24,%25,%26,%27,%28,%29,%30,%31}, da, db, " SD ", 1, 1, %36, %37;\n}"
    if constexpr (ACC == 1)
        asm volatile(WG_ASM("1") : RW32("+f", d) : "r"(loA), "r"(loB), "n"(HI_SW128), "n"(HIB), "n"(TA), "n"(TB));
    else
        asm volatile(WG_ASM("0") : RW32("=f", d) : "r"(loA), "r"(loB), "n"(HI_SW128), "n"(HIB), "n"(TA), "n"(TB));
#undef WG_ASM
}

__device__ __forceinline__ uint32_t pack_bf16(float lo, float hi) {
    uint32_t r;
    asm("cvt.rn.bf16x2.f32 %0, %1, %2;" : "=r"(r) : "f"(hi), "f"(lo));
    return r;
}
__device__ __forceinline__ float ex2(float x) {
    float r;
    asm("ex2.approx.ftz.f32 %0, %1;" : "=f"(r) : "f"(x));
    return r;
}
__device__ __forceinline__ void stsm4t(uint32_t a, uint32_t r0, uint32_t r1, uint32_t r2, uint32_t r3) {
    asm volatile("stmatrix.sync.aligned.m8n8.x4.trans.shared.b16 [%0], {%1,%2,%3,%4};" ::"r"(a), "r"(r0), "r"(r1), "r"(r2), "r"(r3)
                 : "memory");
}
__device__ __forceinline__ uint32_t lds_u(uint32_t a) {
    uint32_t v;
    asm volatile("ld.shared.u32 %0, [%1];" : "=r"(v) : "r"(a) : "memory");
    return v;
}
__device__ __forceinline__ uint4 lds_u4(uint32_t a) {
    uint4 v;
    asm volatile("ld.shared.v4.u32 {%0,%1,%2,%3}, [%4];" : "=r"(v.x), "=r"(v.y), "=r"(v.z), "=r"(v.w) : "r"(a) : "memory");
    return v;
}
__device__ __forceinline__ float2 lds_f2(uint32_t a) {
    float2 v;
    asm volatile("ld.shared.v2.f32 {%0,%1}, [%2];" : "=f"(v.x), "=f"(v.y) : "r"(a) : "memory");
    return v;
}
__device__ __forceinline__ void sts_f(uint32_t a, float v) { asm volatile("st.shared.f32 [%0], %1;" ::"r"(a), "f"(v) : "memory"); }
__device__ __forceinline__ void sts_u(uint32_t a, uint32_t v) { asm volatile("st.shared.u32 [%0], %1;" ::"r"(a), "r"(v) : "memory"); }
__device__ __forceinline__ void sts_f2(uint32_t a, float x, float y) {
    asm volatile("st.shared.v2.f32 [%0], {%1,%2};" ::"r"(a), "f"(x), "f"(y) : "memory");
}

template <bool ADD = false, int NR>
__device__ __forceinline__ void store_tile_t(const float (&d)[NR], uint32_t addr) {
    uint32_t p[NR / 2];
    if (ADD) {
#pragma unroll
        for (int j = 0; j < NR / 8; j++)
            asm volatile("ldmatrix.sync.aligned.m8n8.x4.trans.shared.b16 {%0,%1,%2,%3}, [%4];"
                         : "=r"(p[4 * j]), "=r"(p[4 * j + 1]), "=r"(p[4 * j + 2]), "=r"(p[4 * j + 3])
                         : "r"(addr + j * 2048)
                         : "memory");
    }
#pragma unroll
    for (int k = 0; k < NR / 2; k++)
        p[k] = ADD ? pack_bf16(d[2 * k] + __uint_as_float(p[k] << 16), d[2 * k + 1] + __uint_as_float(p[k] & 0xffff0000u))
                   : pack_bf16(d[2 * k], d[2 * k + 1]);
#pragma unroll
    for (int j = 0; j < NR / 8; j++) stsm4t(addr + j * 2048, p[4 * j], p[4 * j + 1], p[4 * j + 2], p[4 * j + 3]);
}

struct TrueT { static constexpr bool value = true; };
struct FalseT { static constexpr bool value = false; };

template <int V>
struct IntT { static constexpr int value = V; };

__device__ __forceinline__ uint32_t get_item(uint32_t sb, int it, uint32_t dl) {
    mbar_wait(sb + BAR_ITEM + it * 8, 0, dl);
    return lds_u(sb + OFF_ITEM + it * 4);
}
__device__ __forceinline__ uint32_t get_item_warp(uint32_t sb, int it, uint32_t dl) {
    return __shfl_sync(0xffffffffu, get_item(sb, it, dl), 0);
}

struct Ring {
    uint32_t slot, ph, dl;
    __device__ __forceinline__ void adv(uint32_t k) {
        slot += k;
        if (slot >= NSLOT) { slot -= NSLOT; ph ^= 1; }
    }
};

template <int K>
__device__ __forceinline__ void qk_step(float (&s)[80], uint32_t loK, uint32_t loQ) {
    wgmma<0, 0, HI_SW128, K != 0>(s, loK + (K >> 2) * (8192 >> 4) + (K & 3) * 2, loQ + (K >> 2) * (XS >> 4) + (K & 3) * 2);
}
template <int K0, int K1>
__device__ __forceinline__ void qk_steps(float (&s)[80], uint32_t loK, uint32_t loQ) {
    if constexpr (K0 < K1) {
        qk_step<K0>(s, loK, loQ);
        qk_steps<K0 + 1, K1>(s, loK, loQ);
    }
}
__device__ __forceinline__ uint32_t add_bf2(uint32_t a, uint32_t b) {
    uint32_t r;
    asm("add.rn.bf16x2 %0, %1, %2;" : "=r"(r) : "r"(a), "r"(b));
    return r;
}
__device__ __forceinline__ uint32_t fma_bf2(uint32_t a, uint32_t b, uint32_t c) {
    uint32_t r;
    asm("fma.rn.bf16x2 %0, %1, %2, %3;" : "=r"(r) : "r"(a), "r"(b), "r"(c));
    return r;
}
template <int J>
__device__ __forceinline__ void exp_block(const float (&s)[80], uint32_t (&k)[40], uint32_t pa, float mref) {
    if constexpr (J < 10) {
#pragma unroll
        for (int i = 4 * J; i < 4 * J + 4; i++)
            k[i] = pack_bf16(ex2(fmaf(s[2 * i], SM_C, -mref)), ex2(fmaf(s[2 * i + 1], SM_C, -mref)));
#pragma unroll
        for (int i = 0; i < 4; i++)
            asm volatile("stmatrix.sync.aligned.m8n8.x1.trans.shared.b16 [%0], {%1};" ::"r"(((i & 1) ? pa ^ 16 : pa) + J * 2048 + (i >> 1) * 1024),
                         "r"(k[4 * J + i])
                         : "memory");
        exp_block<J + 1>(s, k, pa, mref);
    }
}
__device__ __forceinline__ void sum_block(const uint32_t (&k)[40], float (&l)[10], uint32_t lane) {
    const bool b4 = lane & 16, b3 = lane & 8;
    uint32_t ps[20], t[10];
#pragma unroll
    for (int j = 0; j < 20; j++) ps[j] = add_bf2(k[2 * j], k[2 * j + 1]);
#pragma unroll
    for (int j = 0; j < 10; j++)
        t[j] = add_bf2(b4 ? ps[2 * j + 1] : ps[2 * j], __shfl_xor_sync(0xffffffffu, b4 ? ps[2 * j] : ps[2 * j + 1], 16));
#pragma unroll
    for (int i = 0; i < 5; i++) {
        const uint32_t a = b3 ? t[i + 5] : t[i], b = __shfl_xor_sync(0xffffffffu, b3 ? t[i] : t[i + 5], 8);
        l[2 * i] += __uint_as_float(a << 16) + __uint_as_float(b << 16);
        l[2 * i + 1] += __uint_as_float(a & 0xffff0000u) + __uint_as_float(b & 0xffff0000u);
    }
}
template <bool ADD>
__device__ __forceinline__ void sum_store(const float (&l)[10], uint32_t lane, uint32_t lxa) {
    const bool b2 = lane & 4;
    float t[5];
#pragma unroll
    for (int i = 0; i < 5; i++) t[i] = ADD ? __uint_as_float(lds_u(lxa + i * 64)) : 0.f;
#pragma unroll
    for (int i = 0; i < 5; i++)
        sts_f(lxa + i * 64, t[i] + (b2 ? l[2 * i + 1] : l[2 * i]) + __shfl_xor_sync(0xffffffffu, b2 ? l[2 * i] : l[2 * i + 1], 4));
}

__device__ __forceinline__ void fallback_unit(const Params& P, uint32_t e, uint32_t tid) {
    const uint32_t lane = tid & 31, br = IT_BR(e), b = IT_B(e), h = IT_H0(e);
    const __nv_bfloat162* wq = (const __nv_bfloat162*)(P.pwq[br] + h * 192) + lane;
    const __nv_bfloat162* kp = (const __nv_bfloat162*)(P.pk[br] + (size_t)(b * 32 + h) * 512 * 192) + lane;
    const __nv_bfloat162* vp = (const __nv_bfloat162*)(P.pv[br] + (size_t)(b * 32 + h) * 512 * 192) + lane;
#pragma unroll 1
    for (uint32_t qi = 0; qi < 40; qi++) {
        const uint32_t q = 4 * qi + (tid >> 5);
        const __nv_bfloat16* xr = P.px[br] + (size_t)(b * 160 + q) * 640;
        float a[6] = {0.f, 0.f, 0.f, 0.f, 0.f, 0.f};
#pragma unroll 2
        for (int k = 0; k < 640; k++) {
            const float xv = __bfloat162float(xr[k]);
#pragma unroll
            for (int i = 0; i < 3; i++) {
                const float2 wv = __bfloat1622float2(wq[(size_t)k * 3072 + i * 32]);
                a[2 * i] = fmaf(xv, wv.x, a[2 * i]);
                a[2 * i + 1] = fmaf(xv, wv.y, a[2 * i + 1]);
            }
        }
#pragma unroll
        for (int i = 0; i < 6; i++) a[i] = __bfloat162float(__float2bfloat16(a[i]));
        auto score = [&](int key) {
            float d = 0.f;
#pragma unroll
            for (int i = 0; i < 3; i++) {
                const float2 kv = __bfloat1622float2(kp[key * 96 + i * 32]);
                d = fmaf(a[2 * i], kv.x, fmaf(a[2 * i + 1], kv.y, d));
            }
#pragma unroll
            for (int o = 16; o > 0; o >>= 1) d += __shfl_xor_sync(0xffffffffu, d, o);
            return d;
        };
        float m = -INFINITY, o[6] = {0.f, 0.f, 0.f, 0.f, 0.f, 0.f}, sum = 0.f;
#pragma unroll 1
        for (int n = 0; n < 1024; n++) {
            const int key = n & 511;
            const float d = score(key);
            if (n < 512) {
                m = fmaxf(m, d);
            } else {
                const float p = ex2((d - m) * SM_C);
                sum += p;
#pragma unroll
                for (int i = 0; i < 3; i++) {
                    const float2 vv = __bfloat1622float2(vp[key * 96 + i * 32]);
                    o[2 * i] = fmaf(p, vv.x, o[2 * i]);
                    o[2 * i + 1] = fmaf(p, vv.y, o[2 * i + 1]);
                }
            }
        }
        const float inv = __fdividef(1.f, sum);
        __nv_bfloat16* op = (__nv_bfloat16*)ostash(IT_SLOT(e), b) + (q >> 5) * 256 + 2 * ((q & 31) >> 3) + (q & 1);
#pragma unroll
        for (int i = 0; i < 6; i++) {
            const uint32_t d = (i >> 1) * 64 + 2 * lane + (i & 1);
            op[(d >> 3) * 1280 + (d & 7) * 32 + ((((q & 7) >> 1) ^ ((d & 7) >> 1)) << 3)] = __float2bfloat16(o[i] * inv);
        }
    }
}

template <int W>
struct PendO {
    static constexpr int N = W == 0 ? 56 : 64;
    uint32_t v[N];
    unsigned char* gp;
    static __device__ __forceinline__ uint32_t toff() {
        const uint32_t t = tid_now();
        return ((t >> 5) & 3) * 5120 + ((t >> 2) & 7) * 64 + (((t ^ (t >> 3)) & 3) << 4);
    }
    uint32_t pend, sig;
    static __device__ __forceinline__ void scale(uint32_t& x, uint32_t hi, uint32_t lo) {
        asm("{\n.reg .b32 t;\nmul.rn.bf16x2 t, %0, %2;\nfma.rn.bf16x2 %0, %0, %1, t;\n}" : "+r"(x) : "r"(hi), "r"(lo));
    }
    template <int I, int OFF>
    __device__ __forceinline__ void put() {
        asm volatile("{\n.reg .pred p;\nsetp.ne.u32 p, %6, 0;\n@p st.global.v4.b32 [%0+%5], {%1,%2,%3,%4};\n}" ::"l"(gp), "r"(v[I]),
                     "r"(v[I + 1]), "r"(v[I + 2]), "r"(v[I + 3]), "n"(OFF), "r"(pend)
                     : "memory");
    }
    __device__ __forceinline__ void verdict(const Params& P, uint32_t sb, int ie) {
        if (sig) {
            nb_sync<NB_VOTE + W, 160>();
            pend = !__any_sync(0xffffffffu, lds_u(sb + OFF_FB) != 0);
            if (W == 1 && !pend) {
                fallback_unit(P, lds_u(sb + OFF_ITEM + ie * 4), tid_now() & 127);
                __syncwarp();
            }
        }
    }
    template <int G, int H>
    __device__ __forceinline__ void half(uint32_t sb) {
        constexpr bool T2 = W == 0 ? G >= 3 : G < 3;
        constexpr int B = T2 ? 40 + 8 * (W == 0 ? G - 3 : G) : 0;
        const uint4 a = lds_u4(sb + OFF_LINV + G * 128 + H * 16 + (threadIdx.x & 3) * 32);
#pragma unroll
        for (int i = 2 * H; i < 8; i += 4) {
            scale(v[8 * G + i], a.x, a.y);
            scale(v[8 * G + i + 1], a.z, a.w);
            if (T2) {
                scale(v[B + i], a.x, a.y);
                scale(v[B + i + 1], a.z, a.w);
            }
        }
        if (H == 1) {
            put<8 * G, W * XS + G * 512>();
            put<8 * G + 4, W * XS + G * 512 + 2560>();
            if (T2) {
                put<B, 2 * XS + G * 512>();
                put<B + 4, 2 * XS + G * 512 + 2560>();
            }
            if (G == 4 && sig) nb_arrive<NB_ODONE, 288>();
        }
    }
    template <int G>
    __device__ __forceinline__ void step(uint32_t sb) {
        half<G, 0>(sb);
        half<G, 1>(sb);
    }
    __device__ __forceinline__ void clear() {
#pragma unroll
        for (int i = 0; i < N; i++) v[i] = 0;
        gp = nullptr;
        pend = 0;
        sig = 0;
    }
};

__device__ __forceinline__ uint32_t stsm_off() {
    const uint32_t tid = tid_now(), lane = tid & 31;
    return (lane >> 4) * 1024 + (lane & 7) * 128 + (((((tid >> 4) & 6) + ((lane >> 3) & 1)) ^ (lane & 7)) << 4);
}
template <int W, int KK>
__device__ __forceinline__ void qproj(float (&q0)[80], float (&q1)[80], uint32_t sb, Ring& r, uint32_t pslot, uint32_t phm,
                                      PendO<W>& po, const Params& P, int it) {
    const uint32_t loR = (((sb + OFF_R) & 0x3ffff) >> 4) | LO_LBO1;
    const uint32_t loRing = (((sb + OFF_RING) & 0x3ffff) >> 4) | LO_LBO1;
    auto ready = [&](int k) {
        mbar_wait(sb + BAR_RFULL + r.slot * 8, r.ph, r.dl);
        mbar_wait(sb + BAR_XFULL + (k % 5) * 8, ((phm >> (k % 5)) ^ (k / 5)) & 1, r.dl);
    };
    auto release = [&]() {
        if (KK > 0) {
            wg_wait<1>();
            mbar_arrive_warp(sb + BAR_REMPTY + pslot * 8);
            if (KK <= 5) mbar_arrive_warp(sb + (BAR_XEMPTY + (KK - 1) * 8));
        }
    };
    if (KK == 0 && (W == 1 || !po.sig)) ready(0);
    if (W == 1 && KK == QHOLD) {
        if (QHOLD == 7) {
            wg_wait<0>();
            nb_arrive<NB_PDONE, 256>();
        }
        nb_sync<NB_SDONE, 256>();
    }
    const uint32_t a = loRing + r.slot * (SLOT >> 4) + (W == 0 ? 0 : 512), b = loR + (KK % 5) * (XS >> 4);
    wg_fence();
    wgmma<1, 0, HI_SW128, KK != 0>(q0, a, b);
    if (W == 0) wgmma<1, 0, HI_SW128, KK != 0>(q1, a + 256, b);
#pragma unroll
    for (int k = 1; k < 4; k++) {
        wgmma<1, 0, HI_SW128, true>(q0, a + (k >> 1) * 768 + (k & 1) * 128, b + k * 2);
        if (W == 0) wgmma<1, 0, HI_SW128, true>(q1, a + 256 + (k >> 1) * 768 + (k & 1) * 128, b + k * 2);
    }
    wg_commit();
    const uint32_t cslot = r.slot;
    r.adv(1);
    if (W == 0 || KK < QHOLD) release();
    if (KK == QST0) {
        po.verdict(P, sb, it - 1);
        po.template half<0, 0>(sb);
    }
    if (KK < 9) ready(KK + 1);
    if (W == 1 && KK >= QHOLD) release();
    if (W == 1 && KK == 7 && QHOLD > 7) nb_arrive<NB_PDONE, 256>();
    if (KK == QST0) po.template half<0, 1>(sb);
    if constexpr (KK > QST0 && KK < QST0 + 5) po.template step<KK - QST0>(sb);
    if constexpr (KK < (W == 0 ? 7 : 9)) {
        qproj<W, KK + 1>(q0, q1, sb, r, cslot, phm, po, P, it);
    } else if constexpr (W == 1) {
        wg_wait<0>();
        reg_fence(q0);
        mbar_arrive_warp(sb + BAR_REMPTY + cslot * 8);
        store_tile_t(q0, sb + OFF_R + 2 * XS + stsm_off());
    } else {
        const uint32_t s8 = r.slot, a8 = loRing + s8 * (SLOT >> 4);
        wg_fence();
#pragma unroll
        for (int k = 0; k < 4; k++) wgmma<1, 0, HI_SW128, true>(q0, a8 + (k >> 1) * 768 + (k & 1) * 128, loR + 3 * (XS >> 4) + k * 2);
        r.adv(1);
        ready(9);
        const uint32_t s9 = r.slot, a9 = loRing + s9 * (SLOT >> 4);
        r.adv(1);
        wg_fence();
#pragma unroll
        for (int k = 0; k < 4; k++) wgmma<1, 0, HI_SW128, true>(q0, a9 + (k >> 1) * 768 + (k & 1) * 128, loR + 4 * (XS >> 4) + k * 2);
        wg_commit();
        wg_wait<1>();
        mbar_arrive_warp(sb + BAR_REMPTY + cslot * 8);
        wg_fence();
#pragma unroll
        for (int k = 0; k < 8; k++)
            wgmma<1, 0, HI_SW128, true>(q1, (k < 4 ? a8 : a9) + 256 + ((k >> 1) & 1) * 768 + (k & 1) * 128,
                                        loR + (3 + (k >> 2)) * (XS >> 4) + (k & 3) * 2);
        wg_commit();
        nb_arrive<NB_SDONE, 256>();
        nb_sync<NB_PDONE, 256>();
        wg_wait<1>();
        reg_fence(q0);
        const uint32_t sta = sb + OFF_R + stsm_off();
        store_tile_t(q0, sta);
        sts_u(sb + OFF_GM + 4, r.slot);
        mbar_wait(sb + BAR_RFULL + r.slot * 8, r.ph, r.dl);
        wg_wait<0>();
        reg_fence(q1);
        mbar_arrive_warp(sb + BAR_REMPTY + s8 * 8);
        mbar_arrive_warp(sb + BAR_REMPTY + s9 * 8);
        store_tile_t(q1, sta + XS);
    }
}

template <int NR>
__device__ __forceinline__ void opack(const float (&o)[NR], uint32_t* v) {
#pragma unroll
    for (int g = 0; g < NR / 16; g++)
#pragma unroll
        for (int hh = 0; hh < 2; hh++)
#pragma unroll
            for (int t = 0; t < 4; t++) v[8 * g + 4 * hh + t] = pack_bf16(o[16 * g + 4 * t + 2 * hh], o[16 * g + 4 * t + 2 * hh + 1]);
}

template <bool IS_S>
__device__ __forceinline__ void op_item(uint32_t e, uint32_t sb, Ring& r, uint32_t& phm) {
    constexpr int T0 = IS_S ? 0 : 2;
    constexpr uint32_t BOFF = IS_S ? (3 * 512) >> 4 : 0;
    const uint32_t loRing = (((sb + OFF_RING) & 0x3ffff) >> 4) | LO_LBO1;
    const uint32_t loO = (((sb + OFF_R) & 0x3ffff) >> 4) | LO_OST;
    float c0[80], c1[80], c2[IS_S ? 32 : 48];
    const int T = 3 * (IT_H1(e) - IT_H0(e));
    uint32_t xs = 0;
    auto step = [&](auto first, auto half) {
        constexpr bool F = decltype(first)::value;
        constexpr uint32_t hf = decltype(half)::value;
        if (hf == 0) {
            mbar_wait(sb + BAR_XFULL + xs * 8, (phm >> xs) & 1, r.dl);
            phm ^= 1u << xs;
        }
        mbar_wait(sb + BAR_RFULL + r.slot * 8, r.ph, r.dl);
        const uint32_t a = loRing + r.slot * (SLOT >> 4), b = loO + xs * (XS >> 4) + hf * 640;
        wg_fence();
        wgmma<1, 1, HI_OST, !F>(c0, a + T0 * 128, b);
        wgmma<1, 1, HI_OST, !F>(c1, a + T0 * 128 + 128, b);
        wgmma<1, 1, HI_OST, !F>(c2, a + 512, b + BOFF);
        wgmma<1, 1, HI_OST, true>(c0, a + 640 + T0 * 128, b + 320);
        wgmma<1, 1, HI_OST, true>(c1, a + 640 + T0 * 128 + 128, b + 320);
        wgmma<1, 1, HI_OST, true>(c2, a + 640 + 512, b + 320 + BOFF);
        wg_commit();
    };
    step(TrueT{}, IntT<0>{});
#pragma unroll 1
    for (int t = 1;; t++) {
        uint32_t pslot = r.slot;
        r.adv(1);
        step(FalseT{}, IntT<1>{});
        wg_wait<1>();
        mbar_arrive_warp(sb + BAR_REMPTY + pslot * 8);
        if (t == T) break;
        pslot = r.slot;
        const uint32_t pxs = xs;
        r.adv(1);
        if (++xs == 5) xs = 0;
        step(FalseT{}, IntT<0>{});
        wg_wait<1>();
        mbar_arrive_warp(sb + BAR_REMPTY + pslot * 8);
        mbar_arrive_warp_if(sb + BAR_XEMPTY + pxs * 8, t + 4 < T);
    }
    wg_wait<0>();
    reg_fence(c0);
    reg_fence(c1);
    reg_fence(c2);
    mbar_arrive_warp(sb + BAR_REMPTY + r.slot * 8);
    r.adv(1);
    nb_sync<NB_OPEND, 256>();
    const uint32_t sta = sb + OFF_R + stsm_off();
    store_tile_t(c0, sta + T0 * XS);
    store_tile_t(c1, sta + (T0 + 1) * XS);
    store_tile_t(c2, sta + 4 * XS + (IS_S ? 96 * 128 : 0));
    fence_async_smem();
    nb_arrive<NB_ODONE, 288>();
}

template <int W>
__device__ __forceinline__ void on_item(uint32_t e, uint32_t sb, Ring& r, uint32_t& phm) {
    const uint32_t loRing = (((sb + OFF_RING) & 0x3ffff) >> 4) | LO_LBO1;
    const uint32_t loO = (((sb + OFF_R) & 0x3ffff) >> 4) | LO_OST;
    float c[80];
    const int T = 3 * (IT_H1(e) - IT_H0(e));
    uint32_t xs = 0;
    auto step = [&](auto first) {
        constexpr bool F = decltype(first)::value;
        mbar_wait(sb + BAR_XFULL + xs * 8, (phm >> xs) & 1, r.dl);
        phm ^= 1u << xs;
        mbar_wait(sb + BAR_RFULL + r.slot * 8, r.ph, r.dl);
        const uint32_t a = loRing + r.slot * (SLOT >> 4) + W * 256, b = loO + xs * (XS >> 4);
        wg_fence();
        wgmma<1, 1, HI_OST, !F>(c, a, b);
#pragma unroll
        for (int k = 1; k < 4; k++) wgmma<1, 1, HI_OST, true>(c, a + (k >> 1) * 512 + (k & 1) * 128, b + k * 320);
        wg_commit();
    };
    step(TrueT{});
#pragma unroll 1
    for (int t = 1; t < T; t++) {
        const uint32_t pslot = r.slot, pxs = xs;
        r.adv(1);
        if (++xs == 5) xs = 0;
        step(FalseT{});
        wg_wait<1>();
        mbar_arrive_warp(sb + BAR_REMPTY + pslot * 8);
        mbar_arrive_warp_if(sb + BAR_XEMPTY + pxs * 8, t + 2 < T);
    }
    xs += 1 + W;
    if (xs >= 5) xs -= 5;
    mbar_wait(sb + BAR_XFULL + xs * 8, (phm >> xs) & 1, r.dl);
    wg_wait<0>();
    reg_fence(c);
    store_tile_t<true>(c, sb + OFF_R + xs * XS + stsm_off());
    fence_async_smem();
    nb_arrive<NB_ODONE, 288>();
}

template <int W>
__device__ __forceinline__ uint32_t qa_item(const Params& P, uint32_t e, uint32_t sb, Ring& r, uint32_t phm, PendO<W>& po, int it) {
    const uint32_t loR = (((sb + OFF_R) & 0x3ffff) >> 4) | LO_LBO1;
    const uint32_t loRing = (((sb + OFF_RING) & 0x3ffff) >> 4) | LO_LBO1;
    {
        float q0[80], q1[80];
        qproj<W, 0>(q0, q1, sb, r, 0, phm, po, P, it);
    }
    fence_async_smem();
    TSD(W, 1);
    float s[80], oa[80], ob[W == 0 ? 32 : 48], l[10];
    if (W == 1) {
        nb_arrive<NB_Q2, 256>();
        nb_arrive<NB_L, 160>();
        zero(oa);
        zero(ob);
        reg_fence(oa);
        reg_fence(ob);
    }
    const uint32_t lane = tid_now() & 31, sta = sb + OFF_R + stsm_off();
    auto pv = [&](auto first, uint32_t buf) {
        constexpr bool F = decltype(first)::value;
        mbar_wait(sb + BAR_RFULL + r.slot * 8, r.ph, r.dl);
        const uint32_t a = loRing + r.slot * (SLOT >> 4), b = loR + (3 + buf) * (XS >> 4);
        wg_fence();
        wgmma<1, 0, HI_SW128, !F>(oa, a + W * 512, b);
        wgmma<1, 0, HI_SW128, !F>(ob, a + 1024, b + (W == 0 ? (96 * 128) >> 4 : 0));
#pragma unroll
        for (int k = 1; k < 4; k++) {
            wgmma<1, 0, HI_SW128, true>(oa, a + W * 512 + k * 128, b + k * 2);
            wgmma<1, 0, HI_SW128, true>(ob, a + 1024 + k * 128, b + (W == 0 ? (96 * 128) >> 4 : 0) + k * 2);
        }
        wg_commit();
    };
    zero(l);
    float mref;
    uint32_t kslot, vslot;
    auto tail = [&](auto first, int i) {
        constexpr bool rel_other = !decltype(first)::value;
        uint32_t ps[40];
        exp_block<0>(s, ps, sta + (3 + W) * XS, mref);
        if (rel_other) {
            wg_wait<0>();
            mbar_arrive_warp(sb + BAR_REMPTY + vslot * 8);
            if (W == 1) mbar_arrive_warp_if(sb + BAR_XEMPTY + 24, i == 3);
        }
        fence_async_smem();
        nb_arrive<NB_PFULL + W, 256>();
        TSD(W, 6 + 5 * i);
        if (W == 1) {
            if (XLATE >= 2) mbar_arrive_warp_if<2>(sb + BAR_XEMPTY + 8, i == 3);
            if (XLATE >= 1) mbar_arrive_warp_if<2>(sb + BAR_XEMPTY + 16, i == 3);
        }
        if (rel_other || !PV0FIRST) {
            mbar_wait(sb + BAR_RFULL + r.slot * 8, r.ph, r.dl);
            sum_block(ps, l, lane);
        }
        TSD(W, 7 + 5 * i);
        nb_sync<NB_W + W, 128>();
        pv(first, W);
        if (!rel_other && PV0FIRST) sum_block(ps, l, lane);
        TSD(W, 8 + 5 * i);
    };
    if (W == 0) {
        nb_sync<NB_QK, 160>();
        TSD(W, 2);
        wg_fence();
        qk_steps<0, 8>(s, loRing + r.slot * (SLOT >> 4), loR);
        nb_sync<NB_Q2, 256>();
        qk_steps<8, 12>(s, loRing + r.slot * (SLOT >> 4), loR);
        wg_commit();
        nb_arrive<NB_Q01, 256>();
        TSD(W, 4);
        nb_sync<NB_REF, 160>();
        mref = __uint_as_float(lds_u(sb + OFF_GM));
        wg_wait<0>();
        reg_fence(s);
        mbar_arrive_warp<2>(sb + BAR_REMPTY + r.slot * 8);
        r.adv(2);
        TSD(W, 5);
        tail(TrueT{}, 0);
    } else {
        nb_sync<NB_Q01, 256>();
    }
#pragma unroll 1
    for (int i = (W == 0 ? 1 : 0); i < 4; i++) {
        const uint32_t pvslot = r.slot;
        r.adv(1);
        kslot = r.slot;
        mbar_wait(sb + BAR_RFULL + r.slot * 8, r.ph, r.dl);
        wg_fence();
        qk_steps<0, 12>(s, loRing + r.slot * (SLOT >> 4), loR);
        wg_commit();
        wg_wait<1>();
        mbar_arrive_warp_if(sb + BAR_REMPTY + pvslot * 8, W == 0 || i > 0);
        r.adv(1);
        vslot = r.slot;
        TSD(W, 4 + 5 * i);
        nb_sync<NB_PFULL + (W ^ 1), 256>();
        pv(FalseT{}, W ^ 1);
        if (W == 1) mref = __uint_as_float(lds_u(sb + OFF_GM));
        wg_wait<1>();
        reg_fence(s);
        mbar_arrive_warp<2>(sb + BAR_REMPTY + kslot * 8);
        if (W == 1) {
            mbar_arrive_warp_if<2>(sb + BAR_XEMPTY + 0, i == 3);
            if (XLATE < 2) mbar_arrive_warp_if<2>(sb + BAR_XEMPTY + 8, i == 3);
            if (XLATE < 1) mbar_arrive_warp_if<2>(sb + BAR_XEMPTY + 16, i == 3);
        }
        r.adv(W == 1 && i == 3 ? 1 : 2);
        TSD(W, 5 + 5 * i);
        tail(FalseT{}, i);
    }
    const uint32_t w = (tid_now() >> 5) & 3;
    const uint32_t lxa = sb + OFF_LX + w * 640 + (((lane & 8) ? 80 : 0) + ((lane >> 1) & 8) + 2 * (lane & 3) + ((lane >> 2) & 1)) * 4;
    const uint32_t nx = get_item_warp(sb, it + 1, r.dl);
    po.gp = ostash(IT_SLOT(e), IT_B(e)) + po.toff();
    po.sig = 1;
    if (W == 0) {
        sum_store<false>(l, lane, lxa);
        nb_arrive<NB_LX, 256>();
        wg_wait<0>();
        mbar_arrive_warp(sb + BAR_REMPTY + r.slot * 8);
        mbar_arrive_warp(sb + BAR_XEMPTY + 24);
        r.adv(1);
        nb_sync<NB_PFULL + 1, 256>();
        pv(FalseT{}, 1);
        if (IT_TYPE(nx) == IT_QA) {
            Ring rn = r;
            rn.adv(1);
            mbar_wait(sb + BAR_RFULL + rn.slot * 8, rn.ph, r.dl);
            mbar_wait(sb + BAR_XFULL, phm & 1, r.dl);
        }
    } else {
        nb_sync<NB_LX, 256>();
        sum_store<true>(l, lane, lxa);
        nb_arrive<NB_L, 160>();
    }
    TSD(W, 24);
    wg_wait<0>();
    reg_fence(oa);
    reg_fence(ob);
    mbar_arrive_warp(sb + BAR_REMPTY + r.slot * 8);
    mbar_arrive_warp(sb + BAR_XEMPTY + 32);
    r.adv(1);
    opack(ob, po.v + 40);
    opack(oa, po.v);
    return nx;
}

template <int W>
__device__ __forceinline__ void consumer(const Params& P, uint32_t sb, uint32_t dl) {
    int it = 0;
    if (W == 0) TS(0, 30);
    Ring r{0, 0, dl};
    uint32_t phm = 0;
    uint32_t e = get_item_warp(sb, 0, dl);
#pragma unroll 1
    while (e != 0) {
        if (IT_TYPE(e) == IT_QA) {
            PendO<W> po;
            po.clear();
#pragma unroll 1
            do {
                TS(W, 0);
                if (W == 0) TS_ITEM(e);
                e = qa_item<W>(P, e, sb, r, phm, po, it);
                TS(W, 31);
                it++;
            } while (IT_TYPE(e) == IT_QA);
            po.verdict(P, sb, it - 1);
            po.template step<0>(sb);
            po.template step<1>(sb);
            po.template step<2>(sb);
            po.template step<3>(sb);
            po.template step<4>(sb);
        } else {
            TS(W, 0);
            if (W == 0) TS_ITEM(e);
            if (IT_TYPE(e) == IT_OP) op_item<W == 0>(e, sb, r, phm);
            else on_item<W>(e, sb, r, phm);
            TS(W, 31);
            e = get_item_warp(sb, ++it, dl);
        }
    }
    TS_DUMP(W);
}

__global__ void __cluster_dims__(2, 1, 1) __launch_bounds__(384, 1) fused_kernel(const __grid_constant__ Params P) {
    extern __shared__ __align__(1024) unsigned char smem_raw[];
    const uint32_t sb = (uint32_t)__cvta_generic_to_shared(smem_raw);
    const uint32_t wgid = __shfl_sync(0xffffffffu, threadIdx.x >> 7, 0);
    const uint32_t cta = blockIdx.x;
    const uint32_t dl = deadline();

    if (threadIdx.x == 128) {
#pragma unroll
        for (int i = 0; i < NSLOT; i++) {
            mbar_init(sb + BAR_RFULL + i * 8, 1);
            mbar_init(sb + BAR_REMPTY + i * 8, 8);
            mbar_init(sb + BAR_XFULL + i * 8, 1);
            mbar_init(sb + BAR_XEMPTY + i * 8, 8);
        }
        asm volatile("fence.mbarrier_init.release.cluster;" ::: "memory");
        fence_async_smem();
    } else if (threadIdx.x == 160) {
#pragma unroll
        for (int i = 0; i < NSLOT + MAXI; i++) mbar_init(sb + BAR_PRDY + i * 8, 1);
        asm volatile("fence.mbarrier_init.release.cluster;" ::: "memory");
    } else if (threadIdx.x == 0) {
        sts_u(sb + OFF_ITEM, P.cl[cta >> 1].items[0] ? P.cl[cta >> 1].items[0] + 8 * (cta & 1) : 0);
        sts_u(sb + OFF_FB, P.cl[cta >> 1].delay);
    } else if (threadIdx.x == 64) {
        if (sb & 1023) __trap();
        asm volatile("prefetch.tensormap [%0];" ::"l"(&P.wq[0]) : "memory");
        asm volatile("prefetch.tensormap [%0];" ::"l"(&P.x[0]) : "memory");
    }
    __syncthreads();
    asm volatile("barrier.cluster.arrive.relaxed.aligned;" ::: "memory");

    if (wgid == 0) {
        asm volatile("setmaxnreg.dec.sync.aligned.u32 24;");
        const uint32_t warp = __shfl_sync(0xffffffffu, threadIdx.x >> 5, 0);
        if (warp == 0) {
            const bool lead = threadIdx.x == 0;
            const uint64_t pol_first = mkpol<1>(), pol_norm = mkpol<POL_W>();
            uint32_t e = __shfl_sync(0xffffffffu, lds_u(sb + OFF_ITEM), 0);
            {
                const uint32_t d = lds_u(sb + OFF_FB);
                uint32_t t0, t1;
                asm volatile("mov.u32 %0, %%clock;" : "=r"(t0));
                do {
                    asm volatile("mov.u32 %0, %%clock;" : "=r"(t1));
                } while (t1 - t0 < d);
                __syncwarp();
            }
            if (lead) asm volatile("mbarrier.arrive.shared::cta.b64 _, [%0];" ::"r"(sb + BAR_ITEM) : "memory");
#pragma unroll 1
            for (int n = 0; n < (e ? NSLOT : 0); n++) {
                if (lead) {
                    mbar_expect(sb + BAR_RFULL + n * 8, SLOT);
                    tma3(sb + OFF_RING + n * SLOT, &P.wq[0], n * 64, IT_H0(e) * 3, sb + BAR_RFULL + n * 8, pol_norm);
                    mbar_expect(sb + BAR_XFULL + n * 8, XS);
                    tma3(sb + OFF_R + n * XS, &P.x[0], IT_B(e) * 160, n, sb + BAR_XFULL + n * 8, pol_norm);
                    tma3(sb + OFF_RING + n * SLOT + SLOT / 2, &P.wq[0], n * 64 + 32, IT_H0(e) * 3, sb + BAR_RFULL + n * 8, pol_norm);
                }
            }
            __syncwarp();
            asm volatile("barrier.cluster.wait.aligned;" ::: "memory");
            unsigned int* const ticket = &g_ticket[next_epoch(0) & 1];
            const uint32_t rank = cta & 1;
            uint32_t peer;
            asm volatile("mapa.shared::cluster.u32 %0, %1, %2;" : "=r"(peer) : "r"(sb), "r"(rank ^ 1));
            Ring r{0, 0, dl};
            uint32_t pm = 0;
            auto load_w = [&](const CUtensorMap* m, int row, int blk, uint32_t half_bytes) {
                mbar_wait(sb + BAR_REMPTY + r.slot * 8, r.ph, dl);
                if (lead) {
                    mbar_expect(sb + BAR_RFULL + r.slot * 8, 2 * half_bytes);
                    asm volatile("mbarrier.arrive.shared::cluster.b64 _, [%0];" ::"r"(peer + BAR_PRDY + r.slot * 8) : "memory");
                }
                mbar_wait(sb + BAR_PRDY + r.slot * 8, (pm >> r.slot) & 1, dl);
                pm ^= 1u << r.slot;
                if (lead) tma3_mc(sb + OFF_RING + r.slot * SLOT + rank * half_bytes, m, row, blk, sb + BAR_RFULL + r.slot * 8, pol_norm);
                r.adv(1);
            };
#pragma unroll 1
            for (int it = 0; e != 0; it++) {
                uint32_t nx = 0, tk = 0;
                if (rank == 0 && IT_TYPE(e) != IT_ON && it + 2 < MAXI) nx = it + 1 < NSTAT ? P.cl[cta >> 1].items[it + 1] : IT_DYN;
                const uint32_t br = IT_BR(e);
                if (IT_TYPE(e) == IT_QA) {
                    const uint32_t h = IT_H0(e);
#pragma unroll 1
                    for (int kk = it ? 0 : NSLOT; kk < 10; kk++) load_w(&P.wq[br], kk * 64 + rank * 32, h * 3, SLOT / 2);
                    const int row0 = (IT_B(e) * 32 + h) * 512;
#pragma unroll 1
                    for (int n = 0; n < 16; n++) {
                        if (n == 13 && nx == IT_DYN && lead) tk = atomicAdd(ticket, 1);
                        const bool isv = n == 15 || (n > 0 && !(n & 1));
                        const int j = n == 15 ? 7 : isv ? (n - 2) >> 1 : (n + 1) >> 1;
                        mbar_wait(sb + BAR_REMPTY + r.slot * 8, r.ph, dl);
                        if (lead) {
                            mbar_expect(sb + BAR_RFULL + r.slot * 8, SLOT);
                            tma3(sb + OFF_RING + r.slot * SLOT, isv ? &P.v[br] : &P.k[br], row0 + j * 64, 0,
                                 sb + BAR_RFULL + r.slot * 8, pol_first);
                        }
                        r.adv(1);
                    }
                } else {
                    const bool wide = IT_TYPE(e) == IT_OP;
                    const int step = wide ? 32 : 64, r1 = IT_H1(e) * 192;
#pragma unroll 1
                    for (int row = IT_H0(e) * 192 + rank * (step >> 1); row < r1; row += step)
                        load_w(wide ? &P.wo[br] : &P.won[br], row, IT_HALF(e) * (wide ? 5 : 2), wide ? XS / 2 : 8192);
                    if (nx == IT_DYN && lead) tk = atomicAdd(ticket, 1);
                }
                if (rank == 0) {
                    if (nx == IT_DYN) {
                        tk = __shfl_sync(0xffffffffu, tk, 0);
                        nx = tk < P.nlist ? P.list[tk] : 0;
                    }
                    e = nx;
                    if (lead) {
                        asm volatile("st.async.weak.shared::cluster.mbarrier::complete_tx::bytes.b32 [%0], %1, [%2];" ::"r"(
                                         peer + OFF_ITEM + 4 + it * 4),
                                     "r"(e ? e + 8 : 0), "r"(peer + BAR_ITEM + 8 + it * 8)
                                     : "memory");
                        sts_u(sb + OFF_ITEM + 4 + it * 4, e);
                        asm volatile("mbarrier.arrive.shared::cta.b64 _, [%0];" ::"r"(sb + BAR_ITEM + 8 + it * 8) : "memory");
                    }
                } else {
                    if (lead) mbar_expect(sb + BAR_ITEM + 8 + it * 8, 4);
                    e = get_item_warp(sb, it + 1, dl);
                }
            }
        } else if (warp == 1) {
            const uint64_t pol_norm = mkpol<POL_X>(), pol_o = mkpol<POL_O>();
            const bool lead = threadIdx.x == 32;
            uint32_t phm = 0, epoch = 0;
#pragma unroll 1
            for (int it = 0;; it++) {
                const uint32_t e = get_item_warp(sb, it, dl);
                if (it == 1 || (it == 0 && e == 0)) epoch = next_epoch(1);
                if (e == 0) break;
                const uint32_t br = IT_BR(e);
                uint32_t xs = 0;
                auto acquire = [&]() {
                    mbar_wait(sb + BAR_XEMPTY + xs * 8, (phm >> xs) & 1, dl);
                    phm ^= 1u << xs;
                    if (lead) mbar_expect(sb + BAR_XFULL + xs * 8, XS);
                };
                if (IT_TYPE(e) == IT_QA) {
#pragma unroll 1
                    for (int kk = it ? 0 : 5; kk < 10; kk++) {
                        acquire();
                        if (lead) tma3(sb + OFF_R + xs * XS, &P.x[br], IT_B(e) * 160, kk, sb + BAR_XFULL + xs * 8, pol_norm);
                        if (++xs == 5) xs = 0;
                    }
                } else {
                    const unsigned int* fp = g_flag + (br * 16 + IT_B(e)) * 64 + (threadIdx.x & 31);
                    uint32_t hm = 0, pm = 0;
                    auto poll = [&](uint32_t hneed, uint32_t pneed) {
                        if ((hm & hneed) == hneed && (pm & pneed) == pneed) return;
                        uint32_t n = 0;
                        do {
                            uint32_t a, b;
                            asm volatile("ld.acquire.gpu.global.u32 %0, [%2];\nld.acquire.gpu.global.u32 %1, [%2+128];"
                                         : "=r"(a), "=r"(b) : "l"(fp) : "memory");
                            hm = __ballot_sync(0xffffffffu, a == epoch);
                            pm = __ballot_sync(0xffffffffu, b == epoch);
                            if (++n > 0x1000000) __trap();
                        } while ((hm & hneed) != hneed || (pm & pneed) != pneed);
                        __syncwarp();
                        asm volatile("fence.proxy.async;" ::: "memory");
                    };
#pragma unroll 1
                    for (uint32_t h = IT_H0(e); h < IT_H1(e); h++) {
                        poll(1u << h, 0);
                        const unsigned char* src = ostash(P.slot[br * 32 + h], IT_B(e));
#pragma unroll 1
                        for (int t = 0; t < 3; t++) {
                            acquire();
                            if (lead) bulk_load(sb + OFF_R + xs * XS, src + t * XS, XS, sb + BAR_XFULL + xs * 8, pol_o);
                            if (++xs == 5) xs = 0;
                        }
                        if (IT_TYPE(e) == IT_OP && h >= 1) {
                            const uint32_t x1 = xs == 4 ? 0 : xs + 1;
                            mbar_wait(sb + BAR_XFULL + xs * 8, (phm >> xs) & 1, dl);
                            mbar_wait(sb + BAR_XFULL + x1 * 8, (phm >> x1) & 1, dl);
                            if (lead)
                                asm volatile("st.relaxed.gpu.global.u32 [%0], %1;" ::"l"(fp + 34 + IT_HALF(e)), "r"(epoch * 64 + h) : "memory");
                        }
                    }
                    if (IT_TYPE(e) == IT_ON) {
                        poll(0, IT_HALF(e) < 2 ? 1 : IT_HALF(e) == 2 ? 3 : 2);
#pragma unroll 1
                        for (uint32_t tile = 2 * IT_HALF(e); tile < 2 * IT_HALF(e) + 2; tile++) {
                            acquire();
                            if (lead)
                                asm volatile(
                                    "cp.async.bulk.tensor.5d.shared::cluster.global.mbarrier::complete_tx::bytes [%0], [%1, {%3,%5,%5,%5,%4}], [%2];" ::"r"(
                                        sb + OFF_R + xs * XS),
                                    "l"(&P.out), "r"(sb + BAR_XFULL + xs * 8), "r"(br * 640 + tile * 64), "r"(IT_B(e) * 5), "r"(0)
                                    : "memory");
                            if (++xs == 5) xs = 0;
                        }
                    }
                }
            }
        } else if (warp == 2) {
            asm volatile("barrier.cluster.wait.aligned;" ::: "memory");
            const uint32_t epoch = next_epoch(2);
            if (cta == 0) g_ticket[(epoch + 1) & 1] = 0;
#pragma unroll 1
            for (int it = 0;; it++) {
                const uint32_t e = get_item_warp(sb, it, dl);
                if (e == 0) break;
                nb_sync<NB_ODONE, 288>();
                if (threadIdx.x == 64) {
                    const uint32_t bb = IT_BR(e) * 16 + IT_B(e);
                    if (IT_TYPE(e) != IT_QA) {
                        const bool wide = IT_TYPE(e) == IT_OP;
                        if (wide)
                            asm volatile("st.relaxed.gpu.global.u32 [%0], %1;" ::"l"(&g_flag[bb * 64 + 34 + IT_HALF(e)]),
                                         "r"(epoch * 64 + IT_H1(e))
                                         : "memory");
                        const int cc0 = IT_BR(e) * 640 + IT_HALF(e) * (wide ? 320 : 128);
                        uint32_t xs = wide ? 0 : (3 * (IT_H1(e) - IT_H0(e))) % 5;
#pragma unroll 1
                        for (int m = 0; m < (wide ? 5 : 2); m++) {
                            asm volatile("cp.async.bulk.tensor.5d.global.shared::cta.bulk_group [%0, {%2,%4,%4,%4,%3}], [%1];" ::"l"(&P.out),
                                         "r"(sb + OFF_R + xs * XS), "r"(cc0 + m * 64), "r"((int)IT_B(e) * 5), "r"(0)
                                         : "memory");
                            asm volatile("cp.async.bulk.commit_group;" ::: "memory");
                            if (++xs == 5) xs = 0;
                        }
                        if (wide) {
#define REL(N)                                                          \
    asm volatile("cp.async.bulk.wait_group.read %0;" ::"n"(4 - N) : "memory"); \
    asm volatile("mbarrier.arrive.shared::cta.b64 _, [%0], 8;" ::"r"(sb + BAR_XEMPTY + N * 8) : "memory");
                            REL(0) REL(1) REL(2) REL(3) REL(4)
#undef REL
                        }
                        if (IT_PART(e)) {
                            asm volatile("cp.async.bulk.wait_group 0;" ::: "memory");
                            asm volatile("fence.proxy.async;" ::: "memory");
                        }
                    }
                    if (IT_TYPE(e) == IT_QA || IT_PART(e)) {
                        unsigned int* f = &g_flag[bb * 64 + (IT_TYPE(e) == IT_QA ? IT_H0(e) : 32 + IT_HALF(e))];
                        asm volatile("st.release.gpu.global.u32 [%0], %1;" ::"l"(f), "r"(epoch) : "memory");
                    }
                }
                __syncwarp();
            }
            if (threadIdx.x == 64) asm volatile("cp.async.bulk.wait_group 0;" ::: "memory");
            __syncwarp();
            asm volatile("barrier.cluster.arrive.relaxed.aligned;\nbarrier.cluster.wait.aligned;" ::: "memory");
        } else {
            const uint32_t lane = threadIdx.x & 31, p = lane >> 2;
            const uint32_t epoch = next_epoch(3);
#pragma unroll 1
            for (int it = 0;; it++) {
                const uint32_t e = get_item_warp(sb, it, dl);
                if (e == 0) break;
                if (IT_TYPE(e) != IT_QA) continue;
                nb_sync<NB_QK, 160>();
                const uint32_t co = (((lane & 3) * 2) ^ p) << 4;
                const uint32_t ka = sb + OFF_RING + lds_u(sb + OFF_GM + 4) * SLOT + p * (9 * 128) + co;
                const uint32_t qa = sb + OFF_R + p * (17 * 128) + co;
                uint32_t acc = 0;
#pragma unroll 1
                for (int c = 0; c < 3; c++) {
                    if (c == 2) nb_sync<NB_L, 160>();
                    const uint4 k0 = lds_u4(ka + c * 8192), q0 = lds_u4(qa + c * XS);
                    acc = fma_bf2(k0.x, q0.x, fma_bf2(k0.y, q0.y, fma_bf2(k0.z, q0.z, fma_bf2(k0.w, q0.w, acc))));
                    const uint4 k1 = lds_u4((ka + c * 8192) ^ 16), q1 = lds_u4((qa + c * XS) ^ 16);
                    acc = fma_bf2(k1.x, q1.x, fma_bf2(k1.y, q1.y, fma_bf2(k1.z, q1.z, fma_bf2(k1.w, q1.w, acc))));
                }
                float d = __uint_as_float(acc << 16) + __uint_as_float(acc & 0xffff0000u);
                d += __shfl_xor_sync(0xffffffffu, d, 1);
                d += __shfl_xor_sync(0xffffffffu, d, 2);
                int key = __float_as_int(d);
                key ^= (key >> 31) & 0x7fffffff;
                key = __reduce_max_sync(0xffffffffu, key);
                key ^= (key >> 31) & 0x7fffffff;
                sts_f(sb + OFF_GM, __int_as_float(key) * SM_C);
                nb_arrive<NB_REF, 160>();
                if (IT_DEP(e)) {
                    const uint32_t g = IT_DEP(e) - 1, need = epoch * 64 + (g & 31) + 1;
                    const unsigned int* cp = &g_flag[((g >> 5) * 16 + IT_B(e)) * 64 + 34 + (lane & 1)];
                    for (uint32_t n = 0;; n++) {
                        uint32_t v;
                        asm volatile("ld.acquire.gpu.global.u32 %0, [%1];" : "=r"(v) : "l"(cp) : "memory");
                        if (__all_sync(0xffffffffu, v - need < 64)) break;
                        if (n > 0x800000) __trap();
                        __nanosleep(500);
                    }
                }
                nb_sync<NB_L, 160>();
                bool bad = false;
#pragma unroll
                for (int c = 0; c < 5; c++) {
                    const uint32_t la = sb + OFF_LX + (c * 32 + lane) * 4;
                    const float v = (__uint_as_float(lds_u(la)) + __uint_as_float(lds_u(la + 640))) +
                                    (__uint_as_float(lds_u(la + 1280)) + __uint_as_float(lds_u(la + 1920)));
                    const float inv = __fdividef(1.f, v);
                    const uint32_t hi = pack_bf16(inv, 0.f), lo = pack_bf16(inv - __uint_as_float(hi << 16), 0.f);
                    const uint32_t ia = sb + OFF_LINV + c * 128 + ((lane >> 1) & 3) * 32 + (lane >> 3) * 8 + (lane & 1) * 2;
                    asm volatile("st.shared.u16 [%0], %1;\nst.shared.u16 [%0+4], %2;" ::"r"(ia), "h"((unsigned short)hi), "h"((unsigned short)lo) : "memory");
                    bad |= !(v >= 5.421010862e-20f && v <= 1.8446744e19f);
                }
                sts_u(sb + OFF_FB, __any_sync(0xffffffffu, bad));
                nb_arrive<NB_VOTE, 160>();
                nb_arrive<NB_VOTE + 1, 160>();
            }
        }
    } else if (wgid == 1) {
        asm volatile("setmaxnreg.inc.sync.aligned.u32 240;");
        consumer<0>(P, sb, dl);
    } else {
        asm volatile("setmaxnreg.inc.sync.aligned.u32 240;");
        consumer<1>(P, sb, dl);
    }
}

typedef CUresult (*EncFn)(CUtensorMap*, CUtensorMapDataType, cuuint32_t, void*, const cuuint64_t*, const cuuint64_t*,
                          const cuuint32_t*, const cuuint32_t*, CUtensorMapInterleave, CUtensorMapSwizzle,
                          CUtensorMapL2promotion, CUtensorMapFloatOOBfill);

void make_map3(EncFn enc, CUtensorMap* m, void* p, uint64_t rows, uint64_t rowbytes, uint64_t nblk, uint32_t boxrows,
               uint32_t boxblk) {
    cuuint64_t dims[3] = {64, rows, nblk};
    cuuint64_t str[2] = {rowbytes, 128};
    cuuint32_t box[3] = {64, boxrows, boxblk};
    cuuint32_t es[3] = {1, 1, 1};
    enc(m, CU_TENSOR_MAP_DATA_TYPE_BFLOAT16, 3, p, dims, str, box, es, CU_TENSOR_MAP_INTERLEAVE_NONE,
        CU_TENSOR_MAP_SWIZZLE_128B, CU_TENSOR_MAP_L2_PROMOTION_NONE, CU_TENSOR_MAP_FLOAT_OOB_FILL_NONE);
}

constexpr int tune(const char*, int def) { return def; }

void build_schedule(Params& P) {
    const int mode = tune("MODE", 4), dmax = tune("DMAX", 24900), n0 = tune("N0", 8);
    const int H0[8] = {20, 20, 22, 22, 22, 24, 25, 25}, P0[8] = {352, 352, 344, 348, 352, 345, 333, 336};
    const int ng = tune("NG", 0), d0 = tune("D0", 0), nkeep = tune("NKEEP", 0), odmax = tune("ODMAX", 2000);
    const int ong = tune("ONG", 0), od0 = tune("OD0", 0), jit = tune("JIT", 0);
    const int npos = tune("NPOS", 0), nearly = tune("NEARLY", 0);
    const int ra = tune("RA", 10), ga = tune("GA", 32), rb = tune("RB", 12), g1 = tune("G1", 58);
    int dep[64];
    for (int g = 0, ns = 0, live = 0; g < 64; g++) {
        const bool fresh = mode < 3 || g >= g1 || live < (g < ga ? ra : rb);
        dep[g] = fresh ? 0 : g - live + 1;
        P.slot[g] = fresh ? ns++ : P.slot[g - live];
        live += fresh;
    }
    int u = 0;
    auto unit = [&]() {
        const uint32_t e = mk_item(IT_QA, u >> 8, (u & 7) * 2, (u >> 3) & 31, P.slot[u >> 3], 0) | (dep[u >> 3] << 23);
        u++;
        return e;
    };
    int qa[NCL], nq = 0, op[NCL], no = 0;
    for (int c = 0; c < NCL; c++) {
        P.cl[c].delay = 0;
        for (int i = 0; i < NSTAT; i++) P.cl[c].items[i] = 0;
        if (mode >= 3 && c < 64 && (c & 3) == 3) op[no++] = c;
        else if (mode != 2 || (c & 3) == 0) qa[nq++] = c;
    }
    for (int t = 0; t < no; t++) {
        P.cl[op[t]].items[1] = mk_item(IT_OP, 0, t & ~1, 0, 32, t & 1);
        P.cl[op[t]].items[2] = IT_DYN;
        P.cl[op[t]].delay = ong ? od0 + (t * ong / 16) * (odmax / ong) : od0 + t * odmax / 16;
    }
    for (int k = 0; k < nq; k++) {
        const int c = qa[(k * 19) % nq];
        P.cl[c].items[1] = P.cl[c].items[2] = IT_DYN;
        P.cl[c].delay = k < n0 ? 0 : (int)((long long)dmax * (k + 1 - n0) / (nq - n0));
        if (ng) P.cl[c].delay = d0 + (k * ng / nq) * (dmax / ng) + (k * ng % nq) * jit / nq;
    }
    for (int k = 0; k < no + nq; k++) {
        int best = -1;
        for (int c = 0; c < NCL; c++)
            if (P.cl[c].items[1] && !P.cl[c].items[0] && (best < 0 || P.cl[c].delay < P.cl[best].delay)) best = c;
        P.cl[best].items[0] = unit();
    }
    int H[8], pos[8];
    for (int b = 0; b < 8; b++) {
        char nh[3] = {'H', (char)('0' + b), 0}, np[3] = {'P', (char)('0' + b), 0};
        H[b] = tune(nh, H0[b]);
        pos[b] = tune(np, P0[b]);
        for (int g = 0; g < 64; g++)
            if (dep[g] > 32) {
                if (pos[b] > 8 * g) pos[b] = 8 * g;
                if (H[b] < dep[g] - 32) H[b] = dep[g] - 32;
            }
        if (b < nkeep && no) {
            pos[b] = -1;
            P.cl[op[14 - 2 * b]].items[2] = mk_item(IT_OP, 1, 2 * b, 0, H[b], 0, 1);
            P.cl[op[15 - 2 * b]].items[2] = mk_item(IT_OP, 1, 2 * b, 0, H[b], 1, 1);
        }
    }
    int n = 0, kn = 0;
    const int uend = mode == 2 ? 8 * nq : 512;
    while (u < uend) {
        for (int b = 0; b < 8 && no; b++)
            if (pos[b] == u) {
                P.list[n++] = mk_item(IT_OP, 1, 2 * b, 0, H[b], 0, 1);
                P.list[n++] = mk_item(IT_OP, 1, 2 * b, 0, H[b], 1, 1);
            }
        while (no && u >= uend - npos && kn * npos < (u + 1 - (uend - npos)) * nearly) {
            P.list[n++] = mk_item(IT_ON, 1, kn / 5 * 2, H[kn / 5], 32, kn % 5);
            kn++;
        }
        P.list[n++] = unit();
    }
    for (; no && kn < 40; kn++) P.list[n++] = mk_item(IT_ON, 1, kn / 5 * 2, H[kn / 5], 32, kn % 5);
    P.nlist = n;
}

}

extern "C" void kernel_launch(void* const* d_in, const int* in_sizes, int n_in, void* d_out, int out_size) {
    static Params P;
    static bool init = false;
    if (!init) {
        EncFn enc = nullptr;
        cudaDriverEntryPointQueryResult qr;
        cudaGetDriverEntryPoint("cuTensorMapEncodeTiled", (void**)&enc, cudaEnableDefault, &qr);
        for (int i = 0; i < 2; i++) {
            P.px[i] = (const __nv_bfloat16*)d_in[5 * i + 0];
            P.pk[i] = (const __nv_bfloat16*)d_in[5 * i + 1];
            P.pv[i] = (const __nv_bfloat16*)d_in[5 * i + 2];
            P.pwq[i] = (const __nv_bfloat16*)d_in[5 * i + 3];
            make_map3(enc, &P.x[i], d_in[5 * i + 0], 2560, 1280, 10, 160, 1);
            make_map3(enc, &P.k[i], d_in[5 * i + 1], 16 * 32 * 512, 384, 3, 64, 3);
            make_map3(enc, &P.v[i], d_in[5 * i + 2], 16 * 32 * 512, 384, 3, 64, 3);
            make_map3(enc, &P.wq[i], d_in[5 * i + 3], 640, 12288, 96, 32, 3);
            make_map3(enc, &P.wo[i], d_in[5 * i + 4], 6144, 1280, 10, 16, 5);
            make_map3(enc, &P.won[i], d_in[5 * i + 4], 6144, 1280, 10, 32, 2);
        }
        cuuint64_t dims[5] = {1280, 2, 4, 4, 80};
        cuuint64_t str[4] = {2560, 8 * 2560, 2 * 2560, 32 * 2560};
        cuuint32_t box[5] = {64, 2, 4, 4, 5};
        cuuint32_t es[5] = {1, 1, 1, 1, 1};
        enc(&P.out, CU_TENSOR_MAP_DATA_TYPE_BFLOAT16, 5, d_out, dims, str, box, es, CU_TENSOR_MAP_INTERLEAVE_NONE,
            CU_TENSOR_MAP_SWIZZLE_128B, CU_TENSOR_MAP_L2_PROMOTION_NONE, CU_TENSOR_MAP_FLOAT_OOB_FILL_NONE);
        build_schedule(P);
        cudaFuncSetAttribute(fused_kernel, cudaFuncAttributeMaxDynamicSharedMemorySize, SMEM_LAUNCH);
        init = true;
    }
    fused_kernel<<<NCTA, 384, SMEM_LAUNCH>>>(P);
}
```

```cpp
#include <cuda_runtime.h>
#include <cuda.h>
#include <cuda_bf16.h>
#include <stdint.h>

namespace {

constexpr int NCTA = 132;
constexpr int NCL = NCTA / 2;
constexpr int MAXI = 16;
constexpr int NSTAT = 3;
constexpr uint32_t IT_DYN = 0xffffffffu;
constexpr int SLOT = 24576;
constexpr int NSLOT = 5;
constexpr int XS = 20480;
constexpr int OFF_R = 0;
constexpr int OFF_RING = 5 * XS;
constexpr int OFF_MISC = OFF_RING + NSLOT * SLOT;
constexpr int OFF_LX = OFF_MISC;
constexpr int OFF_LINV = OFF_LX + 2560;
constexpr int OFF_FB = OFF_LINV + 640;
constexpr int OFF_GM = OFF_FB + 16;
constexpr int OFF_BAR = OFF_GM + 16;
constexpr int BAR_RFULL = OFF_BAR;
constexpr int BAR_REMPTY = BAR_RFULL + 40;
constexpr int BAR_XFULL = BAR_REMPTY + 40;
constexpr int BAR_XEMPTY = BAR_XFULL + 40;
constexpr int BAR_PRDY = BAR_XEMPTY + 40;
constexpr int BAR_ITEM = BAR_PRDY + 40;
constexpr int OFF_ITEM = BAR_ITEM + MAXI * 8;
constexpr int SMEM_BYTES = OFF_ITEM + MAXI * 4;
static_assert(SMEM_BYTES <= 232448, "smem");

constexpr int NB_W = 1  , NB_PFULL = 3  , NB_VOTE = 5  , NB_Q2 = 7, NB_SDONE = 8, NB_PDONE = 9,
              NB_L = 10, NB_REF = 11, NB_ODONE = 12, NB_OPEND = 13, NB_LX = 14, NB_Q01 = 15, NB_QK = 0  ;

constexpr uint32_t IT_QA = 1, IT_OP = 2, IT_ON = 3;
__host__ __device__ constexpr uint32_t mk_item(uint32_t type, uint32_t br, uint32_t b, uint32_t h0, uint32_t h1, uint32_t half,
                                               uint32_t part = 0) {
    return type | (br << 2) | (b << 3) | (h0 << 7) | (h1 << 13) | (half << 19) | (part << 22);
}
#define IT_TYPE(e) ((e) & 3u)
#define IT_BR(e) (((e) >> 2) & 1u)
#define IT_B(e) (((e) >> 3) & 15u)
#define IT_H0(e) (((e) >> 7) & 63u)
#define IT_H1(e) (((e) >> 13) & 63u)
#define IT_HALF(e) (((e) >> 19) & 7u)
#define IT_PART(e) (((e) >> 22) & 1u)
#define IT_SLOT(e) IT_H1(e)
#define IT_DEP(e) (((e) >> 23) & 127u)

struct Params {
    CUtensorMap x[2], wq[2], k[2], v[2], wo[2], won[2], out;
    const __nv_bfloat16 *px[2], *pwq[2], *pk[2], *pv[2];
    struct alignas(16) { uint32_t delay, items[NSTAT]; } cl[NCL];
    uint32_t nlist;
    uint8_t slot[64];
    uint32_t list[512];
};

constexpr int OUNIT = 61440;
__device__ __align__(1024) unsigned char g_ostash[(size_t)1024 * OUNIT];
__device__ unsigned int g_flag[32 * 64];
__device__ __forceinline__ unsigned char* ostash(uint32_t slot, uint32_t b) { return g_ostash + (slot * 16 + b) * OUNIT; }
__device__ unsigned int g_epoch[NCTA * 4];
__device__ unsigned int g_ticket[2];

constexpr int SMEM_LAUNCH = SMEM_BYTES;
#define TS(role, idx)
#define TS_ITEM(e)
#define TS_DUMP(role)
#define TSD(role, idx)

#define POL_W 2
#define POL_X 2
#define POL_O 2
template <int M>
__device__ __forceinline__ uint64_t mkpol() {
    uint64_t p;
    if (M == 0) asm volatile("createpolicy.fractional.L2::evict_normal.b64 %0, 1.0;" : "=l"(p));
    if (M == 1) asm volatile("createpolicy.fractional.L2::evict_first.b64 %0, 1.0;" : "=l"(p));
    if (M == 2) asm volatile("createpolicy.fractional.L2::evict_unchanged.b64 %0, 1.0;" : "=l"(p));
    if (M == 3) asm volatile("createpolicy.fractional.L2::evict_normal.L2::evict_unchanged.b64 %0, 0.25;" : "=l"(p));
    return p;
}
#define STSM_W 1
#define LASTORD 0
#define XLATE 2
#define PV0FIRST 1
#define QST0 1
#define QST1 2
#define QHOLD 8
constexpr float SM_C = 0.07216878364870322f * 1.4426950408889634f;

__device__ __forceinline__ uint32_t next_epoch(int warp) {
    unsigned int* p = &g_epoch[blockIdx.x * 4 + warp];
    const uint32_t e = __ldcg(p) + 1;
    *p = e;
    return e;
}

__device__ __forceinline__ uint32_t tid_now() {
    uint32_t t;
    asm volatile("mov.u32 %0, %%tid.x;" : "=r"(t));
    return t;
}
__device__ __forceinline__ void mbar_init(uint32_t a, uint32_t c) {
    asm volatile("mbarrier.init.shared::cta.b64 [%0], %1;" ::"r"(a), "r"(c) : "memory");
}
__device__ __forceinline__ void mbar_expect(uint32_t a, uint32_t b) {
    asm volatile("mbarrier.arrive.expect_tx.shared::cta.b64 _, [%0], %1;" ::"r"(a), "r"(b) : "memory");
}
template <int CNT = 1>
__device__ __forceinline__ void mbar_arrive_warp(uint32_t a) {
    if (CNT == 1)
        asm volatile("{\n.reg .pred p;\nelect.sync _|p, 0xffffffff;\n@p mbarrier.arrive.shared::cta.b64 _, [%0];\n}" ::"r"(a) : "memory");
    else
        asm volatile(
            "{\n.reg .pred p;\nelect.sync _|p, 0xffffffff;\n@p mbarrier.arrive.shared::cta.b64 _, [%0];\n"
            "@p mbarrier.arrive.shared::cta.b64 _, [%0];\n}" ::"r"(a)
            : "memory");
}
template <int CNT = 1>
__device__ __forceinline__ void mbar_arrive_warp_if(uint32_t a, bool cond) {
    if (CNT == 1)
        asm volatile(
            "{\n.reg .pred p, c;\nelect.sync _|p, 0xffffffff;\nsetp.ne.and.u32 c, %1, 0, p;\n"
            "@c mbarrier.arrive.shared::cta.b64 _, [%0];\n}" ::"r"(a), "r"((uint32_t)cond)
            : "memory");
    else
        asm volatile(
            "{\n.reg .pred p, c;\nelect.sync _|p, 0xffffffff;\nsetp.ne.and.u32 c, %1, 0, p;\n"
            "@c mbarrier.arrive.shared::cta.b64 _, [%0];\n@c mbarrier.arrive.shared::cta.b64 _, [%0];\n}" ::"r"(a), "r"((uint32_t)cond)
            : "memory");
}
__device__ __forceinline__ uint32_t deadline() {
    uint32_t c;
    asm volatile("mov.u32 %0, %%clock_hi;" : "=r"(c));
    return c + 4;
}
__device__ __forceinline__ void mbar_wait(uint32_t a, uint32_t ph, uint32_t dl) {
    asm volatile(
        "{\n.reg .pred p;\n.reg .u32 m;\n"
        "LOOP:\n"
        "mbarrier.try_wait.parity.shared::cta.b64 p, [%0], %1;\n"
        "@p bra DONE;\n"
        "mov.u32 m, %%clock_hi;\n"
        "setp.ne.u32 p, m, %2;\n"
        "@p bra LOOP;\n"
        "trap;\n"
        "DONE:\n}" ::"r"(a), "r"(ph), "r"(dl)
        : "memory");
}
template <int ID, int CNT>
__device__ __forceinline__ void nb_sync() { asm volatile("bar.sync %0, %1;" ::"n"(ID), "n"(CNT) : "memory"); }
template <int ID, int CNT>
__device__ __forceinline__ void nb_arrive() { asm volatile("bar.arrive %0, %1;" ::"n"(ID), "n"(CNT) : "memory"); }
__device__ __forceinline__ void fence_async_smem() { asm volatile("fence.proxy.async.shared::cta;" ::: "memory"); }

__device__ __forceinline__ void tma3(uint32_t dst, const CUtensorMap* m, int c1, int c2, uint32_t bar, uint64_t pol) {
    asm volatile(
        "cp.async.bulk.tensor.3d.shared::cluster.global.mbarrier::complete_tx::bytes.L2::cache_hint [%0], [%1, {%3,%4,%5}], [%2], %6;" ::"r"(dst),
        "l"(m), "r"(bar), "r"(0), "r"(c1), "r"(c2), "l"(pol)
        : "memory");
}
__device__ __forceinline__ void tma3_mc(uint32_t dst, const CUtensorMap* m, int c1, int c2, uint32_t bar, uint64_t pol) {
    asm volatile(
        "cp.async.bulk.tensor.3d.shared::cluster.global.mbarrier::complete_tx::bytes.multicast::cluster.L2::cache_hint"
        " [%0], [%1, {%3,%4,%5}], [%2], %6, %7;" ::"r"(dst),
        "l"(m), "r"(bar), "r"(0), "r"(c1), "r"(c2), "h"((unsigned short)3), "l"(pol)
        : "memory");
}
__device__ __forceinline__ void bulk_load(uint32_t dst, const void* src, uint32_t bytes, uint32_t bar, uint64_t pol) {
    asm volatile("cp.async.bulk.shared::cluster.global.mbarrier::complete_tx::bytes.L2::cache_hint [%0], [%1], %2, [%3], %4;" ::"r"(dst),
                 "l"(src), "r"(bytes), "r"(bar), "l"(pol)
                 : "memory");
}
__device__ __forceinline__ void wg_fence() { asm volatile("wgmma.fence.sync.aligned;" ::: "memory"); }
__device__ __forceinline__ void wg_commit() { asm volatile("wgmma.commit_group.sync.aligned;" ::: "memory"); }
template <int N>
__device__ __forceinline__ void wg_wait() { asm volatile("wgmma.wait_group.sync.aligned %0;" ::"n"(N) : "memory"); }

#define RW80(c, d) c(d[0]), c(d[1]), c(d[2]), c(d[3]), c(d[4]), c(d[5]), c(d[6]), c(d[7]), c(d[8]), c(d[9]), c(d[10]), c(d[11]), c(d[12]), c(d[13]), c(d[14]), c(d[15]), c(d[16]), c(d[17]), c(d[18]), c(d[19]), c(d[20]), c(d[21]), c(d[22]), c(d[23]), c(d[24]), c(d[25]), c(d[26]), c(d[27]), c(d[28]), c(d[29]), c(d[30]), c(d[31]), c(d[32]), c(d[33]), c(d[34]), c(d[35]), c(d[36]), c(d[37]), c(d[38]), c(d[39]), c(d[40]), c(d[41]), c(d[42]), c(d[43]), c(d[44]), c(d[45]), c(d[46]), c(d[47]), c(d[48]), c(d[49]), c(d[50]), c(d[51]), c(d[52]), c(d[53]), c(d[54]), c(d[55]), c(d[56]), c(d[57]), c(d[58]), c(d[59]), c(d[60]), c(d[61]), c(d[62]), c(d[63]), c(d[64]), c(d[65]), c(d[66]), c(d[67]), c(d[68]), c(d[69]), c(d[70]), c(d[71]), c(d[72]), c(d[73]), c(d[74]), c(d[75]), c(d[76]), c(d[77]), c(d[78]), c(d[79])
#define RW48(c, d) c(d[0]), c(d[1]), c(d[2]), c(d[3]), c(d[4]), c(d[5]), c(d[6]), c(d[7]), c(d[8]), c(d[9]), c(d[10]), c(d[11]), c(d[12]), c(d[13]), c(d[14]), c(d[15]), c(d[16]), c(d[17]), c(d[18]), c(d[19]), c(d[20]), c(d[21]), c(d[22]), c(d[23]), c(d[24]), c(d[25]), c(d[26]), c(d[27]), c(d[28]), c(d[29]), c(d[30]), c(d[31]), c(d[32]), c(d[33]), c(d[34]), c(d[35]), c(d[36]), c(d[37]), c(d[38]), c(d[39]), c(d[40]), c(d[41]), c(d[42]), c(d[43]), c(d[44]), c(d[45]), c(d[46]), c(d[47])
#define RW32(c, d) c(d[0]), c(d[1]), c(d[2]), c(d[3]), c(d[4]), c(d[5]), c(d[6]), c(d[7]), c(d[8]), c(d[9]), c(d[10]), c(d[11]), c(d[12]), c(d[13]), c(d[14]), c(d[15]), c(d[16]), c(d[17]), c(d[18]), c(d[19]), c(d[20]), c(d[21]), c(d[22]), c(d[23]), c(d[24]), c(d[25]), c(d[26]), c(d[27]), c(d[28]), c(d[29]), c(d[30]), c(d[31])

__device__ __forceinline__ void reg_fence(float (&d)[80]) { asm volatile("" : RW80("+f", d)::"memory"); }
__device__ __forceinline__ void reg_fence(float (&d)[48]) { asm volatile("" : RW48("+f", d)::"memory"); }
__device__ __forceinline__ void reg_fence(float (&d)[32]) { asm volatile("" : RW32("+f", d)::"memory"); }

template <int NR>
__device__ __forceinline__ void zero(float (&d)[NR]) {
#pragma unroll
    for (int i = 0; i < NR; i++) d[i] = 0.f;
}

constexpr uint32_t HI_SW128 = (1024u >> 4) | (1u << 30);
constexpr uint32_t HI_OST = (2560u >> 4) | (2u << 30);
constexpr uint32_t LO_LBO1 = (1u << 16);
constexpr uint32_t LO_OST = ((512u >> 4) << 16);

template <int TA, int TB, uint32_t HIB, int ACC>
__device__ __forceinline__ void wgmma(float (&d)[80], uint32_t loA, uint32_t loB) {
#define WG_ASM(SD)                                                          \
    "{\n.reg .b64 da, db;\nmov.b64 da, {%80, %82};\nmov.b64 db, {%81, %83};\n" \
    "wgmma.mma_async.sync.aligned.m64n160k16.f32.bf16.bf16 "               \
    "{%0,%1,%2,%3,%4,%5,%6,%7,%8,%9,%10,%11,%12,%13,%14,%15,%16,%17,%18,%19,%20,%21,%22,%23,%24,%25,%26,%27,%28,%29,%30,%31,%32,%33,%34,%35,%36,%37,%38,%39,%40,%41,%42,%43,%44,%45,%46,%47,%48,%49,%50,%51,%52,%53,%54,%55,%56,%57,%58,%59,%60,%61,%62,%63,%64,%65,%66,%67,%68,%69,%70,%71,%72,%73,%74,%75,%76,%77,%78,%79}, da, db, " SD ", 1, 1, %84, %85;\n}"
    if constexpr (ACC == 2)
        asm volatile(WG_ASM("0") : RW80("+f", d) : "r"(loA), "r"(loB), "n"(HI_SW128), "n"(HIB), "n"(TA), "n"(TB));
    else if constexpr (ACC == 1)
        asm volatile(WG_ASM("1") : RW80("+f", d) : "r"(loA), "r"(loB), "n"(HI_SW128), "n"(HIB), "n"(TA), "n"(TB));
    else
        asm volatile(WG_ASM("0") : RW80("=f", d) : "r"(loA), "r"(loB), "n"(HI_SW128), "n"(HIB), "n"(TA), "n"(TB));
#undef WG_ASM
}
template <int TA, int TB, uint32_t HIB, int ACC>
__device__ __forceinline__ void wgmma(float (&d)[48], uint32_t loA, uint32_t loB) {
#define WG_ASM(SD)                                                          \
    "{\n.reg .b64 da, db;\nmov.b64 da, {%48, %50};\nmov.b64 db, {%49, %51};\n" \
    "wgmma.mma_async.sync.aligned.m64n96k16.f32.bf16.bf16 "               \
    "{%0,%1,%2,%3,%4,%5,%6,%7,%8,%9,%10,%11,%12,%13,%14,%15,%16,%17,%18,%19,%20,%21,%22,%23,%24,%25,%26,%27,%28,%29,%30,%31,%32,%33,%34,%35,%36,%37,%38,%39,%40,%41,%42,%43,%44,%45,%46,%47}, da, db, " SD ", 1, 1, %52, %53;\n}"
    if constexpr (ACC == 1)
        asm volatile(WG_ASM("1") : RW48("+f", d) : "r"(loA), "r"(loB), "n"(HI_SW128), "n"(HIB), "n"(TA), "n"(TB));
    else
        asm volatile(WG_ASM("0") : RW48("=f", d) : "r"(loA), "r"(loB), "n"(HI_SW128), "n"(HIB), "n"(TA), "n"(TB));
#undef WG_ASM
}
template <int TA, int TB, uint32_t HIB, int ACC>
__device__ __forceinline__ void wgmma(float (&d)[32], uint32_t loA, uint32_t loB) {
#define WG_ASM(SD)                                                          \
    "{\n.reg .b64 da, db;\nmov.b64 da, {%32, %34};\nmov.b64 db, {%33, %35};\n" \
    "wgmma.mma_async.sync.aligned.m64n64k16.f32.bf16.bf16 "               \
    "{%0,%1,%2,%3,%4,%5,%6,%7,%8,%9,%10,%11,%12,%13,%14,%15,%16,%17,%18,%19,%20,%21,%22,%23,%24,%25,%26,%27,%28,%29,%30,%31}, da, db, " SD ", 1, 1, %36, %37;\n}"
    if constexpr (ACC == 1)
        asm volatile(WG_ASM("1") : RW32("+f", d) : "r"(loA), "r"(loB), "n"(HI_SW128), "n"(HIB), "n"(TA), "n"(TB));
    else
        asm volatile(WG_ASM("0") : RW32("=f", d) : "r"(loA), "r"(loB), "n"(HI_SW128), "n"(HIB), "n"(TA), "n"(TB));
#undef WG_ASM
}

__device__ __forceinline__ uint32_t pack_bf16(float lo, float hi) {
    uint32_t r;
    asm("cvt.rn.bf16x2.f32 %0, %1, %2;" : "=r"(r) : "f"(hi), "f"(lo));
    return r;
}
__device__ __forceinline__ float ex2(float x) {
    float r;
    asm("ex2.approx.ftz.f32 %0, %1;" : "=f"(r) : "f"(x));
    return r;
}
__device__ __forceinline__ void stsm4t(uint32_t a, uint32_t r0, uint32_t r1, uint32_t r2, uint32_t r3) {
    asm volatile("stmatrix.sync.aligned.m8n8.x4.trans.shared.b16 [%0], {%1,%2,%3,%4};" ::"r"(a), "r"(r0), "r"(r1), "r"(r2), "r"(r3)
                 : "memory");
}
__device__ __forceinline__ uint32_t lds_u(uint32_t a) {
    uint32_t v;
    asm volatile("ld.shared.u32 %0, [%1];" : "=r"(v) : "r"(a) : "memory");
    return v;
}
__device__ __forceinline__ uint4 lds_u4(uint32_t a) {
    uint4 v;
    asm volatile("ld.shared.v4.u32 {%0,%1,%2,%3}, [%4];" : "=r"(v.x), "=r"(v.y), "=r"(v.z), "=r"(v.w) : "r"(a) : "memory");
    return v;
}
__device__ __forceinline__ float2 lds_f2(uint32_t a) {
    float2 v;
    asm volatile("ld.shared.v2.f32 {%0,%1}, [%2];" : "=f"(v.x), "=f"(v.y) : "r"(a) : "memory");
    return v;
}
__device__ __forceinline__ void sts_f(uint32_t a, float v) { asm volatile("st.shared.f32 [%0], %1;" ::"r"(a), "f"(v) : "memory"); }
__device__ __forceinline__ void sts_u(uint32_t a, uint32_t v) { asm volatile("st.shared.u32 [%0], %1;" ::"r"(a), "r"(v) : "memory"); }
__device__ __forceinline__ void sts_f2(uint32_t a, float x, float y) {
    asm volatile("st.shared.v2.f32 [%0], {%1,%2};" ::"r"(a), "f"(x), "f"(y) : "memory");
}

template <bool ADD = false, bool SIG = false, int NR>
__device__ __forceinline__ void store_tile_t(const float (&d)[NR], uint32_t addr) {
    uint32_t p[NR / 2];
    if (ADD) {
#pragma unroll
        for (int j = 0; j < NR / 8; j++)
            asm volatile("ldmatrix.sync.aligned.m8n8.x4.trans.shared.b16 {%0,%1,%2,%3}, [%4];"
                         : "=r"(p[4 * j]), "=r"(p[4 * j + 1]), "=r"(p[4 * j + 2]), "=r"(p[4 * j + 3])
                         : "r"(addr + j * 2048)
                         : "memory");
    }
#pragma unroll
    for (int k = 0; k < NR / 2; k++)
        p[k] = ADD ? pack_bf16(d[2 * k] + __uint_as_float(p[k] << 16), d[2 * k + 1] + __uint_as_float(p[k] & 0xffff0000u))
                   : pack_bf16(d[2 * k], d[2 * k + 1]);
#pragma unroll
    for (int j = 0; j < NR / 8; j++) {
        stsm4t(addr + j * 2048, p[4 * j], p[4 * j + 1], p[4 * j + 2], p[4 * j + 3]);
        if (SIG && j == 0) nb_arrive<NB_L, 160>();
    }
}

struct TrueT { static constexpr bool value = true; };
struct FalseT { static constexpr bool value = false; };

template <int V>
struct IntT { static constexpr int value = V; };

__device__ __forceinline__ uint32_t get_item(uint32_t sb, int it, uint32_t dl) {
    mbar_wait(sb + BAR_ITEM + it * 8, 0, dl);
    return lds_u(sb + OFF_ITEM + it * 4);
}
__device__ __forceinline__ uint32_t get_item_warp(uint32_t sb, int it, uint32_t dl) {
    return __shfl_sync(0xffffffffu, get_item(sb, it, dl), 0);
}

struct Ring {
    uint32_t slot, ph, dl;
    __device__ __forceinline__ void adv(uint32_t k) {
        slot += k;
        if (slot >= NSLOT) { slot -= NSLOT; ph ^= 1; }
    }
};

template <int K>
__device__ __forceinline__ void qk_step(float (&s)[80], uint32_t loK, uint32_t loQ) {
    wgmma<0, 0, HI_SW128, K != 0>(s, loK + (K >> 2) * (8192 >> 4) + (K & 3) * 2, loQ + (K >> 2) * (XS >> 4) + (K & 3) * 2);
}
template <int K0, int K1>
__device__ __forceinline__ void qk_steps(float (&s)[80], uint32_t loK, uint32_t loQ) {
    if constexpr (K0 < K1) {
        qk_step<K0>(s, loK, loQ);
        qk_steps<K0 + 1, K1>(s, loK, loQ);
    }
}
__device__ __forceinline__ uint32_t add_bf2(uint32_t a, uint32_t b) {
    uint32_t r;
    asm("add.rn.bf16x2 %0, %1, %2;" : "=r"(r) : "r"(a), "r"(b));
    return r;
}
__device__ __forceinline__ uint32_t fma_bf2(uint32_t a, uint32_t b, uint32_t c) {
    uint32_t r;
    asm("fma.rn.bf16x2 %0, %1, %2, %3;" : "=r"(r) : "r"(a), "r"(b), "r"(c));
    return r;
}
template <int J>
__device__ __forceinline__ void exp_block(const float (&s)[80], uint32_t (&k)[40], uint32_t pa, float mref) {
    if constexpr (J < 10) {
#pragma unroll
        for (int i = 4 * J; i < 4 * J + 4; i++)
            k[i] = pack_bf16(ex2(fmaf(s[2 * i], SM_C, -mref)), ex2(fmaf(s[2 * i + 1], SM_C, -mref)));
#pragma unroll
        for (int i = 0; i < 4; i++)
            asm volatile("stmatrix.sync.aligned.m8n8.x1.trans.shared.b16 [%0], {%1};" ::"r"(((i & 1) ? pa ^ 16 : pa) + J * 2048 + (i >> 1) * 1024),
                         "r"(k[4 * J + i])
                         : "memory");
        exp_block<J + 1>(s, k, pa, mref);
    }
}
__device__ __forceinline__ void sum_block(const uint32_t (&k)[40], float (&l)[10], uint32_t lane) {
    const bool b4 = lane & 16, b3 = lane & 8;
    uint32_t ps[20], t[10];
#pragma unroll
    for (int j = 0; j < 20; j++) ps[j] = add_bf2(k[2 * j], k[2 * j + 1]);
#pragma unroll
    for (int j = 0; j < 10; j++)
        t[j] = add_bf2(b4 ? ps[2 * j + 1] : ps[2 * j], __shfl_xor_sync(0xffffffffu, b4 ? ps[2 * j] : ps[2 * j + 1], 16));
#pragma unroll
    for (int i = 0; i < 5; i++) {
        const uint32_t a = b3 ? t[i + 5] : t[i], b = __shfl_xor_sync(0xffffffffu, b3 ? t[i] : t[i + 5], 8);
        l[2 * i] += __uint_as_float(a << 16) + __uint_as_float(b << 16);
        l[2 * i + 1] += __uint_as_float(a & 0xffff0000u) + __uint_as_float(b & 0xffff0000u);
    }
}
template <bool ADD>
__device__ __forceinline__ void sum_store(const float (&l)[10], uint32_t lane, uint32_t lxa) {
    const bool b2 = lane & 4;
    float t[5];
#pragma unroll
    for (int i = 0; i < 5; i++) t[i] = ADD ? __uint_as_float(lds_u(lxa + i * 64)) : 0.f;
#pragma unroll
    for (int i = 0; i < 5; i++)
        sts_f(lxa + i * 64, t[i] + (b2 ? l[2 * i + 1] : l[2 * i]) + __shfl_xor_sync(0xffffffffu, b2 ? l[2 * i] : l[2 * i + 1], 4));
}

__device__ __forceinline__ void fallback_unit(const Params& P, uint32_t e, uint32_t tid) {
    const uint32_t lane = tid & 31, br = IT_BR(e), b = IT_B(e), h = IT_H0(e);
    const __nv_bfloat162* wq = (const __nv_bfloat162*)(P.pwq[br] + h * 192) + lane;
    const __nv_bfloat162* kp = (const __nv_bfloat162*)(P.pk[br] + (size_t)(b * 32 + h) * 512 * 192) + lane;
    const __nv_bfloat162* vp = (const __nv_bfloat162*)(P.pv[br] + (size_t)(b * 32 + h) * 512 * 192) + lane;
#pragma unroll 1
    for (uint32_t qi = 0; qi < 40; qi++) {
        const uint32_t q = 4 * qi + (tid >> 5);
        const __nv_bfloat16* xr = P.px[br] + (size_t)(b * 160 + q) * 640;
        float a[6] = {0.f, 0.f, 0.f, 0.f, 0.f, 0.f};
#pragma unroll 2
        for (int k = 0; k < 640; k++) {
            const float xv = __bfloat162float(xr[k]);
#pragma unroll
            for (int i = 0; i < 3; i++) {
                const float2 wv = __bfloat1622float2(wq[(size_t)k * 3072 + i * 32]);
                a[2 * i] = fmaf(xv, wv.x, a[2 * i]);
                a[2 * i + 1] = fmaf(xv, wv.y, a[2 * i + 1]);
            }
        }
#pragma unroll
        for (int i = 0; i < 6; i++) a[i] = __bfloat162float(__float2bfloat16(a[i]));
        auto score = [&](int key) {
            float d = 0.f;
#pragma unroll
            for (int i = 0; i < 3; i++) {
                const float2 kv = __bfloat1622float2(kp[key * 96 + i * 32]);
                d = fmaf(a[2 * i], kv.x, fmaf(a[2 * i + 1], kv.y, d));
            }
#pragma unroll
            for (int o = 16; o > 0; o >>= 1) d += __shfl_xor_sync(0xffffffffu, d, o);
            return d;
        };
        float m = -INFINITY, o[6] = {0.f, 0.f, 0.f, 0.f, 0.f, 0.f}, sum = 0.f;
#pragma unroll 1
        for (int n = 0; n < 1024; n++) {
            const int key = n & 511;
            const float d = score(key);
            if (n < 512) {
                m = fmaxf(m, d);
            } else {
                const float p = ex2((d - m) * SM_C);
                sum += p;
#pragma unroll
                for (int i = 0; i < 3; i++) {
                    const float2 vv = __bfloat1622float2(vp[key * 96 + i * 32]);
                    o[2 * i] = fmaf(p, vv.x, o[2 * i]);
                    o[2 * i + 1] = fmaf(p, vv.y, o[2 * i + 1]);
                }
            }
        }
        const float inv = __fdividef(1.f, sum);
        __nv_bfloat16* op = (__nv_bfloat16*)ostash(IT_SLOT(e), b) + (q >> 5) * 256 + 2 * ((q & 31) >> 3) + (q & 1);
#pragma unroll
        for (int i = 0; i < 6; i++) {
            const uint32_t d = (i >> 1) * 64 + 2 * lane + (i & 1);
            op[(d >> 3) * 1280 + (d & 7) * 32 + ((((q & 7) >> 1) ^ ((d & 7) >> 1)) << 3)] = __float2bfloat16(o[i] * inv);
        }
    }
}

template <int W>
struct PendO {
    static constexpr int N = W == 0 ? 56 : 64;
    uint32_t v[N];
    unsigned char* gp;
    static __device__ __forceinline__ uint32_t toff() {
        const uint32_t t = tid_now();
        return ((t >> 5) & 3) * 5120 + ((t >> 2) & 7) * 64 + (((t ^ (t >> 3)) & 3) << 4);
    }
    uint32_t pend, sig;
    static __device__ __forceinline__ void scale(uint32_t& x, uint32_t hi, uint32_t lo) {
        asm("{\n.reg .b32 t;\nmul.rn.bf16x2 t, %0, %2;\nfma.rn.bf16x2 %0, %0, %1, t;\n}" : "+r"(x) : "r"(hi), "r"(lo));
    }
    template <int I, int OFF>
    __device__ __forceinline__ void put() {
        asm volatile("{\n.reg .pred p;\nsetp.ne.u32 p, %6, 0;\n@p st.global.v4.b32 [%0+%5], {%1,%2,%3,%4};\n}" ::"l"(gp), "r"(v[I]),
                     "r"(v[I + 1]), "r"(v[I + 2]), "r"(v[I + 3]), "n"(OFF), "r"(pend)
                     : "memory");
    }
    __device__ __forceinline__ void verdict(const Params& P, uint32_t sb, int ie) {
        if (sig) {
            nb_sync<NB_VOTE + W, 160>();
            pend = !__any_sync(0xffffffffu, lds_u(sb + OFF_FB) != 0);
            if (W == 1 && !pend) {
                fallback_unit(P, lds_u(sb + OFF_ITEM + ie * 4), tid_now() & 127);
                __syncwarp();
            }
        }
    }
    template <int G, int H>
    __device__ __forceinline__ void half(uint32_t sb) {
        constexpr bool T2 = W == 0 ? G >= 3 : G < 3;
        constexpr int B = T2 ? 40 + 8 * (W == 0 ? G - 3 : G) : 0;
        const uint4 a = lds_u4(sb + OFF_LINV + G * 128 + H * 16 + (threadIdx.x & 3) * 32);
#pragma unroll
        for (int i = 2 * H; i < 8; i += 4) {
            scale(v[8 * G + i], a.x, a.y);
            scale(v[8 * G + i + 1], a.z, a.w);
            if (T2) {
                scale(v[B + i], a.x, a.y);
                scale(v[B + i + 1], a.z, a.w);
            }
        }
        if (H == 1) {
            put<8 * G, W * XS + G * 512>();
            put<8 * G + 4, W * XS + G * 512 + 2560>();
            if (T2) {
                put<B, 2 * XS + G * 512>();
                put<B + 4, 2 * XS + G * 512 + 2560>();
            }
            if (G == 4 && sig) nb_arrive<NB_ODONE, 288>();
        }
    }
    template <int G>
    __device__ __forceinline__ void step(uint32_t sb) {
        half<G, 0>(sb);
        half<G, 1>(sb);
    }
    __device__ __forceinline__ void clear() {
#pragma unroll
        for (int i = 0; i < N; i++) v[i] = 0;
        gp = nullptr;
        pend = 0;
        sig = 0;
    }
};

__device__ __forceinline__ uint32_t stsm_off() {
    const uint32_t tid = tid_now(), lane = tid & 31;
    return (lane >> 4) * 1024 + (lane & 7) * 128 + (((((tid >> 4) & 6) + ((lane >> 3) & 1)) ^ (lane & 7)) << 4);
}
template <int W, int KK>
__device__ __forceinline__ void qproj(float (&q0)[80], float (&q1)[80], uint32_t sb, Ring& r, uint32_t pslot, uint32_t phm,
                                      PendO<W>& po, const Params& P, int it) {
    const uint32_t loR = (((sb + OFF_R) & 0x3ffff) >> 4) | LO_LBO1;
    const uint32_t loRing = (((sb + OFF_RING) & 0x3ffff) >> 4) | LO_LBO1;
    auto ready = [&](int k) {
        mbar_wait(sb + BAR_RFULL + r.slot * 8, r.ph, r.dl);
        mbar_wait(sb + BAR_XFULL + (k % 5) * 8, ((phm >> (k % 5)) ^ (k / 5)) & 1, r.dl);
    };
    auto release = [&]() {
        if (KK > 0) {
            wg_wait<1>();
            mbar_arrive_warp(sb + BAR_REMPTY + pslot * 8);
            if (KK <= 5) mbar_arrive_warp(sb + (BAR_XEMPTY + (KK - 1) * 8));
        }
    };
    if (KK == 0 && (W == 1 || !po.sig)) ready(0);
    if (W == 1 && KK == QHOLD) {
        if (QHOLD == 7) {
            wg_wait<0>();
            nb_arrive<NB_PDONE, 256>();
        }
        nb_sync<NB_SDONE, 256>();
    }
    const uint32_t a = loRing + r.slot * (SLOT >> 4) + (W == 0 ? 0 : 512), b = loR + (KK % 5) * (XS >> 4);
    wg_fence();
    wgmma<1, 0, HI_SW128, KK != 0>(q0, a, b);
    if (W == 0) wgmma<1, 0, HI_SW128, KK != 0>(q1, a + 256, b);
#pragma unroll
    for (int k = 1; k < 4; k++) {
        wgmma<1, 0, HI_SW128, true>(q0, a + (k >> 1) * 768 + (k & 1) * 128, b + k * 2);
        if (W == 0) wgmma<1, 0, HI_SW128, true>(q1, a + 256 + (k >> 1) * 768 + (k & 1) * 128, b + k * 2);
    }
    wg_commit();
    const uint32_t cslot = r.slot;
    r.adv(1);
    if (W == 0 || KK < QHOLD) release();
    if (KK == QST0) {
        po.verdict(P, sb, it - 1);
        po.template half<0, 0>(sb);
    }
    if (KK < 9) ready(KK + 1);
    if (W == 1 && KK >= QHOLD) release();
    if (W == 1 && KK == 7 && QHOLD > 7) nb_arrive<NB_PDONE, 256>();
    if (KK == QST0) po.template half<0, 1>(sb);
    if constexpr (KK > QST0 && KK < QST0 + 5) po.template step<KK - QST0>(sb);
    if constexpr (KK < (W == 0 ? 7 : 9)) {
        qproj<W, KK + 1>(q0, q1, sb, r, cslot, phm, po, P, it);
    } else if constexpr (W == 1) {
        wg_wait<0>();
        reg_fence(q0);
        mbar_arrive_warp(sb + BAR_REMPTY + cslot * 8);
        store_tile_t<false, true>(q0, sb + OFF_R + 2 * XS + stsm_off());
    } else {
        const uint32_t s8 = r.slot, a8 = loRing + s8 * (SLOT >> 4);
        wg_fence();
#pragma unroll
        for (int k = 0; k < 4; k++) wgmma<1, 0, HI_SW128, true>(q0, a8 + (k >> 1) * 768 + (k & 1) * 128, loR + 3 * (XS >> 4) + k * 2);
        r.adv(1);
        ready(9);
        const uint32_t s9 = r.slot, a9 = loRing + s9 * (SLOT >> 4);
        r.adv(1);
        wg_fence();
#pragma unroll
        for (int k = 0; k < 4; k++) wgmma<1, 0, HI_SW128, true>(q0, a9 + (k >> 1) * 768 + (k & 1) * 128, loR + 4 * (XS >> 4) + k * 2);
        wg_commit();
        wg_wait<1>();
        mbar_arrive_warp(sb + BAR_REMPTY + cslot * 8);
        wg_fence();
#pragma unroll
        for (int k = 0; k < 8; k++)
            wgmma<1, 0, HI_SW128, true>(q1, (k < 4 ? a8 : a9) + 256 + ((k >> 1) & 1) * 768 + (k & 1) * 128,
                                        loR + (3 + (k >> 2)) * (XS >> 4) + (k & 3) * 2);
        wg_commit();
        nb_arrive<NB_SDONE, 256>();
        nb_sync<NB_PDONE, 256>();
        wg_wait<1>();
        reg_fence(q0);
        const uint32_t sta = sb + OFF_R + stsm_off();
        store_tile_t(q0, sta);
        sts_u(sb + OFF_GM + 4, r.slot);
        mbar_wait(sb + BAR_RFULL + r.slot * 8, r.ph, r.dl);
        wg_wait<0>();
        reg_fence(q1);
        mbar_arrive_warp(sb + BAR_REMPTY + s8 * 8);
        mbar_arrive_warp(sb + BAR_REMPTY + s9 * 8);
        store_tile_t(q1, sta + XS);
    }
}

template <int NR>
__device__ __forceinline__ void opack(const float (&o)[NR], uint32_t* v) {
#pragma unroll
    for (int g = 0; g < NR / 16; g++)
#pragma unroll
        for (int hh = 0; hh < 2; hh++)
#pragma unroll
            for (int t = 0; t < 4; t++) v[8 * g + 4 * hh + t] = pack_bf16(o[16 * g + 4 * t + 2 * hh], o[16 * g + 4 * t + 2 * hh + 1]);
}

template <bool IS_S>
__device__ __forceinline__ void op_item(uint32_t e, uint32_t sb, Ring& r, uint32_t& phm) {
    constexpr int T0 = IS_S ? 0 : 2;
    constexpr uint32_t BOFF = IS_S ? (3 * 512) >> 4 : 0;
    const uint32_t loRing = (((sb + OFF_RING) & 0x3ffff) >> 4) | LO_LBO1;
    const uint32_t loO = (((sb + OFF_R) & 0x3ffff) >> 4) | LO_OST;
    float c0[80], c1[80], c2[IS_S ? 32 : 48];
    const int T = 3 * (IT_H1(e) - IT_H0(e));
    uint32_t xs = 0;
    auto step = [&](auto first, auto half) {
        constexpr bool F = decltype(first)::value;
        constexpr uint32_t hf = decltype(half)::value;
        if (hf == 0) {
            mbar_wait(sb + BAR_XFULL + xs * 8, (phm >> xs) & 1, r.dl);
            phm ^= 1u << xs;
        }
        mbar_wait(sb + BAR_RFULL + r.slot * 8, r.ph, r.dl);
        const uint32_t a = loRing + r.slot * (SLOT >> 4), b = loO + xs * (XS >> 4) + hf * 640;
        wg_fence();
        wgmma<1, 1, HI_OST, !F>(c0, a + T0 * 128, b);
        wgmma<1, 1, HI_OST, !F>(c1, a + T0 * 128 + 128, b);
        wgmma<1, 1, HI_OST, !F>(c2, a + 512, b + BOFF);
        wgmma<1, 1, HI_OST, true>(c0, a + 640 + T0 * 128, b + 320);
        wgmma<1, 1, HI_OST, true>(c1, a + 640 + T0 * 128 + 128, b + 320);
        wgmma<1, 1, HI_OST, true>(c2, a + 640 + 512, b + 320 + BOFF);
        wg_commit();
    };
    step(TrueT{}, IntT<0>{});
#pragma unroll 1
    for (int t = 1;; t++) {
        uint32_t pslot = r.slot;
        r.adv(1);
        step(FalseT{}, IntT<1>{});
        wg_wait<1>();
        mbar_arrive_warp(sb + BAR_REMPTY + pslot * 8);
        if (t == T) break;
        pslot = r.slot;
        const uint32_t pxs = xs;
        r.adv(1);
        if (++xs == 5) xs = 0;
        step(FalseT{}, IntT<0>{});
        wg_wait<1>();
        mbar_arrive_warp(sb + BAR_REMPTY + pslot * 8);
        mbar_arrive_warp_if(sb + BAR_XEMPTY + pxs * 8, t + 4 < T);
    }
    wg_wait<0>();
    reg_fence(c0);
    reg_fence(c1);
    reg_fence(c2);
    mbar_arrive_warp(sb + BAR_REMPTY + r.slot * 8);
    r.adv(1);
    nb_sync<NB_OPEND, 256>();
    const uint32_t sta = sb + OFF_R + stsm_off();
    store_tile_t(c0, sta + T0 * XS);
    store_tile_t(c1, sta + (T0 + 1) * XS);
    store_tile_t(c2, sta + 4 * XS + (IS_S ? 96 * 128 : 0));
    fence_async_smem();
    nb_arrive<NB_ODONE, 288>();
}

template <int W>
__device__ __forceinline__ void on_item(uint32_t e, uint32_t sb, Ring& r, uint32_t& phm) {
    const uint32_t loRing = (((sb + OFF_RING) & 0x3ffff) >> 4) | LO_LBO1;
    const uint32_t loO = (((sb + OFF_R) & 0x3ffff) >> 4) | LO_OST;
    float c[80];
    const int T = 3 * (IT_H1(e) - IT_H0(e));
    uint32_t xs = 0;
    auto step = [&](auto first) {
        constexpr bool F = decltype(first)::value;
        mbar_wait(sb + BAR_XFULL + xs * 8, (phm >> xs) & 1, r.dl);
        phm ^= 1u << xs;
        mbar_wait(sb + BAR_RFULL + r.slot * 8, r.ph, r.dl);
        const uint32_t a = loRing + r.slot * (SLOT >> 4) + W * 256, b = loO + xs * (XS >> 4);
        wg_fence();
        wgmma<1, 1, HI_OST, !F>(c, a, b);
#pragma unroll
        for (int k = 1; k < 4; k++) wgmma<1, 1, HI_OST, true>(c, a + (k >> 1) * 512 + (k & 1) * 128, b + k * 320);
        wg_commit();
    };
    step(TrueT{});
#pragma unroll 1
    for (int t = 1; t < T; t++) {
        const uint32_t pslot = r.slot, pxs = xs;
        r.adv(1);
        if (++xs == 5) xs = 0;
        step(FalseT{});
        wg_wait<1>();
        mbar_arrive_warp(sb + BAR_REMPTY + pslot * 8);
        mbar_arrive_warp_if(sb + BAR_XEMPTY + pxs * 8, t + 2 < T);
    }
    xs += 1 + W;
    if (xs >= 5) xs -= 5;
    mbar_wait(sb + BAR_XFULL + xs * 8, (phm >> xs) & 1, r.dl);
    wg_wait<0>();
    reg_fence(c);
    store_tile_t<true>(c, sb + OFF_R + xs * XS + stsm_off());
    fence_async_smem();
    nb_arrive<NB_ODONE, 288>();
}

template <int W>
__device__ __forceinline__ uint32_t qa_item(const Params& P, uint32_t e, uint32_t sb, Ring& r, uint32_t phm, PendO<W>& po, int it) {
    const uint32_t loR = (((sb + OFF_R) & 0x3ffff) >> 4) | LO_LBO1;
    const uint32_t loRing = (((sb + OFF_RING) & 0x3ffff) >> 4) | LO_LBO1;
    {
        float q0[80], q1[80];
        qproj<W, 0>(q0, q1, sb, r, 0, phm, po, P, it);
    }
    fence_async_smem();
    TSD(W, 1);
    float s[80], oa[80], ob[W == 0 ? 32 : 48], l[10];
    if (W == 1) {
        nb_arrive<NB_Q2, 256>();
        zero(oa);
        zero(ob);
        reg_fence(oa);
        reg_fence(ob);
    }
    const uint32_t lane = tid_now() & 31, sta = sb + OFF_R + stsm_off();
    auto pv = [&](auto first, uint32_t buf) {
        constexpr bool F = decltype(first)::value;
        mbar_wait(sb + BAR_RFULL + r.slot * 8, r.ph, r.dl);
        const uint32_t a = loRing + r.slot * (SLOT >> 4), b = loR + (3 + buf) * (XS >> 4);
        wg_fence();
        wgmma<1, 0, HI_SW128, !F>(oa, a + W * 512, b);
        wgmma<1, 0, HI_SW128, !F>(ob, a + 1024, b + (W == 0 ? (96 * 128) >> 4 : 0));
#pragma unroll
        for (int k = 1; k < 4; k++) {
            wgmma<1, 0, HI_SW128, true>(oa, a + W * 512 + k * 128, b + k * 2);
            wgmma<1, 0, HI_SW128, true>(ob, a + 1024 + k * 128, b + (W == 0 ? (96 * 128) >> 4 : 0) + k * 2);
        }
        wg_commit();
    };
    zero(l);
    float mref;
    uint32_t kslot, vslot;
    auto tail = [&](auto first, int i) {
        constexpr bool rel_other = !decltype(first)::value;
        uint32_t ps[40];
        exp_block<0>(s, ps, sta + (3 + W) * XS, mref);
        if (rel_other) {
            wg_wait<0>();
            mbar_arrive_warp(sb + BAR_REMPTY + vslot * 8);
            if (W == 1) mbar_arrive_warp_if(sb + BAR_XEMPTY + 24, i == 3);
        }
        fence_async_smem();
        nb_arrive<NB_PFULL + W, 256>();
        TSD(W, 6 + 5 * i);
        if (W == 1) {
            if (XLATE >= 2) mbar_arrive_warp_if<2>(sb + BAR_XEMPTY + 8, i == 3);
            if (XLATE >= 1) mbar_arrive_warp_if<2>(sb + BAR_XEMPTY + 16, i == 3);
        }
        if (rel_other || !PV0FIRST) {
            mbar_wait(sb + BAR_RFULL + r.slot * 8, r.ph, r.dl);
            sum_block(ps, l, lane);
        }
        TSD(W, 7 + 5 * i);
        if (LASTORD && W == 0 && i == 3) nb_sync<NB_PDONE, 256>();
        else nb_sync<NB_W + W, 128>();
        pv(first, W);
        if (!rel_other && PV0FIRST) sum_block(ps, l, lane);
        TSD(W, 8 + 5 * i);
    };
    if (W == 0) {
        nb_sync<NB_QK, 160>();
        TSD(W, 2);
        wg_fence();
        qk_steps<0, 8>(s, loRing + r.slot * (SLOT >> 4), loR);
        nb_sync<NB_Q2, 256>();
        qk_steps<8, 12>(s, loRing + r.slot * (SLOT >> 4), loR);
        wg_commit();
        nb_arrive<NB_Q01, 256>();
        TSD(W, 4);
        nb_sync<NB_REF, 160>();
        mref = __uint_as_float(lds_u(sb + OFF_GM));
        wg_wait<0>();
        reg_fence(s);
        mbar_arrive_warp<2>(sb + BAR_REMPTY + r.slot * 8);
        r.adv(2);
        TSD(W, 5);
        tail(TrueT{}, 0);
    } else {
        nb_sync<NB_Q01, 256>();
    }
#pragma unroll 1
    for (int i = (W == 0 ? 1 : 0); i < 4; i++) {
        const uint32_t pvslot = r.slot;
        r.adv(1);
        kslot = r.slot;
        mbar_wait(sb + BAR_RFULL + r.slot * 8, r.ph, r.dl);
        wg_fence();
        qk_steps<0, 12>(s, loRing + r.slot * (SLOT >> 4), loR);
        wg_commit();
        wg_wait<1>();
        mbar_arrive_warp_if(sb + BAR_REMPTY + pvslot * 8, W == 0 || i > 0);
        r.adv(1);
        vslot = r.slot;
        TSD(W, 4 + 5 * i);
        nb_sync<NB_PFULL + (W ^ 1), 256>();
        pv(FalseT{}, W ^ 1);
        if (LASTORD && W == 1 && i == 3) nb_arrive<NB_PDONE, 256>();
        if (W == 1) mref = __uint_as_float(lds_u(sb + OFF_GM));
        wg_wait<1>();
        reg_fence(s);
        mbar_arrive_warp<2>(sb + BAR_REMPTY + kslot * 8);
        if (W == 1) {
            mbar_arrive_warp_if<2>(sb + BAR_XEMPTY + 0, i == 3);
            if (XLATE < 2) mbar_arrive_warp_if<2>(sb + BAR_XEMPTY + 8, i == 3);
            if (XLATE < 1) mbar_arrive_warp_if<2>(sb + BAR_XEMPTY + 16, i == 3);
        }
        r.adv(W == 1 && i == 3 ? 1 : 2);
        TSD(W, 5 + 5 * i);
        tail(FalseT{}, i);
    }
    const uint32_t w = (tid_now() >> 5) & 3;
    const uint32_t lxa = sb + OFF_LX + w * 640 + (((lane & 8) ? 80 : 0) + ((lane >> 1) & 8) + 2 * (lane & 3) + ((lane >> 2) & 1)) * 4;
    const uint32_t nx = get_item_warp(sb, it + 1, r.dl);
    po.gp = ostash(IT_SLOT(e), IT_B(e)) + po.toff();
    po.sig = 1;
    if (W == 0) {
        sum_store<false>(l, lane, lxa);
        nb_arrive<NB_LX, 256>();
        wg_wait<0>();
        mbar_arrive_warp(sb + BAR_REMPTY + r.slot * 8);
        mbar_arrive_warp(sb + BAR_XEMPTY + 24);
        r.adv(1);
        nb_sync<NB_PFULL + 1, 256>();
        pv(FalseT{}, 1);
        if (IT_TYPE(nx) == IT_QA) {
            Ring rn = r;
            rn.adv(1);
            mbar_wait(sb + BAR_RFULL + rn.slot * 8, rn.ph, r.dl);
            mbar_wait(sb + BAR_XFULL, phm & 1, r.dl);
        }
    } else {
        nb_sync<NB_LX, 256>();
        sum_store<true>(l, lane, lxa);
        nb_arrive<NB_L, 160>();
    }
    TSD(W, 24);
    wg_wait<0>();
    reg_fence(oa);
    reg_fence(ob);
    mbar_arrive_warp(sb + BAR_REMPTY + r.slot * 8);
    mbar_arrive_warp(sb + BAR_XEMPTY + 32);
    r.adv(1);
    opack(ob, po.v + 40);
    opack(oa, po.v);
    return nx;
}

template <int W>
__device__ __forceinline__ void consumer(const Params& P, uint32_t sb, uint32_t dl) {
    int it = 0;
    if (W == 0) TS(0, 30);
    Ring r{0, 0, dl};
    uint32_t phm = 0;
    uint32_t e = get_item_warp(sb, 0, dl);
#pragma unroll 1
    while (e != 0) {
        if (IT_TYPE(e) == IT_QA) {
            PendO<W> po;
            po.clear();
#pragma unroll 1
            do {
                TS(W, 0);
                if (W == 0) TS_ITEM(e);
                e = qa_item<W>(P, e, sb, r, phm, po, it);
                TS(W, 31);
                it++;
            } while (IT_TYPE(e) == IT_QA);
            po.verdict(P, sb, it - 1);
            po.template step<0>(sb);
            po.template step<1>(sb);
            po.template step<2>(sb);
            po.template step<3>(sb);
            po.template step<4>(sb);
        } else {
            TS(W, 0);
            if (W == 0) TS_ITEM(e);
            if (IT_TYPE(e) == IT_OP) op_item<W == 0>(e, sb, r, phm);
            else on_item<W>(e, sb, r, phm);
            TS(W, 31);
            e = get_item_warp(sb, ++it, dl);
        }
    }
    TS_DUMP(W);
}

__global__ void __cluster_dims__(2, 1, 1) __launch_bounds__(384, 1) fused_kernel(const __grid_constant__ Params P) {
    extern __shared__ __align__(1024) unsigned char smem_raw[];
    const uint32_t sb = (uint32_t)__cvta_generic_to_shared(smem_raw);
    const uint32_t wgid = __shfl_sync(0xffffffffu, threadIdx.x >> 7, 0);
    const uint32_t cta = blockIdx.x;
    const uint32_t dl = deadline();

    if (threadIdx.x == 128) {
#pragma unroll
        for (int i = 0; i < NSLOT; i++) {
            mbar_init(sb + BAR_RFULL + i * 8, 1);
            mbar_init(sb + BAR_REMPTY + i * 8, 8);
            mbar_init(sb + BAR_XFULL + i * 8, 1);
            mbar_init(sb + BAR_XEMPTY + i * 8, 8);
        }
        asm volatile("fence.mbarrier_init.release.cluster;" ::: "memory");
        fence_async_smem();
    } else if (threadIdx.x == 160) {
#pragma unroll
        for (int i = 0; i < NSLOT + MAXI; i++) mbar_init(sb + BAR_PRDY + i * 8, 1);
        asm volatile("fence.mbarrier_init.release.cluster;" ::: "memory");
    } else if (threadIdx.x == 0) {
        sts_u(sb + OFF_ITEM, P.cl[cta >> 1].items[0] ? P.cl[cta >> 1].items[0] + 8 * (cta & 1) : 0);
        sts_u(sb + OFF_FB, P.cl[cta >> 1].delay);
    } else if (threadIdx.x == 64) {
        if (sb & 1023) __trap();
        asm volatile("prefetch.tensormap [%0];" ::"l"(&P.wq[0]) : "memory");
        asm volatile("prefetch.tensormap [%0];" ::"l"(&P.x[0]) : "memory");
    }
    __syncthreads();
    asm volatile("barrier.cluster.arrive.relaxed.aligned;" ::: "memory");

    if (wgid == 0) {
        asm volatile("setmaxnreg.dec.sync.aligned.u32 24;");
        const uint32_t warp = __shfl_sync(0xffffffffu, threadIdx.x >> 5, 0);
        if (warp == 0) {
            const bool lead = threadIdx.x == 0;
            const uint64_t pol_first = mkpol<1>(), pol_norm = mkpol<POL_W>();
            uint32_t e = __shfl_sync(0xffffffffu, lds_u(sb + OFF_ITEM), 0);
            {
                const uint32_t d = lds_u(sb + OFF_FB);
                uint32_t t0, t1;
                asm volatile("mov.u32 %0, %%clock;" : "=r"(t0));
                do {
                    asm volatile("mov.u32 %0, %%clock;" : "=r"(t1));
                } while (t1 - t0 < d);
                __syncwarp();
            }
            if (lead) asm volatile("mbarrier.arrive.shared::cta.b64 _, [%0];" ::"r"(sb + BAR_ITEM) : "memory");
#pragma unroll 1
            for (int n = 0; n < (e ? NSLOT : 0); n++) {
                if (lead) {
                    mbar_expect(sb + BAR_RFULL + n * 8, SLOT);
                    tma3(sb + OFF_RING + n * SLOT, &P.wq[0], n * 64, IT_H0(e) * 3, sb + BAR_RFULL + n * 8, pol_norm);
                    mbar_expect(sb + BAR_XFULL + n * 8, XS);
                    tma3(sb + OFF_R + n * XS, &P.x[0], IT_B(e) * 160, n, sb + BAR_XFULL + n * 8, pol_norm);
                    tma3(sb + OFF_RING + n * SLOT + SLOT / 2, &P.wq[0], n * 64 + 32, IT_H0(e) * 3, sb + BAR_RFULL + n * 8, pol_norm);
                }
            }
            __syncwarp();
            asm volatile("barrier.cluster.wait.aligned;" ::: "memory");
            unsigned int* const ticket = &g_ticket[next_epoch(0) & 1];
            const uint32_t rank = cta & 1;
            uint32_t peer;
            asm volatile("mapa.shared::cluster.u32 %0, %1, %2;" : "=r"(peer) : "r"(sb), "r"(rank ^ 1));
            Ring r{0, 0, dl};
            uint32_t pm = 0;
            auto load_w = [&](const CUtensorMap* m, int row, int blk, uint32_t half_bytes) {
                mbar_wait(sb + BAR_REMPTY + r.slot * 8, r.ph, dl);
                if (lead) {
                    mbar_expect(sb + BAR_RFULL + r.slot * 8, 2 * half_bytes);
                    asm volatile("mbarrier.arrive.shared::cluster.b64 _, [%0];" ::"r"(peer + BAR_PRDY + r.slot * 8) : "memory");
                }
                mbar_wait(sb + BAR_PRDY + r.slot * 8, (pm >> r.slot) & 1, dl);
                pm ^= 1u << r.slot;
                if (lead) tma3_mc(sb + OFF_RING + r.slot * SLOT + rank * half_bytes, m, row, blk, sb + BAR_RFULL + r.slot * 8, pol_norm);
                r.adv(1);
            };
#pragma unroll 1
            for (int it = 0; e != 0; it++) {
                uint32_t nx = 0, tk = 0;
                if (rank == 0 && IT_TYPE(e) != IT_ON && it + 2 < MAXI) nx = it + 1 < NSTAT ? P.cl[cta >> 1].items[it + 1] : IT_DYN;
                const uint32_t br = IT_BR(e);
                if (IT_TYPE(e) == IT_QA) {
                    const uint32_t h = IT_H0(e);
#pragma unroll 1
                    for (int kk = it ? 0 : NSLOT; kk < 10; kk++) load_w(&P.wq[br], kk * 64 + rank * 32, h * 3, SLOT / 2);
                    const int row0 = (IT_B(e) * 32 + h) * 512;
#pragma unroll 1
                    for (int n = 0; n < 16; n++) {
                        if (n == 13 && nx == IT_DYN && lead) tk = atomicAdd(ticket, 1);
                        const bool isv = n == 15 || (n > 0 && !(n & 1));
                        const int j = n == 15 ? 7 : isv ? (n - 2) >> 1 : (n + 1) >> 1;
                        mbar_wait(sb + BAR_REMPTY + r.slot * 8, r.ph, dl);
                        if (lead) {
                            mbar_expect(sb + BAR_RFULL + r.slot * 8, SLOT);
                            tma3(sb + OFF_RING + r.slot * SLOT, isv ? &P.v[br] : &P.k[br], row0 + j * 64, 0,
                                 sb + BAR_RFULL + r.slot * 8, pol_first);
                        }
                        r.adv(1);
                    }
                } else {
                    const bool wide = IT_TYPE(e) == IT_OP;
                    const int step = wide ? 32 : 64, r1 = IT_H1(e) * 192;
#pragma unroll 1
                    for (int row = IT_H0(e) * 192 + rank * (step >> 1); row < r1; row += step)
                        load_w(wide ? &P.wo[br] : &P.won[br], row, IT_HALF(e) * (wide ? 5 : 2), wide ? XS / 2 : 8192);
                    if (nx == IT_DYN && lead) tk = atomicAdd(ticket, 1);
                }
                if (rank == 0) {
                    if (nx == IT_DYN) {
                        tk = __shfl_sync(0xffffffffu, tk, 0);
                        nx = tk < P.nlist ? P.list[tk] : 0;
                    }
                    e = nx;
                    if (lead) {
                        asm volatile("st.async.weak.shared::cluster.mbarrier::complete_tx::bytes.b32 [%0], %1, [%2];" ::"r"(
                                         peer + OFF_ITEM + 4 + it * 4),
                                     "r"(e ? e + 8 : 0), "r"(peer + BAR_ITEM + 8 + it * 8)
                                     : "memory");
                        sts_u(sb + OFF_ITEM + 4 + it * 4, e);
                        asm volatile("mbarrier.arrive.shared::cta.b64 _, [%0];" ::"r"(sb + BAR_ITEM + 8 + it * 8) : "memory");
                    }
                } else {
                    if (lead) mbar_expect(sb + BAR_ITEM + 8 + it * 8, 4);
                    e = get_item_warp(sb, it + 1, dl);
                }
            }
        } else if (warp == 1) {
            const uint64_t pol_norm = mkpol<POL_X>(), pol_o = mkpol<POL_O>();
            const bool lead = threadIdx.x == 32;
            uint32_t phm = 0, epoch = 0;
#pragma unroll 1
            for (int it = 0;; it++) {
                const uint32_t e = get_item_warp(sb, it, dl);
                if (it == 1 || (it == 0 && e == 0)) epoch = next_epoch(1);
                if (e == 0) break;
                const uint32_t br = IT_BR(e);
                uint32_t xs = 0;
                auto acquire = [&]() {
                    mbar_wait(sb + BAR_XEMPTY + xs * 8, (phm >> xs) & 1, dl);
                    phm ^= 1u << xs;
                    if (lead) mbar_expect(sb + BAR_XFULL + xs * 8, XS);
                };
                if (IT_TYPE(e) == IT_QA) {
#pragma unroll 1
                    for (int kk = it ? 0 : 5; kk < 10; kk++) {
                        acquire();
                        if (lead) tma3(sb + OFF_R + xs * XS, &P.x[br], IT_B(e) * 160, kk, sb + BAR_XFULL + xs * 8, pol_norm);
                        if (++xs == 5) xs = 0;
                    }
                } else {
                    const unsigned int* fp = g_flag + (br * 16 + IT_B(e)) * 64 + (threadIdx.x & 31);
                    uint32_t hm = 0, pm = 0;
                    auto poll = [&](uint32_t hneed, uint32_t pneed) {
                        if ((hm & hneed) == hneed && (pm & pneed) == pneed) return;
                        uint32_t n = 0;
                        do {
                            uint32_t a, b;
                            asm volatile("ld.acquire.gpu.global.u32 %0, [%2];\nld.acquire.gpu.global.u32 %1, [%2+128];"
                                         : "=r"(a), "=r"(b) : "l"(fp) : "memory");
                            hm = __ballot_sync(0xffffffffu, a == epoch);
                            pm = __ballot_sync(0xffffffffu, b == epoch);
                            if (++n > 0x1000000) __trap();
                        } while ((hm & hneed) != hneed || (pm & pneed) != pneed);
                        __syncwarp();
                        asm volatile("fence.proxy.async;" ::: "memory");
                    };
#pragma unroll 1
                    for (uint32_t h = IT_H0(e); h < IT_H1(e); h++) {
                        poll(1u << h, 0);
                        const unsigned char* src = ostash(P.slot[br * 32 + h], IT_B(e));
#pragma unroll 1
                        for (int t = 0; t < 3; t++) {
                            acquire();
                            if (lead) bulk_load(sb + OFF_R + xs * XS, src + t * XS, XS, sb + BAR_XFULL + xs * 8, pol_o);
                            if (++xs == 5) xs = 0;
                        }
                        if (IT_TYPE(e) == IT_OP && h >= 1) {
                            const uint32_t x1 = xs == 4 ? 0 : xs + 1;
                            mbar_wait(sb + BAR_XFULL + xs * 8, (phm >> xs) & 1, dl);
                            mbar_wait(sb + BAR_XFULL + x1 * 8, (phm >> x1) & 1, dl);
                            if (lead)
                                asm volatile("st.relaxed.gpu.global.u32 [%0], %1;" ::"l"(fp + 34 + IT_HALF(e)), "r"(epoch * 64 + h) : "memory");
                        }
                    }
                    if (IT_TYPE(e) == IT_ON) {
                        poll(0, IT_HALF(e) < 2 ? 1 : IT_HALF(e) == 2 ? 3 : 2);
#pragma unroll 1
                        for (uint32_t tile = 2 * IT_HALF(e); tile < 2 * IT_HALF(e) + 2; tile++) {
                            acquire();
                            if (lead)
                                asm volatile(
                                    "cp.async.bulk.tensor.5d.shared::cluster.global.mbarrier::complete_tx::bytes [%0], [%1, {%3,%5,%5,%5,%4}], [%2];" ::"r"(
                                        sb + OFF_R + xs * XS),
                                    "l"(&P.out), "r"(sb + BAR_XFULL + xs * 8), "r"(br * 640 + tile * 64), "r"(IT_B(e) * 5), "r"(0)
                                    : "memory");
                            if (++xs == 5) xs = 0;
                        }
                    }
                }
            }
        } else if (warp == 2) {
            asm volatile("barrier.cluster.wait.aligned;" ::: "memory");
            const uint32_t epoch = next_epoch(2);
            if (cta == 0) g_ticket[(epoch + 1) & 1] = 0;
#pragma unroll 1
            for (int it = 0;; it++) {
                const uint32_t e = get_item_warp(sb, it, dl);
                if (e == 0) break;
                nb_sync<NB_ODONE, 288>();
                if (threadIdx.x == 64) {
                    const uint32_t bb = IT_BR(e) * 16 + IT_B(e);
                    if (IT_TYPE(e) != IT_QA) {
                        const bool wide = IT_TYPE(e) == IT_OP;
                        if (wide)
                            asm volatile("st.relaxed.gpu.global.u32 [%0], %1;" ::"l"(&g_flag[bb * 64 + 34 + IT_HALF(e)]),
                                         "r"(epoch * 64 + IT_H1(e))
                                         : "memory");
                        const int cc0 = IT_BR(e) * 640 + IT_HALF(e) * (wide ? 320 : 128);
                        uint32_t xs = wide ? 0 : (3 * (IT_H1(e) - IT_H0(e))) % 5;
#pragma unroll 1
                        for (int m = 0; m < (wide ? 5 : 2); m++) {
                            asm volatile("cp.async.bulk.tensor.5d.global.shared::cta.bulk_group [%0, {%2,%4,%4,%4,%3}], [%1];" ::"l"(&P.out),
                                         "r"(sb + OFF_R + xs * XS), "r"(cc0 + m * 64), "r"((int)IT_B(e) * 5), "r"(0)
                                         : "memory");
                            asm volatile("cp.async.bulk.commit_group;" ::: "memory");
                            if (++xs == 5) xs = 0;
                        }
                        if (wide) {
#define REL(N)                                                          \
    asm volatile("cp.async.bulk.wait_group.read %0;" ::"n"(4 - N) : "memory"); \
    asm volatile("mbarrier.arrive.shared::cta.b64 _, [%0], 8;" ::"r"(sb + BAR_XEMPTY + N * 8) : "memory");
                            REL(0) REL(1) REL(2) REL(3) REL(4)
#undef REL
                        }
                        if (IT_PART(e)) {
                            asm volatile("cp.async.bulk.wait_group 0;" ::: "memory");
                            asm volatile("fence.proxy.async;" ::: "memory");
                        }
                    }
                    if (IT_TYPE(e) == IT_QA || IT_PART(e)) {
                        unsigned int* f = &g_flag[bb * 64 + (IT_TYPE(e) == IT_QA ? IT_H0(e) : 32 + IT_HALF(e))];
                        asm volatile("st.release.gpu.global.u32 [%0], %1;" ::"l"(f), "r"(epoch) : "memory");
                    }
                }
                __syncwarp();
            }
            if (threadIdx.x == 64) asm volatile("cp.async.bulk.wait_group 0;" ::: "memory");
            __syncwarp();
            asm volatile("barrier.cluster.arrive.relaxed.aligned;\nbarrier.cluster.wait.aligned;" ::: "memory");
        } else {
            const uint32_t lane = threadIdx.x & 31, p = lane >> 2;
            const uint32_t epoch = next_epoch(3);
#pragma unroll 1
            for (int it = 0;; it++) {
                const uint32_t e = get_item_warp(sb, it, dl);
                if (e == 0) break;
                if (IT_TYPE(e) != IT_QA) continue;
                nb_sync<NB_QK, 160>();
                const uint32_t co = (((lane & 3) * 2) ^ p) << 4;
                const uint32_t ka = sb + OFF_RING + lds_u(sb + OFF_GM + 4) * SLOT + p * (9 * 128) + co;
                const uint32_t qa = sb + OFF_R + p * 128 + co;
                uint32_t acc = 0;
#pragma unroll 1
                for (int c = 0; c < 3; c++) {
                    if (c == 2) nb_sync<NB_L, 160>();
                    const uint4 k0 = lds_u4(ka + c * 8192), q0 = lds_u4(qa + c * XS);
                    acc = fma_bf2(k0.x, q0.x, fma_bf2(k0.y, q0.y, fma_bf2(k0.z, q0.z, fma_bf2(k0.w, q0.w, acc))));
                    const uint4 k1 = lds_u4((ka + c * 8192) ^ 16), q1 = lds_u4((qa + c * XS) ^ 16);
                    acc = fma_bf2(k1.x, q1.x, fma_bf2(k1.y, q1.y, fma_bf2(k1.z, q1.z, fma_bf2(k1.w, q1.w, acc))));
                }
                float d = __uint_as_float(acc << 16) + __uint_as_float(acc & 0xffff0000u);
                d += __shfl_xor_sync(0xffffffffu, d, 1);
                d += __shfl_xor_sync(0xffffffffu, d, 2);
                int key = __float_as_int(d);
                key ^= (key >> 31) & 0x7fffffff;
                key = __reduce_max_sync(0xffffffffu, key);
                key ^= (key >> 31) & 0x7fffffff;
                sts_f(sb + OFF_GM, __int_as_float(key) * SM_C);
                nb_arrive<NB_REF, 160>();
                if (IT_DEP(e)) {
                    const uint32_t g = IT_DEP(e) - 1, need = epoch * 64 + (g & 31) + 1;
                    const unsigned int* cp = &g_flag[((g >> 5) * 16 + IT_B(e)) * 64 + 34 + (lane & 1)];
                    for (uint32_t n = 0;; n++) {
                        uint32_t v;
                        asm volatile("ld.acquire.gpu.global.u32 %0, [%1];" : "=r"(v) : "l"(cp) : "memory");
                        if (__all_sync(0xffffffffu, v - need < 64)) break;
                        if (n > 0x800000) __trap();
                        __nanosleep(500);
                    }
                }
                nb_sync<NB_L, 160>();
                bool bad = false;
#pragma unroll
                for (int c = 0; c < 5; c++) {
                    const uint32_t la = sb + OFF_LX + (c * 32 + lane) * 4;
                    const float v = (__uint_as_float(lds_u(la)) + __uint_as_float(lds_u(la + 640))) +
                                    (__uint_as_float(lds_u(la + 1280)) + __uint_as_float(lds_u(la + 1920)));
                    const float inv = __fdividef(1.f, v);
                    const uint32_t hi = pack_bf16(inv, 0.f), lo = pack_bf16(inv - __uint_as_float(hi << 16), 0.f);
                    const uint32_t ia = sb + OFF_LINV + c * 128 + ((lane >> 1) & 3) * 32 + (lane >> 3) * 8 + (lane & 1) * 2;
                    asm volatile("st.shared.u16 [%0], %1;\nst.shared.u16 [%0+4], %2;" ::"r"(ia), "h"((unsigned short)hi), "h"((unsigned short)lo) : "memory");
                    bad |= !(v >= 5.421010862e-20f && v <= 1.8446744e19f);
                }
                sts_u(sb + OFF_FB, __any_sync(0xffffffffu, bad));
                nb_arrive<NB_VOTE, 160>();
                nb_arrive<NB_VOTE + 1, 160>();
            }
        }
    } else if (wgid == 1) {
        asm volatile("setmaxnreg.inc.sync.aligned.u32 240;");
        consumer<0>(P, sb, dl);
    } else {
        asm volatile("setmaxnreg.inc.sync.aligned.u32 240;");
        consumer<1>(P, sb, dl);
    }
}

typedef CUresult (*EncFn)(CUtensorMap*, CUtensorMapDataType, cuuint32_t, void*, const cuuint64_t*, const cuuint64_t*,
                          const cuuint32_t*, const cuuint32_t*, CUtensorMapInterleave, CUtensorMapSwizzle,
                          CUtensorMapL2promotion, CUtensorMapFloatOOBfill);

void make_map3(EncFn enc, CUtensorMap* m, void* p, uint64_t rows, uint64_t rowbytes, uint64_t nblk, uint32_t boxrows,
               uint32_t boxblk) {
    cuuint64_t dims[3] = {64, rows, nblk};
    cuuint64_t str[2] = {rowbytes, 128};
    cuuint32_t box[3] = {64, boxrows, boxblk};
    cuuint32_t es[3] = {1, 1, 1};
    enc(m, CU_TENSOR_MAP_DATA_TYPE_BFLOAT16, 3, p, dims, str, box, es, CU_TENSOR_MAP_INTERLEAVE_NONE,
        CU_TENSOR_MAP_SWIZZLE_128B, CU_TENSOR_MAP_L2_PROMOTION_NONE, CU_TENSOR_MAP_FLOAT_OOB_FILL_NONE);
}

constexpr int tune(const char*, int def) { return def; }

void build_schedule(Params& P) {
    const int mode = tune("MODE", 4), dmax = tune("DMAX", 24900), n0 = tune("N0", 8);
    const int H0[8] = {20, 20, 22, 22, 22, 24, 25, 25}, P0[8] = {352, 352, 344, 348, 352, 345, 333, 336};
    const int ng = tune("NG", 0), d0 = tune("D0", 0), nkeep = tune("NKEEP", 0), odmax = tune("ODMAX", 2000);
    const int ong = tune("ONG", 0), od0 = tune("OD0", 0), jit = tune("JIT", 0);
    const int npos = tune("NPOS", 0), nearly = tune("NEARLY", 0);
    const int ra = tune("RA", 10), ga = tune("GA", 32), rb = tune("RB", 12), g1 = tune("G1", 58);
    int dep[64];
    for (int g = 0, ns = 0, live = 0; g < 64; g++) {
        const bool fresh = mode < 3 || g >= g1 || live < (g < ga ? ra : rb);
        dep[g] = fresh ? 0 : g - live + 1;
        P.slot[g] = fresh ? ns++ : P.slot[g - live];
        live += fresh;
    }
    int u = 0;
    auto unit = [&]() {
        const uint32_t e = mk_item(IT_QA, u >> 8, (u & 7) * 2, (u >> 3) & 31, P.slot[u >> 3], 0) | (dep[u >> 3] << 23);
        u++;
        return e;
    };
    int qa[NCL], nq = 0, op[NCL], no = 0;
    for (int c = 0; c < NCL; c++) {
        P.cl[c].delay = 0;
        for (int i = 0; i < NSTAT; i++) P.cl[c].items[i] = 0;
        if (mode >= 3 && c < 64 && (c & 3) == 3) op[no++] = c;
        else if (mode != 2 || (c & 3) == 0) qa[nq++] = c;
    }
    for (int t = 0; t < no; t++) {
        P.cl[op[t]].items[1] = mk_item(IT_OP, 0, t & ~1, 0, 32, t & 1);
        P.cl[op[t]].items[2] = IT_DYN;
        P.cl[op[t]].delay = ong ? od0 + (t * ong / 16) * (odmax / ong) : od0 + t * odmax / 16;
    }
    for (int k = 0; k < nq; k++) {
        const int c = qa[(k * 19) % nq];
        P.cl[c].items[1] = P.cl[c].items[2] = IT_DYN;
        P.cl[c].delay = k < n0 ? 0 : (int)((long long)dmax * (k + 1 - n0) / (nq - n0));
        if (ng) P.cl[c].delay = d0 + (k * ng / nq) * (dmax / ng) + (k * ng % nq) * jit / nq;
    }
    if (tune("OFIRST", 0))
        for (int t = 0; t < no; t++) P.cl[op[t]].items[0] = unit();
    for (int k = u; k < no + nq; k++) {
        int best = -1;
        for (int c = 0; c < NCL; c++)
            if (P.cl[c].items[1] && !P.cl[c].items[0] && (best < 0 || P.cl[c].delay < P.cl[best].delay)) best = c;
        P.cl[best].items[0] = unit();
    }
    int H[8], pos[8];
    for (int b = 0; b < 8; b++) {
        char nh[3] = {'H', (char)('0' + b), 0}, np[3] = {'P', (char)('0' + b), 0};
        H[b] = tune(nh, H0[b]);
        pos[b] = tune(np, P0[b]);
        for (int g = 0; g < 64; g++)
            if (dep[g] > 32) {
                if (pos[b] > 8 * g) pos[b] = 8 * g;
                if (H[b] < dep[g] - 32) H[b] = dep[g] - 32;
            }
        if (b < nkeep && no) {
            pos[b] = -1;
            P.cl[op[14 - 2 * b]].items[2] = mk_item(IT_OP, 1, 2 * b, 0, H[b], 0, 1);
            P.cl[op[15 - 2 * b]].items[2] = mk_item(IT_OP, 1, 2 * b, 0, H[b], 1, 1);
        }
    }
    int n = 0, kn = 0;
    const int uend = mode == 2 ? 8 * nq : 512;
    while (u < uend) {
        for (int b = 0; b < 8 && no; b++)
            if (pos[b] == u) {
                P.list[n++] = mk_item(IT_OP, 1, 2 * b, 0, H[b], 0, 1);
                P.list[n++] = mk_item(IT_OP, 1, 2 * b, 0, H[b], 1, 1);
            }
        while (no && u >= uend - npos && kn * npos < (u + 1 - (uend - npos)) * nearly) {
            P.list[n++] = mk_item(IT_ON, 1, kn / 5 * 2, H[kn / 5], 32, kn % 5);
            kn++;
        }
        P.list[n++] = unit();
    }
    for (; no && kn < 40; kn++) P.list[n++] = mk_item(IT_ON, 1, kn / 5 * 2, H[kn / 5], 32, kn % 5);
    P.nlist = n;
}

}

extern "C" void kernel_launch(void* const* d_in, const int* in_sizes, int n_in, void* d_out, int out_size) {
    static Params P;
    static bool init = false;
    if (!init) {
        EncFn enc = nullptr;
        cudaDriverEntryPointQueryResult qr;
        cudaGetDriverEntryPoint("cuTensorMapEncodeTiled", (void**)&enc, cudaEnableDefault, &qr);
        for (int i = 0; i < 2; i++) {
            P.px[i] = (const __nv_bfloat16*)d_in[5 * i + 0];
            P.pk[i] = (const __nv_bfloat16*)d_in[5 * i + 1];
            P.pv[i] = (const __nv_bfloat16*)d_in[5 * i + 2];
            P.pwq[i] = (const __nv_bfloat16*)d_in[5 * i + 3];
            make_map3(enc, &P.x[i], d_in[5 * i + 0], 2560, 1280, 10, 160, 1);
            make_map3(enc, &P.k[i], d_in[5 * i + 1], 16 * 32 * 512, 384, 3, 64, 3);
            make_map3(enc, &P.v[i], d_in[5 * i + 2], 16 * 32 * 512, 384, 3, 64, 3);
            make_map3(enc, &P.wq[i], d_in[5 * i + 3], 640, 12288, 96, 32, 3);
            make_map3(enc, &P.wo[i], d_in[5 * i + 4], 6144, 1280, 10, 16, 5);
            make_map3(enc, &P.won[i], d_in[5 * i + 4], 6144, 1280, 10, 32, 2);
        }
        cuuint64_t dims[5] = {1280, 2, 4, 4, 80};
        cuuint64_t str[4] = {2560, 8 * 2560, 2 * 2560, 32 * 2560};
        cuuint32_t box[5] = {64, 2, 4, 4, 5};
        cuuint32_t es[5] = {1, 1, 1, 1, 1};
        enc(&P.out, CU_TENSOR_MAP_DATA_TYPE_BFLOAT16, 5, d_out, dims, str, box, es, CU_TENSOR_MAP_INTERLEAVE_NONE,
            CU_TENSOR_MAP_SWIZZLE_128B, CU_TENSOR_MAP_L2_PROMOTION_NONE, CU_TENSOR_MAP_FLOAT_OOB_FILL_NONE);
        build_schedule(P);
        cudaFuncSetAttribute(fused_kernel, cudaFuncAttributeMaxDynamicSharedMemorySize, SMEM_LAUNCH);
        init = true;
    }
    fused_kernel<<<NCTA, 384, SMEM_LAUNCH>>>(P);
}
```

```cpp
#include <cuda_runtime.h>
#include <cuda.h>
#include <cuda_bf16.h>
#include <stdint.h>

namespace {

constexpr int NCTA = 132;
constexpr int NCL = NCTA / 2;
constexpr int MAXI = 16;
constexpr int NSTAT = 3;
constexpr uint32_t IT_DYN = 0xffffffffu;
constexpr int SLOT = 24576;
constexpr int NSLOT = 5;
constexpr int XS = 20480;
constexpr int OFF_R = 0;
constexpr int OFF_RING = 5 * XS;
constexpr int OFF_MISC = OFF_RING + NSLOT * SLOT;
constexpr int OFF_LX = OFF_MISC;
constexpr int OFF_LINV = OFF_LX + 2560;
constexpr int OFF_FB = OFF_LINV + 640;
constexpr int OFF_GM = OFF_FB + 16;
constexpr int OFF_BAR = OFF_GM + 16;
constexpr int BAR_RFULL = OFF_BAR;
constexpr int BAR_REMPTY = BAR_RFULL + 40;
constexpr int BAR_XFULL = BAR_REMPTY + 40;
constexpr int BAR_XEMPTY = BAR_XFULL + 40;
constexpr int BAR_PRDY = BAR_XEMPTY + 40;
constexpr int BAR_ITEM = BAR_PRDY + 40;
constexpr int OFF_ITEM = BAR_ITEM + MAXI * 8;
constexpr int SMEM_BYTES = OFF_ITEM + MAXI * 4;
static_assert(SMEM_BYTES <= 232448, "smem");

constexpr int NB_W = 1  , NB_PFULL = 3  , NB_VOTE = 5  , NB_Q2 = 7, NB_SDONE = 8, NB_PDONE = 9,
              NB_L = 10, NB_REF = 11, NB_ODONE = 12, NB_OPEND = 13, NB_LX = 14, NB_Q01 = 15, NB_QK = 0  ;

constexpr uint32_t IT_QA = 1, IT_OP = 2, IT_ON = 3;
__host__ __device__ constexpr uint32_t mk_item(uint32_t type, uint32_t br, uint32_t b, uint32_t h0, uint32_t h1, uint32_t half,
                                               uint32_t part = 0) {
    return type | (br << 2) | (b << 3) | (h0 << 7) | (h1 << 13) | (half << 19) | (part << 22);
}
#define IT_TYPE(e) ((e) & 3u)
#define IT_BR(e) (((e) >> 2) & 1u)
#define IT_B(e) (((e) >> 3) & 15u)
#define IT_H0(e) (((e) >> 7) & 63u)
#define IT_H1(e) (((e) >> 13) & 63u)
#define IT_HALF(e) (((e) >> 19) & 7u)
#define IT_PART(e) (((e) >> 22) & 1u)
#define IT_SLOT(e) IT_H1(e)
#define IT_DEP(e) (((e) >> 23) & 127u)

struct Params {
    CUtensorMap x[2], wq[2], k[2], v[2], wo[2], won[2], out;
    const __nv_bfloat16 *px[2], *pwq[2], *pk[2], *pv[2];
    struct alignas(16) { uint32_t delay, items[NSTAT]; } cl[NCL];
    uint32_t nlist;
    uint8_t slot[64];
    uint32_t list[512];
};

constexpr int OUNIT = 61440;
__device__ __align__(1024) unsigned char g_ostash[(size_t)1024 * OUNIT];
__device__ unsigned int g_flag[32 * 64];
__device__ __forceinline__ unsigned char* ostash(uint32_t slot, uint32_t b) { return g_ostash + (slot * 16 + b) * OUNIT; }
__device__ unsigned int g_epoch[NCTA * 4];
__device__ unsigned int g_ticket[2];

constexpr int SMEM_LAUNCH = SMEM_BYTES;
#define TS(role, idx)
#define TS_ITEM(e)
#define TS_DUMP(role)
#define TSD(role, idx)

#define POL_W 2
#define POL_X 2
#define POL_O 2
template <int M>
__device__ __forceinline__ uint64_t mkpol() {
    uint64_t p;
    if (M == 0) asm volatile("createpolicy.fractional.L2::evict_normal.b64 %0, 1.0;" : "=l"(p));
    if (M == 1) asm volatile("createpolicy.fractional.L2::evict_first.b64 %0, 1.0;" : "=l"(p));
    if (M == 2) asm volatile("createpolicy.fractional.L2::evict_unchanged.b64 %0, 1.0;" : "=l"(p));
    if (M == 3) asm volatile("createpolicy.fractional.L2::evict_normal.L2::evict_unchanged.b64 %0, 0.25;" : "=l"(p));
    return p;
}
#define STSM_W 1
#define LASTORD 0
#define XLATE 2
#define PV0FIRST 1
#define QST0 1
#define QST1 2
#define QHOLD 8
constexpr float SM_C = 0.07216878364870322f * 1.4426950408889634f;

__device__ __forceinline__ uint32_t next_epoch(int warp) {
    unsigned int* p = &g_epoch[blockIdx.x * 4 + warp];
    const uint32_t e = __ldcg(p) + 1;
    *p = e;
    return e;
}

__device__ __forceinline__ uint32_t tid_now() {
    uint32_t t;
    asm volatile("mov.u32 %0, %%tid.x;" : "=r"(t));
    return t;
}
__device__ __forceinline__ void mbar_init(uint32_t a, uint32_t c) {
    asm volatile("mbarrier.init.shared::cta.b64 [%0], %1;" ::"r"(a), "r"(c) : "memory");
}
__device__ __forceinline__ void mbar_expect(uint32_t a, uint32_t b) {
    asm volatile("mbarrier.arrive.expect_tx.shared::cta.b64 _, [%0], %1;" ::"r"(a), "r"(b) : "memory");
}
template <int CNT = 1>
__device__ __forceinline__ void mbar_arrive_warp(uint32_t a) {
    if (CNT == 1)
        asm volatile("{\n.reg .pred p;\nelect.sync _|p, 0xffffffff;\n@p mbarrier.arrive.shared::cta.b64 _, [%0];\n}" ::"r"(a) : "memory");
    else
        asm volatile(
            "{\n.reg .pred p;\nelect.sync _|p, 0xffffffff;\n@p mbarrier.arrive.shared::cta.b64 _, [%0];\n"
            "@p mbarrier.arrive.shared::cta.b64 _, [%0];\n}" ::"r"(a)
            : "memory");
}
template <int CNT = 1>
__device__ __forceinline__ void mbar_arrive_warp_if(uint32_t a, bool cond) {
    if (CNT == 1)
        asm volatile(
            "{\n.reg .pred p, c;\nelect.sync _|p, 0xffffffff;\nsetp.ne.and.u32 c, %1, 0, p;\n"
            "@c mbarrier.arrive.shared::cta.b64 _, [%0];\n}" ::"r"(a), "r"((uint32_t)cond)
            : "memory");
    else
        asm volatile(
            "{\n.reg .pred p, c;\nelect.sync _|p, 0xffffffff;\nsetp.ne.and.u32 c, %1, 0, p;\n"
            "@c mbarrier.arrive.shared::cta.b64 _, [%0];\n@c mbarrier.arrive.shared::cta.b64 _, [%0];\n}" ::"r"(a), "r"((uint32_t)cond)
            : "memory");
}
__device__ __forceinline__ uint32_t deadline() {
    uint32_t c;
    asm volatile("mov.u32 %0, %%clock_hi;" : "=r"(c));
    return c + 4;
}
__device__ __forceinline__ void mbar_wait(uint32_t a, uint32_t ph, uint32_t dl) {
    asm volatile(
        "{\n.reg .pred p;\n.reg .u32 m;\n"
        "LOOP:\n"
        "mbarrier.try_wait.parity.shared::cta.b64 p, [%0], %1;\n"
        "@p bra DONE;\n"
        "mov.u32 m, %%clock_hi;\n"
        "setp.ne.u32 p, m, %2;\n"
        "@p bra LOOP;\n"
        "trap;\n"
        "DONE:\n}" ::"r"(a), "r"(ph), "r"(dl)
        : "memory");
}
template <int ID, int CNT>
__device__ __forceinline__ void nb_sync() { asm volatile("bar.sync %0, %1;" ::"n"(ID), "n"(CNT) : "memory"); }
template <int ID, int CNT>
__device__ __forceinline__ void nb_arrive() { asm volatile("bar.arrive %0, %1;" ::"n"(ID), "n"(CNT) : "memory"); }
__device__ __forceinline__ void fence_async_smem() { asm volatile("fence.proxy.async.shared::cta;" ::: "memory"); }

__device__ __forceinline__ void tma3(uint32_t dst, const CUtensorMap* m, int c1, int c2, uint32_t bar, uint64_t pol) {
    asm volatile(
        "cp.async.bulk.tensor.3d.shared::cluster.global.mbarrier::complete_tx::bytes.L2::cache_hint [%0], [%1, {%3,%4,%5}], [%2], %6;" ::"r"(dst),
        "l"(m), "r"(bar), "r"(0), "r"(c1), "r"(c2), "l"(pol)
        : "memory");
}
__device__ __forceinline__ void tma3_mc(uint32_t dst, const CUtensorMap* m, int c1, int c2, uint32_t bar, uint64_t pol) {
    asm volatile(
        "cp.async.bulk.tensor.3d.shared::cluster.global.mbarrier::complete_tx::bytes.multicast::cluster.L2::cache_hint"
        " [%0], [%1, {%3,%4,%5}], [%2], %6, %7;" ::"r"(dst),
        "l"(m), "r"(bar), "r"(0), "r"(c1), "r"(c2), "h"((unsigned short)3), "l"(pol)
        : "memory");
}
__device__ __forceinline__ void bulk_load(uint32_t dst, const void* src, uint32_t bytes, uint32_t bar, uint64_t pol) {
    asm volatile("cp.async.bulk.shared::cluster.global.mbarrier::complete_tx::bytes.L2::cache_hint [%0], [%1], %2, [%3], %4;" ::"r"(dst),
                 "l"(src), "r"(bytes), "r"(bar), "l"(pol)
                 : "memory");
}
__device__ __forceinline__ void wg_fence() { asm volatile("wgmma.fence.sync.aligned;" ::: "memory"); }
__device__ __forceinline__ void wg_commit() { asm volatile("wgmma.commit_group.sync.aligned;" ::: "memory"); }
template <int N>
__device__ __forceinline__ void wg_wait() { asm volatile("wgmma.wait_group.sync.aligned %0;" ::"n"(N) : "memory"); }

#define RW80(c, d) c(d[0]), c(d[1]), c(d[2]), c(d[3]), c(d[4]), c(d[5]), c(d[6]), c(d[7]), c(d[8]), c(d[9]), c(d[10]), c(d[11]), c(d[12]), c(d[13]), c(d[14]), c(d[15]), c(d[16]), c(d[17]), c(d[18]), c(d[19]), c(d[20]), c(d[21]), c(d[22]), c(d[23]), c(d[24]), c(d[25]), c(d[26]), c(d[27]), c(d[28]), c(d[29]), c(d[30]), c(d[31]), c(d[32]), c(d[33]), c(d[34]), c(d[35]), c(d[36]), c(d[37]), c(d[38]), c(d[39]), c(d[40]), c(d[41]), c(d[42]), c(d[43]), c(d[44]), c(d[45]), c(d[46]), c(d[47]), c(d[48]), c(d[49]), c(d[50]), c(d[51]), c(d[52]), c(d[53]), c(d[54]), c(d[55]), c(d[56]), c(d[57]), c(d[58]), c(d[59]), c(d[60]), c(d[61]), c(d[62]), c(d[63]), c(d[64]), c(d[65]), c(d[66]), c(d[67]), c(d[68]), c(d[69]), c(d[70]), c(d[71]), c(d[72]), c(d[73]), c(d[74]), c(d[75]), c(d[76]), c(d[77]), c(d[78]), c(d[79])
#define RW48(c, d) c(d[0]), c(d[1]), c(d[2]), c(d[3]), c(d[4]), c(d[5]), c(d[6]), c(d[7]), c(d[8]), c(d[9]), c(d[10]), c(d[11]), c(d[12]), c(d[13]), c(d[14]), c(d[15]), c(d[16]), c(d[17]), c(d[18]), c(d[19]), c(d[20]), c(d[21]), c(d[22]), c(d[23]), c(d[24]), c(d[25]), c(d[26]), c(d[27]), c(d[28]), c(d[29]), c(d[30]), c(d[31]), c(d[32]), c(d[33]), c(d[34]), c(d[35]), c(d[36]), c(d[37]), c(d[38]), c(d[39]), c(d[40]), c(d[41]), c(d[42]), c(d[43]), c(d[44]), c(d[45]), c(d[46]), c(d[47])
#define RW32(c, d) c(d[0]), c(d[1]), c(d[2]), c(d[3]), c(d[4]), c(d[5]), c(d[6]), c(d[7]), c(d[8]), c(d[9]), c(d[10]), c(d[11]), c(d[12]), c(d[13]), c(d[14]), c(d[15]), c(d[16]), c(d[17]), c(d[18]), c(d[19]), c(d[20]), c(d[21]), c(d[22]), c(d[23]), c(d[24]), c(d[25]), c(d[26]), c(d[27]), c(d[28]), c(d[29]), c(d[30]), c(d[31])

__device__ __forceinline__ void reg_fence(float (&d)[80]) { asm volatile("" : RW80("+f", d)::"memory"); }
__device__ __forceinline__ void reg_fence(float (&d)[48]) { asm volatile("" : RW48("+f", d)::"memory"); }
__device__ __forceinline__ void reg_fence(float (&d)[32]) { asm volatile("" : RW32("+f", d)::"memory"); }

template <int NR>
__device__ __forceinline__ void zero(float (&d)[NR]) {
#pragma unroll
    for (int i = 0; i < NR; i++) d[i] = 0.f;
}

constexpr uint32_t HI_SW128 = (1024u >> 4) | (1u << 30);
constexpr uint32_t HI_OST = (2560u >> 4) | (2u << 30);
constexpr uint32_t LO_LBO1 = (1u << 16);
constexpr uint32_t LO_OST = ((512u >> 4) << 16);

template <int TA, int TB, uint32_t HIB, int ACC>
__device__ __forceinline__ void wgmma(float (&d)[80], uint32_t loA, uint32_t loB) {
#define WG_ASM(SD)                                                          \
    "{\n.reg .b64 da, db;\nmov.b64 da, {%80, %82};\nmov.b64 db, {%81, %83};\n" \
    "wgmma.mma_async.sync.aligned.m64n160k16.f32.bf16.bf16 "               \
    "{%0,%1,%2,%3,%4,%5,%6,%7,%8,%9,%10,%11,%12,%13,%14,%15,%16,%17,%18,%19,%20,%21,%22,%23,%24,%25,%26,%27,%28,%29,%30,%31,%32,%33,%34,%35,%36,%37,%38,%39,%40,%41,%42,%43,%44,%45,%46,%47,%48,%49,%50,%51,%52,%53,%54,%55,%56,%57,%58,%59,%60,%61,%62,%63,%64,%65,%66,%67,%68,%69,%70,%71,%72,%73,%74,%75,%76,%77,%78,%79}, da, db, " SD ", 1, 1, %84, %85;\n}"
    if constexpr (ACC == 2)
        asm volatile(WG_ASM("0") : RW80("+f", d) : "r"(loA), "r"(loB), "n"(HI_SW128), "n"(HIB), "n"(TA), "n"(TB));
    else if constexpr (ACC == 1)
        asm volatile(WG_ASM("1") : RW80("+f", d) : "r"(loA), "r"(loB), "n"(HI_SW128), "n"(HIB), "n"(TA), "n"(TB));
    else
        asm volatile(WG_ASM("0") : RW80("=f", d) : "r"(loA), "r"(loB), "n"(HI_SW128), "n"(HIB), "n"(TA), "n"(TB));
#undef WG_ASM
}
template <int TA, int TB, uint32_t HIB, int ACC>
__device__ __forceinline__ void wgmma(float (&d)[48], uint32_t loA, uint32_t loB) {
#define WG_ASM(SD)                                                          \
    "{\n.reg .b64 da, db;\nmov.b64 da, {%48, %50};\nmov.b64 db, {%49, %51};\n" \
    "wgmma.mma_async.sync.aligned.m64n96k16.f32.bf16.bf16 "               \
    "{%0,%1,%2,%3,%4,%5,%6,%7,%8,%9,%10,%11,%12,%13,%14,%15,%16,%17,%18,%19,%20,%21,%22,%23,%24,%25,%26,%27,%28,%29,%30,%31,%32,%33,%34,%35,%36,%37,%38,%39,%40,%41,%42,%43,%44,%45,%46,%47}, da, db, " SD ", 1, 1, %52, %53;\n}"
    if constexpr (ACC == 1)
        asm volatile(WG_ASM("1") : RW48("+f", d) : "r"(loA), "r"(loB), "n"(HI_SW128), "n"(HIB), "n"(TA), "n"(TB));
    else
        asm volatile(WG_ASM("0") : RW48("=f", d) : "r"(loA), "r"(loB), "n"(HI_SW128), "n"(HIB), "n"(TA), "n"(TB));
#undef WG_ASM
}
template <int TA, int TB, uint32_t HIB, int ACC>
__device__ __forceinline__ void wgmma(float (&d)[32], uint32_t loA, uint32_t loB) {
#define WG_ASM(SD)                                                          \
    "{\n.reg .b64 da, db;\nmov.b64 da, {%32, %34};\nmov.b64 db, {%33, %35};\n" \
    "wgmma.mma_async.sync.aligned.m64n64k16.f32.bf16.bf16 "               \
    "{%0,%1,%2,%3,%4,%5,%6,%7,%8,%9,%10,%11,%12,%13,%14,%15,%16,%17,%18,%19,%20,%21,%22,%23,%24,%25,%26,%27,%28,%29,%30,%31}, da, db, " SD ", 1, 1, %36, %37;\n}"
    if constexpr (ACC == 1)
        asm volatile(WG_ASM("1") : RW32("+f", d) : "r"(loA), "r"(loB), "n"(HI_SW128), "n"(HIB), "n"(TA), "n"(TB));
    else
        asm volatile(WG_ASM("0") : RW32("=f", d) : "r"(loA), "r"(loB), "n"(HI_SW128), "n"(HIB), "n"(TA), "n"(TB));
#undef WG_ASM
}

__device__ __forceinline__ uint32_t pack_bf16(float lo, float hi) {
    uint32_t r;
    asm("cvt.rn.bf16x2.f32 %0, %1, %2;" : "=r"(r) : "f"(hi), "f"(lo));
    return r;
}
__device__ __forceinline__ float ex2(float x) {
    float r;
    asm("ex2.approx.ftz.f32 %0, %1;" : "=f"(r) : "f"(x));
    return r;
}
__device__ __forceinline__ void stsm4t(uint32_t a, uint32_t r0, uint32_t r1, uint32_t r2, uint32_t r3) {
    asm volatile("stmatrix.sync.aligned.m8n8.x4.trans.shared.b16 [%0], {%1,%2,%3,%4};" ::"r"(a), "r"(r0), "r"(r1), "r"(r2), "r"(r3)
                 : "memory");
}
__device__ __forceinline__ uint32_t lds_u(uint32_t a) {
    uint32_t v;
    asm volatile("ld.shared.u32 %0, [%1];" : "=r"(v) : "r"(a) : "memory");
    return v;
}
__device__ __forceinline__ uint4 lds_u4(uint32_t a) {
    uint4 v;
    asm volatile("ld.shared.v4.u32 {%0,%1,%2,%3}, [%4];" : "=r"(v.x), "=r"(v.y), "=r"(v.z), "=r"(v.w) : "r"(a) : "memory");
    return v;
}
__device__ __forceinline__ float2 lds_f2(uint32_t a) {
    float2 v;
    asm volatile("ld.shared.v2.f32 {%0,%1}, [%2];" : "=f"(v.x), "=f"(v.y) : "r"(a) : "memory");
    return v;
}
__device__ __forceinline__ void sts_f(uint32_t a, float v) { asm volatile("st.shared.f32 [%0], %1;" ::"r"(a), "f"(v) : "memory"); }
__device__ __forceinline__ void sts_u(uint32_t a, uint32_t v) { asm volatile("st.shared.u32 [%0], %1;" ::"r"(a), "r"(v) : "memory"); }
__device__ __forceinline__ void sts_f2(uint32_t a, float x, float y) {
    asm volatile("st.shared.v2.f32 [%0], {%1,%2};" ::"r"(a), "f"(x), "f"(y) : "memory");
}

template <bool ADD = false, bool SIG = false, int NR>
__device__ __forceinline__ void store_tile_t(const float (&d)[NR], uint32_t addr) {
    uint32_t p[NR / 2];
    if (ADD) {
#pragma unroll
        for (int j = 0; j < NR / 8; j++)
            asm volatile("ldmatrix.sync.aligned.m8n8.x4.trans.shared.b16 {%0,%1,%2,%3}, [%4];"
                         : "=r"(p[4 * j]), "=r"(p[4 * j + 1]), "=r"(p[4 * j + 2]), "=r"(p[4 * j + 3])
                         : "r"(addr + j * 2048)
                         : "memory");
    }
#pragma unroll
    for (int k = 0; k < NR / 2; k++)
        p[k] = ADD ? pack_bf16(d[2 * k] + __uint_as_float(p[k] << 16), d[2 * k + 1] + __uint_as_float(p[k] & 0xffff0000u))
                   : pack_bf16(d[2 * k], d[2 * k + 1]);
#pragma unroll
    for (int j = 0; j < NR / 8; j++) {
        stsm4t(addr + j * 2048, p[4 * j], p[4 * j + 1], p[4 * j + 2], p[4 * j + 3]);
        if (SIG && j == 0) nb_arrive<NB_L, 160>();
    }
}

struct TrueT { static constexpr bool value = true; };
struct FalseT { static constexpr bool value = false; };

template <int V>
struct IntT { static constexpr int value = V; };

__device__ __forceinline__ uint32_t get_item(uint32_t sb, int it, uint32_t dl) {
    mbar_wait(sb + BAR_ITEM + it * 8, 0, dl);
    return lds_u(sb + OFF_ITEM + it * 4);
}
__device__ __forceinline__ uint32_t get_item_warp(uint32_t sb, int it, uint32_t dl) {
    return __shfl_sync(0xffffffffu, get_item(sb, it, dl), 0);
}

struct Ring {
    uint32_t slot, ph, dl;
    __device__ __forceinline__ void adv(uint32_t k) {
        slot += k;
        if (slot >= NSLOT) { slot -= NSLOT; ph ^= 1; }
    }
};

template <int K>
__device__ __forceinline__ void qk_step(float (&s)[80], uint32_t loK, uint32_t loQ) {
    wgmma<0, 0, HI_SW128, K != 0>(s, loK + (K >> 2) * (8192 >> 4) + (K & 3) * 2, loQ + (K >> 2) * (XS >> 4) + (K & 3) * 2);
}
template <int K0, int K1>
__device__ __forceinline__ void qk_steps(float (&s)[80], uint32_t loK, uint32_t loQ) {
    if constexpr (K0 < K1) {
        qk_step<K0>(s, loK, loQ);
        qk_steps<K0 + 1, K1>(s, loK, loQ);
    }
}
__device__ __forceinline__ uint32_t add_bf2(uint32_t a, uint32_t b) {
    uint32_t r;
    asm("add.rn.bf16x2 %0, %1, %2;" : "=r"(r) : "r"(a), "r"(b));
    return r;
}
__device__ __forceinline__ uint32_t fma_bf2(uint32_t a, uint32_t b, uint32_t c) {
    uint32_t r;
    asm("fma.rn.bf16x2 %0, %1, %2, %3;" : "=r"(r) : "r"(a), "r"(b), "r"(c));
    return r;
}
template <int J>
__device__ __forceinline__ void exp_block(const float (&s)[80], uint32_t (&k)[40], uint32_t pa, float mref) {
    if constexpr (J < 10) {
#pragma unroll
        for (int i = 4 * J; i < 4 * J + 4; i++)
            k[i] = pack_bf16(ex2(fmaf(s[2 * i], SM_C, -mref)), ex2(fmaf(s[2 * i + 1], SM_C, -mref)));
#pragma unroll
        for (int i = 0; i < 4; i++)
            asm volatile("stmatrix.sync.aligned.m8n8.x1.trans.shared.b16 [%0], {%1};" ::"r"(((i & 1) ? pa ^ 16 : pa) + J * 2048 + (i >> 1) * 1024),
                         "r"(k[4 * J + i])
                         : "memory");
        exp_block<J + 1>(s, k, pa, mref);
    }
}
__device__ __forceinline__ void sum_block(const uint32_t (&k)[40], float (&l)[10], uint32_t lane) {
    const bool b4 = lane & 16, b3 = lane & 8;
    uint32_t ps[20], t[10];
#pragma unroll
    for (int j = 0; j < 20; j++) ps[j] = add_bf2(k[2 * j], k[2 * j + 1]);
#pragma unroll
    for (int j = 0; j < 10; j++)
        t[j] = add_bf2(b4 ? ps[2 * j + 1] : ps[2 * j], __shfl_xor_sync(0xffffffffu, b4 ? ps[2 * j] : ps[2 * j + 1], 16));
#pragma unroll
    for (int i = 0; i < 5; i++) {
        const uint32_t a = b3 ? t[i + 5] : t[i], b = __shfl_xor_sync(0xffffffffu, b3 ? t[i] : t[i + 5], 8);
        l[2 * i] += __uint_as_float(a << 16) + __uint_as_float(b << 16);
        l[2 * i + 1] += __uint_as_float(a & 0xffff0000u) + __uint_as_float(b & 0xffff0000u);
    }
}
template <bool ADD>
__device__ __forceinline__ void sum_store(const float (&l)[10], uint32_t lane, uint32_t lxa) {
    const bool b2 = lane & 4;
    float t[5];
#pragma unroll
    for (int i = 0; i < 5; i++) t[i] = ADD ? __uint_as_float(lds_u(lxa + i * 64)) : 0.f;
#pragma unroll
    for (int i = 0; i < 5; i++)
        sts_f(lxa + i * 64, t[i] + (b2 ? l[2 * i + 1] : l[2 * i]) + __shfl_xor_sync(0xffffffffu, b2 ? l[2 * i] : l[2 * i + 1], 4));
}

__device__ __forceinline__ void fallback_unit(const Params& P, uint32_t e, uint32_t tid) {
    const uint32_t lane = tid & 31, br = IT_BR(e), b = IT_B(e), h = IT_H0(e);
    const __nv_bfloat162* wq = (const __nv_bfloat162*)(P.pwq[br] + h * 192) + lane;
    const __nv_bfloat162* kp = (const __nv_bfloat162*)(P.pk[br] + (size_t)(b * 32 + h) * 512 * 192) + lane;
    const __nv_bfloat162* vp = (const __nv_bfloat162*)(P.pv[br] + (size_t)(b * 32 + h) * 512 * 192) + lane;
#pragma unroll 1
    for (uint32_t qi = 0; qi < 40; qi++) {
        const uint32_t q = 4 * qi + (tid >> 5);
        const __nv_bfloat16* xr = P.px[br] + (size_t)(b * 160 + q) * 640;
        float a[6] = {0.f, 0.f, 0.f, 0.f, 0.f, 0.f};
#pragma unroll 2
        for (int k = 0; k < 640; k++) {
            const float xv = __bfloat162float(xr[k]);
#pragma unroll
            for (int i = 0; i < 3; i++) {
                const float2 wv = __bfloat1622float2(wq[(size_t)k * 3072 + i * 32]);
                a[2 * i] = fmaf(xv, wv.x, a[2 * i]);
                a[2 * i + 1] = fmaf(xv, wv.y, a[2 * i + 1]);
            }
        }
#pragma unroll
        for (int i = 0; i < 6; i++) a[i] = __bfloat162float(__float2bfloat16(a[i]));
        auto score = [&](int key) {
            float d = 0.f;
#pragma unroll
            for (int i = 0; i < 3; i++) {
                const float2 kv = __bfloat1622float2(kp[key * 96 + i * 32]);
                d = fmaf(a[2 * i], kv.x, fmaf(a[2 * i + 1], kv.y, d));
            }
#pragma unroll
            for (int o = 16; o > 0; o >>= 1) d += __shfl_xor_sync(0xffffffffu, d, o);
            return d;
        };
        float m = -INFINITY, o[6] = {0.f, 0.f, 0.f, 0.f, 0.f, 0.f}, sum = 0.f;
#pragma unroll 1
        for (int n = 0; n < 1024; n++) {
            const int key = n & 511;
            const float d = score(key);
            if (n < 512) {
                m = fmaxf(m, d);
            } else {
                const float p = ex2((d - m) * SM_C);
                sum += p;
#pragma unroll
                for (int i = 0; i < 3; i++) {
                    const float2 vv = __bfloat1622float2(vp[key * 96 + i * 32]);
                    o[2 * i] = fmaf(p, vv.x, o[2 * i]);
                    o[2 * i + 1] = fmaf(p, vv.y, o[2 * i + 1]);
                }
            }
        }
        const float inv = __fdividef(1.f, sum);
        __nv_bfloat16* op = (__nv_bfloat16*)ostash(IT_SLOT(e), b) + (q >> 5) * 256 + 2 * ((q & 31) >> 3) + (q & 1);
#pragma unroll
        for (int i = 0; i < 6; i++) {
            const uint32_t d = (i >> 1) * 64 + 2 * lane + (i & 1);
            op[(d >> 3) * 1280 + (d & 7) * 32 + ((((q & 7) >> 1) ^ ((d & 7) >> 1)) << 3)] = __float2bfloat16(o[i] * inv);
        }
    }
}

template <int W>
struct PendO {
    static constexpr int N = W == 0 ? 56 : 64;
    uint32_t v[N];
    unsigned char* gp;
    static __device__ __forceinline__ uint32_t toff() {
        const uint32_t t = tid_now();
        return ((t >> 5) & 3) * 5120 + ((t >> 2) & 7) * 64 + (((t ^ (t >> 3)) & 3) << 4);
    }
    uint32_t pend, sig;
    static __device__ __forceinline__ void scale(uint32_t& x, uint32_t hi, uint32_t lo) {
        asm("{\n.reg .b32 t;\nmul.rn.bf16x2 t, %0, %2;\nfma.rn.bf16x2 %0, %0, %1, t;\n}" : "+r"(x) : "r"(hi), "r"(lo));
    }
    template <int I, int OFF>
    __device__ __forceinline__ void put() {
        asm volatile("{\n.reg .pred p;\nsetp.ne.u32 p, %6, 0;\n@p st.global.v4.b32 [%0+%5], {%1,%2,%3,%4};\n}" ::"l"(gp), "r"(v[I]),
                     "r"(v[I + 1]), "r"(v[I + 2]), "r"(v[I + 3]), "n"(OFF), "r"(pend)
                     : "memory");
    }
    __device__ __forceinline__ void verdict(const Params& P, uint32_t sb, int ie) {
        if (sig) {
            nb_sync<NB_VOTE + W, 160>();
            pend = !__any_sync(0xffffffffu, lds_u(sb + OFF_FB) != 0);
            if (W == 1 && !pend) {
                fallback_unit(P, lds_u(sb + OFF_ITEM + ie * 4), tid_now() & 127);
                __syncwarp();
            }
        }
    }
    template <int G, int H>
    __device__ __forceinline__ void half(uint32_t sb) {
        constexpr bool T2 = W == 0 ? G >= 3 : G < 3;
        constexpr int B = T2 ? 40 + 8 * (W == 0 ? G - 3 : G) : 0;
        const uint4 a = lds_u4(sb + OFF_LINV + G * 128 + H * 16 + (threadIdx.x & 3) * 32);
#pragma unroll
        for (int i = 2 * H; i < 8; i += 4) {
            scale(v[8 * G + i], a.x, a.y);
            scale(v[8 * G + i + 1], a.z, a.w);
            if (T2) {
                scale(v[B + i], a.x, a.y);
                scale(v[B + i + 1], a.z, a.w);
            }
        }
        if (H == 1) {
            put<8 * G, W * XS + G * 512>();
            put<8 * G + 4, W * XS + G * 512 + 2560>();
            if (T2) {
                put<B, 2 * XS + G * 512>();
                put<B + 4, 2 * XS + G * 512 + 2560>();
            }
            if (G == 4 && sig) nb_arrive<NB_ODONE, 288>();
        }
    }
    template <int G>
    __device__ __forceinline__ void step(uint32_t sb) {
        half<G, 0>(sb);
        half<G, 1>(sb);
    }
    __device__ __forceinline__ void clear() {
#pragma unroll
        for (int i = 0; i < N; i++) v[i] = 0;
        gp = nullptr;
        pend = 0;
        sig = 0;
    }
};

__device__ __forceinline__ uint32_t stsm_off() {
    const uint32_t tid = tid_now(), lane = tid & 31;
    return (lane >> 4) * 1024 + (lane & 7) * 128 + (((((tid >> 4) & 6) + ((lane >> 3) & 1)) ^ (lane & 7)) << 4);
}
template <int W, int KK>
__device__ __forceinline__ void qproj(float (&q0)[80], float (&q1)[80], uint32_t sb, Ring& r, uint32_t pslot, uint32_t phm,
                                      PendO<W>& po, const Params& P, int it) {
    const uint32_t loR = (((sb + OFF_R) & 0x3ffff) >> 4) | LO_LBO1;
    const uint32_t loRing = (((sb + OFF_RING) & 0x3ffff) >> 4) | LO_LBO1;
    auto ready = [&](int k) {
        mbar_wait(sb + BAR_RFULL + r.slot * 8, r.ph, r.dl);
        mbar_wait(sb + BAR_XFULL + (k % 5) * 8, ((phm >> (k % 5)) ^ (k / 5)) & 1, r.dl);
    };
    auto release = [&]() {
        if (KK > 0) {
            wg_wait<1>();
            mbar_arrive_warp(sb + BAR_REMPTY + pslot * 8);
            if (KK <= 5) mbar_arrive_warp(sb + (BAR_XEMPTY + (KK - 1) * 8));
        }
    };
    if (KK == 0 && (W == 1 || !po.sig)) ready(0);
    if (W == 1 && KK == QHOLD) {
        if (QHOLD == 7) {
            wg_wait<0>();
            nb_arrive<NB_PDONE, 256>();
        }
        nb_sync<NB_SDONE, 256>();
    }
    const uint32_t a = loRing + r.slot * (SLOT >> 4) + (W == 0 ? 0 : 512), b = loR + (KK % 5) * (XS >> 4);
    wg_fence();
    wgmma<1, 0, HI_SW128, KK != 0>(q0, a, b);
    if (W == 0) wgmma<1, 0, HI_SW128, KK != 0>(q1, a + 256, b);
#pragma unroll
    for (int k = 1; k < 4; k++) {
        wgmma<1, 0, HI_SW128, true>(q0, a + (k >> 1) * 768 + (k & 1) * 128, b + k * 2);
        if (W == 0) wgmma<1, 0, HI_SW128, true>(q1, a + 256 + (k >> 1) * 768 + (k & 1) * 128, b + k * 2);
    }
    wg_commit();
    const uint32_t cslot = r.slot;
    r.adv(1);
    if (W == 0 || KK < QHOLD) release();
    if (KK == QST0) {
        po.verdict(P, sb, it - 1);
        po.template half<0, 0>(sb);
    }
    if (KK < 9) ready(KK + 1);
    if (W == 1 && KK >= QHOLD) release();
    if (W == 1 && KK == 7 && QHOLD > 7) nb_arrive<NB_PDONE, 256>();
    if (KK == QST0) po.template half<0, 1>(sb);
    if constexpr (KK > QST0 && KK < QST0 + 5) po.template step<KK - QST0>(sb);
    if constexpr (KK < (W == 0 ? 7 : 9)) {
        qproj<W, KK + 1>(q0, q1, sb, r, cslot, phm, po, P, it);
    } else if constexpr (W == 1) {
        wg_wait<0>();
        reg_fence(q0);
        mbar_arrive_warp(sb + BAR_REMPTY + cslot * 8);
        store_tile_t<false, true>(q0, sb + OFF_R + 2 * XS + stsm_off());
    } else {
        const uint32_t s8 = r.slot, a8 = loRing + s8 * (SLOT >> 4);
        wg_fence();
#pragma unroll
        for (int k = 0; k < 4; k++) wgmma<1, 0, HI_SW128, true>(q0, a8 + (k >> 1) * 768 + (k & 1) * 128, loR + 3 * (XS >> 4) + k * 2);
        r.adv(1);
        ready(9);
        const uint32_t s9 = r.slot, a9 = loRing + s9 * (SLOT >> 4);
        r.adv(1);
        wg_fence();
#pragma unroll
        for (int k = 0; k < 4; k++) wgmma<1, 0, HI_SW128, true>(q0, a9 + (k >> 1) * 768 + (k & 1) * 128, loR + 4 * (XS >> 4) + k * 2);
        wg_commit();
        wg_wait<1>();
        mbar_arrive_warp(sb + BAR_REMPTY + cslot * 8);
        wg_fence();
#pragma unroll
        for (int k = 0; k < 8; k++)
            wgmma<1, 0, HI_SW128, true>(q1, (k < 4 ? a8 : a9) + 256 + ((k >> 1) & 1) * 768 + (k & 1) * 128,
                                        loR + (3 + (k >> 2)) * (XS >> 4) + (k & 3) * 2);
        wg_commit();
        nb_arrive<NB_SDONE, 256>();
        nb_sync<NB_PDONE, 256>();
        wg_wait<1>();
        reg_fence(q0);
        const uint32_t sta = sb + OFF_R + stsm_off();
        store_tile_t(q0, sta);
        sts_u(sb + OFF_GM + 4, r.slot);
        mbar_wait(sb + BAR_RFULL + r.slot * 8, r.ph, r.dl);
        wg_wait<0>();
        reg_fence(q1);
        mbar_arrive_warp(sb + BAR_REMPTY + s8 * 8);
        mbar_arrive_warp(sb + BAR_REMPTY + s9 * 8);
        store_tile_t(q1, sta + XS);
    }
}

template <int NR>
__device__ __forceinline__ void opack(const float (&o)[NR], uint32_t* v) {
#pragma unroll
    for (int g = 0; g < NR / 16; g++)
#pragma unroll
        for (int hh = 0; hh < 2; hh++)
#pragma unroll
            for (int t = 0; t < 4; t++) v[8 * g + 4 * hh + t] = pack_bf16(o[16 * g + 4 * t + 2 * hh], o[16 * g + 4 * t + 2 * hh + 1]);
}

template <bool IS_S>
__device__ __forceinline__ void op_item(uint32_t e, uint32_t sb, Ring& r, uint32_t& phm) {
    constexpr int T0 = IS_S ? 0 : 2;
    constexpr uint32_t BOFF = IS_S ? (3 * 512) >> 4 : 0;
    const uint32_t loRing = (((sb + OFF_RING) & 0x3ffff) >> 4) | LO_LBO1;
    const uint32_t loO = (((sb + OFF_R) & 0x3ffff) >> 4) | LO_OST;
    float c0[80], c1[80], c2[IS_S ? 32 : 48];
    const int T = 3 * (IT_H1(e) - IT_H0(e));
    uint32_t xs = 0;
    auto step = [&](auto first, auto half) {
        constexpr bool F = decltype(first)::value;
        constexpr uint32_t hf = decltype(half)::value;
        if (hf == 0) {
            mbar_wait(sb + BAR_XFULL + xs * 8, (phm >> xs) & 1, r.dl);
            phm ^= 1u << xs;
        }
        mbar_wait(sb + BAR_RFULL + r.slot * 8, r.ph, r.dl);
        const uint32_t a = loRing + r.slot * (SLOT >> 4), b = loO + xs * (XS >> 4) + hf * 640;
        wg_fence();
        wgmma<1, 1, HI_OST, !F>(c0, a + T0 * 128, b);
        wgmma<1, 1, HI_OST, !F>(c1, a + T0 * 128 + 128, b);
        wgmma<1, 1, HI_OST, !F>(c2, a + 512, b + BOFF);
        wgmma<1, 1, HI_OST, true>(c0, a + 640 + T0 * 128, b + 320);
        wgmma<1, 1, HI_OST, true>(c1, a + 640 + T0 * 128 + 128, b + 320);
        wgmma<1, 1, HI_OST, true>(c2, a + 640 + 512, b + 320 + BOFF);
        wg_commit();
    };
    step(TrueT{}, IntT<0>{});
#pragma unroll 1
    for (int t = 1;; t++) {
        uint32_t pslot = r.slot;
        r.adv(1);
        step(FalseT{}, IntT<1>{});
        wg_wait<1>();
        mbar_arrive_warp(sb + BAR_REMPTY + pslot * 8);
        if (t == T) break;
        pslot = r.slot;
        const uint32_t pxs = xs;
        r.adv(1);
        if (++xs == 5) xs = 0;
        step(FalseT{}, IntT<0>{});
        wg_wait<1>();
        mbar_arrive_warp(sb + BAR_REMPTY + pslot * 8);
        mbar_arrive_warp_if(sb + BAR_XEMPTY + pxs * 8, t + 4 < T);
    }
    wg_wait<0>();
    reg_fence(c0);
    reg_fence(c1);
    reg_fence(c2);
    mbar_arrive_warp(sb + BAR_REMPTY + r.slot * 8);
    r.adv(1);
    nb_sync<NB_OPEND, 256>();
    const uint32_t sta = sb + OFF_R + stsm_off();
    store_tile_t(c0, sta + T0 * XS);
    store_tile_t(c1, sta + (T0 + 1) * XS);
    store_tile_t(c2, sta + 4 * XS + (IS_S ? 96 * 128 : 0));
    fence_async_smem();
    nb_arrive<NB_ODONE, 288>();
}

__device__ __forceinline__ void on_item(uint32_t W, uint32_t e, uint32_t sb, Ring& r, uint32_t& phm) {
    const uint32_t loRing = (((sb + OFF_RING) & 0x3ffff) >> 4) | LO_LBO1;
    const uint32_t loO = (((sb + OFF_R) & 0x3ffff) >> 4) | LO_OST;
    float c[80];
    const int T = 3 * (IT_H1(e) - IT_H0(e));
    uint32_t xs = 0;
    auto step = [&](auto first) {
        constexpr bool F = decltype(first)::value;
        mbar_wait(sb + BAR_XFULL + xs * 8, (phm >> xs) & 1, r.dl);
        phm ^= 1u << xs;
        mbar_wait(sb + BAR_RFULL + r.slot * 8, r.ph, r.dl);
        const uint32_t a = loRing + r.slot * (SLOT >> 4) + W * 256, b = loO + xs * (XS >> 4);
        wg_fence();
        wgmma<1, 1, HI_OST, !F>(c, a, b);
#pragma unroll
        for (int k = 1; k < 4; k++) wgmma<1, 1, HI_OST, true>(c, a + (k >> 1) * 512 + (k & 1) * 128, b + k * 320);
        wg_commit();
    };
    step(TrueT{});
#pragma unroll 1
    for (int t = 1; t < T; t++) {
        const uint32_t pslot = r.slot, pxs = xs;
        r.adv(1);
        if (++xs == 5) xs = 0;
        step(FalseT{});
        wg_wait<1>();
        mbar_arrive_warp(sb + BAR_REMPTY + pslot * 8);
        mbar_arrive_warp_if(sb + BAR_XEMPTY + pxs * 8, t + 2 < T);
    }
    xs += 1 + W;
    if (xs >= 5) xs -= 5;
    mbar_wait(sb + BAR_XFULL + xs * 8, (phm >> xs) & 1, r.dl);
    wg_wait<0>();
    reg_fence(c);
    store_tile_t<true>(c, sb + OFF_R + xs * XS + stsm_off());
    fence_async_smem();
    nb_arrive<NB_ODONE, 288>();
}

template <int W>
__device__ __forceinline__ uint32_t qa_item(const Params& P, uint32_t e, uint32_t sb, Ring& r, uint32_t phm, PendO<W>& po, int it) {
    const uint32_t loR = (((sb + OFF_R) & 0x3ffff) >> 4) | LO_LBO1;
    const uint32_t loRing = (((sb + OFF_RING) & 0x3ffff) >> 4) | LO_LBO1;
    {
        float q0[80], q1[80];
        qproj<W, 0>(q0, q1, sb, r, 0, phm, po, P, it);
    }
    fence_async_smem();
    TSD(W, 1);
    float s[80], oa[80], ob[W == 0 ? 32 : 48], l[10];
    if (W == 1) {
        nb_arrive<NB_Q2, 256>();
        zero(oa);
        zero(ob);
        reg_fence(oa);
        reg_fence(ob);
    }
    const uint32_t lane = tid_now() & 31, sta = sb + OFF_R + stsm_off();
    auto pv = [&](auto first, uint32_t buf) {
        constexpr bool F = decltype(first)::value;
        mbar_wait(sb + BAR_RFULL + r.slot * 8, r.ph, r.dl);
        const uint32_t a = loRing + r.slot * (SLOT >> 4), b = loR + (3 + buf) * (XS >> 4);
        wg_fence();
        wgmma<1, 0, HI_SW128, !F>(oa, a + W * 512, b);
        wgmma<1, 0, HI_SW128, !F>(ob, a + 1024, b + (W == 0 ? (96 * 128) >> 4 : 0));
#pragma unroll
        for (int k = 1; k < 4; k++) {
            wgmma<1, 0, HI_SW128, true>(oa, a + W * 512 + k * 128, b + k * 2);
            wgmma<1, 0, HI_SW128, true>(ob, a + 1024 + k * 128, b + (W == 0 ? (96 * 128) >> 4 : 0) + k * 2);
        }
        wg_commit();
    };
    zero(l);
    float mref;
    uint32_t kslot, vslot;
    auto tail = [&](auto first, int i) {
        constexpr bool rel_other = !decltype(first)::value;
        uint32_t ps[40];
        exp_block<0>(s, ps, sta + (3 + W) * XS, mref);
        if (rel_other) {
            wg_wait<0>();
            mbar_arrive_warp(sb + BAR_REMPTY + vslot * 8);
            if (W == 1) mbar_arrive_warp_if(sb + BAR_XEMPTY + 24, i == 3);
        }
        fence_async_smem();
        nb_arrive<NB_PFULL + W, 256>();
        TSD(W, 6 + 5 * i);
        if (W == 1) {
            if (XLATE >= 2) mbar_arrive_warp_if<2>(sb + BAR_XEMPTY + 8, i == 3);
            if (XLATE >= 1) mbar_arrive_warp_if<2>(sb + BAR_XEMPTY + 16, i == 3);
        }
        if (rel_other || !PV0FIRST) {
            mbar_wait(sb + BAR_RFULL + r.slot * 8, r.ph, r.dl);
            sum_block(ps, l, lane);
        }
        TSD(W, 7 + 5 * i);
        if (LASTORD && W == 0 && i == 3) nb_sync<NB_PDONE, 256>();
        else nb_sync<NB_W + W, 128>();
        pv(first, W);
        if (!rel_other && PV0FIRST) sum_block(ps, l, lane);
        TSD(W, 8 + 5 * i);
    };
    if (W == 0) {
        nb_sync<NB_QK, 160>();
        TSD(W, 2);
        wg_fence();
        qk_steps<0, 8>(s, loRing + r.slot * (SLOT >> 4), loR);
        nb_sync<NB_Q2, 256>();
        qk_steps<8, 12>(s, loRing + r.slot * (SLOT >> 4), loR);
        wg_commit();
        nb_arrive<NB_Q01, 256>();
        TSD(W, 4);
        nb_sync<NB_REF, 160>();
        mref = __uint_as_float(lds_u(sb + OFF_GM));
        wg_wait<0>();
        reg_fence(s);
        mbar_arrive_warp<2>(sb + BAR_REMPTY + r.slot * 8);
        r.adv(2);
        TSD(W, 5);
        tail(TrueT{}, 0);
    } else {
        nb_sync<NB_Q01, 256>();
    }
#pragma unroll 1
    for (int i = (W == 0 ? 1 : 0); i < 4; i++) {
        const uint32_t pvslot = r.slot;
        r.adv(1);
        kslot = r.slot;
        mbar_wait(sb + BAR_RFULL + r.slot * 8, r.ph, r.dl);
        wg_fence();
        qk_steps<0, 12>(s, loRing + r.slot * (SLOT >> 4), loR);
        wg_commit();
        wg_wait<1>();
        mbar_arrive_warp_if(sb + BAR_REMPTY + pvslot * 8, W == 0 || i > 0);
        r.adv(1);
        vslot = r.slot;
        TSD(W, 4 + 5 * i);
        nb_sync<NB_PFULL + (W ^ 1), 256>();
        pv(FalseT{}, W ^ 1);
        if (LASTORD && W == 1 && i == 3) nb_arrive<NB_PDONE, 256>();
        if (W == 1) mref = __uint_as_float(lds_u(sb + OFF_GM));
        wg_wait<1>();
        reg_fence(s);
        mbar_arrive_warp<2>(sb + BAR_REMPTY + kslot * 8);
        if (W == 1) {
            mbar_arrive_warp_if<2>(sb + BAR_XEMPTY + 0, i == 3);
            if (XLATE < 2) mbar_arrive_warp_if<2>(sb + BAR_XEMPTY + 8, i == 3);
            if (XLATE < 1) mbar_arrive_warp_if<2>(sb + BAR_XEMPTY + 16, i == 3);
        }
        r.adv(W == 1 && i == 3 ? 1 : 2);
        TSD(W, 5 + 5 * i);
        tail(FalseT{}, i);
    }
    const uint32_t w = (tid_now() >> 5) & 3;
    const uint32_t lxa = sb + OFF_LX + w * 640 + (((lane & 8) ? 80 : 0) + ((lane >> 1) & 8) + 2 * (lane & 3) + ((lane >> 2) & 1)) * 4;
    const uint32_t nx = get_item_warp(sb, it + 1, r.dl);
    po.gp = ostash(IT_SLOT(e), IT_B(e)) + po.toff();
    po.sig = 1;
    if (W == 0) {
        sum_store<false>(l, lane, lxa);
        nb_arrive<NB_LX, 256>();
        wg_wait<0>();
        mbar_arrive_warp(sb + BAR_REMPTY + r.slot * 8);
        mbar_arrive_warp(sb + BAR_XEMPTY + 24);
        r.adv(1);
        nb_sync<NB_PFULL + 1, 256>();
        pv(FalseT{}, 1);
        if (IT_TYPE(nx) == IT_QA) {
            Ring rn = r;
            rn.adv(1);
            mbar_wait(sb + BAR_RFULL + rn.slot * 8, rn.ph, r.dl);
            mbar_wait(sb + BAR_XFULL, phm & 1, r.dl);
        }
    } else {
        nb_sync<NB_LX, 256>();
        sum_store<true>(l, lane, lxa);
        nb_arrive<NB_L, 160>();
    }
    TSD(W, 24);
    wg_wait<0>();
    reg_fence(oa);
    reg_fence(ob);
    mbar_arrive_warp(sb + BAR_REMPTY + r.slot * 8);
    mbar_arrive_warp(sb + BAR_XEMPTY + 32);
    r.adv(1);
    opack(ob, po.v + 40);
    opack(oa, po.v);
    return nx;
}

template <int W>
__device__ __forceinline__ uint32_t qa_run(const Params& P, uint32_t e, uint32_t sb, Ring& r, uint32_t phm, int& it) {
    PendO<W> po;
    po.clear();
#pragma unroll 1
    do {
        TS(W, 0);
        if (W == 0) TS_ITEM(e);
        e = qa_item<W>(P, e, sb, r, phm, po, it);
        TS(W, 31);
        it++;
    } while (IT_TYPE(e) == IT_QA);
    po.verdict(P, sb, it - 1);
    po.template step<0>(sb);
    po.template step<1>(sb);
    po.template step<2>(sb);
    po.template step<3>(sb);
    po.template step<4>(sb);
    return e;
}

__device__ __forceinline__ void consumer(const Params& P, uint32_t W, uint32_t sb, uint32_t dl) {
    int it = 0;
    if (W == 0) TS(0, 30);
    Ring r{0, 0, dl};
    uint32_t phm = 0;
    uint32_t e = get_item_warp(sb, 0, dl);
#pragma unroll 1
    while (e != 0) {
        if (IT_TYPE(e) == IT_QA) {
            e = W == 0 ? qa_run<0>(P, e, sb, r, phm, it) : qa_run<1>(P, e, sb, r, phm, it);
        } else {
            TS(W, 0);
            if (W == 0) TS_ITEM(e);
            if (IT_TYPE(e) == IT_ON) on_item(W, e, sb, r, phm);
            else if (W == 0) op_item<true>(e, sb, r, phm);
            else op_item<false>(e, sb, r, phm);
            TS(W, 31);
            e = get_item_warp(sb, ++it, dl);
        }
    }
    TS_DUMP(W);
}

__global__ void __cluster_dims__(2, 1, 1) __launch_bounds__(384, 1) fused_kernel(const __grid_constant__ Params P) {
    extern __shared__ __align__(1024) unsigned char smem_raw[];
    const uint32_t sb = (uint32_t)__cvta_generic_to_shared(smem_raw);
    const uint32_t wgid = __shfl_sync(0xffffffffu, threadIdx.x >> 7, 0);
    const uint32_t cta = blockIdx.x;
    const uint32_t dl = deadline();

    if (threadIdx.x == 128) {
#pragma unroll
        for (int i = 0; i < NSLOT; i++) {
            mbar_init(sb + BAR_RFULL + i * 8, 1);
            mbar_init(sb + BAR_REMPTY + i * 8, 8);
            mbar_init(sb + BAR_XFULL + i * 8, 1);
            mbar_init(sb + BAR_XEMPTY + i * 8, 8);
        }
        asm volatile("fence.mbarrier_init.release.cluster;" ::: "memory");
        fence_async_smem();
    } else if (threadIdx.x == 160) {
#pragma unroll
        for (int i = 0; i < NSLOT + MAXI; i++) mbar_init(sb + BAR_PRDY + i * 8, 1);
        asm volatile("fence.mbarrier_init.release.cluster;" ::: "memory");
    } else if (threadIdx.x == 0) {
        sts_u(sb + OFF_ITEM, P.cl[cta >> 1].items[0] ? P.cl[cta >> 1].items[0] + 8 * (cta & 1) : 0);
        sts_u(sb + OFF_FB, P.cl[cta >> 1].delay);
    } else if (threadIdx.x == 64) {
        if (sb & 1023) __trap();
        asm volatile("prefetch.tensormap [%0];" ::"l"(&P.wq[0]) : "memory");
        asm volatile("prefetch.tensormap [%0];" ::"l"(&P.x[0]) : "memory");
    }
    __syncthreads();
    asm volatile("barrier.cluster.arrive.relaxed.aligned;" ::: "memory");

    if (wgid == 0) {
        asm volatile("setmaxnreg.dec.sync.aligned.u32 24;");
        const uint32_t warp = __shfl_sync(0xffffffffu, threadIdx.x >> 5, 0);
        if (warp == 0) {
            const bool lead = threadIdx.x == 0;
            const uint64_t pol_first = mkpol<1>(), pol_norm = mkpol<POL_W>();
            uint32_t e = __shfl_sync(0xffffffffu, lds_u(sb + OFF_ITEM), 0);
            {
                const uint32_t d = lds_u(sb + OFF_FB);
                uint32_t t0, t1;
                asm volatile("mov.u32 %0, %%clock;" : "=r"(t0));
                do {
                    asm volatile("mov.u32 %0, %%clock;" : "=r"(t1));
                } while (t1 - t0 < d);
                __syncwarp();
            }
            if (lead) asm volatile("mbarrier.arrive.shared::cta.b64 _, [%0];" ::"r"(sb + BAR_ITEM) : "memory");
#pragma unroll 1
            for (int n = 0; n < (e ? NSLOT : 0); n++) {
                if (lead) {
                    mbar_expect(sb + BAR_RFULL + n * 8, SLOT);
                    tma3(sb + OFF_RING + n * SLOT, &P.wq[0], n * 64, IT_H0(e) * 3, sb + BAR_RFULL + n * 8, pol_norm);
                    mbar_expect(sb + BAR_XFULL + n * 8, XS);
                    tma3(sb + OFF_R + n * XS, &P.x[0], IT_B(e) * 160, n, sb + BAR_XFULL + n * 8, pol_norm);
                    tma3(sb + OFF_RING + n * SLOT + SLOT / 2, &P.wq[0], n * 64 + 32, IT_H0(e) * 3, sb + BAR_RFULL + n * 8, pol_norm);
                }
            }
            __syncwarp();
            asm volatile("barrier.cluster.wait.aligned;" ::: "memory");
            unsigned int* const ticket = &g_ticket[next_epoch(0) & 1];
            const uint32_t rank = cta & 1;
            uint32_t peer;
            asm volatile("mapa.shared::cluster.u32 %0, %1, %2;" : "=r"(peer) : "r"(sb), "r"(rank ^ 1));
            Ring r{0, 0, dl};
            uint32_t pm = 0;
            auto load_w = [&](const CUtensorMap* m, int row, int blk, uint32_t half_bytes) {
                mbar_wait(sb + BAR_REMPTY + r.slot * 8, r.ph, dl);
                if (lead) {
                    mbar_expect(sb + BAR_RFULL + r.slot * 8, 2 * half_bytes);
                    asm volatile("mbarrier.arrive.shared::cluster.b64 _, [%0];" ::"r"(peer + BAR_PRDY + r.slot * 8) : "memory");
                }
                mbar_wait(sb + BAR_PRDY + r.slot * 8, (pm >> r.slot) & 1, dl);
                pm ^= 1u << r.slot;
                if (lead) tma3_mc(sb + OFF_RING + r.slot * SLOT + rank * half_bytes, m, row, blk, sb + BAR_RFULL + r.slot * 8, pol_norm);
                r.adv(1);
            };
#pragma unroll 1
            for (int it = 0; e != 0; it++) {
                uint32_t nx = 0, tk = 0;
                if (rank == 0 && IT_TYPE(e) != IT_ON && it + 2 < MAXI) nx = it + 1 < NSTAT ? P.cl[cta >> 1].items[it + 1] : IT_DYN;
                const uint32_t br = IT_BR(e);
                if (IT_TYPE(e) == IT_QA) {
                    const uint32_t h = IT_H0(e);
#pragma unroll 1
                    for (int kk = it ? 0 : NSLOT; kk < 10; kk++) load_w(&P.wq[br], kk * 64 + rank * 32, h * 3, SLOT / 2);
                    const int row0 = (IT_B(e) * 32 + h) * 512;
#pragma unroll 1
                    for (int n = 0; n < 16; n++) {
                        if (n == 13 && nx == IT_DYN && lead) tk = atomicAdd(ticket, 1);
                        const bool isv = n == 15 || (n > 0 && !(n & 1));
                        const int j = n == 15 ? 7 : isv ? (n - 2) >> 1 : (n + 1) >> 1;
                        mbar_wait(sb + BAR_REMPTY + r.slot * 8, r.ph, dl);
                        if (lead) {
                            mbar_expect(sb + BAR_RFULL + r.slot * 8, SLOT);
                            tma3(sb + OFF_RING + r.slot * SLOT, isv ? &P.v[br] : &P.k[br], row0 + j * 64, 0,
                                 sb + BAR_RFULL + r.slot * 8, pol_first);
                        }
                        r.adv(1);
                    }
                } else {
                    const bool wide = IT_TYPE(e) == IT_OP;
                    const int step = wide ? 32 : 64, r1 = IT_H1(e) * 192;
#pragma unroll 1
                    for (int row = IT_H0(e) * 192 + rank * (step >> 1); row < r1; row += step)
                        load_w(wide ? &P.wo[br] : &P.won[br], row, IT_HALF(e) * (wide ? 5 : 2), wide ? XS / 2 : 8192);
                    if (nx == IT_DYN && lead) tk = atomicAdd(ticket, 1);
                }
                if (rank == 0) {
                    if (nx == IT_DYN) {
                        tk = __shfl_sync(0xffffffffu, tk, 0);
                        nx = tk < P.nlist ? P.list[tk] : 0;
                    }
                    e = nx;
                    if (lead) {
                        asm volatile("st.async.weak.shared::cluster.mbarrier::complete_tx::bytes.b32 [%0], %1, [%2];" ::"r"(
                                         peer + OFF_ITEM + 4 + it * 4),
                                     "r"(e ? e + 8 : 0), "r"(peer + BAR_ITEM + 8 + it * 8)
                                     : "memory");
                        sts_u(sb + OFF_ITEM + 4 + it * 4, e);
                        asm volatile("mbarrier.arrive.shared::cta.b64 _, [%0];" ::"r"(sb + BAR_ITEM + 8 + it * 8) : "memory");
                    }
                } else {
                    if (lead) mbar_expect(sb + BAR_ITEM + 8 + it * 8, 4);
                    e = get_item_warp(sb, it + 1, dl);
                }
            }
        } else if (warp == 1) {
            const uint64_t pol_norm = mkpol<POL_X>(), pol_o = mkpol<POL_O>();
            const bool lead = threadIdx.x == 32;
            uint32_t phm = 0, epoch = 0;
#pragma unroll 1
            for (int it = 0;; it++) {
                const uint32_t e = get_item_warp(sb, it, dl);
                if (it == 1 || (it == 0 && e == 0)) epoch = next_epoch(1);
                if (e == 0) break;
                const uint32_t br = IT_BR(e);
                uint32_t xs = 0;
                auto acquire = [&]() {
                    mbar_wait(sb + BAR_XEMPTY + xs * 8, (phm >> xs) & 1, dl);
                    phm ^= 1u << xs;
                    if (lead) mbar_expect(sb + BAR_XFULL + xs * 8, XS);
                };
                if (IT_TYPE(e) == IT_QA) {
#pragma unroll 1
                    for (int kk = it ? 0 : 5; kk < 10; kk++) {
                        acquire();
                        if (lead) tma3(sb + OFF_R + xs * XS, &P.x[br], IT_B(e) * 160, kk, sb + BAR_XFULL + xs * 8, pol_norm);
                        if (++xs == 5) xs = 0;
                    }
                } else {
                    const unsigned int* fp = g_flag + (br * 16 + IT_B(e)) * 64 + (threadIdx.x & 31);
                    uint32_t hm = 0, pm = 0;
                    auto poll = [&](uint32_t hneed, uint32_t pneed) {
                        if ((hm & hneed) == hneed && (pm & pneed) == pneed) return;
                        uint32_t n = 0;
                        do {
                            uint32_t a, b;
                            asm volatile("ld.acquire.gpu.global.u32 %0, [%2];\nld.acquire.gpu.global.u32 %1, [%2+128];"
                                         : "=r"(a), "=r"(b) : "l"(fp) : "memory");
                            hm = __ballot_sync(0xffffffffu, a == epoch);
                            pm = __ballot_sync(0xffffffffu, b == epoch);
                            if (++n > 0x1000000) __trap();
                        } while ((hm & hneed) != hneed || (pm & pneed) != pneed);
                        __syncwarp();
                        asm volatile("fence.proxy.async;" ::: "memory");
                    };
#pragma unroll 1
                    for (uint32_t h = IT_H0(e); h < IT_H1(e); h++) {
                        poll(1u << h, 0);
                        const unsigned char* src = ostash(P.slot[br * 32 + h], IT_B(e));
#pragma unroll 1
                        for (int t = 0; t < 3; t++) {
                            acquire();
                            if (lead) bulk_load(sb + OFF_R + xs * XS, src + t * XS, XS, sb + BAR_XFULL + xs * 8, pol_o);
                            if (++xs == 5) xs = 0;
                        }
                        if (IT_TYPE(e) == IT_OP && h >= 1) {
                            const uint32_t x1 = xs == 4 ? 0 : xs + 1;
                            mbar_wait(sb + BAR_XFULL + xs * 8, (phm >> xs) & 1, dl);
                            mbar_wait(sb + BAR_XFULL + x1 * 8, (phm >> x1) & 1, dl);
                            if (lead)
                                asm volatile("st.relaxed.gpu.global.u32 [%0], %1;" ::"l"(fp + 34 + IT_HALF(e)), "r"(epoch * 64 + h) : "memory");
                        }
                    }
                    if (IT_TYPE(e) == IT_ON) {
                        poll(0, IT_HALF(e) < 2 ? 1 : IT_HALF(e) == 2 ? 3 : 2);
#pragma unroll 1
                        for (uint32_t tile = 2 * IT_HALF(e); tile < 2 * IT_HALF(e) + 2; tile++) {
                            acquire();
                            if (lead)
                                asm volatile(
                                    "cp.async.bulk.tensor.5d.shared::cluster.global.mbarrier::complete_tx::bytes [%0], [%1, {%3,%5,%5,%5,%4}], [%2];" ::"r"(
                                        sb + OFF_R + xs * XS),
                                    "l"(&P.out), "r"(sb + BAR_XFULL + xs * 8), "r"(br * 640 + tile * 64), "r"(IT_B(e) * 5), "r"(0)
                                    : "memory");
                            if (++xs == 5) xs = 0;
                        }
                    }
                }
            }
        } else if (warp == 2) {
            asm volatile("barrier.cluster.wait.aligned;" ::: "memory");
            const uint32_t epoch = next_epoch(2);
            if (cta == 0) g_ticket[(epoch + 1) & 1] = 0;
#pragma unroll 1
            for (int it = 0;; it++) {
                const uint32_t e = get_item_warp(sb, it, dl);
                if (e == 0) break;
                nb_sync<NB_ODONE, 288>();
                if (threadIdx.x == 64) {
                    const uint32_t bb = IT_BR(e) * 16 + IT_B(e);
                    if (IT_TYPE(e) != IT_QA) {
                        const bool wide = IT_TYPE(e) == IT_OP;
                        if (wide)
                            asm volatile("st.relaxed.gpu.global.u32 [%0], %1;" ::"l"(&g_flag[bb * 64 + 34 + IT_HALF(e)]),
                                         "r"(epoch * 64 + IT_H1(e))
                                         : "memory");
                        const int cc0 = IT_BR(e) * 640 + IT_HALF(e) * (wide ? 320 : 128);
                        uint32_t xs = wide ? 0 : (3 * (IT_H1(e) - IT_H0(e))) % 5;
#pragma unroll 1
                        for (int m = 0; m < (wide ? 5 : 2); m++) {
                            asm volatile("cp.async.bulk.tensor.5d.global.shared::cta.bulk_group [%0, {%2,%4,%4,%4,%3}], [%1];" ::"l"(&P.out),
                                         "r"(sb + OFF_R + xs * XS), "r"(cc0 + m * 64), "r"((int)IT_B(e) * 5), "r"(0)
                                         : "memory");
                            asm volatile("cp.async.bulk.commit_group;" ::: "memory");
                            if (++xs == 5) xs = 0;
                        }
                        if (wide) {
#define REL(N)                                                          \
    asm volatile("cp.async.bulk.wait_group.read %0;" ::"n"(4 - N) : "memory"); \
    asm volatile("mbarrier.arrive.shared::cta.b64 _, [%0], 8;" ::"r"(sb + BAR_XEMPTY + N * 8) : "memory");
                            REL(0) REL(1) REL(2) REL(3) REL(4)
#undef REL
                        }
                        if (IT_PART(e)) {
                            asm volatile("cp.async.bulk.wait_group 0;" ::: "memory");
                            asm volatile("fence.proxy.async;" ::: "memory");
                        }
                    }
                    if (IT_TYPE(e) == IT_QA || IT_PART(e)) {
                        unsigned int* f = &g_flag[bb * 64 + (IT_TYPE(e) == IT_QA ? IT_H0(e) : 32 + IT_HALF(e))];
                        asm volatile("st.release.gpu.global.u32 [%0], %1;" ::"l"(f), "r"(epoch) : "memory");
                    }
                }
                __syncwarp();
            }
            if (threadIdx.x == 64) asm volatile("cp.async.bulk.wait_group 0;" ::: "memory");
            __syncwarp();
            asm volatile("barrier.cluster.arrive.relaxed.aligned;\nbarrier.cluster.wait.aligned;" ::: "memory");
        } else {
            const uint32_t lane = threadIdx.x & 31, p = lane >> 2;
            const uint32_t epoch = next_epoch(3);
#pragma unroll 1
            for (int it = 0;; it++) {
                const uint32_t e = get_item_warp(sb, it, dl);
                if (e == 0) break;
                if (IT_TYPE(e) != IT_QA) continue;
                nb_sync<NB_QK, 160>();
                const uint32_t co = (((lane & 3) * 2) ^ p) << 4;
                const uint32_t ka = sb + OFF_RING + lds_u(sb + OFF_GM + 4) * SLOT + p * (9 * 128) + co;
                const uint32_t qa = sb + OFF_R + p * 128 + co;
                uint32_t acc = 0;
#pragma unroll 1
                for (int c = 0; c < 3; c++) {
                    if (c == 2) nb_sync<NB_L, 160>();
                    const uint4 k0 = lds_u4(ka + c * 8192), q0 = lds_u4(qa + c * XS);
                    acc = fma_bf2(k0.x, q0.x, fma_bf2(k0.y, q0.y, fma_bf2(k0.z, q0.z, fma_bf2(k0.w, q0.w, acc))));
                    const uint4 k1 = lds_u4((ka + c * 8192) ^ 16), q1 = lds_u4((qa + c * XS) ^ 16);
                    acc = fma_bf2(k1.x, q1.x, fma_bf2(k1.y, q1.y, fma_bf2(k1.z, q1.z, fma_bf2(k1.w, q1.w, acc))));
                }
                float d = __uint_as_float(acc << 16) + __uint_as_float(acc & 0xffff0000u);
                d += __shfl_xor_sync(0xffffffffu, d, 1);
                d += __shfl_xor_sync(0xffffffffu, d, 2);
                int key = __float_as_int(d);
                key ^= (key >> 31) & 0x7fffffff;
                key = __reduce_max_sync(0xffffffffu, key);
                key ^= (key >> 31) & 0x7fffffff;
                sts_f(sb + OFF_GM, __int_as_float(key) * SM_C);
                nb_arrive<NB_REF, 160>();
                if (IT_DEP(e)) {
                    const uint32_t g = IT_DEP(e) - 1, need = epoch * 64 + (g & 31) + 1;
                    const unsigned int* cp = &g_flag[((g >> 5) * 16 + IT_B(e)) * 64 + 34 + (lane & 1)];
                    for (uint32_t n = 0;; n++) {
                        uint32_t v;
                        asm volatile("ld.acquire.gpu.global.u32 %0, [%1];" : "=r"(v) : "l"(cp) : "memory");
                        if (__all_sync(0xffffffffu, v - need < 64)) break;
                        if (n > 0x800000) __trap();
                        __nanosleep(500);
                    }
                }
                nb_sync<NB_L, 160>();
                bool bad = false;
#pragma unroll
                for (int c = 0; c < 5; c++) {
                    const uint32_t la = sb + OFF_LX + (c * 32 + lane) * 4;
                    const float v = (__uint_as_float(lds_u(la)) + __uint_as_float(lds_u(la + 640))) +
                                    (__uint_as_float(lds_u(la + 1280)) + __uint_as_float(lds_u(la + 1920)));
                    const float inv = __fdividef(1.f, v);
                    const uint32_t hi = pack_bf16(inv, 0.f), lo = pack_bf16(inv - __uint_as_float(hi << 16), 0.f);
                    const uint32_t ia = sb + OFF_LINV + c * 128 + ((lane >> 1) & 3) * 32 + (lane >> 3) * 8 + (lane & 1) * 2;
                    asm volatile("st.shared.u16 [%0], %1;\nst.shared.u16 [%0+4], %2;" ::"r"(ia), "h"((unsigned short)hi), "h"((unsigned short)lo) : "memory");
                    bad |= !(v >= 5.421010862e-20f && v <= 1.8446744e19f);
                }
                sts_u(sb + OFF_FB, __any_sync(0xffffffffu, bad));
                nb_arrive<NB_VOTE, 160>();
                nb_arrive<NB_VOTE + 1, 160>();
            }
        }
    } else {
        asm volatile("setmaxnreg.inc.sync.aligned.u32 240;");
        consumer(P, wgid - 1, sb, dl);
    }
}

typedef CUresult (*EncFn)(CUtensorMap*, CUtensorMapDataType, cuuint32_t, void*, const cuuint64_t*, const cuuint64_t*,
                          const cuuint32_t*, const cuuint32_t*, CUtensorMapInterleave, CUtensorMapSwizzle,
                          CUtensorMapL2promotion, CUtensorMapFloatOOBfill);

void make_map3(EncFn enc, CUtensorMap* m, void* p, uint64_t rows, uint64_t rowbytes, uint64_t nblk, uint32_t boxrows,
               uint32_t boxblk) {
    cuuint64_t dims[3] = {64, rows, nblk};
    cuuint64_t str[2] = {rowbytes, 128};
    cuuint32_t box[3] = {64, boxrows, boxblk};
    cuuint32_t es[3] = {1, 1, 1};
    enc(m, CU_TENSOR_MAP_DATA_TYPE_BFLOAT16, 3, p, dims, str, box, es, CU_TENSOR_MAP_INTERLEAVE_NONE,
        CU_TENSOR_MAP_SWIZZLE_128B, CU_TENSOR_MAP_L2_PROMOTION_NONE, CU_TENSOR_MAP_FLOAT_OOB_FILL_NONE);
}

constexpr int tune(const char*, int def) { return def; }

void build_schedule(Params& P) {
    const int mode = tune("MODE", 4), dmax = tune("DMAX", 24900), n0 = tune("N0", 8);
    const int H0[8] = {20, 20, 22, 22, 22, 24, 25, 25}, P0[8] = {352, 352, 344, 348, 352, 345, 333, 336};
    const int ng = tune("NG", 0), d0 = tune("D0", 0), nkeep = tune("NKEEP", 0), odmax = tune("ODMAX", 2000);
    const int ong = tune("ONG", 0), od0 = tune("OD0", 0), jit = tune("JIT", 0);
    const int npos = tune("NPOS", 0), nearly = tune("NEARLY", 0);
    const int ra = tune("RA", 10), ga = tune("GA", 32), rb = tune("RB", 12), g1 = tune("G1", 58);
    int dep[64];
    for (int g = 0, ns = 0, live = 0; g < 64; g++) {
        const bool fresh = mode < 3 || g >= g1 || live < (g < ga ? ra : rb);
        dep[g] = fresh ? 0 : g - live + 1;
        P.slot[g] = fresh ? ns++ : P.slot[g - live];
        live += fresh;
    }
    int u = 0;
    auto unit = [&]() {
        const uint32_t e = mk_item(IT_QA, u >> 8, (u & 7) * 2, (u >> 3) & 31, P.slot[u >> 3], 0) | (dep[u >> 3] << 23);
        u++;
        return e;
    };
    int qa[NCL], nq = 0, op[NCL], no = 0;
    for (int c = 0; c < NCL; c++) {
        P.cl[c].delay = 0;
        for (int i = 0; i < NSTAT; i++) P.cl[c].items[i] = 0;
        if (mode >= 3 && c < 64 && (c & 3) == 3) op[no++] = c;
        else if (mode != 2 || (c & 3) == 0) qa[nq++] = c;
    }
    for (int t = 0; t < no; t++) {
        P.cl[op[t]].items[1] = mk_item(IT_OP, 0, t & ~1, 0, 32, t & 1);
        P.cl[op[t]].items[2] = IT_DYN;
        P.cl[op[t]].delay = ong ? od0 + (t * ong / 16) * (odmax / ong) : od0 + t * odmax / 16;
    }
    for (int k = 0; k < nq; k++) {
        const int c = qa[(k * 19) % nq];
        P.cl[c].items[1] = P.cl[c].items[2] = IT_DYN;
        P.cl[c].delay = k < n0 ? 0 : (int)((long long)dmax * (k + 1 - n0) / (nq - n0));
        if (ng) P.cl[c].delay = d0 + (k * ng / nq) * (dmax / ng) + (k * ng % nq) * jit / nq;
    }
    if (tune("OFIRST", 0))
        for (int t = 0; t < no; t++) P.cl[op[t]].items[0] = unit();
    for (int k = u; k < no + nq; k++) {
        int best = -1;
        for (int c = 0; c < NCL; c++)
            if (P.cl[c].items[1] && !P.cl[c].items[0] && (best < 0 || P.cl[c].delay < P.cl[best].delay)) best = c;
        P.cl[best].items[0] = unit();
    }
    int H[8], pos[8];
    for (int b = 0; b < 8; b++) {
        char nh[3] = {'H', (char)('0' + b), 0}, np[3] = {'P', (char)('0' + b), 0};
        H[b] = tune(nh, H0[b]);
        pos[b] = tune(np, P0[b]);
        for (int g = 0; g < 64; g++)
            if (dep[g] > 32) {
                if (pos[b] > 8 * g) pos[b] = 8 * g;
                if (H[b] < dep[g] - 32) H[b] = dep[g] - 32;
            }
        if (b < nkeep && no) {
            pos[b] = -1;
            P.cl[op[14 - 2 * b]].items[2] = mk_item(IT_OP, 1, 2 * b, 0, H[b], 0, 1);
            P.cl[op[15 - 2 * b]].items[2] = mk_item(IT_OP, 1, 2 * b, 0, H[b], 1, 1);
        }
    }
    int n = 0, kn = 0;
    const int uend = mode == 2 ? 8 * nq : 512;
    while (u < uend) {
        for (int b = 0; b < 8 && no; b++)
            if (pos[b] == u) {
                P.list[n++] = mk_item(IT_OP, 1, 2 * b, 0, H[b], 0, 1);
                P.list[n++] = mk_item(IT_OP, 1, 2 * b, 0, H[b], 1, 1);
            }
        while (no && u >= uend - npos && kn * npos < (u + 1 - (uend - npos)) * nearly) {
            P.list[n++] = mk_item(IT_ON, 1, kn / 5 * 2, H[kn / 5], 32, kn % 5);
            kn++;
        }
        P.list[n++] = unit();
    }
    for (; no && kn < 40; kn++) P.list[n++] = mk_item(IT_ON, 1, kn / 5 * 2, H[kn / 5], 32, kn % 5);
    P.nlist = n;
}

}

extern "C" void kernel_launch(void* const* d_in, const int* in_sizes, int n_in, void* d_out, int out_size) {
    static Params P;
    static bool init = false;
    if (!init) {
        EncFn enc = nullptr;
        cudaDriverEntryPointQueryResult qr;
        cudaGetDriverEntryPoint("cuTensorMapEncodeTiled", (void**)&enc, cudaEnableDefault, &qr);
        for (int i = 0; i < 2; i++) {
            P.px[i] = (const __nv_bfloat16*)d_in[5 * i + 0];
            P.pk[i] = (const __nv_bfloat16*)d_in[5 * i + 1];
            P.pv[i] = (const __nv_bfloat16*)d_in[5 * i + 2];
            P.pwq[i] = (const __nv_bfloat16*)d_in[5 * i + 3];
            make_map3(enc, &P.x[i], d_in[5 * i + 0], 2560, 1280, 10, 160, 1);
            make_map3(enc, &P.k[i], d_in[5 * i + 1], 16 * 32 * 512, 384, 3, 64, 3);
            make_map3(enc, &P.v[i], d_in[5 * i + 2], 16 * 32 * 512, 384, 3, 64, 3);
            make_map3(enc, &P.wq[i], d_in[5 * i + 3], 640, 12288, 96, 32, 3);
            make_map3(enc, &P.wo[i], d_in[5 * i + 4], 6144, 1280, 10, 16, 5);
            make_map3(enc, &P.won[i], d_in[5 * i + 4], 6144, 1280, 10, 32, 2);
        }
        cuuint64_t dims[5] = {1280, 2, 4, 4, 80};
        cuuint64_t str[4] = {2560, 8 * 2560, 2 * 2560, 32 * 2560};
        cuuint32_t box[5] = {64, 2, 4, 4, 5};
        cuuint32_t es[5] = {1, 1, 1, 1, 1};
        enc(&P.out, CU_TENSOR_MAP_DATA_TYPE_BFLOAT16, 5, d_out, dims, str, box, es, CU_TENSOR_MAP_INTERLEAVE_NONE,
            CU_TENSOR_MAP_SWIZZLE_128B, CU_TENSOR_MAP_L2_PROMOTION_NONE, CU_TENSOR_MAP_FLOAT_OOB_FILL_NONE);
        build_schedule(P);
        cudaFuncSetAttribute(fused_kernel, cudaFuncAttributeMaxDynamicSharedMemorySize, SMEM_LAUNCH);
        init = true;
    }
    fused_kernel<<<NCTA, 384, SMEM_LAUNCH>>>(P);
}
```

```cpp
#include <cuda_runtime.h>
#include <cuda.h>
#include <cuda_bf16.h>
#include <stdint.h>

namespace {

constexpr int NCTA = 132;
constexpr int NCL = NCTA / 2;
constexpr int MAXI = 16;
constexpr int NSTAT = 3;
constexpr uint32_t IT_DYN = 0xffffffffu;
constexpr int SLOT = 24576;
constexpr int NSLOT = 5;
constexpr int XS = 20480;
constexpr int OFF_R = 0;
constexpr int OFF_RING = 5 * XS;
constexpr int OFF_MISC = OFF_RING + NSLOT * SLOT;
constexpr int OFF_LX = OFF_MISC;
constexpr int OFF_LINV = OFF_LX + 2560;
constexpr int OFF_FB = OFF_LINV + 640;
constexpr int OFF_GM = OFF_FB + 16;
constexpr int OFF_BAR = OFF_GM + 16;
constexpr int BAR_RFULL = OFF_BAR;
constexpr int BAR_REMPTY = BAR_RFULL + 40;
constexpr int BAR_XFULL = BAR_REMPTY + 40;
constexpr int BAR_XEMPTY = BAR_XFULL + 40;
constexpr int BAR_PRDY = BAR_XEMPTY + 40;
constexpr int BAR_ITEM = BAR_PRDY + 40;
constexpr int OFF_ITEM = BAR_ITEM + MAXI * 8;
constexpr int SMEM_BYTES = OFF_ITEM + MAXI * 4;
static_assert(SMEM_BYTES <= 232448, "smem");

constexpr int NB_W = 1  , NB_PFULL = 3  , NB_VOTE = 5  , NB_Q2 = 7, NB_SDONE = 8, NB_PDONE = 9,
              NB_L = 10, NB_REF = 11, NB_ODONE = 12, NB_OPEND = 13, NB_LX = 14, NB_Q01 = 15, NB_QK = 0  ;

constexpr uint32_t IT_QA = 1, IT_OP = 2, IT_ON = 3;
__host__ __device__ constexpr uint32_t mk_item(uint32_t type, uint32_t br, uint32_t b, uint32_t h0, uint32_t h1, uint32_t half,
                                               uint32_t part = 0) {
    return type | (br << 2) | (b << 3) | (h0 << 7) | (h1 << 13) | (half << 19) | (part << 22);
}
#define IT_TYPE(e) ((e) & 3u)
#define IT_BR(e) (((e) >> 2) & 1u)
#define IT_B(e) (((e) >> 3) & 15u)
#define IT_H0(e) (((e) >> 7) & 63u)
#define IT_H1(e) (((e) >> 13) & 63u)
#define IT_HALF(e) (((e) >> 19) & 7u)
#define IT_PART(e) (((e) >> 22) & 1u)
#define IT_SLOT(e) IT_H1(e)
#define IT_DEP(e) (((e) >> 23) & 127u)

struct Params {
    CUtensorMap x[2], wq[2], k[2], v[2], wo[2], won[2], out;
    const __nv_bfloat16 *px[2], *pwq[2], *pk[2], *pv[2];
    struct alignas(16) { uint32_t delay, items[NSTAT]; } cl[NCL];
    uint32_t nlist;
    uint8_t slot[64];
    uint32_t list[512];
};

constexpr int OUNIT = 61440;
__device__ __align__(1024) unsigned char g_ostash[(size_t)1024 * OUNIT];
__device__ unsigned int g_flag[32 * 64];
__device__ __forceinline__ unsigned char* ostash(uint32_t slot, uint32_t b) { return g_ostash + (slot * 16 + b) * OUNIT; }
__device__ unsigned int g_epoch[NCTA * 4];
__device__ unsigned int g_ticket[2];

constexpr int SMEM_LAUNCH = SMEM_BYTES;
#define TS(role, idx)
#define TS_ITEM(e)
#define TS_DUMP(role)
#define TSD(role, idx)

#define POL_W 2
#define POL_X 2
#define POL_O 2
template <int M>
__device__ __forceinline__ uint64_t mkpol() {
    uint64_t p;
    if (M == 0) asm volatile("createpolicy.fractional.L2::evict_normal.b64 %0, 1.0;" : "=l"(p));
    if (M == 1) asm volatile("createpolicy.fractional.L2::evict_first.b64 %0, 1.0;" : "=l"(p));
    if (M == 2) asm volatile("createpolicy.fractional.L2::evict_unchanged.b64 %0, 1.0;" : "=l"(p));
    if (M == 3) asm volatile("createpolicy.fractional.L2::evict_normal.L2::evict_unchanged.b64 %0, 0.25;" : "=l"(p));
    return p;
}
#define STSM_W 1
#define LASTORD 0
#define XLATE 2
#define PV0FIRST 1
#define QST0 1
#define QST1 2
#define QHOLD 8
constexpr float SM_C = 0.07216878364870322f * 1.4426950408889634f;

__device__ __forceinline__ uint32_t next_epoch(int warp) {
    unsigned int* p = &g_epoch[blockIdx.x * 4 + warp];
    const uint32_t e = __ldcg(p) + 1;
    *p = e;
    return e;
}

__device__ __forceinline__ uint32_t tid_now() {
    uint32_t t;
    asm volatile("mov.u32 %0, %%tid.x;" : "=r"(t));
    return t;
}
__device__ __forceinline__ void mbar_init(uint32_t a, uint32_t c) {
    asm volatile("mbarrier.init.shared::cta.b64 [%0], %1;" ::"r"(a), "r"(c) : "memory");
}
__device__ __forceinline__ void mbar_expect(uint32_t a, uint32_t b) {
    asm volatile("mbarrier.arrive.expect_tx.shared::cta.b64 _, [%0], %1;" ::"r"(a), "r"(b) : "memory");
}
template <int CNT = 1>
__device__ __forceinline__ void mbar_arrive_warp(uint32_t a) {
    if (CNT == 1)
        asm volatile("{\n.reg .pred p;\nelect.sync _|p, 0xffffffff;\n@p mbarrier.arrive.shared::cta.b64 _, [%0];\n}" ::"r"(a) : "memory");
    else
        asm volatile(
            "{\n.reg .pred p;\nelect.sync _|p, 0xffffffff;\n@p mbarrier.arrive.shared::cta.b64 _, [%0];\n"
            "@p mbarrier.arrive.shared::cta.b64 _, [%0];\n}" ::"r"(a)
            : "memory");
}
template <int CNT = 1>
__device__ __forceinline__ void mbar_arrive_warp_if(uint32_t a, bool cond) {
    if (CNT == 1)
        asm volatile(
            "{\n.reg .pred p, c;\nelect.sync _|p, 0xffffffff;\nsetp.ne.and.u32 c, %1, 0, p;\n"
            "@c mbarrier.arrive.shared::cta.b64 _, [%0];\n}" ::"r"(a), "r"((uint32_t)cond)
            : "memory");
    else
        asm volatile(
            "{\n.reg .pred p, c;\nelect.sync _|p, 0xffffffff;\nsetp.ne.and.u32 c, %1, 0, p;\n"
            "@c mbarrier.arrive.shared::cta.b64 _, [%0];\n@c mbarrier.arrive.shared::cta.b64 _, [%0];\n}" ::"r"(a), "r"((uint32_t)cond)
            : "memory");
}
__device__ __forceinline__ uint32_t deadline() {
    uint32_t c;
    asm volatile("mov.u32 %0, %%clock_hi;" : "=r"(c));
    return c + 4;
}
__device__ __forceinline__ void mbar_wait(uint32_t a, uint32_t ph, uint32_t dl) {
    asm volatile(
        "{\n.reg .pred p;\n.reg .u32 m;\n"
        "LOOP:\n"
        "mbarrier.try_wait.parity.shared::cta.b64 p, [%0], %1;\n"
        "@p bra DONE;\n"
        "mov.u32 m, %%clock_hi;\n"
        "setp.ne.u32 p, m, %2;\n"
        "@p bra LOOP;\n"
        "trap;\n"
        "DONE:\n}" ::"r"(a), "r"(ph), "r"(dl)
        : "memory");
}
template <int ID, int CNT>
__device__ __forceinline__ void nb_sync() { asm volatile("bar.sync %0, %1;" ::"n"(ID), "n"(CNT) : "memory"); }
template <int ID, int CNT>
__device__ __forceinline__ void nb_arrive() { asm volatile("bar.arrive %0, %1;" ::"n"(ID), "n"(CNT) : "memory"); }
__device__ __forceinline__ void fence_async_smem() { asm volatile("fence.proxy.async.shared::cta;" ::: "memory"); }

__device__ __forceinline__ void tma3(uint32_t dst, const CUtensorMap* m, int c1, int c2, uint32_t bar, uint64_t pol) {
    asm volatile(
        "cp.async.bulk.tensor.3d.shared::cluster.global.mbarrier::complete_tx::bytes.L2::cache_hint [%0], [%1, {%3,%4,%5}], [%2], %6;" ::"r"(dst),
        "l"(m), "r"(bar), "r"(0), "r"(c1), "r"(c2), "l"(pol)
        : "memory");
}
__device__ __forceinline__ void tma3_mc(uint32_t dst, const CUtensorMap* m, int c1, int c2, uint32_t bar, uint64_t pol) {
    asm volatile(
        "cp.async.bulk.tensor.3d.shared::cluster.global.mbarrier::complete_tx::bytes.multicast::cluster.L2::cache_hint"
        " [%0], [%1, {%3,%4,%5}], [%2], %6, %7;" ::"r"(dst),
        "l"(m), "r"(bar), "r"(0), "r"(c1), "r"(c2), "h"((unsigned short)3), "l"(pol)
        : "memory");
}
__device__ __forceinline__ void bulk_load(uint32_t dst, const void* src, uint32_t bytes, uint32_t bar, uint64_t pol) {
    asm volatile("cp.async.bulk.shared::cluster.global.mbarrier::complete_tx::bytes.L2::cache_hint [%0], [%1], %2, [%3], %4;" ::"r"(dst),
                 "l"(src), "r"(bytes), "r"(bar), "l"(pol)
                 : "memory");
}
__device__ __forceinline__ void wg_fence() { asm volatile("wgmma.fence.sync.aligned;" ::: "memory"); }
__device__ __forceinline__ void wg_commit() { asm volatile("wgmma.commit_group.sync.aligned;" ::: "memory"); }
template <int N>
__device__ __forceinline__ void wg_wait() { asm volatile("wgmma.wait_group.sync.aligned %0;" ::"n"(N) : "memory"); }

#define RW80(c, d) c(d[0]), c(d[1]), c(d[2]), c(d[3]), c(d[4]), c(d[5]), c(d[6]), c(d[7]), c(d[8]), c(d[9]), c(d[10]), c(d[11]), c(d[12]), c(d[13]), c(d[14]), c(d[15]), c(d[16]), c(d[17]), c(d[18]), c(d[19]), c(d[20]), c(d[21]), c(d[22]), c(d[23]), c(d[24]), c(d[25]), c(d[26]), c(d[27]), c(d[28]), c(d[29]), c(d[30]), c(d[31]), c(d[32]), c(d[33]), c(d[34]), c(d[35]), c(d[36]), c(d[37]), c(d[38]), c(d[39]), c(d[40]), c(d[41]), c(d[42]), c(d[43]), c(d[44]), c(d[45]), c(d[46]), c(d[47]), c(d[48]), c(d[49]), c(d[50]), c(d[51]), c(d[52]), c(d[53]), c(d[54]), c(d[55]), c(d[56]), c(d[57]), c(d[58]), c(d[59]), c(d[60]), c(d[61]), c(d[62]), c(d[63]), c(d[64]), c(d[65]), c(d[66]), c(d[67]), c(d[68]), c(d[69]), c(d[70]), c(d[71]), c(d[72]), c(d[73]), c(d[74]), c(d[75]), c(d[76]), c(d[77]), c(d[78]), c(d[79])
#define RW48(c, d) c(d[0]), c(d[1]), c(d[2]), c(d[3]), c(d[4]), c(d[5]), c(d[6]), c(d[7]), c(d[8]), c(d[9]), c(d[10]), c(d[11]), c(d[12]), c(d[13]), c(d[14]), c(d[15]), c(d[16]), c(d[17]), c(d[18]), c(d[19]), c(d[20]), c(d[21]), c(d[22]), c(d[23]), c(d[24]), c(d[25]), c(d[26]), c(d[27]), c(d[28]), c(d[29]), c(d[30]), c(d[31]), c(d[32]), c(d[33]), c(d[34]), c(d[35]), c(d[36]), c(d[37]), c(d[38]), c(d[39]), c(d[40]), c(d[41]), c(d[42]), c(d[43]), c(d[44]), c(d[45]), c(d[46]), c(d[47])
#define RW32(c, d) c(d[0]), c(d[1]), c(d[2]), c(d[3]), c(d[4]), c(d[5]), c(d[6]), c(d[7]), c(d[8]), c(d[9]), c(d[10]), c(d[11]), c(d[12]), c(d[13]), c(d[14]), c(d[15]), c(d[16]), c(d[17]), c(d[18]), c(d[19]), c(d[20]), c(d[21]), c(d[22]), c(d[23]), c(d[24]), c(d[25]), c(d[26]), c(d[27]), c(d[28]), c(d[29]), c(d[30]), c(d[31])

__device__ __forceinline__ void reg_fence(float (&d)[80]) { asm volatile("" : RW80("+f", d)::"memory"); }
__device__ __forceinline__ void reg_fence(float (&d)[48]) { asm volatile("" : RW48("+f", d)::"memory"); }
__device__ __forceinline__ void reg_fence(float (&d)[32]) { asm volatile("" : RW32("+f", d)::"memory"); }

template <int NR>
__device__ __forceinline__ void zero(float (&d)[NR]) {
#pragma unroll
    for (int i = 0; i < NR; i++) d[i] = 0.f;
}

constexpr uint32_t HI_SW128 = (1024u >> 4) | (1u << 30);
constexpr uint32_t HI_OST = (2560u >> 4) | (2u << 30);
constexpr uint32_t LO_LBO1 = (1u << 16);
constexpr uint32_t LO_OST = ((512u >> 4) << 16);

template <int TA, int TB, uint32_t HIB, int ACC>
__device__ __forceinline__ void wgmma(float (&d)[80], uint32_t loA, uint32_t loB) {
#define WG_ASM(SD)                                                          \
    "{\n.reg .b64 da, db;\nmov.b64 da, {%80, %82};\nmov.b64 db, {%81, %83};\n" \
    "wgmma.mma_async.sync.aligned.m64n160k16.f32.bf16.bf16 "               \
    "{%0,%1,%2,%3,%4,%5,%6,%7,%8,%9,%10,%11,%12,%13,%14,%15,%16,%17,%18,%19,%20,%21,%22,%23,%24,%25,%26,%27,%28,%29,%30,%31,%32,%33,%34,%35,%36,%37,%38,%39,%40,%41,%42,%43,%44,%45,%46,%47,%48,%49,%50,%51,%52,%53,%54,%55,%56,%57,%58,%59,%60,%61,%62,%63,%64,%65,%66,%67,%68,%69,%70,%71,%72,%73,%74,%75,%76,%77,%78,%79}, da, db, " SD ", 1, 1, %84, %85;\n}"
    if constexpr (ACC == 2)
        asm volatile(WG_ASM("0") : RW80("+f", d) : "r"(loA), "r"(loB), "n"(HI_SW128), "n"(HIB), "n"(TA), "n"(TB));
    else if constexpr (ACC == 1)
        asm volatile(WG_ASM("1") : RW80("+f", d) : "r"(loA), "r"(loB), "n"(HI_SW128), "n"(HIB), "n"(TA), "n"(TB));
    else
        asm volatile(WG_ASM("0") : RW80("=f", d) : "r"(loA), "r"(loB), "n"(HI_SW128), "n"(HIB), "n"(TA), "n"(TB));
#undef WG_ASM
}
template <int TA, int TB, uint32_t HIB, int ACC>
__device__ __forceinline__ void wgmma(float (&d)[48], uint32_t loA, uint32_t loB) {
#define WG_ASM(SD)                                                          \
    "{\n.reg .b64 da, db;\nmov.b64 da, {%48, %50};\nmov.b64 db, {%49, %51};\n" \
    "wgmma.mma_async.sync.aligned.m64n96k16.f32.bf16.bf16 "               \
    "{%0,%1,%2,%3,%4,%5,%6,%7,%8,%9,%10,%11,%12,%13,%14,%15,%16,%17,%18,%19,%20,%21,%22,%23,%24,%25,%26,%27,%28,%29,%30,%31,%32,%33,%34,%35,%36,%37,%38,%39,%40,%41,%42,%43,%44,%45,%46,%47}, da, db, " SD ", 1, 1, %52, %53;\n}"
    if constexpr (ACC == 1)
        asm volatile(WG_ASM("1") : RW48("+f", d) : "r"(loA), "r"(loB), "n"(HI_SW128), "n"(HIB), "n"(TA), "n"(TB));
    else
        asm volatile(WG_ASM("0") : RW48("=f", d) : "r"(loA), "r"(loB), "n"(HI_SW128), "n"(HIB), "n"(TA), "n"(TB));
#undef WG_ASM
}
template <int TA, int TB, uint32_t HIB, int ACC>
__device__ __forceinline__ void wgmma(float (&d)[32], uint32_t loA, uint32_t loB) {
#define WG_ASM(SD)                                                          \
    "{\n.reg .b64 da, db;\nmov.b64 da, {%32, %34};\nmov.b64 db, {%33, %35};\n" \
    "wgmma.mma_async.sync.aligned.m64n64k16.f32.bf16.bf16 "               \
    "{%0,%1,%2,%3,%4,%5,%6,%7,%8,%9,%10,%11,%12,%13,%14,%15,%16,%17,%18,%19,%20,%21,%22,%23,%24,%25,%26,%27,%28,%29,%30,%31}, da, db, " SD ", 1, 1, %36, %37;\n}"
    if constexpr (ACC == 1)
        asm volatile(WG_ASM("1") : RW32("+f", d) : "r"(loA), "r"(loB), "n"(HI_SW128), "n"(HIB), "n"(TA), "n"(TB));
    else
        asm volatile(WG_ASM("0") : RW32("=f", d) : "r"(loA), "r"(loB), "n"(HI_SW128), "n"(HIB), "n"(TA), "n"(TB));
#undef WG_ASM
}

__device__ __forceinline__ uint32_t pack_bf16(float lo, float hi) {
    uint32_t r;
    asm("cvt.rn.bf16x2.f32 %0, %1, %2;" : "=r"(r) : "f"(hi), "f"(lo));
    return r;
}
__device__ __forceinline__ float ex2(float x) {
    float r;
    asm("ex2.approx.ftz.f32 %0, %1;" : "=f"(r) : "f"(x));
    return r;
}
__device__ __forceinline__ void stsm4t(uint32_t a, uint32_t r0, uint32_t r1, uint32_t r2, uint32_t r3) {
    asm volatile("stmatrix.sync.aligned.m8n8.x4.trans.shared.b16 [%0], {%1,%2,%3,%4};" ::"r"(a), "r"(r0), "r"(r1), "r"(r2), "r"(r3)
                 : "memory");
}
__device__ __forceinline__ uint32_t lds_u(uint32_t a) {
    uint32_t v;
    asm volatile("ld.shared.u32 %0, [%1];" : "=r"(v) : "r"(a) : "memory");
    return v;
}
__device__ __forceinline__ uint4 lds_u4(uint32_t a) {
    uint4 v;
    asm volatile("ld.shared.v4.u32 {%0,%1,%2,%3}, [%4];" : "=r"(v.x), "=r"(v.y), "=r"(v.z), "=r"(v.w) : "r"(a) : "memory");
    return v;
}
__device__ __forceinline__ float2 lds_f2(uint32_t a) {
    float2 v;
    asm volatile("ld.shared.v2.f32 {%0,%1}, [%2];" : "=f"(v.x), "=f"(v.y) : "r"(a) : "memory");
    return v;
}
__device__ __forceinline__ void sts_f(uint32_t a, float v) { asm volatile("st.shared.f32 [%0], %1;" ::"r"(a), "f"(v) : "memory"); }
__device__ __forceinline__ void sts_u(uint32_t a, uint32_t v) { asm volatile("st.shared.u32 [%0], %1;" ::"r"(a), "r"(v) : "memory"); }
__device__ __forceinline__ void sts_f2(uint32_t a, float x, float y) {
    asm volatile("st.shared.v2.f32 [%0], {%1,%2};" ::"r"(a), "f"(x), "f"(y) : "memory");
}

template <bool ADD = false, bool SIG = false, int NR>
__device__ __forceinline__ void store_tile_t(const float (&d)[NR], uint32_t addr) {
    uint32_t p[NR / 2];
    if (ADD) {
#pragma unroll
        for (int j = 0; j < NR / 8; j++)
            asm volatile("ldmatrix.sync.aligned.m8n8.x4.trans.shared.b16 {%0,%1,%2,%3}, [%4];"
                         : "=r"(p[4 * j]), "=r"(p[4 * j + 1]), "=r"(p[4 * j + 2]), "=r"(p[4 * j + 3])
                         : "r"(addr + j * 2048)
                         : "memory");
    }
#pragma unroll
    for (int k = 0; k < NR / 2; k++)
        p[k] = ADD ? pack_bf16(d[2 * k] + __uint_as_float(p[k] << 16), d[2 * k + 1] + __uint_as_float(p[k] & 0xffff0000u))
                   : pack_bf16(d[2 * k], d[2 * k + 1]);
#pragma unroll
    for (int j = 0; j < NR / 8; j++) {
        stsm4t(addr + j * 2048, p[4 * j], p[4 * j + 1], p[4 * j + 2], p[4 * j + 3]);
        if (SIG && j == 0) nb_arrive<NB_L, 160>();
    }
}

struct TrueT { static constexpr bool value = true; };
struct FalseT { static constexpr bool value = false; };

template <int V>
struct IntT { static constexpr int value = V; };

__device__ __forceinline__ uint32_t get_item(uint32_t sb, int it, uint32_t dl) {
    mbar_wait(sb + BAR_ITEM + it * 8, 0, dl);
    return lds_u(sb + OFF_ITEM + it * 4);
}
__device__ __forceinline__ uint32_t get_item_warp(uint32_t sb, int it, uint32_t dl) {
    return __shfl_sync(0xffffffffu, get_item(sb, it, dl), 0);
}

struct Ring {
    uint32_t slot, ph, dl;
    __device__ __forceinline__ void adv(uint32_t k) {
        slot += k;
        if (slot >= NSLOT) { slot -= NSLOT; ph ^= 1; }
    }
};

template <int K>
__device__ __forceinline__ void qk_step(float (&s)[80], uint32_t loK, uint32_t loQ) {
    wgmma<0, 0, HI_SW128, K != 0>(s, loK + (K >> 2) * (8192 >> 4) + (K & 3) * 2, loQ + (K >> 2) * (XS >> 4) + (K & 3) * 2);
}
template <int K0, int K1>
__device__ __forceinline__ void qk_steps(float (&s)[80], uint32_t loK, uint32_t loQ) {
    if constexpr (K0 < K1) {
        qk_step<K0>(s, loK, loQ);
        qk_steps<K0 + 1, K1>(s, loK, loQ);
    }
}
__device__ __forceinline__ uint32_t add_bf2(uint32_t a, uint32_t b) {
    uint32_t r;
    asm("add.rn.bf16x2 %0, %1, %2;" : "=r"(r) : "r"(a), "r"(b));
    return r;
}
__device__ __forceinline__ uint32_t fma_bf2(uint32_t a, uint32_t b, uint32_t c) {
    uint32_t r;
    asm("fma.rn.bf16x2 %0, %1, %2, %3;" : "=r"(r) : "r"(a), "r"(b), "r"(c));
    return r;
}
template <int J>
__device__ __forceinline__ void exp_block(const float (&s)[80], uint32_t (&k)[40], uint32_t pa, float mref) {
    if constexpr (J < 10) {
#pragma unroll
        for (int i = 4 * J; i < 4 * J + 4; i++)
            k[i] = pack_bf16(ex2(fmaf(s[2 * i], SM_C, -mref)), ex2(fmaf(s[2 * i + 1], SM_C, -mref)));
#pragma unroll
        for (int i = 0; i < 4; i++)
            asm volatile("stmatrix.sync.aligned.m8n8.x1.trans.shared.b16 [%0], {%1};" ::"r"(((i & 1) ? pa ^ 16 : pa) + J * 2048 + (i >> 1) * 1024),
                         "r"(k[4 * J + i])
                         : "memory");
        exp_block<J + 1>(s, k, pa, mref);
    }
}
__device__ __forceinline__ void sum_block(const uint32_t (&k)[40], float (&l)[10], uint32_t lane) {
    const bool b4 = lane & 16, b3 = lane & 8;
    uint32_t ps[20], t[10];
#pragma unroll
    for (int j = 0; j < 20; j++) ps[j] = add_bf2(k[2 * j], k[2 * j + 1]);
#pragma unroll
    for (int j = 0; j < 10; j++)
        t[j] = add_bf2(b4 ? ps[2 * j + 1] : ps[2 * j], __shfl_xor_sync(0xffffffffu, b4 ? ps[2 * j] : ps[2 * j + 1], 16));
#pragma unroll
    for (int i = 0; i < 5; i++) {
        const uint32_t a = b3 ? t[i + 5] : t[i], b = __shfl_xor_sync(0xffffffffu, b3 ? t[i] : t[i + 5], 8);
        l[2 * i] += __uint_as_float(a << 16) + __uint_as_float(b << 16);
        l[2 * i + 1] += __uint_as_float(a & 0xffff0000u) + __uint_as_float(b & 0xffff0000u);
    }
}
template <bool ADD>
__device__ __forceinline__ void sum_store(const float (&l)[10], uint32_t lane, uint32_t lxa) {
    const bool b2 = lane & 4;
    float t[5];
#pragma unroll
    for (int i = 0; i < 5; i++) t[i] = ADD ? __uint_as_float(lds_u(lxa + i * 64)) : 0.f;
#pragma unroll
    for (int i = 0; i < 5; i++)
        sts_f(lxa + i * 64, t[i] + (b2 ? l[2 * i + 1] : l[2 * i]) + __shfl_xor_sync(0xffffffffu, b2 ? l[2 * i] : l[2 * i + 1], 4));
}

__device__ __forceinline__ void fallback_unit(const Params& P, uint32_t e, uint32_t tid) {
    const uint32_t lane = tid & 31, br = IT_BR(e), b = IT_B(e), h = IT_H0(e);
    const __nv_bfloat162* wq = (const __nv_bfloat162*)(P.pwq[br] + h * 192) + lane;
    const __nv_bfloat162* kp = (const __nv_bfloat162*)(P.pk[br] + (size_t)(b * 32 + h) * 512 * 192) + lane;
    const __nv_bfloat162* vp = (const __nv_bfloat162*)(P.pv[br] + (size_t)(b * 32 + h) * 512 * 192) + lane;
#pragma unroll 1
    for (uint32_t qi = 0; qi < 40; qi++) {
        const uint32_t q = 4 * qi + (tid >> 5);
        const __nv_bfloat16* xr = P.px[br] + (size_t)(b * 160 + q) * 640;
        float a[6] = {0.f, 0.f, 0.f, 0.f, 0.f, 0.f};
#pragma unroll 2
        for (int k = 0; k < 640; k++) {
            const float xv = __bfloat162float(xr[k]);
#pragma unroll
            for (int i = 0; i < 3; i++) {
                const float2 wv = __bfloat1622float2(wq[(size_t)k * 3072 + i * 32]);
                a[2 * i] = fmaf(xv, wv.x, a[2 * i]);
                a[2 * i + 1] = fmaf(xv, wv.y, a[2 * i + 1]);
            }
        }
#pragma unroll
        for (int i = 0; i < 6; i++) a[i] = __bfloat162float(__float2bfloat16(a[i]));
        auto score = [&](int key) {
            float d = 0.f;
#pragma unroll
            for (int i = 0; i < 3; i++) {
                const float2 kv = __bfloat1622float2(kp[key * 96 + i * 32]);
                d = fmaf(a[2 * i], kv.x, fmaf(a[2 * i + 1], kv.y, d));
            }
#pragma unroll
            for (int o = 16; o > 0; o >>= 1) d += __shfl_xor_sync(0xffffffffu, d, o);
            return d;
        };
        float m = -INFINITY, o[6] = {0.f, 0.f, 0.f, 0.f, 0.f, 0.f}, sum = 0.f;
#pragma unroll 1
        for (int n = 0; n < 1024; n++) {
            const int key = n & 511;
            const float d = score(key);
            if (n < 512) {
                m = fmaxf(m, d);
            } else {
                const float p = ex2((d - m) * SM_C);
                sum += p;
#pragma unroll
                for (int i = 0; i < 3; i++) {
                    const float2 vv = __bfloat1622float2(vp[key * 96 + i * 32]);
                    o[2 * i] = fmaf(p, vv.x, o[2 * i]);
                    o[2 * i + 1] = fmaf(p, vv.y, o[2 * i + 1]);
                }
            }
        }
        const float inv = __fdividef(1.f, sum);
        __nv_bfloat16* op = (__nv_bfloat16*)ostash(IT_SLOT(e), b) + (q >> 5) * 256 + 2 * ((q & 31) >> 3) + (q & 1);
#pragma unroll
        for (int i = 0; i < 6; i++) {
            const uint32_t d = (i >> 1) * 64 + 2 * lane + (i & 1);
            op[(d >> 3) * 1280 + (d & 7) * 32 + ((((q & 7) >> 1) ^ ((d & 7) >> 1)) << 3)] = __float2bfloat16(o[i] * inv);
        }
    }
}

template <int W>
struct PendO {
    static constexpr int N = W == 0 ? 56 : 64;
    uint32_t v[N];
    unsigned char* gp;
    static __device__ __forceinline__ uint32_t toff() {
        const uint32_t t = tid_now();
        return ((t >> 5) & 3) * 5120 + ((t >> 2) & 7) * 64 + (((t ^ (t >> 3)) & 3) << 4);
    }
    uint32_t pend, sig, bad;
    static __device__ __forceinline__ void scale(uint32_t& x, uint32_t hi, uint32_t lo) {
        asm("{\n.reg .b32 t;\nmul.rn.bf16x2 t, %0, %2;\nfma.rn.bf16x2 %0, %0, %1, t;\n}" : "+r"(x) : "r"(hi), "r"(lo));
    }
    template <int I, int OFF>
    __device__ __forceinline__ void put() {
        asm volatile("{\n.reg .pred p;\nsetp.ne.u32 p, %6, 0;\n@p st.global.v4.b32 [%0+%5], {%1,%2,%3,%4};\n}" ::"l"(gp), "r"(v[I]),
                     "r"(v[I + 1]), "r"(v[I + 2]), "r"(v[I + 3]), "n"(OFF), "r"(pend)
                     : "memory");
    }
    __device__ __forceinline__ void verdict(uint32_t sb) {
        if (sig) {
            nb_sync<NB_VOTE + W, 160>();
            bad = __any_sync(0xffffffffu, lds_u(sb + OFF_FB) != 0);
            pend = !bad;
        }
    }
    template <int G, int H>
    __device__ __forceinline__ void half(uint32_t sb) {
        constexpr bool T2 = W == 0 ? G >= 3 : G < 3;
        constexpr int B = T2 ? 40 + 8 * (W == 0 ? G - 3 : G) : 0;
        const uint4 a = lds_u4(sb + OFF_LINV + G * 128 + H * 16 + (threadIdx.x & 3) * 32);
#pragma unroll
        for (int i = 2 * H; i < 8; i += 4) {
            scale(v[8 * G + i], a.x, a.y);
            scale(v[8 * G + i + 1], a.z, a.w);
            if (T2) {
                scale(v[B + i], a.x, a.y);
                scale(v[B + i + 1], a.z, a.w);
            }
        }
        if (H == 1) {
            put<8 * G, W * XS + G * 512>();
            put<8 * G + 4, W * XS + G * 512 + 2560>();
            if (T2) {
                put<B, 2 * XS + G * 512>();
                put<B + 4, 2 * XS + G * 512 + 2560>();
            }
            if (G == 4 && pend) nb_arrive<NB_ODONE, 288>();
        }
    }
    template <int G>
    __device__ __forceinline__ void step(uint32_t sb) {
        half<G, 0>(sb);
        half<G, 1>(sb);
    }
    __device__ __forceinline__ void clear() {
#pragma unroll
        for (int i = 0; i < N; i++) v[i] = 0;
        gp = nullptr;
        pend = 0;
        sig = 0;
        bad = 0;
    }
};

__device__ __forceinline__ uint32_t stsm_off() {
    const uint32_t tid = tid_now(), lane = tid & 31;
    return (lane >> 4) * 1024 + (lane & 7) * 128 + (((((tid >> 4) & 6) + ((lane >> 3) & 1)) ^ (lane & 7)) << 4);
}
template <int W, int KK>
__device__ __forceinline__ void qproj(float (&q0)[80], float (&q1)[80], uint32_t sb, Ring& r, uint32_t pslot, uint32_t phm,
                                      PendO<W>& po) {
    const uint32_t loR = (((sb + OFF_R) & 0x3ffff) >> 4) | LO_LBO1;
    const uint32_t loRing = (((sb + OFF_RING) & 0x3ffff) >> 4) | LO_LBO1;
    auto ready = [&](int k) {
        mbar_wait(sb + BAR_RFULL + r.slot * 8, r.ph, r.dl);
        mbar_wait(sb + BAR_XFULL + (k % 5) * 8, ((phm >> (k % 5)) ^ (k / 5)) & 1, r.dl);
    };
    auto release = [&]() {
        if (KK > 0) {
            wg_wait<1>();
            mbar_arrive_warp(sb + BAR_REMPTY + pslot * 8);
            if (KK <= 5) mbar_arrive_warp(sb + (BAR_XEMPTY + (KK - 1) * 8));
        }
    };
    if (KK == 0 && (W == 1 || !po.sig)) ready(0);
    if (W == 1 && KK == QHOLD) {
        if (QHOLD == 7) {
            wg_wait<0>();
            nb_arrive<NB_PDONE, 256>();
        }
        nb_sync<NB_SDONE, 256>();
    }
    const uint32_t a = loRing + r.slot * (SLOT >> 4) + (W == 0 ? 0 : 512), b = loR + (KK % 5) * (XS >> 4);
    wg_fence();
    wgmma<1, 0, HI_SW128, KK != 0>(q0, a, b);
    if (W == 0) wgmma<1, 0, HI_SW128, KK != 0>(q1, a + 256, b);
#pragma unroll
    for (int k = 1; k < 4; k++) {
        wgmma<1, 0, HI_SW128, true>(q0, a + (k >> 1) * 768 + (k & 1) * 128, b + k * 2);
        if (W == 0) wgmma<1, 0, HI_SW128, true>(q1, a + 256 + (k >> 1) * 768 + (k & 1) * 128, b + k * 2);
    }
    wg_commit();
    const uint32_t cslot = r.slot;
    r.adv(1);
    if (W == 0 || KK < QHOLD) release();
    if (KK == QST0) {
        po.verdict(sb);
        po.template half<0, 0>(sb);
    }
    if (KK < 9) ready(KK + 1);
    if (W == 1 && KK >= QHOLD) release();
    if (W == 1 && KK == 7 && QHOLD > 7) nb_arrive<NB_PDONE, 256>();
    if (KK == QST0) po.template half<0, 1>(sb);
    if constexpr (KK > QST0 && KK < QST0 + 5) po.template step<KK - QST0>(sb);
    if constexpr (KK < (W == 0 ? 7 : 9)) {
        qproj<W, KK + 1>(q0, q1, sb, r, cslot, phm, po);
    } else if constexpr (W == 1) {
        wg_wait<0>();
        reg_fence(q0);
        mbar_arrive_warp(sb + BAR_REMPTY + cslot * 8);
        store_tile_t<false, true>(q0, sb + OFF_R + 2 * XS + stsm_off());
    } else {
        const uint32_t s8 = r.slot, a8 = loRing + s8 * (SLOT >> 4);
        wg_fence();
#pragma unroll
        for (int k = 0; k < 4; k++) wgmma<1, 0, HI_SW128, true>(q0, a8 + (k >> 1) * 768 + (k & 1) * 128, loR + 3 * (XS >> 4) + k * 2);
        r.adv(1);
        ready(9);
        const uint32_t s9 = r.slot, a9 = loRing + s9 * (SLOT >> 4);
        r.adv(1);
        wg_fence();
#pragma unroll
        for (int k = 0; k < 4; k++) wgmma<1, 0, HI_SW128, true>(q0, a9 + (k >> 1) * 768 + (k & 1) * 128, loR + 4 * (XS >> 4) + k * 2);
        wg_commit();
        wg_wait<1>();
        mbar_arrive_warp(sb + BAR_REMPTY + cslot * 8);
        wg_fence();
#pragma unroll
        for (int k = 0; k < 8; k++)
            wgmma<1, 0, HI_SW128, true>(q1, (k < 4 ? a8 : a9) + 256 + ((k >> 1) & 1) * 768 + (k & 1) * 128,
                                        loR + (3 + (k >> 2)) * (XS >> 4) + (k & 3) * 2);
        wg_commit();
        nb_arrive<NB_SDONE, 256>();
        nb_sync<NB_PDONE, 256>();
        wg_wait<1>();
        reg_fence(q0);
        const uint32_t sta = sb + OFF_R + stsm_off();
        store_tile_t(q0, sta);
        sts_u(sb + OFF_GM + 4, r.slot);
        mbar_wait(sb + BAR_RFULL + r.slot * 8, r.ph, r.dl);
        wg_wait<0>();
        reg_fence(q1);
        mbar_arrive_warp(sb + BAR_REMPTY + s8 * 8);
        mbar_arrive_warp(sb + BAR_REMPTY + s9 * 8);
        store_tile_t(q1, sta + XS);
    }
}

template <int NR>
__device__ __forceinline__ void opack(const float (&o)[NR], uint32_t* v) {
#pragma unroll
    for (int g = 0; g < NR / 16; g++)
#pragma unroll
        for (int hh = 0; hh < 2; hh++)
#pragma unroll
            for (int t = 0; t < 4; t++) v[8 * g + 4 * hh + t] = pack_bf16(o[16 * g + 4 * t + 2 * hh], o[16 * g + 4 * t + 2 * hh + 1]);
}

template <bool IS_S>
__device__ __forceinline__ void op_item(uint32_t e, uint32_t sb, Ring& r, uint32_t& phm) {
    constexpr int T0 = IS_S ? 0 : 2;
    constexpr uint32_t BOFF = IS_S ? (3 * 512) >> 4 : 0;
    const uint32_t loRing = (((sb + OFF_RING) & 0x3ffff) >> 4) | LO_LBO1;
    const uint32_t loO = (((sb + OFF_R) & 0x3ffff) >> 4) | LO_OST;
    float c0[80], c1[80], c2[IS_S ? 32 : 48];
    const int T = 3 * (IT_H1(e) - IT_H0(e));
    uint32_t xs = 0;
    auto step = [&](auto first, auto half) {
        constexpr bool F = decltype(first)::value;
        constexpr uint32_t hf = decltype(half)::value;
        if (hf == 0) {
            mbar_wait(sb + BAR_XFULL + xs * 8, (phm >> xs) & 1, r.dl);
            phm ^= 1u << xs;
        }
        mbar_wait(sb + BAR_RFULL + r.slot * 8, r.ph, r.dl);
        const uint32_t a = loRing + r.slot * (SLOT >> 4), b = loO + xs * (XS >> 4) + hf * 640;
        wg_fence();
        wgmma<1, 1, HI_OST, !F>(c0, a + T0 * 128, b);
        wgmma<1, 1, HI_OST, !F>(c1, a + T0 * 128 + 128, b);
        wgmma<1, 1, HI_OST, !F>(c2, a + 512, b + BOFF);
        wgmma<1, 1, HI_OST, true>(c0, a + 640 + T0 * 128, b + 320);
        wgmma<1, 1, HI_OST, true>(c1, a + 640 + T0 * 128 + 128, b + 320);
        wgmma<1, 1, HI_OST, true>(c2, a + 640 + 512, b + 320 + BOFF);
        wg_commit();
    };
    step(TrueT{}, IntT<0>{});
#pragma unroll 1
    for (int t = 1;; t++) {
        uint32_t pslot = r.slot;
        r.adv(1);
        step(FalseT{}, IntT<1>{});
        wg_wait<1>();
        mbar_arrive_warp(sb + BAR_REMPTY + pslot * 8);
        if (t == T) break;
        pslot = r.slot;
        const uint32_t pxs = xs;
        r.adv(1);
        if (++xs == 5) xs = 0;
        step(FalseT{}, IntT<0>{});
        wg_wait<1>();
        mbar_arrive_warp(sb + BAR_REMPTY + pslot * 8);
        mbar_arrive_warp_if(sb + BAR_XEMPTY + pxs * 8, t + 4 < T);
    }
    wg_wait<0>();
    reg_fence(c0);
    reg_fence(c1);
    reg_fence(c2);
    mbar_arrive_warp(sb + BAR_REMPTY + r.slot * 8);
    r.adv(1);
    nb_sync<NB_OPEND, 256>();
    const uint32_t sta = sb + OFF_R + stsm_off();
    store_tile_t(c0, sta + T0 * XS);
    store_tile_t(c1, sta + (T0 + 1) * XS);
    store_tile_t(c2, sta + 4 * XS + (IS_S ? 96 * 128 : 0));
    fence_async_smem();
    nb_arrive<NB_ODONE, 288>();
}

__device__ __forceinline__ void on_item(uint32_t W, uint32_t e, uint32_t sb, Ring& r, uint32_t& phm) {
    const uint32_t loRing = (((sb + OFF_RING) & 0x3ffff) >> 4) | LO_LBO1;
    const uint32_t loO = (((sb + OFF_R) & 0x3ffff) >> 4) | LO_OST;
    float c[80];
    const int T = 3 * (IT_H1(e) - IT_H0(e));
    uint32_t xs = 0;
    auto step = [&](auto first) {
        constexpr bool F = decltype(first)::value;
        mbar_wait(sb + BAR_XFULL + xs * 8, (phm >> xs) & 1, r.dl);
        phm ^= 1u << xs;
        mbar_wait(sb + BAR_RFULL + r.slot * 8, r.ph, r.dl);
        const uint32_t a = loRing + r.slot * (SLOT >> 4) + W * 256, b = loO + xs * (XS >> 4);
        wg_fence();
        wgmma<1, 1, HI_OST, !F>(c, a, b);
#pragma unroll
        for (int k = 1; k < 4; k++) wgmma<1, 1, HI_OST, true>(c, a + (k >> 1) * 512 + (k & 1) * 128, b + k * 320);
        wg_commit();
    };
    step(TrueT{});
#pragma unroll 1
    for (int t = 1; t < T; t++) {
        const uint32_t pslot = r.slot, pxs = xs;
        r.adv(1);
        if (++xs == 5) xs = 0;
        step(FalseT{});
        wg_wait<1>();
        mbar_arrive_warp(sb + BAR_REMPTY + pslot * 8);
        mbar_arrive_warp_if(sb + BAR_XEMPTY + pxs * 8, t + 2 < T);
    }
    xs += 1 + W;
    if (xs >= 5) xs -= 5;
    mbar_wait(sb + BAR_XFULL + xs * 8, (phm >> xs) & 1, r.dl);
    wg_wait<0>();
    reg_fence(c);
    store_tile_t<true>(c, sb + OFF_R + xs * XS + stsm_off());
    fence_async_smem();
    nb_arrive<NB_ODONE, 288>();
}

template <int W>
__device__ __forceinline__ uint32_t qa_item(uint32_t e, uint32_t sb, Ring& r, uint32_t phm, PendO<W>& po, int it) {
    const uint32_t loR = (((sb + OFF_R) & 0x3ffff) >> 4) | LO_LBO1;
    const uint32_t loRing = (((sb + OFF_RING) & 0x3ffff) >> 4) | LO_LBO1;
    {
        float q0[80], q1[80];
        qproj<W, 0>(q0, q1, sb, r, 0, phm, po);
    }
    fence_async_smem();
    TSD(W, 1);
    float s[80], oa[80], ob[W == 0 ? 32 : 48], l[10];
    if (W == 1) {
        nb_arrive<NB_Q2, 256>();
        zero(oa);
        zero(ob);
        reg_fence(oa);
        reg_fence(ob);
    }
    const uint32_t lane = tid_now() & 31, sta = sb + OFF_R + stsm_off();
    auto pv = [&](auto first, uint32_t buf) {
        constexpr bool F = decltype(first)::value;
        mbar_wait(sb + BAR_RFULL + r.slot * 8, r.ph, r.dl);
        const uint32_t a = loRing + r.slot * (SLOT >> 4), b = loR + (3 + buf) * (XS >> 4);
        wg_fence();
        wgmma<1, 0, HI_SW128, !F>(oa, a + W * 512, b);
        wgmma<1, 0, HI_SW128, !F>(ob, a + 1024, b + (W == 0 ? (96 * 128) >> 4 : 0));
#pragma unroll
        for (int k = 1; k < 4; k++) {
            wgmma<1, 0, HI_SW128, true>(oa, a + W * 512 + k * 128, b + k * 2);
            wgmma<1, 0, HI_SW128, true>(ob, a + 1024 + k * 128, b + (W == 0 ? (96 * 128) >> 4 : 0) + k * 2);
        }
        wg_commit();
    };
    zero(l);
    float mref;
    uint32_t kslot, vslot;
    auto tail = [&](auto first, int i) {
        constexpr bool rel_other = !decltype(first)::value;
        uint32_t ps[40];
        exp_block<0>(s, ps, sta + (3 + W) * XS, mref);
        if (rel_other) {
            wg_wait<0>();
            mbar_arrive_warp(sb + BAR_REMPTY + vslot * 8);
            if (W == 1) mbar_arrive_warp_if(sb + BAR_XEMPTY + 24, i == 3);
        }
        fence_async_smem();
        nb_arrive<NB_PFULL + W, 256>();
        TSD(W, 6 + 5 * i);
        if (W == 1) {
            if (XLATE >= 2) mbar_arrive_warp_if<2>(sb + BAR_XEMPTY + 8, i == 3);
            if (XLATE >= 1) mbar_arrive_warp_if<2>(sb + BAR_XEMPTY + 16, i == 3);
        }
        if (rel_other || !PV0FIRST) {
            mbar_wait(sb + BAR_RFULL + r.slot * 8, r.ph, r.dl);
            sum_block(ps, l, lane);
        }
        TSD(W, 7 + 5 * i);
        if (LASTORD && W == 0 && i == 3) nb_sync<NB_PDONE, 256>();
        else nb_sync<NB_W + W, 128>();
        pv(first, W);
        if (!rel_other && PV0FIRST) sum_block(ps, l, lane);
        TSD(W, 8 + 5 * i);
    };
    if (W == 0) {
        nb_sync<NB_QK, 160>();
        TSD(W, 2);
        wg_fence();
        qk_steps<0, 8>(s, loRing + r.slot * (SLOT >> 4), loR);
        nb_sync<NB_Q2, 256>();
        qk_steps<8, 12>(s, loRing + r.slot * (SLOT >> 4), loR);
        wg_commit();
        nb_arrive<NB_Q01, 256>();
        TSD(W, 4);
        nb_sync<NB_REF, 160>();
        mref = __uint_as_float(lds_u(sb + OFF_GM));
        wg_wait<0>();
        reg_fence(s);
        mbar_arrive_warp<2>(sb + BAR_REMPTY + r.slot * 8);
        r.adv(2);
        TSD(W, 5);
        tail(TrueT{}, 0);
    } else {
        nb_sync<NB_Q01, 256>();
    }
#pragma unroll 1
    for (int i = (W == 0 ? 1 : 0); i < 4; i++) {
        const uint32_t pvslot = r.slot;
        r.adv(1);
        kslot = r.slot;
        mbar_wait(sb + BAR_RFULL + r.slot * 8, r.ph, r.dl);
        wg_fence();
        qk_steps<0, 12>(s, loRing + r.slot * (SLOT >> 4), loR);
        wg_commit();
        wg_wait<1>();
        mbar_arrive_warp_if(sb + BAR_REMPTY + pvslot * 8, W == 0 || i > 0);
        r.adv(1);
        vslot = r.slot;
        TSD(W, 4 + 5 * i);
        nb_sync<NB_PFULL + (W ^ 1), 256>();
        pv(FalseT{}, W ^ 1);
        if (LASTORD && W == 1 && i == 3) nb_arrive<NB_PDONE, 256>();
        if (W == 1) mref = __uint_as_float(lds_u(sb + OFF_GM));
        wg_wait<1>();
        reg_fence(s);
        mbar_arrive_warp<2>(sb + BAR_REMPTY + kslot * 8);
        if (W == 1) {
            mbar_arrive_warp_if<2>(sb + BAR_XEMPTY + 0, i == 3);
            if (XLATE < 2) mbar_arrive_warp_if<2>(sb + BAR_XEMPTY + 8, i == 3);
            if (XLATE < 1) mbar_arrive_warp_if<2>(sb + BAR_XEMPTY + 16, i == 3);
        }
        r.adv(W == 1 && i == 3 ? 1 : 2);
        TSD(W, 5 + 5 * i);
        tail(FalseT{}, i);
    }
    const uint32_t w = (tid_now() >> 5) & 3;
    const uint32_t lxa = sb + OFF_LX + w * 640 + (((lane & 8) ? 80 : 0) + ((lane >> 1) & 8) + 2 * (lane & 3) + ((lane >> 2) & 1)) * 4;
    const uint32_t nx = get_item_warp(sb, it + 1, r.dl);
    po.gp = ostash(IT_SLOT(e), IT_B(e)) + po.toff();
    po.sig = 1;
    if (W == 0) {
        sum_store<false>(l, lane, lxa);
        nb_arrive<NB_LX, 256>();
        wg_wait<0>();
        mbar_arrive_warp(sb + BAR_REMPTY + r.slot * 8);
        mbar_arrive_warp(sb + BAR_XEMPTY + 24);
        r.adv(1);
        nb_sync<NB_PFULL + 1, 256>();
        pv(FalseT{}, 1);
        if (IT_TYPE(nx) == IT_QA) {
            Ring rn = r;
            rn.adv(1);
            mbar_wait(sb + BAR_RFULL + rn.slot * 8, rn.ph, r.dl);
            mbar_wait(sb + BAR_XFULL, phm & 1, r.dl);
        }
    } else {
        nb_sync<NB_LX, 256>();
        sum_store<true>(l, lane, lxa);
        nb_arrive<NB_L, 160>();
    }
    TSD(W, 24);
    wg_wait<0>();
    reg_fence(oa);
    reg_fence(ob);
    mbar_arrive_warp(sb + BAR_REMPTY + r.slot * 8);
    mbar_arrive_warp(sb + BAR_XEMPTY + 32);
    r.adv(1);
    opack(ob, po.v + 40);
    opack(oa, po.v);
    return nx;
}

template <int W>
__device__ __forceinline__ uint32_t qa_run(const Params& P, uint32_t e, uint32_t sb, Ring& r, uint32_t phm, int& it) {
    PendO<W> po;
    po.clear();
#pragma unroll 1
    do {
        TS(W, 0);
        if (W == 0) TS_ITEM(e);
        e = qa_item<W>(e, sb, r, phm, po, it);
        TS(W, 31);
        it++;
    } while (IT_TYPE(e) == IT_QA && !po.bad);
#pragma unroll 1
    for (int m = po.bad ? 2 : 1; m > 0; m--) {
        if (m == 1) {
            po.verdict(sb);
            po.template step<0>(sb);
            po.template step<1>(sb);
            po.template step<2>(sb);
            po.template step<3>(sb);
            po.template step<4>(sb);
        }
        if (po.bad) {
            if (W == 0) fallback_unit(P, lds_u(sb + OFF_ITEM + (it - m) * 4), tid_now() & 127);
            __syncwarp();
            nb_sync<NB_ODONE, 288>();
        }
    }
    return e;
}

__device__ __forceinline__ void consumer(const Params& P, uint32_t W, uint32_t sb, uint32_t dl) {
    int it = 0;
    if (W == 0) TS(0, 30);
    Ring r{0, 0, dl};
    uint32_t phm = 0;
    uint32_t e = get_item_warp(sb, 0, dl);
#pragma unroll 1
    while (true) {
        if (IT_TYPE(e) == IT_QA) e = W == 0 ? qa_run<0>(P, e, sb, r, phm, it) : qa_run<1>(P, e, sb, r, phm, it);
        if (e == 0) break;
        if (IT_TYPE(e) == IT_QA) continue;
        TS(W, 0);
        if (W == 0) TS_ITEM(e);
        if (IT_TYPE(e) == IT_ON) on_item(W, e, sb, r, phm);
        else if (W == 0) op_item<true>(e, sb, r, phm);
        else op_item<false>(e, sb, r, phm);
        TS(W, 31);
        e = get_item_warp(sb, ++it, dl);
    }
    TS_DUMP(W);
}

__global__ void __cluster_dims__(2, 1, 1) __launch_bounds__(384, 1) fused_kernel(const __grid_constant__ Params P) {
    extern __shared__ __align__(1024) unsigned char smem_raw[];
    const uint32_t sb = (uint32_t)__cvta_generic_to_shared(smem_raw);
    const uint32_t wgid = __shfl_sync(0xffffffffu, threadIdx.x >> 7, 0);
    const uint32_t cta = blockIdx.x;
    const uint32_t dl = deadline();

    if (threadIdx.x == 128) {
#pragma unroll
        for (int i = 0; i < NSLOT; i++) {
            mbar_init(sb + BAR_RFULL + i * 8, 1);
            mbar_init(sb + BAR_REMPTY + i * 8, 8);
            mbar_init(sb + BAR_XFULL + i * 8, 1);
            mbar_init(sb + BAR_XEMPTY + i * 8, 8);
        }
        asm volatile("fence.mbarrier_init.release.cluster;" ::: "memory");
        fence_async_smem();
    } else if (threadIdx.x == 160) {
#pragma unroll
        for (int i = 0; i < NSLOT + MAXI; i++) mbar_init(sb + BAR_PRDY + i * 8, 1);
        asm volatile("fence.mbarrier_init.release.cluster;" ::: "memory");
    } else if (threadIdx.x == 0) {
        sts_u(sb + OFF_ITEM, P.cl[cta >> 1].items[0] ? P.cl[cta >> 1].items[0] + 8 * (cta & 1) : 0);
        sts_u(sb + OFF_FB, P.cl[cta >> 1].delay);
    } else if (threadIdx.x == 64) {
        if (sb & 1023) __trap();
        asm volatile("prefetch.tensormap [%0];" ::"l"(&P.wq[0]) : "memory");
        asm volatile("prefetch.tensormap [%0];" ::"l"(&P.x[0]) : "memory");
    }
    __syncthreads();
    asm volatile("barrier.cluster.arrive.relaxed.aligned;" ::: "memory");

    if (wgid == 0) {
        asm volatile("setmaxnreg.dec.sync.aligned.u32 24;");
        const uint32_t warp = __shfl_sync(0xffffffffu, threadIdx.x >> 5, 0);
        if (warp == 0) {
            const bool lead = threadIdx.x == 0;
            const uint64_t pol_first = mkpol<1>(), pol_norm = mkpol<POL_W>();
            uint32_t e = __shfl_sync(0xffffffffu, lds_u(sb + OFF_ITEM), 0);
            {
                const uint32_t d = lds_u(sb + OFF_FB);
                uint32_t t0, t1;
                asm volatile("mov.u32 %0, %%clock;" : "=r"(t0));
                do {
                    asm volatile("mov.u32 %0, %%clock;" : "=r"(t1));
                } while (t1 - t0 < d);
                __syncwarp();
            }
            if (lead) asm volatile("mbarrier.arrive.shared::cta.b64 _, [%0];" ::"r"(sb + BAR_ITEM) : "memory");
#pragma unroll 1
            for (int n = 0; n < (e ? NSLOT : 0); n++) {
                if (lead) {
                    mbar_expect(sb + BAR_RFULL + n * 8, SLOT);
                    tma3(sb + OFF_RING + n * SLOT, &P.wq[0], n * 64, IT_H0(e) * 3, sb + BAR_RFULL + n * 8, pol_norm);
                    mbar_expect(sb + BAR_XFULL + n * 8, XS);
                    tma3(sb + OFF_R + n * XS, &P.x[0], IT_B(e) * 160, n, sb + BAR_XFULL + n * 8, pol_norm);
                    tma3(sb + OFF_RING + n * SLOT + SLOT / 2, &P.wq[0], n * 64 + 32, IT_H0(e) * 3, sb + BAR_RFULL + n * 8, pol_norm);
                }
            }
            __syncwarp();
            asm volatile("barrier.cluster.wait.aligned;" ::: "memory");
            unsigned int* const ticket = &g_ticket[next_epoch(0) & 1];
            const uint32_t rank = cta & 1;
            uint32_t peer;
            asm volatile("mapa.shared::cluster.u32 %0, %1, %2;" : "=r"(peer) : "r"(sb), "r"(rank ^ 1));
            Ring r{0, 0, dl};
            uint32_t pm = 0;
            auto load_w = [&](const CUtensorMap* m, int row, int blk, uint32_t half_bytes) {
                mbar_wait(sb + BAR_REMPTY + r.slot * 8, r.ph, dl);
                if (lead) {
                    mbar_expect(sb + BAR_RFULL + r.slot * 8, 2 * half_bytes);
                    asm volatile("mbarrier.arrive.shared::cluster.b64 _, [%0];" ::"r"(peer + BAR_PRDY + r.slot * 8) : "memory");
                }
                mbar_wait(sb + BAR_PRDY + r.slot * 8, (pm >> r.slot) & 1, dl);
                pm ^= 1u << r.slot;
                if (lead) tma3_mc(sb + OFF_RING + r.slot * SLOT + rank * half_bytes, m, row, blk, sb + BAR_RFULL + r.slot * 8, pol_norm);
                r.adv(1);
            };
#pragma unroll 1
            for (int it = 0; e != 0; it++) {
                uint32_t nx = 0, tk = 0;
                if (rank == 0 && IT_TYPE(e) != IT_ON && it + 2 < MAXI) nx = it + 1 < NSTAT ? P.cl[cta >> 1].items[it + 1] : IT_DYN;
                const uint32_t br = IT_BR(e);
                if (IT_TYPE(e) == IT_QA) {
                    const uint32_t h = IT_H0(e);
#pragma unroll 1
                    for (int kk = it ? 0 : NSLOT; kk < 10; kk++) load_w(&P.wq[br], kk * 64 + rank * 32, h * 3, SLOT / 2);
                    const int row0 = (IT_B(e) * 32 + h) * 512;
#pragma unroll 1
                    for (int n = 0; n < 16; n++) {
                        if (n == 13 && nx == IT_DYN && lead) tk = atomicAdd(ticket, 1);
                        const bool isv = n == 15 || (n > 0 && !(n & 1));
                        const int j = n == 15 ? 7 : isv ? (n - 2) >> 1 : (n + 1) >> 1;
                        mbar_wait(sb + BAR_REMPTY + r.slot * 8, r.ph, dl);
                        if (lead) {
                            mbar_expect(sb + BAR_RFULL + r.slot * 8, SLOT);
                            tma3(sb + OFF_RING + r.slot * SLOT, isv ? &P.v[br] : &P.k[br], row0 + j * 64, 0,
                                 sb + BAR_RFULL + r.slot * 8, pol_first);
                        }
                        r.adv(1);
                    }
                } else {
                    const bool wide = IT_TYPE(e) == IT_OP;
                    const int step = wide ? 32 : 64, r1 = IT_H1(e) * 192;
#pragma unroll 1
                    for (int row = IT_H0(e) * 192 + rank * (step >> 1); row < r1; row += step)
                        load_w(wide ? &P.wo[br] : &P.won[br], row, IT_HALF(e) * (wide ? 5 : 2), wide ? XS / 2 : 8192);
                    if (nx == IT_DYN && lead) tk = atomicAdd(ticket, 1);
                }
                if (rank == 0) {
                    if (nx == IT_DYN) {
                        tk = __shfl_sync(0xffffffffu, tk, 0);
                        nx = tk < P.nlist ? P.list[tk] : 0;
                    }
                    e = nx;
                    if (lead) {
                        asm volatile("st.async.weak.shared::cluster.mbarrier::complete_tx::bytes.b32 [%0], %1, [%2];" ::"r"(
                                         peer + OFF_ITEM + 4 + it * 4),
                                     "r"(e ? e + 8 : 0), "r"(peer + BAR_ITEM + 8 + it * 8)
                                     : "memory");
                        sts_u(sb + OFF_ITEM + 4 + it * 4, e);
                        asm volatile("mbarrier.arrive.shared::cta.b64 _, [%0];" ::"r"(sb + BAR_ITEM + 8 + it * 8) : "memory");
                    }
                } else {
                    if (lead) mbar_expect(sb + BAR_ITEM + 8 + it * 8, 4);
                    e = get_item_warp(sb, it + 1, dl);
                }
            }
        } else if (warp == 1) {
            const uint64_t pol_norm = mkpol<POL_X>(), pol_o = mkpol<POL_O>();
            const bool lead = threadIdx.x == 32;
            uint32_t phm = 0, epoch = 0;
#pragma unroll 1
            for (int it = 0;; it++) {
                const uint32_t e = get_item_warp(sb, it, dl);
                if (it == 1 || (it == 0 && e == 0)) epoch = next_epoch(1);
                if (e == 0) break;
                const uint32_t br = IT_BR(e);
                uint32_t xs = 0;
                auto acquire = [&]() {
                    mbar_wait(sb + BAR_XEMPTY + xs * 8, (phm >> xs) & 1, dl);
                    phm ^= 1u << xs;
                    if (lead) mbar_expect(sb + BAR_XFULL + xs * 8, XS);
                };
                if (IT_TYPE(e) == IT_QA) {
#pragma unroll 1
                    for (int kk = it ? 0 : 5; kk < 10; kk++) {
                        acquire();
                        if (lead) tma3(sb + OFF_R + xs * XS, &P.x[br], IT_B(e) * 160, kk, sb + BAR_XFULL + xs * 8, pol_norm);
                        if (++xs == 5) xs = 0;
                    }
                } else {
                    const unsigned int* fp = g_flag + (br * 16 + IT_B(e)) * 64 + (threadIdx.x & 31);
                    uint32_t hm = 0, pm = 0;
                    auto poll = [&](uint32_t hneed, uint32_t pneed) {
                        if ((hm & hneed) == hneed && (pm & pneed) == pneed) return;
                        uint32_t n = 0;
                        do {
                            uint32_t a, b;
                            asm volatile("ld.acquire.gpu.global.u32 %0, [%2];\nld.acquire.gpu.global.u32 %1, [%2+128];"
                                         : "=r"(a), "=r"(b) : "l"(fp) : "memory");
                            hm = __ballot_sync(0xffffffffu, a == epoch);
                            pm = __ballot_sync(0xffffffffu, b == epoch);
                            if (++n > 0x1000000) __trap();
                        } while ((hm & hneed) != hneed || (pm & pneed) != pneed);
                        __syncwarp();
                        asm volatile("fence.proxy.async;" ::: "memory");
                    };
#pragma unroll 1
                    for (uint32_t h = IT_H0(e); h < IT_H1(e); h++) {
                        poll(1u << h, 0);
                        const unsigned char* src = ostash(P.slot[br * 32 + h], IT_B(e));
#pragma unroll 1
                        for (int t = 0; t < 3; t++) {
                            acquire();
                            if (lead) bulk_load(sb + OFF_R + xs * XS, src + t * XS, XS, sb + BAR_XFULL + xs * 8, pol_o);
                            if (++xs == 5) xs = 0;
                        }
                        if (IT_TYPE(e) == IT_OP && h >= 1) {
                            const uint32_t x1 = xs == 4 ? 0 : xs + 1;
                            mbar_wait(sb + BAR_XFULL + xs * 8, (phm >> xs) & 1, dl);
                            mbar_wait(sb + BAR_XFULL + x1 * 8, (phm >> x1) & 1, dl);
                            if (lead)
                                asm volatile("st.relaxed.gpu.global.u32 [%0], %1;" ::"l"(fp + 34 + IT_HALF(e)), "r"(epoch * 64 + h) : "memory");
                        }
                    }
                    if (IT_TYPE(e) == IT_ON) {
                        poll(0, IT_HALF(e) < 2 ? 1 : IT_HALF(e) == 2 ? 3 : 2);
#pragma unroll 1
                        for (uint32_t tile = 2 * IT_HALF(e); tile < 2 * IT_HALF(e) + 2; tile++) {
                            acquire();
                            if (lead)
                                asm volatile(
                                    "cp.async.bulk.tensor.5d.shared::cluster.global.mbarrier::complete_tx::bytes [%0], [%1, {%3,%5,%5,%5,%4}], [%2];" ::"r"(
                                        sb + OFF_R + xs * XS),
                                    "l"(&P.out), "r"(sb + BAR_XFULL + xs * 8), "r"(br * 640 + tile * 64), "r"(IT_B(e) * 5), "r"(0)
                                    : "memory");
                            if (++xs == 5) xs = 0;
                        }
                    }
                }
            }
        } else if (warp == 2) {
            asm volatile("barrier.cluster.wait.aligned;" ::: "memory");
            const uint32_t epoch = next_epoch(2);
            if (cta == 0) g_ticket[(epoch + 1) & 1] = 0;
#pragma unroll 1
            for (int it = 0;; it++) {
                const uint32_t e = get_item_warp(sb, it, dl);
                if (e == 0) break;
                nb_sync<NB_ODONE, 288>();
                if (threadIdx.x == 64) {
                    const uint32_t bb = IT_BR(e) * 16 + IT_B(e);
                    if (IT_TYPE(e) != IT_QA) {
                        const bool wide = IT_TYPE(e) == IT_OP;
                        if (wide)
                            asm volatile("st.relaxed.gpu.global.u32 [%0], %1;" ::"l"(&g_flag[bb * 64 + 34 + IT_HALF(e)]),
                                         "r"(epoch * 64 + IT_H1(e))
                                         : "memory");
                        const int cc0 = IT_BR(e) * 640 + IT_HALF(e) * (wide ? 320 : 128);
                        uint32_t xs = wide ? 0 : (3 * (IT_H1(e) - IT_H0(e))) % 5;
#pragma unroll 1
                        for (int m = 0; m < (wide ? 5 : 2); m++) {
                            asm volatile("cp.async.bulk.tensor.5d.global.shared::cta.bulk_group [%0, {%2,%4,%4,%4,%3}], [%1];" ::"l"(&P.out),
                                         "r"(sb + OFF_R + xs * XS), "r"(cc0 + m * 64), "r"((int)IT_B(e) * 5), "r"(0)
                                         : "memory");
                            asm volatile("cp.async.bulk.commit_group;" ::: "memory");
                            if (++xs == 5) xs = 0;
                        }
                        if (wide) {
#define REL(N)                                                          \
    asm volatile("cp.async.bulk.wait_group.read %0;" ::"n"(4 - N) : "memory"); \
    asm volatile("mbarrier.arrive.shared::cta.b64 _, [%0], 8;" ::"r"(sb + BAR_XEMPTY + N * 8) : "memory");
                            REL(0) REL(1) REL(2) REL(3) REL(4)
#undef REL
                        }
                        if (IT_PART(e)) {
                            asm volatile("cp.async.bulk.wait_group 0;" ::: "memory");
                            asm volatile("fence.proxy.async;" ::: "memory");
                        }
                    }
                    if (IT_TYPE(e) == IT_QA || IT_PART(e)) {
                        unsigned int* f = &g_flag[bb * 64 + (IT_TYPE(e) == IT_QA ? IT_H0(e) : 32 + IT_HALF(e))];
                        asm volatile("st.release.gpu.global.u32 [%0], %1;" ::"l"(f), "r"(epoch) : "memory");
                    }
                }
                __syncwarp();
            }
            if (threadIdx.x == 64) asm volatile("cp.async.bulk.wait_group 0;" ::: "memory");
            __syncwarp();
            asm volatile("barrier.cluster.arrive.relaxed.aligned;\nbarrier.cluster.wait.aligned;" ::: "memory");
        } else {
            const uint32_t lane = threadIdx.x & 31, p = lane >> 2;
            const uint32_t epoch = next_epoch(3);
#pragma unroll 1
            for (int it = 0;; it++) {
                const uint32_t e = get_item_warp(sb, it, dl);
                if (e == 0) break;
                if (IT_TYPE(e) != IT_QA) continue;
                nb_sync<NB_QK, 160>();
                const uint32_t co = (((lane & 3) * 2) ^ p) << 4;
                const uint32_t ka = sb + OFF_RING + lds_u(sb + OFF_GM + 4) * SLOT + p * (9 * 128) + co;
                const uint32_t qa = sb + OFF_R + p * 128 + co;
                uint32_t acc = 0;
#pragma unroll 1
                for (int c = 0; c < 3; c++) {
                    if (c == 2) nb_sync<NB_L, 160>();
                    const uint4 k0 = lds_u4(ka + c * 8192), q0 = lds_u4(qa + c * XS);
                    acc = fma_bf2(k0.x, q0.x, fma_bf2(k0.y, q0.y, fma_bf2(k0.z, q0.z, fma_bf2(k0.w, q0.w, acc))));
                    const uint4 k1 = lds_u4((ka + c * 8192) ^ 16), q1 = lds_u4((qa + c * XS) ^ 16);
                    acc = fma_bf2(k1.x, q1.x, fma_bf2(k1.y, q1.y, fma_bf2(k1.z, q1.z, fma_bf2(k1.w, q1.w, acc))));
                }
                float d = __uint_as_float(acc << 16) + __uint_as_float(acc & 0xffff0000u);
                d += __shfl_xor_sync(0xffffffffu, d, 1);
                d += __shfl_xor_sync(0xffffffffu, d, 2);
                int key = __float_as_int(d);
                key ^= (key >> 31) & 0x7fffffff;
                key = __reduce_max_sync(0xffffffffu, key);
                key ^= (key >> 31) & 0x7fffffff;
                sts_f(sb + OFF_GM, __int_as_float(key) * SM_C);
                nb_arrive<NB_REF, 160>();
                if (IT_DEP(e)) {
                    const uint32_t g = IT_DEP(e) - 1, need = epoch * 64 + (g & 31) + 1;
                    const unsigned int* cp = &g_flag[((g >> 5) * 16 + IT_B(e)) * 64 + 34 + (lane & 1)];
                    for (uint32_t n = 0;; n++) {
                        uint32_t v;
                        asm volatile("ld.acquire.gpu.global.u32 %0, [%1];" : "=r"(v) : "l"(cp) : "memory");
                        if (__all_sync(0xffffffffu, v - need < 64)) break;
                        if (n > 0x800000) __trap();
                        __nanosleep(500);
                    }
                }
                nb_sync<NB_L, 160>();
                bool bad = false;
#pragma unroll
                for (int c = 0; c < 5; c++) {
                    const uint32_t la = sb + OFF_LX + (c * 32 + lane) * 4;
                    const float v = (__uint_as_float(lds_u(la)) + __uint_as_float(lds_u(la + 640))) +
                                    (__uint_as_float(lds_u(la + 1280)) + __uint_as_float(lds_u(la + 1920)));
                    const float inv = __fdividef(1.f, v);
                    const uint32_t hi = pack_bf16(inv, 0.f), lo = pack_bf16(inv - __uint_as_float(hi << 16), 0.f);
                    const uint32_t ia = sb + OFF_LINV + c * 128 + ((lane >> 1) & 3) * 32 + (lane >> 3) * 8 + (lane & 1) * 2;
                    asm volatile("st.shared.u16 [%0], %1;\nst.shared.u16 [%0+4], %2;" ::"r"(ia), "h"((unsigned short)hi), "h"((unsigned short)lo) : "memory");
                    bad |= !(v >= 5.421010862e-20f && v <= 1.8446744e19f);
                }
                sts_u(sb + OFF_FB, __any_sync(0xffffffffu, bad));
                nb_arrive<NB_VOTE, 160>();
                nb_arrive<NB_VOTE + 1, 160>();
            }
        }
    } else {
        asm volatile("setmaxnreg.inc.sync.aligned.u32 240;");
        consumer(P, wgid - 1, sb, dl);
    }
}

typedef CUresult (*EncFn)(CUtensorMap*, CUtensorMapDataType, cuuint32_t, void*, const cuuint64_t*, const cuuint64_t*,
                          const cuuint32_t*, const cuuint32_t*, CUtensorMapInterleave, CUtensorMapSwizzle,
                          CUtensorMapL2promotion, CUtensorMapFloatOOBfill);

void make_map3(EncFn enc, CUtensorMap* m, void* p, uint64_t rows, uint64_t rowbytes, uint64_t nblk, uint32_t boxrows,
               uint32_t boxblk) {
    cuuint64_t dims[3] = {64, rows, nblk};
    cuuint64_t str[2] = {rowbytes, 128};
    cuuint32_t box[3] = {64, boxrows, boxblk};
    cuuint32_t es[3] = {1, 1, 1};
    enc(m, CU_TENSOR_MAP_DATA_TYPE_BFLOAT16, 3, p, dims, str, box, es, CU_TENSOR_MAP_INTERLEAVE_NONE,
        CU_TENSOR_MAP_SWIZZLE_128B, CU_TENSOR_MAP_L2_PROMOTION_NONE, CU_TENSOR_MAP_FLOAT_OOB_FILL_NONE);
}

constexpr int tune(const char*, int def) { return def; }

void build_schedule(Params& P) {
    const int mode = tune("MODE", 4), dmax = tune("DMAX", 24900), n0 = tune("N0", 8);
    const int H0[8] = {20, 20, 22, 22, 22, 24, 25, 25}, P0[8] = {352, 352, 344, 348, 352, 345, 333, 336};
    const int ng = tune("NG", 0), d0 = tune("D0", 0), nkeep = tune("NKEEP", 0), odmax = tune("ODMAX", 2000);
    const int ong = tune("ONG", 0), od0 = tune("OD0", 0), jit = tune("JIT", 0);
    const int npos = tune("NPOS", 0), nearly = tune("NEARLY", 0);
    const int ra = tune("RA", 10), ga = tune("GA", 32), rb = tune("RB", 12), g1 = tune("G1", 58);
    int dep[64];
    for (int g = 0, ns = 0, live = 0; g < 64; g++) {
        const bool fresh = mode < 3 || g >= g1 || live < (g < ga ? ra : rb);
        dep[g] = fresh ? 0 : g - live + 1;
        P.slot[g] = fresh ? ns++ : P.slot[g - live];
        live += fresh;
    }
    int u = 0;
    auto unit = [&]() {
        const uint32_t e = mk_item(IT_QA, u >> 8, (u & 7) * 2, (u >> 3) & 31, P.slot[u >> 3], 0) | (dep[u >> 3] << 23);
        u++;
        return e;
    };
    int qa[NCL], nq = 0, op[NCL], no = 0;
    for (int c = 0; c < NCL; c++) {
        P.cl[c].delay = 0;
        for (int i = 0; i < NSTAT; i++) P.cl[c].items[i] = 0;
        if (mode >= 3 && c < 64 && (c & 3) == 3) op[no++] = c;
        else if (mode != 2 || (c & 3) == 0) qa[nq++] = c;
    }
    for (int t = 0; t < no; t++) {
        P.cl[op[t]].items[1] = mk_item(IT_OP, 0, t & ~1, 0, 32, t & 1);
        P.cl[op[t]].items[2] = IT_DYN;
        P.cl[op[t]].delay = ong ? od0 + (t * ong / 16) * (odmax / ong) : od0 + t * odmax / 16;
    }
    for (int k = 0; k < nq; k++) {
        const int c = qa[(k * 19) % nq];
        P.cl[c].items[1] = P.cl[c].items[2] = IT_DYN;
        P.cl[c].delay = k < n0 ? 0 : (int)((long long)dmax * (k + 1 - n0) / (nq - n0));
        if (ng) P.cl[c].delay = d0 + (k * ng / nq) * (dmax / ng) + (k * ng % nq) * jit / nq;
    }
    if (tune("OFIRST", 0))
        for (int t = 0; t < no; t++) P.cl[op[t]].items[0] = unit();
    for (int k = u; k < no + nq; k++) {
        int best = -1;
        for (int c = 0; c < NCL; c++)
            if (P.cl[c].items[1] && !P.cl[c].items[0] && (best < 0 || P.cl[c].delay < P.cl[best].delay)) best = c;
        P.cl[best].items[0] = unit();
    }
    int H[8], pos[8];
    for (int b = 0; b < 8; b++) {
        char nh[3] = {'H', (char)('0' + b), 0}, np[3] = {'P', (char)('0' + b), 0};
        H[b] = tune(nh, H0[b]);
        pos[b] = tune(np, P0[b]);
        for (int g = 0; g < 64; g++)
            if (dep[g] > 32) {
                if (pos[b] > 8 * g) pos[b] = 8 * g;
                if (H[b] < dep[g] - 32) H[b] = dep[g] - 32;
            }
        if (b < nkeep && no) {
            pos[b] = -1;
            P.cl[op[14 - 2 * b]].items[2] = mk_item(IT_OP, 1, 2 * b, 0, H[b], 0, 1);
            P.cl[op[15 - 2 * b]].items[2] = mk_item(IT_OP, 1, 2 * b, 0, H[b], 1, 1);
        }
    }
    int n = 0, kn = 0;
    const int uend = mode == 2 ? 8 * nq : 512;
    while (u < uend) {
        for (int b = 0; b < 8 && no; b++)
            if (pos[b] == u) {
                P.list[n++] = mk_item(IT_OP, 1, 2 * b, 0, H[b], 0, 1);
                P.list[n++] = mk_item(IT_OP, 1, 2 * b, 0, H[b], 1, 1);
            }
        while (no && u >= uend - npos && kn * npos < (u + 1 - (uend - npos)) * nearly) {
            P.list[n++] = mk_item(IT_ON, 1, kn / 5 * 2, H[kn / 5], 32, kn % 5);
            kn++;
        }
        P.list[n++] = unit();
    }
    for (; no && kn < 40; kn++) P.list[n++] = mk_item(IT_ON, 1, kn / 5 * 2, H[kn / 5], 32, kn % 5);
    P.nlist = n;
}

}

extern "C" void kernel_launch(void* const* d_in, const int* in_sizes, int n_in, void* d_out, int out_size) {
    static Params P;
    static bool init = false;
    if (!init) {
        EncFn enc = nullptr;
        cudaDriverEntryPointQueryResult qr;
        cudaGetDriverEntryPoint("cuTensorMapEncodeTiled", (void**)&enc, cudaEnableDefault, &qr);
        for (int i = 0; i < 2; i++) {
            P.px[i] = (const __nv_bfloat16*)d_in[5 * i + 0];
            P.pk[i] = (const __nv_bfloat16*)d_in[5 * i + 1];
            P.pv[i] = (const __nv_bfloat16*)d_in[5 * i + 2];
            P.pwq[i] = (const __nv_bfloat16*)d_in[5 * i + 3];
            make_map3(enc, &P.x[i], d_in[5 * i + 0], 2560, 1280, 10, 160, 1);
            make_map3(enc, &P.k[i], d_in[5 * i + 1], 16 * 32 * 512, 384, 3, 64, 3);
            make_map3(enc, &P.v[i], d_in[5 * i + 2], 16 * 32 * 512, 384, 3, 64, 3);
            make_map3(enc, &P.wq[i], d_in[5 * i + 3], 640, 12288, 96, 32, 3);
            make_map3(enc, &P.wo[i], d_in[5 * i + 4], 6144, 1280, 10, 16, 5);
            make_map3(enc, &P.won[i], d_in[5 * i + 4], 6144, 1280, 10, 32, 2);
        }
        cuuint64_t dims[5] = {1280, 2, 4, 4, 80};
        cuuint64_t str[4] = {2560, 8 * 2560, 2 * 2560, 32 * 2560};
        cuuint32_t box[5] = {64, 2, 4, 4, 5};
        cuuint32_t es[5] = {1, 1, 1, 1, 1};
        enc(&P.out, CU_TENSOR_MAP_DATA_TYPE_BFLOAT16, 5, d_out, dims, str, box, es, CU_TENSOR_MAP_INTERLEAVE_NONE,
            CU_TENSOR_MAP_SWIZZLE_128B, CU_TENSOR_MAP_L2_PROMOTION_NONE, CU_TENSOR_MAP_FLOAT_OOB_FILL_NONE);
        build_schedule(P);
        cudaFuncSetAttribute(fused_kernel, cudaFuncAttributeMaxDynamicSharedMemorySize, SMEM_LAUNCH);
        init = true;
    }
    fused_kernel<<<NCTA, 384, SMEM_LAUNCH>>>(P);
}
```

```cpp
#include <cuda_runtime.h>
#include <cuda.h>
#include <cuda_bf16.h>
#include <stdint.h>

namespace {

constexpr int NCTA = 132;
constexpr int NCL = NCTA / 2;
constexpr int MAXI = 16;
constexpr int NSTAT = 3;
constexpr uint32_t IT_DYN = 0xffffffffu;
constexpr int SLOT = 24576;
constexpr int NSLOT = 5;
constexpr int XS = 20480;
constexpr int OFF_R = 0;
constexpr int OFF_RING = 5 * XS;
constexpr int OFF_MISC = OFF_RING + NSLOT * SLOT;
constexpr int OFF_LX = OFF_MISC;
constexpr int OFF_LINV = OFF_LX + 2560;
constexpr int OFF_FB = OFF_LINV + 640;
constexpr int OFF_GM = OFF_FB + 16;
constexpr int OFF_BAR = OFF_GM + 16;
constexpr int BAR_RFULL = OFF_BAR;
constexpr int BAR_REMPTY = BAR_RFULL + 40;
constexpr int BAR_XFULL = BAR_REMPTY + 40;
constexpr int BAR_XEMPTY = BAR_XFULL + 40;
constexpr int BAR_PRDY = BAR_XEMPTY + 40;
constexpr int BAR_ITEM = BAR_PRDY + 40;
constexpr int OFF_ITEM = BAR_ITEM + MAXI * 8;
constexpr int SMEM_BYTES = OFF_ITEM + MAXI * 4;
static_assert(SMEM_BYTES <= 232448, "smem");

constexpr int NB_W = 1  , NB_PFULL = 3  , NB_VOTE = 5  , NB_Q2 = 7, NB_SDONE = 8, NB_PDONE = 9,
              NB_L = 10, NB_REF = 11, NB_ODONE = 12, NB_OPEND = 13, NB_LX = 14, NB_Q01 = 15, NB_QK = 0  ;

constexpr uint32_t IT_QA = 1, IT_OP = 2, IT_ON = 3;
__host__ __device__ constexpr uint32_t mk_item(uint32_t type, uint32_t br, uint32_t b, uint32_t h0, uint32_t h1, uint32_t half,
                                               uint32_t part = 0) {
    return type | (br << 2) | (b << 3) | (h0 << 7) | (h1 << 13) | (half << 19) | (part << 22);
}
#define IT_TYPE(e) ((e) & 3u)
#define IT_BR(e) (((e) >> 2) & 1u)
#define IT_B(e) (((e) >> 3) & 15u)
#define IT_H0(e) (((e) >> 7) & 63u)
#define IT_H1(e) (((e) >> 13) & 63u)
#define IT_HALF(e) (((e) >> 19) & 7u)
#define IT_PART(e) (((e) >> 22) & 1u)
#define IT_SLOT(e) IT_H1(e)
#define IT_DEP(e) (((e) >> 23) & 127u)

struct Params {
    CUtensorMap x[2], wq[2], k[2], v[2], wo[2], won[2], out;
    const __nv_bfloat16 *px[2], *pwq[2], *pk[2], *pv[2];
    struct alignas(16) { uint32_t delay, items[NSTAT]; } cl[NCL];
    uint32_t nlist;
    uint8_t slot[64];
    uint32_t list[512];
};

constexpr int OUNIT = 61440;
__device__ __align__(1024) unsigned char g_ostash[(size_t)1024 * OUNIT];
__device__ unsigned int g_flag[32 * 64];
__device__ __forceinline__ unsigned char* ostash(uint32_t slot, uint32_t b) { return g_ostash + (slot * 16 + b) * OUNIT; }
__device__ unsigned int g_epoch[NCTA * 4];
__device__ unsigned int g_ticket[2];

constexpr int SMEM_LAUNCH = SMEM_BYTES;
#define TS(role, idx)
#define TS_ITEM(e)
#define TS_DUMP(role)
#define TSD(role, idx)

#define POL_W 2
#define POL_X 2
#define POL_O 2
template <int M>
__device__ __forceinline__ uint64_t mkpol() {
    uint64_t p;
    if (M == 0) asm volatile("createpolicy.fractional.L2::evict_normal.b64 %0, 1.0;" : "=l"(p));
    if (M == 1) asm volatile("createpolicy.fractional.L2::evict_first.b64 %0, 1.0;" : "=l"(p));
    if (M == 2) asm volatile("createpolicy.fractional.L2::evict_unchanged.b64 %0, 1.0;" : "=l"(p));
    if (M == 3) asm volatile("createpolicy.fractional.L2::evict_normal.L2::evict_unchanged.b64 %0, 0.25;" : "=l"(p));
    return p;
}
#define STSM_W 1
#define LASTORD 0
#define XLATE 2
#define PV0FIRST 1
#define QST0 1
#define QST1 2
#define QHOLD 8
constexpr float SM_C = 0.07216878364870322f * 1.4426950408889634f;

__device__ __forceinline__ uint32_t next_epoch(int warp) {
    unsigned int* p = &g_epoch[blockIdx.x * 4 + warp];
    const uint32_t e = __ldcg(p) + 1;
    *p = e;
    return e;
}

__device__ __forceinline__ uint32_t tid_now() {
    uint32_t t;
    asm volatile("mov.u32 %0, %%tid.x;" : "=r"(t));
    return t;
}
__device__ __forceinline__ void mbar_init(uint32_t a, uint32_t c) {
    asm volatile("mbarrier.init.shared::cta.b64 [%0], %1;" ::"r"(a), "r"(c) : "memory");
}
__device__ __forceinline__ void mbar_expect(uint32_t a, uint32_t b) {
    asm volatile("mbarrier.arrive.expect_tx.shared::cta.b64 _, [%0], %1;" ::"r"(a), "r"(b) : "memory");
}
template <int CNT = 1>
__device__ __forceinline__ void mbar_arrive_warp(uint32_t a) {
    if (CNT == 1)
        asm volatile("{\n.reg .pred p;\nelect.sync _|p, 0xffffffff;\n@p mbarrier.arrive.shared::cta.b64 _, [%0];\n}" ::"r"(a) : "memory");
    else
        asm volatile(
            "{\n.reg .pred p;\nelect.sync _|p, 0xffffffff;\n@p mbarrier.arrive.shared::cta.b64 _, [%0];\n"
            "@p mbarrier.arrive.shared::cta.b64 _, [%0];\n}" ::"r"(a)
            : "memory");
}
template <int CNT = 1>
__device__ __forceinline__ void mbar_arrive_warp_if(uint32_t a, bool cond) {
    if (CNT == 1)
        asm volatile(
            "{\n.reg .pred p, c;\nelect.sync _|p, 0xffffffff;\nsetp.ne.and.u32 c, %1, 0, p;\n"
            "@c mbarrier.arrive.shared::cta.b64 _, [%0];\n}" ::"r"(a), "r"((uint32_t)cond)
            : "memory");
    else
        asm volatile(
            "{\n.reg .pred p, c;\nelect.sync _|p, 0xffffffff;\nsetp.ne.and.u32 c, %1, 0, p;\n"
            "@c mbarrier.arrive.shared::cta.b64 _, [%0];\n@c mbarrier.arrive.shared::cta.b64 _, [%0];\n}" ::"r"(a), "r"((uint32_t)cond)
            : "memory");
}
__device__ __forceinline__ uint32_t deadline() {
    uint32_t c;
    asm volatile("mov.u32 %0, %%clock_hi;" : "=r"(c));
    return c + 4;
}
__device__ __forceinline__ void mbar_wait(uint32_t a, uint32_t ph, uint32_t dl) {
    asm volatile(
        "{\n.reg .pred p;\n.reg .u32 m;\n"
        "LOOP:\n"
        "mbarrier.try_wait.parity.shared::cta.b64 p, [%0], %1;\n"
        "@p bra DONE;\n"
        "mov.u32 m, %%clock_hi;\n"
        "setp.ne.u32 p, m, %2;\n"
        "@p bra LOOP;\n"
        "trap;\n"
        "DONE:\n}" ::"r"(a), "r"(ph), "r"(dl)
        : "memory");
}
template <int ID, int CNT>
__device__ __forceinline__ void nb_sync() { asm volatile("bar.sync %0, %1;" ::"n"(ID), "n"(CNT) : "memory"); }
template <int ID, int CNT>
__device__ __forceinline__ void nb_arrive() { asm volatile("bar.arrive %0, %1;" ::"n"(ID), "n"(CNT) : "memory"); }
__device__ __forceinline__ void fence_async_smem() { asm volatile("fence.proxy.async.shared::cta;" ::: "memory"); }

__device__ __forceinline__ void tma3(uint32_t dst, const CUtensorMap* m, int c1, int c2, uint32_t bar, uint64_t pol) {
    asm volatile(
        "cp.async.bulk.tensor.3d.shared::cluster.global.mbarrier::complete_tx::bytes.L2::cache_hint [%0], [%1, {%3,%4,%5}], [%2], %6;" ::"r"(dst),
        "l"(m), "r"(bar), "r"(0), "r"(c1), "r"(c2), "l"(pol)
        : "memory");
}
__device__ __forceinline__ void tma3_mc(uint32_t dst, const CUtensorMap* m, int c1, int c2, uint32_t bar, uint64_t pol) {
    asm volatile(
        "cp.async.bulk.tensor.3d.shared::cluster.global.mbarrier::complete_tx::bytes.multicast::cluster.L2::cache_hint"
        " [%0], [%1, {%3,%4,%5}], [%2], %6, %7;" ::"r"(dst),
        "l"(m), "r"(bar), "r"(0), "r"(c1), "r"(c2), "h"((unsigned short)3), "l"(pol)
        : "memory");
}
__device__ __forceinline__ void bulk_load(uint32_t dst, const void* src, uint32_t bytes, uint32_t bar, uint64_t pol) {
    asm volatile("cp.async.bulk.shared::cluster.global.mbarrier::complete_tx::bytes.L2::cache_hint [%0], [%1], %2, [%3], %4;" ::"r"(dst),
                 "l"(src), "r"(bytes), "r"(bar), "l"(pol)
                 : "memory");
}
__device__ __forceinline__ void wg_fence() { asm volatile("wgmma.fence.sync.aligned;" ::: "memory"); }
__device__ __forceinline__ void wg_commit() { asm volatile("wgmma.commit_group.sync.aligned;" ::: "memory"); }
template <int N>
__device__ __forceinline__ void wg_wait() { asm volatile("wgmma.wait_group.sync.aligned %0;" ::"n"(N) : "memory"); }

#define RW80(c, d) c(d[0]), c(d[1]), c(d[2]), c(d[3]), c(d[4]), c(d[5]), c(d[6]), c(d[7]), c(d[8]), c(d[9]), c(d[10]), c(d[11]), c(d[12]), c(d[13]), c(d[14]), c(d[15]), c(d[16]), c(d[17]), c(d[18]), c(d[19]), c(d[20]), c(d[21]), c(d[22]), c(d[23]), c(d[24]), c(d[25]), c(d[26]), c(d[27]), c(d[28]), c(d[29]), c(d[30]), c(d[31]), c(d[32]), c(d[33]), c(d[34]), c(d[35]), c(d[36]), c(d[37]), c(d[38]), c(d[39]), c(d[40]), c(d[41]), c(d[42]), c(d[43]), c(d[44]), c(d[45]), c(d[46]), c(d[47]), c(d[48]), c(d[49]), c(d[50]), c(d[51]), c(d[52]), c(d[53]), c(d[54]), c(d[55]), c(d[56]), c(d[57]), c(d[58]), c(d[59]), c(d[60]), c(d[61]), c(d[62]), c(d[63]), c(d[64]), c(d[65]), c(d[66]), c(d[67]), c(d[68]), c(d[69]), c(d[70]), c(d[71]), c(d[72]), c(d[73]), c(d[74]), c(d[75]), c(d[76]), c(d[77]), c(d[78]), c(d[79])
#define RW48(c, d) c(d[0]), c(d[1]), c(d[2]), c(d[3]), c(d[4]), c(d[5]), c(d[6]), c(d[7]), c(d[8]), c(d[9]), c(d[10]), c(d[11]), c(d[12]), c(d[13]), c(d[14]), c(d[15]), c(d[16]), c(d[17]), c(d[18]), c(d[19]), c(d[20]), c(d[21]), c(d[22]), c(d[23]), c(d[24]), c(d[25]), c(d[26]), c(d[27]), c(d[28]), c(d[29]), c(d[30]), c(d[31]), c(d[32]), c(d[33]), c(d[34]), c(d[35]), c(d[36]), c(d[37]), c(d[38]), c(d[39]), c(d[40]), c(d[41]), c(d[42]), c(d[43]), c(d[44]), c(d[45]), c(d[46]), c(d[47])
#define RW32(c, d) c(d[0]), c(d[1]), c(d[2]), c(d[3]), c(d[4]), c(d[5]), c(d[6]), c(d[7]), c(d[8]), c(d[9]), c(d[10]), c(d[11]), c(d[12]), c(d[13]), c(d[14]), c(d[15]), c(d[16]), c(d[17]), c(d[18]), c(d[19]), c(d[20]), c(d[21]), c(d[22]), c(d[23]), c(d[24]), c(d[25]), c(d[26]), c(d[27]), c(d[28]), c(d[29]), c(d[30]), c(d[31])

__device__ __forceinline__ void reg_fence(float (&d)[80]) { asm volatile("" : RW80("+f", d)::"memory"); }
__device__ __forceinline__ void reg_fence(float (&d)[48]) { asm volatile("" : RW48("+f", d)::"memory"); }
__device__ __forceinline__ void reg_fence(float (&d)[32]) { asm volatile("" : RW32("+f", d)::"memory"); }

template <int NR>
__device__ __forceinline__ void zero(float (&d)[NR]) {
#pragma unroll
    for (int i = 0; i < NR; i++) d[i] = 0.f;
}

constexpr uint32_t HI_SW128 = (1024u >> 4) | (1u << 30);
constexpr uint32_t HI_OST = (2560u >> 4) | (2u << 30);
constexpr uint32_t LO_LBO1 = (1u << 16);
constexpr uint32_t LO_OST = ((512u >> 4) << 16);

template <int TA, int TB, uint32_t HIB, int ACC>
__device__ __forceinline__ void wgmma(float (&d)[80], uint32_t loA, uint32_t loB) {
#define WG_ASM(SD)                                                          \
    "{\n.reg .b64 da, db;\nmov.b64 da, {%80, %82};\nmov.b64 db, {%81, %83};\n" \
    "wgmma.mma_async.sync.aligned.m64n160k16.f32.bf16.bf16 "               \
    "{%0,%1,%2,%3,%4,%5,%6,%7,%8,%9,%10,%11,%12,%13,%14,%15,%16,%17,%18,%19,%20,%21,%22,%23,%24,%25,%26,%27,%28,%29,%30,%31,%32,%33,%34,%35,%36,%37,%38,%39,%40,%41,%42,%43,%44,%45,%46,%47,%48,%49,%50,%51,%52,%53,%54,%55,%56,%57,%58,%59,%60,%61,%62,%63,%64,%65,%66,%67,%68,%69,%70,%71,%72,%73,%74,%75,%76,%77,%78,%79}, da, db, " SD ", 1, 1, %84, %85;\n}"
    if constexpr (ACC == 2)
        asm volatile(WG_ASM("0") : RW80("+f", d) : "r"(loA), "r"(loB), "n"(HI_SW128), "n"(HIB), "n"(TA), "n"(TB));
    else if constexpr (ACC == 1)
        asm volatile(WG_ASM("1") : RW80("+f", d) : "r"(loA), "r"(loB), "n"(HI_SW128), "n"(HIB), "n"(TA), "n"(TB));
    else
        asm volatile(WG_ASM("0") : RW80("=f", d) : "r"(loA), "r"(loB), "n"(HI_SW128), "n"(HIB), "n"(TA), "n"(TB));
#undef WG_ASM
}
template <int TA, int TB, uint32_t HIB, int ACC>
__device__ __forceinline__ void wgmma(float (&d)[48], uint32_t loA, uint32_t loB) {
#define WG_ASM(SD)                                                          \
    "{\n.reg .b64 da, db;\nmov.b64 da, {%48, %50};\nmov.b64 db, {%49, %51};\n" \
    "wgmma.mma_async.sync.aligned.m64n96k16.f32.bf16.bf16 "               \
    "{%0,%1,%2,%3,%4,%5,%6,%7,%8,%9,%10,%11,%12,%13,%14,%15,%16,%17,%18,%19,%20,%21,%22,%23,%24,%25,%26,%27,%28,%29,%30,%31,%32,%33,%34,%35,%36,%37,%38,%39,%40,%41,%42,%43,%44,%45,%46,%47}, da, db, " SD ", 1, 1, %52, %53;\n}"
    if constexpr (ACC == 1)
        asm volatile(WG_ASM("1") : RW48("+f", d) : "r"(loA), "r"(loB), "n"(HI_SW128), "n"(HIB), "n"(TA), "n"(TB));
    else
        asm volatile(WG_ASM("0") : RW48("=f", d) : "r"(loA), "r"(loB), "n"(HI_SW128), "n"(HIB), "n"(TA), "n"(TB));
#undef WG_ASM
}
template <int TA, int TB, uint32_t HIB, int ACC>
__device__ __forceinline__ void wgmma(float (&d)[32], uint32_t loA, uint32_t loB) {
#define WG_ASM(SD)                                                          \
    "{\n.reg .b64 da, db;\nmov.b64 da, {%32, %34};\nmov.b64 db, {%33, %35};\n" \
    "wgmma.mma_async.sync.aligned.m64n64k16.f32.bf16.bf16 "               \
    "{%0,%1,%2,%3,%4,%5,%6,%7,%8,%9,%10,%11,%12,%13,%14,%15,%16,%17,%18,%19,%20,%21,%22,%23,%24,%25,%26,%27,%28,%29,%30,%31}, da, db, " SD ", 1, 1, %36, %37;\n}"
    if constexpr (ACC == 1)
        asm volatile(WG_ASM("1") : RW32("+f", d) : "r"(loA), "r"(loB), "n"(HI_SW128), "n"(HIB), "n"(TA), "n"(TB));
    else
        asm volatile(WG_ASM("0") : RW32("=f", d) : "r"(loA), "r"(loB), "n"(HI_SW128), "n"(HIB), "n"(TA), "n"(TB));
#undef WG_ASM
}

__device__ __forceinline__ uint32_t pack_bf16(float lo, float hi) {
    uint32_t r;
    asm("cvt.rn.bf16x2.f32 %0, %1, %2;" : "=r"(r) : "f"(hi), "f"(lo));
    return r;
}
__device__ __forceinline__ float ex2(float x) {
    float r;
    asm("ex2.approx.ftz.f32 %0, %1;" : "=f"(r) : "f"(x));
    return r;
}
__device__ __forceinline__ void stsm4t(uint32_t a, uint32_t r0, uint32_t r1, uint32_t r2, uint32_t r3) {
    asm volatile("stmatrix.sync.aligned.m8n8.x4.trans.shared.b16 [%0], {%1,%2,%3,%4};" ::"r"(a), "r"(r0), "r"(r1), "r"(r2), "r"(r3)
                 : "memory");
}
__device__ __forceinline__ uint32_t lds_u(uint32_t a) {
    uint32_t v;
    asm volatile("ld.shared.u32 %0, [%1];" : "=r"(v) : "r"(a) : "memory");
    return v;
}
__device__ __forceinline__ uint4 lds_u4(uint32_t a) {
    uint4 v;
    asm volatile("ld.shared.v4.u32 {%0,%1,%2,%3}, [%4];" : "=r"(v.x), "=r"(v.y), "=r"(v.z), "=r"(v.w) : "r"(a) : "memory");
    return v;
}
__device__ __forceinline__ float2 lds_f2(uint32_t a) {
    float2 v;
    asm volatile("ld.shared.v2.f32 {%0,%1}, [%2];" : "=f"(v.x), "=f"(v.y) : "r"(a) : "memory");
    return v;
}
__device__ __forceinline__ void sts_f(uint32_t a, float v) { asm volatile("st.shared.f32 [%0], %1;" ::"r"(a), "f"(v) : "memory"); }
__device__ __forceinline__ void sts_u(uint32_t a, uint32_t v) { asm volatile("st.shared.u32 [%0], %1;" ::"r"(a), "r"(v) : "memory"); }
__device__ __forceinline__ void sts_f2(uint32_t a, float x, float y) {
    asm volatile("st.shared.v2.f32 [%0], {%1,%2};" ::"r"(a), "f"(x), "f"(y) : "memory");
}

template <bool ADD = false, bool SIG = false, int NR>
__device__ __forceinline__ void store_tile_t(const float (&d)[NR], uint32_t addr) {
    uint32_t p[NR / 2];
    if (ADD) {
#pragma unroll
        for (int j = 0; j < NR / 8; j++)
            asm volatile("ldmatrix.sync.aligned.m8n8.x4.trans.shared.b16 {%0,%1,%2,%3}, [%4];"
                         : "=r"(p[4 * j]), "=r"(p[4 * j + 1]), "=r"(p[4 * j + 2]), "=r"(p[4 * j + 3])
                         : "r"(addr + j * 2048)
                         : "memory");
    }
#pragma unroll
    for (int k = 0; k < NR / 2; k++)
        p[k] = ADD ? pack_bf16(d[2 * k] + __uint_as_float(p[k] << 16), d[2 * k + 1] + __uint_as_float(p[k] & 0xffff0000u))
                   : pack_bf16(d[2 * k], d[2 * k + 1]);
#pragma unroll
    for (int j = 0; j < NR / 8; j++) {
        stsm4t(addr + j * 2048, p[4 * j], p[4 * j + 1], p[4 * j + 2], p[4 * j + 3]);
        if (SIG && j == 0) nb_arrive<NB_L, 160>();
    }
}

struct TrueT { static constexpr bool value = true; };
struct FalseT { static constexpr bool value = false; };

template <int V>
struct IntT { static constexpr int value = V; };

__device__ __forceinline__ uint32_t get_item(uint32_t sb, int it, uint32_t dl) {
    mbar_wait(sb + BAR_ITEM + it * 8, 0, dl);
    return lds_u(sb + OFF_ITEM + it * 4);
}
__device__ __forceinline__ uint32_t get_item_warp(uint32_t sb, int it, uint32_t dl) {
    return __shfl_sync(0xffffffffu, get_item(sb, it, dl), 0);
}

struct Ring {
    uint32_t slot, ph, dl;
    __device__ __forceinline__ void adv(uint32_t k) {
        slot += k;
        if (slot >= NSLOT) { slot -= NSLOT; ph ^= 1; }
    }
};

template <int K>
__device__ __forceinline__ void qk_step(float (&s)[80], uint32_t loK, uint32_t loQ) {
    wgmma<0, 0, HI_SW128, K != 0>(s, loK + (K >> 2) * (8192 >> 4) + (K & 3) * 2, loQ + (K >> 2) * (XS >> 4) + (K & 3) * 2);
}
template <int K0, int K1>
__device__ __forceinline__ void qk_steps(float (&s)[80], uint32_t loK, uint32_t loQ) {
    if constexpr (K0 < K1) {
        qk_step<K0>(s, loK, loQ);
        qk_steps<K0 + 1, K1>(s, loK, loQ);
    }
}
__device__ __forceinline__ uint32_t add_bf2(uint32_t a, uint32_t b) {
    uint32_t r;
    asm("add.rn.bf16x2 %0, %1, %2;" : "=r"(r) : "r"(a), "r"(b));
    return r;
}
__device__ __forceinline__ uint32_t fma_bf2(uint32_t a, uint32_t b, uint32_t c) {
    uint32_t r;
    asm("fma.rn.bf16x2 %0, %1, %2, %3;" : "=r"(r) : "r"(a), "r"(b), "r"(c));
    return r;
}
template <int J>
__device__ __forceinline__ void exp_block(const float (&s)[80], uint32_t (&k)[40], uint32_t pa, float mref) {
    if constexpr (J < 10) {
#pragma unroll
        for (int i = 4 * J; i < 4 * J + 4; i++)
            k[i] = pack_bf16(ex2(fmaf(s[2 * i], SM_C, -mref)), ex2(fmaf(s[2 * i + 1], SM_C, -mref)));
#pragma unroll
        for (int i = 0; i < 4; i++)
            asm volatile("stmatrix.sync.aligned.m8n8.x1.trans.shared.b16 [%0], {%1};" ::"r"(((i & 1) ? pa ^ 16 : pa) + J * 2048 + (i >> 1) * 1024),
                         "r"(k[4 * J + i])
                         : "memory");
        exp_block<J + 1>(s, k, pa, mref);
    }
}
__device__ __forceinline__ void sum_block(const uint32_t (&k)[40], float (&l)[10], uint32_t lane) {
    const bool b4 = lane & 16, b3 = lane & 8;
    uint32_t ps[20], t[10];
#pragma unroll
    for (int j = 0; j < 20; j++) ps[j] = add_bf2(k[2 * j], k[2 * j + 1]);
#pragma unroll
    for (int j = 0; j < 10; j++)
        t[j] = add_bf2(b4 ? ps[2 * j + 1] : ps[2 * j], __shfl_xor_sync(0xffffffffu, b4 ? ps[2 * j] : ps[2 * j + 1], 16));
#pragma unroll
    for (int i = 0; i < 5; i++) {
        const uint32_t a = b3 ? t[i + 5] : t[i], b = __shfl_xor_sync(0xffffffffu, b3 ? t[i] : t[i + 5], 8);
        l[2 * i] += __uint_as_float(a << 16) + __uint_as_float(b << 16);
        l[2 * i + 1] += __uint_as_float(a & 0xffff0000u) + __uint_as_float(b & 0xffff0000u);
    }
}
template <bool ADD>
__device__ __forceinline__ void sum_store(const float (&l)[10], uint32_t lane, uint32_t lxa) {
    const bool b2 = lane & 4;
    float t[5];
#pragma unroll
    for (int i = 0; i < 5; i++) t[i] = ADD ? __uint_as_float(lds_u(lxa + i * 64)) : 0.f;
#pragma unroll
    for (int i = 0; i < 5; i++)
        sts_f(lxa + i * 64, t[i] + (b2 ? l[2 * i + 1] : l[2 * i]) + __shfl_xor_sync(0xffffffffu, b2 ? l[2 * i] : l[2 * i + 1], 4));
}

__device__ __forceinline__ void fallback_unit(const Params& P, uint32_t e, uint32_t tid) {
    const uint32_t lane = tid & 31, br = IT_BR(e), b = IT_B(e), h = IT_H0(e);
    const __nv_bfloat162* wq = (const __nv_bfloat162*)(P.pwq[br] + h * 192) + lane;
    const __nv_bfloat162* kp = (const __nv_bfloat162*)(P.pk[br] + (size_t)(b * 32 + h) * 512 * 192) + lane;
    const __nv_bfloat162* vp = (const __nv_bfloat162*)(P.pv[br] + (size_t)(b * 32 + h) * 512 * 192) + lane;
#pragma unroll 1
    for (uint32_t qi = 0; qi < 40; qi++) {
        const uint32_t q = 4 * qi + (tid >> 5);
        const __nv_bfloat16* xr = P.px[br] + (size_t)(b * 160 + q) * 640;
        float a[6] = {0.f, 0.f, 0.f, 0.f, 0.f, 0.f};
#pragma unroll 2
        for (int k = 0; k < 640; k++) {
            const float xv = __bfloat162float(xr[k]);
#pragma unroll
            for (int i = 0; i < 3; i++) {
                const float2 wv = __bfloat1622float2(wq[(size_t)k * 3072 + i * 32]);
                a[2 * i] = fmaf(xv, wv.x, a[2 * i]);
                a[2 * i + 1] = fmaf(xv, wv.y, a[2 * i + 1]);
            }
        }
#pragma unroll
        for (int i = 0; i < 6; i++) a[i] = __bfloat162float(__float2bfloat16(a[i]));
        auto score = [&](int key) {
            float d = 0.f;
#pragma unroll
            for (int i = 0; i < 3; i++) {
                const float2 kv = __bfloat1622float2(kp[key * 96 + i * 32]);
                d = fmaf(a[2 * i], kv.x, fmaf(a[2 * i + 1], kv.y, d));
            }
#pragma unroll
            for (int o = 16; o > 0; o >>= 1) d += __shfl_xor_sync(0xffffffffu, d, o);
            return d;
        };
        float m = -INFINITY, o[6] = {0.f, 0.f, 0.f, 0.f, 0.f, 0.f}, sum = 0.f;
#pragma unroll 1
        for (int n = 0; n < 1024; n++) {
            const int key = n & 511;
            const float d = score(key);
            if (n < 512) {
                m = fmaxf(m, d);
            } else {
                const float p = ex2((d - m) * SM_C);
                sum += p;
#pragma unroll
                for (int i = 0; i < 3; i++) {
                    const float2 vv = __bfloat1622float2(vp[key * 96 + i * 32]);
                    o[2 * i] = fmaf(p, vv.x, o[2 * i]);
                    o[2 * i + 1] = fmaf(p, vv.y, o[2 * i + 1]);
                }
            }
        }
        const float inv = __fdividef(1.f, sum);
        __nv_bfloat16* op = (__nv_bfloat16*)ostash(IT_SLOT(e), b) + (q >> 5) * 256 + 2 * ((q & 31) >> 3) + (q & 1);
#pragma unroll
        for (int i = 0; i < 6; i++) {
            const uint32_t d = (i >> 1) * 64 + 2 * lane + (i & 1);
            op[(d >> 3) * 1280 + (d & 7) * 32 + ((((q & 7) >> 1) ^ ((d & 7) >> 1)) << 3)] = __float2bfloat16(o[i] * inv);
        }
    }
}

template <int W>
struct PendO {
    static constexpr int N = W == 0 ? 56 : 64;
    uint32_t v[N];
    unsigned char* gp;
    static __device__ __forceinline__ uint32_t toff() {
        const uint32_t t = tid_now();
        return ((t >> 5) & 3) * 5120 + ((t >> 2) & 7) * 64 + (((t ^ (t >> 3)) & 3) << 4);
    }
    uint32_t pend, sig, bad;
    static __device__ __forceinline__ void scale(uint32_t& x, uint32_t hi, uint32_t lo) {
        asm("{\n.reg .b32 t;\nmul.rn.bf16x2 t, %0, %2;\nfma.rn.bf16x2 %0, %0, %1, t;\n}" : "+r"(x) : "r"(hi), "r"(lo));
    }
    template <int I, int OFF>
    __device__ __forceinline__ void put() {
        asm volatile("{\n.reg .pred p;\nsetp.ne.u32 p, %6, 0;\n@p st.global.v4.b32 [%0+%5], {%1,%2,%3,%4};\n}" ::"l"(gp), "r"(v[I]),
                     "r"(v[I + 1]), "r"(v[I + 2]), "r"(v[I + 3]), "n"(OFF), "r"(pend)
                     : "memory");
    }
    __device__ __forceinline__ void verdict(uint32_t sb) {
        if (sig) {
            nb_sync<NB_VOTE + W, 160>();
            bad = __any_sync(0xffffffffu, lds_u(sb + OFF_FB) != 0);
            pend = !bad;
        }
    }
    template <int G, int H>
    __device__ __forceinline__ void half(uint32_t sb) {
        constexpr bool T2 = W == 0 ? G >= 3 : G < 3;
        constexpr int B = T2 ? 40 + 8 * (W == 0 ? G - 3 : G) : 0;
        const uint4 a = lds_u4(sb + OFF_LINV + G * 128 + H * 16 + (threadIdx.x & 3) * 32);
#pragma unroll
        for (int i = 2 * H; i < 8; i += 4) {
            scale(v[8 * G + i], a.x, a.y);
            scale(v[8 * G + i + 1], a.z, a.w);
            if (T2) {
                scale(v[B + i], a.x, a.y);
                scale(v[B + i + 1], a.z, a.w);
            }
        }
        if (H == 1) {
            put<8 * G, W * XS + G * 512>();
            put<8 * G + 4, W * XS + G * 512 + 2560>();
            if (T2) {
                put<B, 2 * XS + G * 512>();
                put<B + 4, 2 * XS + G * 512 + 2560>();
            }
            if (G == 4 && pend) nb_arrive<NB_ODONE, 288>();
        }
    }
    template <int G>
    __device__ __forceinline__ void step(uint32_t sb) {
        half<G, 0>(sb);
        half<G, 1>(sb);
    }
    __device__ __forceinline__ void clear() {
#pragma unroll
        for (int i = 0; i < N; i++) v[i] = 0;
        gp = nullptr;
        pend = 0;
        sig = 0;
        bad = 0;
    }
};

__device__ __forceinline__ uint32_t stsm_off() {
    const uint32_t tid = tid_now(), lane = tid & 31;
    return (lane >> 4) * 1024 + (lane & 7) * 128 + (((((tid >> 4) & 6) + ((lane >> 3) & 1)) ^ (lane & 7)) << 4);
}
template <int W, int KK>
__device__ __forceinline__ void qproj(float (&q0)[80], float (&q1)[80], uint32_t sb, Ring& r, uint32_t pslot, uint32_t phm,
                                      PendO<W>& po) {
    const uint32_t loR = (((sb + OFF_R) & 0x3ffff) >> 4) | LO_LBO1;
    const uint32_t loRing = (((sb + OFF_RING) & 0x3ffff) >> 4) | LO_LBO1;
    auto ready = [&](int k) {
        mbar_wait(sb + BAR_RFULL + r.slot * 8, r.ph, r.dl);
        mbar_wait(sb + BAR_XFULL + (k % 5) * 8, ((phm >> (k % 5)) ^ (k / 5)) & 1, r.dl);
    };
    auto release = [&]() {
        if (KK > 0) {
            wg_wait<1>();
            mbar_arrive_warp(sb + BAR_REMPTY + pslot * 8);
            if (KK <= 5) mbar_arrive_warp(sb + (BAR_XEMPTY + (KK - 1) * 8));
        }
    };
    if (KK == 0 && (W == 1 || !po.sig)) ready(0);
    if (W == 1 && KK == QHOLD) {
        if (QHOLD == 7) {
            wg_wait<0>();
            nb_arrive<NB_PDONE, 256>();
        }
        nb_sync<NB_SDONE, 256>();
    }
    const uint32_t a = loRing + r.slot * (SLOT >> 4) + (W == 0 ? 0 : 512), b = loR + (KK % 5) * (XS >> 4);
    wg_fence();
    wgmma<1, 0, HI_SW128, KK != 0>(q0, a, b);
    if (W == 0) wgmma<1, 0, HI_SW128, KK != 0>(q1, a + 256, b);
#pragma unroll
    for (int k = 1; k < 4; k++) {
        wgmma<1, 0, HI_SW128, true>(q0, a + (k >> 1) * 768 + (k & 1) * 128, b + k * 2);
        if (W == 0) wgmma<1, 0, HI_SW128, true>(q1, a + 256 + (k >> 1) * 768 + (k & 1) * 128, b + k * 2);
    }
    wg_commit();
    const uint32_t cslot = r.slot;
    r.adv(1);
    if (W == 0 || KK < QHOLD) release();
    if (KK == QST0) {
        po.verdict(sb);
        po.template half<0, 0>(sb);
    }
    if (KK < 9) ready(KK + 1);
    if (W == 1 && KK >= QHOLD) release();
    if (W == 1 && KK == 7 && QHOLD > 7) nb_arrive<NB_PDONE, 256>();
    if (KK == QST0) po.template half<0, 1>(sb);
    if constexpr (KK > QST0 && KK < QST0 + 5) po.template step<KK - QST0>(sb);
    if constexpr (KK < (W == 0 ? 7 : 9)) {
        qproj<W, KK + 1>(q0, q1, sb, r, cslot, phm, po);
    } else if constexpr (W == 1) {
        wg_wait<0>();
        reg_fence(q0);
        mbar_arrive_warp(sb + BAR_REMPTY + cslot * 8);
        store_tile_t<false, true>(q0, sb + OFF_R + 2 * XS + stsm_off());
    } else {
        const uint32_t s8 = r.slot, a8 = loRing + s8 * (SLOT >> 4);
        wg_fence();
#pragma unroll
        for (int k = 0; k < 4; k++) wgmma<1, 0, HI_SW128, true>(q0, a8 + (k >> 1) * 768 + (k & 1) * 128, loR + 3 * (XS >> 4) + k * 2);
        r.adv(1);
        ready(9);
        const uint32_t s9 = r.slot, a9 = loRing + s9 * (SLOT >> 4);
        r.adv(1);
        wg_fence();
#pragma unroll
        for (int k = 0; k < 4; k++) wgmma<1, 0, HI_SW128, true>(q0, a9 + (k >> 1) * 768 + (k & 1) * 128, loR + 4 * (XS >> 4) + k * 2);
        wg_commit();
        wg_wait<1>();
        mbar_arrive_warp(sb + BAR_REMPTY + cslot * 8);
        wg_fence();
#pragma unroll
        for (int k = 0; k < 8; k++)
            wgmma<1, 0, HI_SW128, true>(q1, (k < 4 ? a8 : a9) + 256 + ((k >> 1) & 1) * 768 + (k & 1) * 128,
                                        loR + (3 + (k >> 2)) * (XS >> 4) + (k & 3) * 2);
        wg_commit();
        nb_arrive<NB_SDONE, 256>();
        nb_sync<NB_PDONE, 256>();
        wg_wait<1>();
        reg_fence(q0);
        const uint32_t sta = sb + OFF_R + stsm_off();
        store_tile_t(q0, sta);
        sts_u(sb + OFF_GM + 4, r.slot);
        mbar_wait(sb + BAR_RFULL + r.slot * 8, r.ph, r.dl);
        wg_wait<0>();
        reg_fence(q1);
        mbar_arrive_warp(sb + BAR_REMPTY + s8 * 8);
        mbar_arrive_warp(sb + BAR_REMPTY + s9 * 8);
        store_tile_t(q1, sta + XS);
    }
}

template <int NR>
__device__ __forceinline__ void opack(const float (&o)[NR], uint32_t* v) {
#pragma unroll
    for (int g = 0; g < NR / 16; g++)
#pragma unroll
        for (int hh = 0; hh < 2; hh++)
#pragma unroll
            for (int t = 0; t < 4; t++) v[8 * g + 4 * hh + t] = pack_bf16(o[16 * g + 4 * t + 2 * hh], o[16 * g + 4 * t + 2 * hh + 1]);
}

template <bool IS_S>
__device__ __forceinline__ void op_item(uint32_t e, uint32_t sb, Ring& r, uint32_t& phm) {
    constexpr int T0 = IS_S ? 0 : 2;
    constexpr uint32_t BOFF = IS_S ? (3 * 512) >> 4 : 0;
    const uint32_t loRing = (((sb + OFF_RING) & 0x3ffff) >> 4) | LO_LBO1;
    const uint32_t loO = (((sb + OFF_R) & 0x3ffff) >> 4) | LO_OST;
    float c0[80], c1[80], c2[IS_S ? 32 : 48];
    const int T = 3 * (IT_H1(e) - IT_H0(e));
    uint32_t xs = 0;
    auto step = [&](auto first, auto half) {
        constexpr bool F = decltype(first)::value;
        constexpr uint32_t hf = decltype(half)::value;
        if (hf == 0) {
            mbar_wait(sb + BAR_XFULL + xs * 8, (phm >> xs) & 1, r.dl);
            phm ^= 1u << xs;
        }
        mbar_wait(sb + BAR_RFULL + r.slot * 8, r.ph, r.dl);
        const uint32_t a = loRing + r.slot * (SLOT >> 4), b = loO + xs * (XS >> 4) + hf * 640;
        wg_fence();
        wgmma<1, 1, HI_OST, !F>(c0, a + T0 * 128, b);
        wgmma<1, 1, HI_OST, !F>(c1, a + T0 * 128 + 128, b);
        wgmma<1, 1, HI_OST, !F>(c2, a + 512, b + BOFF);
        wgmma<1, 1, HI_OST, true>(c0, a + 640 + T0 * 128, b + 320);
        wgmma<1, 1, HI_OST, true>(c1, a + 640 + T0 * 128 + 128, b + 320);
        wgmma<1, 1, HI_OST, true>(c2, a + 640 + 512, b + 320 + BOFF);
        wg_commit();
    };
    step(TrueT{}, IntT<0>{});
#pragma unroll 1
    for (int t = 1;; t++) {
        uint32_t pslot = r.slot;
        r.adv(1);
        step(FalseT{}, IntT<1>{});
        wg_wait<1>();
        mbar_arrive_warp(sb + BAR_REMPTY + pslot * 8);
        if (t == T) break;
        pslot = r.slot;
        const uint32_t pxs = xs;
        r.adv(1);
        if (++xs == 5) xs = 0;
        step(FalseT{}, IntT<0>{});
        wg_wait<1>();
        mbar_arrive_warp(sb + BAR_REMPTY + pslot * 8);
        mbar_arrive_warp_if(sb + BAR_XEMPTY + pxs * 8, t + 4 < T);
    }
    wg_wait<0>();
    reg_fence(c0);
    reg_fence(c1);
    reg_fence(c2);
    mbar_arrive_warp(sb + BAR_REMPTY + r.slot * 8);
    r.adv(1);
    nb_sync<NB_OPEND, 256>();
    const uint32_t sta = sb + OFF_R + stsm_off();
    store_tile_t(c0, sta + T0 * XS);
    store_tile_t(c1, sta + (T0 + 1) * XS);
    store_tile_t(c2, sta + 4 * XS + (IS_S ? 96 * 128 : 0));
    fence_async_smem();
    nb_arrive<NB_ODONE, 288>();
}

__device__ __forceinline__ void on_item(uint32_t W, uint32_t e, uint32_t sb, Ring& r, uint32_t& phm) {
    const uint32_t loRing = (((sb + OFF_RING) & 0x3ffff) >> 4) | LO_LBO1;
    const uint32_t loO = (((sb + OFF_R) & 0x3ffff) >> 4) | LO_OST;
    float c[80];
    const int T = 3 * (IT_H1(e) - IT_H0(e));
    uint32_t xs = 0;
    auto step = [&](auto first) {
        constexpr bool F = decltype(first)::value;
        mbar_wait(sb + BAR_XFULL + xs * 8, (phm >> xs) & 1, r.dl);
        phm ^= 1u << xs;
        mbar_wait(sb + BAR_RFULL + r.slot * 8, r.ph, r.dl);
        const uint32_t a = loRing + r.slot * (SLOT >> 4) + W * 256, b = loO + xs * (XS >> 4);
        wg_fence();
        wgmma<1, 1, HI_OST, !F>(c, a, b);
#pragma unroll
        for (int k = 1; k < 4; k++) wgmma<1, 1, HI_OST, true>(c, a + (k >> 1) * 512 + (k & 1) * 128, b + k * 320);
        wg_commit();
    };
    step(TrueT{});
#pragma unroll 1
    for (int t = 1; t < T; t++) {
        const uint32_t pslot = r.slot, pxs = xs;
        r.adv(1);
        if (++xs == 5) xs = 0;
        step(FalseT{});
        wg_wait<1>();
        mbar_arrive_warp(sb + BAR_REMPTY + pslot * 8);
        mbar_arrive_warp_if(sb + BAR_XEMPTY + pxs * 8, t + 2 < T);
    }
    xs += 1 + W;
    if (xs >= 5) xs -= 5;
    mbar_wait(sb + BAR_XFULL + xs * 8, (phm >> xs) & 1, r.dl);
    wg_wait<0>();
    reg_fence(c);
    store_tile_t<true>(c, sb + OFF_R + xs * XS + stsm_off());
    fence_async_smem();
    nb_arrive<NB_ODONE, 288>();
}

template <int W>
__device__ __forceinline__ uint32_t qa_item(uint32_t e, uint32_t sb, Ring& r, uint32_t phm, PendO<W>& po, int it) {
    const uint32_t loR = (((sb + OFF_R) & 0x3ffff) >> 4) | LO_LBO1;
    const uint32_t loRing = (((sb + OFF_RING) & 0x3ffff) >> 4) | LO_LBO1;
    {
        float q0[80], q1[80];
        qproj<W, 0>(q0, q1, sb, r, 0, phm, po);
    }
    fence_async_smem();
    TSD(W, 1);
    float s[80], oa[80], ob[W == 0 ? 32 : 48], l[10];
    if (W == 1) {
        nb_arrive<NB_Q2, 256>();
        zero(oa);
        zero(ob);
        reg_fence(oa);
        reg_fence(ob);
    }
    const uint32_t lane = tid_now() & 31, sta = sb + OFF_R + stsm_off();
    auto pv = [&](auto first, uint32_t buf) {
        constexpr bool F = decltype(first)::value;
        mbar_wait(sb + BAR_RFULL + r.slot * 8, r.ph, r.dl);
        const uint32_t a = loRing + r.slot * (SLOT >> 4), b = loR + (3 + buf) * (XS >> 4);
        wg_fence();
        wgmma<1, 0, HI_SW128, !F>(oa, a + W * 512, b);
        wgmma<1, 0, HI_SW128, !F>(ob, a + 1024, b + (W == 0 ? (96 * 128) >> 4 : 0));
#pragma unroll
        for (int k = 1; k < 4; k++) {
            wgmma<1, 0, HI_SW128, true>(oa, a + W * 512 + k * 128, b + k * 2);
            wgmma<1, 0, HI_SW128, true>(ob, a + 1024 + k * 128, b + (W == 0 ? (96 * 128) >> 4 : 0) + k * 2);
        }
        wg_commit();
    };
    zero(l);
    float mref;
    uint32_t kslot, vslot;
    auto tail = [&](auto first, int i) {
        constexpr bool rel_other = !decltype(first)::value;
        uint32_t ps[40];
        exp_block<0>(s, ps, sta + (3 + W) * XS, mref);
        if (rel_other) {
            wg_wait<0>();
            mbar_arrive_warp(sb + BAR_REMPTY + vslot * 8);
            if (W == 1) mbar_arrive_warp_if(sb + BAR_XEMPTY + 24, i == 3);
        }
        fence_async_smem();
        nb_arrive<NB_PFULL + W, 256>();
        TSD(W, 6 + 5 * i);
        if (W == 1) {
            if (XLATE >= 2) mbar_arrive_warp_if<2>(sb + BAR_XEMPTY + 8, i == 3);
            if (XLATE >= 1) mbar_arrive_warp_if<2>(sb + BAR_XEMPTY + 16, i == 3);
        }
        if (rel_other || !PV0FIRST) {
            mbar_wait(sb + BAR_RFULL + r.slot * 8, r.ph, r.dl);
            sum_block(ps, l, lane);
        }
        TSD(W, 7 + 5 * i);
        if (LASTORD && W == 0 && i == 3) nb_sync<NB_PDONE, 256>();
        else nb_sync<NB_W + W, 128>();
        pv(first, W);
        if (!rel_other && PV0FIRST) sum_block(ps, l, lane);
        TSD(W, 8 + 5 * i);
    };
    if (W == 0) {
        nb_sync<NB_QK, 160>();
        TSD(W, 2);
        wg_fence();
        qk_steps<0, 8>(s, loRing + r.slot * (SLOT >> 4), loR);
        nb_sync<NB_Q2, 256>();
        qk_steps<8, 12>(s, loRing + r.slot * (SLOT >> 4), loR);
        wg_commit();
        nb_arrive<NB_Q01, 256>();
        TSD(W, 4);
        nb_sync<NB_REF, 160>();
        mref = __uint_as_float(lds_u(sb + OFF_GM));
        wg_wait<0>();
        reg_fence(s);
        mbar_arrive_warp<2>(sb + BAR_REMPTY + r.slot * 8);
        r.adv(2);
        TSD(W, 5);
        tail(TrueT{}, 0);
    } else {
        nb_sync<NB_Q01, 256>();
    }
#pragma unroll 1
    for (int i = (W == 0 ? 1 : 0); i < 4; i++) {
        const uint32_t pvslot = r.slot;
        r.adv(1);
        kslot = r.slot;
        mbar_wait(sb + BAR_RFULL + r.slot * 8, r.ph, r.dl);
        wg_fence();
        qk_steps<0, 12>(s, loRing + r.slot * (SLOT >> 4), loR);
        wg_commit();
        wg_wait<1>();
        mbar_arrive_warp_if(sb + BAR_REMPTY + pvslot * 8, W == 0 || i > 0);
        r.adv(1);
        vslot = r.slot;
        TSD(W, 4 + 5 * i);
        nb_sync<NB_PFULL + (W ^ 1), 256>();
        pv(FalseT{}, W ^ 1);
        if (LASTORD && W == 1 && i == 3) nb_arrive<NB_PDONE, 256>();
        if (W == 1) mref = __uint_as_float(lds_u(sb + OFF_GM));
        wg_wait<1>();
        reg_fence(s);
        mbar_arrive_warp<2>(sb + BAR_REMPTY + kslot * 8);
        if (W == 1) {
            mbar_arrive_warp_if<2>(sb + BAR_XEMPTY + 0, i == 3);
            if (XLATE < 2) mbar_arrive_warp_if<2>(sb + BAR_XEMPTY + 8, i == 3);
            if (XLATE < 1) mbar_arrive_warp_if<2>(sb + BAR_XEMPTY + 16, i == 3);
        }
        r.adv(W == 1 && i == 3 ? 1 : 2);
        TSD(W, 5 + 5 * i);
        tail(FalseT{}, i);
    }
    const uint32_t w = (tid_now() >> 5) & 3;
    const uint32_t lxa = sb + OFF_LX + w * 640 + (((lane & 8) ? 80 : 0) + ((lane >> 1) & 8) + 2 * (lane & 3) + ((lane >> 2) & 1)) * 4;
    const uint32_t nx = get_item_warp(sb, it + 1, r.dl);
    po.gp = ostash(IT_SLOT(e), IT_B(e)) + po.toff();
    po.sig = 1;
    if (W == 0) {
        sum_store<false>(l, lane, lxa);
        nb_arrive<NB_LX, 256>();
        wg_wait<0>();
        mbar_arrive_warp(sb + BAR_REMPTY + r.slot * 8);
        mbar_arrive_warp(sb + BAR_XEMPTY + 24);
        r.adv(1);
        nb_sync<NB_PFULL + 1, 256>();
        pv(FalseT{}, 1);
        if (IT_TYPE(nx) == IT_QA) {
            Ring rn = r;
            rn.adv(1);
            mbar_wait(sb + BAR_RFULL + rn.slot * 8, rn.ph, r.dl);
            mbar_wait(sb + BAR_XFULL, phm & 1, r.dl);
        }
    } else {
        nb_sync<NB_LX, 256>();
        sum_store<true>(l, lane, lxa);
        nb_arrive<NB_L, 160>();
    }
    TSD(W, 24);
    wg_wait<0>();
    reg_fence(oa);
    reg_fence(ob);
    mbar_arrive_warp(sb + BAR_REMPTY + r.slot * 8);
    mbar_arrive_warp(sb + BAR_XEMPTY + 32);
    r.adv(1);
    opack(ob, po.v + 40);
    opack(oa, po.v);
    return nx;
}

template <int W>
__device__ __forceinline__ uint32_t qa_run(const Params& P, uint32_t e, uint32_t sb, Ring& r, uint32_t phm, int& it) {
    PendO<W> po;
    po.clear();
#pragma unroll 1
    do {
        TS(W, 0);
        if (W == 0) TS_ITEM(e);
        e = qa_item<W>(e, sb, r, phm, po, it);
        TS(W, 31);
        it++;
    } while (IT_TYPE(e) == IT_QA && !po.bad);
#pragma unroll 1
    for (int m = po.bad ? 2 : 1; m > 0; m--) {
        if (m == 1) {
            po.verdict(sb);
            po.template step<0>(sb);
            po.template step<1>(sb);
            po.template step<2>(sb);
            po.template step<3>(sb);
            po.template step<4>(sb);
        }
        if (po.bad) {
            if (W == 0) fallback_unit(P, lds_u(sb + OFF_ITEM + (it - m) * 4), tid_now() & 127);
            __syncwarp();
            nb_sync<NB_ODONE, 288>();
        }
    }
    return e;
}

__device__ __forceinline__ void consumer(const Params& P, uint32_t W, uint32_t sb, uint32_t dl) {
    int it = 0;
    if (W == 0) TS(0, 30);
    Ring r{0, 0, dl};
    uint32_t phm = 0;
    uint32_t e = get_item_warp(sb, 0, dl);
#pragma unroll 1
    while (true) {
        if (IT_TYPE(e) == IT_QA) e = W == 0 ? qa_run<0>(P, e, sb, r, phm, it) : qa_run<1>(P, e, sb, r, phm, it);
        if (e == 0) break;
        if (IT_TYPE(e) == IT_QA) continue;
        TS(W, 0);
        if (W == 0) TS_ITEM(e);
        if (IT_TYPE(e) == IT_ON) on_item(W, e, sb, r, phm);
        else if (W == 0) op_item<true>(e, sb, r, phm);
        else op_item<false>(e, sb, r, phm);
        TS(W, 31);
        e = get_item_warp(sb, ++it, dl);
    }
    TS_DUMP(W);
}

__global__ void __cluster_dims__(2, 1, 1) __launch_bounds__(384, 1) fused_kernel(const __grid_constant__ Params P) {
    extern __shared__ __align__(1024) unsigned char smem_raw[];
    const uint32_t sb = (uint32_t)__cvta_generic_to_shared(smem_raw);
    const uint32_t warp = __shfl_sync(0xffffffffu, threadIdx.x >> 5, 0), wgid = warp >> 2;
    const uint32_t cta = blockIdx.x;
    const uint32_t dl = deadline();

    if (threadIdx.x == 128) {
#pragma unroll
        for (int i = 0; i < NSLOT; i++) {
            mbar_init(sb + BAR_RFULL + i * 8, 1);
            mbar_init(sb + BAR_REMPTY + i * 8, 8);
            mbar_init(sb + BAR_XFULL + i * 8, 1);
            mbar_init(sb + BAR_XEMPTY + i * 8, 8);
        }
        asm volatile("fence.mbarrier_init.release.cluster;" ::: "memory");
        fence_async_smem();
    } else if (threadIdx.x == 160) {
#pragma unroll
        for (int i = 0; i < NSLOT + MAXI; i++) mbar_init(sb + BAR_PRDY + i * 8, 1);
        asm volatile("fence.mbarrier_init.release.cluster;" ::: "memory");
    } else if (threadIdx.x == 0) {
        sts_u(sb + OFF_ITEM, P.cl[cta >> 1].items[0] ? P.cl[cta >> 1].items[0] + 8 * (cta & 1) : 0);
        sts_u(sb + OFF_FB, P.cl[cta >> 1].delay);
    } else if (threadIdx.x == 64) {
        if (sb & 1023) __trap();
        asm volatile("prefetch.tensormap [%0];" ::"l"(&P.wq[0]) : "memory");
        asm volatile("prefetch.tensormap [%0];" ::"l"(&P.x[0]) : "memory");
    }
    __syncthreads();
    asm volatile("barrier.cluster.arrive.relaxed.aligned;" ::: "memory");
    if (warp == 0) {
        const uint32_t e = __shfl_sync(0xffffffffu, lds_u(sb + OFF_ITEM), 0), d = lds_u(sb + OFF_FB);
        const uint64_t pol = mkpol<POL_W>();
        uint32_t t0, t1;
        asm volatile("mov.u32 %0, %%clock;" : "=r"(t0));
        do {
            asm volatile("mov.u32 %0, %%clock;" : "=r"(t1));
        } while (t1 - t0 < d);
        __syncwarp();
#pragma unroll 1
        for (int n = 0; n < (e ? NSLOT : 0); n++) {
            if (threadIdx.x == 0) {
                mbar_expect(sb + BAR_RFULL + n * 8, SLOT);
                tma3(sb + OFF_RING + n * SLOT, &P.wq[0], n * 64, IT_H0(e) * 3, sb + BAR_RFULL + n * 8, pol);
                mbar_expect(sb + BAR_XFULL + n * 8, XS);
                tma3(sb + OFF_R + n * XS, &P.x[0], IT_B(e) * 160, n, sb + BAR_XFULL + n * 8, pol);
                tma3(sb + OFF_RING + n * SLOT + SLOT / 2, &P.wq[0], n * 64 + 32, IT_H0(e) * 3, sb + BAR_RFULL + n * 8, pol);
            }
        }
        if (threadIdx.x == 0) asm volatile("mbarrier.arrive.shared::cta.b64 _, [%0];" ::"r"(sb + BAR_ITEM) : "memory");
        __syncwarp();
    }

    if (wgid == 0) {
        asm volatile("setmaxnreg.dec.sync.aligned.u32 24;");
        if (warp == 0) {
            const bool lead = threadIdx.x == 0;
            const uint64_t pol_first = mkpol<1>(), pol_norm = mkpol<POL_W>();
            uint32_t e = __shfl_sync(0xffffffffu, lds_u(sb + OFF_ITEM), 0);
            asm volatile("barrier.cluster.wait.aligned;" ::: "memory");
            unsigned int* const ticket = &g_ticket[next_epoch(0) & 1];
            const uint32_t rank = cta & 1;
            uint32_t peer;
            asm volatile("mapa.shared::cluster.u32 %0, %1, %2;" : "=r"(peer) : "r"(sb), "r"(rank ^ 1));
            Ring r{0, 0, dl};
            uint32_t pm = 0;
            auto load_w = [&](const CUtensorMap* m, int row, int blk, uint32_t half_bytes) {
                mbar_wait(sb + BAR_REMPTY + r.slot * 8, r.ph, dl);
                if (lead) {
                    mbar_expect(sb + BAR_RFULL + r.slot * 8, 2 * half_bytes);
                    asm volatile("mbarrier.arrive.shared::cluster.b64 _, [%0];" ::"r"(peer + BAR_PRDY + r.slot * 8) : "memory");
                }
                mbar_wait(sb + BAR_PRDY + r.slot * 8, (pm >> r.slot) & 1, dl);
                pm ^= 1u << r.slot;
                if (lead) tma3_mc(sb + OFF_RING + r.slot * SLOT + rank * half_bytes, m, row, blk, sb + BAR_RFULL + r.slot * 8, pol_norm);
                r.adv(1);
            };
#pragma unroll 1
            for (int it = 0; e != 0; it++) {
                uint32_t nx = 0, tk = 0;
                if (rank == 0 && IT_TYPE(e) != IT_ON && it + 2 < MAXI) nx = it + 1 < NSTAT ? P.cl[cta >> 1].items[it + 1] : IT_DYN;
                const uint32_t br = IT_BR(e);
                if (IT_TYPE(e) == IT_QA) {
                    const uint32_t h = IT_H0(e);
#pragma unroll 1
                    for (int kk = it ? 0 : NSLOT; kk < 10; kk++) load_w(&P.wq[br], kk * 64 + rank * 32, h * 3, SLOT / 2);
                    const int row0 = (IT_B(e) * 32 + h) * 512;
#pragma unroll 1
                    for (int n = 0; n < 16; n++) {
                        if (n == 13 && nx == IT_DYN && lead) tk = atomicAdd(ticket, 1);
                        const bool isv = n == 15 || (n > 0 && !(n & 1));
                        const int j = n == 15 ? 7 : isv ? (n - 2) >> 1 : (n + 1) >> 1;
                        mbar_wait(sb + BAR_REMPTY + r.slot * 8, r.ph, dl);
                        if (lead) {
                            mbar_expect(sb + BAR_RFULL + r.slot * 8, SLOT);
                            tma3(sb + OFF_RING + r.slot * SLOT, isv ? &P.v[br] : &P.k[br], row0 + j * 64, 0,
                                 sb + BAR_RFULL + r.slot * 8, pol_first);
                        }
                        r.adv(1);
                    }
                } else {
                    const bool wide = IT_TYPE(e) == IT_OP;
                    const int step = wide ? 32 : 64, r1 = IT_H1(e) * 192;
#pragma unroll 1
                    for (int row = IT_H0(e) * 192 + rank * (step >> 1); row < r1; row += step)
                        load_w(wide ? &P.wo[br] : &P.won[br], row, IT_HALF(e) * (wide ? 5 : 2), wide ? XS / 2 : 8192);
                    if (nx == IT_DYN && lead) tk = atomicAdd(ticket, 1);
                }
                if (rank == 0) {
                    if (nx == IT_DYN) {
                        tk = __shfl_sync(0xffffffffu, tk, 0);
                        nx = tk < P.nlist ? P.list[tk] : 0;
                    }
                    e = nx;
                    if (lead) {
                        asm volatile("st.async.weak.shared::cluster.mbarrier::complete_tx::bytes.b32 [%0], %1, [%2];" ::"r"(
                                         peer + OFF_ITEM + 4 + it * 4),
                                     "r"(e ? e + 8 : 0), "r"(peer + BAR_ITEM + 8 + it * 8)
                                     : "memory");
                        sts_u(sb + OFF_ITEM + 4 + it * 4, e);
                        asm volatile("mbarrier.arrive.shared::cta.b64 _, [%0];" ::"r"(sb + BAR_ITEM + 8 + it * 8) : "memory");
                    }
                } else {
                    if (lead) mbar_expect(sb + BAR_ITEM + 8 + it * 8, 4);
                    e = get_item_warp(sb, it + 1, dl);
                }
            }
        } else if (warp == 1) {
            const uint64_t pol_norm = mkpol<POL_X>(), pol_o = mkpol<POL_O>();
            const bool lead = threadIdx.x == 32;
            uint32_t phm = 0, epoch = 0;
#pragma unroll 1
            for (int it = 0;; it++) {
                const uint32_t e = get_item_warp(sb, it, dl);
                if (it == 1 || (it == 0 && e == 0)) epoch = next_epoch(1);
                if (e == 0) break;
                const uint32_t br = IT_BR(e);
                uint32_t xs = 0;
                auto acquire = [&]() {
                    mbar_wait(sb + BAR_XEMPTY + xs * 8, (phm >> xs) & 1, dl);
                    phm ^= 1u << xs;
                    if (lead) mbar_expect(sb + BAR_XFULL + xs * 8, XS);
                };
                if (IT_TYPE(e) == IT_QA) {
#pragma unroll 1
                    for (int kk = it ? 0 : 5; kk < 10; kk++) {
                        acquire();
                        if (lead) tma3(sb + OFF_R + xs * XS, &P.x[br], IT_B(e) * 160, kk, sb + BAR_XFULL + xs * 8, pol_norm);
                        if (++xs == 5) xs = 0;
                    }
                } else {
                    const unsigned int* fp = g_flag + (br * 16 + IT_B(e)) * 64 + (threadIdx.x & 31);
                    uint32_t hm = 0, pm = 0;
                    auto poll = [&](uint32_t hneed, uint32_t pneed) {
                        if ((hm & hneed) == hneed && (pm & pneed) == pneed) return;
                        uint32_t n = 0;
                        do {
                            uint32_t a, b;
                            asm volatile("ld.acquire.gpu.global.u32 %0, [%2];\nld.acquire.gpu.global.u32 %1, [%2+128];"
                                         : "=r"(a), "=r"(b) : "l"(fp) : "memory");
                            hm = __ballot_sync(0xffffffffu, a == epoch);
                            pm = __ballot_sync(0xffffffffu, b == epoch);
                            if (++n > 0x1000000) __trap();
                        } while ((hm & hneed) != hneed || (pm & pneed) != pneed);
                        __syncwarp();
                        asm volatile("fence.proxy.async;" ::: "memory");
                    };
#pragma unroll 1
                    for (uint32_t h = IT_H0(e); h < IT_H1(e); h++) {
                        poll(1u << h, 0);
                        const unsigned char* src = ostash(P.slot[br * 32 + h], IT_B(e));
#pragma unroll 1
                        for (int t = 0; t < 3; t++) {
                            acquire();
                            if (lead) bulk_load(sb + OFF_R + xs * XS, src + t * XS, XS, sb + BAR_XFULL + xs * 8, pol_o);
                            if (++xs == 5) xs = 0;
                        }
                        if (IT_TYPE(e) == IT_OP && h >= 1) {
                            const uint32_t x1 = xs == 4 ? 0 : xs + 1;
                            mbar_wait(sb + BAR_XFULL + xs * 8, (phm >> xs) & 1, dl);
                            mbar_wait(sb + BAR_XFULL + x1 * 8, (phm >> x1) & 1, dl);
                            if (lead)
                                asm volatile("st.relaxed.gpu.global.u32 [%0], %1;" ::"l"(fp + 34 + IT_HALF(e)), "r"(epoch * 64 + h) : "memory");
                        }
                    }
                    if (IT_TYPE(e) == IT_ON) {
                        poll(0, IT_HALF(e) < 2 ? 1 : IT_HALF(e) == 2 ? 3 : 2);
#pragma unroll 1
                        for (uint32_t tile = 2 * IT_HALF(e); tile < 2 * IT_HALF(e) + 2; tile++) {
                            acquire();
                            if (lead)
                                asm volatile(
                                    "cp.async.bulk.tensor.5d.shared::cluster.global.mbarrier::complete_tx::bytes [%0], [%1, {%3,%5,%5,%5,%4}], [%2];" ::"r"(
                                        sb + OFF_R + xs * XS),
                                    "l"(&P.out), "r"(sb + BAR_XFULL + xs * 8), "r"(br * 640 + tile * 64), "r"(IT_B(e) * 5), "r"(0)
                                    : "memory");
                            if (++xs == 5) xs = 0;
                        }
                    }
                }
            }
        } else if (warp == 2) {
            asm volatile("barrier.cluster.wait.aligned;" ::: "memory");
            const uint32_t epoch = next_epoch(2);
            if (cta == 0) g_ticket[(epoch + 1) & 1] = 0;
#pragma unroll 1
            for (int it = 0;; it++) {
                const uint32_t e = get_item_warp(sb, it, dl);
                if (e == 0) break;
                nb_sync<NB_ODONE, 288>();
                if (threadIdx.x == 64) {
                    const uint32_t bb = IT_BR(e) * 16 + IT_B(e);
                    if (IT_TYPE(e) != IT_QA) {
                        const bool wide = IT_TYPE(e) == IT_OP;
                        if (wide)
                            asm volatile("st.relaxed.gpu.global.u32 [%0], %1;" ::"l"(&g_flag[bb * 64 + 34 + IT_HALF(e)]),
                                         "r"(epoch * 64 + IT_H1(e))
                                         : "memory");
                        const int cc0 = IT_BR(e) * 640 + IT_HALF(e) * (wide ? 320 : 128);
                        uint32_t xs = wide ? 0 : (3 * (IT_H1(e) - IT_H0(e))) % 5;
#pragma unroll 1
                        for (int m = 0; m < (wide ? 5 : 2); m++) {
                            asm volatile("cp.async.bulk.tensor.5d.global.shared::cta.bulk_group [%0, {%2,%4,%4,%4,%3}], [%1];" ::"l"(&P.out),
                                         "r"(sb + OFF_R + xs * XS), "r"(cc0 + m * 64), "r"((int)IT_B(e) * 5), "r"(0)
                                         : "memory");
                            asm volatile("cp.async.bulk.commit_group;" ::: "memory");
                            if (++xs == 5) xs = 0;
                        }
                        if (wide) {
#define REL(N)                                                          \
    asm volatile("cp.async.bulk.wait_group.read %0;" ::"n"(4 - N) : "memory"); \
    asm volatile("mbarrier.arrive.shared::cta.b64 _, [%0], 8;" ::"r"(sb + BAR_XEMPTY + N * 8) : "memory");
                            REL(0) REL(1) REL(2) REL(3) REL(4)
#undef REL
                        }
                        if (IT_PART(e)) {
                            asm volatile("cp.async.bulk.wait_group 0;" ::: "memory");
                            asm volatile("fence.proxy.async;" ::: "memory");
                        }
                    }
                    if (IT_TYPE(e) == IT_QA || IT_PART(e)) {
                        unsigned int* f = &g_flag[bb * 64 + (IT_TYPE(e) == IT_QA ? IT_H0(e) : 32 + IT_HALF(e))];
                        asm volatile("st.release.gpu.global.u32 [%0], %1;" ::"l"(f), "r"(epoch) : "memory");
                    }
                }
                __syncwarp();
            }
            if (threadIdx.x == 64) asm volatile("cp.async.bulk.wait_group 0;" ::: "memory");
            __syncwarp();
            asm volatile("barrier.cluster.arrive.relaxed.aligned;\nbarrier.cluster.wait.aligned;" ::: "memory");
        } else {
            const uint32_t lane = threadIdx.x & 31, p = lane >> 2;
            const uint32_t epoch = next_epoch(3);
#pragma unroll 1
            for (int it = 0;; it++) {
                const uint32_t e = get_item_warp(sb, it, dl);
                if (e == 0) break;
                if (IT_TYPE(e) != IT_QA) continue;
                nb_sync<NB_QK, 160>();
                const uint32_t co = (((lane & 3) * 2) ^ p) << 4;
                const uint32_t ka = sb + OFF_RING + lds_u(sb + OFF_GM + 4) * SLOT + p * (9 * 128) + co;
                const uint32_t qa = sb + OFF_R + p * 128 + co;
                uint32_t acc = 0;
#pragma unroll 1
                for (int c = 0; c < 3; c++) {
                    if (c == 2) nb_sync<NB_L, 160>();
                    const uint4 k0 = lds_u4(ka + c * 8192), q0 = lds_u4(qa + c * XS);
                    acc = fma_bf2(k0.x, q0.x, fma_bf2(k0.y, q0.y, fma_bf2(k0.z, q0.z, fma_bf2(k0.w, q0.w, acc))));
                    const uint4 k1 = lds_u4((ka + c * 8192) ^ 16), q1 = lds_u4((qa + c * XS) ^ 16);
                    acc = fma_bf2(k1.x, q1.x, fma_bf2(k1.y, q1.y, fma_bf2(k1.z, q1.z, fma_bf2(k1.w, q1.w, acc))));
                }
                float d = __uint_as_float(acc << 16) + __uint_as_float(acc & 0xffff0000u);
                d += __shfl_xor_sync(0xffffffffu, d, 1);
                d += __shfl_xor_sync(0xffffffffu, d, 2);
                int key = __float_as_int(d);
                key ^= (key >> 31) & 0x7fffffff;
                key = __reduce_max_sync(0xffffffffu, key);
                key ^= (key >> 31) & 0x7fffffff;
                sts_f(sb + OFF_GM, fmaf(__int_as_float(key), SM_C, 16.f));
                nb_arrive<NB_REF, 160>();
                if (IT_DEP(e)) {
                    const uint32_t g = IT_DEP(e) - 1, need = epoch * 64 + (g & 31) + 1;
                    const unsigned int* cp = &g_flag[((g >> 5) * 16 + IT_B(e)) * 64 + 34 + (lane & 1)];
                    for (uint32_t n = 0;; n++) {
                        uint32_t v;
                        asm volatile("ld.acquire.gpu.global.u32 %0, [%1];" : "=r"(v) : "l"(cp) : "memory");
                        if (__all_sync(0xffffffffu, v - need < 64)) break;
                        if (n > 0x800000) __trap();
                        __nanosleep(500);
                    }
                }
                nb_sync<NB_L, 160>();
                bool bad = false;
#pragma unroll
                for (int c = 0; c < 5; c++) {
                    const uint32_t la = sb + OFF_LX + (c * 32 + lane) * 4;
                    const float v = (__uint_as_float(lds_u(la)) + __uint_as_float(lds_u(la + 640))) +
                                    (__uint_as_float(lds_u(la + 1280)) + __uint_as_float(lds_u(la + 1920)));
                    const float inv = __fdividef(1.f, v);
                    const uint32_t hi = pack_bf16(inv, 0.f), lo = pack_bf16(inv - __uint_as_float(hi << 16), 0.f);
                    const uint32_t ia = sb + OFF_LINV + c * 128 + ((lane >> 1) & 3) * 32 + (lane >> 3) * 8 + (lane & 1) * 2;
                    asm volatile("st.shared.u16 [%0], %1;\nst.shared.u16 [%0+4], %2;" ::"r"(ia), "h"((unsigned short)hi), "h"((unsigned short)lo) : "memory");
                    bad |= !(v >= 5.421010862e-20f && v <= 7.9228163e28f);
                }
                sts_u(sb + OFF_FB, __any_sync(0xffffffffu, bad));
                nb_arrive<NB_VOTE, 160>();
                nb_arrive<NB_VOTE + 1, 160>();
            }
        }
    } else {
        asm volatile("setmaxnreg.inc.sync.aligned.u32 240;");
        consumer(P, wgid - 1, sb, dl);
    }
}

typedef CUresult (*EncFn)(CUtensorMap*, CUtensorMapDataType, cuuint32_t, void*, const cuuint64_t*, const cuuint64_t*,
                          const cuuint32_t*, const cuuint32_t*, CUtensorMapInterleave, CUtensorMapSwizzle,
                          CUtensorMapL2promotion, CUtensorMapFloatOOBfill);

void make_map3(EncFn enc, CUtensorMap* m, void* p, uint64_t rows, uint64_t rowbytes, uint64_t nblk, uint32_t boxrows,
               uint32_t boxblk) {
    cuuint64_t dims[3] = {64, rows, nblk};
    cuuint64_t str[2] = {rowbytes, 128};
    cuuint32_t box[3] = {64, boxrows, boxblk};
    cuuint32_t es[3] = {1, 1, 1};
    enc(m, CU_TENSOR_MAP_DATA_TYPE_BFLOAT16, 3, p, dims, str, box, es, CU_TENSOR_MAP_INTERLEAVE_NONE,
        CU_TENSOR_MAP_SWIZZLE_128B, CU_TENSOR_MAP_L2_PROMOTION_NONE, CU_TENSOR_MAP_FLOAT_OOB_FILL_NONE);
}

constexpr int tune(const char*, int def) { return def; }

void build_schedule(Params& P) {
    const int mode = tune("MODE", 4), dmax = tune("DMAX", 24900), n0 = tune("N0", 8);
    const int H0[8] = {20, 20, 22, 22, 22, 24, 25, 25}, P0[8] = {352, 352, 344, 348, 352, 345, 333, 336};
    const int ng = tune("NG", 0), d0 = tune("D0", 0), nkeep = tune("NKEEP", 0), odmax = tune("ODMAX", 2000);
    const int ong = tune("ONG", 0), od0 = tune("OD0", 0), jit = tune("JIT", 0);
    const int npos = tune("NPOS", 0), nearly = tune("NEARLY", 0);
    const int ra = tune("RA", 10), ga = tune("GA", 32), rb = tune("RB", 12), g1 = tune("G1", 58);
    int dep[64];
    for (int g = 0, ns = 0, live = 0; g < 64; g++) {
        const bool fresh = mode < 3 || g >= g1 || live < (g < ga ? ra : rb);
        dep[g] = fresh ? 0 : g - live + 1;
        P.slot[g] = fresh ? ns++ : P.slot[g - live];
        live += fresh;
    }
    int u = 0;
    auto unit = [&]() {
        const uint32_t e = mk_item(IT_QA, u >> 8, (u & 7) * 2, (u >> 3) & 31, P.slot[u >> 3], 0) | (dep[u >> 3] << 23);
        u++;
        return e;
    };
    int qa[NCL], nq = 0, op[NCL], no = 0;
    for (int c = 0; c < NCL; c++) {
        P.cl[c].delay = 0;
        for (int i = 0; i < NSTAT; i++) P.cl[c].items[i] = 0;
        if (mode >= 3 && c < 64 && (c & 3) == 3) op[no++] = c;
        else if (mode != 2 || (c & 3) == 0) qa[nq++] = c;
    }
    for (int t = 0; t < no; t++) {
        P.cl[op[t]].items[1] = mk_item(IT_OP, 0, t & ~1, 0, 32, t & 1);
        P.cl[op[t]].items[2] = IT_DYN;
        P.cl[op[t]].delay = ong ? od0 + (t * ong / 16) * (odmax / ong) : od0 + t * odmax / 16;
    }
    for (int k = 0; k < nq; k++) {
        const int c = qa[(k * 19) % nq];
        P.cl[c].items[1] = P.cl[c].items[2] = IT_DYN;
        P.cl[c].delay = k < n0 ? 0 : (int)((long long)dmax * (k + 1 - n0) / (nq - n0));
        if (ng) P.cl[c].delay = d0 + (k * ng / nq) * (dmax / ng) + (k * ng % nq) * jit / nq;
    }
    if (tune("OFIRST", 0))
        for (int t = 0; t < no; t++) P.cl[op[t]].items[0] = unit();
    for (int k = u; k < no + nq; k++) {
        int best = -1;
        for (int c = 0; c < NCL; c++)
            if (P.cl[c].items[1] && !P.cl[c].items[0] && (best < 0 || P.cl[c].delay < P.cl[best].delay)) best = c;
        P.cl[best].items[0] = unit();
    }
    int H[8], pos[8];
    for (int b = 0; b < 8; b++) {
        char nh[3] = {'H', (char)('0' + b), 0}, np[3] = {'P', (char)('0' + b), 0};
        H[b] = tune(nh, H0[b]);
        pos[b] = tune(np, P0[b]);
        for (int g = 0; g < 64; g++)
            if (dep[g] > 32) {
                if (pos[b] > 8 * g) pos[b] = 8 * g;
                if (H[b] < dep[g] - 32) H[b] = dep[g] - 32;
            }
        if (b < nkeep && no) {
            pos[b] = -1;
            P.cl[op[14 - 2 * b]].items[2] = mk_item(IT_OP, 1, 2 * b, 0, H[b], 0, 1);
            P.cl[op[15 - 2 * b]].items[2] = mk_item(IT_OP, 1, 2 * b, 0, H[b], 1, 1);
        }
    }
    int n = 0, kn = 0;
    const int uend = mode == 2 ? 8 * nq : 512;
    while (u < uend) {
        for (int b = 0; b < 8 && no; b++)
            if (pos[b] == u) {
                P.list[n++] = mk_item(IT_OP, 1, 2 * b, 0, H[b], 0, 1);
                P.list[n++] = mk_item(IT_OP, 1, 2 * b, 0, H[b], 1, 1);
            }
        while (no && u >= uend - npos && kn * npos < (u + 1 - (uend - npos)) * nearly) {
            P.list[n++] = mk_item(IT_ON, 1, kn / 5 * 2, H[kn / 5], 32, kn % 5);
            kn++;
        }
        P.list[n++] = unit();
    }
    for (; no && kn < 40; kn++) P.list[n++] = mk_item(IT_ON, 1, kn / 5 * 2, H[kn / 5], 32, kn % 5);
    P.nlist = n;
}

}

extern "C" void kernel_launch(void* const* d_in, const int* in_sizes, int n_in, void* d_out, int out_size) {
    static Params P;
    static bool init = false;
    if (!init) {
        EncFn enc = nullptr;
        cudaDriverEntryPointQueryResult qr;
        cudaGetDriverEntryPoint("cuTensorMapEncodeTiled", (void**)&enc, cudaEnableDefault, &qr);
        for (int i = 0; i < 2; i++) {
            P.px[i] = (const __nv_bfloat16*)d_in[5 * i + 0];
            P.pk[i] = (const __nv_bfloat16*)d_in[5 * i + 1];
            P.pv[i] = (const __nv_bfloat16*)d_in[5 * i + 2];
            P.pwq[i] = (const __nv_bfloat16*)d_in[5 * i + 3];
            make_map3(enc, &P.x[i], d_in[5 * i + 0], 2560, 1280, 10, 160, 1);
            make_map3(enc, &P.k[i], d_in[5 * i + 1], 16 * 32 * 512, 384, 3, 64, 3);
            make_map3(enc, &P.v[i], d_in[5 * i + 2], 16 * 32 * 512, 384, 3, 64, 3);
            make_map3(enc, &P.wq[i], d_in[5 * i + 3], 640, 12288, 96, 32, 3);
            make_map3(enc, &P.wo[i], d_in[5 * i + 4], 6144, 1280, 10, 16, 5);
            make_map3(enc, &P.won[i], d_in[5 * i + 4], 6144, 1280, 10, 32, 2);
        }
        cuuint64_t dims[5] = {1280, 2, 4, 4, 80};
        cuuint64_t str[4] = {2560, 8 * 2560, 2 * 2560, 32 * 2560};
        cuuint32_t box[5] = {64, 2, 4, 4, 5};
        cuuint32_t es[5] = {1, 1, 1, 1, 1};
        enc(&P.out, CU_TENSOR_MAP_DATA_TYPE_BFLOAT16, 5, d_out, dims, str, box, es, CU_TENSOR_MAP_INTERLEAVE_NONE,
            CU_TENSOR_MAP_SWIZZLE_128B, CU_TENSOR_MAP_L2_PROMOTION_NONE, CU_TENSOR_MAP_FLOAT_OOB_FILL_NONE);
        build_schedule(P);
        cudaFuncSetAttribute(fused_kernel, cudaFuncAttributeMaxDynamicSharedMemorySize, SMEM_LAUNCH);
        init = true;
    }
    fused_kernel<<<NCTA, 384, SMEM_LAUNCH>>>(P);
}
```

```cpp
#include <cuda_runtime.h>
#include <cuda.h>
#include <cuda_bf16.h>
#include <stdint.h>

namespace {

constexpr int NCTA = 132;
constexpr int NCL = NCTA / 2;
constexpr int MAXI = 16;
constexpr int NSTAT = 3;
constexpr uint32_t IT_DYN = 0xffffffffu;
constexpr int SLOT = 24576;
constexpr int NSLOT = 5;
constexpr int XS = 20480;
constexpr int OFF_R = 0;
constexpr int OFF_RING = 5 * XS;
constexpr int OFF_MISC = OFF_RING + NSLOT * SLOT;
constexpr int OFF_LX = OFF_MISC;
constexpr int OFF_LINV = OFF_LX + 2560;
constexpr int OFF_FB = OFF_LINV + 640;
constexpr int OFF_GM = OFF_FB + 16;
constexpr int OFF_BAR = OFF_GM + 16;
constexpr int BAR_RFULL = OFF_BAR;
constexpr int BAR_REMPTY = BAR_RFULL + 40;
constexpr int BAR_XFULL = BAR_REMPTY + 40;
constexpr int BAR_XEMPTY = BAR_XFULL + 40;
constexpr int BAR_PRDY = BAR_XEMPTY + 40;
constexpr int BAR_ITEM = BAR_PRDY + 40;
constexpr int OFF_ITEM = BAR_ITEM + MAXI * 8;
constexpr int SMEM_BYTES = OFF_ITEM + MAXI * 4;
static_assert(SMEM_BYTES <= 232448, "smem");

constexpr int NB_W = 1  , NB_PFULL = 3  , NB_VOTE = 5  , NB_Q2 = 7, NB_SDONE = 8, NB_PDONE = 9,
              NB_L = 10, NB_REF = 11, NB_ODONE = 12, NB_OPEND = 13, NB_LX = 14, NB_Q01 = 15, NB_QK = 0  ;

constexpr uint32_t IT_QA = 1, IT_OP = 2, IT_ON = 3;
__host__ __device__ constexpr uint32_t mk_item(uint32_t type, uint32_t br, uint32_t b, uint32_t h0, uint32_t h1, uint32_t half,
                                               uint32_t part = 0) {
    return type | (br << 2) | (b << 3) | (h0 << 7) | (h1 << 13) | (half << 19) | (part << 22);
}
#define IT_TYPE(e) ((e) & 3u)
#define IT_BR(e) (((e) >> 2) & 1u)
#define IT_B(e) (((e) >> 3) & 15u)
#define IT_H0(e) (((e) >> 7) & 63u)
#define IT_H1(e) (((e) >> 13) & 63u)
#define IT_HALF(e) (((e) >> 19) & 7u)
#define IT_PART(e) (((e) >> 22) & 1u)
#define IT_SLOT(e) IT_H1(e)
#define IT_DEP(e) (((e) >> 23) & 127u)

struct Params {
    CUtensorMap x[2], wq[2], k[2], v[2], wo[2], won[2], out;
    const __nv_bfloat16 *px[2], *pwq[2], *pk[2], *pv[2];
    struct alignas(16) { uint32_t delay, items[NSTAT]; } cl[NCL];
    uint32_t nlist;
    uint8_t slot[64];
    uint32_t list[512];
};

constexpr int OUNIT = 61440;
__device__ __align__(1024) unsigned char g_ostash[(size_t)1024 * OUNIT];
__device__ unsigned int g_flag[32 * 64];
__device__ __forceinline__ unsigned char* ostash(uint32_t slot, uint32_t b) { return g_ostash + (slot * 16 + b) * OUNIT; }
__device__ unsigned int g_epoch[NCTA * 4];
__device__ unsigned int g_ticket[2];

constexpr int SMEM_LAUNCH = SMEM_BYTES;
#define TS(role, idx)
#define TS_ITEM(e)
#define TS_DUMP(role)
#define TSD(role, idx)

#define POL_W 2
#define POL_X 2
#define POL_O 2
template <int M>
__device__ __forceinline__ uint64_t mkpol() {
    uint64_t p;
    if (M == 0) asm volatile("createpolicy.fractional.L2::evict_normal.b64 %0, 1.0;" : "=l"(p));
    if (M == 1) asm volatile("createpolicy.fractional.L2::evict_first.b64 %0, 1.0;" : "=l"(p));
    if (M == 2) asm volatile("createpolicy.fractional.L2::evict_unchanged.b64 %0, 1.0;" : "=l"(p));
    if (M == 3) asm volatile("createpolicy.fractional.L2::evict_normal.L2::evict_unchanged.b64 %0, 0.25;" : "=l"(p));
    return p;
}
#define STSM_W 1
#define LASTORD 0
#define XLATE 2
#define PV0FIRST 1
#define QST0 1
#define QST1 2
#define QHOLD 8
constexpr float SM_C = 0.07216878364870322f * 1.4426950408889634f;

__device__ __forceinline__ uint32_t next_epoch(int warp) {
    unsigned int* p = &g_epoch[blockIdx.x * 4 + warp];
    const uint32_t e = __ldcg(p) + 1;
    *p = e;
    return e;
}

__device__ __forceinline__ uint32_t tid_now() {
    uint32_t t;
    asm volatile("mov.u32 %0, %%tid.x;" : "=r"(t));
    return t;
}
__device__ __forceinline__ void mbar_init(uint32_t a, uint32_t c) {
    asm volatile("mbarrier.init.shared::cta.b64 [%0], %1;" ::"r"(a), "r"(c) : "memory");
}
__device__ __forceinline__ void mbar_expect(uint32_t a, uint32_t b) {
    asm volatile("mbarrier.arrive.expect_tx.shared::cta.b64 _, [%0], %1;" ::"r"(a), "r"(b) : "memory");
}
template <int CNT = 1>
__device__ __forceinline__ void mbar_arrive_warp(uint32_t a) {
    if (CNT == 1)
        asm volatile("{\n.reg .pred p;\nelect.sync _|p, 0xffffffff;\n@p mbarrier.arrive.shared::cta.b64 _, [%0];\n}" ::"r"(a) : "memory");
    else
        asm volatile(
            "{\n.reg .pred p;\nelect.sync _|p, 0xffffffff;\n@p mbarrier.arrive.shared::cta.b64 _, [%0];\n"
            "@p mbarrier.arrive.shared::cta.b64 _, [%0];\n}" ::"r"(a)
            : "memory");
}
template <int CNT = 1>
__device__ __forceinline__ void mbar_arrive_warp_if(uint32_t a, bool cond) {
    if (CNT == 1)
        asm volatile(
            "{\n.reg .pred p, c;\nelect.sync _|p, 0xffffffff;\nsetp.ne.and.u32 c, %1, 0, p;\n"
            "@c mbarrier.arrive.shared::cta.b64 _, [%0];\n}" ::"r"(a), "r"((uint32_t)cond)
            : "memory");
    else
        asm volatile(
            "{\n.reg .pred p, c;\nelect.sync _|p, 0xffffffff;\nsetp.ne.and.u32 c, %1, 0, p;\n"
            "@c mbarrier.arrive.shared::cta.b64 _, [%0];\n@c mbarrier.arrive.shared::cta.b64 _, [%0];\n}" ::"r"(a), "r"((uint32_t)cond)
            : "memory");
}
__device__ __forceinline__ uint32_t deadline() {
    uint32_t c;
    asm volatile("mov.u32 %0, %%clock_hi;" : "=r"(c));
    return c + 4;
}
__device__ __forceinline__ void mbar_wait(uint32_t a, uint32_t ph, uint32_t dl) {
    asm volatile(
        "{\n.reg .pred p;\n.reg .u32 m;\n"
        "LOOP:\n"
        "mbarrier.try_wait.parity.shared::cta.b64 p, [%0], %1;\n"
        "@p bra DONE;\n"
        "mov.u32 m, %%clock_hi;\n"
        "setp.ne.u32 p, m, %2;\n"
        "@p bra LOOP;\n"
        "trap;\n"
        "DONE:\n}" ::"r"(a), "r"(ph), "r"(dl)
        : "memory");
}
template <int ID, int CNT>
__device__ __forceinline__ void nb_sync() { asm volatile("bar.sync %0, %1;" ::"n"(ID), "n"(CNT) : "memory"); }
template <int ID, int CNT>
__device__ __forceinline__ void nb_arrive() { asm volatile("bar.arrive %0, %1;" ::"n"(ID), "n"(CNT) : "memory"); }
__device__ __forceinline__ void fence_async_smem() { asm volatile("fence.proxy.async.shared::cta;" ::: "memory"); }

__device__ __forceinline__ void tma3(uint32_t dst, const CUtensorMap* m, int c1, int c2, uint32_t bar, uint64_t pol) {
    asm volatile(
        "cp.async.bulk.tensor.3d.shared::cluster.global.mbarrier::complete_tx::bytes.L2::cache_hint [%0], [%1, {%3,%4,%5}], [%2], %6;" ::"r"(dst),
        "l"(m), "r"(bar), "r"(0), "r"(c1), "r"(c2), "l"(pol)
        : "memory");
}
__device__ __forceinline__ void tma3_mc(uint32_t dst, const CUtensorMap* m, int c1, int c2, uint32_t bar, uint64_t pol) {
    asm volatile(
        "cp.async.bulk.tensor.3d.shared::cluster.global.mbarrier::complete_tx::bytes.multicast::cluster.L2::cache_hint"
        " [%0], [%1, {%3,%4,%5}], [%2], %6, %7;" ::"r"(dst),
        "l"(m), "r"(bar), "r"(0), "r"(c1), "r"(c2), "h"((unsigned short)3), "l"(pol)
        : "memory");
}
__device__ __forceinline__ void bulk_load(uint32_t dst, const void* src, uint32_t bytes, uint32_t bar, uint64_t pol) {
    asm volatile("cp.async.bulk.shared::cluster.global.mbarrier::complete_tx::bytes.L2::cache_hint [%0], [%1], %2, [%3], %4;" ::"r"(dst),
                 "l"(src), "r"(bytes), "r"(bar), "l"(pol)
                 : "memory");
}
__device__ __forceinline__ void wg_fence() { asm volatile("wgmma.fence.sync.aligned;" ::: "memory"); }
__device__ __forceinline__ void wg_commit() { asm volatile("wgmma.commit_group.sync.aligned;" ::: "memory"); }
template <int N>
__device__ __forceinline__ void wg_wait() { asm volatile("wgmma.wait_group.sync.aligned %0;" ::"n"(N) : "memory"); }

#define RW80(c, d) c(d[0]), c(d[1]), c(d[2]), c(d[3]), c(d[4]), c(d[5]), c(d[6]), c(d[7]), c(d[8]), c(d[9]), c(d[10]), c(d[11]), c(d[12]), c(d[13]), c(d[14]), c(d[15]), c(d[16]), c(d[17]), c(d[18]), c(d[19]), c(d[20]), c(d[21]), c(d[22]), c(d[23]), c(d[24]), c(d[25]), c(d[26]), c(d[27]), c(d[28]), c(d[29]), c(d[30]), c(d[31]), c(d[32]), c(d[33]), c(d[34]), c(d[35]), c(d[36]), c(d[37]), c(d[38]), c(d[39]), c(d[40]), c(d[41]), c(d[42]), c(d[43]), c(d[44]), c(d[45]), c(d[46]), c(d[47]), c(d[48]), c(d[49]), c(d[50]), c(d[51]), c(d[52]), c(d[53]), c(d[54]), c(d[55]), c(d[56]), c(d[57]), c(d[58]), c(d[59]), c(d[60]), c(d[61]), c(d[62]), c(d[63]), c(d[64]), c(d[65]), c(d[66]), c(d[67]), c(d[68]), c(d[69]), c(d[70]), c(d[71]), c(d[72]), c(d[73]), c(d[74]), c(d[75]), c(d[76]), c(d[77]), c(d[78]), c(d[79])
#define RW48(c, d) c(d[0]), c(d[1]), c(d[2]), c(d[3]), c(d[4]), c(d[5]), c(d[6]), c(d[7]), c(d[8]), c(d[9]), c(d[10]), c(d[11]), c(d[12]), c(d[13]), c(d[14]), c(d[15]), c(d[16]), c(d[17]), c(d[18]), c(d[19]), c(d[20]), c(d[21]), c(d[22]), c(d[23]), c(d[24]), c(d[25]), c(d[26]), c(d[27]), c(d[28]), c(d[29]), c(d[30]), c(d[31]), c(d[32]), c(d[33]), c(d[34]), c(d[35]), c(d[36]), c(d[37]), c(d[38]), c(d[39]), c(d[40]), c(d[41]), c(d[42]), c(d[43]), c(d[44]), c(d[45]), c(d[46]), c(d[47])
#define RW32(c, d) c(d[0]), c(d[1]), c(d[2]), c(d[3]), c(d[4]), c(d[5]), c(d[6]), c(d[7]), c(d[8]), c(d[9]), c(d[10]), c(d[11]), c(d[12]), c(d[13]), c(d[14]), c(d[15]), c(d[16]), c(d[17]), c(d[18]), c(d[19]), c(d[20]), c(d[21]), c(d[22]), c(d[23]), c(d[24]), c(d[25]), c(d[26]), c(d[27]), c(d[28]), c(d[29]), c(d[30]), c(d[31])

__device__ __forceinline__ void reg_fence(float (&d)[80]) { asm volatile("" : RW80("+f", d)::"memory"); }
__device__ __forceinline__ void reg_fence(float (&d)[48]) { asm volatile("" : RW48("+f", d)::"memory"); }
__device__ __forceinline__ void reg_fence(float (&d)[32]) { asm volatile("" : RW32("+f", d)::"memory"); }

template <int NR>
__device__ __forceinline__ void zero(float (&d)[NR]) {
#pragma unroll
    for (int i = 0; i < NR; i++) d[i] = 0.f;
}

constexpr uint32_t HI_SW128 = (1024u >> 4) | (1u << 30);
constexpr uint32_t HI_OST = (2560u >> 4) | (2u << 30);
constexpr uint32_t LO_LBO1 = (1u << 16);
constexpr uint32_t LO_OST = ((512u >> 4) << 16);

template <int TA, int TB, uint32_t HIB, int ACC>
__device__ __forceinline__ void wgmma(float (&d)[80], uint32_t loA, uint32_t loB) {
#define WG_ASM(SD)                                                          \
    "{\n.reg .b64 da, db;\nmov.b64 da, {%80, %82};\nmov.b64 db, {%81, %83};\n" \
    "wgmma.mma_async.sync.aligned.m64n160k16.f32.bf16.bf16 "               \
    "{%0,%1,%2,%3,%4,%5,%6,%7,%8,%9,%10,%11,%12,%13,%14,%15,%16,%17,%18,%19,%20,%21,%22,%23,%24,%25,%26,%27,%28,%29,%30,%31,%32,%33,%34,%35,%36,%37,%38,%39,%40,%41,%42,%43,%44,%45,%46,%47,%48,%49,%50,%51,%52,%53,%54,%55,%56,%57,%58,%59,%60,%61,%62,%63,%64,%65,%66,%67,%68,%69,%70,%71,%72,%73,%74,%75,%76,%77,%78,%79}, da, db, " SD ", 1, 1, %84, %85;\n}"
    if constexpr (ACC == 2)
        asm volatile(WG_ASM("0") : RW80("+f", d) : "r"(loA), "r"(loB), "n"(HI_SW128), "n"(HIB), "n"(TA), "n"(TB));
    else if constexpr (ACC == 1)
        asm volatile(WG_ASM("1") : RW80("+f", d) : "r"(loA), "r"(loB), "n"(HI_SW128), "n"(HIB), "n"(TA), "n"(TB));
    else
        asm volatile(WG_ASM("0") : RW80("=f", d) : "r"(loA), "r"(loB), "n"(HI_SW128), "n"(HIB), "n"(TA), "n"(TB));
#undef WG_ASM
}
template <int TA, int TB, uint32_t HIB, int ACC>
__device__ __forceinline__ void wgmma(float (&d)[48], uint32_t loA, uint32_t loB) {
#define WG_ASM(SD)                                                          \
    "{\n.reg .b64 da, db;\nmov.b64 da, {%48, %50};\nmov.b64 db, {%49, %51};\n" \
    "wgmma.mma_async.sync.aligned.m64n96k16.f32.bf16.bf16 "               \
    "{%0,%1,%2,%3,%4,%5,%6,%7,%8,%9,%10,%11,%12,%13,%14,%15,%16,%17,%18,%19,%20,%21,%22,%23,%24,%25,%26,%27,%28,%29,%30,%31,%32,%33,%34,%35,%36,%37,%38,%39,%40,%41,%42,%43,%44,%45,%46,%47}, da, db, " SD ", 1, 1, %52, %53;\n}"
    if constexpr (ACC == 1)
        asm volatile(WG_ASM("1") : RW48("+f", d) : "r"(loA), "r"(loB), "n"(HI_SW128), "n"(HIB), "n"(TA), "n"(TB));
    else
        asm volatile(WG_ASM("0") : RW48("=f", d) : "r"(loA), "r"(loB), "n"(HI_SW128), "n"(HIB), "n"(TA), "n"(TB));
#undef WG_ASM
}
template <int TA, int TB, uint32_t HIB, int ACC>
__device__ __forceinline__ void wgmma(float (&d)[32], uint32_t loA, uint32_t loB) {
#define WG_ASM(SD)                                                          \
    "{\n.reg .b64 da, db;\nmov.b64 da, {%32, %34};\nmov.b64 db, {%33, %35};\n" \
    "wgmma.mma_async.sync.aligned.m64n64k16.f32.bf16.bf16 "               \
    "{%0,%1,%2,%3,%4,%5,%6,%7,%8,%9,%10,%11,%12,%13,%14,%15,%16,%17,%18,%19,%20,%21,%22,%23,%24,%25,%26,%27,%28,%29,%30,%31}, da, db, " SD ", 1, 1, %36, %37;\n}"
    if constexpr (ACC == 1)
        asm volatile(WG_ASM("1") : RW32("+f", d) : "r"(loA), "r"(loB), "n"(HI_SW128), "n"(HIB), "n"(TA), "n"(TB));
    else
        asm volatile(WG_ASM("0") : RW32("=f", d) : "r"(loA), "r"(loB), "n"(HI_SW128), "n"(HIB), "n"(TA), "n"(TB));
#undef WG_ASM
}

__device__ __forceinline__ uint32_t pack_bf16(float lo, float hi) {
    uint32_t r;
    asm("cvt.rn.bf16x2.f32 %0, %1, %2;" : "=r"(r) : "f"(hi), "f"(lo));
    return r;
}
__device__ __forceinline__ float ex2(float x) {
    float r;
    asm("ex2.approx.ftz.f32 %0, %1;" : "=f"(r) : "f"(x));
    return r;
}
__device__ __forceinline__ void stsm4t(uint32_t a, uint32_t r0, uint32_t r1, uint32_t r2, uint32_t r3) {
    asm volatile("stmatrix.sync.aligned.m8n8.x4.trans.shared.b16 [%0], {%1,%2,%3,%4};" ::"r"(a), "r"(r0), "r"(r1), "r"(r2), "r"(r3)
                 : "memory");
}
__device__ __forceinline__ uint32_t lds_u(uint32_t a) {
    uint32_t v;
    asm volatile("ld.shared.u32 %0, [%1];" : "=r"(v) : "r"(a) : "memory");
    return v;
}
__device__ __forceinline__ uint4 lds_u4(uint32_t a) {
    uint4 v;
    asm volatile("ld.shared.v4.u32 {%0,%1,%2,%3}, [%4];" : "=r"(v.x), "=r"(v.y), "=r"(v.z), "=r"(v.w) : "r"(a) : "memory");
    return v;
}
__device__ __forceinline__ float2 lds_f2(uint32_t a) {
    float2 v;
    asm volatile("ld.shared.v2.f32 {%0,%1}, [%2];" : "=f"(v.x), "=f"(v.y) : "r"(a) : "memory");
    return v;
}
__device__ __forceinline__ void sts_f(uint32_t a, float v) { asm volatile("st.shared.f32 [%0], %1;" ::"r"(a), "f"(v) : "memory"); }
__device__ __forceinline__ void sts_u(uint32_t a, uint32_t v) { asm volatile("st.shared.u32 [%0], %1;" ::"r"(a), "r"(v) : "memory"); }
__device__ __forceinline__ void sts_f2(uint32_t a, float x, float y) {
    asm volatile("st.shared.v2.f32 [%0], {%1,%2};" ::"r"(a), "f"(x), "f"(y) : "memory");
}

template <bool ADD = false, bool SIG = false, int NR>
__device__ __forceinline__ void store_tile_t(const float (&d)[NR], uint32_t addr) {
    uint32_t p[NR / 2];
    if (ADD) {
#pragma unroll
        for (int j = 0; j < NR / 8; j++)
            asm volatile("ldmatrix.sync.aligned.m8n8.x4.trans.shared.b16 {%0,%1,%2,%3}, [%4];"
                         : "=r"(p[4 * j]), "=r"(p[4 * j + 1]), "=r"(p[4 * j + 2]), "=r"(p[4 * j + 3])
                         : "r"(addr + j * 2048)
                         : "memory");
    }
#pragma unroll
    for (int k = 0; k < NR / 2; k++)
        p[k] = ADD ? pack_bf16(d[2 * k] + __uint_as_float(p[k] << 16), d[2 * k + 1] + __uint_as_float(p[k] & 0xffff0000u))
                   : pack_bf16(d[2 * k], d[2 * k + 1]);
#pragma unroll
    for (int j = 0; j < NR / 8; j++) {
        stsm4t(addr + j * 2048, p[4 * j], p[4 * j + 1], p[4 * j + 2], p[4 * j + 3]);
        if (SIG && j == 0) nb_arrive<NB_L, 160>();
    }
}

struct TrueT { static constexpr bool value = true; };
struct FalseT { static constexpr bool value = false; };

template <int V>
struct IntT { static constexpr int value = V; };

__device__ __forceinline__ uint32_t get_item(uint32_t sb, int it, uint32_t dl) {
    mbar_wait(sb + BAR_ITEM + it * 8, 0, dl);
    return lds_u(sb + OFF_ITEM + it * 4);
}
__device__ __forceinline__ uint32_t get_item_warp(uint32_t sb, int it, uint32_t dl) {
    return __shfl_sync(0xffffffffu, get_item(sb, it, dl), 0);
}

struct Ring {
    uint32_t slot, ph, dl;
    __device__ __forceinline__ void adv(uint32_t k) {
        slot += k;
        if (slot >= NSLOT) { slot -= NSLOT; ph ^= 1; }
    }
};

template <int K>
__device__ __forceinline__ void qk_step(float (&s)[80], uint32_t loK, uint32_t loQ) {
    wgmma<0, 0, HI_SW128, K != 0>(s, loK + (K >> 2) * (8192 >> 4) + (K & 3) * 2, loQ + (K >> 2) * (XS >> 4) + (K & 3) * 2);
}
template <int K0, int K1>
__device__ __forceinline__ void qk_steps(float (&s)[80], uint32_t loK, uint32_t loQ) {
    if constexpr (K0 < K1) {
        qk_step<K0>(s, loK, loQ);
        qk_steps<K0 + 1, K1>(s, loK, loQ);
    }
}
__device__ __forceinline__ uint32_t add_bf2(uint32_t a, uint32_t b) {
    uint32_t r;
    asm("add.rn.bf16x2 %0, %1, %2;" : "=r"(r) : "r"(a), "r"(b));
    return r;
}
__device__ __forceinline__ uint32_t fma_bf2(uint32_t a, uint32_t b, uint32_t c) {
    uint32_t r;
    asm("fma.rn.bf16x2 %0, %1, %2, %3;" : "=r"(r) : "r"(a), "r"(b), "r"(c));
    return r;
}
template <int J>
__device__ __forceinline__ void exp_block(const float (&s)[80], uint32_t (&k)[40], uint32_t pa, float mref) {
    if constexpr (J < 10) {
#pragma unroll
        for (int i = 4 * J; i < 4 * J + 4; i++)
            k[i] = pack_bf16(ex2(fmaf(s[2 * i], SM_C, -mref)), ex2(fmaf(s[2 * i + 1], SM_C, -mref)));
#pragma unroll
        for (int i = 0; i < 4; i++)
            asm volatile("stmatrix.sync.aligned.m8n8.x1.trans.shared.b16 [%0], {%1};" ::"r"(((i & 1) ? pa ^ 16 : pa) + J * 2048 + (i >> 1) * 1024),
                         "r"(k[4 * J + i])
                         : "memory");
        exp_block<J + 1>(s, k, pa, mref);
    }
}
__device__ __forceinline__ void sum_block(const uint32_t (&k)[40], float (&l)[10], uint32_t lane) {
    const bool b4 = lane & 16, b3 = lane & 8;
    uint32_t ps[20], t[10];
#pragma unroll
    for (int j = 0; j < 20; j++) ps[j] = add_bf2(k[2 * j], k[2 * j + 1]);
#pragma unroll
    for (int j = 0; j < 10; j++)
        t[j] = add_bf2(b4 ? ps[2 * j + 1] : ps[2 * j], __shfl_xor_sync(0xffffffffu, b4 ? ps[2 * j] : ps[2 * j + 1], 16));
#pragma unroll
    for (int i = 0; i < 5; i++) {
        const uint32_t a = b3 ? t[i + 5] : t[i], b = __shfl_xor_sync(0xffffffffu, b3 ? t[i] : t[i + 5], 8);
        l[2 * i] += __uint_as_float(a << 16) + __uint_as_float(b << 16);
        l[2 * i + 1] += __uint_as_float(a & 0xffff0000u) + __uint_as_float(b & 0xffff0000u);
    }
}
template <bool ADD>
__device__ __forceinline__ void sum_store(const float (&l)[10], uint32_t lane, uint32_t lxa) {
    const bool b2 = lane & 4;
    float t[5];
#pragma unroll
    for (int i = 0; i < 5; i++) t[i] = ADD ? __uint_as_float(lds_u(lxa + i * 64)) : 0.f;
#pragma unroll
    for (int i = 0; i < 5; i++)
        sts_f(lxa + i * 64, t[i] + (b2 ? l[2 * i + 1] : l[2 * i]) + __shfl_xor_sync(0xffffffffu, b2 ? l[2 * i] : l[2 * i + 1], 4));
}

__device__ __forceinline__ void fallback_unit(const Params& P, uint32_t e, uint32_t tid) {
    const uint32_t lane = tid & 31, br = IT_BR(e), b = IT_B(e), h = IT_H0(e);
    const __nv_bfloat162* wq = (const __nv_bfloat162*)(P.pwq[br] + h * 192) + lane;
    const __nv_bfloat162* kp = (const __nv_bfloat162*)(P.pk[br] + (size_t)(b * 32 + h) * 512 * 192) + lane;
    const __nv_bfloat162* vp = (const __nv_bfloat162*)(P.pv[br] + (size_t)(b * 32 + h) * 512 * 192) + lane;
#pragma unroll 1
    for (uint32_t qi = 0; qi < 40; qi++) {
        const uint32_t q = 4 * qi + (tid >> 5);
        const __nv_bfloat16* xr = P.px[br] + (size_t)(b * 160 + q) * 640;
        float a[6] = {0.f, 0.f, 0.f, 0.f, 0.f, 0.f};
#pragma unroll 2
        for (int k = 0; k < 640; k++) {
            const float xv = __bfloat162float(xr[k]);
#pragma unroll
            for (int i = 0; i < 3; i++) {
                const float2 wv = __bfloat1622float2(wq[(size_t)k * 3072 + i * 32]);
                a[2 * i] = fmaf(xv, wv.x, a[2 * i]);
                a[2 * i + 1] = fmaf(xv, wv.y, a[2 * i + 1]);
            }
        }
#pragma unroll
        for (int i = 0; i < 6; i++) a[i] = __bfloat162float(__float2bfloat16(a[i]));
        auto score = [&](int key) {
            float d = 0.f;
#pragma unroll
            for (int i = 0; i < 3; i++) {
                const float2 kv = __bfloat1622float2(kp[key * 96 + i * 32]);
                d = fmaf(a[2 * i], kv.x, fmaf(a[2 * i + 1], kv.y, d));
            }
#pragma unroll
            for (int o = 16; o > 0; o >>= 1) d += __shfl_xor_sync(0xffffffffu, d, o);
            return d;
        };
        float m = -INFINITY, o[6] = {0.f, 0.f, 0.f, 0.f, 0.f, 0.f}, sum = 0.f;
#pragma unroll 1
        for (int n = 0; n < 1024; n++) {
            const int key = n & 511;
            const float d = score(key);
            if (n < 512) {
                m = fmaxf(m, d);
            } else {
                const float p = ex2((d - m) * SM_C);
                sum += p;
#pragma unroll
                for (int i = 0; i < 3; i++) {
                    const float2 vv = __bfloat1622float2(vp[key * 96 + i * 32]);
                    o[2 * i] = fmaf(p, vv.x, o[2 * i]);
                    o[2 * i + 1] = fmaf(p, vv.y, o[2 * i + 1]);
                }
            }
        }
        const float inv = __fdividef(1.f, sum);
        __nv_bfloat16* op = (__nv_bfloat16*)ostash(IT_SLOT(e), b) + (q >> 5) * 256 + 2 * ((q & 31) >> 3) + (q & 1);
#pragma unroll
        for (int i = 0; i < 6; i++) {
            const uint32_t d = (i >> 1) * 64 + 2 * lane + (i & 1);
            op[(d >> 3) * 1280 + (d & 7) * 32 + ((((q & 7) >> 1) ^ ((d & 7) >> 1)) << 3)] = __float2bfloat16(o[i] * inv);
        }
    }
}

template <int W>
struct PendO {
    static constexpr int N = W == 0 ? 56 : 64;
    uint32_t v[N];
    unsigned char* gp;
    static __device__ __forceinline__ uint32_t toff() {
        const uint32_t t = tid_now();
        return ((t >> 5) & 3) * 5120 + ((t >> 2) & 7) * 64 + (((t ^ (t >> 3)) & 3) << 4);
    }
    uint32_t pend, sig, bad;
    static __device__ __forceinline__ void scale(uint32_t& x, uint32_t hi, uint32_t lo) {
        asm("{\n.reg .b32 t;\nmul.rn.bf16x2 t, %0, %2;\nfma.rn.bf16x2 %0, %0, %1, t;\n}" : "+r"(x) : "r"(hi), "r"(lo));
    }
    template <int I, int OFF>
    __device__ __forceinline__ void put() {
        asm volatile("{\n.reg .pred p;\nsetp.ne.u32 p, %6, 0;\n@p st.global.v4.b32 [%0+%5], {%1,%2,%3,%4};\n}" ::"l"(gp), "r"(v[I]),
                     "r"(v[I + 1]), "r"(v[I + 2]), "r"(v[I + 3]), "n"(OFF), "r"(pend)
                     : "memory");
    }
    __device__ __forceinline__ void verdict(uint32_t sb) {
        if (sig) {
            nb_sync<NB_VOTE + W, 160>();
            bad = __any_sync(0xffffffffu, lds_u(sb + OFF_FB) != 0);
            pend = !bad;
        }
    }
    template <int G, int H>
    __device__ __forceinline__ void half(uint32_t sb) {
        constexpr bool T2 = W == 0 ? G >= 3 : G < 3;
        constexpr int B = T2 ? 40 + 8 * (W == 0 ? G - 3 : G) : 0;
        const uint4 a = lds_u4(sb + OFF_LINV + G * 128 + H * 16 + (threadIdx.x & 3) * 32);
#pragma unroll
        for (int i = 2 * H; i < 8; i += 4) {
            scale(v[8 * G + i], a.x, a.y);
            scale(v[8 * G + i + 1], a.z, a.w);
            if (T2) {
                scale(v[B + i], a.x, a.y);
                scale(v[B + i + 1], a.z, a.w);
            }
        }
        if (H == 1) {
            put<8 * G, W * XS + G * 512>();
            put<8 * G + 4, W * XS + G * 512 + 2560>();
            if (T2) {
                put<B, 2 * XS + G * 512>();
                put<B + 4, 2 * XS + G * 512 + 2560>();
            }
            if (G == 4 && pend) nb_arrive<NB_ODONE, 288>();
        }
    }
    template <int G>
    __device__ __forceinline__ void step(uint32_t sb) {
        half<G, 0>(sb);
        half<G, 1>(sb);
    }
    __device__ __forceinline__ void clear() {
#pragma unroll
        for (int i = 0; i < N; i++) v[i] = 0;
        gp = nullptr;
        pend = 0;
        sig = 0;
        bad = 0;
    }
};

__device__ __forceinline__ uint32_t stsm_off() {
    const uint32_t tid = tid_now(), lane = tid & 31;
    return (lane >> 4) * 1024 + (lane & 7) * 128 + (((((tid >> 4) & 6) + ((lane >> 3) & 1)) ^ (lane & 7)) << 4);
}
template <int W, int KK>
__device__ __forceinline__ void qproj(float (&q0)[80], float (&q1)[80], uint32_t sb, Ring& r, uint32_t pslot, uint32_t phm,
                                      PendO<W>& po) {
    const uint32_t loR = (((sb + OFF_R) & 0x3ffff) >> 4) | LO_LBO1;
    const uint32_t loRing = (((sb + OFF_RING) & 0x3ffff) >> 4) | LO_LBO1;
    auto ready = [&](int k) {
        mbar_wait(sb + BAR_RFULL + r.slot * 8, r.ph, r.dl);
        mbar_wait(sb + BAR_XFULL + (k % 5) * 8, ((phm >> (k % 5)) ^ (k / 5)) & 1, r.dl);
    };
    auto release = [&]() {
        if (KK > 0) {
            wg_wait<1>();
            mbar_arrive_warp(sb + BAR_REMPTY + pslot * 8);
            if (KK <= 5) mbar_arrive_warp(sb + (BAR_XEMPTY + (KK - 1) * 8));
        }
    };
    if (KK == 0 && (W == 1 || !po.sig)) ready(0);
    if (W == 1 && KK == QHOLD) {
        if (QHOLD == 7) {
            wg_wait<0>();
            nb_arrive<NB_PDONE, 256>();
        }
        nb_sync<NB_SDONE, 256>();
    }
    const uint32_t a = loRing + r.slot * (SLOT >> 4) + (W == 0 ? 0 : 512), b = loR + (KK % 5) * (XS >> 4);
    wg_fence();
    wgmma<1, 0, HI_SW128, KK != 0>(q0, a, b);
    if (W == 0) wgmma<1, 0, HI_SW128, KK != 0>(q1, a + 256, b);
#pragma unroll
    for (int k = 1; k < 4; k++) {
        wgmma<1, 0, HI_SW128, true>(q0, a + (k >> 1) * 768 + (k & 1) * 128, b + k * 2);
        if (W == 0) wgmma<1, 0, HI_SW128, true>(q1, a + 256 + (k >> 1) * 768 + (k & 1) * 128, b + k * 2);
    }
    wg_commit();
    const uint32_t cslot = r.slot;
    r.adv(1);
    if (W == 0 || KK < QHOLD) release();
    if (KK == QST0) {
        po.verdict(sb);
        po.template half<0, 0>(sb);
    }
    if (KK < 9) ready(KK + 1);
    if (W == 1 && KK >= QHOLD) release();
    if (W == 1 && KK == 7 && QHOLD > 7) nb_arrive<NB_PDONE, 256>();
    if (KK == QST0) po.template half<0, 1>(sb);
    if constexpr (KK > QST0 && KK < QST0 + 5) po.template step<KK - QST0>(sb);
    if constexpr (KK < (W == 0 ? 7 : 9)) {
        qproj<W, KK + 1>(q0, q1, sb, r, cslot, phm, po);
    } else if constexpr (W == 1) {
        wg_wait<0>();
        reg_fence(q0);
        mbar_arrive_warp(sb + BAR_REMPTY + cslot * 8);
        store_tile_t<false, true>(q0, sb + OFF_R + 2 * XS + stsm_off());
    } else {
        const uint32_t s8 = r.slot, a8 = loRing + s8 * (SLOT >> 4);
        wg_fence();
#pragma unroll
        for (int k = 0; k < 4; k++) wgmma<1, 0, HI_SW128, true>(q0, a8 + (k >> 1) * 768 + (k & 1) * 128, loR + 3 * (XS >> 4) + k * 2);
        r.adv(1);
        ready(9);
        const uint32_t s9 = r.slot, a9 = loRing + s9 * (SLOT >> 4);
        r.adv(1);
        wg_fence();
#pragma unroll
        for (int k = 0; k < 4; k++) wgmma<1, 0, HI_SW128, true>(q0, a9 + (k >> 1) * 768 + (k & 1) * 128, loR + 4 * (XS >> 4) + k * 2);
        wg_commit();
        wg_wait<1>();
        mbar_arrive_warp(sb + BAR_REMPTY + cslot * 8);
        wg_fence();
#pragma unroll
        for (int k = 0; k < 8; k++)
            wgmma<1, 0, HI_SW128, true>(q1, (k < 4 ? a8 : a9) + 256 + ((k >> 1) & 1) * 768 + (k & 1) * 128,
                                        loR + (3 + (k >> 2)) * (XS >> 4) + (k & 3) * 2);
        wg_commit();
        nb_arrive<NB_SDONE, 256>();
        nb_sync<NB_PDONE, 256>();
        wg_wait<1>();
        reg_fence(q0);
        const uint32_t sta = sb + OFF_R + stsm_off();
        store_tile_t(q0, sta);
        sts_u(sb + OFF_GM + 4, r.slot);
        mbar_wait(sb + BAR_RFULL + r.slot * 8, r.ph, r.dl);
        wg_wait<0>();
        reg_fence(q1);
        mbar_arrive_warp(sb + BAR_REMPTY + s8 * 8);
        mbar_arrive_warp(sb + BAR_REMPTY + s9 * 8);
        store_tile_t(q1, sta + XS);
    }
}

template <int NR>
__device__ __forceinline__ void opack(const float (&o)[NR], uint32_t* v) {
#pragma unroll
    for (int g = 0; g < NR / 16; g++)
#pragma unroll
        for (int hh = 0; hh < 2; hh++)
#pragma unroll
            for (int t = 0; t < 4; t++) v[8 * g + 4 * hh + t] = pack_bf16(o[16 * g + 4 * t + 2 * hh], o[16 * g + 4 * t + 2 * hh + 1]);
}

template <bool IS_S>
__device__ __forceinline__ void op_item(uint32_t e, uint32_t sb, Ring& r, uint32_t& phm) {
    constexpr int T0 = IS_S ? 0 : 2;
    constexpr uint32_t BOFF = IS_S ? (3 * 512) >> 4 : 0;
    const uint32_t loRing = (((sb + OFF_RING) & 0x3ffff) >> 4) | LO_LBO1;
    const uint32_t loO = (((sb + OFF_R) & 0x3ffff) >> 4) | LO_OST;
    float c0[80], c1[80], c2[IS_S ? 32 : 48];
    const int T = 3 * (IT_H1(e) - IT_H0(e));
    uint32_t xs = 0;
    auto step = [&](auto first, auto half) {
        constexpr bool F = decltype(first)::value;
        constexpr uint32_t hf = decltype(half)::value;
        if (hf == 0) {
            mbar_wait(sb + BAR_XFULL + xs * 8, (phm >> xs) & 1, r.dl);
            phm ^= 1u << xs;
        }
        mbar_wait(sb + BAR_RFULL + r.slot * 8, r.ph, r.dl);
        const uint32_t a = loRing + r.slot * (SLOT >> 4), b = loO + xs * (XS >> 4) + hf * 640;
        wg_fence();
        wgmma<1, 1, HI_OST, !F>(c0, a + T0 * 128, b);
        wgmma<1, 1, HI_OST, !F>(c1, a + T0 * 128 + 128, b);
        wgmma<1, 1, HI_OST, !F>(c2, a + 512, b + BOFF);
        wgmma<1, 1, HI_OST, true>(c0, a + 640 + T0 * 128, b + 320);
        wgmma<1, 1, HI_OST, true>(c1, a + 640 + T0 * 128 + 128, b + 320);
        wgmma<1, 1, HI_OST, true>(c2, a + 640 + 512, b + 320 + BOFF);
        wg_commit();
    };
    step(TrueT{}, IntT<0>{});
#pragma unroll 1
    for (int t = 1;; t++) {
        uint32_t pslot = r.slot;
        r.adv(1);
        step(FalseT{}, IntT<1>{});
        wg_wait<1>();
        mbar_arrive_warp(sb + BAR_REMPTY + pslot * 8);
        if (t == T) break;
        pslot = r.slot;
        const uint32_t pxs = xs;
        r.adv(1);
        if (++xs == 5) xs = 0;
        step(FalseT{}, IntT<0>{});
        wg_wait<1>();
        mbar_arrive_warp(sb + BAR_REMPTY + pslot * 8);
        mbar_arrive_warp_if(sb + BAR_XEMPTY + pxs * 8, t + 4 < T);
    }
    wg_wait<0>();
    reg_fence(c0);
    reg_fence(c1);
    reg_fence(c2);
    mbar_arrive_warp(sb + BAR_REMPTY + r.slot * 8);
    r.adv(1);
    nb_sync<NB_OPEND, 256>();
    const uint32_t sta = sb + OFF_R + stsm_off();
    store_tile_t(c0, sta + T0 * XS);
    store_tile_t(c1, sta + (T0 + 1) * XS);
    store_tile_t(c2, sta + 4 * XS + (IS_S ? 96 * 128 : 0));
    fence_async_smem();
    nb_arrive<NB_ODONE, 288>();
}

__device__ __forceinline__ void on_item(uint32_t W, uint32_t e, uint32_t sb, Ring& r, uint32_t& phm) {
    const uint32_t loRing = (((sb + OFF_RING) & 0x3ffff) >> 4) | LO_LBO1;
    const uint32_t loO = (((sb + OFF_R) & 0x3ffff) >> 4) | LO_OST;
    float c[80];
    const int T = 3 * (IT_H1(e) - IT_H0(e));
    uint32_t xs = 0;
    auto step = [&](auto first) {
        constexpr bool F = decltype(first)::value;
        mbar_wait(sb + BAR_XFULL + xs * 8, (phm >> xs) & 1, r.dl);
        phm ^= 1u << xs;
        mbar_wait(sb + BAR_RFULL + r.slot * 8, r.ph, r.dl);
        const uint32_t a = loRing + r.slot * (SLOT >> 4) + W * 256, b = loO + xs * (XS >> 4);
        wg_fence();
        wgmma<1, 1, HI_OST, !F>(c, a, b);
#pragma unroll
        for (int k = 1; k < 4; k++) wgmma<1, 1, HI_OST, true>(c, a + (k >> 1) * 512 + (k & 1) * 128, b + k * 320);
        wg_commit();
    };
    step(TrueT{});
#pragma unroll 1
    for (int t = 1; t < T; t++) {
        const uint32_t pslot = r.slot, pxs = xs;
        r.adv(1);
        if (++xs == 5) xs = 0;
        step(FalseT{});
        wg_wait<1>();
        mbar_arrive_warp(sb + BAR_REMPTY + pslot * 8);
        mbar_arrive_warp_if(sb + BAR_XEMPTY + pxs * 8, t + 2 < T);
    }
    xs += 1 + W;
    if (xs >= 5) xs -= 5;
    mbar_wait(sb + BAR_XFULL + xs * 8, (phm >> xs) & 1, r.dl);
    wg_wait<0>();
    reg_fence(c);
    store_tile_t<true>(c, sb + OFF_R + xs * XS + stsm_off());
    fence_async_smem();
    nb_arrive<NB_ODONE, 288>();
}

template <int W>
__device__ __forceinline__ uint32_t qa_item(uint32_t e, uint32_t sb, Ring& r, uint32_t phm, PendO<W>& po, int it) {
    const uint32_t loR = (((sb + OFF_R) & 0x3ffff) >> 4) | LO_LBO1;
    const uint32_t loRing = (((sb + OFF_RING) & 0x3ffff) >> 4) | LO_LBO1;
    {
        float q0[80], q1[80];
        qproj<W, 0>(q0, q1, sb, r, 0, phm, po);
    }
    fence_async_smem();
    TSD(W, 1);
    float s[80], oa[80], ob[W == 0 ? 32 : 48], l[10];
    if (W == 1) {
        nb_arrive<NB_Q2, 256>();
        zero(oa);
        zero(ob);
        reg_fence(oa);
        reg_fence(ob);
    }
    const uint32_t lane = tid_now() & 31, sta = sb + OFF_R + stsm_off();
    auto pv = [&](auto first, uint32_t buf) {
        constexpr bool F = decltype(first)::value;
        mbar_wait(sb + BAR_RFULL + r.slot * 8, r.ph, r.dl);
        const uint32_t a = loRing + r.slot * (SLOT >> 4), b = loR + (3 + buf) * (XS >> 4);
        wg_fence();
        wgmma<1, 0, HI_SW128, !F>(oa, a + W * 512, b);
        wgmma<1, 0, HI_SW128, !F>(ob, a + 1024, b + (W == 0 ? (96 * 128) >> 4 : 0));
#pragma unroll
        for (int k = 1; k < 4; k++) {
            wgmma<1, 0, HI_SW128, true>(oa, a + W * 512 + k * 128, b + k * 2);
            wgmma<1, 0, HI_SW128, true>(ob, a + 1024 + k * 128, b + (W == 0 ? (96 * 128) >> 4 : 0) + k * 2);
        }
        wg_commit();
    };
    zero(l);
    float mref;
    uint32_t kslot, vslot;
    auto tail = [&](auto first, int i) {
        constexpr bool rel_other = !decltype(first)::value;
        uint32_t ps[40];
        exp_block<0>(s, ps, sta + (3 + W) * XS, mref);
        if (rel_other) {
            wg_wait<0>();
            mbar_arrive_warp(sb + BAR_REMPTY + vslot * 8);
            if (W == 1) mbar_arrive_warp_if(sb + BAR_XEMPTY + 24, i == 3);
        }
        fence_async_smem();
        nb_arrive<NB_PFULL + W, 256>();
        TSD(W, 6 + 5 * i);
        if (W == 1) {
            if (XLATE >= 2) mbar_arrive_warp_if<2>(sb + BAR_XEMPTY + 8, i == 3);
            if (XLATE >= 1) mbar_arrive_warp_if<2>(sb + BAR_XEMPTY + 16, i == 3);
        }
        if (rel_other || !PV0FIRST) {
            mbar_wait(sb + BAR_RFULL + r.slot * 8, r.ph, r.dl);
            sum_block(ps, l, lane);
        }
        TSD(W, 7 + 5 * i);
        if (LASTORD && W == 0 && i == 3) nb_sync<NB_PDONE, 256>();
        else nb_sync<NB_W + W, 128>();
        pv(first, W);
        if (!rel_other && PV0FIRST) sum_block(ps, l, lane);
        TSD(W, 8 + 5 * i);
    };
    if (W == 0) {
        nb_sync<NB_QK, 160>();
        TSD(W, 2);
        wg_fence();
        qk_steps<0, 8>(s, loRing + r.slot * (SLOT >> 4), loR);
        nb_sync<NB_Q2, 256>();
        qk_steps<8, 12>(s, loRing + r.slot * (SLOT >> 4), loR);
        wg_commit();
        nb_arrive<NB_Q01, 256>();
        TSD(W, 4);
        nb_sync<NB_REF, 160>();
        mref = __uint_as_float(lds_u(sb + OFF_GM));
        wg_wait<0>();
        reg_fence(s);
        mbar_arrive_warp<2>(sb + BAR_REMPTY + r.slot * 8);
        r.adv(2);
        TSD(W, 5);
        tail(TrueT{}, 0);
    } else {
        nb_sync<NB_Q01, 256>();
    }
#pragma unroll 1
    for (int i = (W == 0 ? 1 : 0); i < 4; i++) {
        const uint32_t pvslot = r.slot;
        r.adv(1);
        kslot = r.slot;
        mbar_wait(sb + BAR_RFULL + r.slot * 8, r.ph, r.dl);
        wg_fence();
        qk_steps<0, 12>(s, loRing + r.slot * (SLOT >> 4), loR);
        wg_commit();
        wg_wait<1>();
        mbar_arrive_warp_if(sb + BAR_REMPTY + pvslot * 8, W == 0 || i > 0);
        r.adv(1);
        vslot = r.slot;
        TSD(W, 4 + 5 * i);
        nb_sync<NB_PFULL + (W ^ 1), 256>();
        pv(FalseT{}, W ^ 1);
        if (LASTORD && W == 1 && i == 3) nb_arrive<NB_PDONE, 256>();
        if (W == 1) mref = __uint_as_float(lds_u(sb + OFF_GM));
        wg_wait<1>();
        reg_fence(s);
        mbar_arrive_warp<2>(sb + BAR_REMPTY + kslot * 8);
        if (W == 1) {
            mbar_arrive_warp_if<2>(sb + BAR_XEMPTY + 0, i == 3);
            if (XLATE < 2) mbar_arrive_warp_if<2>(sb + BAR_XEMPTY + 8, i == 3);
            if (XLATE < 1) mbar_arrive_warp_if<2>(sb + BAR_XEMPTY + 16, i == 3);
        }
        r.adv(W == 1 && i == 3 ? 1 : 2);
        TSD(W, 5 + 5 * i);
        tail(FalseT{}, i);
    }
    const uint32_t w = (tid_now() >> 5) & 3;
    const uint32_t lxa = sb + OFF_LX + w * 640 + (((lane & 8) ? 80 : 0) + ((lane >> 1) & 8) + 2 * (lane & 3) + ((lane >> 2) & 1)) * 4;
    const uint32_t nx = get_item_warp(sb, it + 1, r.dl);
    po.gp = ostash(IT_SLOT(e), IT_B(e)) + po.toff();
    po.sig = 1;
    if (W == 0) {
        sum_store<false>(l, lane, lxa);
        nb_arrive<NB_LX, 256>();
        wg_wait<0>();
        mbar_arrive_warp(sb + BAR_REMPTY + r.slot * 8);
        mbar_arrive_warp(sb + BAR_XEMPTY + 24);
        r.adv(1);
        nb_sync<NB_PFULL + 1, 256>();
        pv(FalseT{}, 1);
        if (IT_TYPE(nx) == IT_QA) {
            Ring rn = r;
            rn.adv(1);
            mbar_wait(sb + BAR_RFULL + rn.slot * 8, rn.ph, r.dl);
            mbar_wait(sb + BAR_XFULL, phm & 1, r.dl);
        }
    } else {
        nb_sync<NB_LX, 256>();
        sum_store<true>(l, lane, lxa);
        nb_arrive<NB_L, 160>();
    }
    TSD(W, 24);
    wg_wait<0>();
    reg_fence(oa);
    reg_fence(ob);
    mbar_arrive_warp(sb + BAR_REMPTY + r.slot * 8);
    mbar_arrive_warp(sb + BAR_XEMPTY + 32);
    r.adv(1);
    opack(ob, po.v + 40);
    opack(oa, po.v);
    return nx;
}

template <int W>
__device__ __forceinline__ uint32_t qa_run(const Params& P, uint32_t e, uint32_t sb, Ring& r, uint32_t phm, int& it) {
    PendO<W> po;
    po.clear();
#pragma unroll 1
    do {
        TS(W, 0);
        if (W == 0) TS_ITEM(e);
        e = qa_item<W>(e, sb, r, phm, po, it);
        TS(W, 31);
        it++;
    } while (IT_TYPE(e) == IT_QA && !po.bad);
#pragma unroll 1
    for (int m = po.bad ? 2 : 1; m > 0; m--) {
        if (m == 1) {
            po.verdict(sb);
            po.template step<0>(sb);
            po.template step<1>(sb);
            po.template step<2>(sb);
            po.template step<3>(sb);
            po.template step<4>(sb);
        }
        if (po.bad) {
            if (W == 0) fallback_unit(P, lds_u(sb + OFF_ITEM + (it - m) * 4), tid_now() & 127);
            __syncwarp();
            nb_sync<NB_ODONE, 288>();
        }
    }
    return e;
}

__device__ __forceinline__ void consumer(const Params& P, uint32_t W, uint32_t sb, uint32_t dl) {
    int it = 0;
    Ring r{0, 0, dl};
    uint32_t phm = 0;
    uint32_t e = get_item_warp(sb, 0, dl);
#pragma unroll 1
    while (true) {
        if (IT_TYPE(e) == IT_QA) e = W == 0 ? qa_run<0>(P, e, sb, r, phm, it) : qa_run<1>(P, e, sb, r, phm, it);
        if (e == 0) break;
        if (IT_TYPE(e) == IT_QA) continue;
        TS(W, 0);
        if (W == 0) TS_ITEM(e);
        if (IT_TYPE(e) == IT_ON) on_item(W, e, sb, r, phm);
        else if (W == 0) op_item<true>(e, sb, r, phm);
        else op_item<false>(e, sb, r, phm);
        TS(W, 31);
        e = get_item_warp(sb, ++it, dl);
    }
    TS_DUMP(W);
}

__global__ void __cluster_dims__(2, 1, 1) __launch_bounds__(384, 1) fused_kernel(const __grid_constant__ Params P) {
    extern __shared__ __align__(1024) unsigned char smem_raw[];
    const uint32_t sb = (uint32_t)__cvta_generic_to_shared(smem_raw);
    const uint32_t warp = __shfl_sync(0xffffffffu, threadIdx.x >> 5, 0), wgid = warp >> 2;
    const uint32_t cta = blockIdx.x;
    const uint32_t dl = deadline();

    if (threadIdx.x == 128) {
#pragma unroll
        for (int i = 0; i < NSLOT; i++) {
            mbar_init(sb + BAR_RFULL + i * 8, 1);
            mbar_init(sb + BAR_REMPTY + i * 8, 8);
            mbar_init(sb + BAR_XFULL + i * 8, 1);
            mbar_init(sb + BAR_XEMPTY + i * 8, 8);
        }
        asm volatile("fence.mbarrier_init.release.cluster;" ::: "memory");
        fence_async_smem();
    } else if (threadIdx.x == 160) {
#pragma unroll
        for (int i = 0; i < NSLOT + MAXI; i++) mbar_init(sb + BAR_PRDY + i * 8, 1);
        asm volatile("fence.mbarrier_init.release.cluster;" ::: "memory");
    } else if (threadIdx.x == 0) {
        sts_u(sb + OFF_ITEM, P.cl[cta >> 1].items[0] ? P.cl[cta >> 1].items[0] + 8 * (cta & 1) : 0);
        sts_u(sb + OFF_FB, P.cl[cta >> 1].delay);
    } else if (threadIdx.x == 64) {
        if (sb & 1023) __trap();
        asm volatile("prefetch.tensormap [%0];" ::"l"(&P.wq[0]) : "memory");
        asm volatile("prefetch.tensormap [%0];" ::"l"(&P.x[0]) : "memory");
    }
    __syncthreads();
    {
        const int it = 0;
        if (wgid == 1) TS(0, 30);
    }
    asm volatile("barrier.cluster.arrive.relaxed.aligned;" ::: "memory");
    if (warp == 0) {
        const uint32_t e = __shfl_sync(0xffffffffu, lds_u(sb + OFF_ITEM), 0), d = lds_u(sb + OFF_FB);
        const uint64_t pol = mkpol<POL_W>();
        uint32_t t0, t1;
        asm volatile("mov.u32 %0, %%clock;" : "=r"(t0));
        do {
            asm volatile("mov.u32 %0, %%clock;" : "=r"(t1));
        } while (t1 - t0 < d);
        __syncwarp();
#pragma unroll 1
        for (int n = 0; n < (e ? NSLOT : 0); n++) {
            if (threadIdx.x == 0) {
                mbar_expect(sb + BAR_RFULL + n * 8, SLOT);
                tma3(sb + OFF_RING + n * SLOT, &P.wq[0], n * 64, IT_H0(e) * 3, sb + BAR_RFULL + n * 8, pol);
                mbar_expect(sb + BAR_XFULL + n * 8, XS);
                tma3(sb + OFF_R + n * XS, &P.x[0], IT_B(e) * 160, n, sb + BAR_XFULL + n * 8, pol);
                tma3(sb + OFF_RING + n * SLOT + SLOT / 2, &P.wq[0], n * 64 + 32, IT_H0(e) * 3, sb + BAR_RFULL + n * 8, pol);
            }
        }
        if (threadIdx.x == 0) asm volatile("mbarrier.arrive.shared::cta.b64 _, [%0];" ::"r"(sb + BAR_ITEM) : "memory");
        __syncwarp();
    }

    if (wgid == 0) {
        asm volatile("setmaxnreg.dec.sync.aligned.u32 24;");
        if (warp == 0) {
            const bool lead = threadIdx.x == 0;
            const uint64_t pol_first = mkpol<1>(), pol_norm = mkpol<POL_W>();
            uint32_t e = __shfl_sync(0xffffffffu, lds_u(sb + OFF_ITEM), 0);
            asm volatile("barrier.cluster.wait.aligned;" ::: "memory");
            unsigned int* const ticket = &g_ticket[next_epoch(0) & 1];
            const uint32_t rank = cta & 1;
            uint32_t peer;
            asm volatile("mapa.shared::cluster.u32 %0, %1, %2;" : "=r"(peer) : "r"(sb), "r"(rank ^ 1));
            Ring r{0, 0, dl};
            uint32_t pm = 0;
            auto load_w = [&](const CUtensorMap* m, int row, int blk, uint32_t half_bytes) {
                mbar_wait(sb + BAR_REMPTY + r.slot * 8, r.ph, dl);
                if (lead) {
                    mbar_expect(sb + BAR_RFULL + r.slot * 8, 2 * half_bytes);
                    asm volatile("mbarrier.arrive.shared::cluster.b64 _, [%0];" ::"r"(peer + BAR_PRDY + r.slot * 8) : "memory");
                }
                mbar_wait(sb + BAR_PRDY + r.slot * 8, (pm >> r.slot) & 1, dl);
                pm ^= 1u << r.slot;
                if (lead) tma3_mc(sb + OFF_RING + r.slot * SLOT + rank * half_bytes, m, row, blk, sb + BAR_RFULL + r.slot * 8, pol_norm);
                r.adv(1);
            };
#pragma unroll 1
            for (int it = 0; e != 0; it++) {
                uint32_t nx = 0, tk = 0;
                if (rank == 0 && IT_TYPE(e) != IT_ON && it + 2 < MAXI) nx = it + 1 < NSTAT ? P.cl[cta >> 1].items[it + 1] : IT_DYN;
                const uint32_t br = IT_BR(e);
                if (IT_TYPE(e) == IT_QA) {
                    const uint32_t h = IT_H0(e);
#pragma unroll 1
                    for (int kk = it ? 0 : NSLOT; kk < 10; kk++) load_w(&P.wq[br], kk * 64 + rank * 32, h * 3, SLOT / 2);
                    const int row0 = (IT_B(e) * 32 + h) * 512;
#pragma unroll 1
                    for (int n = 0; n < 16; n++) {
                        if (n == 13 && nx == IT_DYN && lead) tk = atomicAdd(ticket, 1);
                        const bool isv = n == 15 || (n > 0 && !(n & 1));
                        const int j = n == 15 ? 7 : isv ? (n - 2) >> 1 : (n + 1) >> 1;
                        mbar_wait(sb + BAR_REMPTY + r.slot * 8, r.ph, dl);
                        if (lead) {
                            mbar_expect(sb + BAR_RFULL + r.slot * 8, SLOT);
                            tma3(sb + OFF_RING + r.slot * SLOT, isv ? &P.v[br] : &P.k[br], row0 + j * 64, 0,
                                 sb + BAR_RFULL + r.slot * 8, pol_first);
                        }
                        r.adv(1);
                    }
                } else {
                    const bool wide = IT_TYPE(e) == IT_OP;
                    const int step = wide ? 32 : 64, r1 = IT_H1(e) * 192;
#pragma unroll 1
                    for (int row = IT_H0(e) * 192 + rank * (step >> 1); row < r1; row += step)
                        load_w(wide ? &P.wo[br] : &P.won[br], row, IT_HALF(e) * (wide ? 5 : 2), wide ? XS / 2 : 8192);
                    if (nx == IT_DYN && lead) tk = atomicAdd(ticket, 1);
                }
                if (rank == 0) {
                    if (nx == IT_DYN) {
                        tk = __shfl_sync(0xffffffffu, tk, 0);
                        nx = tk < P.nlist ? P.list[tk] : 0;
                    }
                    e = nx;
                    if (lead) {
                        asm volatile("st.async.weak.shared::cluster.mbarrier::complete_tx::bytes.b32 [%0], %1, [%2];" ::"r"(
                                         peer + OFF_ITEM + 4 + it * 4),
                                     "r"(e ? e + 8 : 0), "r"(peer + BAR_ITEM + 8 + it * 8)
                                     : "memory");
                        sts_u(sb + OFF_ITEM + 4 + it * 4, e);
                        asm volatile("mbarrier.arrive.shared::cta.b64 _, [%0];" ::"r"(sb + BAR_ITEM + 8 + it * 8) : "memory");
                    }
                } else {
                    if (lead) mbar_expect(sb + BAR_ITEM + 8 + it * 8, 4);
                    e = get_item_warp(sb, it + 1, dl);
                }
            }
        } else if (warp == 1) {
            const uint64_t pol_norm = mkpol<POL_X>(), pol_o = mkpol<POL_O>();
            const bool lead = threadIdx.x == 32;
            uint32_t phm = 0, epoch = 0;
#pragma unroll 1
            for (int it = 0;; it++) {
                const uint32_t e = get_item_warp(sb, it, dl);
                if (it == 1 || (it == 0 && e == 0)) epoch = next_epoch(1);
                if (e == 0) break;
                const uint32_t br = IT_BR(e);
                uint32_t xs = 0;
                auto acquire = [&]() {
                    mbar_wait(sb + BAR_XEMPTY + xs * 8, (phm >> xs) & 1, dl);
                    phm ^= 1u << xs;
                    if (lead) mbar_expect(sb + BAR_XFULL + xs * 8, XS);
                };
                if (IT_TYPE(e) == IT_QA) {
#pragma unroll 1
                    for (int kk = it ? 0 : 5; kk < 10; kk++) {
                        acquire();
                        if (lead) tma3(sb + OFF_R + xs * XS, &P.x[br], IT_B(e) * 160, kk, sb + BAR_XFULL + xs * 8, pol_norm);
                        if (++xs == 5) xs = 0;
                    }
                } else {
                    const unsigned int* fp = g_flag + (br * 16 + IT_B(e)) * 64 + (threadIdx.x & 31);
                    uint32_t hm = 0, pm = 0;
                    auto poll = [&](uint32_t hneed, uint32_t pneed) {
                        if ((hm & hneed) == hneed && (pm & pneed) == pneed) return;
                        uint32_t n = 0;
                        do {
                            uint32_t a, b;
                            asm volatile("ld.acquire.gpu.global.u32 %0, [%2];\nld.acquire.gpu.global.u32 %1, [%2+128];"
                                         : "=r"(a), "=r"(b) : "l"(fp) : "memory");
                            hm = __ballot_sync(0xffffffffu, a == epoch);
                            pm = __ballot_sync(0xffffffffu, b == epoch);
                            if (++n > 0x1000000) __trap();
                        } while ((hm & hneed) != hneed || (pm & pneed) != pneed);
                        __syncwarp();
                        asm volatile("fence.proxy.async;" ::: "memory");
                    };
#pragma unroll 1
                    for (uint32_t h = IT_H0(e); h < IT_H1(e); h++) {
                        poll(1u << h, 0);
                        const unsigned char* src = ostash(P.slot[br * 32 + h], IT_B(e));
#pragma unroll 1
                        for (int t = 0; t < 3; t++) {
                            acquire();
                            if (lead) bulk_load(sb + OFF_R + xs * XS, src + t * XS, XS, sb + BAR_XFULL + xs * 8, pol_o);
                            if (++xs == 5) xs = 0;
                        }
                        if (IT_TYPE(e) == IT_OP && h >= 1) {
                            const uint32_t x1 = xs == 4 ? 0 : xs + 1;
                            mbar_wait(sb + BAR_XFULL + xs * 8, (phm >> xs) & 1, dl);
                            mbar_wait(sb + BAR_XFULL + x1 * 8, (phm >> x1) & 1, dl);
                            if (lead)
                                asm volatile("st.relaxed.gpu.global.u32 [%0], %1;" ::"l"(fp + 34 + IT_HALF(e)), "r"(epoch * 64 + h) : "memory");
                        }
                    }
                    if (IT_TYPE(e) == IT_ON) {
                        poll(0, IT_HALF(e) < 2 ? 1 : IT_HALF(e) == 2 ? 3 : 2);
#pragma unroll 1
                        for (uint32_t tile = 2 * IT_HALF(e); tile < 2 * IT_HALF(e) + 2; tile++) {
                            acquire();
                            if (lead)
                                asm volatile(
                                    "cp.async.bulk.tensor.5d.shared::cluster.global.mbarrier::complete_tx::bytes [%0], [%1, {%3,%5,%5,%5,%4}], [%2];" ::"r"(
                                        sb + OFF_R + xs * XS),
                                    "l"(&P.out), "r"(sb + BAR_XFULL + xs * 8), "r"(br * 640 + tile * 64), "r"(IT_B(e) * 5), "r"(0)
                                    : "memory");
                            if (++xs == 5) xs = 0;
                        }
                    }
                }
            }
        } else if (warp == 2) {
            asm volatile("barrier.cluster.wait.aligned;" ::: "memory");
            const uint32_t epoch = next_epoch(2);
            if (cta == 0) g_ticket[(epoch + 1) & 1] = 0;
#pragma unroll 1
            for (int it = 0;; it++) {
                const uint32_t e = get_item_warp(sb, it, dl);
                if (e == 0) break;
                nb_sync<NB_ODONE, 288>();
                if (threadIdx.x == 64) {
                    const uint32_t bb = IT_BR(e) * 16 + IT_B(e);
                    if (IT_TYPE(e) != IT_QA) {
                        const bool wide = IT_TYPE(e) == IT_OP;
                        if (wide)
                            asm volatile("st.relaxed.gpu.global.u32 [%0], %1;" ::"l"(&g_flag[bb * 64 + 34 + IT_HALF(e)]),
                                         "r"(epoch * 64 + IT_H1(e))
                                         : "memory");
                        const int cc0 = IT_BR(e) * 640 + IT_HALF(e) * (wide ? 320 : 128);
                        uint32_t xs = wide ? 0 : (3 * (IT_H1(e) - IT_H0(e))) % 5;
#pragma unroll 1
                        for (int m = 0; m < (wide ? 5 : 2); m++) {
                            asm volatile("cp.async.bulk.tensor.5d.global.shared::cta.bulk_group [%0, {%2,%4,%4,%4,%3}], [%1];" ::"l"(&P.out),
                                         "r"(sb + OFF_R + xs * XS), "r"(cc0 + m * 64), "r"((int)IT_B(e) * 5), "r"(0)
                                         : "memory");
                            asm volatile("cp.async.bulk.commit_group;" ::: "memory");
                            if (++xs == 5) xs = 0;
                        }
                        if (wide) {
#define REL(N)                                                          \
    asm volatile("cp.async.bulk.wait_group.read %0;" ::"n"(4 - N) : "memory"); \
    asm volatile("mbarrier.arrive.shared::cta.b64 _, [%0], 8;" ::"r"(sb + BAR_XEMPTY + N * 8) : "memory");
                            REL(0) REL(1) REL(2) REL(3) REL(4)
#undef REL
                        }
                        if (IT_PART(e)) {
                            asm volatile("cp.async.bulk.wait_group 0;" ::: "memory");
                            asm volatile("fence.proxy.async;" ::: "memory");
                        }
                    }
                    if (IT_TYPE(e) == IT_QA || IT_PART(e)) {
                        unsigned int* f = &g_flag[bb * 64 + (IT_TYPE(e) == IT_QA ? IT_H0(e) : 32 + IT_HALF(e))];
                        asm volatile("st.release.gpu.global.u32 [%0], %1;" ::"l"(f), "r"(epoch) : "memory");
                    }
                }
                __syncwarp();
            }
            if (threadIdx.x == 64) asm volatile("cp.async.bulk.wait_group 0;" ::: "memory");
            __syncwarp();
            asm volatile("barrier.cluster.arrive.relaxed.aligned;\nbarrier.cluster.wait.aligned;" ::: "memory");
        } else {
            const uint32_t lane = threadIdx.x & 31, p = lane >> 2;
            const uint32_t epoch = next_epoch(3);
#pragma unroll 1
            for (int it = 0;; it++) {
                const uint32_t e = get_item_warp(sb, it, dl);
                if (e == 0) break;
                if (IT_TYPE(e) != IT_QA) continue;
                nb_sync<NB_QK, 160>();
                const uint32_t co = (((lane & 3) * 2) ^ p) << 4;
                const uint32_t ka = sb + OFF_RING + lds_u(sb + OFF_GM + 4) * SLOT + p * (9 * 128) + co;
                const uint32_t qa = sb + OFF_R + p * 128 + co;
                uint32_t acc = 0;
#pragma unroll 1
                for (int c = 0; c < 3; c++) {
                    if (c == 2) nb_sync<NB_L, 160>();
                    const uint4 k0 = lds_u4(ka + c * 8192), q0 = lds_u4(qa + c * XS);
                    acc = fma_bf2(k0.x, q0.x, fma_bf2(k0.y, q0.y, fma_bf2(k0.z, q0.z, fma_bf2(k0.w, q0.w, acc))));
                    const uint4 k1 = lds_u4((ka + c * 8192) ^ 16), q1 = lds_u4((qa + c * XS) ^ 16);
                    acc = fma_bf2(k1.x, q1.x, fma_bf2(k1.y, q1.y, fma_bf2(k1.z, q1.z, fma_bf2(k1.w, q1.w, acc))));
                }
                float d = __uint_as_float(acc << 16) + __uint_as_float(acc & 0xffff0000u);
                d += __shfl_xor_sync(0xffffffffu, d, 1);
                d += __shfl_xor_sync(0xffffffffu, d, 2);
                int key = __float_as_int(d);
                key ^= (key >> 31) & 0x7fffffff;
                key = __reduce_max_sync(0xffffffffu, key);
                key ^= (key >> 31) & 0x7fffffff;
                sts_f(sb + OFF_GM, fmaf(__int_as_float(key), SM_C, 16.f));
                nb_arrive<NB_REF, 160>();
                if (IT_DEP(e)) {
                    const uint32_t g = IT_DEP(e) - 1, need = epoch * 64 + (g & 31) + 1;
                    const unsigned int* cp = &g_flag[((g >> 5) * 16 + IT_B(e)) * 64 + 34 + (lane & 1)];
                    for (uint32_t n = 0;; n++) {
                        uint32_t v;
                        asm volatile("ld.acquire.gpu.global.u32 %0, [%1];" : "=r"(v) : "l"(cp) : "memory");
                        if (__all_sync(0xffffffffu, v - need < 64)) break;
                        if (n > 0x800000) __trap();
                        __nanosleep(500);
                    }
                }
                nb_sync<NB_L, 160>();
                bool bad = false;
#pragma unroll
                for (int c = 0; c < 5; c++) {
                    const uint32_t la = sb + OFF_LX + (c * 32 + lane) * 4;
                    const float v = (__uint_as_float(lds_u(la)) + __uint_as_float(lds_u(la + 640))) +
                                    (__uint_as_float(lds_u(la + 1280)) + __uint_as_float(lds_u(la + 1920)));
                    const float inv = __fdividef(1.f, v);
                    const uint32_t hi = pack_bf16(inv, 0.f), lo = pack_bf16(inv - __uint_as_float(hi << 16), 0.f);
                    const uint32_t ia = sb + OFF_LINV + c * 128 + ((lane >> 1) & 3) * 32 + (lane >> 3) * 8 + (lane & 1) * 2;
                    asm volatile("st.shared.u16 [%0], %1;\nst.shared.u16 [%0+4], %2;" ::"r"(ia), "h"((unsigned short)hi), "h"((unsigned short)lo) : "memory");
                    bad |= !(v >= 5.421010862e-20f && v <= 7.9228163e28f);
                }
                sts_u(sb + OFF_FB, __any_sync(0xffffffffu, bad));
                nb_arrive<NB_VOTE, 160>();
                nb_arrive<NB_VOTE + 1, 160>();
            }
        }
    } else {
        asm volatile("setmaxnreg.inc.sync.aligned.u32 240;");
        consumer(P, wgid - 1, sb, dl);
    }
}

typedef CUresult (*EncFn)(CUtensorMap*, CUtensorMapDataType, cuuint32_t, void*, const cuuint64_t*, const cuuint64_t*,
                          const cuuint32_t*, const cuuint32_t*, CUtensorMapInterleave, CUtensorMapSwizzle,
                          CUtensorMapL2promotion, CUtensorMapFloatOOBfill);

void make_map3(EncFn enc, CUtensorMap* m, void* p, uint64_t rows, uint64_t rowbytes, uint64_t nblk, uint32_t boxrows,
               uint32_t boxblk) {
    cuuint64_t dims[3] = {64, rows, nblk};
    cuuint64_t str[2] = {rowbytes, 128};
    cuuint32_t box[3] = {64, boxrows, boxblk};
    cuuint32_t es[3] = {1, 1, 1};
    enc(m, CU_TENSOR_MAP_DATA_TYPE_BFLOAT16, 3, p, dims, str, box, es, CU_TENSOR_MAP_INTERLEAVE_NONE,
        CU_TENSOR_MAP_SWIZZLE_128B, CU_TENSOR_MAP_L2_PROMOTION_NONE, CU_TENSOR_MAP_FLOAT_OOB_FILL_NONE);
}

constexpr int tune(const char*, int def) { return def; }

void build_schedule(Params& P) {
    const int mode = tune("MODE", 4), dmax = tune("DMAX", 24900), n0 = tune("N0", 11), odmax = tune("ODMAX", 0);
    const int H0[8] = {19, 20, 21, 23, 23, 24, 25, 25}, P0[8] = {367, 340, 338, 331, 341, 339, 331, 334};
    const int ra = tune("RA", 10), ga = tune("GA", 17), rb = tune("RB", 11), g1 = tune("G1", 58);
    int dep[64];
    for (int g = 0, ns = 0, live = 0; g < 64; g++) {
        const bool fresh = mode < 3 || g >= g1 || live < (g < ga ? ra : rb);
        dep[g] = fresh ? 0 : g - live + 1;
        P.slot[g] = fresh ? ns++ : P.slot[g - live];
        live += fresh;
    }
    int H[8], pos[8], psum = 0;
    for (int b = 0; b < 8; b++) {
        const char nh[3] = {'H', (char)('0' + b), 0}, np[3] = {'P', (char)('0' + b), 0};
        H[b] = tune(nh, H0[b]);
        pos[b] = tune(np, P0[b]);
        psum += pos[b];
    }
    const int sk = tune("SK", 10), g0 = tune("G0", 20), g2 = tune("G2", 40);
    int ord[512], nxt[8] = {0, 0, 0, 0, 0, 0, 0, 0};
    for (int k = 0; k < 512; k++) {
        int best = -1;
        float bkey = 0.f;
        for (int b = 0; b < 8; b++) {
            const int g = nxt[b];
            if (g == 64) continue;
            const float w = g < g0 ? 0.f : g < 32 ? (g - g0) / (32.f - g0) : g < g2 ? 1.f : (64 - g) / (64.f - g2);
            const float key = g + w * sk * 0.1f * (pos[b] - psum / 8.f) / 8.f;
            if (best < 0 || key < bkey) best = b, bkey = key;
        }
        ord[k] = nxt[best]++ * 8 + best;
        const int d = dep[ord[k] >> 3];
        if (d > 32) {
            if (pos[best] > k) pos[best] = k;
            if (H[best] < d - 32) H[best] = d - 32;
        }
    }
    int u = 0;
    auto unit = [&]() {
        const int v = ord[u++];
        return mk_item(IT_QA, v >> 8, (v & 7) * 2, (v >> 3) & 31, P.slot[v >> 3], 0) | (dep[v >> 3] << 23);
    };
    int qa[NCL], nq = 0, op[NCL], no = 0;
    for (int c = 0; c < NCL; c++) {
        P.cl[c].delay = 0;
        for (int i = 0; i < NSTAT; i++) P.cl[c].items[i] = 0;
        if (mode >= 3 && c < 64 && (c & 3) == 3) op[no++] = c;
        else if (mode != 2 || (c & 3) == 0) qa[nq++] = c;
    }
    for (int t = 0; t < no; t++) {
        P.cl[op[t]].items[1] = mk_item(IT_OP, 0, t & ~1, 0, 32, t & 1);
        P.cl[op[t]].items[2] = IT_DYN;
        P.cl[op[t]].delay = t * odmax / 16;
    }
    for (int k = 0; k < nq; k++) {
        const int c = qa[(k * 19) % nq];
        P.cl[c].items[1] = P.cl[c].items[2] = IT_DYN;
        P.cl[c].delay = k < n0 ? 0 : (int)((long long)dmax * (k + 1 - n0) / (nq - n0));
    }
    if (tune("OFIRST", 0))
        for (int t = 0; t < no; t++) P.cl[op[t]].items[0] = unit();
    for (int k = u; k < no + nq; k++) {
        int best = -1;
        for (int c = 0; c < NCL; c++)
            if (P.cl[c].items[1] && !P.cl[c].items[0] && (best < 0 || P.cl[c].delay < P.cl[best].delay)) best = c;
        P.cl[best].items[0] = unit();
    }
    int n = 0;
    const int uend = mode == 2 ? 8 * nq : 512;
    while (u < uend) {
        for (int b = 0; b < 8 && no; b++)
            if (pos[b] == u) {
                P.list[n++] = mk_item(IT_OP, 1, 2 * b, 0, H[b], 0, 1);
                P.list[n++] = mk_item(IT_OP, 1, 2 * b, 0, H[b], 1, 1);
            }
        P.list[n++] = unit();
    }
    for (int k = 0; no && k < 40; k++) P.list[n++] = mk_item(IT_ON, 1, k / 5 * 2, H[k / 5], 32, k % 5);
    P.nlist = n;
}

}

extern "C" void kernel_launch(void* const* d_in, const int* in_sizes, int n_in, void* d_out, int out_size) {
    static Params P;
    static bool init = false;
    if (!init) {
        EncFn enc = nullptr;
        cudaDriverEntryPointQueryResult qr;
        cudaGetDriverEntryPoint("cuTensorMapEncodeTiled", (void**)&enc, cudaEnableDefault, &qr);
        for (int i = 0; i < 2; i++) {
            P.px[i] = (const __nv_bfloat16*)d_in[5 * i + 0];
            P.pk[i] = (const __nv_bfloat16*)d_in[5 * i + 1];
            P.pv[i] = (const __nv_bfloat16*)d_in[5 * i + 2];
            P.pwq[i] = (const __nv_bfloat16*)d_in[5 * i + 3];
            make_map3(enc, &P.x[i], d_in[5 * i + 0], 2560, 1280, 10, 160, 1);
            make_map3(enc, &P.k[i], d_in[5 * i + 1], 16 * 32 * 512, 384, 3, 64, 3);
            make_map3(enc, &P.v[i], d_in[5 * i + 2], 16 * 32 * 512, 384, 3, 64, 3);
            make_map3(enc, &P.wq[i], d_in[5 * i + 3], 640, 12288, 96, 32, 3);
            make_map3(enc, &P.wo[i], d_in[5 * i + 4], 6144, 1280, 10, 16, 5);
            make_map3(enc, &P.won[i], d_in[5 * i + 4], 6144, 1280, 10, 32, 2);
        }
        cuuint64_t dims[5] = {1280, 2, 4, 4, 80};
        cuuint64_t str[4] = {2560, 8 * 2560, 2 * 2560, 32 * 2560};
        cuuint32_t box[5] = {64, 2, 4, 4, 5};
        cuuint32_t es[5] = {1, 1, 1, 1, 1};
        enc(&P.out, CU_TENSOR_MAP_DATA_TYPE_BFLOAT16, 5, d_out, dims, str, box, es, CU_TENSOR_MAP_INTERLEAVE_NONE,
            CU_TENSOR_MAP_SWIZZLE_128B, CU_TENSOR_MAP_L2_PROMOTION_NONE, CU_TENSOR_MAP_FLOAT_OOB_FILL_NONE);
        build_schedule(P);
        cudaFuncSetAttribute(fused_kernel, cudaFuncAttributeMaxDynamicSharedMemorySize, SMEM_LAUNCH);
        init = true;
    }
    fused_kernel<<<NCTA, 384, SMEM_LAUNCH>>>(P);
}
```

```cpp
#include <cuda_runtime.h>
#include <cuda.h>
#include <cuda_bf16.h>
#include <stdint.h>

namespace {

constexpr int NCTA = 132;
constexpr int NCL = NCTA / 2;
constexpr int MAXI = 16;
constexpr int NSTAT = 3;
constexpr uint32_t IT_DYN = 0xffffffffu;
constexpr int SLOT = 24576;
constexpr int NSLOT = 5;
constexpr int XS = 20480;
constexpr int OFF_R = 0;
constexpr int OFF_RING = 5 * XS;
constexpr int OFF_MISC = OFF_RING + NSLOT * SLOT;
constexpr int OFF_LX = OFF_MISC;
constexpr int OFF_LINV = OFF_LX + 2560;
constexpr int OFF_FB = OFF_LINV + 640;
constexpr int OFF_GM = OFF_FB + 16;
constexpr int OFF_BAR = OFF_GM + 16;
constexpr int BAR_RFULL = OFF_BAR;
constexpr int BAR_REMPTY = BAR_RFULL + 40;
constexpr int BAR_XFULL = BAR_REMPTY + 40;
constexpr int BAR_XEMPTY = BAR_XFULL + 40;
constexpr int BAR_PRDY = BAR_XEMPTY + 40;
constexpr int BAR_ITEM = BAR_PRDY + 40;
constexpr int OFF_ITEM = BAR_ITEM + MAXI * 8;
constexpr int SMEM_BYTES = OFF_ITEM + MAXI * 4;
static_assert(SMEM_BYTES <= 232448, "smem");

constexpr int NB_W = 1  , NB_PFULL = 3  , NB_VOTE = 5  , NB_Q2 = 7, NB_SDONE = 8, NB_PDONE = 9,
              NB_L = 10, NB_REF = 11, NB_ODONE = 12, NB_OPEND = 13, NB_LX = 14, NB_Q01 = 15, NB_QK = 0  ;

constexpr uint32_t IT_QA = 1, IT_OP = 2, IT_ON = 3;
__host__ __device__ constexpr uint32_t mk_item(uint32_t type, uint32_t br, uint32_t b, uint32_t h0, uint32_t h1, uint32_t half,
                                               uint32_t part = 0) {
    return type | (br << 2) | (b << 3) | (h0 << 7) | (h1 << 13) | (half << 19) | (part << 22);
}
#define IT_TYPE(e) ((e) & 3u)
#define IT_BR(e) (((e) >> 2) & 1u)
#define IT_B(e) (((e) >> 3) & 15u)
#define IT_H0(e) (((e) >> 7) & 63u)
#define IT_H1(e) (((e) >> 13) & 63u)
#define IT_HALF(e) (((e) >> 19) & 7u)
#define IT_PART(e) (((e) >> 22) & 1u)
#define IT_SLOT(e) IT_H1(e)
#define IT_DEP(e) (((e) >> 23) & 127u)

struct Params {
    CUtensorMap x[2], wq[2], k[2], v[2], wo[2], won[2], out;
    const __nv_bfloat16 *px[2], *pwq[2], *pk[2], *pv[2];
    struct alignas(16) { uint32_t delay, items[NSTAT]; } cl[NCL];
    uint32_t nlist;
    uint8_t slot[64];
    uint32_t list[512];
};

constexpr int OUNIT = 61440;
__device__ __align__(1024) unsigned char g_ostash[(size_t)1024 * OUNIT];
__device__ unsigned int g_flag[32 * 64];
__device__ __forceinline__ unsigned char* ostash(uint32_t slot, uint32_t b) { return g_ostash + (slot * 16 + b) * OUNIT; }
__device__ unsigned int g_epoch[NCTA * 4];
__device__ unsigned int g_ticket[2];

constexpr int SMEM_LAUNCH = SMEM_BYTES;
#define TS(role, idx)
#define TS_ITEM(e)
#define TS_DUMP(role)
#define TSD(role, idx)

#define POL_W 2
#define POL_X 2
#define POL_O 2
template <int M>
__device__ __forceinline__ uint64_t mkpol() {
    uint64_t p;
    if (M == 0) asm volatile("createpolicy.fractional.L2::evict_normal.b64 %0, 1.0;" : "=l"(p));
    if (M == 1) asm volatile("createpolicy.fractional.L2::evict_first.b64 %0, 1.0;" : "=l"(p));
    if (M == 2) asm volatile("createpolicy.fractional.L2::evict_unchanged.b64 %0, 1.0;" : "=l"(p));
    if (M == 3) asm volatile("createpolicy.fractional.L2::evict_normal.L2::evict_unchanged.b64 %0, 0.25;" : "=l"(p));
    return p;
}
#define STSM_W 1
#define LASTORD 0
#define XLATE 2
#define PV0FIRST 1
#define QST0 1
#define QST1 2
#define QHOLD 8
constexpr float SM_C = 0.07216878364870322f * 1.4426950408889634f;

__device__ __forceinline__ uint32_t next_epoch(int warp) {
    unsigned int* p = &g_epoch[blockIdx.x * 4 + warp];
    const uint32_t e = __ldcg(p) + 1;
    *p = e;
    return e;
}

__device__ __forceinline__ uint32_t tid_now() {
    uint32_t t;
    asm volatile("mov.u32 %0, %%tid.x;" : "=r"(t));
    return t;
}
__device__ __forceinline__ void mbar_init(uint32_t a, uint32_t c) {
    asm volatile("mbarrier.init.shared::cta.b64 [%0], %1;" ::"r"(a), "r"(c) : "memory");
}
__device__ __forceinline__ void mbar_expect(uint32_t a, uint32_t b) {
    asm volatile("mbarrier.arrive.expect_tx.shared::cta.b64 _, [%0], %1;" ::"r"(a), "r"(b) : "memory");
}
template <int CNT = 1>
__device__ __forceinline__ void mbar_arrive_warp(uint32_t a) {
    if (CNT == 1)
        asm volatile("{\n.reg .pred p;\nelect.sync _|p, 0xffffffff;\n@p mbarrier.arrive.shared::cta.b64 _, [%0];\n}" ::"r"(a) : "memory");
    else
        asm volatile(
            "{\n.reg .pred p;\nelect.sync _|p, 0xffffffff;\n@p mbarrier.arrive.shared::cta.b64 _, [%0];\n"
            "@p mbarrier.arrive.shared::cta.b64 _, [%0];\n}" ::"r"(a)
            : "memory");
}
template <int CNT = 1>
__device__ __forceinline__ void mbar_arrive_warp_if(uint32_t a, bool cond) {
    if (CNT == 1)
        asm volatile(
            "{\n.reg .pred p, c;\nelect.sync _|p, 0xffffffff;\nsetp.ne.and.u32 c, %1, 0, p;\n"
            "@c mbarrier.arrive.shared::cta.b64 _, [%0];\n}" ::"r"(a), "r"((uint32_t)cond)
            : "memory");
    else
        asm volatile(
            "{\n.reg .pred p, c;\nelect.sync _|p, 0xffffffff;\nsetp.ne.and.u32 c, %1, 0, p;\n"
            "@c mbarrier.arrive.shared::cta.b64 _, [%0];\n@c mbarrier.arrive.shared::cta.b64 _, [%0];\n}" ::"r"(a), "r"((uint32_t)cond)
            : "memory");
}
__device__ __forceinline__ uint32_t deadline() {
    uint32_t c;
    asm volatile("mov.u32 %0, %%clock_hi;" : "=r"(c));
    return c + 4;
}
__device__ __forceinline__ void mbar_wait(uint32_t a, uint32_t ph, uint32_t dl) {
    asm volatile(
        "{\n.reg .pred p;\n.reg .u32 m;\n"
        "LOOP:\n"
        "mbarrier.try_wait.parity.shared::cta.b64 p, [%0], %1;\n"
        "@p bra DONE;\n"
        "mov.u32 m, %%clock_hi;\n"
        "setp.ne.u32 p, m, %2;\n"
        "@p bra LOOP;\n"
        "trap;\n"
        "DONE:\n}" ::"r"(a), "r"(ph), "r"(dl)
        : "memory");
}
template <int ID, int CNT>
__device__ __forceinline__ void nb_sync() { asm volatile("bar.sync %0, %1;" ::"n"(ID), "n"(CNT) : "memory"); }
template <int ID, int CNT>
__device__ __forceinline__ void nb_arrive() { asm volatile("bar.arrive %0, %1;" ::"n"(ID), "n"(CNT) : "memory"); }
__device__ __forceinline__ void fence_async_smem() { asm volatile("fence.proxy.async.shared::cta;" ::: "memory"); }

__device__ __forceinline__ void tma3(uint32_t dst, const CUtensorMap* m, int c1, int c2, uint32_t bar, uint64_t pol) {
    asm volatile(
        "cp.async.bulk.tensor.3d.shared::cluster.global.mbarrier::complete_tx::bytes.L2::cache_hint [%0], [%1, {%3,%4,%5}], [%2], %6;" ::"r"(dst),
        "l"(m), "r"(bar), "r"(0), "r"(c1), "r"(c2), "l"(pol)
        : "memory");
}
__device__ __forceinline__ void tma3_mc(uint32_t dst, const CUtensorMap* m, int c1, int c2, uint32_t bar, uint64_t pol) {
    asm volatile(
        "cp.async.bulk.tensor.3d.shared::cluster.global.mbarrier::complete_tx::bytes.multicast::cluster.L2::cache_hint"
        " [%0], [%1, {%3,%4,%5}], [%2], %6, %7;" ::"r"(dst),
        "l"(m), "r"(bar), "r"(0), "r"(c1), "r"(c2), "h"((unsigned short)3), "l"(pol)
        : "memory");
}
__device__ __forceinline__ void bulk_load(uint32_t dst, const void* src, uint32_t bytes, uint32_t bar, uint64_t pol) {
    asm volatile("cp.async.bulk.shared::cluster.global.mbarrier::complete_tx::bytes.L2::cache_hint [%0], [%1], %2, [%3], %4;" ::"r"(dst),
                 "l"(src), "r"(bytes), "r"(bar), "l"(pol)
                 : "memory");
}
__device__ __forceinline__ void wg_fence() { asm volatile("wgmma.fence.sync.aligned;" ::: "memory"); }
__device__ __forceinline__ void wg_commit() { asm volatile("wgmma.commit_group.sync.aligned;" ::: "memory"); }
template <int N>
__device__ __forceinline__ void wg_wait() { asm volatile("wgmma.wait_group.sync.aligned %0;" ::"n"(N) : "memory"); }

#define RW80(c, d) c(d[0]), c(d[1]), c(d[2]), c(d[3]), c(d[4]), c(d[5]), c(d[6]), c(d[7]), c(d[8]), c(d[9]), c(d[10]), c(d[11]), c(d[12]), c(d[13]), c(d[14]), c(d[15]), c(d[16]), c(d[17]), c(d[18]), c(d[19]), c(d[20]), c(d[21]), c(d[22]), c(d[23]), c(d[24]), c(d[25]), c(d[26]), c(d[27]), c(d[28]), c(d[29]), c(d[30]), c(d[31]), c(d[32]), c(d[33]), c(d[34]), c(d[35]), c(d[36]), c(d[37]), c(d[38]), c(d[39]), c(d[40]), c(d[41]), c(d[42]), c(d[43]), c(d[44]), c(d[45]), c(d[46]), c(d[47]), c(d[48]), c(d[49]), c(d[50]), c(d[51]), c(d[52]), c(d[53]), c(d[54]), c(d[55]), c(d[56]), c(d[57]), c(d[58]), c(d[59]), c(d[60]), c(d[61]), c(d[62]), c(d[63]), c(d[64]), c(d[65]), c(d[66]), c(d[67]), c(d[68]), c(d[69]), c(d[70]), c(d[71]), c(d[72]), c(d[73]), c(d[74]), c(d[75]), c(d[76]), c(d[77]), c(d[78]), c(d[79])
#define RW48(c, d) c(d[0]), c(d[1]), c(d[2]), c(d[3]), c(d[4]), c(d[5]), c(d[6]), c(d[7]), c(d[8]), c(d[9]), c(d[10]), c(d[11]), c(d[12]), c(d[13]), c(d[14]), c(d[15]), c(d[16]), c(d[17]), c(d[18]), c(d[19]), c(d[20]), c(d[21]), c(d[22]), c(d[23]), c(d[24]), c(d[25]), c(d[26]), c(d[27]), c(d[28]), c(d[29]), c(d[30]), c(d[31]), c(d[32]), c(d[33]), c(d[34]), c(d[35]), c(d[36]), c(d[37]), c(d[38]), c(d[39]), c(d[40]), c(d[41]), c(d[42]), c(d[43]), c(d[44]), c(d[45]), c(d[46]), c(d[47])
#define RW32(c, d) c(d[0]), c(d[1]), c(d[2]), c(d[3]), c(d[4]), c(d[5]), c(d[6]), c(d[7]), c(d[8]), c(d[9]), c(d[10]), c(d[11]), c(d[12]), c(d[13]), c(d[14]), c(d[15]), c(d[16]), c(d[17]), c(d[18]), c(d[19]), c(d[20]), c(d[21]), c(d[22]), c(d[23]), c(d[24]), c(d[25]), c(d[26]), c(d[27]), c(d[28]), c(d[29]), c(d[30]), c(d[31])

__device__ __forceinline__ void reg_fence(float (&d)[80]) { asm volatile("" : RW80("+f", d)::"memory"); }
__device__ __forceinline__ void reg_fence(float (&d)[48]) { asm volatile("" : RW48("+f", d)::"memory"); }
__device__ __forceinline__ void reg_fence(float (&d)[32]) { asm volatile("" : RW32("+f", d)::"memory"); }

template <int NR>
__device__ __forceinline__ void zero(float (&d)[NR]) {
#pragma unroll
    for (int i = 0; i < NR; i++) d[i] = 0.f;
}

constexpr uint32_t HI_SW128 = (1024u >> 4) | (1u << 30);
constexpr uint32_t HI_OST = (2560u >> 4) | (2u << 30);
constexpr uint32_t LO_LBO1 = (1u << 16);
constexpr uint32_t LO_OST = ((512u >> 4) << 16);

template <int TA, int TB, uint32_t HIB, int ACC>
__device__ __forceinline__ void wgmma(float (&d)[80], uint32_t loA, uint32_t loB) {
#define WG_ASM(SD)                                                          \
    "{\n.reg .b64 da, db;\nmov.b64 da, {%80, %82};\nmov.b64 db, {%81, %83};\n" \
    "wgmma.mma_async.sync.aligned.m64n160k16.f32.bf16.bf16 "               \
    "{%0,%1,%2,%3,%4,%5,%6,%7,%8,%9,%10,%11,%12,%13,%14,%15,%16,%17,%18,%19,%20,%21,%22,%23,%24,%25,%26,%27,%28,%29,%30,%31,%32,%33,%34,%35,%36,%37,%38,%39,%40,%41,%42,%43,%44,%45,%46,%47,%48,%49,%50,%51,%52,%53,%54,%55,%56,%57,%58,%59,%60,%61,%62,%63,%64,%65,%66,%67,%68,%69,%70,%71,%72,%73,%74,%75,%76,%77,%78,%79}, da, db, " SD ", 1, 1, %84, %85;\n}"
    if constexpr (ACC == 2)
        asm volatile(WG_ASM("0") : RW80("+f", d) : "r"(loA), "r"(loB), "n"(HI_SW128), "n"(HIB), "n"(TA), "n"(TB));
    else if constexpr (ACC == 1)
        asm volatile(WG_ASM("1") : RW80("+f", d) : "r"(loA), "r"(loB), "n"(HI_SW128), "n"(HIB), "n"(TA), "n"(TB));
    else
        asm volatile(WG_ASM("0") : RW80("=f", d) : "r"(loA), "r"(loB), "n"(HI_SW128), "n"(HIB), "n"(TA), "n"(TB));
#undef WG_ASM
}
template <int TA, int TB, uint32_t HIB, int ACC>
__device__ __forceinline__ void wgmma(float (&d)[48], uint32_t loA, uint32_t loB) {
#define WG_ASM(SD)                                                          \
    "{\n.reg .b64 da, db;\nmov.b64 da, {%48, %50};\nmov.b64 db, {%49, %51};\n" \
    "wgmma.mma_async.sync.aligned.m64n96k16.f32.bf16.bf16 "               \
    "{%0,%1,%2,%3,%4,%5,%6,%7,%8,%9,%10,%11,%12,%13,%14,%15,%16,%17,%18,%19,%20,%21,%22,%23,%24,%25,%26,%27,%28,%29,%30,%31,%32,%33,%34,%35,%36,%37,%38,%39,%40,%41,%42,%43,%44,%45,%46,%47}, da, db, " SD ", 1, 1, %52, %53;\n}"
    if constexpr (ACC == 1)
        asm volatile(WG_ASM("1") : RW48("+f", d) : "r"(loA), "r"(loB), "n"(HI_SW128), "n"(HIB), "n"(TA), "n"(TB));
    else
        asm volatile(WG_ASM("0") : RW48("=f", d) : "r"(loA), "r"(loB), "n"(HI_SW128), "n"(HIB), "n"(TA), "n"(TB));
#undef WG_ASM
}
template <int TA, int TB, uint32_t HIB, int ACC>
__device__ __forceinline__ void wgmma(float (&d)[32], uint32_t loA, uint32_t loB) {
#define WG_ASM(SD)                                                          \
    "{\n.reg .b64 da, db;\nmov.b64 da, {%32, %34};\nmov.b64 db, {%33, %35};\n" \
    "wgmma.mma_async.sync.aligned.m64n64k16.f32.bf16.bf16 "               \
    "{%0,%1,%2,%3,%4,%5,%6,%7,%8,%9,%10,%11,%12,%13,%14,%15,%16,%17,%18,%19,%20,%21,%22,%23,%24,%25,%26,%27,%28,%29,%30,%31}, da, db, " SD ", 1, 1, %36, %37;\n}"
    if constexpr (ACC == 1)
        asm volatile(WG_ASM("1") : RW32("+f", d) : "r"(loA), "r"(loB), "n"(HI_SW128), "n"(HIB), "n"(TA), "n"(TB));
    else
        asm volatile(WG_ASM("0") : RW32("=f", d) : "r"(loA), "r"(loB), "n"(HI_SW128), "n"(HIB), "n"(TA), "n"(TB));
#undef WG_ASM
}

__device__ __forceinline__ uint32_t pack_bf16(float lo, float hi) {
    uint32_t r;
    asm("cvt.rn.bf16x2.f32 %0, %1, %2;" : "=r"(r) : "f"(hi), "f"(lo));
    return r;
}
__device__ __forceinline__ float ex2(float x) {
    float r;
    asm("ex2.approx.ftz.f32 %0, %1;" : "=f"(r) : "f"(x));
    return r;
}
__device__ __forceinline__ void stsm4t(uint32_t a, uint32_t r0, uint32_t r1, uint32_t r2, uint32_t r3) {
    asm volatile("stmatrix.sync.aligned.m8n8.x4.trans.shared.b16 [%0], {%1,%2,%3,%4};" ::"r"(a), "r"(r0), "r"(r1), "r"(r2), "r"(r3)
                 : "memory");
}
__device__ __forceinline__ uint32_t lds_u(uint32_t a) {
    uint32_t v;
    asm volatile("ld.shared.u32 %0, [%1];" : "=r"(v) : "r"(a) : "memory");
    return v;
}
__device__ __forceinline__ uint4 lds_u4(uint32_t a) {
    uint4 v;
    asm volatile("ld.shared.v4.u32 {%0,%1,%2,%3}, [%4];" : "=r"(v.x), "=r"(v.y), "=r"(v.z), "=r"(v.w) : "r"(a) : "memory");
    return v;
}
__device__ __forceinline__ float2 lds_f2(uint32_t a) {
    float2 v;
    asm volatile("ld.shared.v2.f32 {%0,%1}, [%2];" : "=f"(v.x), "=f"(v.y) : "r"(a) : "memory");
    return v;
}
__device__ __forceinline__ void sts_f(uint32_t a, float v) { asm volatile("st.shared.f32 [%0], %1;" ::"r"(a), "f"(v) : "memory"); }
__device__ __forceinline__ void sts_u(uint32_t a, uint32_t v) { asm volatile("st.shared.u32 [%0], %1;" ::"r"(a), "r"(v) : "memory"); }
__device__ __forceinline__ void sts_f2(uint32_t a, float x, float y) {
    asm volatile("st.shared.v2.f32 [%0], {%1,%2};" ::"r"(a), "f"(x), "f"(y) : "memory");
}

template <bool ADD = false, bool SIG = false, int NR>
__device__ __forceinline__ void store_tile_t(const float (&d)[NR], uint32_t addr) {
    uint32_t p[NR / 2];
    if (ADD) {
#pragma unroll
        for (int j = 0; j < NR / 8; j++)
            asm volatile("ldmatrix.sync.aligned.m8n8.x4.trans.shared.b16 {%0,%1,%2,%3}, [%4];"
                         : "=r"(p[4 * j]), "=r"(p[4 * j + 1]), "=r"(p[4 * j + 2]), "=r"(p[4 * j + 3])
                         : "r"(addr + j * 2048)
                         : "memory");
    }
#pragma unroll
    for (int k = 0; k < NR / 2; k++)
        p[k] = ADD ? pack_bf16(d[2 * k] + __uint_as_float(p[k] << 16), d[2 * k + 1] + __uint_as_float(p[k] & 0xffff0000u))
                   : pack_bf16(d[2 * k], d[2 * k + 1]);
#pragma unroll
    for (int j = 0; j < NR / 8; j++) {
        stsm4t(addr + j * 2048, p[4 * j], p[4 * j + 1], p[4 * j + 2], p[4 * j + 3]);
        if (SIG && j == 0) nb_arrive<NB_L, 160>();
    }
}

struct TrueT { static constexpr bool value = true; };
struct FalseT { static constexpr bool value = false; };

template <int V>
struct IntT { static constexpr int value = V; };

__device__ __forceinline__ uint32_t get_item(uint32_t sb, int it, uint32_t dl) {
    mbar_wait(sb + BAR_ITEM + it * 8, 0, dl);
    return lds_u(sb + OFF_ITEM + it * 4);
}
__device__ __forceinline__ uint32_t get_item_warp(uint32_t sb, int it, uint32_t dl) {
    return __shfl_sync(0xffffffffu, get_item(sb, it, dl), 0);
}

struct Ring {
    uint32_t slot, ph, dl;
    __device__ __forceinline__ void adv(uint32_t k) {
        slot += k;
        if (slot >= NSLOT) { slot -= NSLOT; ph ^= 1; }
    }
};

template <int K>
__device__ __forceinline__ void qk_step(float (&s)[80], uint32_t loK, uint32_t loQ) {
    wgmma<0, 0, HI_SW128, K != 0>(s, loK + (K >> 2) * (8192 >> 4) + (K & 3) * 2, loQ + (K >> 2) * (XS >> 4) + (K & 3) * 2);
}
template <int K0, int K1>
__device__ __forceinline__ void qk_steps(float (&s)[80], uint32_t loK, uint32_t loQ) {
    if constexpr (K0 < K1) {
        qk_step<K0>(s, loK, loQ);
        qk_steps<K0 + 1, K1>(s, loK, loQ);
    }
}
__device__ __forceinline__ uint32_t add_bf2(uint32_t a, uint32_t b) {
    uint32_t r;
    asm("add.rn.bf16x2 %0, %1, %2;" : "=r"(r) : "r"(a), "r"(b));
    return r;
}
__device__ __forceinline__ uint32_t fma_bf2(uint32_t a, uint32_t b, uint32_t c) {
    uint32_t r;
    asm("fma.rn.bf16x2 %0, %1, %2, %3;" : "=r"(r) : "r"(a), "r"(b), "r"(c));
    return r;
}
template <int J>
__device__ __forceinline__ void exp_block(const float (&s)[80], uint32_t (&k)[40], uint32_t pa, float mref) {
    if constexpr (J < 10) {
#pragma unroll
        for (int i = 4 * J; i < 4 * J + 4; i++)
            k[i] = pack_bf16(ex2(fmaf(s[2 * i], SM_C, -mref)), ex2(fmaf(s[2 * i + 1], SM_C, -mref)));
#pragma unroll
        for (int i = 0; i < 4; i++)
            asm volatile("stmatrix.sync.aligned.m8n8.x1.trans.shared.b16 [%0], {%1};" ::"r"(((i & 1) ? pa ^ 16 : pa) + J * 2048 + (i >> 1) * 1024),
                         "r"(k[4 * J + i])
                         : "memory");
        exp_block<J + 1>(s, k, pa, mref);
    }
}
__device__ __forceinline__ void sum_block(const uint32_t (&k)[40], float (&l)[10], uint32_t lane) {
    const bool b4 = lane & 16, b3 = lane & 8;
    uint32_t ps[20], t[10];
#pragma unroll
    for (int j = 0; j < 20; j++) ps[j] = add_bf2(k[2 * j], k[2 * j + 1]);
#pragma unroll
    for (int j = 0; j < 10; j++)
        t[j] = add_bf2(b4 ? ps[2 * j + 1] : ps[2 * j], __shfl_xor_sync(0xffffffffu, b4 ? ps[2 * j] : ps[2 * j + 1], 16));
#pragma unroll
    for (int i = 0; i < 5; i++) {
        const uint32_t a = b3 ? t[i + 5] : t[i], b = __shfl_xor_sync(0xffffffffu, b3 ? t[i] : t[i + 5], 8);
        l[2 * i] += __uint_as_float(a << 16) + __uint_as_float(b << 16);
        l[2 * i + 1] += __uint_as_float(a & 0xffff0000u) + __uint_as_float(b & 0xffff0000u);
    }
}
template <bool ADD>
__device__ __forceinline__ void sum_store(const float (&l)[10], uint32_t lane, uint32_t lxa) {
    const bool b2 = lane & 4;
    float t[5];
#pragma unroll
    for (int i = 0; i < 5; i++) t[i] = ADD ? __uint_as_float(lds_u(lxa + i * 64)) : 0.f;
#pragma unroll
    for (int i = 0; i < 5; i++)
        sts_f(lxa + i * 64, t[i] + (b2 ? l[2 * i + 1] : l[2 * i]) + __shfl_xor_sync(0xffffffffu, b2 ? l[2 * i] : l[2 * i + 1], 4));
}

__device__ __forceinline__ void fallback_unit(const Params& P, uint32_t e, uint32_t tid) {
    const uint32_t lane = tid & 31, br = IT_BR(e), b = IT_B(e), h = IT_H0(e);
    const __nv_bfloat162* wq = (const __nv_bfloat162*)(P.pwq[br] + h * 192) + lane;
    const __nv_bfloat162* kp = (const __nv_bfloat162*)(P.pk[br] + (size_t)(b * 32 + h) * 512 * 192) + lane;
    const __nv_bfloat162* vp = (const __nv_bfloat162*)(P.pv[br] + (size_t)(b * 32 + h) * 512 * 192) + lane;
#pragma unroll 1
    for (uint32_t qi = 0; qi < 40; qi++) {
        const uint32_t q = 4 * qi + (tid >> 5);
        const __nv_bfloat16* xr = P.px[br] + (size_t)(b * 160 + q) * 640;
        float a[6] = {0.f, 0.f, 0.f, 0.f, 0.f, 0.f};
#pragma unroll 2
        for (int k = 0; k < 640; k++) {
            const float xv = __bfloat162float(xr[k]);
#pragma unroll
            for (int i = 0; i < 3; i++) {
                const float2 wv = __bfloat1622float2(wq[(size_t)k * 3072 + i * 32]);
                a[2 * i] = fmaf(xv, wv.x, a[2 * i]);
                a[2 * i + 1] = fmaf(xv, wv.y, a[2 * i + 1]);
            }
        }
#pragma unroll
        for (int i = 0; i < 6; i++) a[i] = __bfloat162float(__float2bfloat16(a[i]));
        auto score = [&](int key) {
            float d = 0.f;
#pragma unroll
            for (int i = 0; i < 3; i++) {
                const float2 kv = __bfloat1622float2(kp[key * 96 + i * 32]);
                d = fmaf(a[2 * i], kv.x, fmaf(a[2 * i + 1], kv.y, d));
            }
#pragma unroll
            for (int o = 16; o > 0; o >>= 1) d += __shfl_xor_sync(0xffffffffu, d, o);
            return d;
        };
        float m = -INFINITY, o[6] = {0.f, 0.f, 0.f, 0.f, 0.f, 0.f}, sum = 0.f;
#pragma unroll 1
        for (int n = 0; n < 1024; n++) {
            const int key = n & 511;
            const float d = score(key);
            if (n < 512) {
                m = fmaxf(m, d);
            } else {
                const float p = ex2((d - m) * SM_C);
                sum += p;
#pragma unroll
                for (int i = 0; i < 3; i++) {
                    const float2 vv = __bfloat1622float2(vp[key * 96 + i * 32]);
                    o[2 * i] = fmaf(p, vv.x, o[2 * i]);
                    o[2 * i + 1] = fmaf(p, vv.y, o[2 * i + 1]);
                }
            }
        }
        const float inv = __fdividef(1.f, sum);
        __nv_bfloat16* op = (__nv_bfloat16*)ostash(IT_SLOT(e), b) + (q >> 5) * 256 + 2 * ((q & 31) >> 3) + (q & 1);
#pragma unroll
        for (int i = 0; i < 6; i++) {
            const uint32_t d = (i >> 1) * 64 + 2 * lane + (i & 1);
            op[(d >> 3) * 1280 + (d & 7) * 32 + ((((q & 7) >> 1) ^ ((d & 7) >> 1)) << 3)] = __float2bfloat16(o[i] * inv);
        }
    }
}

template <int W>
struct PendO {
    static constexpr int N = W == 0 ? 56 : 64;
    uint32_t v[N];
    unsigned char* gp;
    static __device__ __forceinline__ uint32_t toff() {
        const uint32_t t = tid_now();
        return ((t >> 5) & 3) * 5120 + ((t >> 2) & 7) * 64 + (((t ^ (t >> 3)) & 3) << 4);
    }
    uint32_t pend, sig, bad;
    static __device__ __forceinline__ void scale(uint32_t& x, uint32_t hi, uint32_t lo) {
        asm("{\n.reg .b32 t;\nmul.rn.bf16x2 t, %0, %2;\nfma.rn.bf16x2 %0, %0, %1, t;\n}" : "+r"(x) : "r"(hi), "r"(lo));
    }
    template <int I, int OFF>
    __device__ __forceinline__ void put() {
        asm volatile("{\n.reg .pred p;\nsetp.ne.u32 p, %6, 0;\n@p st.global.v4.b32 [%0+%5], {%1,%2,%3,%4};\n}" ::"l"(gp), "r"(v[I]),
                     "r"(v[I + 1]), "r"(v[I + 2]), "r"(v[I + 3]), "n"(OFF), "r"(pend)
                     : "memory");
    }
    __device__ __forceinline__ void verdict(uint32_t sb) {
        if (sig) {
            nb_sync<NB_VOTE + W, 160>();
            bad = __any_sync(0xffffffffu, lds_u(sb + OFF_FB) != 0);
            pend = !bad;
        }
    }
    template <int G, int H>
    __device__ __forceinline__ void half(uint32_t sb) {
        constexpr bool T2 = W == 0 ? G >= 3 : G < 3;
        constexpr int B = T2 ? 40 + 8 * (W == 0 ? G - 3 : G) : 0;
        const uint4 a = lds_u4(sb + OFF_LINV + G * 128 + H * 16 + (threadIdx.x & 3) * 32);
#pragma unroll
        for (int i = 2 * H; i < 8; i += 4) {
            scale(v[8 * G + i], a.x, a.y);
            scale(v[8 * G + i + 1], a.z, a.w);
            if (T2) {
                scale(v[B + i], a.x, a.y);
                scale(v[B + i + 1], a.z, a.w);
            }
        }
        if (H == 1) {
            put<8 * G, W * XS + G * 512>();
            put<8 * G + 4, W * XS + G * 512 + 2560>();
            if (T2) {
                put<B, 2 * XS + G * 512>();
                put<B + 4, 2 * XS + G * 512 + 2560>();
            }
            if (G == 4 && pend) nb_arrive<NB_ODONE, 288>();
        }
    }
    template <int G>
    __device__ __forceinline__ void step(uint32_t sb) {
        half<G, 0>(sb);
        half<G, 1>(sb);
    }
    __device__ __forceinline__ void clear() {
#pragma unroll
        for (int i = 0; i < N; i++) v[i] = 0;
        gp = nullptr;
        pend = 0;
        sig = 0;
        bad = 0;
    }
};

__device__ __forceinline__ uint32_t stsm_off() {
    const uint32_t tid = tid_now(), lane = tid & 31;
    return (lane >> 4) * 1024 + (lane & 7) * 128 + (((((tid >> 4) & 6) + ((lane >> 3) & 1)) ^ (lane & 7)) << 4);
}
template <int W, int KK>
__device__ __forceinline__ void qproj(float (&q0)[80], float (&q1)[80], uint32_t sb, Ring& r, uint32_t pslot, uint32_t phm,
                                      PendO<W>& po) {
    const uint32_t loR = (((sb + OFF_R) & 0x3ffff) >> 4) | LO_LBO1;
    const uint32_t loRing = (((sb + OFF_RING) & 0x3ffff) >> 4) | LO_LBO1;
    auto ready = [&](int k) {
        mbar_wait(sb + BAR_RFULL + r.slot * 8, r.ph, r.dl);
        mbar_wait(sb + BAR_XFULL + (k % 5) * 8, ((phm >> (k % 5)) ^ (k / 5)) & 1, r.dl);
    };
    auto release = [&]() {
        if (KK > 0) {
            wg_wait<1>();
            mbar_arrive_warp(sb + BAR_REMPTY + pslot * 8);
            if (KK <= 5) mbar_arrive_warp(sb + (BAR_XEMPTY + (KK - 1) * 8));
        }
    };
    if (KK == 0 && (W == 1 || !po.sig)) ready(0);
    if (W == 1 && KK == QHOLD) {
        if (QHOLD == 7) {
            wg_wait<0>();
            nb_arrive<NB_PDONE, 256>();
        }
        nb_sync<NB_SDONE, 256>();
    }
    const uint32_t a = loRing + r.slot * (SLOT >> 4) + (W == 0 ? 0 : 512), b = loR + (KK % 5) * (XS >> 4);
    wg_fence();
    wgmma<1, 0, HI_SW128, KK != 0>(q0, a, b);
    if (W == 0) wgmma<1, 0, HI_SW128, KK != 0>(q1, a + 256, b);
#pragma unroll
    for (int k = 1; k < 4; k++) {
        wgmma<1, 0, HI_SW128, true>(q0, a + (k >> 1) * 768 + (k & 1) * 128, b + k * 2);
        if (W == 0) wgmma<1, 0, HI_SW128, true>(q1, a + 256 + (k >> 1) * 768 + (k & 1) * 128, b + k * 2);
    }
    wg_commit();
    const uint32_t cslot = r.slot;
    r.adv(1);
    if (W == 0 || KK < QHOLD) release();
    if (KK == QST0) {
        po.verdict(sb);
        po.template half<0, 0>(sb);
    }
    if (KK < 9) ready(KK + 1);
    if (W == 1 && KK >= QHOLD) release();
    if (W == 1 && KK == 7 && QHOLD > 7) nb_arrive<NB_PDONE, 256>();
    if (KK == QST0) po.template half<0, 1>(sb);
    if constexpr (KK > QST0 && KK < QST0 + 5) po.template step<KK - QST0>(sb);
    if constexpr (KK < (W == 0 ? 7 : 9)) {
        qproj<W, KK + 1>(q0, q1, sb, r, cslot, phm, po);
    } else if constexpr (W == 1) {
        wg_wait<0>();
        reg_fence(q0);
        mbar_arrive_warp(sb + BAR_REMPTY + cslot * 8);
        store_tile_t<false, true>(q0, sb + OFF_R + 2 * XS + stsm_off());
    } else {
        const uint32_t s8 = r.slot, a8 = loRing + s8 * (SLOT >> 4);
        wg_fence();
#pragma unroll
        for (int k = 0; k < 4; k++) wgmma<1, 0, HI_SW128, true>(q0, a8 + (k >> 1) * 768 + (k & 1) * 128, loR + 3 * (XS >> 4) + k * 2);
        r.adv(1);
        ready(9);
        const uint32_t s9 = r.slot, a9 = loRing + s9 * (SLOT >> 4);
        r.adv(1);
        wg_fence();
#pragma unroll
        for (int k = 0; k < 4; k++) wgmma<1, 0, HI_SW128, true>(q0, a9 + (k >> 1) * 768 + (k & 1) * 128, loR + 4 * (XS >> 4) + k * 2);
        wg_commit();
        wg_wait<1>();
        mbar_arrive_warp(sb + BAR_REMPTY + cslot * 8);
        wg_fence();
#pragma unroll
        for (int k = 0; k < 8; k++)
            wgmma<1, 0, HI_SW128, true>(q1, (k < 4 ? a8 : a9) + 256 + ((k >> 1) & 1) * 768 + (k & 1) * 128,
                                        loR + (3 + (k >> 2)) * (XS >> 4) + (k & 3) * 2);
        wg_commit();
        nb_arrive<NB_SDONE, 256>();
        nb_sync<NB_PDONE, 256>();
        wg_wait<1>();
        reg_fence(q0);
        const uint32_t sta = sb + OFF_R + stsm_off();
        store_tile_t(q0, sta);
        sts_u(sb + OFF_GM + 4, r.slot);
        mbar_wait(sb + BAR_RFULL + r.slot * 8, r.ph, r.dl);
        wg_wait<0>();
        reg_fence(q1);
        mbar_arrive_warp(sb + BAR_REMPTY + s8 * 8);
        mbar_arrive_warp(sb + BAR_REMPTY + s9 * 8);
        store_tile_t(q1, sta + XS);
    }
}

template <int NR>
__device__ __forceinline__ void opack(const float (&o)[NR], uint32_t* v) {
#pragma unroll
    for (int g = 0; g < NR / 16; g++)
#pragma unroll
        for (int hh = 0; hh < 2; hh++)
#pragma unroll
            for (int t = 0; t < 4; t++) v[8 * g + 4 * hh + t] = pack_bf16(o[16 * g + 4 * t + 2 * hh], o[16 * g + 4 * t + 2 * hh + 1]);
}

template <bool IS_S>
__device__ __forceinline__ void op_item(uint32_t e, uint32_t sb, Ring& r, uint32_t& phm) {
    constexpr int T0 = IS_S ? 0 : 2;
    constexpr uint32_t BOFF = IS_S ? (3 * 512) >> 4 : 0;
    const uint32_t loRing = (((sb + OFF_RING) & 0x3ffff) >> 4) | LO_LBO1;
    const uint32_t loO = (((sb + OFF_R) & 0x3ffff) >> 4) | LO_OST;
    float c0[80], c1[80], c2[IS_S ? 32 : 48];
    const int T = 3 * (IT_H1(e) - IT_H0(e));
    uint32_t xs = 0;
    auto step = [&](auto first, auto half) {
        constexpr bool F = decltype(first)::value;
        constexpr uint32_t hf = decltype(half)::value;
        if (hf == 0) {
            mbar_wait(sb + BAR_XFULL + xs * 8, (phm >> xs) & 1, r.dl);
            phm ^= 1u << xs;
        }
        mbar_wait(sb + BAR_RFULL + r.slot * 8, r.ph, r.dl);
        const uint32_t a = loRing + r.slot * (SLOT >> 4), b = loO + xs * (XS >> 4) + hf * 640;
        wg_fence();
        wgmma<1, 1, HI_OST, !F>(c0, a + T0 * 128, b);
        wgmma<1, 1, HI_OST, !F>(c1, a + T0 * 128 + 128, b);
        wgmma<1, 1, HI_OST, !F>(c2, a + 512, b + BOFF);
        wgmma<1, 1, HI_OST, true>(c0, a + 640 + T0 * 128, b + 320);
        wgmma<1, 1, HI_OST, true>(c1, a + 640 + T0 * 128 + 128, b + 320);
        wgmma<1, 1, HI_OST, true>(c2, a + 640 + 512, b + 320 + BOFF);
        wg_commit();
    };
    step(TrueT{}, IntT<0>{});
#pragma unroll 1
    for (int t = 1;; t++) {
        uint32_t pslot = r.slot;
        r.adv(1);
        step(FalseT{}, IntT<1>{});
        wg_wait<1>();
        mbar_arrive_warp(sb + BAR_REMPTY + pslot * 8);
        if (t == T) break;
        pslot = r.slot;
        const uint32_t pxs = xs;
        r.adv(1);
        if (++xs == 5) xs = 0;
        step(FalseT{}, IntT<0>{});
        wg_wait<1>();
        mbar_arrive_warp(sb + BAR_REMPTY + pslot * 8);
        mbar_arrive_warp_if(sb + BAR_XEMPTY + pxs * 8, t + 4 < T);
    }
    wg_wait<0>();
    reg_fence(c0);
    reg_fence(c1);
    reg_fence(c2);
    mbar_arrive_warp(sb + BAR_REMPTY + r.slot * 8);
    r.adv(1);
    nb_sync<NB_OPEND, 256>();
    const uint32_t sta = sb + OFF_R + stsm_off();
    store_tile_t(c0, sta + T0 * XS);
    store_tile_t(c1, sta + (T0 + 1) * XS);
    store_tile_t(c2, sta + 4 * XS + (IS_S ? 96 * 128 : 0));
    fence_async_smem();
    nb_arrive<NB_ODONE, 288>();
}

__device__ __forceinline__ void on_item(uint32_t W, uint32_t e, uint32_t sb, Ring& r, uint32_t& phm) {
    const uint32_t loRing = (((sb + OFF_RING) & 0x3ffff) >> 4) | LO_LBO1;
    const uint32_t loO = (((sb + OFF_R) & 0x3ffff) >> 4) | LO_OST;
    float c[80];
    const int T = 3 * (IT_H1(e) - IT_H0(e));
    uint32_t xs = 0;
    auto step = [&](auto first) {
        constexpr bool F = decltype(first)::value;
        mbar_wait(sb + BAR_XFULL + xs * 8, (phm >> xs) & 1, r.dl);
        phm ^= 1u << xs;
        mbar_wait(sb + BAR_RFULL + r.slot * 8, r.ph, r.dl);
        const uint32_t a = loRing + r.slot * (SLOT >> 4) + W * 256, b = loO + xs * (XS >> 4);
        wg_fence();
        wgmma<1, 1, HI_OST, !F>(c, a, b);
#pragma unroll
        for (int k = 1; k < 4; k++) wgmma<1, 1, HI_OST, true>(c, a + (k >> 1) * 512 + (k & 1) * 128, b + k * 320);
        wg_commit();
    };
    step(TrueT{});
#pragma unroll 1
    for (int t = 1; t < T; t++) {
        const uint32_t pslot = r.slot, pxs = xs;
        r.adv(1);
        if (++xs == 5) xs = 0;
        step(FalseT{});
        wg_wait<1>();
        mbar_arrive_warp(sb + BAR_REMPTY + pslot * 8);
        mbar_arrive_warp_if(sb + BAR_XEMPTY + pxs * 8, t + 2 < T);
    }
    xs += 1 + W;
    if (xs >= 5) xs -= 5;
    mbar_wait(sb + BAR_XFULL + xs * 8, (phm >> xs) & 1, r.dl);
    wg_wait<0>();
    reg_fence(c);
    store_tile_t<true>(c, sb + OFF_R + xs * XS + stsm_off());
    fence_async_smem();
    nb_arrive<NB_ODONE, 288>();
}

template <int W>
__device__ __forceinline__ uint32_t qa_item(uint32_t e, uint32_t sb, Ring& r, uint32_t phm, PendO<W>& po, int it) {
    const uint32_t loR = (((sb + OFF_R) & 0x3ffff) >> 4) | LO_LBO1;
    const uint32_t loRing = (((sb + OFF_RING) & 0x3ffff) >> 4) | LO_LBO1;
    {
        float q0[80], q1[80];
        qproj<W, 0>(q0, q1, sb, r, 0, phm, po);
    }
    fence_async_smem();
    TSD(W, 1);
    float s[80], oa[80], ob[W == 0 ? 32 : 48], l[10];
    if (W == 1) {
        nb_arrive<NB_Q2, 256>();
        zero(oa);
        zero(ob);
        reg_fence(oa);
        reg_fence(ob);
    }
    const uint32_t lane = tid_now() & 31, sta = sb + OFF_R + stsm_off();
    auto pv = [&](auto first, uint32_t buf) {
        constexpr bool F = decltype(first)::value;
        mbar_wait(sb + BAR_RFULL + r.slot * 8, r.ph, r.dl);
        const uint32_t a = loRing + r.slot * (SLOT >> 4), b = loR + (3 + buf) * (XS >> 4);
        wg_fence();
        wgmma<1, 0, HI_SW128, !F>(oa, a + W * 512, b);
        wgmma<1, 0, HI_SW128, !F>(ob, a + 1024, b + (W == 0 ? (96 * 128) >> 4 : 0));
#pragma unroll
        for (int k = 1; k < 4; k++) {
            wgmma<1, 0, HI_SW128, true>(oa, a + W * 512 + k * 128, b + k * 2);
            wgmma<1, 0, HI_SW128, true>(ob, a + 1024 + k * 128, b + (W == 0 ? (96 * 128) >> 4 : 0) + k * 2);
        }
        wg_commit();
    };
    zero(l);
    float mref;
    uint32_t kslot, vslot;
    auto tail = [&](auto first, int i) {
        constexpr bool rel_other = !decltype(first)::value;
        uint32_t ps[40];
        exp_block<0>(s, ps, sta + (3 + W) * XS, mref);
        if (rel_other) {
            wg_wait<0>();
            mbar_arrive_warp(sb + BAR_REMPTY + vslot * 8);
            if (W == 1) mbar_arrive_warp_if(sb + BAR_XEMPTY + 24, i == 3);
        }
        fence_async_smem();
        nb_arrive<NB_PFULL + W, 256>();
        TSD(W, 6 + 5 * i);
        if (W == 1) {
            if (XLATE >= 2) mbar_arrive_warp_if<2>(sb + BAR_XEMPTY + 8, i == 3);
            if (XLATE >= 1) mbar_arrive_warp_if<2>(sb + BAR_XEMPTY + 16, i == 3);
        }
        if (rel_other || !PV0FIRST) {
            mbar_wait(sb + BAR_RFULL + r.slot * 8, r.ph, r.dl);
            sum_block(ps, l, lane);
        }
        TSD(W, 7 + 5 * i);
        if (LASTORD && W == 0 && i == 3) nb_sync<NB_PDONE, 256>();
        else nb_sync<NB_W + W, 128>();
        pv(first, W);
        if (!rel_other && PV0FIRST) sum_block(ps, l, lane);
        TSD(W, 8 + 5 * i);
    };
    if (W == 0) {
        nb_sync<NB_QK, 160>();
        TSD(W, 2);
        wg_fence();
        qk_steps<0, 8>(s, loRing + r.slot * (SLOT >> 4), loR);
        nb_sync<NB_Q2, 256>();
        qk_steps<8, 12>(s, loRing + r.slot * (SLOT >> 4), loR);
        wg_commit();
        nb_arrive<NB_Q01, 256>();
        TSD(W, 4);
        nb_sync<NB_REF, 160>();
        mref = __uint_as_float(lds_u(sb + OFF_GM));
        wg_wait<0>();
        reg_fence(s);
        mbar_arrive_warp<2>(sb + BAR_REMPTY + r.slot * 8);
        r.adv(2);
        TSD(W, 5);
        tail(TrueT{}, 0);
    } else {
        nb_sync<NB_Q01, 256>();
    }
#pragma unroll 1
    for (int i = (W == 0 ? 1 : 0); i < 4; i++) {
        const uint32_t pvslot = r.slot;
        r.adv(1);
        kslot = r.slot;
        mbar_wait(sb + BAR_RFULL + r.slot * 8, r.ph, r.dl);
        wg_fence();
        qk_steps<0, 12>(s, loRing + r.slot * (SLOT >> 4), loR);
        wg_commit();
        wg_wait<1>();
        mbar_arrive_warp_if(sb + BAR_REMPTY + pvslot * 8, W == 0 || i > 0);
        r.adv(1);
        vslot = r.slot;
        TSD(W, 4 + 5 * i);
        nb_sync<NB_PFULL + (W ^ 1), 256>();
        pv(FalseT{}, W ^ 1);
        if (LASTORD && W == 1 && i == 3) nb_arrive<NB_PDONE, 256>();
        if (W == 1) mref = __uint_as_float(lds_u(sb + OFF_GM));
        wg_wait<1>();
        reg_fence(s);
        mbar_arrive_warp<2>(sb + BAR_REMPTY + kslot * 8);
        if (W == 1) {
            mbar_arrive_warp_if<2>(sb + BAR_XEMPTY + 0, i == 3);
            if (XLATE < 2) mbar_arrive_warp_if<2>(sb + BAR_XEMPTY + 8, i == 3);
            if (XLATE < 1) mbar_arrive_warp_if<2>(sb + BAR_XEMPTY + 16, i == 3);
        }
        r.adv(W == 1 && i == 3 ? 1 : 2);
        TSD(W, 5 + 5 * i);
        tail(FalseT{}, i);
    }
    const uint32_t w = (tid_now() >> 5) & 3;
    const uint32_t lxa = sb + OFF_LX + w * 640 + (((lane & 8) ? 80 : 0) + ((lane >> 1) & 8) + 2 * (lane & 3) + ((lane >> 2) & 1)) * 4;
    const uint32_t nx = get_item_warp(sb, it + 1, r.dl);
    po.gp = ostash(IT_SLOT(e), IT_B(e)) + po.toff();
    po.sig = 1;
    if (W == 0) {
        sum_store<false>(l, lane, lxa);
        nb_arrive<NB_LX, 256>();
        wg_wait<0>();
        mbar_arrive_warp(sb + BAR_REMPTY + r.slot * 8);
        mbar_arrive_warp(sb + BAR_XEMPTY + 24);
        r.adv(1);
        nb_sync<NB_PFULL + 1, 256>();
        pv(FalseT{}, 1);
        if (IT_TYPE(nx) == IT_QA) {
            Ring rn = r;
            rn.adv(1);
            mbar_wait(sb + BAR_RFULL + rn.slot * 8, rn.ph, r.dl);
            mbar_wait(sb + BAR_XFULL, phm & 1, r.dl);
        }
    } else {
        nb_sync<NB_LX, 256>();
        sum_store<true>(l, lane, lxa);
        nb_arrive<NB_L, 160>();
    }
    TSD(W, 24);
    wg_wait<0>();
    reg_fence(oa);
    reg_fence(ob);
    mbar_arrive_warp(sb + BAR_REMPTY + r.slot * 8);
    mbar_arrive_warp(sb + BAR_XEMPTY + 32);
    r.adv(1);
    opack(ob, po.v + 40);
    opack(oa, po.v);
    return nx;
}

template <int W>
__device__ __forceinline__ uint32_t qa_run(const Params& P, uint32_t e, uint32_t sb, Ring& r, uint32_t phm, int& it) {
    PendO<W> po;
    po.clear();
#pragma unroll 1
    do {
        TS(W, 0);
        if (W == 0) TS_ITEM(e);
        e = qa_item<W>(e, sb, r, phm, po, it);
        TS(W, 31);
        it++;
    } while (IT_TYPE(e) == IT_QA && !po.bad);
#pragma unroll 1
    for (int m = po.bad ? 2 : 1; m > 0; m--) {
        if (m == 1) {
            po.verdict(sb);
            po.template step<0>(sb);
            po.template step<1>(sb);
            po.template step<2>(sb);
            po.template step<3>(sb);
            po.template step<4>(sb);
        }
        if (po.bad) {
            if (W == 0) fallback_unit(P, lds_u(sb + OFF_ITEM + (it - m) * 4), tid_now() & 127);
            __syncwarp();
            nb_sync<NB_ODONE, 288>();
        }
    }
    return e;
}

__device__ __forceinline__ void consumer(const Params& P, uint32_t W, uint32_t sb, uint32_t dl) {
    int it = 0;
    Ring r{0, 0, dl};
    uint32_t phm = 0;
    uint32_t e = get_item_warp(sb, 0, dl);
#pragma unroll 1
    while (true) {
        if (IT_TYPE(e) == IT_QA) e = W == 0 ? qa_run<0>(P, e, sb, r, phm, it) : qa_run<1>(P, e, sb, r, phm, it);
        if (e == 0) break;
        if (IT_TYPE(e) == IT_QA) continue;
        TS(W, 0);
        if (W == 0) TS_ITEM(e);
        if (IT_TYPE(e) == IT_ON) on_item(W, e, sb, r, phm);
        else if (W == 0) op_item<true>(e, sb, r, phm);
        else op_item<false>(e, sb, r, phm);
        TS(W, 31);
        e = get_item_warp(sb, ++it, dl);
    }
    TS_DUMP(W);
}

__global__ void __cluster_dims__(2, 1, 1) __launch_bounds__(384, 1) fused_kernel(const __grid_constant__ Params P) {
    extern __shared__ __align__(1024) unsigned char smem_raw[];
    const uint32_t sb = (uint32_t)__cvta_generic_to_shared(smem_raw);
    const uint32_t warp = __shfl_sync(0xffffffffu, threadIdx.x >> 5, 0), wgid = warp >> 2;
    const uint32_t cta = blockIdx.x;
    const uint32_t dl = deadline();

    if (threadIdx.x == 128) {
#pragma unroll
        for (int i = 0; i < NSLOT; i++) {
            mbar_init(sb + BAR_RFULL + i * 8, 1);
            mbar_init(sb + BAR_REMPTY + i * 8, 8);
            mbar_init(sb + BAR_XFULL + i * 8, 1);
            mbar_init(sb + BAR_XEMPTY + i * 8, 8);
        }
        asm volatile("fence.mbarrier_init.release.cluster;" ::: "memory");
        fence_async_smem();
    } else if (threadIdx.x == 160) {
#pragma unroll
        for (int i = 0; i < NSLOT + MAXI; i++) mbar_init(sb + BAR_PRDY + i * 8, 1);
        asm volatile("fence.mbarrier_init.release.cluster;" ::: "memory");
    } else if (threadIdx.x == 0) {
        sts_u(sb + OFF_ITEM, P.cl[cta >> 1].items[0] ? P.cl[cta >> 1].items[0] + 8 * (cta & 1) : 0);
        sts_u(sb + OFF_FB, P.cl[cta >> 1].delay);
    } else if (threadIdx.x == 64) {
        if (sb & 1023) __trap();
        asm volatile("prefetch.tensormap [%0];" ::"l"(&P.wq[0]) : "memory");
        asm volatile("prefetch.tensormap [%0];" ::"l"(&P.x[0]) : "memory");
    }
    __syncthreads();
    {
        const int it = 0;
        if (wgid == 1) TS(0, 30);
    }
    asm volatile("barrier.cluster.arrive.relaxed.aligned;" ::: "memory");
    if (warp < 3) {
        const uint32_t e = __shfl_sync(0xffffffffu, lds_u(sb + OFF_ITEM), 0), d = lds_u(sb + OFF_FB);
        const uint64_t pol = mkpol<POL_W>();
        const bool isx = warp == 1, lead = (threadIdx.x & 31) == 0;
        uint32_t t0, t1;
        asm volatile("mov.u32 %0, %%clock;" : "=r"(t0));
        do {
            asm volatile("mov.u32 %0, %%clock;" : "=r"(t1));
        } while (t1 - t0 < d);
        __syncwarp();
#pragma unroll 1
        for (int n = 0; n < (e ? NSLOT : 0); n++) {
            const uint32_t bar = sb + (isx ? BAR_XFULL : BAR_RFULL) + n * 8;
            if (lead) {
                if (warp < 2) mbar_expect(bar, isx ? XS : SLOT);
                tma3(sb + (isx ? OFF_R + n * XS : OFF_RING + n * SLOT + warp * (SLOT / 4)), isx ? &P.x[0] : &P.wq[0],
                     isx ? IT_B(e) * 160 : n * 64 + warp * 16, isx ? n : IT_H0(e) * 3, bar, pol);
            }
        }
        if (threadIdx.x == 0) asm volatile("mbarrier.arrive.shared::cta.b64 _, [%0];" ::"r"(sb + BAR_ITEM) : "memory");
        __syncwarp();
    }

    if (wgid == 0) {
        asm volatile("setmaxnreg.dec.sync.aligned.u32 24;");
        if (warp == 0) {
            const bool lead = threadIdx.x == 0;
            const uint64_t pol_first = mkpol<1>(), pol_norm = mkpol<POL_W>();
            uint32_t e = __shfl_sync(0xffffffffu, lds_u(sb + OFF_ITEM), 0);
            asm volatile("barrier.cluster.wait.aligned;" ::: "memory");
            unsigned int* const ticket = &g_ticket[next_epoch(0) & 1];
            const uint32_t rank = cta & 1;
            uint32_t peer;
            asm volatile("mapa.shared::cluster.u32 %0, %1, %2;" : "=r"(peer) : "r"(sb), "r"(rank ^ 1));
            Ring r{0, 0, dl};
            uint32_t pm = 0;
            auto load_w = [&](const CUtensorMap* m, int row, int blk, uint32_t half_bytes) {
                mbar_wait(sb + BAR_REMPTY + r.slot * 8, r.ph, dl);
                if (lead) {
                    mbar_expect(sb + BAR_RFULL + r.slot * 8, 2 * half_bytes);
                    asm volatile("mbarrier.arrive.shared::cluster.b64 _, [%0];" ::"r"(peer + BAR_PRDY + r.slot * 8) : "memory");
                }
                mbar_wait(sb + BAR_PRDY + r.slot * 8, (pm >> r.slot) & 1, dl);
                pm ^= 1u << r.slot;
                if (lead) tma3_mc(sb + OFF_RING + r.slot * SLOT + rank * half_bytes, m, row, blk, sb + BAR_RFULL + r.slot * 8, pol_norm);
                r.adv(1);
            };
#pragma unroll 1
            for (int it = 0; e != 0; it++) {
                uint32_t nx = 0, tk = 0;
                if (rank == 0 && IT_TYPE(e) != IT_ON && it + 2 < MAXI) nx = it + 1 < NSTAT ? P.cl[cta >> 1].items[it + 1] : IT_DYN;
                const uint32_t br = IT_BR(e);
                if (IT_TYPE(e) == IT_QA) {
                    const uint32_t h = IT_H0(e);
#pragma unroll 1
                    for (int kk = it ? 0 : NSLOT; kk < 10; kk++) load_w(&P.wq[br], kk * 64 + rank * 32, h * 3, SLOT / 2);
                    const int row0 = (IT_B(e) * 32 + h) * 512;
#pragma unroll 1
                    for (int n = 0; n < 16; n++) {
                        if (n == 13 && nx == IT_DYN && lead) tk = atomicAdd(ticket, 1);
                        const bool isv = n == 15 || (n > 0 && !(n & 1));
                        const int j = n == 15 ? 7 : isv ? (n - 2) >> 1 : (n + 1) >> 1;
                        mbar_wait(sb + BAR_REMPTY + r.slot * 8, r.ph, dl);
                        if (lead) {
                            mbar_expect(sb + BAR_RFULL + r.slot * 8, SLOT);
                            tma3(sb + OFF_RING + r.slot * SLOT, isv ? &P.v[br] : &P.k[br], row0 + j * 64, 0,
                                 sb + BAR_RFULL + r.slot * 8, pol_first);
                        }
                        r.adv(1);
                    }
                } else {
                    const bool wide = IT_TYPE(e) == IT_OP;
                    const int step = wide ? 32 : 64, r1 = IT_H1(e) * 192;
#pragma unroll 1
                    for (int row = IT_H0(e) * 192 + rank * (step >> 1); row < r1; row += step)
                        load_w(wide ? &P.wo[br] : &P.won[br], row, IT_HALF(e) * (wide ? 5 : 2), wide ? XS / 2 : 8192);
                    if (nx == IT_DYN && lead) tk = atomicAdd(ticket, 1);
                }
                if (rank == 0) {
                    if (nx == IT_DYN) {
                        tk = __shfl_sync(0xffffffffu, tk, 0);
                        nx = tk < P.nlist ? P.list[tk] : 0;
                    }
                    e = nx;
                    if (lead) {
                        asm volatile("st.async.weak.shared::cluster.mbarrier::complete_tx::bytes.b32 [%0], %1, [%2];" ::"r"(
                                         peer + OFF_ITEM + 4 + it * 4),
                                     "r"(e ? e + 8 : 0), "r"(peer + BAR_ITEM + 8 + it * 8)
                                     : "memory");
                        sts_u(sb + OFF_ITEM + 4 + it * 4, e);
                        asm volatile("mbarrier.arrive.shared::cta.b64 _, [%0];" ::"r"(sb + BAR_ITEM + 8 + it * 8) : "memory");
                    }
                } else {
                    if (lead) mbar_expect(sb + BAR_ITEM + 8 + it * 8, 4);
                    e = get_item_warp(sb, it + 1, dl);
                }
            }
        } else if (warp == 1) {
            const uint64_t pol_norm = mkpol<POL_X>(), pol_o = mkpol<POL_O>();
            const bool lead = threadIdx.x == 32;
            uint32_t phm = 0, epoch = 0;
#pragma unroll 1
            for (int it = 0;; it++) {
                const uint32_t e = get_item_warp(sb, it, dl);
                if (it == 1 || (it == 0 && e == 0)) epoch = next_epoch(1);
                if (e == 0) break;
                const uint32_t br = IT_BR(e);
                uint32_t xs = 0;
                auto acquire = [&]() {
                    mbar_wait(sb + BAR_XEMPTY + xs * 8, (phm >> xs) & 1, dl);
                    phm ^= 1u << xs;
                    if (lead) mbar_expect(sb + BAR_XFULL + xs * 8, XS);
                };
                if (IT_TYPE(e) == IT_QA) {
#pragma unroll 1
                    for (int kk = it ? 0 : 5; kk < 10; kk++) {
                        acquire();
                        if (lead) tma3(sb + OFF_R + xs * XS, &P.x[br], IT_B(e) * 160, kk, sb + BAR_XFULL + xs * 8, pol_norm);
                        if (++xs == 5) xs = 0;
                    }
                } else {
                    const unsigned int* fp = g_flag + (br * 16 + IT_B(e)) * 64 + (threadIdx.x & 31);
                    uint32_t hm = 0, pm = 0;
                    auto poll = [&](uint32_t hneed, uint32_t pneed) {
                        if ((hm & hneed) == hneed && (pm & pneed) == pneed) return;
                        uint32_t n = 0;
                        do {
                            uint32_t a, b;
                            asm volatile("ld.acquire.gpu.global.u32 %0, [%2];\nld.acquire.gpu.global.u32 %1, [%2+128];"
                                         : "=r"(a), "=r"(b) : "l"(fp) : "memory");
                            hm = __ballot_sync(0xffffffffu, a == epoch);
                            pm = __ballot_sync(0xffffffffu, b == epoch);
                            if (++n > 0x1000000) __trap();
                        } while ((hm & hneed) != hneed || (pm & pneed) != pneed);
                        __syncwarp();
                        asm volatile("fence.proxy.async;" ::: "memory");
                    };
#pragma unroll 1
                    for (uint32_t h = IT_H0(e); h < IT_H1(e); h++) {
                        poll(1u << h, 0);
                        const unsigned char* src = ostash(P.slot[br * 32 + h], IT_B(e));
#pragma unroll 1
                        for (int t = 0; t < 3; t++) {
                            acquire();
                            if (lead) bulk_load(sb + OFF_R + xs * XS, src + t * XS, XS, sb + BAR_XFULL + xs * 8, pol_o);
                            if (++xs == 5) xs = 0;
                        }
                        if (IT_TYPE(e) == IT_OP && h >= 1) {
                            const uint32_t x1 = xs == 4 ? 0 : xs + 1;
                            mbar_wait(sb + BAR_XFULL + xs * 8, (phm >> xs) & 1, dl);
                            mbar_wait(sb + BAR_XFULL + x1 * 8, (phm >> x1) & 1, dl);
                            if (lead)
                                asm volatile("st.relaxed.gpu.global.u32 [%0], %1;" ::"l"(fp + 34 + IT_HALF(e)), "r"(epoch * 64 + h) : "memory");
                        }
                    }
                    if (IT_TYPE(e) == IT_ON) {
                        poll(0, IT_HALF(e) < 2 ? 1 : IT_HALF(e) == 2 ? 3 : 2);
#pragma unroll 1
                        for (uint32_t tile = 2 * IT_HALF(e); tile < 2 * IT_HALF(e) + 2; tile++) {
                            acquire();
                            if (lead)
                                asm volatile(
                                    "cp.async.bulk.tensor.5d.shared::cluster.global.mbarrier::complete_tx::bytes [%0], [%1, {%3,%5,%5,%5,%4}], [%2];" ::"r"(
                                        sb + OFF_R + xs * XS),
                                    "l"(&P.out), "r"(sb + BAR_XFULL + xs * 8), "r"(br * 640 + tile * 64), "r"(IT_B(e) * 5), "r"(0)
                                    : "memory");
                            if (++xs == 5) xs = 0;
                        }
                    }
                }
            }
        } else if (warp == 2) {
            asm volatile("barrier.cluster.wait.aligned;" ::: "memory");
            const uint32_t epoch = next_epoch(2);
            if (cta == 0) g_ticket[(epoch + 1) & 1] = 0;
#pragma unroll 1
            for (int it = 0;; it++) {
                const uint32_t e = get_item_warp(sb, it, dl);
                if (e == 0) break;
                nb_sync<NB_ODONE, 288>();
                if (threadIdx.x == 64) {
                    const uint32_t bb = IT_BR(e) * 16 + IT_B(e);
                    if (IT_TYPE(e) != IT_QA) {
                        const bool wide = IT_TYPE(e) == IT_OP;
                        if (wide)
                            asm volatile("st.relaxed.gpu.global.u32 [%0], %1;" ::"l"(&g_flag[bb * 64 + 34 + IT_HALF(e)]),
                                         "r"(epoch * 64 + IT_H1(e))
                                         : "memory");
                        const int cc0 = IT_BR(e) * 640 + IT_HALF(e) * (wide ? 320 : 128);
                        uint32_t xs = wide ? 0 : (3 * (IT_H1(e) - IT_H0(e))) % 5;
#pragma unroll 1
                        for (int m = 0; m < (wide ? 5 : 2); m++) {
                            asm volatile("cp.async.bulk.tensor.5d.global.shared::cta.bulk_group [%0, {%2,%4,%4,%4,%3}], [%1];" ::"l"(&P.out),
                                         "r"(sb + OFF_R + xs * XS), "r"(cc0 + m * 64), "r"((int)IT_B(e) * 5), "r"(0)
                                         : "memory");
                            asm volatile("cp.async.bulk.commit_group;" ::: "memory");
                            if (++xs == 5) xs = 0;
                        }
                        if (wide) {
#define REL(N)                                                          \
    asm volatile("cp.async.bulk.wait_group.read %0;" ::"n"(4 - N) : "memory"); \
    asm volatile("mbarrier.arrive.shared::cta.b64 _, [%0], 8;" ::"r"(sb + BAR_XEMPTY + N * 8) : "memory");
                            REL(0) REL(1) REL(2) REL(3) REL(4)
#undef REL
                        }
                        if (IT_PART(e)) {
                            asm volatile("cp.async.bulk.wait_group 0;" ::: "memory");
                            asm volatile("fence.proxy.async;" ::: "memory");
                        }
                    }
                    if (IT_TYPE(e) == IT_QA || IT_PART(e)) {
                        unsigned int* f = &g_flag[bb * 64 + (IT_TYPE(e) == IT_QA ? IT_H0(e) : 32 + IT_HALF(e))];
                        asm volatile("st.release.gpu.global.u32 [%0], %1;" ::"l"(f), "r"(epoch) : "memory");
                    }
                }
                __syncwarp();
            }
            if (threadIdx.x == 64) asm volatile("cp.async.bulk.wait_group 0;" ::: "memory");
            __syncwarp();
            asm volatile("barrier.cluster.arrive.relaxed.aligned;\nbarrier.cluster.wait.aligned;" ::: "memory");
        } else {
            const uint32_t lane = threadIdx.x & 31, p = lane >> 2;
            const uint32_t epoch = next_epoch(3);
#pragma unroll 1
            for (int it = 0;; it++) {
                const uint32_t e = get_item_warp(sb, it, dl);
                if (e == 0) break;
                if (IT_TYPE(e) != IT_QA) continue;
                nb_sync<NB_QK, 160>();
                const uint32_t co = (((lane & 3) * 2) ^ p) << 4;
                const uint32_t ka = sb + OFF_RING + lds_u(sb + OFF_GM + 4) * SLOT + p * (9 * 128) + co;
                const uint32_t qa = sb + OFF_R + p * 128 + co;
                uint32_t acc = 0;
#pragma unroll 1
                for (int c = 0; c < 3; c++) {
                    if (c == 2) nb_sync<NB_L, 160>();
                    const uint4 k0 = lds_u4(ka + c * 8192), q0 = lds_u4(qa + c * XS);
                    acc = fma_bf2(k0.x, q0.x, fma_bf2(k0.y, q0.y, fma_bf2(k0.z, q0.z, fma_bf2(k0.w, q0.w, acc))));
                    const uint4 k1 = lds_u4((ka + c * 8192) ^ 16), q1 = lds_u4((qa + c * XS) ^ 16);
                    acc = fma_bf2(k1.x, q1.x, fma_bf2(k1.y, q1.y, fma_bf2(k1.z, q1.z, fma_bf2(k1.w, q1.w, acc))));
                }
                float d = __uint_as_float(acc << 16) + __uint_as_float(acc & 0xffff0000u);
                d += __shfl_xor_sync(0xffffffffu, d, 1);
                d += __shfl_xor_sync(0xffffffffu, d, 2);
                int key = __float_as_int(d);
                key ^= (key >> 31) & 0x7fffffff;
                key = __reduce_max_sync(0xffffffffu, key);
                key ^= (key >> 31) & 0x7fffffff;
                sts_f(sb + OFF_GM, fmaf(__int_as_float(key), SM_C, 16.f));
                nb_arrive<NB_REF, 160>();
                if (IT_DEP(e)) {
                    const uint32_t g = IT_DEP(e) - 1, need = epoch * 64 + (g & 31) + 1;
                    const unsigned int* cp = &g_flag[((g >> 5) * 16 + IT_B(e)) * 64 + 34 + (lane & 1)];
                    for (uint32_t n = 0;; n++) {
                        uint32_t v;
                        asm volatile("ld.acquire.gpu.global.u32 %0, [%1];" : "=r"(v) : "l"(cp) : "memory");
                        if (__all_sync(0xffffffffu, v - need < 64)) break;
                        if (n > 0x800000) __trap();
                        __nanosleep(500);
                    }
                }
                nb_sync<NB_L, 160>();
                bool bad = false;
#pragma unroll
                for (int c = 0; c < 5; c++) {
                    const uint32_t la = sb + OFF_LX + (c * 32 + lane) * 4;
                    const float v = (__uint_as_float(lds_u(la)) + __uint_as_float(lds_u(la + 640))) +
                                    (__uint_as_float(lds_u(la + 1280)) + __uint_as_float(lds_u(la + 1920)));
                    const float inv = __fdividef(1.f, v);
                    const uint32_t hi = pack_bf16(inv, 0.f), lo = pack_bf16(inv - __uint_as_float(hi << 16), 0.f);
                    const uint32_t ia = sb + OFF_LINV + c * 128 + ((lane >> 1) & 3) * 32 + (lane >> 3) * 8 + (lane & 1) * 2;
                    asm volatile("st.shared.u16 [%0], %1;\nst.shared.u16 [%0+4], %2;" ::"r"(ia), "h"((unsigned short)hi), "h"((unsigned short)lo) : "memory");
                    bad |= !(v >= 5.421010862e-20f && v <= 7.9228163e28f);
                }
                sts_u(sb + OFF_FB, __any_sync(0xffffffffu, bad));
                nb_arrive<NB_VOTE, 160>();
                nb_arrive<NB_VOTE + 1, 160>();
            }
        }
    } else {
        asm volatile("setmaxnreg.inc.sync.aligned.u32 240;");
        consumer(P, wgid - 1, sb, dl);
    }
}

typedef CUresult (*EncFn)(CUtensorMap*, CUtensorMapDataType, cuuint32_t, void*, const cuuint64_t*, const cuuint64_t*,
                          const cuuint32_t*, const cuuint32_t*, CUtensorMapInterleave, CUtensorMapSwizzle,
                          CUtensorMapL2promotion, CUtensorMapFloatOOBfill);

void make_map3(EncFn enc, CUtensorMap* m, void* p, uint64_t rows, uint64_t rowbytes, uint64_t nblk, uint32_t boxrows,
               uint32_t boxblk) {
    cuuint64_t dims[3] = {64, rows, nblk};
    cuuint64_t str[2] = {rowbytes, 128};
    cuuint32_t box[3] = {64, boxrows, boxblk};
    cuuint32_t es[3] = {1, 1, 1};
    enc(m, CU_TENSOR_MAP_DATA_TYPE_BFLOAT16, 3, p, dims, str, box, es, CU_TENSOR_MAP_INTERLEAVE_NONE,
        CU_TENSOR_MAP_SWIZZLE_128B, CU_TENSOR_MAP_L2_PROMOTION_NONE, CU_TENSOR_MAP_FLOAT_OOB_FILL_NONE);
}

constexpr int tune(const char*, int def) { return def; }

void build_schedule(Params& P) {
    const int mode = tune("MODE", 4), dmax = tune("DMAX", 24900), n0 = tune("N0", 11), odmax = tune("ODMAX", 0), d1 = tune("D1", 0);
    const int H0[8] = {19, 20, 21, 23, 23, 24, 25, 25}, P0[8] = {367, 340, 338, 331, 341, 339, 331, 334};
    const int ra = tune("RA", 10), ga = tune("GA", 17), rb = tune("RB", 11), g1 = tune("G1", 58);
    int dep[64];
    for (int g = 0, ns = 0, live = 0; g < 64; g++) {
        const bool fresh = mode < 3 || g >= g1 || live < (g < ga ? ra : rb);
        dep[g] = fresh ? 0 : g - live + 1;
        P.slot[g] = fresh ? ns++ : P.slot[g - live];
        live += fresh;
    }
    int H[8], pos[8], psum = 0;
    for (int b = 0; b < 8; b++) {
        const char nh[3] = {'H', (char)('0' + b), 0}, np[3] = {'P', (char)('0' + b), 0};
        H[b] = tune(nh, H0[b]);
        pos[b] = tune(np, P0[b]);
        psum += pos[b];
    }
    const int sk = tune("SK", 10), g0 = tune("G0", 20), g2 = tune("G2", 40);
    int ord[512], nxt[8] = {0, 0, 0, 0, 0, 0, 0, 0};
    for (int k = 0; k < 512; k++) {
        int best = -1;
        float bkey = 0.f;
        for (int b = 0; b < 8; b++) {
            const int g = nxt[b];
            if (g == 64) continue;
            const float w = g < g0 ? 0.f : g < 32 ? (g - g0) / (32.f - g0) : g < g2 ? 1.f : (64 - g) / (64.f - g2);
            const float key = g + w * sk * 0.1f * (pos[b] - psum / 8.f) / 8.f;
            if (best < 0 || key < bkey) best = b, bkey = key;
        }
        ord[k] = nxt[best]++ * 8 + best;
        const int d = dep[ord[k] >> 3];
        if (d > 32) {
            if (pos[best] > k) pos[best] = k;
            if (H[best] < d - 32) H[best] = d - 32;
        }
    }
    int u = 0;
    auto unit = [&]() {
        const int v = ord[u++];
        return mk_item(IT_QA, v >> 8, (v & 7) * 2, (v >> 3) & 31, P.slot[v >> 3], 0) | (dep[v >> 3] << 23);
    };
    int qa[NCL], nq = 0, op[NCL], no = 0;
    for (int c = 0; c < NCL; c++) {
        P.cl[c].delay = 0;
        for (int i = 0; i < NSTAT; i++) P.cl[c].items[i] = 0;
        if (mode >= 3 && c < 64 && (c & 3) == 3) op[no++] = c;
        else if (mode != 2 || (c & 3) == 0) qa[nq++] = c;
    }
    for (int t = 0; t < no; t++) {
        P.cl[op[t]].items[1] = mk_item(IT_OP, 0, t & ~1, 0, 32, t & 1);
        P.cl[op[t]].items[2] = IT_DYN;
        P.cl[op[t]].delay = tune("OD0", 0) + t * odmax / 16;
    }
    for (int k = 0; k < nq; k++) {
        const int c = qa[(k * 19) % nq];
        P.cl[c].items[1] = P.cl[c].items[2] = IT_DYN;
        P.cl[c].delay = k < n0 ? k * tune("J0", 0) : d1 + (dmax - d1) * (k + 1 - n0) / (nq - n0);
    }
    if (tune("OFIRST", 0))
        for (int t = 0; t < no; t++) P.cl[op[t]].items[0] = unit();
    for (int k = u; k < no + nq; k++) {
        int best = -1;
        for (int c = 0; c < NCL; c++)
            if (P.cl[c].items[1] && !P.cl[c].items[0] && (best < 0 || P.cl[c].delay < P.cl[best].delay)) best = c;
        P.cl[best].items[0] = unit();
    }
    int n = 0;
    const int uend = mode == 2 ? 8 * nq : 512;
    while (u < uend) {
        for (int b = 0; b < 8 && no; b++)
            if (pos[b] == u) {
                P.list[n++] = mk_item(IT_OP, 1, 2 * b, 0, H[b], 0, 1);
                P.list[n++] = mk_item(IT_OP, 1, 2 * b, 0, H[b], 1, 1);
            }
        P.list[n++] = unit();
    }
    for (int k = 0; no && k < 40; k++) P.list[n++] = mk_item(IT_ON, 1, k / 5 * 2, H[k / 5], 32, k % 5);
    P.nlist = n;
}

}

extern "C" void kernel_launch(void* const* d_in, const int* in_sizes, int n_in, void* d_out, int out_size) {
    static Params P;
    static bool init = false;
    if (!init) {
        EncFn enc = nullptr;
        cudaDriverEntryPointQueryResult qr;
        cudaGetDriverEntryPoint("cuTensorMapEncodeTiled", (void**)&enc, cudaEnableDefault, &qr);
        for (int i = 0; i < 2; i++) {
            P.px[i] = (const __nv_bfloat16*)d_in[5 * i + 0];
            P.pk[i] = (const __nv_bfloat16*)d_in[5 * i + 1];
            P.pv[i] = (const __nv_bfloat16*)d_in[5 * i + 2];
            P.pwq[i] = (const __nv_bfloat16*)d_in[5 * i + 3];
            make_map3(enc, &P.x[i], d_in[5 * i + 0], 2560, 1280, 10, 160, 1);
            make_map3(enc, &P.k[i], d_in[5 * i + 1], 16 * 32 * 512, 384, 3, 64, 3);
            make_map3(enc, &P.v[i], d_in[5 * i + 2], 16 * 32 * 512, 384, 3, 64, 3);
            make_map3(enc, &P.wq[i], d_in[5 * i + 3], 640, 12288, 96, 32, 3);
            make_map3(enc, &P.wo[i], d_in[5 * i + 4], 6144, 1280, 10, 16, 5);
            make_map3(enc, &P.won[i], d_in[5 * i + 4], 6144, 1280, 10, 32, 2);
        }
        cuuint64_t dims[5] = {1280, 2, 4, 4, 80};
        cuuint64_t str[4] = {2560, 8 * 2560, 2 * 2560, 32 * 2560};
        cuuint32_t box[5] = {64, 2, 4, 4, 5};
        cuuint32_t es[5] = {1, 1, 1, 1, 1};
        enc(&P.out, CU_TENSOR_MAP_DATA_TYPE_BFLOAT16, 5, d_out, dims, str, box, es, CU_TENSOR_MAP_INTERLEAVE_NONE,
            CU_TENSOR_MAP_SWIZZLE_128B, CU_TENSOR_MAP_L2_PROMOTION_NONE, CU_TENSOR_MAP_FLOAT_OOB_FILL_NONE);
        build_schedule(P);
        cudaFuncSetAttribute(fused_kernel, cudaFuncAttributeMaxDynamicSharedMemorySize, SMEM_LAUNCH);
        init = true;
    }
    fused_kernel<<<NCTA, 384, SMEM_LAUNCH>>>(P);
}
```

```cpp
#include <cuda_runtime.h>
#include <cuda.h>
#include <cuda_bf16.h>
#include <stdint.h>

namespace {

constexpr int NCTA = 132;
constexpr int NCL = NCTA / 2;
constexpr int MAXI = 16;
constexpr int NSTAT = 3;
constexpr uint32_t IT_DYN = 0xffffffffu;
constexpr int SLOT = 24576;
constexpr int NSLOT = 5;
constexpr int XS = 20480;
constexpr int OFF_R = 0;
constexpr int OFF_RING = 5 * XS;
constexpr int OFF_MISC = OFF_RING + NSLOT * SLOT;
constexpr int OFF_LX = OFF_MISC;
constexpr int OFF_LINV = OFF_LX + 2560;
constexpr int OFF_FB = OFF_LINV + 640;
constexpr int OFF_GM = OFF_FB + 16;
constexpr int OFF_BAR = OFF_GM + 16;
constexpr int BAR_RFULL = OFF_BAR;
constexpr int BAR_REMPTY = BAR_RFULL + 40;
constexpr int BAR_XFULL = BAR_REMPTY + 40;
constexpr int BAR_XEMPTY = BAR_XFULL + 40;
constexpr int BAR_PRDY = BAR_XEMPTY + 40;
constexpr int BAR_ITEM = BAR_PRDY + 40;
constexpr int OFF_ITEM = BAR_ITEM + MAXI * 8;
constexpr int SMEM_BYTES = OFF_ITEM + MAXI * 4;
static_assert(SMEM_BYTES <= 232448, "smem");

constexpr int NB_W = 1  , NB_PFULL = 3  , NB_VOTE = 5  , NB_Q2 = 7, NB_SDONE = 8, NB_PDONE = 9,
              NB_L = 10, NB_REF = 11, NB_ODONE = 12, NB_OPEND = 13, NB_LX = 14, NB_Q01 = 15, NB_QK = 0  ;

constexpr uint32_t IT_QA = 1, IT_OP = 2, IT_ON = 3;
__host__ __device__ constexpr uint32_t mk_item(uint32_t type, uint32_t br, uint32_t b, uint32_t h0, uint32_t h1, uint32_t half,
                                               uint32_t part = 0) {
    return type | (br << 2) | (b << 3) | (h0 << 7) | (h1 << 13) | (half << 19) | (part << 22);
}
#define IT_TYPE(e) ((e) & 3u)
#define IT_BR(e) (((e) >> 2) & 1u)
#define IT_B(e) (((e) >> 3) & 15u)
#define IT_H0(e) (((e) >> 7) & 63u)
#define IT_H1(e) (((e) >> 13) & 63u)
#define IT_HALF(e) (((e) >> 19) & 7u)
#define IT_PART(e) (((e) >> 22) & 1u)
#define IT_SLOT(e) IT_H1(e)
#define IT_DEP(e) (((e) >> 23) & 127u)

struct Params {
    CUtensorMap x[2], wq[2], k[2], v[2], wo[2], won[2], out;
    const __nv_bfloat16 *px[2], *pwq[2], *pk[2], *pv[2];
    struct alignas(16) { uint32_t delay, items[NSTAT]; } cl[NCL];
    uint32_t nlist;
    uint8_t slot[64];
    uint32_t list[512];
};

constexpr int OUNIT = 61440;
__device__ __align__(1024) unsigned char g_ostash[(size_t)1024 * OUNIT];
__device__ unsigned int g_flag[32 * 64];
__device__ __forceinline__ unsigned char* ostash(uint32_t slot, uint32_t b) { return g_ostash + (slot * 16 + b) * OUNIT; }
__device__ unsigned int g_epoch[NCTA * 4];
__device__ unsigned int g_ticket[2];

constexpr int SMEM_LAUNCH = SMEM_BYTES;
#define TS(role, idx)
#define TS_ITEM(e)
#define TS_DUMP(role)
#define TSD(role, idx)

#define POL_W 2
#define POL_X 2
#define POL_O 2
template <int M>
__device__ __forceinline__ uint64_t mkpol() {
    uint64_t p;
    if (M == 0) asm volatile("createpolicy.fractional.L2::evict_normal.b64 %0, 1.0;" : "=l"(p));
    if (M == 1) asm volatile("createpolicy.fractional.L2::evict_first.b64 %0, 1.0;" : "=l"(p));
    if (M == 2) asm volatile("createpolicy.fractional.L2::evict_unchanged.b64 %0, 1.0;" : "=l"(p));
    if (M == 3) asm volatile("createpolicy.fractional.L2::evict_normal.L2::evict_unchanged.b64 %0, 0.25;" : "=l"(p));
    return p;
}
#define STSM_W 1
#define LASTORD 0
#define XLATE 2
#define PV0FIRST 1
#define QST0 1
#define QST1 2
#define QHOLD 8
constexpr float SM_C = 0.07216878364870322f * 1.4426950408889634f;

__device__ __forceinline__ uint32_t next_epoch(int warp) {
    unsigned int* p = &g_epoch[blockIdx.x * 4 + warp];
    const uint32_t e = __ldcg(p) + 1;
    *p = e;
    return e;
}

__device__ __forceinline__ uint32_t tid_now() {
    uint32_t t;
    asm volatile("mov.u32 %0, %%tid.x;" : "=r"(t));
    return t;
}
__device__ __forceinline__ void mbar_init(uint32_t a, uint32_t c) {
    asm volatile("mbarrier.init.shared::cta.b64 [%0], %1;" ::"r"(a), "r"(c) : "memory");
}
__device__ __forceinline__ void mbar_expect(uint32_t a, uint32_t b) {
    asm volatile("mbarrier.arrive.expect_tx.shared::cta.b64 _, [%0], %1;" ::"r"(a), "r"(b) : "memory");
}
template <int CNT = 1>
__device__ __forceinline__ void mbar_arrive_warp(uint32_t a) {
    if (CNT == 1)
        asm volatile("{\n.reg .pred p;\nelect.sync _|p, 0xffffffff;\n@p mbarrier.arrive.shared::cta.b64 _, [%0];\n}" ::"r"(a) : "memory");
    else
        asm volatile(
            "{\n.reg .pred p;\nelect.sync _|p, 0xffffffff;\n@p mbarrier.arrive.shared::cta.b64 _, [%0];\n"
            "@p mbarrier.arrive.shared::cta.b64 _, [%0];\n}" ::"r"(a)
            : "memory");
}
template <int CNT = 1>
__device__ __forceinline__ void mbar_arrive_warp_if(uint32_t a, bool cond) {
    if (CNT == 1)
        asm volatile(
            "{\n.reg .pred p, c;\nelect.sync _|p, 0xffffffff;\nsetp.ne.and.u32 c, %1, 0, p;\n"
            "@c mbarrier.arrive.shared::cta.b64 _, [%0];\n}" ::"r"(a), "r"((uint32_t)cond)
            : "memory");
    else
        asm volatile(
            "{\n.reg .pred p, c;\nelect.sync _|p, 0xffffffff;\nsetp.ne.and.u32 c, %1, 0, p;\n"
            "@c mbarrier.arrive.shared::cta.b64 _, [%0];\n@c mbarrier.arrive.shared::cta.b64 _, [%0];\n}" ::"r"(a), "r"((uint32_t)cond)
            : "memory");
}
__device__ __forceinline__ uint32_t deadline() {
    uint32_t c;
    asm volatile("mov.u32 %0, %%clock_hi;" : "=r"(c));
    return c + 4;
}
__device__ __forceinline__ void mbar_wait(uint32_t a, uint32_t ph, uint32_t dl) {
    asm volatile(
        "{\n.reg .pred p;\n.reg .u32 m;\n"
        "LOOP:\n"
        "mbarrier.try_wait.parity.shared::cta.b64 p, [%0], %1;\n"
        "@p bra DONE;\n"
        "mov.u32 m, %%clock_hi;\n"
        "setp.ne.u32 p, m, %2;\n"
        "@p bra LOOP;\n"
        "trap;\n"
        "DONE:\n}" ::"r"(a), "r"(ph), "r"(dl)
        : "memory");
}
template <int ID, int CNT>
__device__ __forceinline__ void nb_sync() { asm volatile("bar.sync %0, %1;" ::"n"(ID), "n"(CNT) : "memory"); }
template <int ID, int CNT>
__device__ __forceinline__ void nb_arrive() { asm volatile("bar.arrive %0, %1;" ::"n"(ID), "n"(CNT) : "memory"); }
__device__ __forceinline__ void fence_async_smem() { asm volatile("fence.proxy.async.shared::cta;" ::: "memory"); }

__device__ __forceinline__ void tma3(uint32_t dst, const CUtensorMap* m, int c1, int c2, uint32_t bar, uint64_t pol) {
    asm volatile(
        "cp.async.bulk.tensor.3d.shared::cluster.global.mbarrier::complete_tx::bytes.L2::cache_hint [%0], [%1, {%3,%4,%5}], [%2], %6;" ::"r"(dst),
        "l"(m), "r"(bar), "r"(0), "r"(c1), "r"(c2), "l"(pol)
        : "memory");
}
__device__ __forceinline__ void tma3_mc(uint32_t dst, const CUtensorMap* m, int c1, int c2, uint32_t bar, uint64_t pol) {
    asm volatile(
        "cp.async.bulk.tensor.3d.shared::cluster.global.mbarrier::complete_tx::bytes.multicast::cluster.L2::cache_hint"
        " [%0], [%1, {%3,%4,%5}], [%2], %6, %7;" ::"r"(dst),
        "l"(m), "r"(bar), "r"(0), "r"(c1), "r"(c2), "h"((unsigned short)3), "l"(pol)
        : "memory");
}
__device__ __forceinline__ void bulk_load(uint32_t dst, const void* src, uint32_t bytes, uint32_t bar, uint64_t pol) {
    asm volatile("cp.async.bulk.shared::cluster.global.mbarrier::complete_tx::bytes.L2::cache_hint [%0], [%1], %2, [%3], %4;" ::"r"(dst),
                 "l"(src), "r"(bytes), "r"(bar), "l"(pol)
                 : "memory");
}
__device__ __forceinline__ void wg_fence() { asm volatile("wgmma.fence.sync.aligned;" ::: "memory"); }
__device__ __forceinline__ void wg_commit() { asm volatile("wgmma.commit_group.sync.aligned;" ::: "memory"); }
template <int N>
__device__ __forceinline__ void wg_wait() { asm volatile("wgmma.wait_group.sync.aligned %0;" ::"n"(N) : "memory"); }

#define RW80(c, d) c(d[0]), c(d[1]), c(d[2]), c(d[3]), c(d[4]), c(d[5]), c(d[6]), c(d[7]), c(d[8]), c(d[9]), c(d[10]), c(d[11]), c(d[12]), c(d[13]), c(d[14]), c(d[15]), c(d[16]), c(d[17]), c(d[18]), c(d[19]), c(d[20]), c(d[21]), c(d[22]), c(d[23]), c(d[24]), c(d[25]), c(d[26]), c(d[27]), c(d[28]), c(d[29]), c(d[30]), c(d[31]), c(d[32]), c(d[33]), c(d[34]), c(d[35]), c(d[36]), c(d[37]), c(d[38]), c(d[39]), c(d[40]), c(d[41]), c(d[42]), c(d[43]), c(d[44]), c(d[45]), c(d[46]), c(d[47]), c(d[48]), c(d[49]), c(d[50]), c(d[51]), c(d[52]), c(d[53]), c(d[54]), c(d[55]), c(d[56]), c(d[57]), c(d[58]), c(d[59]), c(d[60]), c(d[61]), c(d[62]), c(d[63]), c(d[64]), c(d[65]), c(d[66]), c(d[67]), c(d[68]), c(d[69]), c(d[70]), c(d[71]), c(d[72]), c(d[73]), c(d[74]), c(d[75]), c(d[76]), c(d[77]), c(d[78]), c(d[79])
#define RW48(c, d) c(d[0]), c(d[1]), c(d[2]), c(d[3]), c(d[4]), c(d[5]), c(d[6]), c(d[7]), c(d[8]), c(d[9]), c(d[10]), c(d[11]), c(d[12]), c(d[13]), c(d[14]), c(d[15]), c(d[16]), c(d[17]), c(d[18]), c(d[19]), c(d[20]), c(d[21]), c(d[22]), c(d[23]), c(d[24]), c(d[25]), c(d[26]), c(d[27]), c(d[28]), c(d[29]), c(d[30]), c(d[31]), c(d[32]), c(d[33]), c(d[34]), c(d[35]), c(d[36]), c(d[37]), c(d[38]), c(d[39]), c(d[40]), c(d[41]), c(d[42]), c(d[43]), c(d[44]), c(d[45]), c(d[46]), c(d[47])
#define RW32(c, d) c(d[0]), c(d[1]), c(d[2]), c(d[3]), c(d[4]), c(d[5]), c(d[6]), c(d[7]), c(d[8]), c(d[9]), c(d[10]), c(d[11]), c(d[12]), c(d[13]), c(d[14]), c(d[15]), c(d[16]), c(d[17]), c(d[18]), c(d[19]), c(d[20]), c(d[21]), c(d[22]), c(d[23]), c(d[24]), c(d[25]), c(d[26]), c(d[27]), c(d[28]), c(d[29]), c(d[30]), c(d[31])

__device__ __forceinline__ void reg_fence(float (&d)[80]) { asm volatile("" : RW80("+f", d)::"memory"); }
__device__ __forceinline__ void reg_fence(float (&d)[48]) { asm volatile("" : RW48("+f", d)::"memory"); }
__device__ __forceinline__ void reg_fence(float (&d)[32]) { asm volatile("" : RW32("+f", d)::"memory"); }

template <int NR>
__device__ __forceinline__ void zero(float (&d)[NR]) {
#pragma unroll
    for (int i = 0; i < NR; i++) d[i] = 0.f;
}

constexpr uint32_t HI_SW128 = (1024u >> 4) | (1u << 30);
constexpr uint32_t HI_OST = (2560u >> 4) | (2u << 30);
constexpr uint32_t LO_LBO1 = (1u << 16);
constexpr uint32_t LO_OST = ((512u >> 4) << 16);

template <int TA, int TB, uint32_t HIB, int ACC>
__device__ __forceinline__ void wgmma(float (&d)[80], uint32_t loA, uint32_t loB) {
#define WG_ASM(SD)                                                          \
    "{\n.reg .b64 da, db;\nmov.b64 da, {%80, %82};\nmov.b64 db, {%81, %83};\n" \
    "wgmma.mma_async.sync.aligned.m64n160k16.f32.bf16.bf16 "               \
    "{%0,%1,%2,%3,%4,%5,%6,%7,%8,%9,%10,%11,%12,%13,%14,%15,%16,%17,%18,%19,%20,%21,%22,%23,%24,%25,%26,%27,%28,%29,%30,%31,%32,%33,%34,%35,%36,%37,%38,%39,%40,%41,%42,%43,%44,%45,%46,%47,%48,%49,%50,%51,%52,%53,%54,%55,%56,%57,%58,%59,%60,%61,%62,%63,%64,%65,%66,%67,%68,%69,%70,%71,%72,%73,%74,%75,%76,%77,%78,%79}, da, db, " SD ", 1, 1, %84, %85;\n}"
    if constexpr (ACC == 2)
        asm volatile(WG_ASM("0") : RW80("+f", d) : "r"(loA), "r"(loB), "n"(HI_SW128), "n"(HIB), "n"(TA), "n"(TB));
    else if constexpr (ACC == 1)
        asm volatile(WG_ASM("1") : RW80("+f", d) : "r"(loA), "r"(loB), "n"(HI_SW128), "n"(HIB), "n"(TA), "n"(TB));
    else
        asm volatile(WG_ASM("0") : RW80("=f", d) : "r"(loA), "r"(loB), "n"(HI_SW128), "n"(HIB), "n"(TA), "n"(TB));
#undef WG_ASM
}
template <int TA, int TB, uint32_t HIB, int ACC>
__device__ __forceinline__ void wgmma(float (&d)[48], uint32_t loA, uint32_t loB) {
#define WG_ASM(SD)                                                          \
    "{\n.reg .b64 da, db;\nmov.b64 da, {%48, %50};\nmov.b64 db, {%49, %51};\n" \
    "wgmma.mma_async.sync.aligned.m64n96k16.f32.bf16.bf16 "               \
    "{%0,%1,%2,%3,%4,%5,%6,%7,%8,%9,%10,%11,%12,%13,%14,%15,%16,%17,%18,%19,%20,%21,%22,%23,%24,%25,%26,%27,%28,%29,%30,%31,%32,%33,%34,%35,%36,%37,%38,%39,%40,%41,%42,%43,%44,%45,%46,%47}, da, db, " SD ", 1, 1, %52, %53;\n}"
    if constexpr (ACC == 1)
        asm volatile(WG_ASM("1") : RW48("+f", d) : "r"(loA), "r"(loB), "n"(HI_SW128), "n"(HIB), "n"(TA), "n"(TB));
    else
        asm volatile(WG_ASM("0") : RW48("=f", d) : "r"(loA), "r"(loB), "n"(HI_SW128), "n"(HIB), "n"(TA), "n"(TB));
#undef WG_ASM
}
template <int TA, int TB, uint32_t HIB, int ACC>
__device__ __forceinline__ void wgmma(float (&d)[32], uint32_t loA, uint32_t loB) {
#define WG_ASM(SD)                                                          \
    "{\n.reg .b64 da, db;\nmov.b64 da, {%32, %34};\nmov.b64 db, {%33, %35};\n" \
    "wgmma.mma_async.sync.aligned.m64n64k16.f32.bf16.bf16 "               \
    "{%0,%1,%2,%3,%4,%5,%6,%7,%8,%9,%10,%11,%12,%13,%14,%15,%16,%17,%18,%19,%20,%21,%22,%23,%24,%25,%26,%27,%28,%29,%30,%31}, da, db, " SD ", 1, 1, %36, %37;\n}"
    if constexpr (ACC == 1)
        asm volatile(WG_ASM("1") : RW32("+f", d) : "r"(loA), "r"(loB), "n"(HI_SW128), "n"(HIB), "n"(TA), "n"(TB));
    else
        asm volatile(WG_ASM("0") : RW32("=f", d) : "r"(loA), "r"(loB), "n"(HI_SW128), "n"(HIB), "n"(TA), "n"(TB));
#undef WG_ASM
}

__device__ __forceinline__ uint32_t pack_bf16(float lo, float hi) {
    uint32_t r;
    asm("cvt.rn.bf16x2.f32 %0, %1, %2;" : "=r"(r) : "f"(hi), "f"(lo));
    return r;
}
__device__ __forceinline__ float ex2(float x) {
    float r;
    asm("ex2.approx.ftz.f32 %0, %1;" : "=f"(r) : "f"(x));
    return r;
}
__device__ __forceinline__ void stsm4t(uint32_t a, uint32_t r0, uint32_t r1, uint32_t r2, uint32_t r3) {
    asm volatile("stmatrix.sync.aligned.m8n8.x4.trans.shared.b16 [%0], {%1,%2,%3,%4};" ::"r"(a), "r"(r0), "r"(r1), "r"(r2), "r"(r3)
                 : "memory");
}
__device__ __forceinline__ uint32_t lds_u(uint32_t a) {
    uint32_t v;
    asm volatile("ld.shared.u32 %0, [%1];" : "=r"(v) : "r"(a) : "memory");
    return v;
}
__device__ __forceinline__ uint4 lds_u4(uint32_t a) {
    uint4 v;
    asm volatile("ld.shared.v4.u32 {%0,%1,%2,%3}, [%4];" : "=r"(v.x), "=r"(v.y), "=r"(v.z), "=r"(v.w) : "r"(a) : "memory");
    return v;
}
__device__ __forceinline__ float2 lds_f2(uint32_t a) {
    float2 v;
    asm volatile("ld.shared.v2.f32 {%0,%1}, [%2];" : "=f"(v.x), "=f"(v.y) : "r"(a) : "memory");
    return v;
}
__device__ __forceinline__ void sts_f(uint32_t a, float v) { asm volatile("st.shared.f32 [%0], %1;" ::"r"(a), "f"(v) : "memory"); }
__device__ __forceinline__ void sts_u(uint32_t a, uint32_t v) { asm volatile("st.shared.u32 [%0], %1;" ::"r"(a), "r"(v) : "memory"); }
__device__ __forceinline__ void sts_f2(uint32_t a, float x, float y) {
    asm volatile("st.shared.v2.f32 [%0], {%1,%2};" ::"r"(a), "f"(x), "f"(y) : "memory");
}

template <bool ADD = false, bool SIG = false, int NR>
__device__ __forceinline__ void store_tile_t(const float (&d)[NR], uint32_t addr) {
    uint32_t p[NR / 2];
    if (ADD) {
#pragma unroll
        for (int j = 0; j < NR / 8; j++)
            asm volatile("ldmatrix.sync.aligned.m8n8.x4.trans.shared.b16 {%0,%1,%2,%3}, [%4];"
                         : "=r"(p[4 * j]), "=r"(p[4 * j + 1]), "=r"(p[4 * j + 2]), "=r"(p[4 * j + 3])
                         : "r"(addr + j * 2048)
                         : "memory");
    }
#pragma unroll
    for (int k = 0; k < NR / 2; k++)
        p[k] = ADD ? pack_bf16(d[2 * k] + __uint_as_float(p[k] << 16), d[2 * k + 1] + __uint_as_float(p[k] & 0xffff0000u))
                   : pack_bf16(d[2 * k], d[2 * k + 1]);
#pragma unroll
    for (int j = 0; j < NR / 8; j++) {
        stsm4t(addr + j * 2048, p[4 * j], p[4 * j + 1], p[4 * j + 2], p[4 * j + 3]);
        if (SIG && j == 0) nb_arrive<NB_L, 160>();
    }
}

struct TrueT { static constexpr bool value = true; };
struct FalseT { static constexpr bool value = false; };

template <int V>
struct IntT { static constexpr int value = V; };

__device__ __forceinline__ uint32_t get_item(uint32_t sb, int it, uint32_t dl) {
    mbar_wait(sb + BAR_ITEM + it * 8, 0, dl);
    return lds_u(sb + OFF_ITEM + it * 4);
}
__device__ __forceinline__ uint32_t get_item_warp(uint32_t sb, int it, uint32_t dl) {
    return __shfl_sync(0xffffffffu, get_item(sb, it, dl), 0);
}

struct Ring {
    uint32_t slot, ph, dl;
    __device__ __forceinline__ void adv(uint32_t k) {
        slot += k;
        if (slot >= NSLOT) { slot -= NSLOT; ph ^= 1; }
    }
};

template <int K>
__device__ __forceinline__ void qk_step(float (&s)[80], uint32_t loK, uint32_t loQ) {
    wgmma<0, 0, HI_SW128, K != 0>(s, loK + (K >> 2) * (8192 >> 4) + (K & 3) * 2, loQ + (K >> 2) * (XS >> 4) + (K & 3) * 2);
}
template <int K0, int K1>
__device__ __forceinline__ void qk_steps(float (&s)[80], uint32_t loK, uint32_t loQ) {
    if constexpr (K0 < K1) {
        qk_step<K0>(s, loK, loQ);
        qk_steps<K0 + 1, K1>(s, loK, loQ);
    }
}
__device__ __forceinline__ uint32_t add_bf2(uint32_t a, uint32_t b) {
    uint32_t r;
    asm("add.rn.bf16x2 %0, %1, %2;" : "=r"(r) : "r"(a), "r"(b));
    return r;
}
__device__ __forceinline__ uint32_t fma_bf2(uint32_t a, uint32_t b, uint32_t c) {
    uint32_t r;
    asm("fma.rn.bf16x2 %0, %1, %2, %3;" : "=r"(r) : "r"(a), "r"(b), "r"(c));
    return r;
}
template <int J>
__device__ __forceinline__ void exp_block(const float (&s)[80], uint32_t (&k)[40], uint32_t pa, float mref) {
    if constexpr (J < 10) {
#pragma unroll
        for (int i = 4 * J; i < 4 * J + 4; i++)
            k[i] = pack_bf16(ex2(fmaf(s[2 * i], SM_C, -mref)), ex2(fmaf(s[2 * i + 1], SM_C, -mref)));
#pragma unroll
        for (int i = 0; i < 4; i++)
            asm volatile("stmatrix.sync.aligned.m8n8.x1.trans.shared.b16 [%0], {%1};" ::"r"(((i & 1) ? pa ^ 16 : pa) + J * 2048 + (i >> 1) * 1024),
                         "r"(k[4 * J + i])
                         : "memory");
        exp_block<J + 1>(s, k, pa, mref);
    }
}
__device__ __forceinline__ void sum_block(const uint32_t (&k)[40], float (&l)[10], uint32_t lane) {
    const bool b4 = lane & 16, b3 = lane & 8;
    uint32_t ps[20], t[10];
#pragma unroll
    for (int j = 0; j < 20; j++) ps[j] = add_bf2(k[2 * j], k[2 * j + 1]);
#pragma unroll
    for (int j = 0; j < 10; j++)
        t[j] = add_bf2(b4 ? ps[2 * j + 1] : ps[2 * j], __shfl_xor_sync(0xffffffffu, b4 ? ps[2 * j] : ps[2 * j + 1], 16));
#pragma unroll
    for (int i = 0; i < 5; i++) {
        const uint32_t a = b3 ? t[i + 5] : t[i], b = __shfl_xor_sync(0xffffffffu, b3 ? t[i] : t[i + 5], 8);
        l[2 * i] += __uint_as_float(a << 16) + __uint_as_float(b << 16);
        l[2 * i + 1] += __uint_as_float(a & 0xffff0000u) + __uint_as_float(b & 0xffff0000u);
    }
}
template <bool ADD>
__device__ __forceinline__ void sum_store(const float (&l)[10], uint32_t lane, uint32_t lxa) {
    const bool b2 = lane & 4;
    float t[5];
#pragma unroll
    for (int i = 0; i < 5; i++) t[i] = ADD ? __uint_as_float(lds_u(lxa + i * 64)) : 0.f;
#pragma unroll
    for (int i = 0; i < 5; i++)
        sts_f(lxa + i * 64, t[i] + (b2 ? l[2 * i + 1] : l[2 * i]) + __shfl_xor_sync(0xffffffffu, b2 ? l[2 * i] : l[2 * i + 1], 4));
}

__device__ __forceinline__ void fallback_unit(const Params& P, uint32_t e, uint32_t tid) {
    const uint32_t lane = tid & 31, br = IT_BR(e), b = IT_B(e), h = IT_H0(e);
    const __nv_bfloat162* wq = (const __nv_bfloat162*)(P.pwq[br] + h * 192) + lane;
    const __nv_bfloat162* kp = (const __nv_bfloat162*)(P.pk[br] + (size_t)(b * 32 + h) * 512 * 192) + lane;
    const __nv_bfloat162* vp = (const __nv_bfloat162*)(P.pv[br] + (size_t)(b * 32 + h) * 512 * 192) + lane;
#pragma unroll 1
    for (uint32_t qi = 0; qi < 40; qi++) {
        const uint32_t q = 4 * qi + (tid >> 5);
        const __nv_bfloat16* xr = P.px[br] + (size_t)(b * 160 + q) * 640;
        float a[6] = {0.f, 0.f, 0.f, 0.f, 0.f, 0.f};
#pragma unroll 2
        for (int k = 0; k < 640; k++) {
            const float xv = __bfloat162float(xr[k]);
#pragma unroll
            for (int i = 0; i < 3; i++) {
                const float2 wv = __bfloat1622float2(wq[(size_t)k * 3072 + i * 32]);
                a[2 * i] = fmaf(xv, wv.x, a[2 * i]);
                a[2 * i + 1] = fmaf(xv, wv.y, a[2 * i + 1]);
            }
        }
#pragma unroll
        for (int i = 0; i < 6; i++) a[i] = __bfloat162float(__float2bfloat16(a[i]));
        auto score = [&](int key) {
            float d = 0.f;
#pragma unroll
            for (int i = 0; i < 3; i++) {
                const float2 kv = __bfloat1622float2(kp[key * 96 + i * 32]);
                d = fmaf(a[2 * i], kv.x, fmaf(a[2 * i + 1], kv.y, d));
            }
#pragma unroll
            for (int o = 16; o > 0; o >>= 1) d += __shfl_xor_sync(0xffffffffu, d, o);
            return d;
        };
        float m = -INFINITY, o[6] = {0.f, 0.f, 0.f, 0.f, 0.f, 0.f}, sum = 0.f;
#pragma unroll 1
        for (int n = 0; n < 1024; n++) {
            const int key = n & 511;
            const float d = score(key);
            if (n < 512) {
                m = fmaxf(m, d);
            } else {
                const float p = ex2((d - m) * SM_C);
                sum += p;
#pragma unroll
                for (int i = 0; i < 3; i++) {
                    const float2 vv = __bfloat1622float2(vp[key * 96 + i * 32]);
                    o[2 * i] = fmaf(p, vv.x, o[2 * i]);
                    o[2 * i + 1] = fmaf(p, vv.y, o[2 * i + 1]);
                }
            }
        }
        const float inv = __fdividef(1.f, sum);
        __nv_bfloat16* op = (__nv_bfloat16*)ostash(IT_SLOT(e), b) + (q >> 5) * 256 + 2 * ((q & 31) >> 3) + (q & 1);
#pragma unroll
        for (int i = 0; i < 6; i++) {
            const uint32_t d = (i >> 1) * 64 + 2 * lane + (i & 1);
            op[(d >> 3) * 1280 + (d & 7) * 32 + ((((q & 7) >> 1) ^ ((d & 7) >> 1)) << 3)] = __float2bfloat16(o[i] * inv);
        }
    }
}

template <int W>
struct PendO {
    static constexpr int N = W == 0 ? 56 : 64;
    uint32_t v[N];
    unsigned char* gp;
    static __device__ __forceinline__ uint32_t toff() {
        const uint32_t t = tid_now();
        return ((t >> 5) & 3) * 5120 + ((t >> 2) & 7) * 64 + (((t ^ (t >> 3)) & 3) << 4);
    }
    uint32_t pend, sig, bad;
    static __device__ __forceinline__ void scale(uint32_t& x, uint32_t hi, uint32_t lo) {
        asm("{\n.reg .b32 t;\nmul.rn.bf16x2 t, %0, %2;\nfma.rn.bf16x2 %0, %0, %1, t;\n}" : "+r"(x) : "r"(hi), "r"(lo));
    }
    template <int I, int OFF>
    __device__ __forceinline__ void put() {
        asm volatile("{\n.reg .pred p;\nsetp.ne.u32 p, %6, 0;\n@p st.global.v4.b32 [%0+%5], {%1,%2,%3,%4};\n}" ::"l"(gp), "r"(v[I]),
                     "r"(v[I + 1]), "r"(v[I + 2]), "r"(v[I + 3]), "n"(OFF), "r"(pend)
                     : "memory");
    }
    __device__ __forceinline__ void verdict(uint32_t sb) {
        if (sig) {
            nb_sync<NB_VOTE + W, 160>();
            bad = __any_sync(0xffffffffu, lds_u(sb + OFF_FB) != 0);
            pend = !bad;
        }
    }
    template <int G, int H>
    __device__ __forceinline__ void half(uint32_t sb) {
        constexpr bool T2 = W == 0 ? G >= 3 : G < 3;
        constexpr int B = T2 ? 40 + 8 * (W == 0 ? G - 3 : G) : 0;
        const uint4 a = lds_u4(sb + OFF_LINV + G * 128 + H * 16 + (threadIdx.x & 3) * 32);
#pragma unroll
        for (int i = 2 * H; i < 8; i += 4) {
            scale(v[8 * G + i], a.x, a.y);
            scale(v[8 * G + i + 1], a.z, a.w);
            if (T2) {
                scale(v[B + i], a.x, a.y);
                scale(v[B + i + 1], a.z, a.w);
            }
        }
        if (H == 1) {
            put<8 * G, W * XS + G * 512>();
            put<8 * G + 4, W * XS + G * 512 + 2560>();
            if (T2) {
                put<B, 2 * XS + G * 512>();
                put<B + 4, 2 * XS + G * 512 + 2560>();
            }
            if (G == 4 && pend) nb_arrive<NB_ODONE, 288>();
        }
    }
    template <int G>
    __device__ __forceinline__ void step(uint32_t sb) {
        half<G, 0>(sb);
        half<G, 1>(sb);
    }
    __device__ __forceinline__ void clear() {
#pragma unroll
        for (int i = 0; i < N; i++) v[i] = 0;
        gp = nullptr;
        pend = 0;
        sig = 0;
        bad = 0;
    }
};

__device__ __forceinline__ uint32_t stsm_off() {
    const uint32_t tid = tid_now(), lane = tid & 31;
    return (lane >> 4) * 1024 + (lane & 7) * 128 + (((((tid >> 4) & 6) + ((lane >> 3) & 1)) ^ (lane & 7)) << 4);
}
__device__ __forceinline__ void q_ahead(float (&q0)[80], uint32_t sb, const Ring& rn, uint32_t phm, bool valid) {
    if (valid) {
        mbar_wait(sb + BAR_RFULL + rn.slot * 8, rn.ph, rn.dl);
        mbar_wait(sb + BAR_XFULL, phm & 1, rn.dl);
    }
    const uint32_t a = ((((sb + OFF_RING) & 0x3ffff) >> 4) | LO_LBO1) + rn.slot * (SLOT >> 4);
    const uint32_t b = (((sb + OFF_R) & 0x3ffff) >> 4) | LO_LBO1;
    wg_fence();
    wgmma<1, 0, HI_SW128, false>(q0, a, b);
#pragma unroll
    for (int k = 1; k < 4; k++) wgmma<1, 0, HI_SW128, true>(q0, a + (k >> 1) * 768 + (k & 1) * 128, b + k * 2);
    wg_commit();
}
template <int W, int KK>
__device__ __forceinline__ void qproj(float (&q0)[80], float (&q1)[80], uint32_t sb, Ring& r, uint32_t pslot, uint32_t phm,
                                      PendO<W>& po) {
    const uint32_t loR = (((sb + OFF_R) & 0x3ffff) >> 4) | LO_LBO1;
    const uint32_t loRing = (((sb + OFF_RING) & 0x3ffff) >> 4) | LO_LBO1;
    auto ready = [&](int k) {
        mbar_wait(sb + BAR_RFULL + r.slot * 8, r.ph, r.dl);
        mbar_wait(sb + BAR_XFULL + (k % 5) * 8, ((phm >> (k % 5)) ^ (k / 5)) & 1, r.dl);
    };
    auto release = [&]() {
        if (KK > 0) {
            wg_wait<1>();
            mbar_arrive_warp(sb + BAR_REMPTY + pslot * 8);
            if (KK <= 5) mbar_arrive_warp(sb + (BAR_XEMPTY + (KK - 1) * 8));
        }
    };
    if (KK == 0 && W == 1) ready(0);
    if (W == 1 && KK == QHOLD) {
        if (QHOLD == 7) {
            wg_wait<0>();
            nb_arrive<NB_PDONE, 256>();
        }
        nb_sync<NB_SDONE, 256>();
    }
    const uint32_t a = loRing + r.slot * (SLOT >> 4) + (W == 0 ? 0 : 512), b = loR + (KK % 5) * (XS >> 4);
    wg_fence();
    constexpr bool T0 = W == 1 || KK > 0;
    if (T0) wgmma<1, 0, HI_SW128, KK != 0>(q0, a, b);
    if (W == 0) wgmma<1, 0, HI_SW128, KK != 0 ? 1 : 2>(q1, a + 256, b);
#pragma unroll
    for (int k = 1; k < 4; k++) {
        if (T0) wgmma<1, 0, HI_SW128, true>(q0, a + (k >> 1) * 768 + (k & 1) * 128, b + k * 2);
        if (W == 0) wgmma<1, 0, HI_SW128, true>(q1, a + 256 + (k >> 1) * 768 + (k & 1) * 128, b + k * 2);
    }
    wg_commit();
    const uint32_t cslot = r.slot;
    r.adv(1);
    if (W == 0 || KK < QHOLD) release();
    if (KK == QST0) {
        po.verdict(sb);
        po.template half<0, 0>(sb);
    }
    if (KK < 9) ready(KK + 1);
    if (W == 1 && KK >= QHOLD) release();
    if (W == 1 && KK == 7 && QHOLD > 7) nb_arrive<NB_PDONE, 256>();
    if (KK == QST0) po.template half<0, 1>(sb);
    if constexpr (KK > QST0 && KK < QST0 + 5) po.template step<KK - QST0>(sb);
    if constexpr (KK < (W == 0 ? 7 : 9)) {
        qproj<W, KK + 1>(q0, q1, sb, r, cslot, phm, po);
    } else if constexpr (W == 1) {
        wg_wait<0>();
        reg_fence(q0);
        mbar_arrive_warp(sb + BAR_REMPTY + cslot * 8);
        store_tile_t<false, true>(q0, sb + OFF_R + 2 * XS + stsm_off());
    } else {
        const uint32_t s8 = r.slot, a8 = loRing + s8 * (SLOT >> 4);
        wg_fence();
#pragma unroll
        for (int k = 0; k < 4; k++) wgmma<1, 0, HI_SW128, true>(q0, a8 + (k >> 1) * 768 + (k & 1) * 128, loR + 3 * (XS >> 4) + k * 2);
        r.adv(1);
        ready(9);
        const uint32_t s9 = r.slot, a9 = loRing + s9 * (SLOT >> 4);
        r.adv(1);
        wg_fence();
#pragma unroll
        for (int k = 0; k < 4; k++) wgmma<1, 0, HI_SW128, true>(q0, a9 + (k >> 1) * 768 + (k & 1) * 128, loR + 4 * (XS >> 4) + k * 2);
        wg_commit();
        wg_wait<1>();
        mbar_arrive_warp(sb + BAR_REMPTY + cslot * 8);
        wg_fence();
#pragma unroll
        for (int k = 0; k < 8; k++)
            wgmma<1, 0, HI_SW128, true>(q1, (k < 4 ? a8 : a9) + 256 + ((k >> 1) & 1) * 768 + (k & 1) * 128,
                                        loR + (3 + (k >> 2)) * (XS >> 4) + (k & 3) * 2);
        wg_commit();
        nb_arrive<NB_SDONE, 256>();
        nb_sync<NB_PDONE, 256>();
        wg_wait<1>();
        reg_fence(q0);
        const uint32_t sta = sb + OFF_R + stsm_off();
        store_tile_t(q0, sta);
        sts_u(sb + OFF_GM + 4, r.slot);
        mbar_wait(sb + BAR_RFULL + r.slot * 8, r.ph, r.dl);
        wg_wait<0>();
        reg_fence(q1);
        mbar_arrive_warp(sb + BAR_REMPTY + s8 * 8);
        mbar_arrive_warp(sb + BAR_REMPTY + s9 * 8);
        store_tile_t(q1, sta + XS);
    }
}

template <int NR>
__device__ __forceinline__ void opack(const float (&o)[NR], uint32_t* v) {
#pragma unroll
    for (int g = 0; g < NR / 16; g++)
#pragma unroll
        for (int hh = 0; hh < 2; hh++)
#pragma unroll
            for (int t = 0; t < 4; t++) v[8 * g + 4 * hh + t] = pack_bf16(o[16 * g + 4 * t + 2 * hh], o[16 * g + 4 * t + 2 * hh + 1]);
}

template <bool IS_S>
__device__ __forceinline__ void op_item(uint32_t e, uint32_t sb, Ring& r, uint32_t& phm) {
    constexpr int T0 = IS_S ? 0 : 2;
    constexpr uint32_t BOFF = IS_S ? (3 * 512) >> 4 : 0;
    const uint32_t loRing = (((sb + OFF_RING) & 0x3ffff) >> 4) | LO_LBO1;
    const uint32_t loO = (((sb + OFF_R) & 0x3ffff) >> 4) | LO_OST;
    float c0[80], c1[80], c2[IS_S ? 32 : 48];
    const int T = 3 * (IT_H1(e) - IT_H0(e));
    uint32_t xs = 0;
    auto step = [&](auto first, auto half) {
        constexpr bool F = decltype(first)::value;
        constexpr uint32_t hf = decltype(half)::value;
        if (hf == 0) {
            mbar_wait(sb + BAR_XFULL + xs * 8, (phm >> xs) & 1, r.dl);
            phm ^= 1u << xs;
        }
        mbar_wait(sb + BAR_RFULL + r.slot * 8, r.ph, r.dl);
        const uint32_t a = loRing + r.slot * (SLOT >> 4), b = loO + xs * (XS >> 4) + hf * 640;
        wg_fence();
        wgmma<1, 1, HI_OST, !F>(c0, a + T0 * 128, b);
        wgmma<1, 1, HI_OST, !F>(c1, a + T0 * 128 + 128, b);
        wgmma<1, 1, HI_OST, !F>(c2, a + 512, b + BOFF);
        wgmma<1, 1, HI_OST, true>(c0, a + 640 + T0 * 128, b + 320);
        wgmma<1, 1, HI_OST, true>(c1, a + 640 + T0 * 128 + 128, b + 320);
        wgmma<1, 1, HI_OST, true>(c2, a + 640 + 512, b + 320 + BOFF);
        wg_commit();
    };
    step(TrueT{}, IntT<0>{});
#pragma unroll 1
    for (int t = 1;; t++) {
        uint32_t pslot = r.slot;
        r.adv(1);
        step(FalseT{}, IntT<1>{});
        wg_wait<1>();
        mbar_arrive_warp(sb + BAR_REMPTY + pslot * 8);
        if (t == T) break;
        pslot = r.slot;
        const uint32_t pxs = xs;
        r.adv(1);
        if (++xs == 5) xs = 0;
        step(FalseT{}, IntT<0>{});
        wg_wait<1>();
        mbar_arrive_warp(sb + BAR_REMPTY + pslot * 8);
        mbar_arrive_warp_if(sb + BAR_XEMPTY + pxs * 8, t + 4 < T);
    }
    wg_wait<0>();
    reg_fence(c0);
    reg_fence(c1);
    reg_fence(c2);
    mbar_arrive_warp(sb + BAR_REMPTY + r.slot * 8);
    r.adv(1);
    nb_sync<NB_OPEND, 256>();
    const uint32_t sta = sb + OFF_R + stsm_off();
    store_tile_t(c0, sta + T0 * XS);
    store_tile_t(c1, sta + (T0 + 1) * XS);
    store_tile_t(c2, sta + 4 * XS + (IS_S ? 96 * 128 : 0));
    fence_async_smem();
    nb_arrive<NB_ODONE, 288>();
}

__device__ __forceinline__ void on_item(uint32_t W, uint32_t e, uint32_t sb, Ring& r, uint32_t& phm) {
    const uint32_t loRing = (((sb + OFF_RING) & 0x3ffff) >> 4) | LO_LBO1;
    const uint32_t loO = (((sb + OFF_R) & 0x3ffff) >> 4) | LO_OST;
    float c[80];
    const int T = 3 * (IT_H1(e) - IT_H0(e));
    uint32_t xs = 0;
    auto step = [&](auto first) {
        constexpr bool F = decltype(first)::value;
        mbar_wait(sb + BAR_XFULL + xs * 8, (phm >> xs) & 1, r.dl);
        phm ^= 1u << xs;
        mbar_wait(sb + BAR_RFULL + r.slot * 8, r.ph, r.dl);
        const uint32_t a = loRing + r.slot * (SLOT >> 4) + W * 256, b = loO + xs * (XS >> 4);
        wg_fence();
        wgmma<1, 1, HI_OST, !F>(c, a, b);
#pragma unroll
        for (int k = 1; k < 4; k++) wgmma<1, 1, HI_OST, true>(c, a + (k >> 1) * 512 + (k & 1) * 128, b + k * 320);
        wg_commit();
    };
    step(TrueT{});
#pragma unroll 1
    for (int t = 1; t < T; t++) {
        const uint32_t pslot = r.slot, pxs = xs;
        r.adv(1);
        if (++xs == 5) xs = 0;
        step(FalseT{});
        wg_wait<1>();
        mbar_arrive_warp(sb + BAR_REMPTY + pslot * 8);
        mbar_arrive_warp_if(sb + BAR_XEMPTY + pxs * 8, t + 2 < T);
    }
    xs += 1 + W;
    if (xs >= 5) xs -= 5;
    mbar_wait(sb + BAR_XFULL + xs * 8, (phm >> xs) & 1, r.dl);
    wg_wait<0>();
    reg_fence(c);
    store_tile_t<true>(c, sb + OFF_R + xs * XS + stsm_off());
    fence_async_smem();
    nb_arrive<NB_ODONE, 288>();
}

template <int W>
__device__ __forceinline__ uint32_t qa_item(uint32_t e, uint32_t sb, Ring& r, uint32_t phm, PendO<W>& po, float (&q0)[80],
                                            float (&oa)[80], int it) {
    const uint32_t loR = (((sb + OFF_R) & 0x3ffff) >> 4) | LO_LBO1;
    const uint32_t loRing = (((sb + OFF_RING) & 0x3ffff) >> 4) | LO_LBO1;
    qproj<W, 0>(q0, oa, sb, r, 0, phm, po);
    fence_async_smem();
    TSD(W, 1);
    float s[80], ob[W == 0 ? 32 : 48], l[10];
    if (W == 1) {
        nb_arrive<NB_Q2, 256>();
        zero(oa);
        zero(ob);
        reg_fence(oa);
        reg_fence(ob);
    }
    const uint32_t lane = tid_now() & 31, sta = sb + OFF_R + stsm_off();
    auto pv = [&](auto first, uint32_t buf) {
        constexpr bool F = decltype(first)::value;
        mbar_wait(sb + BAR_RFULL + r.slot * 8, r.ph, r.dl);
        const uint32_t a = loRing + r.slot * (SLOT >> 4), b = loR + (3 + buf) * (XS >> 4);
        wg_fence();
        wgmma<1, 0, HI_SW128, F ? 2 : 1>(oa, a + W * 512, b);
        wgmma<1, 0, HI_SW128, !F>(ob, a + 1024, b + (W == 0 ? (96 * 128) >> 4 : 0));
#pragma unroll
        for (int k = 1; k < 4; k++) {
            wgmma<1, 0, HI_SW128, true>(oa, a + W * 512 + k * 128, b + k * 2);
            wgmma<1, 0, HI_SW128, true>(ob, a + 1024 + k * 128, b + (W == 0 ? (96 * 128) >> 4 : 0) + k * 2);
        }
        wg_commit();
    };
    zero(l);
    float mref;
    uint32_t kslot, vslot, nx = 0;
    auto tail = [&](auto first, int i) {
        constexpr bool rel_other = !decltype(first)::value;
        uint32_t ps[40];
        exp_block<0>(s, ps, sta + (3 + W) * XS, mref);
        if (rel_other) {
            wg_wait<0>();
            mbar_arrive_warp(sb + BAR_REMPTY + vslot * 8);
            if (W == 1) mbar_arrive_warp_if(sb + BAR_XEMPTY + 24, i == 3);
        }
        fence_async_smem();
        nb_arrive<NB_PFULL + W, 256>();
        TSD(W, 6 + 5 * i);
        if (W == 1) {
            if (XLATE >= 2) mbar_arrive_warp_if<2>(sb + BAR_XEMPTY + 8, i == 3);
            if (XLATE >= 1) mbar_arrive_warp_if<2>(sb + BAR_XEMPTY + 16, i == 3);
        }
        if (rel_other || !PV0FIRST) {
            mbar_wait(sb + BAR_RFULL + r.slot * 8, r.ph, r.dl);
            sum_block(ps, l, lane);
        }
        if (W == 0 && i == 3) nx = get_item_warp(sb, it + 1, r.dl);
        TSD(W, 7 + 5 * i);
        if (LASTORD && W == 0 && i == 3) nb_sync<NB_PDONE, 256>();
        else nb_sync<NB_W + W, 128>();
        pv(first, W);
        if (!rel_other && PV0FIRST) sum_block(ps, l, lane);
        TSD(W, 8 + 5 * i);
    };
    if (W == 0) {
        nb_sync<NB_QK, 160>();
        TSD(W, 2);
        wg_fence();
        qk_steps<0, 8>(s, loRing + r.slot * (SLOT >> 4), loR);
        nb_sync<NB_Q2, 256>();
        qk_steps<8, 12>(s, loRing + r.slot * (SLOT >> 4), loR);
        wg_commit();
        nb_arrive<NB_Q01, 256>();
        TSD(W, 4);
        nb_sync<NB_REF, 160>();
        mref = __uint_as_float(lds_u(sb + OFF_GM));
        wg_wait<0>();
        reg_fence(s);
        mbar_arrive_warp<2>(sb + BAR_REMPTY + r.slot * 8);
        r.adv(2);
        TSD(W, 5);
        tail(TrueT{}, 0);
    } else {
        nb_sync<NB_Q01, 256>();
    }
#pragma unroll 1
    for (int i = (W == 0 ? 1 : 0); i < 4; i++) {
        const uint32_t pvslot = r.slot;
        r.adv(1);
        kslot = r.slot;
        mbar_wait(sb + BAR_RFULL + r.slot * 8, r.ph, r.dl);
        wg_fence();
        qk_steps<0, 4>(s, loRing + r.slot * (SLOT >> 4), loR);
        if (W == 1) wg_commit();
        qk_steps<4, 12>(s, loRing + r.slot * (SLOT >> 4), loR);
        wg_commit();
        wg_wait<1>();
        if (W == 1) mbar_arrive_warp_if(sb + BAR_XEMPTY + 0, i == 3);
        mbar_arrive_warp_if(sb + BAR_REMPTY + pvslot * 8, W == 0 || i > 0);
        r.adv(1);
        vslot = r.slot;
        TSD(W, 4 + 5 * i);
        nb_sync<NB_PFULL + (W ^ 1), 256>();
        pv(FalseT{}, W ^ 1);
        if (LASTORD && W == 1 && i == 3) nb_arrive<NB_PDONE, 256>();
        if (W == 1) mref = __uint_as_float(lds_u(sb + OFF_GM));
        wg_wait<1>();
        reg_fence(s);
        mbar_arrive_warp<2>(sb + BAR_REMPTY + kslot * 8);
        if (W == 0) mbar_arrive_warp_if(sb + BAR_XEMPTY + 0, i == 3);
        if (W == 1) {
            if (XLATE < 2) mbar_arrive_warp_if<2>(sb + BAR_XEMPTY + 8, i == 3);
            if (XLATE < 1) mbar_arrive_warp_if<2>(sb + BAR_XEMPTY + 16, i == 3);
        }
        r.adv(W == 1 && i == 3 ? 1 : 2);
        TSD(W, 5 + 5 * i);
        tail(FalseT{}, i);
    }
    if (W == 1) nx = get_item_warp(sb, it + 1, r.dl);
    if (W == 0) {
        Ring rn = r;
        rn.adv(2);
        q_ahead(q0, sb, rn, phm, IT_TYPE(nx) == IT_QA);
        TSD(W, 25);
    }
    const uint32_t w = (tid_now() >> 5) & 3;
    const uint32_t lxa = sb + OFF_LX + w * 640 + (((lane & 8) ? 80 : 0) + ((lane >> 1) & 8) + 2 * (lane & 3) + ((lane >> 2) & 1)) * 4;
    po.gp = ostash(IT_SLOT(e), IT_B(e)) + po.toff();
    po.sig = 1;
    if (W == 0) {
        sum_store<false>(l, lane, lxa);
        nb_arrive<NB_LX, 256>();
        wg_wait<1>();
        mbar_arrive_warp(sb + BAR_REMPTY + r.slot * 8);
        mbar_arrive_warp(sb + BAR_XEMPTY + 24);
        r.adv(1);
        nb_sync<NB_PFULL + 1, 256>();
        pv(FalseT{}, 1);
    } else {
        nb_sync<NB_LX, 256>();
        sum_store<true>(l, lane, lxa);
        nb_arrive<NB_L, 160>();
    }
    TSD(W, 24);
    wg_wait<0>();
    reg_fence(oa);
    reg_fence(ob);
    mbar_arrive_warp(sb + BAR_REMPTY + r.slot * 8);
    mbar_arrive_warp(sb + BAR_XEMPTY + 32);
    r.adv(1);
    opack(ob, po.v + 40);
    opack(oa, po.v);
    return nx;
}

template <int W>
__device__ __forceinline__ uint32_t qa_run(const Params& P, uint32_t e, uint32_t sb, Ring& r, uint32_t phm, int& it) {
    PendO<W> po;
    po.clear();
    float q0[80], oa[80];
    if (W == 0) {
        zero(oa);
        q_ahead(q0, sb, r, phm, true);
        wg_wait<0>();
    }
#pragma unroll 1
    do {
        TS(W, 0);
        if (W == 0) TS_ITEM(e);
        e = qa_item<W>(e, sb, r, phm, po, q0, oa, it);
        TS(W, 31);
        it++;
    } while (IT_TYPE(e) == IT_QA && !po.bad);
#pragma unroll 1
    for (int m = po.bad ? 2 : 1; m > 0; m--) {
        if (m == 1) {
            po.verdict(sb);
            po.template step<0>(sb);
            po.template step<1>(sb);
            po.template step<2>(sb);
            po.template step<3>(sb);
            po.template step<4>(sb);
        }
        if (po.bad) {
            if (W == 0) fallback_unit(P, lds_u(sb + OFF_ITEM + (it - m) * 4), tid_now() & 127);
            __syncwarp();
            nb_sync<NB_ODONE, 288>();
        }
    }
    return e;
}

__device__ __forceinline__ void consumer(const Params& P, uint32_t W, uint32_t sb, uint32_t dl) {
    int it = 0;
    Ring r{0, 0, dl};
    uint32_t phm = 0;
    uint32_t e = get_item_warp(sb, 0, dl);
#pragma unroll 1
    while (true) {
        if (IT_TYPE(e) == IT_QA) e = W == 0 ? qa_run<0>(P, e, sb, r, phm, it) : qa_run<1>(P, e, sb, r, phm, it);
        if (e == 0) break;
        if (IT_TYPE(e) == IT_QA) continue;
        TS(W, 0);
        if (W == 0) TS_ITEM(e);
        if (IT_TYPE(e) == IT_ON) on_item(W, e, sb, r, phm);
        else if (W == 0) op_item<true>(e, sb, r, phm);
        else op_item<false>(e, sb, r, phm);
        TS(W, 31);
        e = get_item_warp(sb, ++it, dl);
    }
    TS_DUMP(W);
}

__global__ void __cluster_dims__(2, 1, 1) __launch_bounds__(384, 1) fused_kernel(const __grid_constant__ Params P) {
    extern __shared__ __align__(1024) unsigned char smem_raw[];
    const uint32_t sb = (uint32_t)__cvta_generic_to_shared(smem_raw);
    const uint32_t warp = __shfl_sync(0xffffffffu, threadIdx.x >> 5, 0), wgid = warp >> 2;
    const uint32_t cta = blockIdx.x;
    const uint32_t dl = deadline();

    if (threadIdx.x == 128) {
#pragma unroll
        for (int i = 0; i < NSLOT; i++) {
            mbar_init(sb + BAR_RFULL + i * 8, 1);
            mbar_init(sb + BAR_REMPTY + i * 8, 8);
            mbar_init(sb + BAR_XFULL + i * 8, 1);
            mbar_init(sb + BAR_XEMPTY + i * 8, 8);
        }
        asm volatile("fence.mbarrier_init.release.cluster;" ::: "memory");
        fence_async_smem();
    } else if (threadIdx.x == 160) {
#pragma unroll
        for (int i = 0; i < NSLOT + MAXI; i++) mbar_init(sb + BAR_PRDY + i * 8, 1);
        asm volatile("fence.mbarrier_init.release.cluster;" ::: "memory");
    } else if (threadIdx.x == 0) {
        sts_u(sb + OFF_ITEM, P.cl[cta >> 1].items[0] ? P.cl[cta >> 1].items[0] + 8 * (cta & 1) : 0);
        sts_u(sb + OFF_FB, P.cl[cta >> 1].delay);
    } else if (threadIdx.x == 64) {
        if (sb & 1023) __trap();
        asm volatile("prefetch.tensormap [%0];" ::"l"(&P.wq[0]) : "memory");
        asm volatile("prefetch.tensormap [%0];" ::"l"(&P.x[0]) : "memory");
    }
    __syncthreads();
    {
        const int it = 0;
        if (wgid == 1) TS(0, 30);
    }
    asm volatile("barrier.cluster.arrive.relaxed.aligned;" ::: "memory");
    if (warp < 3) {
        const uint32_t e = __shfl_sync(0xffffffffu, lds_u(sb + OFF_ITEM), 0), d = lds_u(sb + OFF_FB);
        const uint64_t pol = mkpol<POL_W>();
        const bool isx = warp == 1, lead = (threadIdx.x & 31) == 0;
        uint32_t t0, t1;
        asm volatile("mov.u32 %0, %%clock;" : "=r"(t0));
        do {
            asm volatile("mov.u32 %0, %%clock;" : "=r"(t1));
        } while (t1 - t0 < d);
        __syncwarp();
#pragma unroll 1
        for (int n = 0; n < (e ? NSLOT : 0); n++) {
            const uint32_t bar = sb + (isx ? BAR_XFULL : BAR_RFULL) + n * 8;
            if (lead) {
                if (warp < 2) mbar_expect(bar, isx ? XS : SLOT);
                tma3(sb + (isx ? OFF_R + n * XS : OFF_RING + n * SLOT + warp * (SLOT / 4)), isx ? &P.x[0] : &P.wq[0],
                     isx ? IT_B(e) * 160 : n * 64 + warp * 16, isx ? n : IT_H0(e) * 3, bar, pol);
            }
        }
        if (threadIdx.x == 0) asm volatile("mbarrier.arrive.shared::cta.b64 _, [%0];" ::"r"(sb + BAR_ITEM) : "memory");
        __syncwarp();
    }

    if (wgid == 0) {
        asm volatile("setmaxnreg.dec.sync.aligned.u32 24;");
        if (warp == 0) {
            const bool lead = threadIdx.x == 0;
            const uint64_t pol_first = mkpol<1>(), pol_norm = mkpol<POL_W>();
            uint32_t e = __shfl_sync(0xffffffffu, lds_u(sb + OFF_ITEM), 0);
            asm volatile("barrier.cluster.wait.aligned;" ::: "memory");
            unsigned int* const ticket = &g_ticket[next_epoch(0) & 1];
            const uint32_t rank = cta & 1;
            uint32_t peer;
            asm volatile("mapa.shared::cluster.u32 %0, %1, %2;" : "=r"(peer) : "r"(sb), "r"(rank ^ 1));
            Ring r{0, 0, dl};
            uint32_t pm = 0;
            auto load_w = [&](const CUtensorMap* m, int row, int blk, uint32_t half_bytes) {
                mbar_wait(sb + BAR_REMPTY + r.slot * 8, r.ph, dl);
                if (lead) {
                    mbar_expect(sb + BAR_RFULL + r.slot * 8, 2 * half_bytes);
                    asm volatile("mbarrier.arrive.shared::cluster.b64 _, [%0];" ::"r"(peer + BAR_PRDY + r.slot * 8) : "memory");
                }
                mbar_wait(sb + BAR_PRDY + r.slot * 8, (pm >> r.slot) & 1, dl);
                pm ^= 1u << r.slot;
                if (lead) tma3_mc(sb + OFF_RING + r.slot * SLOT + rank * half_bytes, m, row, blk, sb + BAR_RFULL + r.slot * 8, pol_norm);
                r.adv(1);
            };
#pragma unroll 1
            for (int it = 0; e != 0; it++) {
                uint32_t nx = 0, tk = 0;
                if (rank == 0 && IT_TYPE(e) != IT_ON && it + 2 < MAXI) nx = it + 1 < NSTAT ? P.cl[cta >> 1].items[it + 1] : IT_DYN;
                const uint32_t br = IT_BR(e);
                if (IT_TYPE(e) == IT_QA) {
                    const uint32_t h = IT_H0(e);
#pragma unroll 1
                    for (int kk = it ? 0 : NSLOT; kk < 10; kk++) load_w(&P.wq[br], kk * 64 + rank * 32, h * 3, SLOT / 2);
                    const int row0 = (IT_B(e) * 32 + h) * 512;
#pragma unroll 1
                    for (int n = 0; n < 16; n++) {
                        if (n == 13 && nx == IT_DYN && lead) tk = atomicAdd(ticket, 1);
                        const bool isv = n == 15 || (n > 0 && !(n & 1));
                        const int j = n == 15 ? 7 : isv ? (n - 2) >> 1 : (n + 1) >> 1;
                        mbar_wait(sb + BAR_REMPTY + r.slot * 8, r.ph, dl);
                        if (lead) {
                            mbar_expect(sb + BAR_RFULL + r.slot * 8, SLOT);
                            tma3(sb + OFF_RING + r.slot * SLOT, isv ? &P.v[br] : &P.k[br], row0 + j * 64, 0,
                                 sb + BAR_RFULL + r.slot * 8, pol_first);
                        }
                        r.adv(1);
                    }
                } else {
                    const bool wide = IT_TYPE(e) == IT_OP;
                    const int step = wide ? 32 : 64, r1 = IT_H1(e) * 192;
#pragma unroll 1
                    for (int row = IT_H0(e) * 192 + rank * (step >> 1); row < r1; row += step)
                        load_w(wide ? &P.wo[br] : &P.won[br], row, IT_HALF(e) * (wide ? 5 : 2), wide ? XS / 2 : 8192);
                    if (nx == IT_DYN && lead) tk = atomicAdd(ticket, 1);
                }
                if (rank == 0) {
                    if (nx == IT_DYN) {
                        tk = __shfl_sync(0xffffffffu, tk, 0);
                        nx = tk < P.nlist ? P.list[tk] : 0;
                    }
                    e = nx;
                    if (lead) {
                        asm volatile("st.async.weak.shared::cluster.mbarrier::complete_tx::bytes.b32 [%0], %1, [%2];" ::"r"(
                                         peer + OFF_ITEM + 4 + it * 4),
                                     "r"(e ? e + 8 : 0), "r"(peer + BAR_ITEM + 8 + it * 8)
                                     : "memory");
                        sts_u(sb + OFF_ITEM + 4 + it * 4, e);
                        asm volatile("mbarrier.arrive.shared::cta.b64 _, [%0];" ::"r"(sb + BAR_ITEM + 8 + it * 8) : "memory");
                    }
                } else {
                    if (lead) mbar_expect(sb + BAR_ITEM + 8 + it * 8, 4);
                    e = get_item_warp(sb, it + 1, dl);
                }
            }
        } else if (warp == 1) {
            const uint64_t pol_norm = mkpol<POL_X>(), pol_o = mkpol<POL_O>();
            const bool lead = threadIdx.x == 32;
            uint32_t phm = 0, epoch = 0;
#pragma unroll 1
            for (int it = 0;; it++) {
                const uint32_t e = get_item_warp(sb, it, dl);
                if (it == 1 || (it == 0 && e == 0)) epoch = next_epoch(1);
                if (e == 0) break;
                const uint32_t br = IT_BR(e);
                uint32_t xs = 0;
                auto acquire = [&]() {
                    mbar_wait(sb + BAR_XEMPTY + xs * 8, (phm >> xs) & 1, dl);
                    phm ^= 1u << xs;
                    if (lead) mbar_expect(sb + BAR_XFULL + xs * 8, XS);
                };
                if (IT_TYPE(e) == IT_QA) {
#pragma unroll 1
                    for (int kk = it ? 0 : 5; kk < 10; kk++) {
                        acquire();
                        if (lead) tma3(sb + OFF_R + xs * XS, &P.x[br], IT_B(e) * 160, kk, sb + BAR_XFULL + xs * 8, pol_norm);
                        if (++xs == 5) xs = 0;
                    }
                } else {
                    const unsigned int* fp = g_flag + (br * 16 + IT_B(e)) * 64 + (threadIdx.x & 31);
                    uint32_t hm = 0, pm = 0;
                    auto poll = [&](uint32_t hneed, uint32_t pneed) {
                        if ((hm & hneed) == hneed && (pm & pneed) == pneed) return;
                        uint32_t n = 0;
                        do {
                            uint32_t a, b;
                            asm volatile("ld.acquire.gpu.global.u32 %0, [%2];\nld.acquire.gpu.global.u32 %1, [%2+128];"
                                         : "=r"(a), "=r"(b) : "l"(fp) : "memory");
                            hm = __ballot_sync(0xffffffffu, a == epoch);
                            pm = __ballot_sync(0xffffffffu, b == epoch);
                            if (++n > 0x1000000) __trap();
                        } while ((hm & hneed) != hneed || (pm & pneed) != pneed);
                        __syncwarp();
                        asm volatile("fence.proxy.async;" ::: "memory");
                    };
#pragma unroll 1
                    for (uint32_t h = IT_H0(e); h < IT_H1(e); h++) {
                        poll(1u << h, 0);
                        const unsigned char* src = ostash(P.slot[br * 32 + h], IT_B(e));
#pragma unroll 1
                        for (int t = 0; t < 3; t++) {
                            acquire();
                            if (lead) bulk_load(sb + OFF_R + xs * XS, src + t * XS, XS, sb + BAR_XFULL + xs * 8, pol_o);
                            if (++xs == 5) xs = 0;
                        }
                        if (IT_TYPE(e) == IT_OP && h >= 1) {
                            const uint32_t x1 = xs == 4 ? 0 : xs + 1;
                            mbar_wait(sb + BAR_XFULL + xs * 8, (phm >> xs) & 1, dl);
                            mbar_wait(sb + BAR_XFULL + x1 * 8, (phm >> x1) & 1, dl);
                            if (lead)
                                asm volatile("st.relaxed.gpu.global.u32 [%0], %1;" ::"l"(fp + 34 + IT_HALF(e)), "r"(epoch * 64 + h) : "memory");
                        }
                    }
                    if (IT_TYPE(e) == IT_ON) {
                        poll(0, IT_HALF(e) < 2 ? 1 : IT_HALF(e) == 2 ? 3 : 2);
#pragma unroll 1
                        for (uint32_t tile = 2 * IT_HALF(e); tile < 2 * IT_HALF(e) + 2; tile++) {
                            acquire();
                            if (lead)
                                asm volatile(
                                    "cp.async.bulk.tensor.5d.shared::cluster.global.mbarrier::complete_tx::bytes [%0], [%1, {%3,%5,%5,%5,%4}], [%2];" ::"r"(
                                        sb + OFF_R + xs * XS),
                                    "l"(&P.out), "r"(sb + BAR_XFULL + xs * 8), "r"(br * 640 + tile * 64), "r"(IT_B(e) * 5), "r"(0)
                                    : "memory");
                            if (++xs == 5) xs = 0;
                        }
                    }
                }
            }
        } else if (warp == 2) {
            asm volatile("barrier.cluster.wait.aligned;" ::: "memory");
            const uint32_t epoch = next_epoch(2);
            if (cta == 0) g_ticket[(epoch + 1) & 1] = 0;
#pragma unroll 1
            for (int it = 0;; it++) {
                const uint32_t e = get_item_warp(sb, it, dl);
                if (e == 0) break;
                nb_sync<NB_ODONE, 288>();
                if (threadIdx.x == 64) {
                    const uint32_t bb = IT_BR(e) * 16 + IT_B(e);
                    if (IT_TYPE(e) != IT_QA) {
                        const bool wide = IT_TYPE(e) == IT_OP;
                        if (wide)
                            asm volatile("st.relaxed.gpu.global.u32 [%0], %1;" ::"l"(&g_flag[bb * 64 + 34 + IT_HALF(e)]),
                                         "r"(epoch * 64 + IT_H1(e))
                                         : "memory");
                        const int cc0 = IT_BR(e) * 640 + IT_HALF(e) * (wide ? 320 : 128);
                        uint32_t xs = wide ? 0 : (3 * (IT_H1(e) - IT_H0(e))) % 5;
#pragma unroll 1
                        for (int m = 0; m < (wide ? 5 : 2); m++) {
                            asm volatile("cp.async.bulk.tensor.5d.global.shared::cta.bulk_group [%0, {%2,%4,%4,%4,%3}], [%1];" ::"l"(&P.out),
                                         "r"(sb + OFF_R + xs * XS), "r"(cc0 + m * 64), "r"((int)IT_B(e) * 5), "r"(0)
                                         : "memory");
                            asm volatile("cp.async.bulk.commit_group;" ::: "memory");
                            if (++xs == 5) xs = 0;
                        }
                        if (wide) {
#define REL(N)                                                          \
    asm volatile("cp.async.bulk.wait_group.read %0;" ::"n"(4 - N) : "memory"); \
    asm volatile("mbarrier.arrive.shared::cta.b64 _, [%0], 8;" ::"r"(sb + BAR_XEMPTY + N * 8) : "memory");
                            REL(0) REL(1) REL(2) REL(3) REL(4)
#undef REL
                        }
                        if (IT_PART(e)) {
                            asm volatile("cp.async.bulk.wait_group 0;" ::: "memory");
                            asm volatile("fence.proxy.async;" ::: "memory");
                        }
                    }
                    if (IT_TYPE(e) == IT_QA || IT_PART(e)) {
                        unsigned int* f = &g_flag[bb * 64 + (IT_TYPE(e) == IT_QA ? IT_H0(e) : 32 + IT_HALF(e))];
                        asm volatile("st.release.gpu.global.u32 [%0], %1;" ::"l"(f), "r"(epoch) : "memory");
                    }
                }
                __syncwarp();
            }
            if (threadIdx.x == 64) asm volatile("cp.async.bulk.wait_group 0;" ::: "memory");
            __syncwarp();
            asm volatile("barrier.cluster.arrive.relaxed.aligned;\nbarrier.cluster.wait.aligned;" ::: "memory");
        } else {
            const uint32_t lane = threadIdx.x & 31, p = lane >> 2;
            const uint32_t epoch = next_epoch(3);
#pragma unroll 1
            for (int it = 0;; it++) {
                const uint32_t e = get_item_warp(sb, it, dl);
                if (e == 0) break;
                if (IT_TYPE(e) != IT_QA) continue;
                nb_sync<NB_QK, 160>();
                const uint32_t co = (((lane & 3) * 2) ^ p) << 4;
                const uint32_t ka = sb + OFF_RING + lds_u(sb + OFF_GM + 4) * SLOT + p * (9 * 128) + co;
                const uint32_t qa = sb + OFF_R + p * 128 + co;
                uint32_t acc = 0;
#pragma unroll 1
                for (int c = 0; c < 3; c++) {
                    if (c == 2) nb_sync<NB_L, 160>();
                    const uint4 k0 = lds_u4(ka + c * 8192), q0 = lds_u4(qa + c * XS);
                    acc = fma_bf2(k0.x, q0.x, fma_bf2(k0.y, q0.y, fma_bf2(k0.z, q0.z, fma_bf2(k0.w, q0.w, acc))));
                    const uint4 k1 = lds_u4((ka + c * 8192) ^ 16), q1 = lds_u4((qa + c * XS) ^ 16);
                    acc = fma_bf2(k1.x, q1.x, fma_bf2(k1.y, q1.y, fma_bf2(k1.z, q1.z, fma_bf2(k1.w, q1.w, acc))));
                }
                float d = __uint_as_float(acc << 16) + __uint_as_float(acc & 0xffff0000u);
                d += __shfl_xor_sync(0xffffffffu, d, 1);
                d += __shfl_xor_sync(0xffffffffu, d, 2);
                int key = __float_as_int(d);
                key ^= (key >> 31) & 0x7fffffff;
                key = __reduce_max_sync(0xffffffffu, key);
                key ^= (key >> 31) & 0x7fffffff;
                sts_f(sb + OFF_GM, fmaf(__int_as_float(key), SM_C, 16.f));
                nb_arrive<NB_REF, 160>();
                if (IT_DEP(e)) {
                    const uint32_t g = IT_DEP(e) - 1, need = epoch * 64 + (g & 31) + 1;
                    const unsigned int* cp = &g_flag[((g >> 5) * 16 + IT_B(e)) * 64 + 34 + (lane & 1)];
                    for (uint32_t n = 0;; n++) {
                        uint32_t v;
                        asm volatile("ld.acquire.gpu.global.u32 %0, [%1];" : "=r"(v) : "l"(cp) : "memory");
                        if (__all_sync(0xffffffffu, v - need < 64)) break;
                        if (n > 0x800000) __trap();
                        __nanosleep(500);
                    }
                }
                nb_sync<NB_L, 160>();
                bool bad = false;
#pragma unroll
                for (int c = 0; c < 5; c++) {
                    const uint32_t la = sb + OFF_LX + (c * 32 + lane) * 4;
                    const float v = (__uint_as_float(lds_u(la)) + __uint_as_float(lds_u(la + 640))) +
                                    (__uint_as_float(lds_u(la + 1280)) + __uint_as_float(lds_u(la + 1920)));
                    const float inv = __fdividef(1.f, v);
                    const uint32_t hi = pack_bf16(inv, 0.f), lo = pack_bf16(inv - __uint_as_float(hi << 16), 0.f);
                    const uint32_t ia = sb + OFF_LINV + c * 128 + ((lane >> 1) & 3) * 32 + (lane >> 3) * 8 + (lane & 1) * 2;
                    asm volatile("st.shared.u16 [%0], %1;\nst.shared.u16 [%0+4], %2;" ::"r"(ia), "h"((unsigned short)hi), "h"((unsigned short)lo) : "memory");
                    bad |= !(v >= 5.421010862e-20f && v <= 7.9228163e28f);
                }
                sts_u(sb + OFF_FB, __any_sync(0xffffffffu, bad));
                nb_arrive<NB_VOTE, 160>();
                nb_arrive<NB_VOTE + 1, 160>();
            }
        }
    } else {
        asm volatile("setmaxnreg.inc.sync.aligned.u32 240;");
        consumer(P, wgid - 1, sb, dl);
    }
}

typedef CUresult (*EncFn)(CUtensorMap*, CUtensorMapDataType, cuuint32_t, void*, const cuuint64_t*, const cuuint64_t*,
                          const cuuint32_t*, const cuuint32_t*, CUtensorMapInterleave, CUtensorMapSwizzle,
                          CUtensorMapL2promotion, CUtensorMapFloatOOBfill);

void make_map3(EncFn enc, CUtensorMap* m, void* p, uint64_t rows, uint64_t rowbytes, uint64_t nblk, uint32_t boxrows,
               uint32_t boxblk) {
    cuuint64_t dims[3] = {64, rows, nblk};
    cuuint64_t str[2] = {rowbytes, 128};
    cuuint32_t box[3] = {64, boxrows, boxblk};
    cuuint32_t es[3] = {1, 1, 1};
    enc(m, CU_TENSOR_MAP_DATA_TYPE_BFLOAT16, 3, p, dims, str, box, es, CU_TENSOR_MAP_INTERLEAVE_NONE,
        CU_TENSOR_MAP_SWIZZLE_128B, CU_TENSOR_MAP_L2_PROMOTION_NONE, CU_TENSOR_MAP_FLOAT_OOB_FILL_NONE);
}

constexpr int tune(const char*, int def) { return def; }

void build_schedule(Params& P) {
    const int mode = tune("MODE", 4), dmax = tune("DMAX", 24900), n0 = tune("N0", 11), odmax = tune("ODMAX", 0), d1 = tune("D1", 0);
    const int H0[8] = {19, 20, 21, 23, 23, 24, 25, 25}, P0[8] = {367, 340, 338, 331, 341, 339, 331, 334};
    const int ra = tune("RA", 10), ga = tune("GA", 17), rb = tune("RB", 11), g1 = tune("G1", 58);
    int dep[64];
    for (int g = 0, ns = 0, live = 0; g < 64; g++) {
        const bool fresh = mode < 3 || g >= g1 || live < (g < ga ? ra : rb);
        dep[g] = fresh ? 0 : g - live + 1;
        P.slot[g] = fresh ? ns++ : P.slot[g - live];
        live += fresh;
    }
    int H[8], pos[8], psum = 0;
    for (int b = 0; b < 8; b++) {
        const char nh[3] = {'H', (char)('0' + b), 0}, np[3] = {'P', (char)('0' + b), 0};
        H[b] = tune(nh, H0[b]);
        pos[b] = tune(np, P0[b]);
        psum += pos[b];
    }
    const int sk = tune("SK", 10), g0 = tune("G0", 20), g2 = tune("G2", 40);
    int ord[512], nxt[8] = {0, 0, 0, 0, 0, 0, 0, 0};
    for (int k = 0; k < 512; k++) {
        int best = -1;
        float bkey = 0.f;
        for (int b = 0; b < 8; b++) {
            const int g = nxt[b];
            if (g == 64) continue;
            const float w = g < g0 ? 0.f : g < 32 ? (g - g0) / (32.f - g0) : g < g2 ? 1.f : (64 - g) / (64.f - g2);
            const float key = g + w * sk * 0.1f * (pos[b] - psum / 8.f) / 8.f;
            if (best < 0 || key < bkey) best = b, bkey = key;
        }
        ord[k] = nxt[best]++ * 8 + best;
        const int d = dep[ord[k] >> 3];
        if (d > 32) {
            if (pos[best] > k) pos[best] = k;
            if (H[best] < d - 32) H[best] = d - 32;
        }
    }
    int u = 0;
    auto unit = [&]() {
        const int v = ord[u++];
        return mk_item(IT_QA, v >> 8, (v & 7) * 2, (v >> 3) & 31, P.slot[v >> 3], 0) | (dep[v >> 3] << 23);
    };
    int qa[NCL], nq = 0, op[NCL], no = 0;
    for (int c = 0; c < NCL; c++) {
        P.cl[c].delay = 0;
        for (int i = 0; i < NSTAT; i++) P.cl[c].items[i] = 0;
        if (mode >= 3 && c < 64 && (c & 3) == 3) op[no++] = c;
        else if (mode != 2 || (c & 3) == 0) qa[nq++] = c;
    }
    for (int t = 0; t < no; t++) {
        P.cl[op[t]].items[1] = mk_item(IT_OP, 0, t & ~1, 0, 32, t & 1);
        P.cl[op[t]].items[2] = IT_DYN;
        P.cl[op[t]].delay = tune("OD0", 0) + t * odmax / 16;
    }
    for (int k = 0; k < nq; k++) {
        const int c = qa[(k * 19) % nq];
        P.cl[c].items[1] = P.cl[c].items[2] = IT_DYN;
        P.cl[c].delay = k < n0 ? k * tune("J0", 0) : d1 + (dmax - d1) * (k + 1 - n0) / (nq - n0);
    }
    if (tune("OFIRST", 0))
        for (int t = 0; t < no; t++) P.cl[op[t]].items[0] = unit();
    for (int k = u; k < no + nq; k++) {
        int best = -1;
        for (int c = 0; c < NCL; c++)
            if (P.cl[c].items[1] && !P.cl[c].items[0] && (best < 0 || P.cl[c].delay < P.cl[best].delay)) best = c;
        P.cl[best].items[0] = unit();
    }
    int n = 0;
    const int uend = mode == 2 ? 8 * nq : 512;
    while (u < uend) {
        for (int b = 0; b < 8 && no; b++)
            if (pos[b] == u) {
                P.list[n++] = mk_item(IT_OP, 1, 2 * b, 0, H[b], 0, 1);
                P.list[n++] = mk_item(IT_OP, 1, 2 * b, 0, H[b], 1, 1);
            }
        P.list[n++] = unit();
    }
    for (int k = 0; no && k < 40; k++) P.list[n++] = mk_item(IT_ON, 1, k / 5 * 2, H[k / 5], 32, k % 5);
    P.nlist = n;
}

}

extern "C" void kernel_launch(void* const* d_in, const int* in_sizes, int n_in, void* d_out, int out_size) {
    static Params P;
    static bool init = false;
    if (!init) {
        EncFn enc = nullptr;
        cudaDriverEntryPointQueryResult qr;
        cudaGetDriverEntryPoint("cuTensorMapEncodeTiled", (void**)&enc, cudaEnableDefault, &qr);
        for (int i = 0; i < 2; i++) {
            P.px[i] = (const __nv_bfloat16*)d_in[5 * i + 0];
            P.pk[i] = (const __nv_bfloat16*)d_in[5 * i + 1];
            P.pv[i] = (const __nv_bfloat16*)d_in[5 * i + 2];
            P.pwq[i] = (const __nv_bfloat16*)d_in[5 * i + 3];
            make_map3(enc, &P.x[i], d_in[5 * i + 0], 2560, 1280, 10, 160, 1);
            make_map3(enc, &P.k[i], d_in[5 * i + 1], 16 * 32 * 512, 384, 3, 64, 3);
            make_map3(enc, &P.v[i], d_in[5 * i + 2], 16 * 32 * 512, 384, 3, 64, 3);
            make_map3(enc, &P.wq[i], d_in[5 * i + 3], 640, 12288, 96, 32, 3);
            make_map3(enc, &P.wo[i], d_in[5 * i + 4], 6144, 1280, 10, 16, 5);
            make_map3(enc, &P.won[i], d_in[5 * i + 4], 6144, 1280, 10, 32, 2);
        }
        cuuint64_t dims[5] = {1280, 2, 4, 4, 80};
        cuuint64_t str[4] = {2560, 8 * 2560, 2 * 2560, 32 * 2560};
        cuuint32_t box[5] = {64, 2, 4, 4, 5};
        cuuint32_t es[5] = {1, 1, 1, 1, 1};
        enc(&P.out, CU_TENSOR_MAP_DATA_TYPE_BFLOAT16, 5, d_out, dims, str, box, es, CU_TENSOR_MAP_INTERLEAVE_NONE,
            CU_TENSOR_MAP_SWIZZLE_128B, CU_TENSOR_MAP_L2_PROMOTION_NONE, CU_TENSOR_MAP_FLOAT_OOB_FILL_NONE);
        build_schedule(P);
        cudaFuncSetAttribute(fused_kernel, cudaFuncAttributeMaxDynamicSharedMemorySize, SMEM_LAUNCH);
        init = true;
    }
    fused_kernel<<<NCTA, 384, SMEM_LAUNCH>>>(P);
}
```

```cpp
#include <cuda_runtime.h>
#include <cuda.h>
#include <cuda_bf16.h>
#include <stdint.h>

namespace {

constexpr int NCTA = 132;
constexpr int NCL = NCTA / 2;
constexpr int MAXI = 16;
constexpr int NSTAT = 3;
constexpr uint32_t IT_DYN = 0xffffffffu;
constexpr int SLOT = 24576;
constexpr int NSLOT = 5;
constexpr int XS = 20480;
constexpr int OFF_R = 0;
constexpr int OFF_RING = 5 * XS;
constexpr int OFF_MISC = OFF_RING + NSLOT * SLOT;
constexpr int OFF_LX = OFF_MISC;
constexpr int OFF_LINV = OFF_LX + 2560;
constexpr int OFF_FB = OFF_LINV + 640;
constexpr int OFF_GM = OFF_FB + 16;
constexpr int OFF_BAR = OFF_GM + 16;
constexpr int BAR_RFULL = OFF_BAR;
constexpr int BAR_REMPTY = BAR_RFULL + 40;
constexpr int BAR_XFULL = BAR_REMPTY + 40;
constexpr int BAR_XEMPTY = BAR_XFULL + 40;
constexpr int BAR_PRDY = BAR_XEMPTY + 40;
constexpr int BAR_ITEM = BAR_PRDY + 40;
constexpr int OFF_ITEM = BAR_ITEM + MAXI * 8;
constexpr int SMEM_BYTES = OFF_ITEM + MAXI * 4;
static_assert(SMEM_BYTES <= 232448, "smem");

constexpr int NB_W = 1  , NB_PFULL = 3  , NB_VOTE = 5  , NB_Q2 = 7, NB_SDONE = 8, NB_PDONE = 9,
              NB_L = 10, NB_REF = 11, NB_ODONE = 12, NB_OPEND = 13, NB_LX = 14, NB_Q01 = 15, NB_QK = 0  ;

constexpr uint32_t IT_QA = 1, IT_OP = 2, IT_ON = 3;
__host__ __device__ constexpr uint32_t mk_item(uint32_t type, uint32_t br, uint32_t b, uint32_t h0, uint32_t h1, uint32_t half,
                                               uint32_t part = 0) {
    return type | (br << 2) | (b << 3) | (h0 << 7) | (h1 << 13) | (half << 19) | (part << 22);
}
#define IT_TYPE(e) ((e) & 3u)
#define IT_BR(e) (((e) >> 2) & 1u)
#define IT_B(e) (((e) >> 3) & 15u)
#define IT_H0(e) (((e) >> 7) & 63u)
#define IT_H1(e) (((e) >> 13) & 63u)
#define IT_HALF(e) (((e) >> 19) & 7u)
#define IT_PART(e) (((e) >> 22) & 1u)
#define IT_SLOT(e) IT_H1(e)
#define IT_DEP(e) (((e) >> 23) & 127u)

struct Params {
    CUtensorMap x[2], wq[2], k[2], v[2], wo[2], won[2], out;
    const __nv_bfloat16 *px[2], *pwq[2], *pk[2], *pv[2];
    struct alignas(16) { uint32_t delay, items[NSTAT]; } cl[NCL];
    uint32_t nlist;
    uint8_t slot[64];
    uint32_t list[512];
};

constexpr int OUNIT = 61440;
__device__ __align__(1024) unsigned char g_ostash[(size_t)1024 * OUNIT];
__device__ unsigned int g_flag[32 * 64];
__device__ __forceinline__ unsigned char* ostash(uint32_t slot, uint32_t b) { return g_ostash + (slot * 16 + b) * OUNIT; }
__device__ unsigned int g_epoch[NCTA * 4];
__device__ unsigned int g_ticket[2];

constexpr int SMEM_LAUNCH = SMEM_BYTES;
#define TS(role, idx)
#define TS_ITEM(e)
#define TS_DUMP(role)
#define TSD(role, idx)

#define POL_W 2
#define POL_X 2
#define POL_O 2
template <int M>
__device__ __forceinline__ uint64_t mkpol() {
    uint64_t p;
    if (M == 0) asm volatile("createpolicy.fractional.L2::evict_normal.b64 %0, 1.0;" : "=l"(p));
    if (M == 1) asm volatile("createpolicy.fractional.L2::evict_first.b64 %0, 1.0;" : "=l"(p));
    if (M == 2) asm volatile("createpolicy.fractional.L2::evict_unchanged.b64 %0, 1.0;" : "=l"(p));
    if (M == 3) asm volatile("createpolicy.fractional.L2::evict_normal.L2::evict_unchanged.b64 %0, 0.25;" : "=l"(p));
    return p;
}
#define STSM_W 1
#define SIGJ 0
#define STLAG 1
#define LASTORD 0
#define XLATE 2
#define PV0FIRST 1
#define QST0 1
#define QST1 2
#define QHOLD 8
constexpr float SM_C = 0.07216878364870322f * 1.4426950408889634f;

__device__ __forceinline__ uint32_t next_epoch(int warp) {
    unsigned int* p = &g_epoch[blockIdx.x * 4 + warp];
    const uint32_t e = __ldcg(p) + 1;
    *p = e;
    return e;
}

__device__ __forceinline__ uint32_t tid_now() {
    uint32_t t;
    asm volatile("mov.u32 %0, %%tid.x;" : "=r"(t));
    return t;
}
__device__ __forceinline__ void mbar_init(uint32_t a, uint32_t c) {
    asm volatile("mbarrier.init.shared::cta.b64 [%0], %1;" ::"r"(a), "r"(c) : "memory");
}
__device__ __forceinline__ void mbar_expect(uint32_t a, uint32_t b) {
    asm volatile("mbarrier.arrive.expect_tx.shared::cta.b64 _, [%0], %1;" ::"r"(a), "r"(b) : "memory");
}
template <int CNT = 1>
__device__ __forceinline__ void mbar_arrive_warp(uint32_t a) {
    if (CNT == 1)
        asm volatile("{\n.reg .pred p;\nelect.sync _|p, 0xffffffff;\n@p mbarrier.arrive.shared::cta.b64 _, [%0];\n}" ::"r"(a) : "memory");
    else
        asm volatile(
            "{\n.reg .pred p;\nelect.sync _|p, 0xffffffff;\n@p mbarrier.arrive.shared::cta.b64 _, [%0];\n"
            "@p mbarrier.arrive.shared::cta.b64 _, [%0];\n}" ::"r"(a)
            : "memory");
}
template <int CNT = 1>
__device__ __forceinline__ void mbar_arrive_warp_if(uint32_t a, bool cond) {
    if (CNT == 1)
        asm volatile(
            "{\n.reg .pred p, c;\nelect.sync _|p, 0xffffffff;\nsetp.ne.and.u32 c, %1, 0, p;\n"
            "@c mbarrier.arrive.shared::cta.b64 _, [%0];\n}" ::"r"(a), "r"((uint32_t)cond)
            : "memory");
    else
        asm volatile(
            "{\n.reg .pred p, c;\nelect.sync _|p, 0xffffffff;\nsetp.ne.and.u32 c, %1, 0, p;\n"
            "@c mbarrier.arrive.shared::cta.b64 _, [%0];\n@c mbarrier.arrive.shared::cta.b64 _, [%0];\n}" ::"r"(a), "r"((uint32_t)cond)
            : "memory");
}
__device__ __forceinline__ uint32_t deadline() {
    uint32_t c;
    asm volatile("mov.u32 %0, %%clock_hi;" : "=r"(c));
    return c + 4;
}
__device__ __forceinline__ void mbar_wait(uint32_t a, uint32_t ph, uint32_t dl) {
    asm volatile(
        "{\n.reg .pred p;\n.reg .u32 m;\n"
        "LOOP:\n"
        "mbarrier.try_wait.parity.shared::cta.b64 p, [%0], %1;\n"
        "@p bra DONE;\n"
        "mov.u32 m, %%clock_hi;\n"
        "setp.ne.u32 p, m, %2;\n"
        "@p bra LOOP;\n"
        "trap;\n"
        "DONE:\n}" ::"r"(a), "r"(ph), "r"(dl)
        : "memory");
}
template <int ID, int CNT>
__device__ __forceinline__ void nb_sync() { asm volatile("bar.sync %0, %1;" ::"n"(ID), "n"(CNT) : "memory"); }
template <int ID, int CNT>
__device__ __forceinline__ void nb_arrive() { asm volatile("bar.arrive %0, %1;" ::"n"(ID), "n"(CNT) : "memory"); }
__device__ __forceinline__ void fence_async_smem() { asm volatile("fence.proxy.async.shared::cta;" ::: "memory"); }

__device__ __forceinline__ void tma3(uint32_t dst, const CUtensorMap* m, int c1, int c2, uint32_t bar, uint64_t pol) {
    asm volatile(
        "cp.async.bulk.tensor.3d.shared::cluster.global.mbarrier::complete_tx::bytes.L2::cache_hint [%0], [%1, {%3,%4,%5}], [%2], %6;" ::"r"(dst),
        "l"(m), "r"(bar), "r"(0), "r"(c1), "r"(c2), "l"(pol)
        : "memory");
}
__device__ __forceinline__ void tma3_mc(uint32_t dst, const CUtensorMap* m, int c1, int c2, uint32_t bar, uint64_t pol) {
    asm volatile(
        "cp.async.bulk.tensor.3d.shared::cluster.global.mbarrier::complete_tx::bytes.multicast::cluster.L2::cache_hint"
        " [%0], [%1, {%3,%4,%5}], [%2], %6, %7;" ::"r"(dst),
        "l"(m), "r"(bar), "r"(0), "r"(c1), "r"(c2), "h"((unsigned short)3), "l"(pol)
        : "memory");
}
__device__ __forceinline__ void bulk_load(uint32_t dst, const void* src, uint32_t bytes, uint32_t bar, uint64_t pol) {
    asm volatile("cp.async.bulk.shared::cluster.global.mbarrier::complete_tx::bytes.L2::cache_hint [%0], [%1], %2, [%3], %4;" ::"r"(dst),
                 "l"(src), "r"(bytes), "r"(bar), "l"(pol)
                 : "memory");
}
__device__ __forceinline__ void wg_fence() { asm volatile("wgmma.fence.sync.aligned;" ::: "memory"); }
__device__ __forceinline__ void wg_commit() { asm volatile("wgmma.commit_group.sync.aligned;" ::: "memory"); }
template <int N>
__device__ __forceinline__ void wg_wait() { asm volatile("wgmma.wait_group.sync.aligned %0;" ::"n"(N) : "memory"); }

#define RW80(c, d) c(d[0]), c(d[1]), c(d[2]), c(d[3]), c(d[4]), c(d[5]), c(d[6]), c(d[7]), c(d[8]), c(d[9]), c(d[10]), c(d[11]), c(d[12]), c(d[13]), c(d[14]), c(d[15]), c(d[16]), c(d[17]), c(d[18]), c(d[19]), c(d[20]), c(d[21]), c(d[22]), c(d[23]), c(d[24]), c(d[25]), c(d[26]), c(d[27]), c(d[28]), c(d[29]), c(d[30]), c(d[31]), c(d[32]), c(d[33]), c(d[34]), c(d[35]), c(d[36]), c(d[37]), c(d[38]), c(d[39]), c(d[40]), c(d[41]), c(d[42]), c(d[43]), c(d[44]), c(d[45]), c(d[46]), c(d[47]), c(d[48]), c(d[49]), c(d[50]), c(d[51]), c(d[52]), c(d[53]), c(d[54]), c(d[55]), c(d[56]), c(d[57]), c(d[58]), c(d[59]), c(d[60]), c(d[61]), c(d[62]), c(d[63]), c(d[64]), c(d[65]), c(d[66]), c(d[67]), c(d[68]), c(d[69]), c(d[70]), c(d[71]), c(d[72]), c(d[73]), c(d[74]), c(d[75]), c(d[76]), c(d[77]), c(d[78]), c(d[79])
#define RW48(c, d) c(d[0]), c(d[1]), c(d[2]), c(d[3]), c(d[4]), c(d[5]), c(d[6]), c(d[7]), c(d[8]), c(d[9]), c(d[10]), c(d[11]), c(d[12]), c(d[13]), c(d[14]), c(d[15]), c(d[16]), c(d[17]), c(d[18]), c(d[19]), c(d[20]), c(d[21]), c(d[22]), c(d[23]), c(d[24]), c(d[25]), c(d[26]), c(d[27]), c(d[28]), c(d[29]), c(d[30]), c(d[31]), c(d[32]), c(d[33]), c(d[34]), c(d[35]), c(d[36]), c(d[37]), c(d[38]), c(d[39]), c(d[40]), c(d[41]), c(d[42]), c(d[43]), c(d[44]), c(d[45]), c(d[46]), c(d[47])
#define RW32(c, d) c(d[0]), c(d[1]), c(d[2]), c(d[3]), c(d[4]), c(d[5]), c(d[6]), c(d[7]), c(d[8]), c(d[9]), c(d[10]), c(d[11]), c(d[12]), c(d[13]), c(d[14]), c(d[15]), c(d[16]), c(d[17]), c(d[18]), c(d[19]), c(d[20]), c(d[21]), c(d[22]), c(d[23]), c(d[24]), c(d[25]), c(d[26]), c(d[27]), c(d[28]), c(d[29]), c(d[30]), c(d[31])

__device__ __forceinline__ void reg_fence(float (&d)[80]) { asm volatile("" : RW80("+f", d)::"memory"); }
__device__ __forceinline__ void reg_fence(float (&d)[48]) { asm volatile("" : RW48("+f", d)::"memory"); }
__device__ __forceinline__ void reg_fence(float (&d)[32]) { asm volatile("" : RW32("+f", d)::"memory"); }

template <int NR>
__device__ __forceinline__ void zero(float (&d)[NR]) {
#pragma unroll
    for (int i = 0; i < NR; i++) d[i] = 0.f;
}

constexpr uint32_t HI_SW128 = (1024u >> 4) | (1u << 30);
constexpr uint32_t HI_OST = (2560u >> 4) | (2u << 30);
constexpr uint32_t LO_LBO1 = (1u << 16);
constexpr uint32_t LO_OST = ((512u >> 4) << 16);

template <int TA, int TB, uint32_t HIB, int ACC>
__device__ __forceinline__ void wgmma(float (&d)[80], uint32_t loA, uint32_t loB) {
#define WG_ASM(SD)                                                          \
    "{\n.reg .b64 da, db;\nmov.b64 da, {%80, %82};\nmov.b64 db, {%81, %83};\n" \
    "wgmma.mma_async.sync.aligned.m64n160k16.f32.bf16.bf16 "               \
    "{%0,%1,%2,%3,%4,%5,%6,%7,%8,%9,%10,%11,%12,%13,%14,%15,%16,%17,%18,%19,%20,%21,%22,%23,%24,%25,%26,%27,%28,%29,%30,%31,%32,%33,%34,%35,%36,%37,%38,%39,%40,%41,%42,%43,%44,%45,%46,%47,%48,%49,%50,%51,%52,%53,%54,%55,%56,%57,%58,%59,%60,%61,%62,%63,%64,%65,%66,%67,%68,%69,%70,%71,%72,%73,%74,%75,%76,%77,%78,%79}, da, db, " SD ", 1, 1, %84, %85;\n}"
    if constexpr (ACC == 2)
        asm volatile(WG_ASM("0") : RW80("+f", d) : "r"(loA), "r"(loB), "n"(HI_SW128), "n"(HIB), "n"(TA), "n"(TB));
    else if constexpr (ACC == 1)
        asm volatile(WG_ASM("1") : RW80("+f", d) : "r"(loA), "r"(loB), "n"(HI_SW128), "n"(HIB), "n"(TA), "n"(TB));
    else
        asm volatile(WG_ASM("0") : RW80("=f", d) : "r"(loA), "r"(loB), "n"(HI_SW128), "n"(HIB), "n"(TA), "n"(TB));
#undef WG_ASM
}
template <int TA, int TB, uint32_t HIB, int ACC>
__device__ __forceinline__ void wgmma(float (&d)[48], uint32_t loA, uint32_t loB) {
#define WG_ASM(SD)                                                          \
    "{\n.reg .b64 da, db;\nmov.b64 da, {%48, %50};\nmov.b64 db, {%49, %51};\n" \
    "wgmma.mma_async.sync.aligned.m64n96k16.f32.bf16.bf16 "               \
    "{%0,%1,%2,%3,%4,%5,%6,%7,%8,%9,%10,%11,%12,%13,%14,%15,%16,%17,%18,%19,%20,%21,%22,%23,%24,%25,%26,%27,%28,%29,%30,%31,%32,%33,%34,%35,%36,%37,%38,%39,%40,%41,%42,%43,%44,%45,%46,%47}, da, db, " SD ", 1, 1, %52, %53;\n}"
    if constexpr (ACC == 1)
        asm volatile(WG_ASM("1") : RW48("+f", d) : "r"(loA), "r"(loB), "n"(HI_SW128), "n"(HIB), "n"(TA), "n"(TB));
    else
        asm volatile(WG_ASM("0") : RW48("=f", d) : "r"(loA), "r"(loB), "n"(HI_SW128), "n"(HIB), "n"(TA), "n"(TB));
#undef WG_ASM
}
template <int TA, int TB, uint32_t HIB, int ACC>
__device__ __forceinline__ void wgmma(float (&d)[32], uint32_t loA, uint32_t loB) {
#define WG_ASM(SD)                                                          \
    "{\n.reg .b64 da, db;\nmov.b64 da, {%32, %34};\nmov.b64 db, {%33, %35};\n" \
    "wgmma.mma_async.sync.aligned.m64n64k16.f32.bf16.bf16 "               \
    "{%0,%1,%2,%3,%4,%5,%6,%7,%8,%9,%10,%11,%12,%13,%14,%15,%16,%17,%18,%19,%20,%21,%22,%23,%24,%25,%26,%27,%28,%29,%30,%31}, da, db, " SD ", 1, 1, %36, %37;\n}"
    if constexpr (ACC == 1)
        asm volatile(WG_ASM("1") : RW32("+f", d) : "r"(loA), "r"(loB), "n"(HI_SW128), "n"(HIB), "n"(TA), "n"(TB));
    else
        asm volatile(WG_ASM("0") : RW32("=f", d) : "r"(loA), "r"(loB), "n"(HI_SW128), "n"(HIB), "n"(TA), "n"(TB));
#undef WG_ASM
}

__device__ __forceinline__ uint32_t pack_bf16(float lo, float hi) {
    uint32_t r;
    asm("cvt.rn.bf16x2.f32 %0, %1, %2;" : "=r"(r) : "f"(hi), "f"(lo));
    return r;
}
__device__ __forceinline__ float ex2(float x) {
    float r;
    asm("ex2.approx.ftz.f32 %0, %1;" : "=f"(r) : "f"(x));
    return r;
}
__device__ __forceinline__ void stsm4t(uint32_t a, uint32_t r0, uint32_t r1, uint32_t r2, uint32_t r3) {
    asm volatile("stmatrix.sync.aligned.m8n8.x4.trans.shared.b16 [%0], {%1,%2,%3,%4};" ::"r"(a), "r"(r0), "r"(r1), "r"(r2), "r"(r3)
                 : "memory");
}
__device__ __forceinline__ uint32_t lds_u(uint32_t a) {
    uint32_t v;
    asm volatile("ld.shared.u32 %0, [%1];" : "=r"(v) : "r"(a) : "memory");
    return v;
}
__device__ __forceinline__ uint4 lds_u4(uint32_t a) {
    uint4 v;
    asm volatile("ld.shared.v4.u32 {%0,%1,%2,%3}, [%4];" : "=r"(v.x), "=r"(v.y), "=r"(v.z), "=r"(v.w) : "r"(a) : "memory");
    return v;
}
__device__ __forceinline__ float2 lds_f2(uint32_t a) {
    float2 v;
    asm volatile("ld.shared.v2.f32 {%0,%1}, [%2];" : "=f"(v.x), "=f"(v.y) : "r"(a) : "memory");
    return v;
}
__device__ __forceinline__ void sts_f(uint32_t a, float v) { asm volatile("st.shared.f32 [%0], %1;" ::"r"(a), "f"(v) : "memory"); }
__device__ __forceinline__ void sts_u(uint32_t a, uint32_t v) { asm volatile("st.shared.u32 [%0], %1;" ::"r"(a), "r"(v) : "memory"); }
__device__ __forceinline__ void sts_f2(uint32_t a, float x, float y) {
    asm volatile("st.shared.v2.f32 [%0], {%1,%2};" ::"r"(a), "f"(x), "f"(y) : "memory");
}

template <bool ADD = false, bool SIG = false, int NR>
__device__ __forceinline__ void store_tile_t(const float (&d)[NR], uint32_t addr) {
    uint32_t p[NR / 2];
    if (ADD) {
#pragma unroll
        for (int j = 0; j < NR / 8; j++)
            asm volatile("ldmatrix.sync.aligned.m8n8.x4.trans.shared.b16 {%0,%1,%2,%3}, [%4];"
                         : "=r"(p[4 * j]), "=r"(p[4 * j + 1]), "=r"(p[4 * j + 2]), "=r"(p[4 * j + 3])
                         : "r"(addr + j * 2048)
                         : "memory");
    }
#pragma unroll
    for (int k = 0; k < NR / 2; k++)
        p[k] = ADD ? pack_bf16(d[2 * k] + __uint_as_float(p[k] << 16), d[2 * k + 1] + __uint_as_float(p[k] & 0xffff0000u))
                   : pack_bf16(d[2 * k], d[2 * k + 1]);
#pragma unroll
    for (int j = 0; j < NR / 8; j++) {
        stsm4t(addr + j * 2048, p[4 * j], p[4 * j + 1], p[4 * j + 2], p[4 * j + 3]);
        if (SIG && j == SIGJ) nb_arrive<NB_L, 160>();
    }
}

struct TrueT { static constexpr bool value = true; };
struct FalseT { static constexpr bool value = false; };

template <int V>
struct IntT { static constexpr int value = V; };

__device__ __forceinline__ uint32_t get_item(uint32_t sb, int it, uint32_t dl) {
    mbar_wait(sb + BAR_ITEM + it * 8, 0, dl);
    return lds_u(sb + OFF_ITEM + it * 4);
}
__device__ __forceinline__ uint32_t get_item_warp(uint32_t sb, int it, uint32_t dl) {
    return __shfl_sync(0xffffffffu, get_item(sb, it, dl), 0);
}

struct Ring {
    uint32_t slot, ph, dl;
    __device__ __forceinline__ void adv(uint32_t k) {
        slot += k;
        if (slot >= NSLOT) { slot -= NSLOT; ph ^= 1; }
    }
};

template <int K>
__device__ __forceinline__ void qk_step(float (&s)[80], uint32_t loK, uint32_t loQ) {
    wgmma<0, 0, HI_SW128, K != 0>(s, loK + (K >> 2) * (8192 >> 4) + (K & 3) * 2, loQ + (K >> 2) * (XS >> 4) + (K & 3) * 2);
}
template <int K0, int K1>
__device__ __forceinline__ void qk_steps(float (&s)[80], uint32_t loK, uint32_t loQ) {
    if constexpr (K0 < K1) {
        qk_step<K0>(s, loK, loQ);
        qk_steps<K0 + 1, K1>(s, loK, loQ);
    }
}
__device__ __forceinline__ uint32_t add_bf2(uint32_t a, uint32_t b) {
    uint32_t r;
    asm("add.rn.bf16x2 %0, %1, %2;" : "=r"(r) : "r"(a), "r"(b));
    return r;
}
__device__ __forceinline__ uint32_t fma_bf2(uint32_t a, uint32_t b, uint32_t c) {
    uint32_t r;
    asm("fma.rn.bf16x2 %0, %1, %2, %3;" : "=r"(r) : "r"(a), "r"(b), "r"(c));
    return r;
}
template <int J>
__device__ __forceinline__ void exp_block(const float (&s)[80], uint32_t (&k)[40], uint32_t pa, float mref) {
    if constexpr (J < 10) {
#pragma unroll
        for (int i = 4 * J; i < 4 * J + 4; i++)
            k[i] = pack_bf16(ex2(fmaf(s[2 * i], SM_C, -mref)), ex2(fmaf(s[2 * i + 1], SM_C, -mref)));
#pragma unroll
        for (int i = 0; i < 4; i++)
            asm volatile("stmatrix.sync.aligned.m8n8.x1.trans.shared.b16 [%0], {%1};" ::"r"(((i & 1) ? pa ^ 16 : pa) + J * 2048 + (i >> 1) * 1024),
                         "r"(k[4 * J + i])
                         : "memory");
        exp_block<J + 1>(s, k, pa, mref);
    }
}
__device__ __forceinline__ void sum_block(const uint32_t (&k)[40], float (&l)[10], uint32_t lane) {
    const bool b4 = lane & 16, b3 = lane & 8;
    uint32_t ps[20], t[10];
#pragma unroll
    for (int j = 0; j < 20; j++) ps[j] = add_bf2(k[2 * j], k[2 * j + 1]);
#pragma unroll
    for (int j = 0; j < 10; j++)
        t[j] = add_bf2(b4 ? ps[2 * j + 1] : ps[2 * j], __shfl_xor_sync(0xffffffffu, b4 ? ps[2 * j] : ps[2 * j + 1], 16));
#pragma unroll
    for (int i = 0; i < 5; i++) {
        const uint32_t a = b3 ? t[i + 5] : t[i], b = __shfl_xor_sync(0xffffffffu, b3 ? t[i] : t[i + 5], 8);
        l[2 * i] += __uint_as_float(a << 16) + __uint_as_float(b << 16);
        l[2 * i + 1] += __uint_as_float(a & 0xffff0000u) + __uint_as_float(b & 0xffff0000u);
    }
}
template <bool ADD>
__device__ __forceinline__ void sum_store(const float (&l)[10], uint32_t lane, uint32_t lxa) {
    const bool b2 = lane & 4;
    float t[5];
#pragma unroll
    for (int i = 0; i < 5; i++) t[i] = ADD ? __uint_as_float(lds_u(lxa + i * 64)) : 0.f;
#pragma unroll
    for (int i = 0; i < 5; i++)
        sts_f(lxa + i * 64, t[i] + (b2 ? l[2 * i + 1] : l[2 * i]) + __shfl_xor_sync(0xffffffffu, b2 ? l[2 * i] : l[2 * i + 1], 4));
}

__device__ __forceinline__ void fallback_unit(const Params& P, uint32_t e, uint32_t tid) {
    const uint32_t lane = tid & 31, br = IT_BR(e), b = IT_B(e), h = IT_H0(e);
    const __nv_bfloat162* wq = (const __nv_bfloat162*)(P.pwq[br] + h * 192) + lane;
    const __nv_bfloat162* kp = (const __nv_bfloat162*)(P.pk[br] + (size_t)(b * 32 + h) * 512 * 192) + lane;
    const __nv_bfloat162* vp = (const __nv_bfloat162*)(P.pv[br] + (size_t)(b * 32 + h) * 512 * 192) + lane;
#pragma unroll 1
    for (uint32_t qi = 0; qi < 40; qi++) {
        const uint32_t q = 4 * qi + (tid >> 5);
        const __nv_bfloat16* xr = P.px[br] + (size_t)(b * 160 + q) * 640;
        float a[6] = {0.f, 0.f, 0.f, 0.f, 0.f, 0.f};
#pragma unroll 2
        for (int k = 0; k < 640; k++) {
            const float xv = __bfloat162float(xr[k]);
#pragma unroll
            for (int i = 0; i < 3; i++) {
                const float2 wv = __bfloat1622float2(wq[(size_t)k * 3072 + i * 32]);
                a[2 * i] = fmaf(xv, wv.x, a[2 * i]);
                a[2 * i + 1] = fmaf(xv, wv.y, a[2 * i + 1]);
            }
        }
#pragma unroll
        for (int i = 0; i < 6; i++) a[i] = __bfloat162float(__float2bfloat16(a[i]));
        auto score = [&](int key) {
            float d = 0.f;
#pragma unroll
            for (int i = 0; i < 3; i++) {
                const float2 kv = __bfloat1622float2(kp[key * 96 + i * 32]);
                d = fmaf(a[2 * i], kv.x, fmaf(a[2 * i + 1], kv.y, d));
            }
#pragma unroll
            for (int o = 16; o > 0; o >>= 1) d += __shfl_xor_sync(0xffffffffu, d, o);
            return d;
        };
        float m = -INFINITY, o[6] = {0.f, 0.f, 0.f, 0.f, 0.f, 0.f}, sum = 0.f;
#pragma unroll 1
        for (int n = 0; n < 1024; n++) {
            const int key = n & 511;
            const float d = score(key);
            if (n < 512) {
                m = fmaxf(m, d);
            } else {
                const float p = ex2((d - m) * SM_C);
                sum += p;
#pragma unroll
                for (int i = 0; i < 3; i++) {
                    const float2 vv = __bfloat1622float2(vp[key * 96 + i * 32]);
                    o[2 * i] = fmaf(p, vv.x, o[2 * i]);
                    o[2 * i + 1] = fmaf(p, vv.y, o[2 * i + 1]);
                }
            }
        }
        const float inv = __fdividef(1.f, sum);
        __nv_bfloat16* op = (__nv_bfloat16*)ostash(IT_SLOT(e), b) + (q >> 5) * 256 + 2 * ((q & 31) >> 3) + (q & 1);
#pragma unroll
        for (int i = 0; i < 6; i++) {
            const uint32_t d = (i >> 1) * 64 + 2 * lane + (i & 1);
            op[(d >> 3) * 1280 + (d & 7) * 32 + ((((q & 7) >> 1) ^ ((d & 7) >> 1)) << 3)] = __float2bfloat16(o[i] * inv);
        }
    }
}

template <int W>
struct PendO {
    static constexpr int N = W == 0 ? 56 : 64;
    uint32_t v[N];
    unsigned char* gp;
    static __device__ __forceinline__ uint32_t toff() {
        const uint32_t t = tid_now();
        return ((t >> 5) & 3) * 5120 + ((t >> 2) & 7) * 64 + (((t ^ (t >> 3)) & 3) << 4);
    }
    uint32_t pend, sig, bad;
    static __device__ __forceinline__ void scale(uint32_t& x, uint32_t hi, uint32_t lo) {
        asm("{\n.reg .b32 t;\nmul.rn.bf16x2 t, %0, %2;\nfma.rn.bf16x2 %0, %0, %1, t;\n}" : "+r"(x) : "r"(hi), "r"(lo));
    }
    template <int I, int OFF>
    __device__ __forceinline__ void put() {
        asm volatile("{\n.reg .pred p;\nsetp.ne.u32 p, %6, 0;\n@p st.global.v4.b32 [%0+%5], {%1,%2,%3,%4};\n}" ::"l"(gp), "r"(v[I]),
                     "r"(v[I + 1]), "r"(v[I + 2]), "r"(v[I + 3]), "n"(OFF), "r"(pend)
                     : "memory");
    }
    __device__ __forceinline__ void verdict(uint32_t sb) {
        if (sig) {
            nb_sync<NB_VOTE + W, 160>();
            bad = __any_sync(0xffffffffu, lds_u(sb + OFF_FB) != 0);
            pend = !bad;
        }
    }
    template <int G, int H>
    __device__ __forceinline__ void half(uint32_t sb) {
        constexpr bool T2 = W == 0 ? G >= 3 : G < 3;
        constexpr int B = T2 ? 40 + 8 * (W == 0 ? G - 3 : G) : 0;
        const uint4 a = lds_u4(sb + OFF_LINV + G * 128 + H * 16 + (threadIdx.x & 3) * 32);
#pragma unroll
        for (int i = 2 * H; i < 8; i += 4) {
            scale(v[8 * G + i], a.x, a.y);
            scale(v[8 * G + i + 1], a.z, a.w);
            if (T2) {
                scale(v[B + i], a.x, a.y);
                scale(v[B + i + 1], a.z, a.w);
            }
        }
        if (H == 1) {
            put<8 * G, W * XS + G * 512>();
            put<8 * G + 4, W * XS + G * 512 + 2560>();
            if (T2) {
                put<B, 2 * XS + G * 512>();
                put<B + 4, 2 * XS + G * 512 + 2560>();
            }
            if (G == 4 && pend) nb_arrive<NB_ODONE, 288>();
        }
    }
    template <int G>
    __device__ __forceinline__ void step(uint32_t sb) {
        half<G, 0>(sb);
        half<G, 1>(sb);
    }
    __device__ __forceinline__ void clear() {
#pragma unroll
        for (int i = 0; i < N; i++) v[i] = 0;
        gp = nullptr;
        pend = 0;
        sig = 0;
        bad = 0;
    }
};

__device__ __forceinline__ uint32_t stsm_off() {
    const uint32_t tid = tid_now(), lane = tid & 31;
    return (lane >> 4) * 1024 + (lane & 7) * 128 + (((((tid >> 4) & 6) + ((lane >> 3) & 1)) ^ (lane & 7)) << 4);
}
__device__ __forceinline__ void q_ahead(float (&q0)[80], uint32_t sb, const Ring& rn, uint32_t phm, bool valid) {
    if (valid) {
        mbar_wait(sb + BAR_RFULL + rn.slot * 8, rn.ph, rn.dl);
        mbar_wait(sb + BAR_XFULL, phm & 1, rn.dl);
    }
    const uint32_t a = ((((sb + OFF_RING) & 0x3ffff) >> 4) | LO_LBO1) + rn.slot * (SLOT >> 4);
    const uint32_t b = (((sb + OFF_R) & 0x3ffff) >> 4) | LO_LBO1;
    wg_fence();
    wgmma<1, 0, HI_SW128, false>(q0, a, b);
#pragma unroll
    for (int k = 1; k < 4; k++) wgmma<1, 0, HI_SW128, true>(q0, a + (k >> 1) * 768 + (k & 1) * 128, b + k * 2);
    wg_commit();
}
template <int W, int KK>
__device__ __forceinline__ void qproj(float (&q0)[80], float (&q1)[80], uint32_t sb, Ring& r, uint32_t pslot, uint32_t phm,
                                      PendO<W>& po) {
    const uint32_t loR = (((sb + OFF_R) & 0x3ffff) >> 4) | LO_LBO1;
    const uint32_t loRing = (((sb + OFF_RING) & 0x3ffff) >> 4) | LO_LBO1;
    auto ready = [&](int k) {
        mbar_wait(sb + BAR_RFULL + r.slot * 8, r.ph, r.dl);
        mbar_wait(sb + BAR_XFULL + (k % 5) * 8, ((phm >> (k % 5)) ^ (k / 5)) & 1, r.dl);
    };
    auto release = [&]() {
        if (KK > 0) {
            wg_wait<1>();
            mbar_arrive_warp(sb + BAR_REMPTY + pslot * 8);
            if (KK <= 5) mbar_arrive_warp(sb + (BAR_XEMPTY + (KK - 1) * 8));
        }
    };
    if (KK == 0 && W == 1) ready(0);
    if (W == 1 && KK == QHOLD) {
        if (QHOLD == 7) {
            wg_wait<0>();
            nb_arrive<NB_PDONE, 256>();
        }
        nb_sync<NB_SDONE, 256>();
    }
    const uint32_t a = loRing + r.slot * (SLOT >> 4) + (W == 0 ? 0 : 512), b = loR + (KK % 5) * (XS >> 4);
    wg_fence();
    constexpr bool T0 = W == 1 || KK > 0;
    if (T0) wgmma<1, 0, HI_SW128, KK != 0>(q0, a, b);
    if (W == 0) wgmma<1, 0, HI_SW128, KK != 0 ? 1 : 2>(q1, a + 256, b);
#pragma unroll
    for (int k = 1; k < 4; k++) {
        if (T0) wgmma<1, 0, HI_SW128, true>(q0, a + (k >> 1) * 768 + (k & 1) * 128, b + k * 2);
        if (W == 0) wgmma<1, 0, HI_SW128, true>(q1, a + 256 + (k >> 1) * 768 + (k & 1) * 128, b + k * 2);
    }
    wg_commit();
    const uint32_t cslot = r.slot;
    r.adv(1);
    if (W == 0 || KK < QHOLD) release();
    if (KK == QST0) {
        po.verdict(sb);
        po.template half<0, 0>(sb);
    }
    if (KK < 9) ready(KK + 1);
    if (W == 1 && KK >= QHOLD) release();
    if (W == 1 && KK == 7 && QHOLD > 7) nb_arrive<NB_PDONE, 256>();
    if (KK == QST0) po.template half<0, 1>(sb);
    if constexpr (KK > QST0 && KK < QST0 + 5) po.template step<KK - QST0>(sb);
    if constexpr (KK < (W == 0 ? 7 : 9)) {
        qproj<W, KK + 1>(q0, q1, sb, r, cslot, phm, po);
    } else if constexpr (W == 1) {
        const uint32_t sta = sb + OFF_R + 2 * XS + stsm_off();
        wg_wait<0>();
        reg_fence(q0);
        store_tile_t<false, true>(q0, sta);
        mbar_arrive_warp(sb + BAR_REMPTY + cslot * 8);
    } else {
        const uint32_t s8 = r.slot, a8 = loRing + s8 * (SLOT >> 4);
        wg_fence();
#pragma unroll
        for (int k = 0; k < 4; k++) wgmma<1, 0, HI_SW128, true>(q0, a8 + (k >> 1) * 768 + (k & 1) * 128, loR + 3 * (XS >> 4) + k * 2);
        r.adv(1);
        ready(9);
        const uint32_t s9 = r.slot, a9 = loRing + s9 * (SLOT >> 4);
        r.adv(1);
        wg_fence();
#pragma unroll
        for (int k = 0; k < 4; k++) wgmma<1, 0, HI_SW128, true>(q0, a9 + (k >> 1) * 768 + (k & 1) * 128, loR + 4 * (XS >> 4) + k * 2);
        wg_commit();
        wg_wait<1>();
        mbar_arrive_warp(sb + BAR_REMPTY + cslot * 8);
        wg_fence();
#pragma unroll
        for (int k = 0; k < 8; k++)
            wgmma<1, 0, HI_SW128, true>(q1, (k < 4 ? a8 : a9) + 256 + ((k >> 1) & 1) * 768 + (k & 1) * 128,
                                        loR + (3 + (k >> 2)) * (XS >> 4) + (k & 3) * 2);
        wg_commit();
        nb_arrive<NB_SDONE, 256>();
        nb_sync<NB_PDONE, 256>();
        wg_wait<1>();
        reg_fence(q0);
        const uint32_t sta = sb + OFF_R + stsm_off();
        store_tile_t(q0, sta);
        sts_u(sb + OFF_GM + 4, r.slot);
        mbar_wait(sb + BAR_RFULL + r.slot * 8, r.ph, r.dl);
        wg_wait<0>();
        reg_fence(q1);
        mbar_arrive_warp(sb + BAR_REMPTY + s8 * 8);
        mbar_arrive_warp(sb + BAR_REMPTY + s9 * 8);
        store_tile_t(q1, sta + XS);
    }
}

template <int NR>
__device__ __forceinline__ void opack(const float (&o)[NR], uint32_t* v) {
#pragma unroll
    for (int g = 0; g < NR / 16; g++)
#pragma unroll
        for (int hh = 0; hh < 2; hh++)
#pragma unroll
            for (int t = 0; t < 4; t++) v[8 * g + 4 * hh + t] = pack_bf16(o[16 * g + 4 * t + 2 * hh], o[16 * g + 4 * t + 2 * hh + 1]);
}

template <bool IS_S>
__device__ __forceinline__ void op_item(uint32_t e, uint32_t sb, Ring& r, uint32_t& phm) {
    constexpr int T0 = IS_S ? 0 : 2;
    constexpr uint32_t BOFF = IS_S ? (3 * 512) >> 4 : 0;
    const uint32_t loRing = (((sb + OFF_RING) & 0x3ffff) >> 4) | LO_LBO1;
    const uint32_t loO = (((sb + OFF_R) & 0x3ffff) >> 4) | LO_OST;
    float c0[80], c1[80], c2[IS_S ? 32 : 48];
    const int T = 3 * (IT_H1(e) - IT_H0(e));
    uint32_t xs = 0;
    auto step = [&](auto first, auto half) {
        constexpr bool F = decltype(first)::value;
        constexpr uint32_t hf = decltype(half)::value;
        if (hf == 0) {
            mbar_wait(sb + BAR_XFULL + xs * 8, (phm >> xs) & 1, r.dl);
            phm ^= 1u << xs;
        }
        mbar_wait(sb + BAR_RFULL + r.slot * 8, r.ph, r.dl);
        const uint32_t a = loRing + r.slot * (SLOT >> 4), b = loO + xs * (XS >> 4) + hf * 640;
        wg_fence();
        wgmma<1, 1, HI_OST, !F>(c0, a + T0 * 128, b);
        wgmma<1, 1, HI_OST, !F>(c1, a + T0 * 128 + 128, b);
        wgmma<1, 1, HI_OST, !F>(c2, a + 512, b + BOFF);
        wgmma<1, 1, HI_OST, true>(c0, a + 640 + T0 * 128, b + 320);
        wgmma<1, 1, HI_OST, true>(c1, a + 640 + T0 * 128 + 128, b + 320);
        wgmma<1, 1, HI_OST, true>(c2, a + 640 + 512, b + 320 + BOFF);
        wg_commit();
    };
    step(TrueT{}, IntT<0>{});
#pragma unroll 1
    for (int t = 1;; t++) {
        uint32_t pslot = r.slot;
        r.adv(1);
        step(FalseT{}, IntT<1>{});
        wg_wait<1>();
        mbar_arrive_warp(sb + BAR_REMPTY + pslot * 8);
        if (t == T) break;
        pslot = r.slot;
        const uint32_t pxs = xs;
        r.adv(1);
        if (++xs == 5) xs = 0;
        step(FalseT{}, IntT<0>{});
        wg_wait<1>();
        mbar_arrive_warp(sb + BAR_REMPTY + pslot * 8);
        mbar_arrive_warp_if(sb + BAR_XEMPTY + pxs * 8, t + 4 < T);
    }
    wg_wait<0>();
    reg_fence(c0);
    reg_fence(c1);
    reg_fence(c2);
    mbar_arrive_warp(sb + BAR_REMPTY + r.slot * 8);
    r.adv(1);
    nb_sync<NB_OPEND, 256>();
    const uint32_t sta = sb + OFF_R + stsm_off();
    store_tile_t(c0, sta + T0 * XS);
    store_tile_t(c1, sta + (T0 + 1) * XS);
    store_tile_t(c2, sta + 4 * XS + (IS_S ? 96 * 128 : 0));
    fence_async_smem();
    nb_arrive<NB_ODONE, 288>();
}

__device__ __forceinline__ void on_item(uint32_t W, uint32_t e, uint32_t sb, Ring& r, uint32_t& phm) {
    const uint32_t loRing = (((sb + OFF_RING) & 0x3ffff) >> 4) | LO_LBO1;
    const uint32_t loO = (((sb + OFF_R) & 0x3ffff) >> 4) | LO_OST;
    float c[80];
    const int T = 3 * (IT_H1(e) - IT_H0(e));
    uint32_t xs = 0;
    auto step = [&](auto first) {
        constexpr bool F = decltype(first)::value;
        mbar_wait(sb + BAR_XFULL + xs * 8, (phm >> xs) & 1, r.dl);
        phm ^= 1u << xs;
        mbar_wait(sb + BAR_RFULL + r.slot * 8, r.ph, r.dl);
        const uint32_t a = loRing + r.slot * (SLOT >> 4) + W * 256, b = loO + xs * (XS >> 4);
        wg_fence();
        wgmma<1, 1, HI_OST, !F>(c, a, b);
#pragma unroll
        for (int k = 1; k < 4; k++) wgmma<1, 1, HI_OST, true>(c, a + (k >> 1) * 512 + (k & 1) * 128, b + k * 320);
        wg_commit();
    };
    step(TrueT{});
#pragma unroll 1
    for (int t = 1; t < T; t++) {
        const uint32_t pslot = r.slot, pxs = xs;
        r.adv(1);
        if (++xs == 5) xs = 0;
        step(FalseT{});
        wg_wait<1>();
        mbar_arrive_warp(sb + BAR_REMPTY + pslot * 8);
        mbar_arrive_warp_if(sb + BAR_XEMPTY + pxs * 8, t + 2 < T);
    }
    xs += 1 + W;
    if (xs >= 5) xs -= 5;
    mbar_wait(sb + BAR_XFULL + xs * 8, (phm >> xs) & 1, r.dl);
    wg_wait<0>();
    reg_fence(c);
    store_tile_t<true>(c, sb + OFF_R + xs * XS + stsm_off());
    fence_async_smem();
    nb_arrive<NB_ODONE, 288>();
}

template <int W>
__device__ __forceinline__ uint32_t qa_item(uint32_t e, uint32_t sb, Ring& r, uint32_t phm, PendO<W>& po, float (&q0)[80],
                                            float (&oa)[80], int it) {
    const uint32_t loR = (((sb + OFF_R) & 0x3ffff) >> 4) | LO_LBO1;
    const uint32_t loRing = (((sb + OFF_RING) & 0x3ffff) >> 4) | LO_LBO1;
    qproj<W, 0>(q0, oa, sb, r, 0, phm, po);
    fence_async_smem();
    TSD(W, 1);
    float s[80], ob[W == 0 ? 32 : 48], l[10];
    if (W == 1) {
        nb_arrive<NB_Q2, 256>();
        zero(oa);
        zero(ob);
        reg_fence(oa);
        reg_fence(ob);
    }
    const uint32_t lane = tid_now() & 31, sta = sb + OFF_R + stsm_off();
    auto pv = [&](auto first, uint32_t buf) {
        constexpr bool F = decltype(first)::value;
        mbar_wait(sb + BAR_RFULL + r.slot * 8, r.ph, r.dl);
        const uint32_t a = loRing + r.slot * (SLOT >> 4), b = loR + (3 + buf) * (XS >> 4);
        wg_fence();
        wgmma<1, 0, HI_SW128, F ? 2 : 1>(oa, a + W * 512, b);
        wgmma<1, 0, HI_SW128, !F>(ob, a + 1024, b + (W == 0 ? (96 * 128) >> 4 : 0));
#pragma unroll
        for (int k = 1; k < 4; k++) {
            wgmma<1, 0, HI_SW128, true>(oa, a + W * 512 + k * 128, b + k * 2);
            wgmma<1, 0, HI_SW128, true>(ob, a + 1024 + k * 128, b + (W == 0 ? (96 * 128) >> 4 : 0) + k * 2);
        }
        wg_commit();
    };
    zero(l);
    float mref;
    uint32_t kslot, vslot, nx = 0;
    auto tail = [&](auto first, int i) {
        constexpr bool rel_other = !decltype(first)::value;
        uint32_t ps[40];
        exp_block<0>(s, ps, sta + (3 + W) * XS, mref);
        if (rel_other) {
            wg_wait<0>();
            mbar_arrive_warp(sb + BAR_REMPTY + vslot * 8);
            if (W == 1) mbar_arrive_warp_if(sb + BAR_XEMPTY + 24, i == 3);
        }
        fence_async_smem();
        nb_arrive<NB_PFULL + W, 256>();
        TSD(W, 6 + 5 * i);
        if (W == 1) {
            if (XLATE >= 2) mbar_arrive_warp_if<2>(sb + BAR_XEMPTY + 8, i == 3);
            if (XLATE >= 1) mbar_arrive_warp_if<2>(sb + BAR_XEMPTY + 16, i == 3);
        }
        if (rel_other || !PV0FIRST) {
            mbar_wait(sb + BAR_RFULL + r.slot * 8, r.ph, r.dl);
            sum_block(ps, l, lane);
        }
        if (W == 0 && i == 3) nx = get_item_warp(sb, it + 1, r.dl);
        TSD(W, 7 + 5 * i);
        if (LASTORD && W == 0 && i == 3) nb_sync<NB_PDONE, 256>();
        else nb_sync<NB_W + W, 128>();
        pv(first, W);
        if (!rel_other && PV0FIRST) sum_block(ps, l, lane);
        TSD(W, 8 + 5 * i);
    };
    if (W == 0) {
        nb_sync<NB_QK, 160>();
        TSD(W, 2);
        wg_fence();
        qk_steps<0, 8>(s, loRing + r.slot * (SLOT >> 4), loR);
        nb_sync<NB_Q2, 256>();
        qk_steps<8, 12>(s, loRing + r.slot * (SLOT >> 4), loR);
        wg_commit();
        nb_arrive<NB_Q01, 256>();
        TSD(W, 4);
        nb_sync<NB_REF, 160>();
        mref = __uint_as_float(lds_u(sb + OFF_GM));
        wg_wait<0>();
        reg_fence(s);
        mbar_arrive_warp<2>(sb + BAR_REMPTY + r.slot * 8);
        r.adv(2);
        TSD(W, 5);
        tail(TrueT{}, 0);
    } else {
        nb_sync<NB_Q01, 256>();
    }
#pragma unroll 1
    for (int i = (W == 0 ? 1 : 0); i < 4; i++) {
        const uint32_t pvslot = r.slot;
        r.adv(1);
        kslot = r.slot;
        mbar_wait(sb + BAR_RFULL + r.slot * 8, r.ph, r.dl);
        wg_fence();
        qk_steps<0, 4>(s, loRing + r.slot * (SLOT >> 4), loR);
        if (W == 1) wg_commit();
        qk_steps<4, 12>(s, loRing + r.slot * (SLOT >> 4), loR);
        wg_commit();
        wg_wait<1>();
        if (W == 1) mbar_arrive_warp_if(sb + BAR_XEMPTY + 0, i == 3);
        mbar_arrive_warp_if(sb + BAR_REMPTY + pvslot * 8, W == 0 || i > 0);
        r.adv(1);
        vslot = r.slot;
        TSD(W, 4 + 5 * i);
        nb_sync<NB_PFULL + (W ^ 1), 256>();
        pv(FalseT{}, W ^ 1);
        if (LASTORD && W == 1 && i == 3) nb_arrive<NB_PDONE, 256>();
        if (W == 1) mref = __uint_as_float(lds_u(sb + OFF_GM));
        wg_wait<1>();
        reg_fence(s);
        mbar_arrive_warp<2>(sb + BAR_REMPTY + kslot * 8);
        if (W == 0) mbar_arrive_warp_if(sb + BAR_XEMPTY + 0, i == 3);
        if (W == 1) {
            if (XLATE < 2) mbar_arrive_warp_if<2>(sb + BAR_XEMPTY + 8, i == 3);
            if (XLATE < 1) mbar_arrive_warp_if<2>(sb + BAR_XEMPTY + 16, i == 3);
        }
        r.adv(W == 1 && i == 3 ? 1 : 2);
        TSD(W, 5 + 5 * i);
        tail(FalseT{}, i);
    }
    if (W == 1) nx = get_item_warp(sb, it + 1, r.dl);
    if (W == 0) {
        Ring rn = r;
        rn.adv(2);
        q_ahead(q0, sb, rn, phm, IT_TYPE(nx) == IT_QA);
        TSD(W, 25);
    }
    const uint32_t w = (tid_now() >> 5) & 3;
    const uint32_t lxa = sb + OFF_LX + w * 640 + (((lane & 8) ? 80 : 0) + ((lane >> 1) & 8) + 2 * (lane & 3) + ((lane >> 2) & 1)) * 4;
    po.gp = ostash(IT_SLOT(e), IT_B(e)) + po.toff();
    po.sig = 1;
    if (W == 0) {
        sum_store<false>(l, lane, lxa);
        nb_arrive<NB_LX, 256>();
        wg_wait<1>();
        mbar_arrive_warp(sb + BAR_REMPTY + r.slot * 8);
        mbar_arrive_warp(sb + BAR_XEMPTY + 24);
        r.adv(1);
        nb_sync<NB_PFULL + 1, 256>();
        pv(FalseT{}, 1);
    } else {
        nb_sync<NB_LX, 256>();
        sum_store<true>(l, lane, lxa);
        nb_arrive<NB_L, 160>();
    }
    TSD(W, 24);
    wg_wait<0>();
    reg_fence(oa);
    reg_fence(ob);
    mbar_arrive_warp(sb + BAR_REMPTY + r.slot * 8);
    mbar_arrive_warp(sb + BAR_XEMPTY + 32);
    r.adv(1);
    opack(ob, po.v + 40);
    opack(oa, po.v);
    return nx;
}

template <int W>
__device__ __forceinline__ uint32_t qa_run(const Params& P, uint32_t e, uint32_t sb, Ring& r, uint32_t phm, int& it) {
    PendO<W> po;
    po.clear();
    float q0[80], oa[80];
    if (W == 0) {
        zero(oa);
        q_ahead(q0, sb, r, phm, true);
        wg_wait<0>();
    }
#pragma unroll 1
    do {
        TS(W, 0);
        if (W == 0) TS_ITEM(e);
        e = qa_item<W>(e, sb, r, phm, po, q0, oa, it);
        TS(W, 31);
        it++;
    } while (IT_TYPE(e) == IT_QA && !po.bad);
#pragma unroll 1
    for (int m = po.bad ? 2 : 1; m > 0; m--) {
        if (m == 1) {
            po.verdict(sb);
            po.template step<0>(sb);
            po.template step<1>(sb);
            po.template step<2>(sb);
            po.template step<3>(sb);
            po.template step<4>(sb);
        }
        if (po.bad) {
            if (W == 0) fallback_unit(P, lds_u(sb + OFF_ITEM + (it - m) * 4), tid_now() & 127);
            __syncwarp();
            nb_sync<NB_ODONE, 288>();
        }
    }
    return e;
}

__device__ __forceinline__ void consumer(const Params& P, uint32_t W, uint32_t sb, uint32_t dl) {
    int it = 0;
    Ring r{0, 0, dl};
    uint32_t phm = 0;
    uint32_t e = get_item_warp(sb, 0, dl);
#pragma unroll 1
    while (true) {
        if (IT_TYPE(e) == IT_QA) e = W == 0 ? qa_run<0>(P, e, sb, r, phm, it) : qa_run<1>(P, e, sb, r, phm, it);
        if (e == 0) break;
        if (IT_TYPE(e) == IT_QA) continue;
        TS(W, 0);
        if (W == 0) TS_ITEM(e);
        if (IT_TYPE(e) == IT_ON) on_item(W, e, sb, r, phm);
        else if (W == 0) op_item<true>(e, sb, r, phm);
        else op_item<false>(e, sb, r, phm);
        TS(W, 31);
        e = get_item_warp(sb, ++it, dl);
    }
    TS_DUMP(W);
}

__global__ void __cluster_dims__(2, 1, 1) __launch_bounds__(384, 1) fused_kernel(const __grid_constant__ Params P) {
    extern __shared__ __align__(1024) unsigned char smem_raw[];
    const uint32_t sb = (uint32_t)__cvta_generic_to_shared(smem_raw);
    const uint32_t warp = __shfl_sync(0xffffffffu, threadIdx.x >> 5, 0), wgid = warp >> 2;
    const uint32_t cta = blockIdx.x;
    const uint32_t dl = deadline();

    if (threadIdx.x == 128) {
#pragma unroll
        for (int i = 0; i < NSLOT; i++) {
            mbar_init(sb + BAR_RFULL + i * 8, 1);
            mbar_init(sb + BAR_REMPTY + i * 8, 8);
            mbar_init(sb + BAR_XFULL + i * 8, 1);
            mbar_init(sb + BAR_XEMPTY + i * 8, 8);
        }
        asm volatile("fence.mbarrier_init.release.cluster;" ::: "memory");
        fence_async_smem();
    } else if (threadIdx.x == 160) {
#pragma unroll
        for (int i = 0; i < NSLOT + MAXI; i++) mbar_init(sb + BAR_PRDY + i * 8, 1);
        asm volatile("fence.mbarrier_init.release.cluster;" ::: "memory");
    } else if (threadIdx.x == 0) {
        sts_u(sb + OFF_ITEM, P.cl[cta >> 1].items[0] ? P.cl[cta >> 1].items[0] + 8 * (cta & 1) : 0);
        sts_u(sb + OFF_FB, P.cl[cta >> 1].delay);
    } else if (threadIdx.x == 64) {
        if (sb & 1023) __trap();
        asm volatile("prefetch.tensormap [%0];" ::"l"(&P.wq[0]) : "memory");
        asm volatile("prefetch.tensormap [%0];" ::"l"(&P.x[0]) : "memory");
    }
    __syncthreads();
    {
        const int it = 0;
        if (wgid == 1) TS(0, 30);
    }
    asm volatile("barrier.cluster.arrive.relaxed.aligned;" ::: "memory");
    if (warp < 3) {
        const uint32_t e = __shfl_sync(0xffffffffu, lds_u(sb + OFF_ITEM), 0), d = lds_u(sb + OFF_FB);
        const uint64_t pol = mkpol<POL_W>();
        const bool isx = warp == 1, lead = (threadIdx.x & 31) == 0;
        uint32_t t0, t1;
        asm volatile("mov.u32 %0, %%clock;" : "=r"(t0));
        do {
            asm volatile("mov.u32 %0, %%clock;" : "=r"(t1));
        } while (t1 - t0 < d);
        __syncwarp();
#pragma unroll 1
        for (int n = 0; n < (e ? NSLOT : 0); n++) {
            const uint32_t bar = sb + (isx ? BAR_XFULL : BAR_RFULL) + n * 8;
            if (lead) {
                if (warp < 2) mbar_expect(bar, isx ? XS : SLOT);
                tma3(sb + (isx ? OFF_R + n * XS : OFF_RING + n * SLOT + warp * (SLOT / 4)), isx ? &P.x[0] : &P.wq[0],
                     isx ? IT_B(e) * 160 : n * 64 + warp * 16, isx ? n : IT_H0(e) * 3, bar, pol);
            }
        }
        if (threadIdx.x == 0) asm volatile("mbarrier.arrive.shared::cta.b64 _, [%0];" ::"r"(sb + BAR_ITEM) : "memory");
        __syncwarp();
    }

    if (wgid == 0) {
        asm volatile("setmaxnreg.dec.sync.aligned.u32 24;");
        if (warp == 0) {
            const bool lead = threadIdx.x == 0;
            const uint64_t pol_first = mkpol<1>(), pol_norm = mkpol<POL_W>();
            uint32_t e = __shfl_sync(0xffffffffu, lds_u(sb + OFF_ITEM), 0);
            asm volatile("barrier.cluster.wait.aligned;" ::: "memory");
            unsigned int* const ticket = &g_ticket[next_epoch(0) & 1];
            const uint32_t rank = cta & 1;
            uint32_t peer;
            asm volatile("mapa.shared::cluster.u32 %0, %1, %2;" : "=r"(peer) : "r"(sb), "r"(rank ^ 1));
            Ring r{0, 0, dl};
            uint32_t pm = 0;
            auto load_w = [&](const CUtensorMap* m, int row, int blk, uint32_t half_bytes) {
                mbar_wait(sb + BAR_REMPTY + r.slot * 8, r.ph, dl);
                if (lead) {
                    mbar_expect(sb + BAR_RFULL + r.slot * 8, 2 * half_bytes);
                    asm volatile("mbarrier.arrive.shared::cluster.b64 _, [%0];" ::"r"(peer + BAR_PRDY + r.slot * 8) : "memory");
                }
                mbar_wait(sb + BAR_PRDY + r.slot * 8, (pm >> r.slot) & 1, dl);
                pm ^= 1u << r.slot;
                if (lead) tma3_mc(sb + OFF_RING + r.slot * SLOT + rank * half_bytes, m, row, blk, sb + BAR_RFULL + r.slot * 8, pol_norm);
                r.adv(1);
            };
#pragma unroll 1
            for (int it = 0; e != 0; it++) {
                uint32_t nx = 0, tk = 0;
                if (rank == 0 && IT_TYPE(e) != IT_ON && it + 2 < MAXI) nx = it + 1 < NSTAT ? P.cl[cta >> 1].items[it + 1] : IT_DYN;
                const uint32_t br = IT_BR(e);
                if (IT_TYPE(e) == IT_QA) {
                    const uint32_t h = IT_H0(e);
#pragma unroll 1
                    for (int kk = it ? 0 : NSLOT; kk < 10; kk++) load_w(&P.wq[br], kk * 64 + rank * 32, h * 3, SLOT / 2);
                    const int row0 = (IT_B(e) * 32 + h) * 512;
#pragma unroll 1
                    for (int n = 0; n < 16; n++) {
                        if (n == 13 && nx == IT_DYN && lead) tk = atomicAdd(ticket, 1);
                        const bool isv = n == 15 || (n > 0 && !(n & 1));
                        const int j = n == 15 ? 7 : isv ? (n - 2) >> 1 : (n + 1) >> 1;
                        mbar_wait(sb + BAR_REMPTY + r.slot * 8, r.ph, dl);
                        if (lead) {
                            mbar_expect(sb + BAR_RFULL + r.slot * 8, SLOT);
                            tma3(sb + OFF_RING + r.slot * SLOT, isv ? &P.v[br] : &P.k[br], row0 + j * 64, 0,
                                 sb + BAR_RFULL + r.slot * 8, pol_first);
                        }
                        r.adv(1);
                    }
                } else {
                    const bool wide = IT_TYPE(e) == IT_OP;
                    const int step = wide ? 32 : 64, r1 = IT_H1(e) * 192;
#pragma unroll 1
                    for (int row = IT_H0(e) * 192 + rank * (step >> 1); row < r1; row += step)
                        load_w(wide ? &P.wo[br] : &P.won[br], row, IT_HALF(e) * (wide ? 5 : 2), wide ? XS / 2 : 8192);
                    if (nx == IT_DYN && lead) tk = atomicAdd(ticket, 1);
                }
                if (rank == 0) {
                    if (nx == IT_DYN) {
                        tk = __shfl_sync(0xffffffffu, tk, 0);
                        nx = tk < P.nlist ? P.list[tk] : 0;
                    }
                    e = nx;
                    if (lead) {
                        asm volatile("st.async.weak.shared::cluster.mbarrier::complete_tx::bytes.b32 [%0], %1, [%2];" ::"r"(
                                         peer + OFF_ITEM + 4 + it * 4),
                                     "r"(e ? e + 8 : 0), "r"(peer + BAR_ITEM + 8 + it * 8)
                                     : "memory");
                        sts_u(sb + OFF_ITEM + 4 + it * 4, e);
                        asm volatile("mbarrier.arrive.shared::cta.b64 _, [%0];" ::"r"(sb + BAR_ITEM + 8 + it * 8) : "memory");
                    }
                } else {
                    if (lead) mbar_expect(sb + BAR_ITEM + 8 + it * 8, 4);
                    e = get_item_warp(sb, it + 1, dl);
                }
            }
        } else if (warp == 1) {
            const uint64_t pol_norm = mkpol<POL_X>(), pol_o = mkpol<POL_O>();
            const bool lead = threadIdx.x == 32;
            uint32_t phm = 0, epoch = 0;
#pragma unroll 1
            for (int it = 0;; it++) {
                const uint32_t e = get_item_warp(sb, it, dl);
                if (it == 1 || (it == 0 && e == 0)) epoch = next_epoch(1);
                if (e == 0) break;
                const uint32_t br = IT_BR(e);
                uint32_t xs = 0;
                auto acquire = [&]() {
                    mbar_wait(sb + BAR_XEMPTY + xs * 8, (phm >> xs) & 1, dl);
                    phm ^= 1u << xs;
                    if (lead) mbar_expect(sb + BAR_XFULL + xs * 8, XS);
                };
                if (IT_TYPE(e) == IT_QA) {
#pragma unroll 1
                    for (int kk = it ? 0 : 5; kk < 10; kk++) {
                        acquire();
                        if (lead) tma3(sb + OFF_R + xs * XS, &P.x[br], IT_B(e) * 160, kk, sb + BAR_XFULL + xs * 8, pol_norm);
                        if (++xs == 5) xs = 0;
                    }
                } else {
                    const unsigned int* fp = g_flag + (br * 16 + IT_B(e)) * 64 + (threadIdx.x & 31);
                    uint32_t hm = 0, pm = 0;
                    auto poll = [&](uint32_t hneed, uint32_t pneed) {
                        if ((hm & hneed) == hneed && (pm & pneed) == pneed) return;
                        uint32_t n = 0;
                        do {
                            uint32_t a, b;
                            asm volatile("ld.acquire.gpu.global.u32 %0, [%2];\nld.acquire.gpu.global.u32 %1, [%2+128];"
                                         : "=r"(a), "=r"(b) : "l"(fp) : "memory");
                            hm = __ballot_sync(0xffffffffu, a == epoch);
                            pm = __ballot_sync(0xffffffffu, b == epoch);
                            if (++n > 0x1000000) __trap();
                        } while ((hm & hneed) != hneed || (pm & pneed) != pneed);
                        __syncwarp();
                        asm volatile("fence.proxy.async;" ::: "memory");
                    };
#pragma unroll 1
                    for (uint32_t h = IT_H0(e); h < IT_H1(e); h++) {
                        poll(1u << h, 0);
                        const unsigned char* src = ostash(P.slot[br * 32 + h], IT_B(e));
#pragma unroll 1
                        for (int t = 0; t < 3; t++) {
                            acquire();
                            if (lead) bulk_load(sb + OFF_R + xs * XS, src + t * XS, XS, sb + BAR_XFULL + xs * 8, pol_o);
                            if (++xs == 5) xs = 0;
                        }
                        if (IT_TYPE(e) == IT_OP && h >= 1) {
                            const uint32_t x1 = xs == 4 ? 0 : xs + 1;
                            mbar_wait(sb + BAR_XFULL + xs * 8, (phm >> xs) & 1, dl);
                            mbar_wait(sb + BAR_XFULL + x1 * 8, (phm >> x1) & 1, dl);
                            if (lead)
                                asm volatile("st.relaxed.gpu.global.u32 [%0], %1;" ::"l"(fp + 34 + IT_HALF(e)), "r"(epoch * 64 + h) : "memory");
                        }
                    }
                    if (IT_TYPE(e) == IT_ON) {
                        poll(0, IT_HALF(e) < 2 ? 1 : IT_HALF(e) == 2 ? 3 : 2);
#pragma unroll 1
                        for (uint32_t tile = 2 * IT_HALF(e); tile < 2 * IT_HALF(e) + 2; tile++) {
                            acquire();
                            if (lead)
                                asm volatile(
                                    "cp.async.bulk.tensor.5d.shared::cluster.global.mbarrier::complete_tx::bytes [%0], [%1, {%3,%5,%5,%5,%4}], [%2];" ::"r"(
                                        sb + OFF_R + xs * XS),
                                    "l"(&P.out), "r"(sb + BAR_XFULL + xs * 8), "r"(br * 640 + tile * 64), "r"(IT_B(e) * 5), "r"(0)
                                    : "memory");
                            if (++xs == 5) xs = 0;
                        }
                    }
                }
            }
        } else if (warp == 2) {
            asm volatile("barrier.cluster.wait.aligned;" ::: "memory");
            const uint32_t epoch = next_epoch(2);
            if (cta == 0) g_ticket[(epoch + 1) & 1] = 0;
#pragma unroll 1
            for (int it = 0;; it++) {
                const uint32_t e = get_item_warp(sb, it, dl);
                if (e == 0) break;
                nb_sync<NB_ODONE, 288>();
                if (threadIdx.x == 64) {
                    const uint32_t bb = IT_BR(e) * 16 + IT_B(e);
                    if (IT_TYPE(e) != IT_QA) {
                        const bool wide = IT_TYPE(e) == IT_OP;
                        if (wide)
                            asm volatile("st.relaxed.gpu.global.u32 [%0], %1;" ::"l"(&g_flag[bb * 64 + 34 + IT_HALF(e)]),
                                         "r"(epoch * 64 + IT_H1(e))
                                         : "memory");
                        const int cc0 = IT_BR(e) * 640 + IT_HALF(e) * (wide ? 320 : 128);
                        uint32_t xs = wide ? 0 : (3 * (IT_H1(e) - IT_H0(e))) % 5;
#pragma unroll 1
                        for (int m = 0; m < (wide ? 5 : 2); m++) {
                            asm volatile("cp.async.bulk.tensor.5d.global.shared::cta.bulk_group [%0, {%2,%4,%4,%4,%3}], [%1];" ::"l"(&P.out),
                                         "r"(sb + OFF_R + xs * XS), "r"(cc0 + m * 64), "r"((int)IT_B(e) * 5), "r"(0)
                                         : "memory");
                            asm volatile("cp.async.bulk.commit_group;" ::: "memory");
                            if (wide && m >= STLAG) {
                                asm volatile("cp.async.bulk.wait_group.read %0;" ::"n"(STLAG) : "memory");
                                asm volatile("mbarrier.arrive.shared::cta.b64 _, [%0], 8;" ::"r"(sb + BAR_XEMPTY + (m - STLAG) * 8) : "memory");
                            }
                            if (++xs == 5) xs = 0;
                        }
                        if (wide && STLAG) {
                            asm volatile("cp.async.bulk.wait_group.read 0;" ::: "memory");
                            asm volatile("mbarrier.arrive.shared::cta.b64 _, [%0], 8;" ::"r"(sb + BAR_XEMPTY + 32) : "memory");
                        }
                        if (IT_PART(e)) {
                            asm volatile("cp.async.bulk.wait_group 0;" ::: "memory");
                            asm volatile("fence.proxy.async;" ::: "memory");
                        }
                    }
                    if (IT_TYPE(e) == IT_QA || IT_PART(e)) {
                        unsigned int* f = &g_flag[bb * 64 + (IT_TYPE(e) == IT_QA ? IT_H0(e) : 32 + IT_HALF(e))];
                        asm volatile("st.release.gpu.global.u32 [%0], %1;" ::"l"(f), "r"(epoch) : "memory");
                    }
                }
                __syncwarp();
            }
            if (threadIdx.x == 64) asm volatile("cp.async.bulk.wait_group 0;" ::: "memory");
            __syncwarp();
            asm volatile("barrier.cluster.arrive.relaxed.aligned;\nbarrier.cluster.wait.aligned;" ::: "memory");
        } else {
            const uint32_t lane = threadIdx.x & 31, p = lane >> 2;
            const uint32_t epoch = next_epoch(3);
#pragma unroll 1
            for (int it = 0;; it++) {
                const uint32_t e = get_item_warp(sb, it, dl);
                if (e == 0) break;
                if (IT_TYPE(e) != IT_QA) continue;
                nb_sync<NB_QK, 160>();
                const uint32_t co = (((lane & 3) * 2) ^ p) << 4;
                const uint32_t ka = sb + OFF_RING + lds_u(sb + OFF_GM + 4) * SLOT + p * (9 * 128) + co;
                const uint32_t qa = sb + OFF_R + p * 128 + co;
                uint32_t acc = 0;
#pragma unroll 1
                for (int c = 0; c < 3; c++) {
                    if (c == 2) nb_sync<NB_L, 160>();
                    const uint4 k0 = lds_u4(ka + c * 8192), q0 = lds_u4(qa + c * XS);
                    acc = fma_bf2(k0.x, q0.x, fma_bf2(k0.y, q0.y, fma_bf2(k0.z, q0.z, fma_bf2(k0.w, q0.w, acc))));
                    const uint4 k1 = lds_u4((ka + c * 8192) ^ 16), q1 = lds_u4((qa + c * XS) ^ 16);
                    acc = fma_bf2(k1.x, q1.x, fma_bf2(k1.y, q1.y, fma_bf2(k1.z, q1.z, fma_bf2(k1.w, q1.w, acc))));
                }
                float d = __uint_as_float(acc << 16) + __uint_as_float(acc & 0xffff0000u);
                d += __shfl_xor_sync(0xffffffffu, d, 1);
                d += __shfl_xor_sync(0xffffffffu, d, 2);
                int key = __float_as_int(d);
                key ^= (key >> 31) & 0x7fffffff;
                key = __reduce_max_sync(0xffffffffu, key);
                key ^= (key >> 31) & 0x7fffffff;
                sts_f(sb + OFF_GM, fmaf(__int_as_float(key), SM_C, 16.f));
                nb_arrive<NB_REF, 160>();
                if (IT_DEP(e)) {
                    const uint32_t g = IT_DEP(e) - 1, need = epoch * 64 + (g & 31) + 1;
                    const unsigned int* cp = &g_flag[((g >> 5) * 16 + IT_B(e)) * 64 + 34 + (lane & 1)];
                    for (uint32_t n = 0;; n++) {
                        uint32_t v;
                        asm volatile("ld.acquire.gpu.global.u32 %0, [%1];" : "=r"(v) : "l"(cp) : "memory");
                        if (__all_sync(0xffffffffu, v - need < 64)) break;
                        if (n > 0x800000) __trap();
                        __nanosleep(500);
                    }
                }
                nb_sync<NB_L, 160>();
                bool bad = false;
#pragma unroll
                for (int c = 0; c < 5; c++) {
                    const uint32_t la = sb + OFF_LX + (c * 32 + lane) * 4;
                    const float v = (__uint_as_float(lds_u(la)) + __uint_as_float(lds_u(la + 640))) +
                                    (__uint_as_float(lds_u(la + 1280)) + __uint_as_float(lds_u(la + 1920)));
                    const float inv = __fdividef(1.f, v);
                    const uint32_t hi = pack_bf16(inv, 0.f), lo = pack_bf16(inv - __uint_as_float(hi << 16), 0.f);
                    const uint32_t ia = sb + OFF_LINV + c * 128 + ((lane >> 1) & 3) * 32 + (lane >> 3) * 8 + (lane & 1) * 2;
                    asm volatile("st.shared.u16 [%0], %1;\nst.shared.u16 [%0+4], %2;" ::"r"(ia), "h"((unsigned short)hi), "h"((unsigned short)lo) : "memory");
                    bad |= !(v >= 5.421010862e-20f && v <= 7.9228163e28f);
                }
                sts_u(sb + OFF_FB, __any_sync(0xffffffffu, bad));
                nb_arrive<NB_VOTE, 160>();
                nb_arrive<NB_VOTE + 1, 160>();
            }
        }
    } else {
        asm volatile("setmaxnreg.inc.sync.aligned.u32 240;");
        consumer(P, wgid - 1, sb, dl);
    }
}

typedef CUresult (*EncFn)(CUtensorMap*, CUtensorMapDataType, cuuint32_t, void*, const cuuint64_t*, const cuuint64_t*,
                          const cuuint32_t*, const cuuint32_t*, CUtensorMapInterleave, CUtensorMapSwizzle,
                          CUtensorMapL2promotion, CUtensorMapFloatOOBfill);

void make_map3(EncFn enc, CUtensorMap* m, void* p, uint64_t rows, uint64_t rowbytes, uint64_t nblk, uint32_t boxrows,
               uint32_t boxblk) {
    cuuint64_t dims[3] = {64, rows, nblk};
    cuuint64_t str[2] = {rowbytes, 128};
    cuuint32_t box[3] = {64, boxrows, boxblk};
    cuuint32_t es[3] = {1, 1, 1};
    enc(m, CU_TENSOR_MAP_DATA_TYPE_BFLOAT16, 3, p, dims, str, box, es, CU_TENSOR_MAP_INTERLEAVE_NONE,
        CU_TENSOR_MAP_SWIZZLE_128B, CU_TENSOR_MAP_L2_PROMOTION_NONE, CU_TENSOR_MAP_FLOAT_OOB_FILL_NONE);
}

constexpr int tune(const char*, int def) { return def; }

void build_schedule(Params& P) {
    const int mode = tune("MODE", 4), dmax = tune("DMAX", 24900), n0 = tune("N0", 11), odmax = tune("ODMAX", 0), d1 = tune("D1", 0);
    const int H0[8] = {19, 20, 21, 23, 23, 24, 25, 25}, P0[8] = {367, 340, 338, 331, 341, 339, 331, 334};
    const int ra = tune("RA", 10), ga = tune("GA", 17), rb = tune("RB", 11), g1 = tune("G1", 58);
    int dep[64];
    for (int g = 0, ns = 0, live = 0; g < 64; g++) {
        const bool fresh = mode < 3 || g >= g1 || live < (g < ga ? ra : rb);
        dep[g] = fresh ? 0 : g - live + 1;
        P.slot[g] = fresh ? ns++ : P.slot[g - live];
        live += fresh;
    }
    int H[8], pos[8], psum = 0;
    for (int b = 0; b < 8; b++) {
        const char nh[3] = {'H', (char)('0' + b), 0}, np[3] = {'P', (char)('0' + b), 0};
        H[b] = tune(nh, H0[b]);
        pos[b] = tune(np, P0[b]);
        psum += pos[b];
    }
    const int sk = tune("SK", 10), g0 = tune("G0", 20), g2 = tune("G2", 40);
    int ord[512], nxt[8] = {0, 0, 0, 0, 0, 0, 0, 0};
    for (int k = 0; k < 512; k++) {
        int best = -1;
        float bkey = 0.f;
        for (int b = 0; b < 8; b++) {
            const int g = nxt[b];
            if (g == 64) continue;
            const float w = g < g0 ? 0.f : g < 32 ? (g - g0) / (32.f - g0) : g < g2 ? 1.f : (64 - g) / (64.f - g2);
            const float key = g + w * sk * 0.1f * (pos[b] - psum / 8.f) / 8.f;
            if (best < 0 || key < bkey) best = b, bkey = key;
        }
        ord[k] = nxt[best]++ * 8 + best;
        const int d = dep[ord[k] >> 3];
        if (d > 32) {
            if (pos[best] > k) pos[best] = k;
            if (H[best] < d - 32) H[best] = d - 32;
        }
    }
    int u = 0;
    auto unit = [&]() {
        const int v = ord[u++];
        return mk_item(IT_QA, v >> 8, (v & 7) * 2, (v >> 3) & 31, P.slot[v >> 3], 0) | (dep[v >> 3] << 23);
    };
    int qa[NCL], nq = 0, op[NCL], no = 0;
    for (int c = 0; c < NCL; c++) {
        P.cl[c].delay = 0;
        for (int i = 0; i < NSTAT; i++) P.cl[c].items[i] = 0;
        if (mode >= 3 && c < 64 && (c & 3) == 3) op[no++] = c;
        else if (mode != 2 || (c & 3) == 0) qa[nq++] = c;
    }
    for (int t = 0; t < no; t++) {
        P.cl[op[t]].items[1] = mk_item(IT_OP, 0, t & ~1, 0, 32, t & 1);
        P.cl[op[t]].items[2] = IT_DYN;
        P.cl[op[t]].delay = tune("OD0", 0) + t * odmax / 16;
    }
    for (int k = 0; k < nq; k++) {
        const int c = qa[(k * 19) % nq];
        P.cl[c].items[1] = P.cl[c].items[2] = IT_DYN;
        P.cl[c].delay = k < n0 ? k * tune("J0", 0) : d1 + (dmax - d1) * (k + 1 - n0) / (nq - n0);
    }
    if (tune("OFIRST", 0))
        for (int t = 0; t < no; t++) P.cl[op[t]].items[0] = unit();
    for (int k = u; k < no + nq; k++) {
        int best = -1;
        for (int c = 0; c < NCL; c++)
            if (P.cl[c].items[1] && !P.cl[c].items[0] && (best < 0 || P.cl[c].delay < P.cl[best].delay)) best = c;
        P.cl[best].items[0] = unit();
    }
    int n = 0;
    const int uend = mode == 2 ? 8 * nq : 512;
    while (u < uend) {
        for (int b = 0; b < 8 && no; b++)
            if (pos[b] == u) {
                P.list[n++] = mk_item(IT_OP, 1, 2 * b, 0, H[b], 0, 1);
                P.list[n++] = mk_item(IT_OP, 1, 2 * b, 0, H[b], 1, 1);
            }
        P.list[n++] = unit();
    }
    for (int k = 0; no && k < 40; k++) P.list[n++] = mk_item(IT_ON, 1, k / 5 * 2, H[k / 5], 32, k % 5);
    P.nlist = n;
}

}

extern "C" void kernel_launch(void* const* d_in, const int* in_sizes, int n_in, void* d_out, int out_size) {
    static Params P;
    static bool init = false;
    if (!init) {
        EncFn enc = nullptr;
        cudaDriverEntryPointQueryResult qr;
        cudaGetDriverEntryPoint("cuTensorMapEncodeTiled", (void**)&enc, cudaEnableDefault, &qr);
        for (int i = 0; i < 2; i++) {
            P.px[i] = (const __nv_bfloat16*)d_in[5 * i + 0];
            P.pk[i] = (const __nv_bfloat16*)d_in[5 * i + 1];
            P.pv[i] = (const __nv_bfloat16*)d_in[5 * i + 2];
            P.pwq[i] = (const __nv_bfloat16*)d_in[5 * i + 3];
            make_map3(enc, &P.x[i], d_in[5 * i + 0], 2560, 1280, 10, 160, 1);
            make_map3(enc, &P.k[i], d_in[5 * i + 1], 16 * 32 * 512, 384, 3, 64, 3);
            make_map3(enc, &P.v[i], d_in[5 * i + 2], 16 * 32 * 512, 384, 3, 64, 3);
            make_map3(enc, &P.wq[i], d_in[5 * i + 3], 640, 12288, 96, 32, 3);
            make_map3(enc, &P.wo[i], d_in[5 * i + 4], 6144, 1280, 10, 16, 5);
            make_map3(enc, &P.won[i], d_in[5 * i + 4], 6144, 1280, 10, 32, 2);
        }
        cuuint64_t dims[5] = {1280, 2, 4, 4, 80};
        cuuint64_t str[4] = {2560, 8 * 2560, 2 * 2560, 32 * 2560};
        cuuint32_t box[5] = {64, 2, 4, 4, 5};
        cuuint32_t es[5] = {1, 1, 1, 1, 1};
        enc(&P.out, CU_TENSOR_MAP_DATA_TYPE_BFLOAT16, 5, d_out, dims, str, box, es, CU_TENSOR_MAP_INTERLEAVE_NONE,
            CU_TENSOR_MAP_SWIZZLE_128B, CU_TENSOR_MAP_L2_PROMOTION_NONE, CU_TENSOR_MAP_FLOAT_OOB_FILL_NONE);
        build_schedule(P);
        cudaFuncSetAttribute(fused_kernel, cudaFuncAttributeMaxDynamicSharedMemorySize, SMEM_LAUNCH);
        init = true;
    }
    fused_kernel<<<NCTA, 384, SMEM_LAUNCH>>>(P);
}
```

```cpp
#include <cuda_runtime.h>
#include <cuda.h>
#include <cuda_bf16.h>
#include <stdint.h>

namespace {

constexpr int NCTA = 132;
constexpr int NCL = NCTA / 2;
constexpr int MAXI = 16;
constexpr int NSTAT = 3;
constexpr uint32_t IT_DYN = 0xffffffffu;
constexpr int SLOT = 24576;
constexpr int NSLOT = 5;
constexpr int XS = 20480;
constexpr int OFF_R = 0;
constexpr int OFF_RING = 5 * XS;
constexpr int OFF_MISC = OFF_RING + NSLOT * SLOT;
constexpr int OFF_LX = OFF_MISC;
constexpr int OFF_LINV = OFF_LX + 2560;
constexpr int OFF_FB = OFF_LINV + 640;
constexpr int OFF_GM = OFF_FB + 16;
constexpr int OFF_BAR = OFF_GM + 16;
constexpr int BAR_RFULL = OFF_BAR;
constexpr int BAR_REMPTY = BAR_RFULL + 40;
constexpr int BAR_XFULL = BAR_REMPTY + 40;
constexpr int BAR_XEMPTY = BAR_XFULL + 40;
constexpr int BAR_PRDY = BAR_XEMPTY + 40;
constexpr int BAR_ITEM = BAR_PRDY + 40;
constexpr int OFF_ITEM = BAR_ITEM + MAXI * 8;
constexpr int SMEM_BYTES = OFF_ITEM + MAXI * 4;
static_assert(SMEM_BYTES <= 232448, "smem");

constexpr int NB_W = 1  , NB_PFULL = 3  , NB_VOTE = 5  , NB_Q2 = 7, NB_SDONE = 8, NB_PDONE = 9,
              NB_L = 10, NB_REF = 11, NB_ODONE = 12, NB_OPEND = 13, NB_LX = 14, NB_Q01 = 15, NB_QK = 0  ;

constexpr uint32_t IT_QA = 1, IT_OP = 2, IT_ON = 3;
__host__ __device__ constexpr uint32_t mk_item(uint32_t type, uint32_t br, uint32_t b, uint32_t h0, uint32_t h1, uint32_t half,
                                               uint32_t part = 0) {
    return type | (br << 2) | (b << 3) | (h0 << 7) | (h1 << 13) | (half << 19) | (part << 22);
}
#define IT_TYPE(e) ((e) & 3u)
#define IT_BR(e) (((e) >> 2) & 1u)
#define IT_B(e) (((e) >> 3) & 15u)
#define IT_H0(e) (((e) >> 7) & 63u)
#define IT_H1(e) (((e) >> 13) & 63u)
#define IT_HALF(e) (((e) >> 19) & 7u)
#define IT_PART(e) (((e) >> 22) & 1u)
#define IT_SLOT(e) IT_H1(e)
#define IT_DEP(e) (((e) >> 23) & 127u)

struct Params {
    CUtensorMap x[2], wq[2], k[2], v[2], wo[2], won[2], out;
    const __nv_bfloat16 *px[2], *pwq[2], *pk[2], *pv[2];
    struct alignas(16) { uint32_t delay, items[NSTAT]; } cl[NCL];
    uint32_t nlist;
    uint8_t slot[64];
    uint32_t list[512];
};

constexpr int OUNIT = 61440;
__device__ __align__(1024) unsigned char g_ostash[(size_t)1024 * OUNIT];
__device__ unsigned int g_flag[32 * 64];
__device__ __forceinline__ unsigned char* ostash(uint32_t slot, uint32_t b) { return g_ostash + (slot * 16 + b) * OUNIT; }
__device__ unsigned int g_epoch[NCTA * 4];
__device__ unsigned int g_ticket[2];

constexpr int SMEM_LAUNCH = SMEM_BYTES;
#define TS(role, idx)
#define TS_ITEM(e)
#define TS_DUMP(role)
#define TSD(role, idx)

#define POL_W 2
#define POL_X 2
#define POL_O 2
template <int M>
__device__ __forceinline__ uint64_t mkpol() {
    uint64_t p;
    if (M == 0) asm volatile("createpolicy.fractional.L2::evict_normal.b64 %0, 1.0;" : "=l"(p));
    if (M == 1) asm volatile("createpolicy.fractional.L2::evict_first.b64 %0, 1.0;" : "=l"(p));
    if (M == 2) asm volatile("createpolicy.fractional.L2::evict_unchanged.b64 %0, 1.0;" : "=l"(p));
    if (M == 3) asm volatile("createpolicy.fractional.L2::evict_normal.L2::evict_unchanged.b64 %0, 0.25;" : "=l"(p));
    return p;
}
#define STSM_W 1
#define SIGJ 0
#define STLAG 1
#define LASTORD 0
#define XLATE 2
#define PV0FIRST 1
#define QST0 1
#define QST1 2
#define QHOLD 8
constexpr float SM_C = 0.07216878364870322f * 1.4426950408889634f;

__device__ __forceinline__ uint32_t next_epoch(int warp) {
    unsigned int* p = &g_epoch[blockIdx.x * 4 + warp];
    const uint32_t e = __ldcg(p) + 1;
    *p = e;
    return e;
}

__device__ __forceinline__ uint32_t tid_now() {
    uint32_t t;
    asm volatile("mov.u32 %0, %%tid.x;" : "=r"(t));
    return t;
}
__device__ __forceinline__ void mbar_init(uint32_t a, uint32_t c) {
    asm volatile("mbarrier.init.shared::cta.b64 [%0], %1;" ::"r"(a), "r"(c) : "memory");
}
__device__ __forceinline__ void mbar_expect(uint32_t a, uint32_t b) {
    asm volatile("mbarrier.arrive.expect_tx.shared::cta.b64 _, [%0], %1;" ::"r"(a), "r"(b) : "memory");
}
template <int CNT = 1>
__device__ __forceinline__ void mbar_arrive_warp(uint32_t a) {
    if (CNT == 1)
        asm volatile("{\n.reg .pred p;\nelect.sync _|p, 0xffffffff;\n@p mbarrier.arrive.shared::cta.b64 _, [%0];\n}" ::"r"(a) : "memory");
    else
        asm volatile(
            "{\n.reg .pred p;\nelect.sync _|p, 0xffffffff;\n@p mbarrier.arrive.shared::cta.b64 _, [%0];\n"
            "@p mbarrier.arrive.shared::cta.b64 _, [%0];\n}" ::"r"(a)
            : "memory");
}
template <int CNT = 1>
__device__ __forceinline__ void mbar_arrive_warp_if(uint32_t a, bool cond) {
    if (CNT == 1)
        asm volatile(
            "{\n.reg .pred p, c;\nelect.sync _|p, 0xffffffff;\nsetp.ne.and.u32 c, %1, 0, p;\n"
            "@c mbarrier.arrive.shared::cta.b64 _, [%0];\n}" ::"r"(a), "r"((uint32_t)cond)
            : "memory");
    else
        asm volatile(
            "{\n.reg .pred p, c;\nelect.sync _|p, 0xffffffff;\nsetp.ne.and.u32 c, %1, 0, p;\n"
            "@c mbarrier.arrive.shared::cta.b64 _, [%0];\n@c mbarrier.arrive.shared::cta.b64 _, [%0];\n}" ::"r"(a), "r"((uint32_t)cond)
            : "memory");
}
__device__ __forceinline__ uint32_t deadline() {
    uint32_t c;
    asm volatile("mov.u32 %0, %%clock_hi;" : "=r"(c));
    return c + 4;
}
__device__ __forceinline__ void mbar_wait(uint32_t a, uint32_t ph, uint32_t dl) {
    asm volatile(
        "{\n.reg .pred p;\n.reg .u32 m;\n"
        "LOOP:\n"
        "mbarrier.try_wait.parity.shared::cta.b64 p, [%0], %1;\n"
        "@p bra DONE;\n"
        "mov.u32 m, %%clock_hi;\n"
        "setp.ne.u32 p, m, %2;\n"
        "@p bra LOOP;\n"
        "trap;\n"
        "DONE:\n}" ::"r"(a), "r"(ph), "r"(dl)
        : "memory");
}
template <int ID, int CNT>
__device__ __forceinline__ void nb_sync() { asm volatile("bar.sync %0, %1;" ::"n"(ID), "n"(CNT) : "memory"); }
template <int ID, int CNT>
__device__ __forceinline__ void nb_arrive() { asm volatile("bar.arrive %0, %1;" ::"n"(ID), "n"(CNT) : "memory"); }
__device__ __forceinline__ void fence_async_smem() { asm volatile("fence.proxy.async.shared::cta;" ::: "memory"); }

__device__ __forceinline__ void tma3(uint32_t dst, const CUtensorMap* m, int c1, int c2, uint32_t bar, uint64_t pol) {
    asm volatile(
        "cp.async.bulk.tensor.3d.shared::cluster.global.mbarrier::complete_tx::bytes.L2::cache_hint [%0], [%1, {%3,%4,%5}], [%2], %6;" ::"r"(dst),
        "l"(m), "r"(bar), "r"(0), "r"(c1), "r"(c2), "l"(pol)
        : "memory");
}
__device__ __forceinline__ void tma3_mc(uint32_t dst, const CUtensorMap* m, int c1, int c2, uint32_t bar, uint64_t pol) {
    asm volatile(
        "cp.async.bulk.tensor.3d.shared::cluster.global.mbarrier::complete_tx::bytes.multicast::cluster.L2::cache_hint"
        " [%0], [%1, {%3,%4,%5}], [%2], %6, %7;" ::"r"(dst),
        "l"(m), "r"(bar), "r"(0), "r"(c1), "r"(c2), "h"((unsigned short)3), "l"(pol)
        : "memory");
}
__device__ __forceinline__ void bulk_load(uint32_t dst, const void* src, uint32_t bytes, uint32_t bar, uint64_t pol) {
    asm volatile("cp.async.bulk.shared::cluster.global.mbarrier::complete_tx::bytes.L2::cache_hint [%0], [%1], %2, [%3], %4;" ::"r"(dst),
                 "l"(src), "r"(bytes), "r"(bar), "l"(pol)
                 : "memory");
}
__device__ __forceinline__ void wg_fence() { asm volatile("wgmma.fence.sync.aligned;" ::: "memory"); }
__device__ __forceinline__ void wg_commit() { asm volatile("wgmma.commit_group.sync.aligned;" ::: "memory"); }
template <int N>
__device__ __forceinline__ void wg_wait() { asm volatile("wgmma.wait_group.sync.aligned %0;" ::"n"(N) : "memory"); }

#define RW80(c, d) c(d[0]), c(d[1]), c(d[2]), c(d[3]), c(d[4]), c(d[5]), c(d[6]), c(d[7]), c(d[8]), c(d[9]), c(d[10]), c(d[11]), c(d[12]), c(d[13]), c(d[14]), c(d[15]), c(d[16]), c(d[17]), c(d[18]), c(d[19]), c(d[20]), c(d[21]), c(d[22]), c(d[23]), c(d[24]), c(d[25]), c(d[26]), c(d[27]), c(d[28]), c(d[29]), c(d[30]), c(d[31]), c(d[32]), c(d[33]), c(d[34]), c(d[35]), c(d[36]), c(d[37]), c(d[38]), c(d[39]), c(d[40]), c(d[41]), c(d[42]), c(d[43]), c(d[44]), c(d[45]), c(d[46]), c(d[47]), c(d[48]), c(d[49]), c(d[50]), c(d[51]), c(d[52]), c(d[53]), c(d[54]), c(d[55]), c(d[56]), c(d[57]), c(d[58]), c(d[59]), c(d[60]), c(d[61]), c(d[62]), c(d[63]), c(d[64]), c(d[65]), c(d[66]), c(d[67]), c(d[68]), c(d[69]), c(d[70]), c(d[71]), c(d[72]), c(d[73]), c(d[74]), c(d[75]), c(d[76]), c(d[77]), c(d[78]), c(d[79])
#define RW48(c, d) c(d[0]), c(d[1]), c(d[2]), c(d[3]), c(d[4]), c(d[5]), c(d[6]), c(d[7]), c(d[8]), c(d[9]), c(d[10]), c(d[11]), c(d[12]), c(d[13]), c(d[14]), c(d[15]), c(d[16]), c(d[17]), c(d[18]), c(d[19]), c(d[20]), c(d[21]), c(d[22]), c(d[23]), c(d[24]), c(d[25]), c(d[26]), c(d[27]), c(d[28]), c(d[29]), c(d[30]), c(d[31]), c(d[32]), c(d[33]), c(d[34]), c(d[35]), c(d[36]), c(d[37]), c(d[38]), c(d[39]), c(d[40]), c(d[41]), c(d[42]), c(d[43]), c(d[44]), c(d[45]), c(d[46]), c(d[47])
#define RW32(c, d) c(d[0]), c(d[1]), c(d[2]), c(d[3]), c(d[4]), c(d[5]), c(d[6]), c(d[7]), c(d[8]), c(d[9]), c(d[10]), c(d[11]), c(d[12]), c(d[13]), c(d[14]), c(d[15]), c(d[16]), c(d[17]), c(d[18]), c(d[19]), c(d[20]), c(d[21]), c(d[22]), c(d[23]), c(d[24]), c(d[25]), c(d[26]), c(d[27]), c(d[28]), c(d[29]), c(d[30]), c(d[31])

__device__ __forceinline__ void reg_fence(float (&d)[80]) { asm volatile("" : RW80("+f", d)::"memory"); }
__device__ __forceinline__ void reg_fence(float (&d)[48]) { asm volatile("" : RW48("+f", d)::"memory"); }
__device__ __forceinline__ void reg_fence(float (&d)[32]) { asm volatile("" : RW32("+f", d)::"memory"); }

template <int NR>
__device__ __forceinline__ void zero(float (&d)[NR]) {
#pragma unroll
    for (int i = 0; i < NR; i++) d[i] = 0.f;
}

constexpr uint32_t HI_SW128 = (1024u >> 4) | (1u << 30);
constexpr uint32_t HI_KV = (3072u >> 4) | (1u << 30);
constexpr uint32_t HI_OST = (2560u >> 4) | (2u << 30);
constexpr uint32_t LO_LBO1 = (1u << 16);
constexpr uint32_t LO_OST = ((512u >> 4) << 16);

template <int TA, int TB, uint32_t HIB, int ACC, uint32_t HIA = HI_SW128>
__device__ __forceinline__ void wgmma(float (&d)[80], uint32_t loA, uint32_t loB) {
#define WG_ASM(SD)                                                          \
    "{\n.reg .b64 da, db;\nmov.b64 da, {%80, %82};\nmov.b64 db, {%81, %83};\n" \
    "wgmma.mma_async.sync.aligned.m64n160k16.f32.bf16.bf16 "               \
    "{%0,%1,%2,%3,%4,%5,%6,%7,%8,%9,%10,%11,%12,%13,%14,%15,%16,%17,%18,%19,%20,%21,%22,%23,%24,%25,%26,%27,%28,%29,%30,%31,%32,%33,%34,%35,%36,%37,%38,%39,%40,%41,%42,%43,%44,%45,%46,%47,%48,%49,%50,%51,%52,%53,%54,%55,%56,%57,%58,%59,%60,%61,%62,%63,%64,%65,%66,%67,%68,%69,%70,%71,%72,%73,%74,%75,%76,%77,%78,%79}, da, db, " SD ", 1, 1, %84, %85;\n}"
    if constexpr (ACC == 2)
        asm volatile(WG_ASM("0") : RW80("+f", d) : "r"(loA), "r"(loB), "n"(HIA), "n"(HIB), "n"(TA), "n"(TB));
    else if constexpr (ACC == 1)
        asm volatile(WG_ASM("1") : RW80("+f", d) : "r"(loA), "r"(loB), "n"(HIA), "n"(HIB), "n"(TA), "n"(TB));
    else
        asm volatile(WG_ASM("0") : RW80("=f", d) : "r"(loA), "r"(loB), "n"(HIA), "n"(HIB), "n"(TA), "n"(TB));
#undef WG_ASM
}
template <int TA, int TB, uint32_t HIB, int ACC, uint32_t HIA = HI_SW128>
__device__ __forceinline__ void wgmma(float (&d)[48], uint32_t loA, uint32_t loB) {
#define WG_ASM(SD)                                                          \
    "{\n.reg .b64 da, db;\nmov.b64 da, {%48, %50};\nmov.b64 db, {%49, %51};\n" \
    "wgmma.mma_async.sync.aligned.m64n96k16.f32.bf16.bf16 "               \
    "{%0,%1,%2,%3,%4,%5,%6,%7,%8,%9,%10,%11,%12,%13,%14,%15,%16,%17,%18,%19,%20,%21,%22,%23,%24,%25,%26,%27,%28,%29,%30,%31,%32,%33,%34,%35,%36,%37,%38,%39,%40,%41,%42,%43,%44,%45,%46,%47}, da, db, " SD ", 1, 1, %52, %53;\n}"
    if constexpr (ACC == 1)
        asm volatile(WG_ASM("1") : RW48("+f", d) : "r"(loA), "r"(loB), "n"(HIA), "n"(HIB), "n"(TA), "n"(TB));
    else
        asm volatile(WG_ASM("0") : RW48("=f", d) : "r"(loA), "r"(loB), "n"(HIA), "n"(HIB), "n"(TA), "n"(TB));
#undef WG_ASM
}
template <int TA, int TB, uint32_t HIB, int ACC, uint32_t HIA = HI_SW128>
__device__ __forceinline__ void wgmma(float (&d)[32], uint32_t loA, uint32_t loB) {
#define WG_ASM(SD)                                                          \
    "{\n.reg .b64 da, db;\nmov.b64 da, {%32, %34};\nmov.b64 db, {%33, %35};\n" \
    "wgmma.mma_async.sync.aligned.m64n64k16.f32.bf16.bf16 "               \
    "{%0,%1,%2,%3,%4,%5,%6,%7,%8,%9,%10,%11,%12,%13,%14,%15,%16,%17,%18,%19,%20,%21,%22,%23,%24,%25,%26,%27,%28,%29,%30,%31}, da, db, " SD ", 1, 1, %36, %37;\n}"
    if constexpr (ACC == 1)
        asm volatile(WG_ASM("1") : RW32("+f", d) : "r"(loA), "r"(loB), "n"(HIA), "n"(HIB), "n"(TA), "n"(TB));
    else
        asm volatile(WG_ASM("0") : RW32("=f", d) : "r"(loA), "r"(loB), "n"(HIA), "n"(HIB), "n"(TA), "n"(TB));
#undef WG_ASM
}

__device__ __forceinline__ uint32_t pack_bf16(float lo, float hi) {
    uint32_t r;
    asm("cvt.rn.bf16x2.f32 %0, %1, %2;" : "=r"(r) : "f"(hi), "f"(lo));
    return r;
}
__device__ __forceinline__ float ex2(float x) {
    float r;
    asm("ex2.approx.ftz.f32 %0, %1;" : "=f"(r) : "f"(x));
    return r;
}
__device__ __forceinline__ void stsm4t(uint32_t a, uint32_t r0, uint32_t r1, uint32_t r2, uint32_t r3) {
    asm volatile("stmatrix.sync.aligned.m8n8.x4.trans.shared.b16 [%0], {%1,%2,%3,%4};" ::"r"(a), "r"(r0), "r"(r1), "r"(r2), "r"(r3)
                 : "memory");
}
__device__ __forceinline__ uint32_t lds_u(uint32_t a) {
    uint32_t v;
    asm volatile("ld.shared.u32 %0, [%1];" : "=r"(v) : "r"(a) : "memory");
    return v;
}
__device__ __forceinline__ uint4 lds_u4(uint32_t a) {
    uint4 v;
    asm volatile("ld.shared.v4.u32 {%0,%1,%2,%3}, [%4];" : "=r"(v.x), "=r"(v.y), "=r"(v.z), "=r"(v.w) : "r"(a) : "memory");
    return v;
}
__device__ __forceinline__ float2 lds_f2(uint32_t a) {
    float2 v;
    asm volatile("ld.shared.v2.f32 {%0,%1}, [%2];" : "=f"(v.x), "=f"(v.y) : "r"(a) : "memory");
    return v;
}
__device__ __forceinline__ void sts_f(uint32_t a, float v) { asm volatile("st.shared.f32 [%0], %1;" ::"r"(a), "f"(v) : "memory"); }
__device__ __forceinline__ void sts_u(uint32_t a, uint32_t v) { asm volatile("st.shared.u32 [%0], %1;" ::"r"(a), "r"(v) : "memory"); }
__device__ __forceinline__ void sts_f2(uint32_t a, float x, float y) {
    asm volatile("st.shared.v2.f32 [%0], {%1,%2};" ::"r"(a), "f"(x), "f"(y) : "memory");
}

template <bool ADD = false, bool SIG = false, int NR>
__device__ __forceinline__ void store_tile_t(const float (&d)[NR], uint32_t addr) {
    uint32_t p[NR / 2];
    if (ADD) {
#pragma unroll
        for (int j = 0; j < NR / 8; j++)
            asm volatile("ldmatrix.sync.aligned.m8n8.x4.trans.shared.b16 {%0,%1,%2,%3}, [%4];"
                         : "=r"(p[4 * j]), "=r"(p[4 * j + 1]), "=r"(p[4 * j + 2]), "=r"(p[4 * j + 3])
                         : "r"(addr + j * 2048)
                         : "memory");
    }
#pragma unroll
    for (int k = 0; k < NR / 2; k++)
        p[k] = ADD ? pack_bf16(d[2 * k] + __uint_as_float(p[k] << 16), d[2 * k + 1] + __uint_as_float(p[k] & 0xffff0000u))
                   : pack_bf16(d[2 * k], d[2 * k + 1]);
#pragma unroll
    for (int j = 0; j < NR / 8; j++) {
        stsm4t(addr + j * 2048, p[4 * j], p[4 * j + 1], p[4 * j + 2], p[4 * j + 3]);
        if (SIG && j == SIGJ) nb_arrive<NB_L, 160>();
    }
}

struct TrueT { static constexpr bool value = true; };
struct FalseT { static constexpr bool value = false; };

template <int V>
struct IntT { static constexpr int value = V; };

__device__ __forceinline__ uint32_t get_item(uint32_t sb, int it, uint32_t dl) {
    mbar_wait(sb + BAR_ITEM + it * 8, 0, dl);
    return lds_u(sb + OFF_ITEM + it * 4);
}
__device__ __forceinline__ uint32_t get_item_warp(uint32_t sb, int it, uint32_t dl) {
    return __shfl_sync(0xffffffffu, get_item(sb, it, dl), 0);
}

struct Ring {
    uint32_t slot, ph, dl;
    __device__ __forceinline__ void adv(uint32_t k) {
        slot += k;
        if (slot >= NSLOT) { slot -= NSLOT; ph ^= 1; }
    }
};

template <int K>
__device__ __forceinline__ void qk_step(float (&s)[80], uint32_t loK, uint32_t loQ) {
    wgmma<0, 0, HI_SW128, K != 0, HI_KV>(s, loK + (K >> 2) * 64 + (K & 3) * 2, loQ + (K >> 2) * (XS >> 4) + (K & 3) * 2);
}
template <int K0, int K1>
__device__ __forceinline__ void qk_steps(float (&s)[80], uint32_t loK, uint32_t loQ) {
    if constexpr (K0 < K1) {
        qk_step<K0>(s, loK, loQ);
        qk_steps<K0 + 1, K1>(s, loK, loQ);
    }
}
__device__ __forceinline__ uint32_t add_bf2(uint32_t a, uint32_t b) {
    uint32_t r;
    asm("add.rn.bf16x2 %0, %1, %2;" : "=r"(r) : "r"(a), "r"(b));
    return r;
}
__device__ __forceinline__ uint32_t fma_bf2(uint32_t a, uint32_t b, uint32_t c) {
    uint32_t r;
    asm("fma.rn.bf16x2 %0, %1, %2, %3;" : "=r"(r) : "r"(a), "r"(b), "r"(c));
    return r;
}
template <int J>
__device__ __forceinline__ void exp_block(const float (&s)[80], uint32_t (&k)[40], uint32_t pa, float mref) {
    if constexpr (J < 10) {
#pragma unroll
        for (int i = 4 * J; i < 4 * J + 4; i++)
            k[i] = pack_bf16(ex2(fmaf(s[2 * i], SM_C, -mref)), ex2(fmaf(s[2 * i + 1], SM_C, -mref)));
#pragma unroll
        for (int i = 0; i < 4; i++)
            asm volatile("stmatrix.sync.aligned.m8n8.x1.trans.shared.b16 [%0], {%1};" ::"r"(((i & 1) ? pa ^ 16 : pa) + J * 2048 + (i >> 1) * 1024),
                         "r"(k[4 * J + i])
                         : "memory");
        exp_block<J + 1>(s, k, pa, mref);
    }
}
__device__ __forceinline__ void sum_block(const uint32_t (&k)[40], float (&l)[10], uint32_t lane) {
    const bool b4 = lane & 16, b3 = lane & 8;
    uint32_t ps[20], t[10];
#pragma unroll
    for (int j = 0; j < 20; j++) ps[j] = add_bf2(k[2 * j], k[2 * j + 1]);
#pragma unroll
    for (int j = 0; j < 10; j++)
        t[j] = add_bf2(b4 ? ps[2 * j + 1] : ps[2 * j], __shfl_xor_sync(0xffffffffu, b4 ? ps[2 * j] : ps[2 * j + 1], 16));
#pragma unroll
    for (int i = 0; i < 5; i++) {
        const uint32_t a = b3 ? t[i + 5] : t[i], b = __shfl_xor_sync(0xffffffffu, b3 ? t[i] : t[i + 5], 8);
        l[2 * i] += __uint_as_float(a << 16) + __uint_as_float(b << 16);
        l[2 * i + 1] += __uint_as_float(a & 0xffff0000u) + __uint_as_float(b & 0xffff0000u);
    }
}
template <bool ADD>
__device__ __forceinline__ void sum_store(const float (&l)[10], uint32_t lane, uint32_t lxa) {
    const bool b2 = lane & 4;
    float t[5];
#pragma unroll
    for (int i = 0; i < 5; i++) t[i] = ADD ? __uint_as_float(lds_u(lxa + i * 64)) : 0.f;
#pragma unroll
    for (int i = 0; i < 5; i++)
        sts_f(lxa + i * 64, t[i] + (b2 ? l[2 * i + 1] : l[2 * i]) + __shfl_xor_sync(0xffffffffu, b2 ? l[2 * i] : l[2 * i + 1], 4));
}

__device__ __forceinline__ void fallback_unit(const Params& P, uint32_t e, uint32_t tid) {
    const uint32_t lane = tid & 31, br = IT_BR(e), b = IT_B(e), h = IT_H0(e);
    const __nv_bfloat162* wq = (const __nv_bfloat162*)(P.pwq[br] + h * 192) + lane;
    const __nv_bfloat162* kp = (const __nv_bfloat162*)(P.pk[br] + (size_t)(b * 32 + h) * 512 * 192) + lane;
    const __nv_bfloat162* vp = (const __nv_bfloat162*)(P.pv[br] + (size_t)(b * 32 + h) * 512 * 192) + lane;
#pragma unroll 1
    for (uint32_t qi = 0; qi < 40; qi++) {
        const uint32_t q = 4 * qi + (tid >> 5);
        const __nv_bfloat16* xr = P.px[br] + (size_t)(b * 160 + q) * 640;
        float a[6] = {0.f, 0.f, 0.f, 0.f, 0.f, 0.f};
#pragma unroll 2
        for (int k = 0; k < 640; k++) {
            const float xv = __bfloat162float(xr[k]);
#pragma unroll
            for (int i = 0; i < 3; i++) {
                const float2 wv = __bfloat1622float2(wq[(size_t)k * 3072 + i * 32]);
                a[2 * i] = fmaf(xv, wv.x, a[2 * i]);
                a[2 * i + 1] = fmaf(xv, wv.y, a[2 * i + 1]);
            }
        }
#pragma unroll
        for (int i = 0; i < 6; i++) a[i] = __bfloat162float(__float2bfloat16(a[i]));
        auto score = [&](int key) {
            float d = 0.f;
#pragma unroll
            for (int i = 0; i < 3; i++) {
                const float2 kv = __bfloat1622float2(kp[key * 96 + i * 32]);
                d = fmaf(a[2 * i], kv.x, fmaf(a[2 * i + 1], kv.y, d));
            }
#pragma unroll
            for (int o = 16; o > 0; o >>= 1) d += __shfl_xor_sync(0xffffffffu, d, o);
            return d;
        };
        float m = -INFINITY, o[6] = {0.f, 0.f, 0.f, 0.f, 0.f, 0.f}, sum = 0.f;
#pragma unroll 1
        for (int n = 0; n < 1024; n++) {
            const int key = n & 511;
            const float d = score(key);
            if (n < 512) {
                m = fmaxf(m, d);
            } else {
                const float p = ex2((d - m) * SM_C);
                sum += p;
#pragma unroll
                for (int i = 0; i < 3; i++) {
                    const float2 vv = __bfloat1622float2(vp[key * 96 + i * 32]);
                    o[2 * i] = fmaf(p, vv.x, o[2 * i]);
                    o[2 * i + 1] = fmaf(p, vv.y, o[2 * i + 1]);
                }
            }
        }
        const float inv = __fdividef(1.f, sum);
        __nv_bfloat16* op = (__nv_bfloat16*)ostash(IT_SLOT(e), b) + (q >> 5) * 256 + 2 * ((q & 31) >> 3) + (q & 1);
#pragma unroll
        for (int i = 0; i < 6; i++) {
            const uint32_t d = (i >> 1) * 64 + 2 * lane + (i & 1);
            op[(d >> 3) * 1280 + (d & 7) * 32 + ((((q & 7) >> 1) ^ ((d & 7) >> 1)) << 3)] = __float2bfloat16(o[i] * inv);
        }
    }
}

template <int W>
struct PendO {
    static constexpr int N = W == 0 ? 56 : 64;
    uint32_t v[N];
    unsigned char* gp;
    static __device__ __forceinline__ uint32_t toff() {
        const uint32_t t = tid_now();
        return ((t >> 5) & 3) * 5120 + ((t >> 2) & 7) * 64 + (((t ^ (t >> 3)) & 3) << 4);
    }
    uint32_t pend, sig, bad;
    static __device__ __forceinline__ void scale(uint32_t& x, uint32_t hi, uint32_t lo) {
        asm("{\n.reg .b32 t;\nmul.rn.bf16x2 t, %0, %2;\nfma.rn.bf16x2 %0, %0, %1, t;\n}" : "+r"(x) : "r"(hi), "r"(lo));
    }
    template <int I, int OFF>
    __device__ __forceinline__ void put() {
        asm volatile("{\n.reg .pred p;\nsetp.ne.u32 p, %6, 0;\n@p st.global.v4.b32 [%0+%5], {%1,%2,%3,%4};\n}" ::"l"(gp), "r"(v[I]),
                     "r"(v[I + 1]), "r"(v[I + 2]), "r"(v[I + 3]), "n"(OFF), "r"(pend)
                     : "memory");
    }
    __device__ __forceinline__ void verdict(uint32_t sb) {
        if (sig) {
            nb_sync<NB_VOTE + W, 160>();
            bad = __any_sync(0xffffffffu, lds_u(sb + OFF_FB) != 0);
            pend = !bad;
        }
    }
    template <int G, int H>
    __device__ __forceinline__ void half(uint32_t sb) {
        constexpr bool T2 = W == 0 ? G >= 3 : G < 3;
        constexpr int B = T2 ? 40 + 8 * (W == 0 ? G - 3 : G) : 0;
        const uint4 a = lds_u4(sb + OFF_LINV + G * 128 + H * 16 + (threadIdx.x & 3) * 32);
#pragma unroll
        for (int i = 2 * H; i < 8; i += 4) {
            scale(v[8 * G + i], a.x, a.y);
            scale(v[8 * G + i + 1], a.z, a.w);
            if (T2) {
                scale(v[B + i], a.x, a.y);
                scale(v[B + i + 1], a.z, a.w);
            }
        }
        if (H == 1) {
            put<8 * G, W * XS + G * 512>();
            put<8 * G + 4, W * XS + G * 512 + 2560>();
            if (T2) {
                put<B, 2 * XS + G * 512>();
                put<B + 4, 2 * XS + G * 512 + 2560>();
            }
            if (G == 4 && pend) nb_arrive<NB_ODONE, 288>();
        }
    }
    template <int G>
    __device__ __forceinline__ void step(uint32_t sb) {
        half<G, 0>(sb);
        half<G, 1>(sb);
    }
    __device__ __forceinline__ void clear() {
#pragma unroll
        for (int i = 0; i < N; i++) v[i] = 0;
        gp = nullptr;
        pend = 0;
        sig = 0;
        bad = 0;
    }
};

__device__ __forceinline__ uint32_t stsm_off() {
    const uint32_t tid = tid_now(), lane = tid & 31;
    return (lane >> 4) * 1024 + (lane & 7) * 128 + (((((tid >> 4) & 6) + ((lane >> 3) & 1)) ^ (lane & 7)) << 4);
}
__device__ __forceinline__ void q_ahead(float (&q0)[80], uint32_t sb, const Ring& rn, uint32_t phm, bool valid) {
    if (valid) {
        mbar_wait(sb + BAR_RFULL + rn.slot * 8, rn.ph, rn.dl);
        mbar_wait(sb + BAR_XFULL, phm & 1, rn.dl);
    }
    const uint32_t a = ((((sb + OFF_RING) & 0x3ffff) >> 4) | LO_LBO1) + rn.slot * (SLOT >> 4);
    const uint32_t b = (((sb + OFF_R) & 0x3ffff) >> 4) | LO_LBO1;
    wg_fence();
    wgmma<1, 0, HI_SW128, false>(q0, a, b);
#pragma unroll
    for (int k = 1; k < 4; k++) wgmma<1, 0, HI_SW128, true>(q0, a + (k >> 1) * 768 + (k & 1) * 128, b + k * 2);
    wg_commit();
}
template <int W, int KK>
__device__ __forceinline__ void qproj(float (&q0)[80], float (&q1)[80], uint32_t sb, Ring& r, uint32_t pslot, uint32_t phm,
                                      PendO<W>& po) {
    const uint32_t loR = (((sb + OFF_R) & 0x3ffff) >> 4) | LO_LBO1;
    const uint32_t loRing = (((sb + OFF_RING) & 0x3ffff) >> 4) | LO_LBO1;
    auto ready = [&](int k) {
        mbar_wait(sb + BAR_RFULL + r.slot * 8, r.ph, r.dl);
        mbar_wait(sb + BAR_XFULL + (k % 5) * 8, ((phm >> (k % 5)) ^ (k / 5)) & 1, r.dl);
    };
    auto release = [&]() {
        if (KK > 0) {
            wg_wait<1>();
            mbar_arrive_warp(sb + BAR_REMPTY + pslot * 8);
            if (KK <= 5) mbar_arrive_warp(sb + (BAR_XEMPTY + (KK - 1) * 8));
        }
    };
    if (KK == 0 && W == 1) ready(0);
    if (W == 1 && KK == QHOLD) {
        if (QHOLD == 7) {
            wg_wait<0>();
            nb_arrive<NB_PDONE, 256>();
        }
        nb_sync<NB_SDONE, 256>();
    }
    const uint32_t a = loRing + r.slot * (SLOT >> 4) + (W == 0 ? 0 : 512), b = loR + (KK % 5) * (XS >> 4);
    wg_fence();
    constexpr bool T0 = W == 1 || KK > 0;
    if (T0) wgmma<1, 0, HI_SW128, KK != 0>(q0, a, b);
    if (W == 0) wgmma<1, 0, HI_SW128, KK != 0 ? 1 : 2>(q1, a + 256, b);
#pragma unroll
    for (int k = 1; k < 4; k++) {
        if (T0) wgmma<1, 0, HI_SW128, true>(q0, a + (k >> 1) * 768 + (k & 1) * 128, b + k * 2);
        if (W == 0) wgmma<1, 0, HI_SW128, true>(q1, a + 256 + (k >> 1) * 768 + (k & 1) * 128, b + k * 2);
    }
    wg_commit();
    const uint32_t cslot = r.slot;
    r.adv(1);
    if (W == 0 || KK < QHOLD) release();
    if (KK == QST0) {
        po.verdict(sb);
        po.template half<0, 0>(sb);
    }
    if (KK < 9) ready(KK + 1);
    if (W == 1 && KK >= QHOLD) release();
    if (W == 1 && KK == 7 && QHOLD > 7) nb_arrive<NB_PDONE, 256>();
    if (KK == QST0) po.template half<0, 1>(sb);
    if constexpr (KK > QST0 && KK < QST0 + 5) po.template step<KK - QST0>(sb);
    if constexpr (KK < (W == 0 ? 7 : 9)) {
        qproj<W, KK + 1>(q0, q1, sb, r, cslot, phm, po);
    } else if constexpr (W == 1) {
        const uint32_t sta = sb + OFF_R + 2 * XS + stsm_off();
        wg_wait<0>();
        reg_fence(q0);
        store_tile_t<false, true>(q0, sta);
        mbar_arrive_warp(sb + BAR_REMPTY + cslot * 8);
    } else {
        const uint32_t s8 = r.slot, a8 = loRing + s8 * (SLOT >> 4);
        wg_fence();
#pragma unroll
        for (int k = 0; k < 4; k++) wgmma<1, 0, HI_SW128, true>(q0, a8 + (k >> 1) * 768 + (k & 1) * 128, loR + 3 * (XS >> 4) + k * 2);
        r.adv(1);
        ready(9);
        const uint32_t s9 = r.slot, a9 = loRing + s9 * (SLOT >> 4);
        r.adv(1);
        wg_fence();
#pragma unroll
        for (int k = 0; k < 4; k++) wgmma<1, 0, HI_SW128, true>(q0, a9 + (k >> 1) * 768 + (k & 1) * 128, loR + 4 * (XS >> 4) + k * 2);
        wg_commit();
        wg_wait<1>();
        mbar_arrive_warp(sb + BAR_REMPTY + cslot * 8);
        wg_fence();
#pragma unroll
        for (int k = 0; k < 8; k++)
            wgmma<1, 0, HI_SW128, true>(q1, (k < 4 ? a8 : a9) + 256 + ((k >> 1) & 1) * 768 + (k & 1) * 128,
                                        loR + (3 + (k >> 2)) * (XS >> 4) + (k & 3) * 2);
        wg_commit();
        nb_arrive<NB_SDONE, 256>();
        nb_sync<NB_PDONE, 256>();
        wg_wait<1>();
        reg_fence(q0);
        const uint32_t sta = sb + OFF_R + stsm_off();
        store_tile_t(q0, sta);
        sts_u(sb + OFF_GM + 4, r.slot);
        mbar_wait(sb + BAR_RFULL + r.slot * 8, r.ph, r.dl);
        wg_wait<0>();
        reg_fence(q1);
        mbar_arrive_warp(sb + BAR_REMPTY + s8 * 8);
        mbar_arrive_warp(sb + BAR_REMPTY + s9 * 8);
        store_tile_t(q1, sta + XS);
    }
}

template <int NR>
__device__ __forceinline__ void opack(const float (&o)[NR], uint32_t* v) {
#pragma unroll
    for (int g = 0; g < NR / 16; g++)
#pragma unroll
        for (int hh = 0; hh < 2; hh++)
#pragma unroll
            for (int t = 0; t < 4; t++) v[8 * g + 4 * hh + t] = pack_bf16(o[16 * g + 4 * t + 2 * hh], o[16 * g + 4 * t + 2 * hh + 1]);
}

template <bool IS_S>
__device__ __forceinline__ void op_item(uint32_t e, uint32_t sb, Ring& r, uint32_t& phm) {
    constexpr int T0 = IS_S ? 0 : 2;
    constexpr uint32_t BOFF = IS_S ? (3 * 512) >> 4 : 0;
    const uint32_t loRing = (((sb + OFF_RING) & 0x3ffff) >> 4) | LO_LBO1;
    const uint32_t loO = (((sb + OFF_R) & 0x3ffff) >> 4) | LO_OST;
    float c0[80], c1[80], c2[IS_S ? 32 : 48];
    const int T = 3 * (IT_H1(e) - IT_H0(e));
    uint32_t xs = 0;
    auto step = [&](auto first, auto half) {
        constexpr bool F = decltype(first)::value;
        constexpr uint32_t hf = decltype(half)::value;
        if (hf == 0) {
            mbar_wait(sb + BAR_XFULL + xs * 8, (phm >> xs) & 1, r.dl);
            phm ^= 1u << xs;
        }
        mbar_wait(sb + BAR_RFULL + r.slot * 8, r.ph, r.dl);
        const uint32_t a = loRing + r.slot * (SLOT >> 4), b = loO + xs * (XS >> 4) + hf * 640;
        wg_fence();
        wgmma<1, 1, HI_OST, !F>(c0, a + T0 * 128, b);
        wgmma<1, 1, HI_OST, !F>(c1, a + T0 * 128 + 128, b);
        wgmma<1, 1, HI_OST, !F>(c2, a + 512, b + BOFF);
        wgmma<1, 1, HI_OST, true>(c0, a + 640 + T0 * 128, b + 320);
        wgmma<1, 1, HI_OST, true>(c1, a + 640 + T0 * 128 + 128, b + 320);
        wgmma<1, 1, HI_OST, true>(c2, a + 640 + 512, b + 320 + BOFF);
        wg_commit();
    };
    step(TrueT{}, IntT<0>{});
#pragma unroll 1
    for (int t = 1;; t++) {
        uint32_t pslot = r.slot;
        r.adv(1);
        step(FalseT{}, IntT<1>{});
        wg_wait<1>();
        mbar_arrive_warp(sb + BAR_REMPTY + pslot * 8);
        if (t == T) break;
        pslot = r.slot;
        const uint32_t pxs = xs;
        r.adv(1);
        if (++xs == 5) xs = 0;
        step(FalseT{}, IntT<0>{});
        wg_wait<1>();
        mbar_arrive_warp(sb + BAR_REMPTY + pslot * 8);
        mbar_arrive_warp_if(sb + BAR_XEMPTY + pxs * 8, t + 4 < T);
    }
    wg_wait<0>();
    reg_fence(c0);
    reg_fence(c1);
    reg_fence(c2);
    mbar_arrive_warp(sb + BAR_REMPTY + r.slot * 8);
    r.adv(1);
    nb_sync<NB_OPEND, 256>();
    const uint32_t sta = sb + OFF_R + stsm_off();
    store_tile_t(c0, sta + T0 * XS);
    store_tile_t(c1, sta + (T0 + 1) * XS);
    store_tile_t(c2, sta + 4 * XS + (IS_S ? 96 * 128 : 0));
    fence_async_smem();
    nb_arrive<NB_ODONE, 288>();
}

__device__ __forceinline__ void on_item(uint32_t W, uint32_t e, uint32_t sb, Ring& r, uint32_t& phm) {
    const uint32_t loRing = (((sb + OFF_RING) & 0x3ffff) >> 4) | LO_LBO1;
    const uint32_t loO = (((sb + OFF_R) & 0x3ffff) >> 4) | LO_OST;
    float c[80];
    const int T = 3 * (IT_H1(e) - IT_H0(e));
    uint32_t xs = 0;
    auto step = [&](auto first) {
        constexpr bool F = decltype(first)::value;
        mbar_wait(sb + BAR_XFULL + xs * 8, (phm >> xs) & 1, r.dl);
        phm ^= 1u << xs;
        mbar_wait(sb + BAR_RFULL + r.slot * 8, r.ph, r.dl);
        const uint32_t a = loRing + r.slot * (SLOT >> 4) + W * 256, b = loO + xs * (XS >> 4);
        wg_fence();
        wgmma<1, 1, HI_OST, !F>(c, a, b);
#pragma unroll
        for (int k = 1; k < 4; k++) wgmma<1, 1, HI_OST, true>(c, a + (k >> 1) * 512 + (k & 1) * 128, b + k * 320);
        wg_commit();
    };
    step(TrueT{});
#pragma unroll 1
    for (int t = 1; t < T; t++) {
        const uint32_t pslot = r.slot, pxs = xs;
        r.adv(1);
        if (++xs == 5) xs = 0;
        step(FalseT{});
        wg_wait<1>();
        mbar_arrive_warp(sb + BAR_REMPTY + pslot * 8);
        mbar_arrive_warp_if(sb + BAR_XEMPTY + pxs * 8, t + 2 < T);
    }
    xs += 1 + W;
    if (xs >= 5) xs -= 5;
    mbar_wait(sb + BAR_XFULL + xs * 8, (phm >> xs) & 1, r.dl);
    wg_wait<0>();
    reg_fence(c);
    store_tile_t<true>(c, sb + OFF_R + xs * XS + stsm_off());
    fence_async_smem();
    nb_arrive<NB_ODONE, 288>();
}

template <int W>
__device__ __forceinline__ uint32_t qa_item(uint32_t e, uint32_t sb, Ring& r, uint32_t phm, PendO<W>& po, float (&q0)[80],
                                            float (&oa)[80], int it) {
    const uint32_t loR = (((sb + OFF_R) & 0x3ffff) >> 4) | LO_LBO1;
    const uint32_t loRing = (((sb + OFF_RING) & 0x3ffff) >> 4) | LO_LBO1;
    qproj<W, 0>(q0, oa, sb, r, 0, phm, po);
    fence_async_smem();
    TSD(W, 1);
    float s[80], ob[W == 0 ? 32 : 48], l[10];
    if (W == 1) {
        nb_arrive<NB_Q2, 256>();
        zero(oa);
        zero(ob);
        reg_fence(oa);
        reg_fence(ob);
    }
    const uint32_t lane = tid_now() & 31, sta = sb + OFF_R + stsm_off();
    auto pv = [&](auto first, uint32_t buf) {
        constexpr bool F = decltype(first)::value;
        mbar_wait(sb + BAR_RFULL + r.slot * 8, r.ph, r.dl);
        const uint32_t a = loRing + r.slot * (SLOT >> 4), b = loR + (3 + buf) * (XS >> 4);
        wg_fence();
        wgmma<1, 0, HI_SW128, F ? 2 : 1, HI_KV>(oa, a + W * 64, b);
        wgmma<1, 0, HI_SW128, !F, HI_KV>(ob, a + 128, b + (W == 0 ? (96 * 128) >> 4 : 0));
#pragma unroll
        for (int k = 1; k < 4; k++) {
            wgmma<1, 0, HI_SW128, true, HI_KV>(oa, a + W * 64 + k * 384, b + k * 2);
            wgmma<1, 0, HI_SW128, true, HI_KV>(ob, a + 128 + k * 384, b + (W == 0 ? (96 * 128) >> 4 : 0) + k * 2);
        }
        wg_commit();
    };
    zero(l);
    float mref;
    uint32_t kslot, vslot, nx = 0;
    auto tail = [&](auto first, int i) {
        constexpr bool rel_other = !decltype(first)::value;
        uint32_t ps[40];
        exp_block<0>(s, ps, sta + (3 + W) * XS, mref);
        if (rel_other) {
            wg_wait<0>();
            mbar_arrive_warp(sb + BAR_REMPTY + vslot * 8);
            if (W == 1) mbar_arrive_warp_if(sb + BAR_XEMPTY + 24, i == 3);
        }
        fence_async_smem();
        nb_arrive<NB_PFULL + W, 256>();
        TSD(W, 6 + 5 * i);
        if (W == 1) {
            if (XLATE >= 2) mbar_arrive_warp_if<2>(sb + BAR_XEMPTY + 8, i == 3);
            if (XLATE >= 1) mbar_arrive_warp_if<2>(sb + BAR_XEMPTY + 16, i == 3);
        }
        if (rel_other || !PV0FIRST) {
            mbar_wait(sb + BAR_RFULL + r.slot * 8, r.ph, r.dl);
            sum_block(ps, l, lane);
        }
        if (W == 0 && i == 3) nx = get_item_warp(sb, it + 1, r.dl);
        TSD(W, 7 + 5 * i);
        if (LASTORD && W == 0 && i == 3) nb_sync<NB_PDONE, 256>();
        else nb_sync<NB_W + W, 128>();
        pv(first, W);
        if (!rel_other && PV0FIRST) sum_block(ps, l, lane);
        TSD(W, 8 + 5 * i);
    };
    if (W == 0) {
        nb_sync<NB_QK, 160>();
        TSD(W, 2);
        wg_fence();
        qk_steps<0, 8>(s, loRing + r.slot * (SLOT >> 4), loR);
        nb_sync<NB_Q2, 256>();
        qk_steps<8, 12>(s, loRing + r.slot * (SLOT >> 4), loR);
        wg_commit();
        nb_arrive<NB_Q01, 256>();
        TSD(W, 4);
        nb_sync<NB_REF, 160>();
        mref = __uint_as_float(lds_u(sb + OFF_GM));
        wg_wait<0>();
        reg_fence(s);
        mbar_arrive_warp<2>(sb + BAR_REMPTY + r.slot * 8);
        r.adv(2);
        TSD(W, 5);
        tail(TrueT{}, 0);
    } else {
        nb_sync<NB_Q01, 256>();
    }
#pragma unroll 1
    for (int i = (W == 0 ? 1 : 0); i < 4; i++) {
        const uint32_t pvslot = r.slot;
        r.adv(1);
        kslot = r.slot;
        mbar_wait(sb + BAR_RFULL + r.slot * 8, r.ph, r.dl);
        wg_fence();
        qk_steps<0, 4>(s, loRing + r.slot * (SLOT >> 4), loR);
        if (W == 1) wg_commit();
        qk_steps<4, 12>(s, loRing + r.slot * (SLOT >> 4), loR);
        wg_commit();
        wg_wait<1>();
        if (W == 1) mbar_arrive_warp_if(sb + BAR_XEMPTY + 0, i == 3);
        mbar_arrive_warp_if(sb + BAR_REMPTY + pvslot * 8, W == 0 || i > 0);
        r.adv(1);
        vslot = r.slot;
        TSD(W, 4 + 5 * i);
        nb_sync<NB_PFULL + (W ^ 1), 256>();
        pv(FalseT{}, W ^ 1);
        if (LASTORD && W == 1 && i == 3) nb_arrive<NB_PDONE, 256>();
        if (W == 1) mref = __uint_as_float(lds_u(sb + OFF_GM));
        wg_wait<1>();
        reg_fence(s);
        mbar_arrive_warp<2>(sb + BAR_REMPTY + kslot * 8);
        if (W == 0) mbar_arrive_warp_if(sb + BAR_XEMPTY + 0, i == 3);
        if (W == 1) {
            if (XLATE < 2) mbar_arrive_warp_if<2>(sb + BAR_XEMPTY + 8, i == 3);
            if (XLATE < 1) mbar_arrive_warp_if<2>(sb + BAR_XEMPTY + 16, i == 3);
        }
        r.adv(W == 1 && i == 3 ? 1 : 2);
        TSD(W, 5 + 5 * i);
        tail(FalseT{}, i);
    }
    if (W == 1) nx = get_item_warp(sb, it + 1, r.dl);
    if (W == 0) {
        Ring rn = r;
        rn.adv(2);
        q_ahead(q0, sb, rn, phm, IT_TYPE(nx) == IT_QA);
        TSD(W, 25);
    }
    const uint32_t w = (tid_now() >> 5) & 3;
    const uint32_t lxa = sb + OFF_LX + w * 640 + (((lane & 8) ? 80 : 0) + ((lane >> 1) & 8) + 2 * (lane & 3) + ((lane >> 2) & 1)) * 4;
    po.gp = ostash(IT_SLOT(e), IT_B(e)) + po.toff();
    po.sig = 1;
    if (W == 0) {
        sum_store<false>(l, lane, lxa);
        nb_arrive<NB_LX, 256>();
        wg_wait<1>();
        mbar_arrive_warp(sb + BAR_REMPTY + r.slot * 8);
        mbar_arrive_warp(sb + BAR_XEMPTY + 24);
        r.adv(1);
        nb_sync<NB_PFULL + 1, 256>();
        pv(FalseT{}, 1);
    } else {
        nb_sync<NB_LX, 256>();
        sum_store<true>(l, lane, lxa);
        nb_arrive<NB_L, 160>();
    }
    TSD(W, 24);
    wg_wait<0>();
    reg_fence(oa);
    reg_fence(ob);
    mbar_arrive_warp(sb + BAR_REMPTY + r.slot * 8);
    mbar_arrive_warp(sb + BAR_XEMPTY + 32);
    r.adv(1);
    opack(ob, po.v + 40);
    opack(oa, po.v);
    return nx;
}

template <int W>
__device__ __forceinline__ uint32_t qa_run(const Params& P, uint32_t e, uint32_t sb, Ring& r, uint32_t phm, int& it) {
    PendO<W> po;
    po.clear();
    float q0[80], oa[80];
    if (W == 0) {
        zero(oa);
        q_ahead(q0, sb, r, phm, true);
        wg_wait<0>();
    }
#pragma unroll 1
    do {
        TS(W, 0);
        if (W == 0) TS_ITEM(e);
        e = qa_item<W>(e, sb, r, phm, po, q0, oa, it);
        TS(W, 31);
        it++;
    } while (IT_TYPE(e) == IT_QA && !po.bad);
#pragma unroll 1
    for (int m = po.bad ? 2 : 1; m > 0; m--) {
        if (m == 1) {
            po.verdict(sb);
            po.template step<0>(sb);
            po.template step<1>(sb);
            po.template step<2>(sb);
            po.template step<3>(sb);
            po.template step<4>(sb);
        }
        if (po.bad) {
            if (W == 0) fallback_unit(P, lds_u(sb + OFF_ITEM + (it - m) * 4), tid_now() & 127);
            __syncwarp();
            nb_sync<NB_ODONE, 288>();
        }
    }
    return e;
}

__device__ __forceinline__ void consumer(const Params& P, uint32_t W, uint32_t sb, uint32_t dl) {
    int it = 0;
    Ring r{0, 0, dl};
    uint32_t phm = 0;
    uint32_t e = get_item_warp(sb, 0, dl);
#pragma unroll 1
    while (true) {
        if (IT_TYPE(e) == IT_QA) e = W == 0 ? qa_run<0>(P, e, sb, r, phm, it) : qa_run<1>(P, e, sb, r, phm, it);
        if (e == 0) break;
        if (IT_TYPE(e) == IT_QA) continue;
        TS(W, 0);
        if (W == 0) TS_ITEM(e);
        if (IT_TYPE(e) == IT_ON) on_item(W, e, sb, r, phm);
        else if (W == 0) op_item<true>(e, sb, r, phm);
        else op_item<false>(e, sb, r, phm);
        TS(W, 31);
        e = get_item_warp(sb, ++it, dl);
    }
    TS_DUMP(W);
}

__global__ void __cluster_dims__(2, 1, 1) __launch_bounds__(384, 1) fused_kernel(const __grid_constant__ Params P) {
    extern __shared__ __align__(1024) unsigned char smem_raw[];
    const uint32_t sb = (uint32_t)__cvta_generic_to_shared(smem_raw);
    const uint32_t warp = __shfl_sync(0xffffffffu, threadIdx.x >> 5, 0), wgid = warp >> 2;
    const uint32_t cta = blockIdx.x;
    const uint32_t dl = deadline();

    if (threadIdx.x == 128) {
#pragma unroll
        for (int i = 0; i < NSLOT; i++) {
            mbar_init(sb + BAR_RFULL + i * 8, 1);
            mbar_init(sb + BAR_REMPTY + i * 8, 8);
            mbar_init(sb + BAR_XFULL + i * 8, 1);
            mbar_init(sb + BAR_XEMPTY + i * 8, 8);
        }
        asm volatile("fence.mbarrier_init.release.cluster;" ::: "memory");
        fence_async_smem();
    } else if (threadIdx.x == 160) {
#pragma unroll
        for (int i = 0; i < NSLOT + MAXI; i++) mbar_init(sb + BAR_PRDY + i * 8, 1);
        asm volatile("fence.mbarrier_init.release.cluster;" ::: "memory");
    } else if (threadIdx.x == 0) {
        sts_u(sb + OFF_ITEM, P.cl[cta >> 1].items[0] ? P.cl[cta >> 1].items[0] + 8 * (cta & 1) : 0);
        sts_u(sb + OFF_FB, P.cl[cta >> 1].delay);
    } else if (threadIdx.x == 64) {
        if (sb & 1023) __trap();
        asm volatile("prefetch.tensormap [%0];" ::"l"(&P.wq[0]) : "memory");
        asm volatile("prefetch.tensormap [%0];" ::"l"(&P.x[0]) : "memory");
    }
    __syncthreads();
    {
        const int it = 0;
        if (wgid == 1) TS(0, 30);
    }
    asm volatile("barrier.cluster.arrive.relaxed.aligned;" ::: "memory");
    if (warp < 3) {
        const uint32_t e = __shfl_sync(0xffffffffu, lds_u(sb + OFF_ITEM), 0), d = lds_u(sb + OFF_FB);
        const uint64_t pol = mkpol<POL_W>();
        const bool isx = warp == 1, lead = (threadIdx.x & 31) == 0;
        uint32_t t0, t1;
        asm volatile("mov.u32 %0, %%clock;" : "=r"(t0));
        do {
            asm volatile("mov.u32 %0, %%clock;" : "=r"(t1));
        } while (t1 - t0 < d);
        __syncwarp();
#pragma unroll 1
        for (int n = 0; n < (e ? NSLOT : 0); n++) {
            const uint32_t bar = sb + (isx ? BAR_XFULL : BAR_RFULL) + n * 8;
            if (lead) {
                if (warp < 2) mbar_expect(bar, isx ? XS : SLOT);
                tma3(sb + (isx ? OFF_R + n * XS : OFF_RING + n * SLOT + warp * (SLOT / 4)), isx ? &P.x[0] : &P.wq[0],
                     isx ? IT_B(e) * 160 : n * 64 + warp * 16, isx ? n : IT_H0(e) * 3, bar, pol);
            }
        }
        if (threadIdx.x == 0) asm volatile("mbarrier.arrive.shared::cta.b64 _, [%0];" ::"r"(sb + BAR_ITEM) : "memory");
        __syncwarp();
    }

    if (wgid == 0) {
        asm volatile("setmaxnreg.dec.sync.aligned.u32 24;");
        if (warp == 0) {
            const bool lead = threadIdx.x == 0;
            const uint64_t pol_first = mkpol<1>(), pol_norm = mkpol<POL_W>();
            uint32_t e = __shfl_sync(0xffffffffu, lds_u(sb + OFF_ITEM), 0);
            asm volatile("barrier.cluster.wait.aligned;" ::: "memory");
            unsigned int* const ticket = &g_ticket[next_epoch(0) & 1];
            const uint32_t rank = cta & 1;
            uint32_t peer;
            asm volatile("mapa.shared::cluster.u32 %0, %1, %2;" : "=r"(peer) : "r"(sb), "r"(rank ^ 1));
            Ring r{0, 0, dl};
            uint32_t pm = 0;
            auto load_w = [&](const CUtensorMap* m, int row, int blk, uint32_t half_bytes) {
                mbar_wait(sb + BAR_REMPTY + r.slot * 8, r.ph, dl);
                if (lead) {
                    mbar_expect(sb + BAR_RFULL + r.slot * 8, 2 * half_bytes);
                    asm volatile("mbarrier.arrive.shared::cluster.b64 _, [%0];" ::"r"(peer + BAR_PRDY + r.slot * 8) : "memory");
                }
                mbar_wait(sb + BAR_PRDY + r.slot * 8, (pm >> r.slot) & 1, dl);
                pm ^= 1u << r.slot;
                if (lead) tma3_mc(sb + OFF_RING + r.slot * SLOT + rank * half_bytes, m, row, blk, sb + BAR_RFULL + r.slot * 8, pol_norm);
                r.adv(1);
            };
#pragma unroll 1
            for (int it = 0; e != 0; it++) {
                uint32_t nx = 0, tk = 0;
                if (rank == 0 && IT_TYPE(e) != IT_ON && it + 2 < MAXI) nx = it + 1 < NSTAT ? P.cl[cta >> 1].items[it + 1] : IT_DYN;
                const uint32_t br = IT_BR(e);
                if (IT_TYPE(e) == IT_QA) {
                    const uint32_t h = IT_H0(e);
#pragma unroll 1
                    for (int kk = it ? 0 : NSLOT; kk < 10; kk++) load_w(&P.wq[br], kk * 64 + rank * 32, h * 3, SLOT / 2);
                    const int grp0 = (IT_B(e) * 32 + h) * 64;
#pragma unroll 1
                    for (int n = 0; n < 16; n++) {
                        if (n == 13 && nx == IT_DYN && lead) tk = atomicAdd(ticket, 1);
                        const bool isv = n == 15 || (n > 0 && !(n & 1));
                        const int j = n == 15 ? 7 : isv ? (n - 2) >> 1 : (n + 1) >> 1;
                        mbar_wait(sb + BAR_REMPTY + r.slot * 8, r.ph, dl);
                        if (lead) {
                            mbar_expect(sb + BAR_RFULL + r.slot * 8, SLOT);
                            asm volatile(
                                "cp.async.bulk.tensor.4d.shared::cluster.global.mbarrier::complete_tx::bytes.L2::cache_hint"
                                " [%0], [%1, {%3,%3,%3,%4}], [%2], %5;" ::"r"(sb + OFF_RING + r.slot * SLOT),
                                "l"(isv ? &P.v[br] : &P.k[br]), "r"(sb + BAR_RFULL + r.slot * 8), "r"(0), "r"(grp0 + j * 8), "l"(pol_first)
                                : "memory");
                        }
                        r.adv(1);
                    }
                } else {
                    const bool wide = IT_TYPE(e) == IT_OP;
                    const int step = wide ? 32 : 64, r1 = IT_H1(e) * 192;
#pragma unroll 1
                    for (int row = IT_H0(e) * 192 + rank * (step >> 1); row < r1; row += step)
                        load_w(wide ? &P.wo[br] : &P.won[br], row, IT_HALF(e) * (wide ? 5 : 2), wide ? XS / 2 : 8192);
                    if (nx == IT_DYN && lead) tk = atomicAdd(ticket, 1);
                }
                if (rank == 0) {
                    if (nx == IT_DYN) {
                        tk = __shfl_sync(0xffffffffu, tk, 0);
                        nx = tk < P.nlist ? P.list[tk] : 0;
                    }
                    e = nx;
                    if (lead) {
                        asm volatile("st.async.weak.shared::cluster.mbarrier::complete_tx::bytes.b32 [%0], %1, [%2];" ::"r"(
                                         peer + OFF_ITEM + 4 + it * 4),
                                     "r"(e ? e + 8 : 0), "r"(peer + BAR_ITEM + 8 + it * 8)
                                     : "memory");
                        sts_u(sb + OFF_ITEM + 4 + it * 4, e);
                        asm volatile("mbarrier.arrive.shared::cta.b64 _, [%0];" ::"r"(sb + BAR_ITEM + 8 + it * 8) : "memory");
                    }
                } else {
                    if (lead) mbar_expect(sb + BAR_ITEM + 8 + it * 8, 4);
                    e = get_item_warp(sb, it + 1, dl);
                }
            }
        } else if (warp == 1) {
            const uint64_t pol_norm = mkpol<POL_X>(), pol_o = mkpol<POL_O>();
            const bool lead = threadIdx.x == 32;
            uint32_t phm = 0, epoch = 0;
#pragma unroll 1
            for (int it = 0;; it++) {
                const uint32_t e = get_item_warp(sb, it, dl);
                if (it == 1 || (it == 0 && e == 0)) epoch = next_epoch(1);
                if (e == 0) break;
                const uint32_t br = IT_BR(e);
                uint32_t xs = 0;
                auto acquire = [&]() {
                    mbar_wait(sb + BAR_XEMPTY + xs * 8, (phm >> xs) & 1, dl);
                    phm ^= 1u << xs;
                    if (lead) mbar_expect(sb + BAR_XFULL + xs * 8, XS);
                };
                if (IT_TYPE(e) == IT_QA) {
#pragma unroll 1
                    for (int kk = it ? 0 : 5; kk < 10; kk++) {
                        acquire();
                        if (lead) tma3(sb + OFF_R + xs * XS, &P.x[br], IT_B(e) * 160, kk, sb + BAR_XFULL + xs * 8, pol_norm);
                        if (++xs == 5) xs = 0;
                    }
                } else {
                    const unsigned int* fp = g_flag + (br * 16 + IT_B(e)) * 64 + (threadIdx.x & 31);
                    uint32_t hm = 0, pm = 0;
                    auto poll = [&](uint32_t hneed, uint32_t pneed) {
                        if ((hm & hneed) == hneed && (pm & pneed) == pneed) return;
                        uint32_t n = 0;
                        do {
                            uint32_t a, b;
                            asm volatile("ld.acquire.gpu.global.u32 %0, [%2];\nld.acquire.gpu.global.u32 %1, [%2+128];"
                                         : "=r"(a), "=r"(b) : "l"(fp) : "memory");
                            hm = __ballot_sync(0xffffffffu, a == epoch);
                            pm = __ballot_sync(0xffffffffu, b == epoch);
                            if (++n > 0x1000000) __trap();
                        } while ((hm & hneed) != hneed || (pm & pneed) != pneed);
                        __syncwarp();
                        asm volatile("fence.proxy.async;" ::: "memory");
                    };
#pragma unroll 1
                    for (uint32_t h = IT_H0(e); h < IT_H1(e); h++) {
                        poll(1u << h, 0);
                        const unsigned char* src = ostash(P.slot[br * 32 + h], IT_B(e));
#pragma unroll 1
                        for (int t = 0; t < 3; t++) {
                            acquire();
                            if (lead) bulk_load(sb + OFF_R + xs * XS, src + t * XS, XS, sb + BAR_XFULL + xs * 8, pol_o);
                            if (++xs == 5) xs = 0;
                        }
                        if (IT_TYPE(e) == IT_OP && h >= 1) {
                            const uint32_t x1 = xs == 4 ? 0 : xs + 1;
                            mbar_wait(sb + BAR_XFULL + xs * 8, (phm >> xs) & 1, dl);
                            mbar_wait(sb + BAR_XFULL + x1 * 8, (phm >> x1) & 1, dl);
                            if (lead)
                                asm volatile("st.relaxed.gpu.global.u32 [%0], %1;" ::"l"(fp + 34 + IT_HALF(e)), "r"(epoch * 64 + h) : "memory");
                        }
                    }
                    if (IT_TYPE(e) == IT_ON) {
                        poll(0, IT_HALF(e) < 2 ? 1 : IT_HALF(e) == 2 ? 3 : 2);
#pragma unroll 1
                        for (uint32_t tile = 2 * IT_HALF(e); tile < 2 * IT_HALF(e) + 2; tile++) {
                            acquire();
                            if (lead)
                                asm volatile(
                                    "cp.async.bulk.tensor.5d.shared::cluster.global.mbarrier::complete_tx::bytes [%0], [%1, {%3,%5,%5,%5,%4}], [%2];" ::"r"(
                                        sb + OFF_R + xs * XS),
                                    "l"(&P.out), "r"(sb + BAR_XFULL + xs * 8), "r"(br * 640 + tile * 64), "r"(IT_B(e) * 5), "r"(0)
                                    : "memory");
                            if (++xs == 5) xs = 0;
                        }
                    }
                }
            }
        } else if (warp == 2) {
            asm volatile("barrier.cluster.wait.aligned;" ::: "memory");
            const uint32_t epoch = next_epoch(2);
            if (cta == 0) g_ticket[(epoch + 1) & 1] = 0;
#pragma unroll 1
            for (int it = 0;; it++) {
                const uint32_t e = get_item_warp(sb, it, dl);
                if (e == 0) break;
                nb_sync<NB_ODONE, 288>();
                if (threadIdx.x == 64) {
                    const uint32_t bb = IT_BR(e) * 16 + IT_B(e);
                    if (IT_TYPE(e) != IT_QA) {
                        const bool wide = IT_TYPE(e) == IT_OP;
                        if (wide)
                            asm volatile("st.relaxed.gpu.global.u32 [%0], %1;" ::"l"(&g_flag[bb * 64 + 34 + IT_HALF(e)]),
                                         "r"(epoch * 64 + IT_H1(e))
                                         : "memory");
                        const int cc0 = IT_BR(e) * 640 + IT_HALF(e) * (wide ? 320 : 128);
                        uint32_t xs = wide ? 0 : (3 * (IT_H1(e) - IT_H0(e))) % 5;
#pragma unroll 1
                        for (int m = 0; m < (wide ? 5 : 2); m++) {
                            asm volatile("cp.async.bulk.tensor.5d.global.shared::cta.bulk_group [%0, {%2,%4,%4,%4,%3}], [%1];" ::"l"(&P.out),
                                         "r"(sb + OFF_R + xs * XS), "r"(cc0 + m * 64), "r"((int)IT_B(e) * 5), "r"(0)
                                         : "memory");
                            asm volatile("cp.async.bulk.commit_group;" ::: "memory");
                            if (wide && m >= STLAG) {
                                asm volatile("cp.async.bulk.wait_group.read %0;" ::"n"(STLAG) : "memory");
                                asm volatile("mbarrier.arrive.shared::cta.b64 _, [%0], 8;" ::"r"(sb + BAR_XEMPTY + (m - STLAG) * 8) : "memory");
                            }
                            if (++xs == 5) xs = 0;
                        }
                        if (wide && STLAG) {
                            asm volatile("cp.async.bulk.wait_group.read 0;" ::: "memory");
                            asm volatile("mbarrier.arrive.shared::cta.b64 _, [%0], 8;" ::"r"(sb + BAR_XEMPTY + 32) : "memory");
                        }
                        if (IT_PART(e)) {
                            asm volatile("cp.async.bulk.wait_group 0;" ::: "memory");
                            asm volatile("fence.proxy.async;" ::: "memory");
                        }
                    }
                    if (IT_TYPE(e) == IT_QA || IT_PART(e)) {
                        unsigned int* f = &g_flag[bb * 64 + (IT_TYPE(e) == IT_QA ? IT_H0(e) : 32 + IT_HALF(e))];
                        asm volatile("st.release.gpu.global.u32 [%0], %1;" ::"l"(f), "r"(epoch) : "memory");
                    }
                }
                __syncwarp();
            }
            if (threadIdx.x == 64) asm volatile("cp.async.bulk.wait_group 0;" ::: "memory");
            __syncwarp();
            asm volatile("barrier.cluster.arrive.relaxed.aligned;\nbarrier.cluster.wait.aligned;" ::: "memory");
        } else {
            const uint32_t lane = threadIdx.x & 31, p = lane >> 2;
            const uint32_t epoch = next_epoch(3);
#pragma unroll 1
            for (int it = 0;; it++) {
                const uint32_t e = get_item_warp(sb, it, dl);
                if (e == 0) break;
                if (IT_TYPE(e) != IT_QA) continue;
                nb_sync<NB_QK, 160>();
                const uint32_t co = (((lane & 3) * 2) ^ p) << 4;
                const uint32_t ka = sb + OFF_RING + lds_u(sb + OFF_GM + 4) * SLOT + p * (3072 + 128) + co;
                const uint32_t qa = sb + OFF_R + p * 128 + co;
                uint32_t acc = 0;
#pragma unroll 1
                for (int c = 0; c < 3; c++) {
                    if (c == 2) nb_sync<NB_L, 160>();
                    const uint4 k0 = lds_u4(ka + c * 1024), q0 = lds_u4(qa + c * XS);
                    acc = fma_bf2(k0.x, q0.x, fma_bf2(k0.y, q0.y, fma_bf2(k0.z, q0.z, fma_bf2(k0.w, q0.w, acc))));
                    const uint4 k1 = lds_u4((ka + c * 1024) ^ 16), q1 = lds_u4((qa + c * XS) ^ 16);
                    acc = fma_bf2(k1.x, q1.x, fma_bf2(k1.y, q1.y, fma_bf2(k1.z, q1.z, fma_bf2(k1.w, q1.w, acc))));
                }
                float d = __uint_as_float(acc << 16) + __uint_as_float(acc & 0xffff0000u);
                d += __shfl_xor_sync(0xffffffffu, d, 1);
                d += __shfl_xor_sync(0xffffffffu, d, 2);
                int key = __float_as_int(d);
                key ^= (key >> 31) & 0x7fffffff;
                key = __reduce_max_sync(0xffffffffu, key);
                key ^= (key >> 31) & 0x7fffffff;
                sts_f(sb + OFF_GM, fmaf(__int_as_float(key), SM_C, 16.f));
                nb_arrive<NB_REF, 160>();
                if (IT_DEP(e)) {
                    const uint32_t g = IT_DEP(e) - 1, need = epoch * 64 + (g & 31) + 1;
                    const unsigned int* cp = &g_flag[((g >> 5) * 16 + IT_B(e)) * 64 + 34 + (lane & 1)];
                    for (uint32_t n = 0;; n++) {
                        uint32_t v;
                        asm volatile("ld.acquire.gpu.global.u32 %0, [%1];" : "=r"(v) : "l"(cp) : "memory");
                        if (__all_sync(0xffffffffu, v - need < 64)) break;
                        if (n > 0x800000) __trap();
                        __nanosleep(500);
                    }
                }
                nb_sync<NB_L, 160>();
                bool bad = false;
#pragma unroll
                for (int c = 0; c < 5; c++) {
                    const uint32_t la = sb + OFF_LX + (c * 32 + lane) * 4;
                    const float v = (__uint_as_float(lds_u(la)) + __uint_as_float(lds_u(la + 640))) +
                                    (__uint_as_float(lds_u(la + 1280)) + __uint_as_float(lds_u(la + 1920)));
                    const float inv = __fdividef(1.f, v);
                    const uint32_t hi = pack_bf16(inv, 0.f), lo = pack_bf16(inv - __uint_as_float(hi << 16), 0.f);
                    const uint32_t ia = sb + OFF_LINV + c * 128 + ((lane >> 1) & 3) * 32 + (lane >> 3) * 8 + (lane & 1) * 2;
                    asm volatile("st.shared.u16 [%0], %1;\nst.shared.u16 [%0+4], %2;" ::"r"(ia), "h"((unsigned short)hi), "h"((unsigned short)lo) : "memory");
                    bad |= !(v >= 5.421010862e-20f && v <= 7.9228163e28f);
                }
                sts_u(sb + OFF_FB, __any_sync(0xffffffffu, bad));
                nb_arrive<NB_VOTE, 160>();
                nb_arrive<NB_VOTE + 1, 160>();
            }
        }
    } else {
        asm volatile("setmaxnreg.inc.sync.aligned.u32 240;");
        consumer(P, wgid - 1, sb, dl);
    }
}

typedef CUresult (*EncFn)(CUtensorMap*, CUtensorMapDataType, cuuint32_t, void*, const cuuint64_t*, const cuuint64_t*,
                          const cuuint32_t*, const cuuint32_t*, CUtensorMapInterleave, CUtensorMapSwizzle,
                          CUtensorMapL2promotion, CUtensorMapFloatOOBfill);

void make_map3(EncFn enc, CUtensorMap* m, void* p, uint64_t rows, uint64_t rowbytes, uint64_t nblk, uint32_t boxrows,
               uint32_t boxblk) {
    cuuint64_t dims[3] = {64, rows, nblk};
    cuuint64_t str[2] = {rowbytes, 128};
    cuuint32_t box[3] = {64, boxrows, boxblk};
    cuuint32_t es[3] = {1, 1, 1};
    enc(m, CU_TENSOR_MAP_DATA_TYPE_BFLOAT16, 3, p, dims, str, box, es, CU_TENSOR_MAP_INTERLEAVE_NONE,
        CU_TENSOR_MAP_SWIZZLE_128B, CU_TENSOR_MAP_L2_PROMOTION_NONE, CU_TENSOR_MAP_FLOAT_OOB_FILL_NONE);
}

constexpr int tune(const char*, int def) { return def; }

void build_schedule(Params& P) {
    const int mode = tune("MODE", 4), dmax = tune("DMAX", 24900), n0 = tune("N0", 11), odmax = tune("ODMAX", 0), d1 = tune("D1", 0);
    const int H0[8] = {19, 20, 21, 23, 23, 24, 25, 25}, P0[8] = {367, 340, 338, 331, 341, 339, 331, 334};
    const int ra = tune("RA", 10), ga = tune("GA", 17), rb = tune("RB", 11), g1 = tune("G1", 58);
    int dep[64];
    for (int g = 0, ns = 0, live = 0; g < 64; g++) {
        const bool fresh = mode < 3 || g >= g1 || live < (g < ga ? ra : rb);
        dep[g] = fresh ? 0 : g - live + 1;
        P.slot[g] = fresh ? ns++ : P.slot[g - live];
        live += fresh;
    }
    int H[8], pos[8], psum = 0;
    for (int b = 0; b < 8; b++) {
        const char nh[3] = {'H', (char)('0' + b), 0}, np[3] = {'P', (char)('0' + b), 0};
        H[b] = tune(nh, H0[b]);
        pos[b] = tune(np, P0[b]);
        psum += pos[b];
    }
    const int sk = tune("SK", 10), g0 = tune("G0", 20), g2 = tune("G2", 40);
    int ord[512], nxt[8] = {0, 0, 0, 0, 0, 0, 0, 0};
    for (int k = 0; k < 512; k++) {
        int best = -1;
        float bkey = 0.f;
        for (int b = 0; b < 8; b++) {
            const int g = nxt[b];
            if (g == 64) continue;
            const float w = g < g0 ? 0.f : g < 32 ? (g - g0) / (32.f - g0) : g < g2 ? 1.f : (64 - g) / (64.f - g2);
            const float key = g + w * sk * 0.1f * (pos[b] - psum / 8.f) / 8.f;
            if (best < 0 || key < bkey) best = b, bkey = key;
        }
        ord[k] = nxt[best]++ * 8 + best;
        const int d = dep[ord[k] >> 3];
        if (d > 32) {
            if (pos[best] > k) pos[best] = k;
            if (H[best] < d - 32) H[best] = d - 32;
        }
    }
    int u = 0;
    auto unit = [&]() {
        const int v = ord[u++];
        return mk_item(IT_QA, v >> 8, (v & 7) * 2, (v >> 3) & 31, P.slot[v >> 3], 0) | (dep[v >> 3] << 23);
    };
    int qa[NCL], nq = 0, op[NCL], no = 0;
    for (int c = 0; c < NCL; c++) {
        P.cl[c].delay = 0;
        for (int i = 0; i < NSTAT; i++) P.cl[c].items[i] = 0;
        if (mode >= 3 && c < 64 && (c & 3) == 3) op[no++] = c;
        else if (mode != 2 || (c & 3) == 0) qa[nq++] = c;
    }
    for (int t = 0; t < no; t++) {
        P.cl[op[t]].items[1] = mk_item(IT_OP, 0, t & ~1, 0, 32, t & 1);
        P.cl[op[t]].items[2] = IT_DYN;
        P.cl[op[t]].delay = tune("OD0", 0) + t * odmax / 16;
    }
    for (int k = 0; k < nq; k++) {
        const int c = qa[(k * 19) % nq];
        P.cl[c].items[1] = P.cl[c].items[2] = IT_DYN;
        P.cl[c].delay = k < n0 ? k * tune("J0", 0) : d1 + (dmax - d1) * (k + 1 - n0) / (nq - n0);
    }
    if (tune("OFIRST", 0))
        for (int t = 0; t < no; t++) P.cl[op[t]].items[0] = unit();
    for (int k = u; k < no + nq; k++) {
        int best = -1;
        for (int c = 0; c < NCL; c++)
            if (P.cl[c].items[1] && !P.cl[c].items[0] && (best < 0 || P.cl[c].delay < P.cl[best].delay)) best = c;
        P.cl[best].items[0] = unit();
    }
    int n = 0;
    const int uend = mode == 2 ? 8 * nq : 512;
    while (u < uend) {
        for (int b = 0; b < 8 && no; b++)
            if (pos[b] == u) {
                P.list[n++] = mk_item(IT_OP, 1, 2 * b, 0, H[b], 0, 1);
                P.list[n++] = mk_item(IT_OP, 1, 2 * b, 0, H[b], 1, 1);
            }
        P.list[n++] = unit();
    }
    for (int k = 0; no && k < 40; k++) P.list[n++] = mk_item(IT_ON, 1, k / 5 * 2, H[k / 5], 32, k % 5);
    P.nlist = n;
}

}

extern "C" void kernel_launch(void* const* d_in, const int* in_sizes, int n_in, void* d_out, int out_size) {
    static Params P;
    static bool init = false;
    if (!init) {
        EncFn enc = nullptr;
        cudaDriverEntryPointQueryResult qr;
        cudaGetDriverEntryPoint("cuTensorMapEncodeTiled", (void**)&enc, cudaEnableDefault, &qr);
        for (int i = 0; i < 2; i++) {
            P.px[i] = (const __nv_bfloat16*)d_in[5 * i + 0];
            P.pk[i] = (const __nv_bfloat16*)d_in[5 * i + 1];
            P.pv[i] = (const __nv_bfloat16*)d_in[5 * i + 2];
            P.pwq[i] = (const __nv_bfloat16*)d_in[5 * i + 3];
            make_map3(enc, &P.x[i], d_in[5 * i + 0], 2560, 1280, 10, 160, 1);
            for (int j = 0; j < 2; j++) {
                cuuint64_t dims[4] = {64, 8, 3, 16 * 32 * 64};
                cuuint64_t str[3] = {384, 128, 3072};
                cuuint32_t box[4] = {64, 8, 3, 8};
                cuuint32_t es[4] = {1, 1, 1, 1};
                enc(j ? &P.v[i] : &P.k[i], CU_TENSOR_MAP_DATA_TYPE_BFLOAT16, 4, d_in[5 * i + 1 + j], dims, str, box, es,
                    CU_TENSOR_MAP_INTERLEAVE_NONE, CU_TENSOR_MAP_SWIZZLE_128B, (CUtensorMapL2promotion)tune("PROMO", 0),
                    CU_TENSOR_MAP_FLOAT_OOB_FILL_NONE);
            }
            make_map3(enc, &P.wq[i], d_in[5 * i + 3], 640, 12288, 96, 32, 3);
            make_map3(enc, &P.wo[i], d_in[5 * i + 4], 6144, 1280, 10, 16, 5);
            make_map3(enc, &P.won[i], d_in[5 * i + 4], 6144, 1280, 10, 32, 2);
        }
        cuuint64_t dims[5] = {1280, 2, 4, 4, 80};
        cuuint64_t str[4] = {2560, 8 * 2560, 2 * 2560, 32 * 2560};
        cuuint32_t box[5] = {64, 2, 4, 4, 5};
        cuuint32_t es[5] = {1, 1, 1, 1, 1};
        enc(&P.out, CU_TENSOR_MAP_DATA_TYPE_BFLOAT16, 5, d_out, dims, str, box, es, CU_TENSOR_MAP_INTERLEAVE_NONE,
            CU_TENSOR_MAP_SWIZZLE_128B, CU_TENSOR_MAP_L2_PROMOTION_NONE, CU_TENSOR_MAP_FLOAT_OOB_FILL_NONE);
        build_schedule(P);
        cudaFuncSetAttribute(fused_kernel, cudaFuncAttributeMaxDynamicSharedMemorySize, SMEM_LAUNCH);
        init = true;
    }
    fused_kernel<<<NCTA, 384, SMEM_LAUNCH>>>(P);
}
```

```cpp
#include <cuda_runtime.h>
#include <cuda.h>
#include <cuda_bf16.h>
#include <stdint.h>

namespace {

constexpr int NCTA = 132;
constexpr int NCL = NCTA / 2;
constexpr int MAXI = 16;
constexpr int NSTAT = 3;
constexpr uint32_t IT_DYN = 0xffffffffu;
constexpr int SLOT = 24576;
constexpr int NSLOT = 5;
constexpr int XS = 20480;
constexpr int OFF_R = 0;
constexpr int OFF_RING = 5 * XS;
constexpr int OFF_MISC = OFF_RING + NSLOT * SLOT;
constexpr int OFF_LX = OFF_MISC;
constexpr int OFF_LINV = OFF_LX + 2560;
constexpr int OFF_FB = OFF_LINV + 640;
constexpr int OFF_GM = OFF_FB + 16;
constexpr int OFF_BAR = OFF_GM + 16;
constexpr int BAR_RFULL = OFF_BAR;
constexpr int BAR_REMPTY = BAR_RFULL + 40;
constexpr int BAR_XFULL = BAR_REMPTY + 40;
constexpr int BAR_XEMPTY = BAR_XFULL + 40;
constexpr int BAR_PRDY = BAR_XEMPTY + 40;
constexpr int BAR_ITEM = BAR_PRDY + 40;
constexpr int OFF_ITEM = BAR_ITEM + MAXI * 8;
constexpr int SMEM_BYTES = OFF_ITEM + MAXI * 4;
static_assert(SMEM_BYTES <= 232448, "smem");

constexpr int NB_W = 1  , NB_PFULL = 3  , NB_VOTE = 5  , NB_Q2 = 7, NB_SDONE = 8, NB_PDONE = 9,
              NB_L = 10, NB_REF = 11, NB_ODONE = 12, NB_OPEND = 13, NB_LX = 14, NB_Q01 = 15, NB_QK = 0  ;

constexpr uint32_t IT_QA = 1, IT_OP = 2, IT_ON = 3;
__host__ __device__ constexpr uint32_t mk_item(uint32_t type, uint32_t br, uint32_t b, uint32_t h0, uint32_t h1, uint32_t half,
                                               uint32_t part = 0) {
    return type | (br << 2) | (b << 3) | (h0 << 7) | (h1 << 13) | (half << 19) | (part << 22);
}
#define IT_TYPE(e) ((e) & 3u)
#define IT_BR(e) (((e) >> 2) & 1u)
#define IT_B(e) (((e) >> 3) & 15u)
#define IT_H0(e) (((e) >> 7) & 63u)
#define IT_H1(e) (((e) >> 13) & 63u)
#define IT_HALF(e) (((e) >> 19) & 7u)
#define IT_PART(e) (((e) >> 22) & 1u)
#define IT_SLOT(e) IT_H1(e)
#define IT_DEP(e) (((e) >> 23) & 127u)

struct Params {
    CUtensorMap x[2], wq[2], k[2], v[2], wo[2], won[2], out;
    const __nv_bfloat16 *px[2], *pwq[2], *pk[2], *pv[2];
    struct alignas(16) { uint32_t delay, items[NSTAT]; } cl[NCL];
    uint32_t nlist;
    uint8_t slot[64];
    uint32_t list[512];
};

constexpr int OUNIT = 61440;
__device__ __align__(1024) unsigned char g_ostash[(size_t)1024 * OUNIT];
__device__ unsigned int g_flag[32 * 64];
__device__ __forceinline__ unsigned char* ostash(uint32_t slot, uint32_t b) { return g_ostash + (slot * 16 + b) * OUNIT; }
__device__ unsigned int g_epoch[NCTA * 4];
__device__ unsigned int g_ticket[2];

constexpr int SMEM_LAUNCH = SMEM_BYTES;
#define TS(role, idx)
#define TS_ITEM(e)
#define TS_DUMP(role)
#define TSD(role, idx)

#define POL_W 2
#define POL_X 2
#define POL_O 2
template <int M>
__device__ __forceinline__ uint64_t mkpol() {
    uint64_t p;
    if (M == 0) asm volatile("createpolicy.fractional.L2::evict_normal.b64 %0, 1.0;" : "=l"(p));
    if (M == 1) asm volatile("createpolicy.fractional.L2::evict_first.b64 %0, 1.0;" : "=l"(p));
    if (M == 2) asm volatile("createpolicy.fractional.L2::evict_unchanged.b64 %0, 1.0;" : "=l"(p));
    if (M == 3) asm volatile("createpolicy.fractional.L2::evict_normal.L2::evict_unchanged.b64 %0, 0.25;" : "=l"(p));
    return p;
}
#define STSM_W 1
#define SIGJ 0
#define STLAG 1
#define LASTORD 0
#define XLATE 2
#define PV0FIRST 1
#define QST0 1
#define QST1 2
#define QHOLD 8
constexpr float SM_C = 0.07216878364870322f * 1.4426950408889634f;

__device__ __forceinline__ uint32_t next_epoch(int warp) {
    unsigned int* p = &g_epoch[blockIdx.x * 4 + warp];
    const uint32_t e = __ldcg(p) + 1;
    *p = e;
    return e;
}

__device__ __forceinline__ uint32_t tid_now() {
    uint32_t t;
    asm volatile("mov.u32 %0, %%tid.x;" : "=r"(t));
    return t;
}
__device__ __forceinline__ void mbar_init(uint32_t a, uint32_t c) {
    asm volatile("mbarrier.init.shared::cta.b64 [%0], %1;" ::"r"(a), "r"(c) : "memory");
}
__device__ __forceinline__ void mbar_expect(uint32_t a, uint32_t b) {
    asm volatile("mbarrier.arrive.expect_tx.shared::cta.b64 _, [%0], %1;" ::"r"(a), "r"(b) : "memory");
}
template <int CNT = 1>
__device__ __forceinline__ void mbar_arrive_warp(uint32_t a) {
    if (CNT == 1)
        asm volatile("{\n.reg .pred p;\nelect.sync _|p, 0xffffffff;\n@p mbarrier.arrive.shared::cta.b64 _, [%0];\n}" ::"r"(a) : "memory");
    else
        asm volatile(
            "{\n.reg .pred p;\nelect.sync _|p, 0xffffffff;\n@p mbarrier.arrive.shared::cta.b64 _, [%0];\n"
            "@p mbarrier.arrive.shared::cta.b64 _, [%0];\n}" ::"r"(a)
            : "memory");
}
template <int CNT = 1>
__device__ __forceinline__ void mbar_arrive_warp_if(uint32_t a, bool cond) {
    if (CNT == 1)
        asm volatile(
            "{\n.reg .pred p, c;\nelect.sync _|p, 0xffffffff;\nsetp.ne.and.u32 c, %1, 0, p;\n"
            "@c mbarrier.arrive.shared::cta.b64 _, [%0];\n}" ::"r"(a), "r"((uint32_t)cond)
            : "memory");
    else
        asm volatile(
            "{\n.reg .pred p, c;\nelect.sync _|p, 0xffffffff;\nsetp.ne.and.u32 c, %1, 0, p;\n"
            "@c mbarrier.arrive.shared::cta.b64 _, [%0];\n@c mbarrier.arrive.shared::cta.b64 _, [%0];\n}" ::"r"(a), "r"((uint32_t)cond)
            : "memory");
}
__device__ __forceinline__ uint32_t deadline() {
    uint32_t c;
    asm volatile("mov.u32 %0, %%clock_hi;" : "=r"(c));
    return c + 4;
}
__device__ __forceinline__ void mbar_wait(uint32_t a, uint32_t ph, uint32_t dl) {
    asm volatile(
        "{\n.reg .pred p;\n.reg .u32 m;\n"
        "LOOP:\n"
        "mbarrier.try_wait.parity.shared::cta.b64 p, [%0], %1;\n"
        "@p bra DONE;\n"
        "mov.u32 m, %%clock_hi;\n"
        "setp.ne.u32 p, m, %2;\n"
        "@p bra LOOP;\n"
        "trap;\n"
        "DONE:\n}" ::"r"(a), "r"(ph), "r"(dl)
        : "memory");
}
template <int ID, int CNT>
__device__ __forceinline__ void nb_sync() { asm volatile("bar.sync %0, %1;" ::"n"(ID), "n"(CNT) : "memory"); }
template <int ID, int CNT>
__device__ __forceinline__ void nb_arrive() { asm volatile("bar.arrive %0, %1;" ::"n"(ID), "n"(CNT) : "memory"); }
__device__ __forceinline__ void fence_async_smem() { asm volatile("fence.proxy.async.shared::cta;" ::: "memory"); }

__device__ __forceinline__ void tma3(uint32_t dst, const CUtensorMap* m, int c1, int c2, uint32_t bar, uint64_t pol) {
    asm volatile(
        "cp.async.bulk.tensor.3d.shared::cluster.global.mbarrier::complete_tx::bytes.L2::cache_hint [%0], [%1, {%3,%4,%5}], [%2], %6;" ::"r"(dst),
        "l"(m), "r"(bar), "r"(0), "r"(c1), "r"(c2), "l"(pol)
        : "memory");
}
__device__ __forceinline__ void tma3_mc(uint32_t dst, const CUtensorMap* m, int c1, int c2, uint32_t bar, uint64_t pol) {
    asm volatile(
        "cp.async.bulk.tensor.3d.shared::cluster.global.mbarrier::complete_tx::bytes.multicast::cluster.L2::cache_hint"
        " [%0], [%1, {%3,%4,%5}], [%2], %6, %7;" ::"r"(dst),
        "l"(m), "r"(bar), "r"(0), "r"(c1), "r"(c2), "h"((unsigned short)3), "l"(pol)
        : "memory");
}
__device__ __forceinline__ void bulk_load(uint32_t dst, const void* src, uint32_t bytes, uint32_t bar, uint64_t pol) {
    asm volatile("cp.async.bulk.shared::cluster.global.mbarrier::complete_tx::bytes.L2::cache_hint [%0], [%1], %2, [%3], %4;" ::"r"(dst),
                 "l"(src), "r"(bytes), "r"(bar), "l"(pol)
                 : "memory");
}
__device__ __forceinline__ void wg_fence() { asm volatile("wgmma.fence.sync.aligned;" ::: "memory"); }
__device__ __forceinline__ void wg_commit() { asm volatile("wgmma.commit_group.sync.aligned;" ::: "memory"); }
template <int N>
__device__ __forceinline__ void wg_wait() { asm volatile("wgmma.wait_group.sync.aligned %0;" ::"n"(N) : "memory"); }

#define RW80(c, d) c(d[0]), c(d[1]), c(d[2]), c(d[3]), c(d[4]), c(d[5]), c(d[6]), c(d[7]), c(d[8]), c(d[9]), c(d[10]), c(d[11]), c(d[12]), c(d[13]), c(d[14]), c(d[15]), c(d[16]), c(d[17]), c(d[18]), c(d[19]), c(d[20]), c(d[21]), c(d[22]), c(d[23]), c(d[24]), c(d[25]), c(d[26]), c(d[27]), c(d[28]), c(d[29]), c(d[30]), c(d[31]), c(d[32]), c(d[33]), c(d[34]), c(d[35]), c(d[36]), c(d[37]), c(d[38]), c(d[39]), c(d[40]), c(d[41]), c(d[42]), c(d[43]), c(d[44]), c(d[45]), c(d[46]), c(d[47]), c(d[48]), c(d[49]), c(d[50]), c(d[51]), c(d[52]), c(d[53]), c(d[54]), c(d[55]), c(d[56]), c(d[57]), c(d[58]), c(d[59]), c(d[60]), c(d[61]), c(d[62]), c(d[63]), c(d[64]), c(d[65]), c(d[66]), c(d[67]), c(d[68]), c(d[69]), c(d[70]), c(d[71]), c(d[72]), c(d[73]), c(d[74]), c(d[75]), c(d[76]), c(d[77]), c(d[78]), c(d[79])
#define RW48(c, d) c(d[0]), c(d[1]), c(d[2]), c(d[3]), c(d[4]), c(d[5]), c(d[6]), c(d[7]), c(d[8]), c(d[9]), c(d[10]), c(d[11]), c(d[12]), c(d[13]), c(d[14]), c(d[15]), c(d[16]), c(d[17]), c(d[18]), c(d[19]), c(d[20]), c(d[21]), c(d[22]), c(d[23]), c(d[24]), c(d[25]), c(d[26]), c(d[27]), c(d[28]), c(d[29]), c(d[30]), c(d[31]), c(d[32]), c(d[33]), c(d[34]), c(d[35]), c(d[36]), c(d[37]), c(d[38]), c(d[39]), c(d[40]), c(d[41]), c(d[42]), c(d[43]), c(d[44]), c(d[45]), c(d[46]), c(d[47])
#define RW32(c, d) c(d[0]), c(d[1]), c(d[2]), c(d[3]), c(d[4]), c(d[5]), c(d[6]), c(d[7]), c(d[8]), c(d[9]), c(d[10]), c(d[11]), c(d[12]), c(d[13]), c(d[14]), c(d[15]), c(d[16]), c(d[17]), c(d[18]), c(d[19]), c(d[20]), c(d[21]), c(d[22]), c(d[23]), c(d[24]), c(d[25]), c(d[26]), c(d[27]), c(d[28]), c(d[29]), c(d[30]), c(d[31])

__device__ __forceinline__ void reg_fence(float (&d)[80]) { asm volatile("" : RW80("+f", d)::"memory"); }
__device__ __forceinline__ void reg_fence(float (&d)[48]) { asm volatile("" : RW48("+f", d)::"memory"); }
__device__ __forceinline__ void reg_fence(float (&d)[32]) { asm volatile("" : RW32("+f", d)::"memory"); }

template <int NR>
__device__ __forceinline__ void zero(float (&d)[NR]) {
#pragma unroll
    for (int i = 0; i < NR; i++) d[i] = 0.f;
}

constexpr uint32_t HI_SW128 = (1024u >> 4) | (1u << 30);
constexpr uint32_t HI_KV = (3072u >> 4) | (1u << 30);
constexpr uint32_t HI_OST = (2560u >> 4) | (2u << 30);
constexpr uint32_t LO_LBO1 = (1u << 16);
constexpr uint32_t LO_OST = ((512u >> 4) << 16);

template <int TA, int TB, uint32_t HIB, int ACC, uint32_t HIA = HI_SW128>
__device__ __forceinline__ void wgmma(float (&d)[80], uint32_t loA, uint32_t loB) {
#define WG_ASM(SD)                                                          \
    "{\n.reg .b64 da, db;\nmov.b64 da, {%80, %82};\nmov.b64 db, {%81, %83};\n" \
    "wgmma.mma_async.sync.aligned.m64n160k16.f32.bf16.bf16 "               \
    "{%0,%1,%2,%3,%4,%5,%6,%7,%8,%9,%10,%11,%12,%13,%14,%15,%16,%17,%18,%19,%20,%21,%22,%23,%24,%25,%26,%27,%28,%29,%30,%31,%32,%33,%34,%35,%36,%37,%38,%39,%40,%41,%42,%43,%44,%45,%46,%47,%48,%49,%50,%51,%52,%53,%54,%55,%56,%57,%58,%59,%60,%61,%62,%63,%64,%65,%66,%67,%68,%69,%70,%71,%72,%73,%74,%75,%76,%77,%78,%79}, da, db, " SD ", 1, 1, %84, %85;\n}"
    if constexpr (ACC == 2)
        asm volatile(WG_ASM("0") : RW80("+f", d) : "r"(loA), "r"(loB), "n"(HIA), "n"(HIB), "n"(TA), "n"(TB));
    else if constexpr (ACC == 1)
        asm volatile(WG_ASM("1") : RW80("+f", d) : "r"(loA), "r"(loB), "n"(HIA), "n"(HIB), "n"(TA), "n"(TB));
    else
        asm volatile(WG_ASM("0") : RW80("=f", d) : "r"(loA), "r"(loB), "n"(HIA), "n"(HIB), "n"(TA), "n"(TB));
#undef WG_ASM
}
template <int TA, int TB, uint32_t HIB, int ACC, uint32_t HIA = HI_SW128>
__device__ __forceinline__ void wgmma(float (&d)[48], uint32_t loA, uint32_t loB) {
#define WG_ASM(SD)                                                          \
    "{\n.reg .b64 da, db;\nmov.b64 da, {%48, %50};\nmov.b64 db, {%49, %51};\n" \
    "wgmma.mma_async.sync.aligned.m64n96k16.f32.bf16.bf16 "               \
    "{%0,%1,%2,%3,%4,%5,%6,%7,%8,%9,%10,%11,%12,%13,%14,%15,%16,%17,%18,%19,%20,%21,%22,%23,%24,%25,%26,%27,%28,%29,%30,%31,%32,%33,%34,%35,%36,%37,%38,%39,%40,%41,%42,%43,%44,%45,%46,%47}, da, db, " SD ", 1, 1, %52, %53;\n}"
    if constexpr (ACC == 1)
        asm volatile(WG_ASM("1") : RW48("+f", d) : "r"(loA), "r"(loB), "n"(HIA), "n"(HIB), "n"(TA), "n"(TB));
    else
        asm volatile(WG_ASM("0") : RW48("=f", d) : "r"(loA), "r"(loB), "n"(HIA), "n"(HIB), "n"(TA), "n"(TB));
#undef WG_ASM
}
template <int TA, int TB, uint32_t HIB, int ACC, uint32_t HIA = HI_SW128>
__device__ __forceinline__ void wgmma(float (&d)[32], uint32_t loA, uint32_t loB) {
#define WG_ASM(SD)                                                          \
    "{\n.reg .b64 da, db;\nmov.b64 da, {%32, %34};\nmov.b64 db, {%33, %35};\n" \
    "wgmma.mma_async.sync.aligned.m64n64k16.f32.bf16.bf16 "               \
    "{%0,%1,%2,%3,%4,%5,%6,%7,%8,%9,%10,%11,%12,%13,%14,%15,%16,%17,%18,%19,%20,%21,%22,%23,%24,%25,%26,%27,%28,%29,%30,%31}, da, db, " SD ", 1, 1, %36, %37;\n}"
    if constexpr (ACC == 1)
        asm volatile(WG_ASM("1") : RW32("+f", d) : "r"(loA), "r"(loB), "n"(HIA), "n"(HIB), "n"(TA), "n"(TB));
    else
        asm volatile(WG_ASM("0") : RW32("=f", d) : "r"(loA), "r"(loB), "n"(HIA), "n"(HIB), "n"(TA), "n"(TB));
#undef WG_ASM
}

__device__ __forceinline__ uint32_t pack_bf16(float lo, float hi) {
    uint32_t r;
    asm("cvt.rn.bf16x2.f32 %0, %1, %2;" : "=r"(r) : "f"(hi), "f"(lo));
    return r;
}
__device__ __forceinline__ float ex2(float x) {
    float r;
    asm("ex2.approx.ftz.f32 %0, %1;" : "=f"(r) : "f"(x));
    return r;
}
__device__ __forceinline__ void stsm4t(uint32_t a, uint32_t r0, uint32_t r1, uint32_t r2, uint32_t r3) {
    asm volatile("stmatrix.sync.aligned.m8n8.x4.trans.shared.b16 [%0], {%1,%2,%3,%4};" ::"r"(a), "r"(r0), "r"(r1), "r"(r2), "r"(r3)
                 : "memory");
}
__device__ __forceinline__ uint32_t lds_u(uint32_t a) {
    uint32_t v;
    asm volatile("ld.shared.u32 %0, [%1];" : "=r"(v) : "r"(a) : "memory");
    return v;
}
__device__ __forceinline__ uint4 lds_u4(uint32_t a) {
    uint4 v;
    asm volatile("ld.shared.v4.u32 {%0,%1,%2,%3}, [%4];" : "=r"(v.x), "=r"(v.y), "=r"(v.z), "=r"(v.w) : "r"(a) : "memory");
    return v;
}
__device__ __forceinline__ float2 lds_f2(uint32_t a) {
    float2 v;
    asm volatile("ld.shared.v2.f32 {%0,%1}, [%2];" : "=f"(v.x), "=f"(v.y) : "r"(a) : "memory");
    return v;
}
__device__ __forceinline__ void sts_f(uint32_t a, float v) { asm volatile("st.shared.f32 [%0], %1;" ::"r"(a), "f"(v) : "memory"); }
__device__ __forceinline__ void sts_u(uint32_t a, uint32_t v) { asm volatile("st.shared.u32 [%0], %1;" ::"r"(a), "r"(v) : "memory"); }
__device__ __forceinline__ void sts_f2(uint32_t a, float x, float y) {
    asm volatile("st.shared.v2.f32 [%0], {%1,%2};" ::"r"(a), "f"(x), "f"(y) : "memory");
}

template <bool ADD = false, bool SIG = false, int NR>
__device__ __forceinline__ void store_tile_t(const float (&d)[NR], uint32_t addr) {
    uint32_t p[NR / 2];
    if (ADD) {
#pragma unroll
        for (int j = 0; j < NR / 8; j++)
            asm volatile("ldmatrix.sync.aligned.m8n8.x4.trans.shared.b16 {%0,%1,%2,%3}, [%4];"
                         : "=r"(p[4 * j]), "=r"(p[4 * j + 1]), "=r"(p[4 * j + 2]), "=r"(p[4 * j + 3])
                         : "r"(addr + j * 2048)
                         : "memory");
    }
#pragma unroll
    for (int k = 0; k < NR / 2; k++)
        p[k] = ADD ? pack_bf16(d[2 * k] + __uint_as_float(p[k] << 16), d[2 * k + 1] + __uint_as_float(p[k] & 0xffff0000u))
                   : pack_bf16(d[2 * k], d[2 * k + 1]);
#pragma unroll
    for (int j = 0; j < NR / 8; j++) {
        stsm4t(addr + j * 2048, p[4 * j], p[4 * j + 1], p[4 * j + 2], p[4 * j + 3]);
        if (SIG && j == SIGJ) nb_arrive<NB_L, 160>();
    }
}

struct TrueT { static constexpr bool value = true; };
struct FalseT { static constexpr bool value = false; };

template <int V>
struct IntT { static constexpr int value = V; };

__device__ __forceinline__ uint32_t get_item(uint32_t sb, int it, uint32_t dl) {
    mbar_wait(sb + BAR_ITEM + it * 8, 0, dl);
    return lds_u(sb + OFF_ITEM + it * 4);
}
__device__ __forceinline__ uint32_t get_item_warp(uint32_t sb, int it, uint32_t dl) {
    return __shfl_sync(0xffffffffu, get_item(sb, it, dl), 0);
}

struct Ring {
    uint32_t slot, ph, dl;
    __device__ __forceinline__ void adv(uint32_t k) {
        slot += k;
        if (slot >= NSLOT) { slot -= NSLOT; ph ^= 1; }
    }
};

template <int K>
__device__ __forceinline__ void qk_step(float (&s)[80], uint32_t loK, uint32_t loQ) {
    wgmma<0, 0, HI_SW128, K != 0, HI_KV>(s, loK + (K >> 2) * 64 + (K & 3) * 2, loQ + (K >> 2) * (XS >> 4) + (K & 3) * 2);
}
template <int K0, int K1>
__device__ __forceinline__ void qk_steps(float (&s)[80], uint32_t loK, uint32_t loQ) {
    if constexpr (K0 < K1) {
        qk_step<K0>(s, loK, loQ);
        qk_steps<K0 + 1, K1>(s, loK, loQ);
    }
}
__device__ __forceinline__ uint32_t add_bf2(uint32_t a, uint32_t b) {
    uint32_t r;
    asm("add.rn.bf16x2 %0, %1, %2;" : "=r"(r) : "r"(a), "r"(b));
    return r;
}
__device__ __forceinline__ uint32_t fma_bf2(uint32_t a, uint32_t b, uint32_t c) {
    uint32_t r;
    asm("fma.rn.bf16x2 %0, %1, %2, %3;" : "=r"(r) : "r"(a), "r"(b), "r"(c));
    return r;
}
template <int J>
__device__ __forceinline__ void exp_block(const float (&s)[80], uint32_t (&k)[40], uint32_t pa, float mref) {
    if constexpr (J < 10) {
#pragma unroll
        for (int i = 4 * J; i < 4 * J + 4; i++)
            k[i] = pack_bf16(ex2(fmaf(s[2 * i], SM_C, -mref)), ex2(fmaf(s[2 * i + 1], SM_C, -mref)));
#pragma unroll
        for (int i = 0; i < 4; i++)
            asm volatile("stmatrix.sync.aligned.m8n8.x1.trans.shared.b16 [%0], {%1};" ::"r"(((i & 1) ? pa ^ 16 : pa) + J * 2048 + (i >> 1) * 1024),
                         "r"(k[4 * J + i])
                         : "memory");
        exp_block<J + 1>(s, k, pa, mref);
    }
}
__device__ __forceinline__ void sum_block(const uint32_t (&k)[40], float (&l)[10], uint32_t lane) {
    const bool b4 = lane & 16, b3 = lane & 8;
    uint32_t ps[20], t[10];
#pragma unroll
    for (int j = 0; j < 20; j++) ps[j] = add_bf2(k[2 * j], k[2 * j + 1]);
#pragma unroll
    for (int j = 0; j < 10; j++)
        t[j] = add_bf2(b4 ? ps[2 * j + 1] : ps[2 * j], __shfl_xor_sync(0xffffffffu, b4 ? ps[2 * j] : ps[2 * j + 1], 16));
#pragma unroll
    for (int i = 0; i < 5; i++) {
        const uint32_t a = b3 ? t[i + 5] : t[i], b = __shfl_xor_sync(0xffffffffu, b3 ? t[i] : t[i + 5], 8);
        l[2 * i] += __uint_as_float(a << 16) + __uint_as_float(b << 16);
        l[2 * i + 1] += __uint_as_float(a & 0xffff0000u) + __uint_as_float(b & 0xffff0000u);
    }
}
template <bool ADD>
__device__ __forceinline__ void sum_store(const float (&l)[10], uint32_t lane, uint32_t lxa) {
    const bool b2 = lane & 4;
    float t[5];
#pragma unroll
    for (int i = 0; i < 5; i++) t[i] = ADD ? __uint_as_float(lds_u(lxa + i * 64)) : 0.f;
#pragma unroll
    for (int i = 0; i < 5; i++)
        sts_f(lxa + i * 64, t[i] + (b2 ? l[2 * i + 1] : l[2 * i]) + __shfl_xor_sync(0xffffffffu, b2 ? l[2 * i] : l[2 * i + 1], 4));
}

__device__ __forceinline__ void fallback_unit(const Params& P, uint32_t e, uint32_t tid) {
    const uint32_t lane = tid & 31, br = IT_BR(e), b = IT_B(e), h = IT_H0(e);
    const __nv_bfloat162* wq = (const __nv_bfloat162*)(P.pwq[br] + h * 192) + lane;
    const __nv_bfloat162* kp = (const __nv_bfloat162*)(P.pk[br] + (size_t)(b * 32 + h) * 512 * 192) + lane;
    const __nv_bfloat162* vp = (const __nv_bfloat162*)(P.pv[br] + (size_t)(b * 32 + h) * 512 * 192) + lane;
#pragma unroll 1
    for (uint32_t qi = 0; qi < 40; qi++) {
        const uint32_t q = 4 * qi + (tid >> 5);
        const __nv_bfloat16* xr = P.px[br] + (size_t)(b * 160 + q) * 640;
        float a[6] = {0.f, 0.f, 0.f, 0.f, 0.f, 0.f};
#pragma unroll 2
        for (int k = 0; k < 640; k++) {
            const float xv = __bfloat162float(xr[k]);
#pragma unroll
            for (int i = 0; i < 3; i++) {
                const float2 wv = __bfloat1622float2(wq[(size_t)k * 3072 + i * 32]);
                a[2 * i] = fmaf(xv, wv.x, a[2 * i]);
                a[2 * i + 1] = fmaf(xv, wv.y, a[2 * i + 1]);
            }
        }
#pragma unroll
        for (int i = 0; i < 6; i++) a[i] = __bfloat162float(__float2bfloat16(a[i]));
        auto score = [&](int key) {
            float d = 0.f;
#pragma unroll
            for (int i = 0; i < 3; i++) {
                const float2 kv = __bfloat1622float2(kp[key * 96 + i * 32]);
                d = fmaf(a[2 * i], kv.x, fmaf(a[2 * i + 1], kv.y, d));
            }
#pragma unroll
            for (int o = 16; o > 0; o >>= 1) d += __shfl_xor_sync(0xffffffffu, d, o);
            return d;
        };
        float m = -INFINITY, o[6] = {0.f, 0.f, 0.f, 0.f, 0.f, 0.f}, sum = 0.f;
#pragma unroll 1
        for (int n = 0; n < 1024; n++) {
            const int key = n & 511;
            const float d = score(key);
            if (n < 512) {
                m = fmaxf(m, d);
            } else {
                const float p = ex2((d - m) * SM_C);
                sum += p;
#pragma unroll
                for (int i = 0; i < 3; i++) {
                    const float2 vv = __bfloat1622float2(vp[key * 96 + i * 32]);
                    o[2 * i] = fmaf(p, vv.x, o[2 * i]);
                    o[2 * i + 1] = fmaf(p, vv.y, o[2 * i + 1]);
                }
            }
        }
        const float inv = __fdividef(1.f, sum);
        __nv_bfloat16* op = (__nv_bfloat16*)ostash(IT_SLOT(e), b) + (q >> 5) * 256 + 2 * ((q & 31) >> 3) + (q & 1);
#pragma unroll
        for (int i = 0; i < 6; i++) {
            const uint32_t d = (i >> 1) * 64 + 2 * lane + (i & 1);
            op[(d >> 3) * 1280 + (d & 7) * 32 + ((((q & 7) >> 1) ^ ((d & 7) >> 1)) << 3)] = __float2bfloat16(o[i] * inv);
        }
    }
}

template <int W>
struct PendO {
    static constexpr int N = W == 0 ? 56 : 64;
    uint32_t v[N];
    unsigned char* gp;
    static __device__ __forceinline__ uint32_t toff() {
        const uint32_t t = tid_now();
        return ((t >> 5) & 3) * 5120 + ((t >> 2) & 7) * 64 + (((t ^ (t >> 3)) & 3) << 4);
    }
    uint32_t pend, sig, bad;
    static __device__ __forceinline__ void scale(uint32_t& x, uint32_t hi, uint32_t lo) {
        asm("{\n.reg .b32 t;\nmul.rn.bf16x2 t, %0, %2;\nfma.rn.bf16x2 %0, %0, %1, t;\n}" : "+r"(x) : "r"(hi), "r"(lo));
    }
    template <int I, int OFF>
    __device__ __forceinline__ void put() {
        asm volatile("{\n.reg .pred p;\nsetp.ne.u32 p, %6, 0;\n@p st.global.v4.b32 [%0+%5], {%1,%2,%3,%4};\n}" ::"l"(gp), "r"(v[I]),
                     "r"(v[I + 1]), "r"(v[I + 2]), "r"(v[I + 3]), "n"(OFF), "r"(pend)
                     : "memory");
    }
    __device__ __forceinline__ void verdict(uint32_t sb) {
        if (sig) {
            nb_sync<NB_VOTE + W, 160>();
            bad = __any_sync(0xffffffffu, lds_u(sb + OFF_FB) != 0);
            pend = !bad;
        }
    }
    template <int G, int H>
    __device__ __forceinline__ void half(uint32_t sb) {
        constexpr bool T2 = W == 0 ? G >= 3 : G < 3;
        constexpr int B = T2 ? 40 + 8 * (W == 0 ? G - 3 : G) : 0;
        const uint4 a = lds_u4(sb + OFF_LINV + G * 128 + H * 16 + (threadIdx.x & 3) * 32);
#pragma unroll
        for (int i = 2 * H; i < 8; i += 4) {
            scale(v[8 * G + i], a.x, a.y);
            scale(v[8 * G + i + 1], a.z, a.w);
            if (T2) {
                scale(v[B + i], a.x, a.y);
                scale(v[B + i + 1], a.z, a.w);
            }
        }
        if (H == 1) {
            put<8 * G, W * XS + G * 512>();
            put<8 * G + 4, W * XS + G * 512 + 2560>();
            if (T2) {
                put<B, 2 * XS + G * 512>();
                put<B + 4, 2 * XS + G * 512 + 2560>();
            }
            if (G == 4 && pend) nb_arrive<NB_ODONE, 288>();
        }
    }
    template <int G>
    __device__ __forceinline__ void step(uint32_t sb) {
        half<G, 0>(sb);
        half<G, 1>(sb);
    }
    __device__ __forceinline__ void clear() {
#pragma unroll
        for (int i = 0; i < N; i++) v[i] = 0;
        gp = nullptr;
        pend = 0;
        sig = 0;
        bad = 0;
    }
};

__device__ __forceinline__ uint32_t stsm_off() {
    const uint32_t tid = tid_now(), lane = tid & 31;
    return (lane >> 4) * 1024 + (lane & 7) * 128 + (((((tid >> 4) & 6) + ((lane >> 3) & 1)) ^ (lane & 7)) << 4);
}
__device__ __forceinline__ void q_ahead(float (&q0)[80], uint32_t sb, const Ring& rn, uint32_t phm, bool valid) {
    if (valid) {
        mbar_wait(sb + BAR_RFULL + rn.slot * 8, rn.ph, rn.dl);
        mbar_wait(sb + BAR_XFULL, phm & 1, rn.dl);
    }
    const uint32_t a = ((((sb + OFF_RING) & 0x3ffff) >> 4) | LO_LBO1) + rn.slot * (SLOT >> 4);
    const uint32_t b = (((sb + OFF_R) & 0x3ffff) >> 4) | LO_LBO1;
    wg_fence();
    wgmma<1, 0, HI_SW128, false>(q0, a, b);
#pragma unroll
    for (int k = 1; k < 4; k++) wgmma<1, 0, HI_SW128, true>(q0, a + (k >> 1) * 768 + (k & 1) * 128, b + k * 2);
    wg_commit();
}
template <int W, int KK>
__device__ __forceinline__ void qproj(float (&q0)[80], float (&q1)[80], uint32_t sb, Ring& r, uint32_t pslot, uint32_t phm,
                                      PendO<W>& po) {
    const uint32_t loR = (((sb + OFF_R) & 0x3ffff) >> 4) | LO_LBO1;
    const uint32_t loRing = (((sb + OFF_RING) & 0x3ffff) >> 4) | LO_LBO1;
    auto ready = [&](int k) {
        mbar_wait(sb + BAR_RFULL + r.slot * 8, r.ph, r.dl);
        mbar_wait(sb + BAR_XFULL + (k % 5) * 8, ((phm >> (k % 5)) ^ (k / 5)) & 1, r.dl);
    };
    auto release = [&]() {
        if (KK > 0) {
            wg_wait<1>();
            mbar_arrive_warp(sb + BAR_REMPTY + pslot * 8);
            if (KK <= 5) mbar_arrive_warp(sb + (BAR_XEMPTY + (KK - 1) * 8));
        }
    };
    if (KK == 0 && W == 1) ready(0);
    if (W == 1 && KK == QHOLD) {
        if (QHOLD == 7) {
            wg_wait<0>();
            nb_arrive<NB_PDONE, 256>();
        }
        nb_sync<NB_SDONE, 256>();
    }
    const uint32_t a = loRing + r.slot * (SLOT >> 4) + (W == 0 ? 0 : 512), b = loR + (KK % 5) * (XS >> 4);
    wg_fence();
    constexpr bool T0 = W == 1 || KK > 0;
    if (T0) wgmma<1, 0, HI_SW128, KK != 0>(q0, a, b);
    if (W == 0) wgmma<1, 0, HI_SW128, KK != 0 ? 1 : 2>(q1, a + 256, b);
#pragma unroll
    for (int k = 1; k < 4; k++) {
        if (T0) wgmma<1, 0, HI_SW128, true>(q0, a + (k >> 1) * 768 + (k & 1) * 128, b + k * 2);
        if (W == 0) wgmma<1, 0, HI_SW128, true>(q1, a + 256 + (k >> 1) * 768 + (k & 1) * 128, b + k * 2);
    }
    wg_commit();
    const uint32_t cslot = r.slot;
    r.adv(1);
    if (W == 0 || KK < QHOLD) release();
    if (KK == QST0) {
        po.verdict(sb);
        po.template half<0, 0>(sb);
    }
    if (KK < 9) ready(KK + 1);
    if (W == 1 && KK >= QHOLD) release();
    if (W == 1 && KK == 7 && QHOLD > 7) nb_arrive<NB_PDONE, 256>();
    if (KK == QST0) po.template half<0, 1>(sb);
    if constexpr (KK > QST0 && KK < QST0 + 5) po.template step<KK - QST0>(sb);
    if constexpr (KK < (W == 0 ? 7 : 9)) {
        qproj<W, KK + 1>(q0, q1, sb, r, cslot, phm, po);
    } else if constexpr (W == 1) {
        const uint32_t sta = sb + OFF_R + 2 * XS + stsm_off();
        wg_wait<0>();
        reg_fence(q0);
        store_tile_t<false, true>(q0, sta);
        mbar_arrive_warp(sb + BAR_REMPTY + cslot * 8);
    } else {
        const uint32_t s8 = r.slot, a8 = loRing + s8 * (SLOT >> 4);
        wg_fence();
#pragma unroll
        for (int k = 0; k < 4; k++) wgmma<1, 0, HI_SW128, true>(q0, a8 + (k >> 1) * 768 + (k & 1) * 128, loR + 3 * (XS >> 4) + k * 2);
        r.adv(1);
        ready(9);
        const uint32_t s9 = r.slot, a9 = loRing + s9 * (SLOT >> 4);
        r.adv(1);
        wg_fence();
#pragma unroll
        for (int k = 0; k < 4; k++) wgmma<1, 0, HI_SW128, true>(q0, a9 + (k >> 1) * 768 + (k & 1) * 128, loR + 4 * (XS >> 4) + k * 2);
        wg_commit();
        wg_wait<1>();
        mbar_arrive_warp(sb + BAR_REMPTY + cslot * 8);
        wg_fence();
#pragma unroll
        for (int k = 0; k < 8; k++)
            wgmma<1, 0, HI_SW128, true>(q1, (k < 4 ? a8 : a9) + 256 + ((k >> 1) & 1) * 768 + (k & 1) * 128,
                                        loR + (3 + (k >> 2)) * (XS >> 4) + (k & 3) * 2);
        wg_commit();
        nb_arrive<NB_SDONE, 256>();
        nb_sync<NB_PDONE, 256>();
        wg_wait<1>();
        reg_fence(q0);
        const uint32_t sta = sb + OFF_R + stsm_off();
        store_tile_t(q0, sta);
        sts_u(sb + OFF_GM + 4, r.slot);
        mbar_wait(sb + BAR_RFULL + r.slot * 8, r.ph, r.dl);
        wg_wait<0>();
        reg_fence(q1);
        mbar_arrive_warp(sb + BAR_REMPTY + s8 * 8);
        mbar_arrive_warp(sb + BAR_REMPTY + s9 * 8);
        store_tile_t(q1, sta + XS);
    }
}

template <int NR>
__device__ __forceinline__ void opack(const float (&o)[NR], uint32_t* v) {
#pragma unroll
    for (int g = 0; g < NR / 16; g++)
#pragma unroll
        for (int hh = 0; hh < 2; hh++)
#pragma unroll
            for (int t = 0; t < 4; t++) v[8 * g + 4 * hh + t] = pack_bf16(o[16 * g + 4 * t + 2 * hh], o[16 * g + 4 * t + 2 * hh + 1]);
}

template <bool IS_S>
__device__ __forceinline__ void op_item(uint32_t e, uint32_t sb, Ring& r, uint32_t& phm) {
    constexpr int T0 = IS_S ? 0 : 2;
    constexpr uint32_t BOFF = IS_S ? (3 * 512) >> 4 : 0;
    const uint32_t loRing = (((sb + OFF_RING) & 0x3ffff) >> 4) | LO_LBO1;
    const uint32_t loO = (((sb + OFF_R) & 0x3ffff) >> 4) | LO_OST;
    float c0[80], c1[80], c2[IS_S ? 32 : 48];
    const int T = 3 * (IT_H1(e) - IT_H0(e));
    uint32_t xs = 0;
    auto step = [&](auto first, auto half) {
        constexpr bool F = decltype(first)::value;
        constexpr uint32_t hf = decltype(half)::value;
        if (hf == 0) {
            mbar_wait(sb + BAR_XFULL + xs * 8, (phm >> xs) & 1, r.dl);
            phm ^= 1u << xs;
        }
        mbar_wait(sb + BAR_RFULL + r.slot * 8, r.ph, r.dl);
        const uint32_t a = loRing + r.slot * (SLOT >> 4), b = loO + xs * (XS >> 4) + hf * 640;
        wg_fence();
        wgmma<1, 1, HI_OST, !F>(c0, a + T0 * 128, b);
        wgmma<1, 1, HI_OST, !F>(c1, a + T0 * 128 + 128, b);
        wgmma<1, 1, HI_OST, !F>(c2, a + 512, b + BOFF);
        wgmma<1, 1, HI_OST, true>(c0, a + 640 + T0 * 128, b + 320);
        wgmma<1, 1, HI_OST, true>(c1, a + 640 + T0 * 128 + 128, b + 320);
        wgmma<1, 1, HI_OST, true>(c2, a + 640 + 512, b + 320 + BOFF);
        wg_commit();
    };
    step(TrueT{}, IntT<0>{});
#pragma unroll 1
    for (int t = 1;; t++) {
        uint32_t pslot = r.slot;
        r.adv(1);
        step(FalseT{}, IntT<1>{});
        wg_wait<1>();
        mbar_arrive_warp(sb + BAR_REMPTY + pslot * 8);
        if (t == T) break;
        pslot = r.slot;
        const uint32_t pxs = xs;
        r.adv(1);
        if (++xs == 5) xs = 0;
        step(FalseT{}, IntT<0>{});
        wg_wait<1>();
        mbar_arrive_warp(sb + BAR_REMPTY + pslot * 8);
        mbar_arrive_warp_if(sb + BAR_XEMPTY + pxs * 8, t + 4 < T);
    }
    wg_wait<0>();
    reg_fence(c0);
    reg_fence(c1);
    reg_fence(c2);
    mbar_arrive_warp(sb + BAR_REMPTY + r.slot * 8);
    r.adv(1);
    nb_sync<NB_OPEND, 256>();
    const uint32_t sta = sb + OFF_R + stsm_off();
    store_tile_t(c0, sta + T0 * XS);
    store_tile_t(c1, sta + (T0 + 1) * XS);
    store_tile_t(c2, sta + 4 * XS + (IS_S ? 96 * 128 : 0));
    fence_async_smem();
    nb_arrive<NB_ODONE, 288>();
}

__device__ __forceinline__ void on_item(uint32_t W, uint32_t e, uint32_t sb, Ring& r, uint32_t& phm) {
    const uint32_t loRing = (((sb + OFF_RING) & 0x3ffff) >> 4) | LO_LBO1;
    const uint32_t loO = (((sb + OFF_R) & 0x3ffff) >> 4) | LO_OST;
    float c[80];
    const int T = 3 * (IT_H1(e) - IT_H0(e));
    uint32_t xs = 0;
    auto step = [&](auto first) {
        constexpr bool F = decltype(first)::value;
        mbar_wait(sb + BAR_XFULL + xs * 8, (phm >> xs) & 1, r.dl);
        phm ^= 1u << xs;
        mbar_wait(sb + BAR_RFULL + r.slot * 8, r.ph, r.dl);
        const uint32_t a = loRing + r.slot * (SLOT >> 4) + W * 256, b = loO + xs * (XS >> 4);
        wg_fence();
        wgmma<1, 1, HI_OST, !F>(c, a, b);
#pragma unroll
        for (int k = 1; k < 4; k++) wgmma<1, 1, HI_OST, true>(c, a + (k >> 1) * 512 + (k & 1) * 128, b + k * 320);
        wg_commit();
    };
    step(TrueT{});
#pragma unroll 1
    for (int t = 1; t < T; t++) {
        const uint32_t pslot = r.slot, pxs = xs;
        r.adv(1);
        if (++xs == 5) xs = 0;
        step(FalseT{});
        wg_wait<1>();
        mbar_arrive_warp(sb + BAR_REMPTY + pslot * 8);
        mbar_arrive_warp_if(sb + BAR_XEMPTY + pxs * 8, t + 2 < T);
    }
    xs += 1 + W;
    if (xs >= 5) xs -= 5;
    mbar_wait(sb + BAR_XFULL + xs * 8, (phm >> xs) & 1, r.dl);
    wg_wait<0>();
    reg_fence(c);
    store_tile_t<true>(c, sb + OFF_R + xs * XS + stsm_off());
    fence_async_smem();
    nb_arrive<NB_ODONE, 288>();
}

template <int W>
__device__ __forceinline__ uint32_t qa_item(uint32_t e, uint32_t sb, Ring& r, uint32_t phm, PendO<W>& po, float (&q0)[80],
                                            float (&oa)[80], int it) {
    const uint32_t loR = (((sb + OFF_R) & 0x3ffff) >> 4) | LO_LBO1;
    const uint32_t loRing = (((sb + OFF_RING) & 0x3ffff) >> 4) | LO_LBO1;
    qproj<W, 0>(q0, oa, sb, r, 0, phm, po);
    fence_async_smem();
    TSD(W, 1);
    float s[80], ob[W == 0 ? 32 : 48], l[10];
    if (W == 1) {
        nb_arrive<NB_Q2, 256>();
        zero(oa);
        zero(ob);
        reg_fence(oa);
        reg_fence(ob);
    }
    const uint32_t lane = tid_now() & 31, sta = sb + OFF_R + stsm_off();
    auto pv = [&](auto first, uint32_t buf) {
        constexpr bool F = decltype(first)::value;
        mbar_wait(sb + BAR_RFULL + r.slot * 8, r.ph, r.dl);
        const uint32_t a = loRing + r.slot * (SLOT >> 4), b = loR + (3 + buf) * (XS >> 4);
        wg_fence();
        wgmma<1, 0, HI_SW128, F ? 2 : 1, HI_KV>(oa, a + W * 64, b);
        wgmma<1, 0, HI_SW128, !F, HI_KV>(ob, a + 128, b + (W == 0 ? (96 * 128) >> 4 : 0));
#pragma unroll
        for (int k = 1; k < 4; k++) {
            wgmma<1, 0, HI_SW128, true, HI_KV>(oa, a + W * 64 + k * 384, b + k * 2);
            wgmma<1, 0, HI_SW128, true, HI_KV>(ob, a + 128 + k * 384, b + (W == 0 ? (96 * 128) >> 4 : 0) + k * 2);
        }
        wg_commit();
    };
    zero(l);
    float mref;
    uint32_t kslot, vslot, nx = 0;
    auto tail = [&](auto first, int i) {
        constexpr bool rel_other = !decltype(first)::value;
        uint32_t ps[40];
        exp_block<0>(s, ps, sta + (3 + W) * XS, mref);
        if (rel_other) {
            wg_wait<0>();
            mbar_arrive_warp(sb + BAR_REMPTY + vslot * 8);
            if (W == 1) mbar_arrive_warp_if(sb + BAR_XEMPTY + 24, i == 3);
        }
        fence_async_smem();
        nb_arrive<NB_PFULL + W, 256>();
        TSD(W, 6 + 5 * i);
        if (W == 1) {
            if (XLATE >= 2) mbar_arrive_warp_if<2>(sb + BAR_XEMPTY + 8, i == 3);
            if (XLATE >= 1) mbar_arrive_warp_if<2>(sb + BAR_XEMPTY + 16, i == 3);
        }
        if (rel_other || !PV0FIRST) {
            mbar_wait(sb + BAR_RFULL + r.slot * 8, r.ph, r.dl);
            sum_block(ps, l, lane);
        }
        if (W == 0 && i == 3) nx = get_item_warp(sb, it + 1, r.dl);
        TSD(W, 7 + 5 * i);
        if (LASTORD && W == 0 && i == 3) nb_sync<NB_PDONE, 256>();
        else nb_sync<NB_W + W, 128>();
        pv(first, W);
        if (!rel_other && PV0FIRST) sum_block(ps, l, lane);
        TSD(W, 8 + 5 * i);
    };
    if (W == 0) {
        nb_sync<NB_QK, 160>();
        TSD(W, 2);
        wg_fence();
        qk_steps<0, 8>(s, loRing + r.slot * (SLOT >> 4), loR);
        nb_sync<NB_Q2, 256>();
        qk_steps<8, 12>(s, loRing + r.slot * (SLOT >> 4), loR);
        wg_commit();
        nb_arrive<NB_Q01, 256>();
        TSD(W, 4);
        nb_sync<NB_REF, 160>();
        mref = __uint_as_float(lds_u(sb + OFF_GM));
        wg_wait<0>();
        reg_fence(s);
        mbar_arrive_warp<2>(sb + BAR_REMPTY + r.slot * 8);
        r.adv(2);
        TSD(W, 5);
        tail(TrueT{}, 0);
    } else {
        nb_sync<NB_Q01, 256>();
    }
#pragma unroll 1
    for (int i = (W == 0 ? 1 : 0); i < 4; i++) {
        const uint32_t pvslot = r.slot;
        r.adv(1);
        kslot = r.slot;
        mbar_wait(sb + BAR_RFULL + r.slot * 8, r.ph, r.dl);
        wg_fence();
        qk_steps<0, 4>(s, loRing + r.slot * (SLOT >> 4), loR);
        if (W == 1) wg_commit();
        qk_steps<4, 12>(s, loRing + r.slot * (SLOT >> 4), loR);
        wg_commit();
        wg_wait<1>();
        if (W == 1) mbar_arrive_warp_if(sb + BAR_XEMPTY + 0, i == 3);
        mbar_arrive_warp_if(sb + BAR_REMPTY + pvslot * 8, W == 0 || i > 0);
        r.adv(1);
        vslot = r.slot;
        TSD(W, 4 + 5 * i);
        nb_sync<NB_PFULL + (W ^ 1), 256>();
        pv(FalseT{}, W ^ 1);
        if (LASTORD && W == 1 && i == 3) nb_arrive<NB_PDONE, 256>();
        if (W == 1) mref = __uint_as_float(lds_u(sb + OFF_GM));
        wg_wait<1>();
        reg_fence(s);
        mbar_arrive_warp<2>(sb + BAR_REMPTY + kslot * 8);
        if (W == 0) mbar_arrive_warp_if(sb + BAR_XEMPTY + 0, i == 3);
        if (W == 1) {
            if (XLATE < 2) mbar_arrive_warp_if<2>(sb + BAR_XEMPTY + 8, i == 3);
            if (XLATE < 1) mbar_arrive_warp_if<2>(sb + BAR_XEMPTY + 16, i == 3);
        }
        r.adv(W == 1 && i == 3 ? 1 : 2);
        TSD(W, 5 + 5 * i);
        tail(FalseT{}, i);
    }
    if (W == 1) nx = get_item_warp(sb, it + 1, r.dl);
    if (W == 0) {
        Ring rn = r;
        rn.adv(2);
        q_ahead(q0, sb, rn, phm, IT_TYPE(nx) == IT_QA);
        TSD(W, 25);
    }
    const uint32_t w = (tid_now() >> 5) & 3;
    const uint32_t lxa = sb + OFF_LX + w * 640 + (((lane & 8) ? 80 : 0) + ((lane >> 1) & 8) + 2 * (lane & 3) + ((lane >> 2) & 1)) * 4;
    po.gp = ostash(IT_SLOT(e), IT_B(e)) + po.toff();
    po.sig = 1;
    if (W == 0) {
        sum_store<false>(l, lane, lxa);
        nb_arrive<NB_LX, 256>();
        wg_wait<1>();
        mbar_arrive_warp(sb + BAR_REMPTY + r.slot * 8);
        mbar_arrive_warp(sb + BAR_XEMPTY + 24);
        r.adv(1);
        nb_sync<NB_PFULL + 1, 256>();
        pv(FalseT{}, 1);
    } else {
        nb_sync<NB_LX, 256>();
        sum_store<true>(l, lane, lxa);
        nb_arrive<NB_L, 160>();
    }
    TSD(W, 24);
    wg_wait<0>();
    reg_fence(oa);
    reg_fence(ob);
    mbar_arrive_warp(sb + BAR_REMPTY + r.slot * 8);
    mbar_arrive_warp(sb + BAR_XEMPTY + 32);
    r.adv(1);
    opack(ob, po.v + 40);
    opack(oa, po.v);
    return nx;
}

template <int W>
__device__ __forceinline__ uint32_t qa_run(const Params& P, uint32_t e, uint32_t sb, Ring& r, uint32_t phm, int& it) {
    PendO<W> po;
    po.clear();
    float q0[80], oa[80];
    if (W == 0) {
        zero(oa);
        q_ahead(q0, sb, r, phm, true);
        wg_wait<0>();
    }
#pragma unroll 1
    do {
        TS(W, 0);
        if (W == 0) TS_ITEM(e);
        e = qa_item<W>(e, sb, r, phm, po, q0, oa, it);
        TS(W, 31);
        it++;
    } while (IT_TYPE(e) == IT_QA && !po.bad);
#pragma unroll 1
    for (int m = po.bad ? 2 : 1; m > 0; m--) {
        if (m == 1) {
            po.verdict(sb);
            po.template step<0>(sb);
            po.template step<1>(sb);
            po.template step<2>(sb);
            po.template step<3>(sb);
            po.template step<4>(sb);
        }
        if (po.bad) {
            if (W == 0) fallback_unit(P, lds_u(sb + OFF_ITEM + (it - m) * 4), tid_now() & 127);
            __syncwarp();
            nb_sync<NB_ODONE, 288>();
        }
    }
    return e;
}

__device__ __forceinline__ void consumer(const Params& P, uint32_t W, uint32_t sb, uint32_t dl) {
    int it = 0;
    Ring r{0, 0, dl};
    uint32_t phm = 0;
    uint32_t e = get_item_warp(sb, 0, dl);
#pragma unroll 1
    while (true) {
        if (IT_TYPE(e) == IT_QA) e = W == 0 ? qa_run<0>(P, e, sb, r, phm, it) : qa_run<1>(P, e, sb, r, phm, it);
        if (e == 0) break;
        if (IT_TYPE(e) == IT_QA) continue;
        TS(W, 0);
        if (W == 0) TS_ITEM(e);
        if (IT_TYPE(e) == IT_ON) on_item(W, e, sb, r, phm);
        else if (W == 0) op_item<true>(e, sb, r, phm);
        else op_item<false>(e, sb, r, phm);
        TS(W, 31);
        e = get_item_warp(sb, ++it, dl);
    }
    TS_DUMP(W);
}

__global__ void __cluster_dims__(2, 1, 1) __launch_bounds__(384, 1) fused_kernel(const __grid_constant__ Params P) {
    extern __shared__ __align__(1024) unsigned char smem_raw[];
    const uint32_t sb = (uint32_t)__cvta_generic_to_shared(smem_raw);
    const uint32_t warp = __shfl_sync(0xffffffffu, threadIdx.x >> 5, 0), wgid = warp >> 2;
    const uint32_t cta = blockIdx.x;
    const uint32_t dl = deadline();

    if (threadIdx.x == 128) {
#pragma unroll
        for (int i = 0; i < NSLOT; i++) {
            mbar_init(sb + BAR_RFULL + i * 8, 1);
            mbar_init(sb + BAR_REMPTY + i * 8, 8);
            mbar_init(sb + BAR_XFULL + i * 8, 1);
            mbar_init(sb + BAR_XEMPTY + i * 8, 8);
        }
        asm volatile("fence.mbarrier_init.release.cluster;" ::: "memory");
        fence_async_smem();
    } else if (threadIdx.x == 160) {
#pragma unroll
        for (int i = 0; i < NSLOT + MAXI; i++) mbar_init(sb + BAR_PRDY + i * 8, 1);
        asm volatile("fence.mbarrier_init.release.cluster;" ::: "memory");
    } else if (threadIdx.x == 0) {
        sts_u(sb + OFF_ITEM, P.cl[cta >> 1].items[0] ? P.cl[cta >> 1].items[0] + 8 * (cta & 1) : 0);
        sts_u(sb + OFF_FB, P.cl[cta >> 1].delay);
    } else if (threadIdx.x == 64) {
        if (sb & 1023) __trap();
        asm volatile("prefetch.tensormap [%0];" ::"l"(&P.wq[0]) : "memory");
        asm volatile("prefetch.tensormap [%0];" ::"l"(&P.x[0]) : "memory");
    }
    __syncthreads();
    {
        const int it = 0;
        if (wgid == 1) TS(0, 30);
    }
    asm volatile("barrier.cluster.arrive.relaxed.aligned;" ::: "memory");
    if (warp < 3) {
        const uint32_t e = __shfl_sync(0xffffffffu, lds_u(sb + OFF_ITEM), 0), d = lds_u(sb + OFF_FB);
        const uint64_t pol = mkpol<POL_W>();
        const bool isx = warp == 1, lead = (threadIdx.x & 31) == 0;
        uint32_t t0, t1;
        asm volatile("mov.u32 %0, %%clock;" : "=r"(t0));
        do {
            asm volatile("mov.u32 %0, %%clock;" : "=r"(t1));
        } while (t1 - t0 < d);
        __syncwarp();
#pragma unroll 1
        for (int n = 0; n < (e ? NSLOT : 0); n++) {
            const uint32_t bar = sb + (isx ? BAR_XFULL : BAR_RFULL) + n * 8;
            if (lead) {
                if (warp < 2) mbar_expect(bar, isx ? XS : SLOT);
                tma3(sb + (isx ? OFF_R + n * XS : OFF_RING + n * SLOT + warp * (SLOT / 4)), isx ? &P.x[0] : &P.wq[0],
                     isx ? IT_B(e) * 160 : n * 64 + warp * 16, isx ? n : IT_H0(e) * 3, bar, pol);
            }
        }
        if (threadIdx.x == 0) asm volatile("mbarrier.arrive.shared::cta.b64 _, [%0];" ::"r"(sb + BAR_ITEM) : "memory");
        __syncwarp();
    }

    if (wgid == 0) {
        asm volatile("setmaxnreg.dec.sync.aligned.u32 24;");
        if (warp == 0) {
            const bool lead = threadIdx.x == 0;
            const uint64_t pol_first = mkpol<1>(), pol_norm = mkpol<POL_W>();
            uint32_t e = __shfl_sync(0xffffffffu, lds_u(sb + OFF_ITEM), 0);
            asm volatile("barrier.cluster.wait.aligned;" ::: "memory");
            unsigned int* const ticket = &g_ticket[next_epoch(0) & 1];
            const uint32_t rank = cta & 1;
            uint32_t peer;
            asm volatile("mapa.shared::cluster.u32 %0, %1, %2;" : "=r"(peer) : "r"(sb), "r"(rank ^ 1));
            Ring r{0, 0, dl};
            uint32_t pm = 0;
            auto load_w = [&](const CUtensorMap* m, int row, int blk, uint32_t half_bytes) {
                mbar_wait(sb + BAR_REMPTY + r.slot * 8, r.ph, dl);
                if (lead) {
                    mbar_expect(sb + BAR_RFULL + r.slot * 8, 2 * half_bytes);
                    asm volatile("mbarrier.arrive.shared::cluster.b64 _, [%0];" ::"r"(peer + BAR_PRDY + r.slot * 8) : "memory");
                }
                mbar_wait(sb + BAR_PRDY + r.slot * 8, (pm >> r.slot) & 1, dl);
                pm ^= 1u << r.slot;
                if (lead) tma3_mc(sb + OFF_RING + r.slot * SLOT + rank * half_bytes, m, row, blk, sb + BAR_RFULL + r.slot * 8, pol_norm);
                r.adv(1);
            };
#pragma unroll 1
            for (int it = 0; e != 0; it++) {
                uint32_t nx = 0, tk = 0;
                if (rank == 0 && IT_TYPE(e) != IT_ON && it + 2 < MAXI) nx = it + 1 < NSTAT ? P.cl[cta >> 1].items[it + 1] : IT_DYN;
                const uint32_t br = IT_BR(e);
                if (IT_TYPE(e) == IT_QA) {
                    const uint32_t h = IT_H0(e);
#pragma unroll 1
                    for (int kk = it ? 0 : NSLOT; kk < 10; kk++) load_w(&P.wq[br], kk * 64 + rank * 32, h * 3, SLOT / 2);
                    const int grp0 = (IT_B(e) * 32 + h) * 64;
#pragma unroll 1
                    for (int n = 0; n < 16; n++) {
                        if (n == 13 && nx == IT_DYN && lead) tk = atomicAdd(ticket, 1);
                        const bool isv = n == 15 || (n > 0 && !(n & 1));
                        const int j = n == 15 ? 7 : isv ? (n - 2) >> 1 : (n + 1) >> 1;
                        mbar_wait(sb + BAR_REMPTY + r.slot * 8, r.ph, dl);
                        if (lead) {
                            mbar_expect(sb + BAR_RFULL + r.slot * 8, SLOT);
                            asm volatile(
                                "cp.async.bulk.tensor.4d.shared::cluster.global.mbarrier::complete_tx::bytes.L2::cache_hint"
                                " [%0], [%1, {%3,%3,%3,%4}], [%2], %5;" ::"r"(sb + OFF_RING + r.slot * SLOT),
                                "l"(isv ? &P.v[br] : &P.k[br]), "r"(sb + BAR_RFULL + r.slot * 8), "r"(0), "r"(grp0 + j * 8), "l"(pol_first)
                                : "memory");
                        }
                        r.adv(1);
                    }
                } else {
                    const bool wide = IT_TYPE(e) == IT_OP;
                    const int step = wide ? 32 : 64, r1 = IT_H1(e) * 192;
#pragma unroll 1
                    for (int row = IT_H0(e) * 192 + rank * (step >> 1); row < r1; row += step)
                        load_w(wide ? &P.wo[br] : &P.won[br], row, IT_HALF(e) * (wide ? 5 : 2), wide ? XS / 2 : 8192);
                    if (nx == IT_DYN && lead) tk = atomicAdd(ticket, 1);
                }
                if (rank == 0) {
                    if (nx == IT_DYN) {
                        tk = __shfl_sync(0xffffffffu, tk, 0);
                        nx = tk < P.nlist ? P.list[tk] : 0;
                    }
                    e = nx;
                    if (lead) {
                        asm volatile("st.async.weak.shared::cluster.mbarrier::complete_tx::bytes.b32 [%0], %1, [%2];" ::"r"(
                                         peer + OFF_ITEM + 4 + it * 4),
                                     "r"(e ? e + 8 : 0), "r"(peer + BAR_ITEM + 8 + it * 8)
                                     : "memory");
                        sts_u(sb + OFF_ITEM + 4 + it * 4, e);
                        asm volatile("mbarrier.arrive.shared::cta.b64 _, [%0];" ::"r"(sb + BAR_ITEM + 8 + it * 8) : "memory");
                    }
                } else {
                    if (lead) mbar_expect(sb + BAR_ITEM + 8 + it * 8, 4);
                    e = get_item_warp(sb, it + 1, dl);
                }
            }
        } else if (warp == 1) {
            const uint64_t pol_norm = mkpol<POL_X>(), pol_o = mkpol<POL_O>();
            const bool lead = threadIdx.x == 32;
            uint32_t phm = 0, epoch = 0;
#pragma unroll 1
            for (int it = 0;; it++) {
                const uint32_t e = get_item_warp(sb, it, dl);
                if (it == 1 || (it == 0 && e == 0)) epoch = next_epoch(1);
                if (e == 0) break;
                const uint32_t br = IT_BR(e);
                uint32_t xs = 0;
                auto acquire = [&]() {
                    mbar_wait(sb + BAR_XEMPTY + xs * 8, (phm >> xs) & 1, dl);
                    phm ^= 1u << xs;
                    if (lead) mbar_expect(sb + BAR_XFULL + xs * 8, XS);
                };
                if (IT_TYPE(e) == IT_QA) {
#pragma unroll 1
                    for (int kk = it ? 0 : 5; kk < 10; kk++) {
                        acquire();
                        if (lead) tma3(sb + OFF_R + xs * XS, &P.x[br], IT_B(e) * 160, kk, sb + BAR_XFULL + xs * 8, pol_norm);
                        if (++xs == 5) xs = 0;
                    }
                } else {
                    const unsigned int* fp = g_flag + (br * 16 + IT_B(e)) * 64 + (threadIdx.x & 31);
                    uint32_t hm = 0, pm = 0;
                    auto poll = [&](uint32_t hneed, uint32_t pneed) {
                        if ((hm & hneed) == hneed && (pm & pneed) == pneed) return;
                        uint32_t n = 0;
                        do {
                            uint32_t a, b;
                            asm volatile("ld.acquire.gpu.global.u32 %0, [%2];\nld.acquire.gpu.global.u32 %1, [%2+128];"
                                         : "=r"(a), "=r"(b) : "l"(fp) : "memory");
                            hm = __ballot_sync(0xffffffffu, a == epoch);
                            pm = __ballot_sync(0xffffffffu, b == epoch);
                            if (++n > 0x1000000) __trap();
                        } while ((hm & hneed) != hneed || (pm & pneed) != pneed);
                        __syncwarp();
                        asm volatile("fence.proxy.async;" ::: "memory");
                    };
#pragma unroll 1
                    for (uint32_t h = IT_H0(e); h < IT_H1(e); h++) {
                        poll(1u << h, 0);
                        const unsigned char* src = ostash(P.slot[br * 32 + h], IT_B(e));
#pragma unroll 1
                        for (int t = 0; t < 3; t++) {
                            acquire();
                            if (lead) bulk_load(sb + OFF_R + xs * XS, src + t * XS, XS, sb + BAR_XFULL + xs * 8, pol_o);
                            if (++xs == 5) xs = 0;
                        }
                        if (IT_TYPE(e) == IT_OP && h >= 1) {
                            const uint32_t x1 = xs == 4 ? 0 : xs + 1;
                            mbar_wait(sb + BAR_XFULL + xs * 8, (phm >> xs) & 1, dl);
                            mbar_wait(sb + BAR_XFULL + x1 * 8, (phm >> x1) & 1, dl);
                            if (lead)
                                asm volatile("st.relaxed.gpu.global.u32 [%0], %1;" ::"l"(fp + 34 + IT_HALF(e)), "r"(epoch * 64 + h) : "memory");
                        }
                    }
                    if (IT_TYPE(e) == IT_ON) {
                        poll(0, IT_HALF(e) < 2 ? 1 : IT_HALF(e) == 2 ? 3 : 2);
#pragma unroll 1
                        for (uint32_t tile = 2 * IT_HALF(e); tile < 2 * IT_HALF(e) + 2; tile++) {
                            acquire();
                            if (lead)
                                asm volatile(
                                    "cp.async.bulk.tensor.5d.shared::cluster.global.mbarrier::complete_tx::bytes [%0], [%1, {%3,%5,%5,%5,%4}], [%2];" ::"r"(
                                        sb + OFF_R + xs * XS),
                                    "l"(&P.out), "r"(sb + BAR_XFULL + xs * 8), "r"(br * 640 + tile * 64), "r"(IT_B(e) * 5), "r"(0)
                                    : "memory");
                            if (++xs == 5) xs = 0;
                        }
                    }
                }
            }
        } else if (warp == 2) {
            asm volatile("barrier.cluster.wait.aligned;" ::: "memory");
            const uint32_t epoch = next_epoch(2);
            if (cta == 0) g_ticket[(epoch + 1) & 1] = 0;
#pragma unroll 1
            for (int it = 0;; it++) {
                const uint32_t e = get_item_warp(sb, it, dl);
                if (e == 0) break;
                nb_sync<NB_ODONE, 288>();
                if (threadIdx.x == 64) {
                    const uint32_t bb = IT_BR(e) * 16 + IT_B(e);
                    if (IT_TYPE(e) != IT_QA) {
                        const bool wide = IT_TYPE(e) == IT_OP;
                        if (wide)
                            asm volatile("st.relaxed.gpu.global.u32 [%0], %1;" ::"l"(&g_flag[bb * 64 + 34 + IT_HALF(e)]),
                                         "r"(epoch * 64 + IT_H1(e))
                                         : "memory");
                        const int cc0 = IT_BR(e) * 640 + IT_HALF(e) * (wide ? 320 : 128);
                        uint32_t xs = wide ? 0 : (3 * (IT_H1(e) - IT_H0(e))) % 5;
#pragma unroll 1
                        for (int m = 0; m < (wide ? 5 : 2); m++) {
                            asm volatile("cp.async.bulk.tensor.5d.global.shared::cta.bulk_group [%0, {%2,%4,%4,%4,%3}], [%1];" ::"l"(&P.out),
                                         "r"(sb + OFF_R + xs * XS), "r"(cc0 + m * 64), "r"((int)IT_B(e) * 5), "r"(0)
                                         : "memory");
                            asm volatile("cp.async.bulk.commit_group;" ::: "memory");
                            if (wide && m >= STLAG) {
                                asm volatile("cp.async.bulk.wait_group.read %0;" ::"n"(STLAG) : "memory");
                                asm volatile("mbarrier.arrive.shared::cta.b64 _, [%0], 8;" ::"r"(sb + BAR_XEMPTY + (m - STLAG) * 8) : "memory");
                            }
                            if (++xs == 5) xs = 0;
                        }
                        if (wide && STLAG) {
                            asm volatile("cp.async.bulk.wait_group.read 0;" ::: "memory");
                            asm volatile("mbarrier.arrive.shared::cta.b64 _, [%0], 8;" ::"r"(sb + BAR_XEMPTY + 32) : "memory");
                        }
                        if (IT_PART(e)) {
                            asm volatile("cp.async.bulk.wait_group 0;" ::: "memory");
                            asm volatile("fence.proxy.async;" ::: "memory");
                        }
                    }
                    if (IT_TYPE(e) == IT_QA || IT_PART(e)) {
                        unsigned int* f = &g_flag[bb * 64 + (IT_TYPE(e) == IT_QA ? IT_H0(e) : 32 + IT_HALF(e))];
                        asm volatile("st.release.gpu.global.u32 [%0], %1;" ::"l"(f), "r"(epoch) : "memory");
                    }
                }
                __syncwarp();
            }
            if (threadIdx.x == 64) asm volatile("cp.async.bulk.wait_group 0;" ::: "memory");
            __syncwarp();
            asm volatile("barrier.cluster.arrive.relaxed.aligned;\nbarrier.cluster.wait.aligned;" ::: "memory");
        } else {
            const uint32_t lane = threadIdx.x & 31, p = lane >> 2;
            const uint32_t epoch = next_epoch(3);
#pragma unroll 1
            for (int it = 0;; it++) {
                const uint32_t e = get_item_warp(sb, it, dl);
                if (e == 0) break;
                if (IT_TYPE(e) != IT_QA) continue;
                nb_sync<NB_QK, 160>();
                const uint32_t co = (((lane & 3) * 2) ^ p) << 4;
                const uint32_t ka = sb + OFF_RING + lds_u(sb + OFF_GM + 4) * SLOT + p * (3072 + 128) + co;
                const uint32_t qa = sb + OFF_R + p * 128 + co;
                uint32_t acc = 0;
#pragma unroll 1
                for (int c = 0; c < 3; c++) {
                    if (c == 2) nb_sync<NB_L, 160>();
                    const uint4 k0 = lds_u4(ka + c * 1024), q0 = lds_u4(qa + c * XS);
                    acc = fma_bf2(k0.x, q0.x, fma_bf2(k0.y, q0.y, fma_bf2(k0.z, q0.z, fma_bf2(k0.w, q0.w, acc))));
                    const uint4 k1 = lds_u4((ka + c * 1024) ^ 16), q1 = lds_u4((qa + c * XS) ^ 16);
                    acc = fma_bf2(k1.x, q1.x, fma_bf2(k1.y, q1.y, fma_bf2(k1.z, q1.z, fma_bf2(k1.w, q1.w, acc))));
                }
                float d = __uint_as_float(acc << 16) + __uint_as_float(acc & 0xffff0000u);
                d += __shfl_xor_sync(0xffffffffu, d, 1);
                d += __shfl_xor_sync(0xffffffffu, d, 2);
                int key = __float_as_int(d);
                key ^= (key >> 31) & 0x7fffffff;
                key = __reduce_max_sync(0xffffffffu, key);
                key ^= (key >> 31) & 0x7fffffff;
                sts_f(sb + OFF_GM, fmaf(__int_as_float(key), SM_C, 16.f));
                nb_arrive<NB_REF, 160>();
                if (IT_DEP(e)) {
                    const uint32_t g = IT_DEP(e) - 1, need = epoch * 64 + (g & 31) + 1;
                    const unsigned int* cp = &g_flag[((g >> 5) * 16 + IT_B(e)) * 64 + 34 + (lane & 1)];
                    for (uint32_t n = 0;; n++) {
                        uint32_t v;
                        asm volatile("ld.acquire.gpu.global.u32 %0, [%1];" : "=r"(v) : "l"(cp) : "memory");
                        if (__all_sync(0xffffffffu, v - need < 64)) break;
                        if (n > 0x800000) __trap();
                        __nanosleep(500);
                    }
                }
                nb_sync<NB_L, 160>();
                bool bad = false;
#pragma unroll
                for (int c = 0; c < 5; c++) {
                    const uint32_t la = sb + OFF_LX + (c * 32 + lane) * 4;
                    const float v = (__uint_as_float(lds_u(la)) + __uint_as_float(lds_u(la + 640))) +
                                    (__uint_as_float(lds_u(la + 1280)) + __uint_as_float(lds_u(la + 1920)));
                    const float inv = __fdividef(1.f, v);
                    const uint32_t hi = pack_bf16(inv, 0.f), lo = pack_bf16(inv - __uint_as_float(hi << 16), 0.f);
                    const uint32_t ia = sb + OFF_LINV + c * 128 + ((lane >> 1) & 3) * 32 + (lane >> 3) * 8 + (lane & 1) * 2;
                    asm volatile("st.shared.u16 [%0], %1;\nst.shared.u16 [%0+4], %2;" ::"r"(ia), "h"((unsigned short)hi), "h"((unsigned short)lo) : "memory");
                    bad |= !(v >= 5.421010862e-20f && v <= 7.9228163e28f);
                }
                sts_u(sb + OFF_FB, __any_sync(0xffffffffu, bad));
                nb_arrive<NB_VOTE, 160>();
                nb_arrive<NB_VOTE + 1, 160>();
            }
        }
    } else {
        asm volatile("setmaxnreg.inc.sync.aligned.u32 240;");
        consumer(P, wgid - 1, sb, dl);
    }
}

typedef CUresult (*EncFn)(CUtensorMap*, CUtensorMapDataType, cuuint32_t, void*, const cuuint64_t*, const cuuint64_t*,
                          const cuuint32_t*, const cuuint32_t*, CUtensorMapInterleave, CUtensorMapSwizzle,
                          CUtensorMapL2promotion, CUtensorMapFloatOOBfill);

void make_map3(EncFn enc, CUtensorMap* m, void* p, uint64_t rows, uint64_t rowbytes, uint64_t nblk, uint32_t boxrows,
               uint32_t boxblk) {
    cuuint64_t dims[3] = {64, rows, nblk};
    cuuint64_t str[2] = {rowbytes, 128};
    cuuint32_t box[3] = {64, boxrows, boxblk};
    cuuint32_t es[3] = {1, 1, 1};
    enc(m, CU_TENSOR_MAP_DATA_TYPE_BFLOAT16, 3, p, dims, str, box, es, CU_TENSOR_MAP_INTERLEAVE_NONE,
        CU_TENSOR_MAP_SWIZZLE_128B, CU_TENSOR_MAP_L2_PROMOTION_NONE, CU_TENSOR_MAP_FLOAT_OOB_FILL_NONE);
}

constexpr int tune(const char*, int def) { return def; }

void build_schedule(Params& P) {
    const int mode = tune("MODE", 4), dmax = tune("DMAX", 24900), n0 = tune("N0", 11), odmax = tune("ODMAX", 0), d1 = tune("D1", 0);
    const int H0[8] = {19, 20, 21, 23, 23, 24, 25, 25}, P0[8] = {367, 340, 338, 331, 341, 339, 331, 334};
    const int ra = tune("RA", 10), ga = tune("GA", 17), rb = tune("RB", 11), g1 = tune("G1", 58);
    int dep[64];
    for (int g = 0, ns = 0, live = 0; g < 64; g++) {
        const bool fresh = mode < 3 || g >= g1 || live < (g < ga ? ra : rb);
        dep[g] = fresh ? 0 : g - live + 1;
        P.slot[g] = fresh ? ns++ : P.slot[g - live];
        live += fresh;
    }
    int H[8], pos[8], psum = 0;
    for (int b = 0; b < 8; b++) {
        const char nh[3] = {'H', (char)('0' + b), 0}, np[3] = {'P', (char)('0' + b), 0};
        H[b] = tune(nh, H0[b]);
        pos[b] = tune(np, P0[b]);
        psum += pos[b];
    }
    const int sk = tune("SK", 10), g0 = tune("G0", 20), g2 = tune("G2", 40);
    int ord[512], nxt[8] = {0, 0, 0, 0, 0, 0, 0, 0};
    for (int k = 0; k < 512; k++) {
        int best = -1;
        float bkey = 0.f;
        for (int b = 0; b < 8; b++) {
            const int g = nxt[b];
            if (g == 64) continue;
            const float w = g < g0 ? 0.f : g < 32 ? (g - g0) / (32.f - g0) : g < g2 ? 1.f : (64 - g) / (64.f - g2);
            const float key = g + w * sk * 0.1f * (pos[b] - psum / 8.f) / 8.f;
            if (best < 0 || key < bkey) best = b, bkey = key;
        }
        ord[k] = nxt[best]++ * 8 + best;
        const int d = dep[ord[k] >> 3];
        if (d > 32) {
            if (pos[best] > k) pos[best] = k;
            if (H[best] < d - 32) H[best] = d - 32;
        }
    }
    int u = 0;
    auto unit = [&]() {
        const int v = ord[u++];
        return mk_item(IT_QA, v >> 8, (v & 7) * 2, (v >> 3) & 31, P.slot[v >> 3], 0) | (dep[v >> 3] << 23);
    };
    const int ob = tune("OB", 4), qm = tune("QM", 19);
    int qa[NCL], nq = 0, op[NCL], no = 0;
    for (int c = 0; c < NCL; c++) {
        P.cl[c].delay = 0;
        for (int i = 0; i < NSTAT; i++) P.cl[c].items[i] = 0;
        if (mode >= 3 && ob >= 0 && c >= ob && c < ob + 16) op[((c - ob) & 7) * 2 + ((c - ob) >> 3)] = c, no++;
        else if (mode >= 3 && ob < 0 && c < 64 && (c & 3) == 3) op[no++] = c;
        else if (mode != 2 || (c & 3) == 0) qa[nq++] = c;
    }
    for (int t = 0; t < no; t++) {
        P.cl[op[t]].items[1] = mk_item(IT_OP, 0, t & ~1, 0, 32, t & 1);
        P.cl[op[t]].items[2] = IT_DYN;
        P.cl[op[t]].delay = tune("OD0", 0) + t * odmax / 16;
    }
    for (int k = 0; k < nq; k++) {
        const int c = qa[(k * qm) % nq];
        P.cl[c].items[1] = P.cl[c].items[2] = IT_DYN;
        P.cl[c].delay = k < n0 ? k * tune("J0", 0) : d1 + (dmax - d1) * (k + 1 - n0) / (nq - n0);
    }
    if (tune("OFIRST", 0))
        for (int t = 0; t < no; t++) P.cl[op[t]].items[0] = unit();
    for (int k = u; k < no + nq; k++) {
        int best = -1;
        for (int c = 0; c < NCL; c++)
            if (P.cl[c].items[1] && !P.cl[c].items[0] && (best < 0 || P.cl[c].delay < P.cl[best].delay)) best = c;
        P.cl[best].items[0] = unit();
    }
    int n = 0;
    const int uend = mode == 2 ? 8 * nq : 512;
    while (u < uend) {
        for (int b = 0; b < 8 && no; b++)
            if (pos[b] == u) {
                P.list[n++] = mk_item(IT_OP, 1, 2 * b, 0, H[b], 0, 1);
                P.list[n++] = mk_item(IT_OP, 1, 2 * b, 0, H[b], 1, 1);
            }
        P.list[n++] = unit();
    }
    for (int k = 0; no && k < 40; k++) P.list[n++] = mk_item(IT_ON, 1, k / 5 * 2, H[k / 5], 32, k % 5);
    P.nlist = n;
}

}

extern "C" void kernel_launch(void* const* d_in, const int* in_sizes, int n_in, void* d_out, int out_size) {
    static Params P;
    static bool init = false;
    if (!init) {
        EncFn enc = nullptr;
        cudaDriverEntryPointQueryResult qr;
        cudaGetDriverEntryPoint("cuTensorMapEncodeTiled", (void**)&enc, cudaEnableDefault, &qr);
        for (int i = 0; i < 2; i++) {
            P.px[i] = (const __nv_bfloat16*)d_in[5 * i + 0];
            P.pk[i] = (const __nv_bfloat16*)d_in[5 * i + 1];
            P.pv[i] = (const __nv_bfloat16*)d_in[5 * i + 2];
            P.pwq[i] = (const __nv_bfloat16*)d_in[5 * i + 3];
            make_map3(enc, &P.x[i], d_in[5 * i + 0], 2560, 1280, 10, 160, 1);
            for (int j = 0; j < 2; j++) {
                cuuint64_t dims[4] = {64, 8, 3, 16 * 32 * 64};
                cuuint64_t str[3] = {384, 128, 3072};
                cuuint32_t box[4] = {64, 8, 3, 8};
                cuuint32_t es[4] = {1, 1, 1, 1};
                enc(j ? &P.v[i] : &P.k[i], CU_TENSOR_MAP_DATA_TYPE_BFLOAT16, 4, d_in[5 * i + 1 + j], dims, str, box, es,
                    CU_TENSOR_MAP_INTERLEAVE_NONE, CU_TENSOR_MAP_SWIZZLE_128B, (CUtensorMapL2promotion)tune("PROMO", 0),
                    CU_TENSOR_MAP_FLOAT_OOB_FILL_NONE);
            }
            make_map3(enc, &P.wq[i], d_in[5 * i + 3], 640, 12288, 96, 32, 3);
            make_map3(enc, &P.wo[i], d_in[5 * i + 4], 6144, 1280, 10, 16, 5);
            make_map3(enc, &P.won[i], d_in[5 * i + 4], 6144, 1280, 10, 32, 2);
        }
        cuuint64_t dims[5] = {1280, 2, 4, 4, 80};
        cuuint64_t str[4] = {2560, 8 * 2560, 2 * 2560, 32 * 2560};
        cuuint32_t box[5] = {64, 2, 4, 4, 5};
        cuuint32_t es[5] = {1, 1, 1, 1, 1};
        enc(&P.out, CU_TENSOR_MAP_DATA_TYPE_BFLOAT16, 5, d_out, dims, str, box, es, CU_TENSOR_MAP_INTERLEAVE_NONE,
            CU_TENSOR_MAP_SWIZZLE_128B, CU_TENSOR_MAP_L2_PROMOTION_NONE, CU_TENSOR_MAP_FLOAT_OOB_FILL_NONE);
        build_schedule(P);
        cudaFuncSetAttribute(fused_kernel, cudaFuncAttributeMaxDynamicSharedMemorySize, SMEM_LAUNCH);
        init = true;
    }
    fused_kernel<<<NCTA, 384, SMEM_LAUNCH>>>(P);
}
```

```cpp
#include <cuda_runtime.h>
#include <cuda.h>
#include <cuda_bf16.h>
#include <stdint.h>

namespace {

constexpr int NCTA = 132;
constexpr int NCL = NCTA / 2;
constexpr int MAXI = 16;
constexpr int NSTAT = 3;
constexpr uint32_t IT_DYN = 0xffffffffu;
constexpr int SLOT = 24576;
constexpr int NSLOT = 5;
constexpr int XS = 20480;
constexpr int OFF_R = 0;
constexpr int OFF_RING = 5 * XS;
constexpr int OFF_MISC = OFF_RING + NSLOT * SLOT;
constexpr int OFF_LX = OFF_MISC;
constexpr int OFF_LINV = OFF_LX + 2560;
constexpr int OFF_FB = OFF_LINV + 640;
constexpr int OFF_GM = OFF_FB + 16;
constexpr int OFF_BAR = OFF_GM + 16;
constexpr int BAR_RFULL = OFF_BAR;
constexpr int BAR_REMPTY = BAR_RFULL + 40;
constexpr int BAR_XFULL = BAR_REMPTY + 40;
constexpr int BAR_XEMPTY = BAR_XFULL + 40;
constexpr int BAR_PRDY = BAR_XEMPTY + 40;
constexpr int BAR_ITEM = BAR_PRDY + 40;
constexpr int OFF_ITEM = BAR_ITEM + MAXI * 8;
constexpr int SMEM_BYTES = OFF_ITEM + MAXI * 4;
static_assert(SMEM_BYTES <= 232448, "smem");

constexpr int NB_W = 1  , NB_PFULL = 3  , NB_VOTE = 5  , NB_Q2 = 7, NB_SDONE = 8, NB_PDONE = 9,
              NB_L = 10, NB_REF = 11, NB_ODONE = 12, NB_OPEND = 13, NB_LX = 14, NB_Q01 = 15, NB_QK = 0  ;

constexpr uint32_t IT_QA = 1, IT_OP = 2, IT_ON = 3;
__host__ __device__ constexpr uint32_t mk_item(uint32_t type, uint32_t br, uint32_t b, uint32_t h0, uint32_t h1, uint32_t half,
                                               uint32_t part = 0) {
    return type | (br << 2) | (b << 3) | (h0 << 7) | (h1 << 13) | (half << 19) | (part << 22);
}
#define IT_TYPE(e) ((e) & 3u)
#define IT_BR(e) (((e) >> 2) & 1u)
#define IT_B(e) (((e) >> 3) & 15u)
#define IT_H0(e) (((e) >> 7) & 63u)
#define IT_H1(e) (((e) >> 13) & 63u)
#define IT_HALF(e) (((e) >> 19) & 7u)
#define IT_PART(e) (((e) >> 22) & 1u)
#define IT_SLOT(e) IT_H1(e)
#define IT_DEP(e) (((e) >> 23) & 127u)

struct Params {
    CUtensorMap x[2], wq[2], k[2], v[2], wo[2], won[2], out;
    const __nv_bfloat16 *px[2], *pwq[2], *pk[2], *pv[2];
    struct alignas(16) { uint32_t delay, items[NSTAT]; } cl[NCL];
    uint32_t nlist;
    uint8_t slot[64];
    uint32_t list[512];
};

constexpr int OUNIT = 61440;
__device__ __align__(1024) unsigned char g_ostash[(size_t)1024 * OUNIT];
__device__ unsigned int g_flag[32 * 64];
__device__ __forceinline__ unsigned char* ostash(uint32_t slot, uint32_t b) { return g_ostash + (slot * 16 + b) * OUNIT; }
__device__ unsigned int g_epoch[NCTA * 4];
__device__ unsigned int g_ticket[2];

constexpr int SMEM_LAUNCH = SMEM_BYTES;
#define TS(role, idx)
#define TS_ITEM(e)
#define TS_DUMP(role)
#define TSD(role, idx)

#define POL_W 2
#define POL_X 2
#define POL_O 2
template <int M>
__device__ __forceinline__ uint64_t mkpol() {
    uint64_t p;
    if (M == 0) asm volatile("createpolicy.fractional.L2::evict_normal.b64 %0, 1.0;" : "=l"(p));
    if (M == 1) asm volatile("createpolicy.fractional.L2::evict_first.b64 %0, 1.0;" : "=l"(p));
    if (M == 2) asm volatile("createpolicy.fractional.L2::evict_unchanged.b64 %0, 1.0;" : "=l"(p));
    if (M == 3) asm volatile("createpolicy.fractional.L2::evict_normal.L2::evict_unchanged.b64 %0, 0.25;" : "=l"(p));
    return p;
}
#define STSM_W 1
#define SIGJ 0
#define STLAG 1
#define VEARLY 1
#define LASTORD 0
#define XLATE 2
#define PV0FIRST 1
#define QST0 1
#define QST1 2
#define QHOLD 8
constexpr float SM_C = 0.07216878364870322f * 1.4426950408889634f;

__device__ __forceinline__ uint32_t next_epoch(int warp) {
    unsigned int* p = &g_epoch[blockIdx.x * 4 + warp];
    const uint32_t e = __ldcg(p) + 1;
    *p = e;
    return e;
}

__device__ __forceinline__ uint32_t tid_now() {
    uint32_t t;
    asm volatile("mov.u32 %0, %%tid.x;" : "=r"(t));
    return t;
}
__device__ __forceinline__ void mbar_init(uint32_t a, uint32_t c) {
    asm volatile("mbarrier.init.shared::cta.b64 [%0], %1;" ::"r"(a), "r"(c) : "memory");
}
__device__ __forceinline__ void mbar_expect(uint32_t a, uint32_t b) {
    asm volatile("mbarrier.arrive.expect_tx.shared::cta.b64 _, [%0], %1;" ::"r"(a), "r"(b) : "memory");
}
template <int CNT = 1>
__device__ __forceinline__ void mbar_arrive_warp(uint32_t a) {
    if (CNT == 1)
        asm volatile("{\n.reg .pred p;\nelect.sync _|p, 0xffffffff;\n@p mbarrier.arrive.shared::cta.b64 _, [%0];\n}" ::"r"(a) : "memory");
    else
        asm volatile(
            "{\n.reg .pred p;\nelect.sync _|p, 0xffffffff;\n@p mbarrier.arrive.shared::cta.b64 _, [%0];\n"
            "@p mbarrier.arrive.shared::cta.b64 _, [%0];\n}" ::"r"(a)
            : "memory");
}
template <int CNT = 1>
__device__ __forceinline__ void mbar_arrive_warp_if(uint32_t a, bool cond) {
    if (CNT == 1)
        asm volatile(
            "{\n.reg .pred p, c;\nelect.sync _|p, 0xffffffff;\nsetp.ne.and.u32 c, %1, 0, p;\n"
            "@c mbarrier.arrive.shared::cta.b64 _, [%0];\n}" ::"r"(a), "r"((uint32_t)cond)
            : "memory");
    else
        asm volatile(
            "{\n.reg .pred p, c;\nelect.sync _|p, 0xffffffff;\nsetp.ne.and.u32 c, %1, 0, p;\n"
            "@c mbarrier.arrive.shared::cta.b64 _, [%0];\n@c mbarrier.arrive.shared::cta.b64 _, [%0];\n}" ::"r"(a), "r"((uint32_t)cond)
            : "memory");
}
__device__ __forceinline__ uint32_t deadline() {
    uint32_t c;
    asm volatile("mov.u32 %0, %%clock_hi;" : "=r"(c));
    return c + 4;
}
__device__ __forceinline__ void mbar_wait(uint32_t a, uint32_t ph, uint32_t dl) {
    asm volatile(
        "{\n.reg .pred p;\n.reg .u32 m;\n"
        "LOOP:\n"
        "mbarrier.try_wait.parity.shared::cta.b64 p, [%0], %1;\n"
        "@p bra DONE;\n"
        "mov.u32 m, %%clock_hi;\n"
        "setp.ne.u32 p, m, %2;\n"
        "@p bra LOOP;\n"
        "trap;\n"
        "DONE:\n}" ::"r"(a), "r"(ph), "r"(dl)
        : "memory");
}
__device__ __forceinline__ void mbar_wait2(uint32_t a, uint32_t pa, uint32_t b, uint32_t pb, uint32_t dl) {
    asm volatile(
        "{\n.reg .pred p, q;\n.reg .u32 m;\n"
        "LOOP:\n"
        "mbarrier.try_wait.parity.shared::cta.b64 p, [%0], %1;\n"
        "mbarrier.try_wait.parity.shared::cta.b64 q, [%2], %3;\n"
        "and.pred p, p, q;\n"
        "@p bra DONE;\n"
        "mov.u32 m, %%clock_hi;\n"
        "setp.ne.u32 p, m, %4;\n"
        "@p bra LOOP;\n"
        "trap;\n"
        "DONE:\n}" ::"r"(a), "r"(pa), "r"(b), "r"(pb), "r"(dl)
        : "memory");
}
template <int ID, int CNT>
__device__ __forceinline__ void nb_sync() { asm volatile("bar.sync %0, %1;" ::"n"(ID), "n"(CNT) : "memory"); }
template <int ID, int CNT>
__device__ __forceinline__ void nb_arrive() { asm volatile("bar.arrive %0, %1;" ::"n"(ID), "n"(CNT) : "memory"); }
__device__ __forceinline__ void fence_async_smem() { asm volatile("fence.proxy.async.shared::cta;" ::: "memory"); }

__device__ __forceinline__ void tma3(uint32_t dst, const CUtensorMap* m, int c1, int c2, uint32_t bar, uint64_t pol) {
    asm volatile(
        "cp.async.bulk.tensor.3d.shared::cluster.global.mbarrier::complete_tx::bytes.L2::cache_hint [%0], [%1, {%3,%4,%5}], [%2], %6;" ::"r"(dst),
        "l"(m), "r"(bar), "r"(0), "r"(c1), "r"(c2), "l"(pol)
        : "memory");
}
__device__ __forceinline__ void tma3_mc(uint32_t dst, const CUtensorMap* m, int c1, int c2, uint32_t bar, uint64_t pol) {
    asm volatile(
        "cp.async.bulk.tensor.3d.shared::cluster.global.mbarrier::complete_tx::bytes.multicast::cluster.L2::cache_hint"
        " [%0], [%1, {%3,%4,%5}], [%2], %6, %7;" ::"r"(dst),
        "l"(m), "r"(bar), "r"(0), "r"(c1), "r"(c2), "h"((unsigned short)3), "l"(pol)
        : "memory");
}
__device__ __forceinline__ void bulk_load(uint32_t dst, const void* src, uint32_t bytes, uint32_t bar, uint64_t pol) {
    asm volatile("cp.async.bulk.shared::cluster.global.mbarrier::complete_tx::bytes.L2::cache_hint [%0], [%1], %2, [%3], %4;" ::"r"(dst),
                 "l"(src), "r"(bytes), "r"(bar), "l"(pol)
                 : "memory");
}
__device__ __forceinline__ void wg_fence() { asm volatile("wgmma.fence.sync.aligned;" ::: "memory"); }
__device__ __forceinline__ void wg_commit() { asm volatile("wgmma.commit_group.sync.aligned;" ::: "memory"); }
template <int N>
__device__ __forceinline__ void wg_wait() { asm volatile("wgmma.wait_group.sync.aligned %0;" ::"n"(N) : "memory"); }

#define RW80(c, d) c(d[0]), c(d[1]), c(d[2]), c(d[3]), c(d[4]), c(d[5]), c(d[6]), c(d[7]), c(d[8]), c(d[9]), c(d[10]), c(d[11]), c(d[12]), c(d[13]), c(d[14]), c(d[15]), c(d[16]), c(d[17]), c(d[18]), c(d[19]), c(d[20]), c(d[21]), c(d[22]), c(d[23]), c(d[24]), c(d[25]), c(d[26]), c(d[27]), c(d[28]), c(d[29]), c(d[30]), c(d[31]), c(d[32]), c(d[33]), c(d[34]), c(d[35]), c(d[36]), c(d[37]), c(d[38]), c(d[39]), c(d[40]), c(d[41]), c(d[42]), c(d[43]), c(d[44]), c(d[45]), c(d[46]), c(d[47]), c(d[48]), c(d[49]), c(d[50]), c(d[51]), c(d[52]), c(d[53]), c(d[54]), c(d[55]), c(d[56]), c(d[57]), c(d[58]), c(d[59]), c(d[60]), c(d[61]), c(d[62]), c(d[63]), c(d[64]), c(d[65]), c(d[66]), c(d[67]), c(d[68]), c(d[69]), c(d[70]), c(d[71]), c(d[72]), c(d[73]), c(d[74]), c(d[75]), c(d[76]), c(d[77]), c(d[78]), c(d[79])
#define RW48(c, d) c(d[0]), c(d[1]), c(d[2]), c(d[3]), c(d[4]), c(d[5]), c(d[6]), c(d[7]), c(d[8]), c(d[9]), c(d[10]), c(d[11]), c(d[12]), c(d[13]), c(d[14]), c(d[15]), c(d[16]), c(d[17]), c(d[18]), c(d[19]), c(d[20]), c(d[21]), c(d[22]), c(d[23]), c(d[24]), c(d[25]), c(d[26]), c(d[27]), c(d[28]), c(d[29]), c(d[30]), c(d[31]), c(d[32]), c(d[33]), c(d[34]), c(d[35]), c(d[36]), c(d[37]), c(d[38]), c(d[39]), c(d[40]), c(d[41]), c(d[42]), c(d[43]), c(d[44]), c(d[45]), c(d[46]), c(d[47])
#define RW32(c, d) c(d[0]), c(d[1]), c(d[2]), c(d[3]), c(d[4]), c(d[5]), c(d[6]), c(d[7]), c(d[8]), c(d[9]), c(d[10]), c(d[11]), c(d[12]), c(d[13]), c(d[14]), c(d[15]), c(d[16]), c(d[17]), c(d[18]), c(d[19]), c(d[20]), c(d[21]), c(d[22]), c(d[23]), c(d[24]), c(d[25]), c(d[26]), c(d[27]), c(d[28]), c(d[29]), c(d[30]), c(d[31])

__device__ __forceinline__ void reg_fence(float (&d)[80]) { asm volatile("" : RW80("+f", d)::"memory"); }
__device__ __forceinline__ void reg_fence(float (&d)[48]) { asm volatile("" : RW48("+f", d)::"memory"); }
__device__ __forceinline__ void reg_fence(float (&d)[32]) { asm volatile("" : RW32("+f", d)::"memory"); }

template <int NR>
__device__ __forceinline__ void zero(float (&d)[NR]) {
#pragma unroll
    for (int i = 0; i < NR; i++) d[i] = 0.f;
}

constexpr uint32_t HI_SW128 = (1024u >> 4) | (1u << 30);
constexpr uint32_t HI_KV = (3072u >> 4) | (1u << 30);
constexpr uint32_t HI_OST = (2560u >> 4) | (2u << 30);
constexpr uint32_t LO_LBO1 = (1u << 16);
constexpr uint32_t LO_OST = ((512u >> 4) << 16);

template <int TA, int TB, uint32_t HIB, int ACC, uint32_t HIA = HI_SW128>
__device__ __forceinline__ void wgmma(float (&d)[80], uint32_t loA, uint32_t loB) {
#define WG_ASM(SD)                                                          \
    "{\n.reg .b64 da, db;\nmov.b64 da, {%80, %82};\nmov.b64 db, {%81, %83};\n" \
    "wgmma.mma_async.sync.aligned.m64n160k16.f32.bf16.bf16 "               \
    "{%0,%1,%2,%3,%4,%5,%6,%7,%8,%9,%10,%11,%12,%13,%14,%15,%16,%17,%18,%19,%20,%21,%22,%23,%24,%25,%26,%27,%28,%29,%30,%31,%32,%33,%34,%35,%36,%37,%38,%39,%40,%41,%42,%43,%44,%45,%46,%47,%48,%49,%50,%51,%52,%53,%54,%55,%56,%57,%58,%59,%60,%61,%62,%63,%64,%65,%66,%67,%68,%69,%70,%71,%72,%73,%74,%75,%76,%77,%78,%79}, da, db, " SD ", 1, 1, %84, %85;\n}"
    if constexpr (ACC == 2)
        asm volatile(WG_ASM("0") : RW80("+f", d) : "r"(loA), "r"(loB), "n"(HIA), "n"(HIB), "n"(TA), "n"(TB));
    else if constexpr (ACC == 1)
        asm volatile(WG_ASM("1") : RW80("+f", d) : "r"(loA), "r"(loB), "n"(HIA), "n"(HIB), "n"(TA), "n"(TB));
    else
        asm volatile(WG_ASM("0") : RW80("=f", d) : "r"(loA), "r"(loB), "n"(HIA), "n"(HIB), "n"(TA), "n"(TB));
#undef WG_ASM
}
template <int TA, int TB, uint32_t HIB, int ACC, uint32_t HIA = HI_SW128>
__device__ __forceinline__ void wgmma(float (&d)[48], uint32_t loA, uint32_t loB) {
#define WG_ASM(SD)                                                          \
    "{\n.reg .b64 da, db;\nmov.b64 da, {%48, %50};\nmov.b64 db, {%49, %51};\n" \
    "wgmma.mma_async.sync.aligned.m64n96k16.f32.bf16.bf16 "               \
    "{%0,%1,%2,%3,%4,%5,%6,%7,%8,%9,%10,%11,%12,%13,%14,%15,%16,%17,%18,%19,%20,%21,%22,%23,%24,%25,%26,%27,%28,%29,%30,%31,%32,%33,%34,%35,%36,%37,%38,%39,%40,%41,%42,%43,%44,%45,%46,%47}, da, db, " SD ", 1, 1, %52, %53;\n}"
    if constexpr (ACC == 1)
        asm volatile(WG_ASM("1") : RW48("+f", d) : "r"(loA), "r"(loB), "n"(HIA), "n"(HIB), "n"(TA), "n"(TB));
    else
        asm volatile(WG_ASM("0") : RW48("=f", d) : "r"(loA), "r"(loB), "n"(HIA), "n"(HIB), "n"(TA), "n"(TB));
#undef WG_ASM
}
template <int TA, int TB, uint32_t HIB, int ACC, uint32_t HIA = HI_SW128>
__device__ __forceinline__ void wgmma(float (&d)[32], uint32_t loA, uint32_t loB) {
#define WG_ASM(SD)                                                          \
    "{\n.reg .b64 da, db;\nmov.b64 da, {%32, %34};\nmov.b64 db, {%33, %35};\n" \
    "wgmma.mma_async.sync.aligned.m64n64k16.f32.bf16.bf16 "               \
    "{%0,%1,%2,%3,%4,%5,%6,%7,%8,%9,%10,%11,%12,%13,%14,%15,%16,%17,%18,%19,%20,%21,%22,%23,%24,%25,%26,%27,%28,%29,%30,%31}, da, db, " SD ", 1, 1, %36, %37;\n}"
    if constexpr (ACC == 1)
        asm volatile(WG_ASM("1") : RW32("+f", d) : "r"(loA), "r"(loB), "n"(HIA), "n"(HIB), "n"(TA), "n"(TB));
    else
        asm volatile(WG_ASM("0") : RW32("=f", d) : "r"(loA), "r"(loB), "n"(HIA), "n"(HIB), "n"(TA), "n"(TB));
#undef WG_ASM
}

__device__ __forceinline__ uint32_t pack_bf16(float lo, float hi) {
    uint32_t r;
    asm("cvt.rn.bf16x2.f32 %0, %1, %2;" : "=r"(r) : "f"(hi), "f"(lo));
    return r;
}
__device__ __forceinline__ float ex2(float x) {
    float r;
    asm("ex2.approx.ftz.f32 %0, %1;" : "=f"(r) : "f"(x));
    return r;
}
__device__ __forceinline__ void stsm4t(uint32_t a, uint32_t r0, uint32_t r1, uint32_t r2, uint32_t r3) {
    asm volatile("stmatrix.sync.aligned.m8n8.x4.trans.shared.b16 [%0], {%1,%2,%3,%4};" ::"r"(a), "r"(r0), "r"(r1), "r"(r2), "r"(r3)
                 : "memory");
}
__device__ __forceinline__ uint32_t lds_u(uint32_t a) {
    uint32_t v;
    asm volatile("ld.shared.u32 %0, [%1];" : "=r"(v) : "r"(a) : "memory");
    return v;
}
__device__ __forceinline__ uint4 lds_u4(uint32_t a) {
    uint4 v;
    asm volatile("ld.shared.v4.u32 {%0,%1,%2,%3}, [%4];" : "=r"(v.x), "=r"(v.y), "=r"(v.z), "=r"(v.w) : "r"(a) : "memory");
    return v;
}
__device__ __forceinline__ float2 lds_f2(uint32_t a) {
    float2 v;
    asm volatile("ld.shared.v2.f32 {%0,%1}, [%2];" : "=f"(v.x), "=f"(v.y) : "r"(a) : "memory");
    return v;
}
__device__ __forceinline__ void sts_f(uint32_t a, float v) { asm volatile("st.shared.f32 [%0], %1;" ::"r"(a), "f"(v) : "memory"); }
__device__ __forceinline__ void sts_u(uint32_t a, uint32_t v) { asm volatile("st.shared.u32 [%0], %1;" ::"r"(a), "r"(v) : "memory"); }
__device__ __forceinline__ void sts_f2(uint32_t a, float x, float y) {
    asm volatile("st.shared.v2.f32 [%0], {%1,%2};" ::"r"(a), "f"(x), "f"(y) : "memory");
}

template <bool ADD = false, bool SIG = false, int NR>
__device__ __forceinline__ void store_tile_t(const float (&d)[NR], uint32_t addr) {
    uint32_t p[NR / 2];
    if (ADD) {
#pragma unroll
        for (int j = 0; j < NR / 8; j++)
            asm volatile("ldmatrix.sync.aligned.m8n8.x4.trans.shared.b16 {%0,%1,%2,%3}, [%4];"
                         : "=r"(p[4 * j]), "=r"(p[4 * j + 1]), "=r"(p[4 * j + 2]), "=r"(p[4 * j + 3])
                         : "r"(addr + j * 2048)
                         : "memory");
    }
#pragma unroll
    for (int k = 0; k < NR / 2; k++)
        p[k] = ADD ? pack_bf16(d[2 * k] + __uint_as_float(p[k] << 16), d[2 * k + 1] + __uint_as_float(p[k] & 0xffff0000u))
                   : pack_bf16(d[2 * k], d[2 * k + 1]);
#pragma unroll
    for (int j = 0; j < NR / 8; j++) {
        stsm4t(addr + j * 2048, p[4 * j], p[4 * j + 1], p[4 * j + 2], p[4 * j + 3]);
        if (SIG && j == SIGJ) nb_arrive<NB_L, 160>();
    }
}

struct TrueT { static constexpr bool value = true; };
struct FalseT { static constexpr bool value = false; };

template <int V>
struct IntT { static constexpr int value = V; };

__device__ __forceinline__ uint32_t get_item(uint32_t sb, int it, uint32_t dl) {
    mbar_wait(sb + BAR_ITEM + it * 8, 0, dl);
    return lds_u(sb + OFF_ITEM + it * 4);
}
__device__ __forceinline__ uint32_t get_item_warp(uint32_t sb, int it, uint32_t dl) {
    return __shfl_sync(0xffffffffu, get_item(sb, it, dl), 0);
}

struct Ring {
    uint32_t slot, ph, dl;
    __device__ __forceinline__ void adv(uint32_t k) {
        slot += k;
        if (slot >= NSLOT) { slot -= NSLOT; ph ^= 1; }
    }
};

template <int K>
__device__ __forceinline__ void qk_step(float (&s)[80], uint32_t loK, uint32_t loQ) {
    wgmma<0, 0, HI_SW128, K != 0, HI_KV>(s, loK + (K >> 2) * 64 + (K & 3) * 2, loQ + (K >> 2) * (XS >> 4) + (K & 3) * 2);
}
template <int K0, int K1>
__device__ __forceinline__ void qk_steps(float (&s)[80], uint32_t loK, uint32_t loQ) {
    if constexpr (K0 < K1) {
        qk_step<K0>(s, loK, loQ);
        qk_steps<K0 + 1, K1>(s, loK, loQ);
    }
}
__device__ __forceinline__ uint32_t add_bf2(uint32_t a, uint32_t b) {
    uint32_t r;
    asm("add.rn.bf16x2 %0, %1, %2;" : "=r"(r) : "r"(a), "r"(b));
    return r;
}
__device__ __forceinline__ uint32_t fma_bf2(uint32_t a, uint32_t b, uint32_t c) {
    uint32_t r;
    asm("fma.rn.bf16x2 %0, %1, %2, %3;" : "=r"(r) : "r"(a), "r"(b), "r"(c));
    return r;
}
template <int J>
__device__ __forceinline__ void exp_block(const float (&s)[80], uint32_t (&k)[40], uint32_t pa, float mref) {
    if constexpr (J < 10) {
#pragma unroll
        for (int i = 4 * J; i < 4 * J + 4; i++)
            k[i] = pack_bf16(ex2(fmaf(s[2 * i], SM_C, -mref)), ex2(fmaf(s[2 * i + 1], SM_C, -mref)));
#pragma unroll
        for (int i = 0; i < 4; i++)
            asm volatile("stmatrix.sync.aligned.m8n8.x1.trans.shared.b16 [%0], {%1};" ::"r"(((i & 1) ? pa ^ 16 : pa) + J * 2048 + (i >> 1) * 1024),
                         "r"(k[4 * J + i])
                         : "memory");
        exp_block<J + 1>(s, k, pa, mref);
    }
}
__device__ __forceinline__ void sum_block(const uint32_t (&k)[40], float (&l)[10], uint32_t lane) {
    const bool b4 = lane & 16, b3 = lane & 8;
    uint32_t ps[20], t[10];
#pragma unroll
    for (int j = 0; j < 20; j++) ps[j] = add_bf2(k[2 * j], k[2 * j + 1]);
#pragma unroll
    for (int j = 0; j < 10; j++)
        t[j] = add_bf2(b4 ? ps[2 * j + 1] : ps[2 * j], __shfl_xor_sync(0xffffffffu, b4 ? ps[2 * j] : ps[2 * j + 1], 16));
#pragma unroll
    for (int i = 0; i < 5; i++) {
        const uint32_t a = b3 ? t[i + 5] : t[i], b = __shfl_xor_sync(0xffffffffu, b3 ? t[i] : t[i + 5], 8);
        l[2 * i] += __uint_as_float(a << 16) + __uint_as_float(b << 16);
        l[2 * i + 1] += __uint_as_float(a & 0xffff0000u) + __uint_as_float(b & 0xffff0000u);
    }
}
template <bool ADD>
__device__ __forceinline__ void sum_store(const float (&l)[10], uint32_t lane, uint32_t lxa) {
    const bool b2 = lane & 4;
    float t[5];
#pragma unroll
    for (int i = 0; i < 5; i++) t[i] = ADD ? __uint_as_float(lds_u(lxa + i * 64)) : 0.f;
#pragma unroll
    for (int i = 0; i < 5; i++)
        sts_f(lxa + i * 64, t[i] + (b2 ? l[2 * i + 1] : l[2 * i]) + __shfl_xor_sync(0xffffffffu, b2 ? l[2 * i] : l[2 * i + 1], 4));
}

__device__ __forceinline__ void fallback_unit(const Params& P, uint32_t e, uint32_t tid) {
    const uint32_t lane = tid & 31, br = IT_BR(e), b = IT_B(e), h = IT_H0(e);
    const __nv_bfloat162* wq = (const __nv_bfloat162*)(P.pwq[br] + h * 192) + lane;
    const __nv_bfloat162* kp = (const __nv_bfloat162*)(P.pk[br] + (size_t)(b * 32 + h) * 512 * 192) + lane;
    const __nv_bfloat162* vp = (const __nv_bfloat162*)(P.pv[br] + (size_t)(b * 32 + h) * 512 * 192) + lane;
#pragma unroll 1
    for (uint32_t qi = 0; qi < 40; qi++) {
        const uint32_t q = 4 * qi + (tid >> 5);
        const __nv_bfloat16* xr = P.px[br] + (size_t)(b * 160 + q) * 640;
        float a[6] = {0.f, 0.f, 0.f, 0.f, 0.f, 0.f};
#pragma unroll 2
        for (int k = 0; k < 640; k++) {
            const float xv = __bfloat162float(xr[k]);
#pragma unroll
            for (int i = 0; i < 3; i++) {
                const float2 wv = __bfloat1622float2(wq[(size_t)k * 3072 + i * 32]);
                a[2 * i] = fmaf(xv, wv.x, a[2 * i]);
                a[2 * i + 1] = fmaf(xv, wv.y, a[2 * i + 1]);
            }
        }
#pragma unroll
        for (int i = 0; i < 6; i++) a[i] = __bfloat162float(__float2bfloat16(a[i]));
        auto score = [&](int key) {
            float d = 0.f;
#pragma unroll
            for (int i = 0; i < 3; i++) {
                const float2 kv = __bfloat1622float2(kp[key * 96 + i * 32]);
                d = fmaf(a[2 * i], kv.x, fmaf(a[2 * i + 1], kv.y, d));
            }
#pragma unroll
            for (int o = 16; o > 0; o >>= 1) d += __shfl_xor_sync(0xffffffffu, d, o);
            return d;
        };
        float m = -INFINITY, o[6] = {0.f, 0.f, 0.f, 0.f, 0.f, 0.f}, sum = 0.f;
#pragma unroll 1
        for (int n = 0; n < 1024; n++) {
            const int key = n & 511;
            const float d = score(key);
            if (n < 512) {
                m = fmaxf(m, d);
            } else {
                const float p = ex2((d - m) * SM_C);
                sum += p;
#pragma unroll
                for (int i = 0; i < 3; i++) {
                    const float2 vv = __bfloat1622float2(vp[key * 96 + i * 32]);
                    o[2 * i] = fmaf(p, vv.x, o[2 * i]);
                    o[2 * i + 1] = fmaf(p, vv.y, o[2 * i + 1]);
                }
            }
        }
        const float inv = __fdividef(1.f, sum);
        __nv_bfloat16* op = (__nv_bfloat16*)ostash(IT_SLOT(e), b) + (q >> 5) * 256 + 2 * ((q & 31) >> 3) + (q & 1);
#pragma unroll
        for (int i = 0; i < 6; i++) {
            const uint32_t d = (i >> 1) * 64 + 2 * lane + (i & 1);
            op[(d >> 3) * 1280 + (d & 7) * 32 + ((((q & 7) >> 1) ^ ((d & 7) >> 1)) << 3)] = __float2bfloat16(o[i] * inv);
        }
    }
}

template <int W>
struct PendO {
    static constexpr int N = W == 0 ? 56 : 64;
    uint32_t v[N];
    unsigned char* gp;
    static __device__ __forceinline__ uint32_t toff() {
        const uint32_t t = tid_now();
        return ((t >> 5) & 3) * 5120 + ((t >> 2) & 7) * 64 + (((t ^ (t >> 3)) & 3) << 4);
    }
    uint32_t pend, sig, bad;
    static __device__ __forceinline__ void scale(uint32_t& x, uint32_t hi, uint32_t lo) {
        asm("{\n.reg .b32 t;\nmul.rn.bf16x2 t, %0, %2;\nfma.rn.bf16x2 %0, %0, %1, t;\n}" : "+r"(x) : "r"(hi), "r"(lo));
    }
    template <int I, int OFF>
    __device__ __forceinline__ void put() {
        asm volatile("{\n.reg .pred p;\nsetp.ne.u32 p, %6, 0;\n@p st.global.v4.b32 [%0+%5], {%1,%2,%3,%4};\n}" ::"l"(gp), "r"(v[I]),
                     "r"(v[I + 1]), "r"(v[I + 2]), "r"(v[I + 3]), "n"(OFF), "r"(pend)
                     : "memory");
    }
    __device__ __forceinline__ void verdict(uint32_t sb) {
        if (sig) {
            nb_sync<NB_VOTE + W, 160>();
            bad = __any_sync(0xffffffffu, lds_u(sb + OFF_FB) != 0);
            pend = !bad;
        }
    }
    template <int G, int H>
    __device__ __forceinline__ void half(uint32_t sb) {
        constexpr bool T2 = W == 0 ? G >= 3 : G < 3;
        constexpr int B = T2 ? 40 + 8 * (W == 0 ? G - 3 : G) : 0;
        const uint4 a = lds_u4(sb + OFF_LINV + G * 128 + H * 16 + (threadIdx.x & 3) * 32);
#pragma unroll
        for (int i = 2 * H; i < 8; i += 4) {
            scale(v[8 * G + i], a.x, a.y);
            scale(v[8 * G + i + 1], a.z, a.w);
            if (T2) {
                scale(v[B + i], a.x, a.y);
                scale(v[B + i + 1], a.z, a.w);
            }
        }
        if (H == 1) {
            put<8 * G, W * XS + G * 512>();
            put<8 * G + 4, W * XS + G * 512 + 2560>();
            if (T2) {
                put<B, 2 * XS + G * 512>();
                put<B + 4, 2 * XS + G * 512 + 2560>();
            }
            if (G == 4 && pend) nb_arrive<NB_ODONE, 288>();
        }
    }
    template <int G>
    __device__ __forceinline__ void step(uint32_t sb) {
        half<G, 0>(sb);
        half<G, 1>(sb);
    }
    __device__ __forceinline__ void clear() {
#pragma unroll
        for (int i = 0; i < N; i++) v[i] = 0;
        gp = nullptr;
        pend = 0;
        sig = 0;
        bad = 0;
    }
};

__device__ __forceinline__ uint32_t stsm_off() {
    const uint32_t tid = tid_now(), lane = tid & 31;
    return (lane >> 4) * 1024 + (lane & 7) * 128 + (((((tid >> 4) & 6) + ((lane >> 3) & 1)) ^ (lane & 7)) << 4);
}
__device__ __forceinline__ void q_ahead(float (&q0)[80], uint32_t sb, const Ring& rn, uint32_t phm, bool valid) {
    if (valid) mbar_wait2(sb + BAR_RFULL + rn.slot * 8, rn.ph, sb + BAR_XFULL, phm & 1, rn.dl);
    const uint32_t a = ((((sb + OFF_RING) & 0x3ffff) >> 4) | LO_LBO1) + rn.slot * (SLOT >> 4);
    const uint32_t b = (((sb + OFF_R) & 0x3ffff) >> 4) | LO_LBO1;
    wg_fence();
    wgmma<1, 0, HI_SW128, false>(q0, a, b);
#pragma unroll
    for (int k = 1; k < 4; k++) wgmma<1, 0, HI_SW128, true>(q0, a + (k >> 1) * 768 + (k & 1) * 128, b + k * 2);
    wg_commit();
}
template <int W, int KK>
__device__ __forceinline__ void qproj(float (&q0)[80], float (&q1)[80], uint32_t sb, Ring& r, uint32_t pslot, uint32_t phm,
                                      PendO<W>& po) {
    const uint32_t loR = (((sb + OFF_R) & 0x3ffff) >> 4) | LO_LBO1;
    const uint32_t loRing = (((sb + OFF_RING) & 0x3ffff) >> 4) | LO_LBO1;
    auto ready = [&](int k) {
        mbar_wait2(sb + BAR_RFULL + r.slot * 8, r.ph, sb + BAR_XFULL + (k % 5) * 8, ((phm >> (k % 5)) ^ (k / 5)) & 1, r.dl);
    };
    auto release = [&]() {
        if (KK > 0) {
            wg_wait<1>();
            mbar_arrive_warp(sb + BAR_REMPTY + pslot * 8);
            if (KK <= 5) mbar_arrive_warp(sb + (BAR_XEMPTY + (KK - 1) * 8));
        }
    };
    if (KK == 0 && W == 1) ready(0);
    if (W == 1 && KK == QHOLD) {
        if (QHOLD == 7) {
            wg_wait<0>();
            nb_arrive<NB_PDONE, 256>();
        }
        nb_sync<NB_SDONE, 256>();
    }
    const uint32_t a = loRing + r.slot * (SLOT >> 4) + (W == 0 ? 0 : 512), b = loR + (KK % 5) * (XS >> 4);
    wg_fence();
    constexpr bool T0 = W == 1 || KK > 0;
    if (T0) wgmma<1, 0, HI_SW128, KK != 0>(q0, a, b);
    if (W == 0) wgmma<1, 0, HI_SW128, KK != 0 ? 1 : 2>(q1, a + 256, b);
#pragma unroll
    for (int k = 1; k < 4; k++) {
        if (T0) wgmma<1, 0, HI_SW128, true>(q0, a + (k >> 1) * 768 + (k & 1) * 128, b + k * 2);
        if (W == 0) wgmma<1, 0, HI_SW128, true>(q1, a + 256 + (k >> 1) * 768 + (k & 1) * 128, b + k * 2);
    }
    wg_commit();
    const uint32_t cslot = r.slot;
    r.adv(1);
    if (W == 0 || KK < QHOLD) release();
    if (KK == QST0) {
        po.verdict(sb);
        po.template half<0, 0>(sb);
    }
    if (KK < 9) ready(KK + 1);
    if (W == 1 && KK >= QHOLD) release();
    if (W == 1 && KK == 7 && QHOLD > 7) nb_arrive<NB_PDONE, 256>();
    if (KK == QST0) po.template half<0, 1>(sb);
    if constexpr (KK > QST0 && KK < QST0 + 5) po.template step<KK - QST0>(sb);
    if constexpr (KK < (W == 0 ? 7 : 9)) {
        qproj<W, KK + 1>(q0, q1, sb, r, cslot, phm, po);
    } else if constexpr (W == 1) {
        const uint32_t sta = sb + OFF_R + 2 * XS + stsm_off();
        wg_wait<0>();
        reg_fence(q0);
        store_tile_t<false, true>(q0, sta);
        mbar_arrive_warp(sb + BAR_REMPTY + cslot * 8);
    } else {
        const uint32_t s8 = r.slot, a8 = loRing + s8 * (SLOT >> 4);
        wg_fence();
#pragma unroll
        for (int k = 0; k < 4; k++) wgmma<1, 0, HI_SW128, true>(q0, a8 + (k >> 1) * 768 + (k & 1) * 128, loR + 3 * (XS >> 4) + k * 2);
        r.adv(1);
        ready(9);
        const uint32_t s9 = r.slot, a9 = loRing + s9 * (SLOT >> 4);
        r.adv(1);
        wg_fence();
#pragma unroll
        for (int k = 0; k < 4; k++) wgmma<1, 0, HI_SW128, true>(q0, a9 + (k >> 1) * 768 + (k & 1) * 128, loR + 4 * (XS >> 4) + k * 2);
        wg_commit();
        wg_wait<1>();
        mbar_arrive_warp(sb + BAR_REMPTY + cslot * 8);
        wg_fence();
#pragma unroll
        for (int k = 0; k < 8; k++)
            wgmma<1, 0, HI_SW128, true>(q1, (k < 4 ? a8 : a9) + 256 + ((k >> 1) & 1) * 768 + (k & 1) * 128,
                                        loR + (3 + (k >> 2)) * (XS >> 4) + (k & 3) * 2);
        wg_commit();
        nb_arrive<NB_SDONE, 256>();
        nb_sync<NB_PDONE, 256>();
        wg_wait<1>();
        reg_fence(q0);
        const uint32_t sta = sb + OFF_R + stsm_off();
        store_tile_t(q0, sta);
        sts_u(sb + OFF_GM + 4, r.slot);
        mbar_wait(sb + BAR_RFULL + r.slot * 8, r.ph, r.dl);
        wg_wait<0>();
        reg_fence(q1);
        mbar_arrive_warp(sb + BAR_REMPTY + s8 * 8);
        mbar_arrive_warp(sb + BAR_REMPTY + s9 * 8);
        store_tile_t(q1, sta + XS);
    }
}

template <int NR>
__device__ __forceinline__ void opack(const float (&o)[NR], uint32_t* v) {
#pragma unroll
    for (int g = 0; g < NR / 16; g++)
#pragma unroll
        for (int hh = 0; hh < 2; hh++)
#pragma unroll
            for (int t = 0; t < 4; t++) v[8 * g + 4 * hh + t] = pack_bf16(o[16 * g + 4 * t + 2 * hh], o[16 * g + 4 * t + 2 * hh + 1]);
}

template <bool IS_S>
__device__ __forceinline__ void op_item(uint32_t e, uint32_t sb, Ring& r, uint32_t& phm) {
    constexpr int T0 = IS_S ? 0 : 2;
    constexpr uint32_t BOFF = IS_S ? (3 * 512) >> 4 : 0;
    const uint32_t loRing = (((sb + OFF_RING) & 0x3ffff) >> 4) | LO_LBO1;
    const uint32_t loO = (((sb + OFF_R) & 0x3ffff) >> 4) | LO_OST;
    float c0[80], c1[80], c2[IS_S ? 32 : 48];
    const int T = 3 * (IT_H1(e) - IT_H0(e));
    uint32_t xs = 0;
    auto step = [&](auto first, auto half) {
        constexpr bool F = decltype(first)::value;
        constexpr uint32_t hf = decltype(half)::value;
        if (hf == 0) {
            mbar_wait(sb + BAR_XFULL + xs * 8, (phm >> xs) & 1, r.dl);
            phm ^= 1u << xs;
        }
        mbar_wait(sb + BAR_RFULL + r.slot * 8, r.ph, r.dl);
        const uint32_t a = loRing + r.slot * (SLOT >> 4), b = loO + xs * (XS >> 4) + hf * 640;
        wg_fence();
        wgmma<1, 1, HI_OST, !F>(c0, a + T0 * 128, b);
        wgmma<1, 1, HI_OST, !F>(c1, a + T0 * 128 + 128, b);
        wgmma<1, 1, HI_OST, !F>(c2, a + 512, b + BOFF);
        wgmma<1, 1, HI_OST, true>(c0, a + 640 + T0 * 128, b + 320);
        wgmma<1, 1, HI_OST, true>(c1, a + 640 + T0 * 128 + 128, b + 320);
        wgmma<1, 1, HI_OST, true>(c2, a + 640 + 512, b + 320 + BOFF);
        wg_commit();
    };
    step(TrueT{}, IntT<0>{});
#pragma unroll 1
    for (int t = 1;; t++) {
        uint32_t pslot = r.slot;
        r.adv(1);
        step(FalseT{}, IntT<1>{});
        wg_wait<1>();
        mbar_arrive_warp(sb + BAR_REMPTY + pslot * 8);
        if (t == T) break;
        pslot = r.slot;
        const uint32_t pxs = xs;
        r.adv(1);
        if (++xs == 5) xs = 0;
        step(FalseT{}, IntT<0>{});
        wg_wait<1>();
        mbar_arrive_warp(sb + BAR_REMPTY + pslot * 8);
        mbar_arrive_warp_if(sb + BAR_XEMPTY + pxs * 8, t + 4 < T);
    }
    wg_wait<0>();
    reg_fence(c0);
    reg_fence(c1);
    reg_fence(c2);
    mbar_arrive_warp(sb + BAR_REMPTY + r.slot * 8);
    r.adv(1);
    nb_sync<NB_OPEND, 256>();
    const uint32_t sta = sb + OFF_R + stsm_off();
    store_tile_t(c0, sta + T0 * XS);
    store_tile_t(c1, sta + (T0 + 1) * XS);
    store_tile_t(c2, sta + 4 * XS + (IS_S ? 96 * 128 : 0));
    fence_async_smem();
    nb_arrive<NB_ODONE, 288>();
}

__device__ __forceinline__ void on_item(uint32_t W, uint32_t e, uint32_t sb, Ring& r, uint32_t& phm) {
    const uint32_t loRing = (((sb + OFF_RING) & 0x3ffff) >> 4) | LO_LBO1;
    const uint32_t loO = (((sb + OFF_R) & 0x3ffff) >> 4) | LO_OST;
    float c[80];
    const int T = 3 * (IT_H1(e) - IT_H0(e));
    uint32_t xs = 0;
    auto step = [&](auto first) {
        constexpr bool F = decltype(first)::value;
        mbar_wait2(sb + BAR_XFULL + xs * 8, (phm >> xs) & 1, sb + BAR_RFULL + r.slot * 8, r.ph, r.dl);
        phm ^= 1u << xs;
        const uint32_t a = loRing + r.slot * (SLOT >> 4) + W * 256, b = loO + xs * (XS >> 4);
        wg_fence();
        wgmma<1, 1, HI_OST, !F>(c, a, b);
#pragma unroll
        for (int k = 1; k < 4; k++) wgmma<1, 1, HI_OST, true>(c, a + (k >> 1) * 512 + (k & 1) * 128, b + k * 320);
        wg_commit();
    };
    step(TrueT{});
#pragma unroll 1
    for (int t = 1; t < T; t++) {
        const uint32_t pslot = r.slot, pxs = xs;
        r.adv(1);
        if (++xs == 5) xs = 0;
        step(FalseT{});
        wg_wait<1>();
        mbar_arrive_warp(sb + BAR_REMPTY + pslot * 8);
        mbar_arrive_warp_if(sb + BAR_XEMPTY + pxs * 8, t + 2 < T);
    }
    xs += 1 + W;
    if (xs >= 5) xs -= 5;
    mbar_wait(sb + BAR_XFULL + xs * 8, (phm >> xs) & 1, r.dl);
    wg_wait<0>();
    reg_fence(c);
    store_tile_t<true>(c, sb + OFF_R + xs * XS + stsm_off());
    fence_async_smem();
    nb_arrive<NB_ODONE, 288>();
}

template <int W>
__device__ __forceinline__ uint32_t qa_item(uint32_t e, uint32_t sb, Ring& r, uint32_t phm, PendO<W>& po, float (&q0)[80],
                                            float (&oa)[80], int it) {
    const uint32_t loR = (((sb + OFF_R) & 0x3ffff) >> 4) | LO_LBO1;
    const uint32_t loRing = (((sb + OFF_RING) & 0x3ffff) >> 4) | LO_LBO1;
    qproj<W, 0>(q0, oa, sb, r, 0, phm, po);
    fence_async_smem();
    TSD(W, 1);
    float s[80], ob[W == 0 ? 32 : 48], l[10];
    if (W == 1) {
        nb_arrive<NB_Q2, 256>();
        zero(oa);
        zero(ob);
        reg_fence(oa);
        reg_fence(ob);
    }
    const uint32_t lane = tid_now() & 31, sta = sb + OFF_R + stsm_off();
    auto pv = [&](auto first, uint32_t buf, bool wait = true) {
        constexpr bool F = decltype(first)::value;
        if (wait) mbar_wait(sb + BAR_RFULL + r.slot * 8, r.ph, r.dl);
        const uint32_t a = loRing + r.slot * (SLOT >> 4), b = loR + (3 + buf) * (XS >> 4);
        wg_fence();
        wgmma<1, 0, HI_SW128, F ? 2 : 1, HI_KV>(oa, a + W * 64, b);
        wgmma<1, 0, HI_SW128, !F, HI_KV>(ob, a + 128, b + (W == 0 ? (96 * 128) >> 4 : 0));
#pragma unroll
        for (int k = 1; k < 4; k++) {
            wgmma<1, 0, HI_SW128, true, HI_KV>(oa, a + W * 64 + k * 384, b + k * 2);
            wgmma<1, 0, HI_SW128, true, HI_KV>(ob, a + 128 + k * 384, b + (W == 0 ? (96 * 128) >> 4 : 0) + k * 2);
        }
        wg_commit();
    };
    zero(l);
    float mref;
    uint32_t kslot, vslot, nx = 0;
    auto tail = [&](auto first, int i) {
        constexpr bool rel_other = !decltype(first)::value;
        uint32_t ps[40];
        exp_block<0>(s, ps, sta + (3 + W) * XS, mref);
        if (rel_other) {
            wg_wait<0>();
            mbar_arrive_warp(sb + BAR_REMPTY + vslot * 8);
            if (W == 1) mbar_arrive_warp_if(sb + BAR_XEMPTY + 24, i == 3);
        }
        fence_async_smem();
        nb_arrive<NB_PFULL + W, 256>();
        TSD(W, 6 + 5 * i);
        if (W == 1) {
            if (XLATE >= 2) mbar_arrive_warp_if<2>(sb + BAR_XEMPTY + 8, i == 3);
            if (XLATE >= 1) mbar_arrive_warp_if<2>(sb + BAR_XEMPTY + 16, i == 3);
        }
        if (rel_other || !PV0FIRST) {
            mbar_wait(sb + BAR_RFULL + r.slot * 8, r.ph, r.dl);
            sum_block(ps, l, lane);
        }
        if (W == 0 && i == 3) nx = get_item_warp(sb, it + 1, r.dl);
        TSD(W, 7 + 5 * i);
        if (LASTORD && W == 0 && i == 3) nb_sync<NB_PDONE, 256>();
        else nb_sync<NB_W + W, 128>();
        pv(first, W, !rel_other && PV0FIRST);
        if (!rel_other && PV0FIRST) sum_block(ps, l, lane);
        TSD(W, 8 + 5 * i);
    };
    if (W == 0) {
        nb_sync<NB_QK, 160>();
        TSD(W, 2);
        wg_fence();
        qk_steps<0, 8>(s, loRing + r.slot * (SLOT >> 4), loR);
        nb_sync<NB_Q2, 256>();
        qk_steps<8, 12>(s, loRing + r.slot * (SLOT >> 4), loR);
        wg_commit();
        nb_arrive<NB_Q01, 256>();
        TSD(W, 4);
        nb_sync<NB_REF, 160>();
        mref = __uint_as_float(lds_u(sb + OFF_GM));
        wg_wait<0>();
        reg_fence(s);
        mbar_arrive_warp<2>(sb + BAR_REMPTY + r.slot * 8);
        r.adv(2);
        TSD(W, 5);
        tail(TrueT{}, 0);
    } else {
        nb_sync<NB_Q01, 256>();
    }
#pragma unroll 1
    for (int i = (W == 0 ? 1 : 0); i < 4; i++) {
        const uint32_t pvslot = r.slot;
        r.adv(1);
        kslot = r.slot;
        mbar_wait(sb + BAR_RFULL + r.slot * 8, r.ph, r.dl);
        wg_fence();
        qk_steps<0, 4>(s, loRing + r.slot * (SLOT >> 4), loR);
        if (W == 1) wg_commit();
        qk_steps<4, 12>(s, loRing + r.slot * (SLOT >> 4), loR);
        wg_commit();
        wg_wait<1>();
        if (W == 1) mbar_arrive_warp_if(sb + BAR_XEMPTY + 0, i == 3);
        mbar_arrive_warp_if(sb + BAR_REMPTY + pvslot * 8, W == 0 || i > 0);
        r.adv(1);
        vslot = r.slot;
        TSD(W, 4 + 5 * i);
        if (VEARLY) mbar_wait(sb + BAR_RFULL + r.slot * 8, r.ph, r.dl);
        nb_sync<NB_PFULL + (W ^ 1), 256>();
        pv(FalseT{}, W ^ 1, !VEARLY);
        if (LASTORD && W == 1 && i == 3) nb_arrive<NB_PDONE, 256>();
        if (W == 1) mref = __uint_as_float(lds_u(sb + OFF_GM));
        wg_wait<1>();
        reg_fence(s);
        mbar_arrive_warp<2>(sb + BAR_REMPTY + kslot * 8);
        if (W == 0) mbar_arrive_warp_if(sb + BAR_XEMPTY + 0, i == 3);
        if (W == 1) {
            if (XLATE < 2) mbar_arrive_warp_if<2>(sb + BAR_XEMPTY + 8, i == 3);
            if (XLATE < 1) mbar_arrive_warp_if<2>(sb + BAR_XEMPTY + 16, i == 3);
        }
        r.adv(W == 1 && i == 3 ? 1 : 2);
        TSD(W, 5 + 5 * i);
        tail(FalseT{}, i);
    }
    if (W == 1) nx = get_item_warp(sb, it + 1, r.dl);
    if (W == 0) {
        Ring rn = r;
        rn.adv(2);
        q_ahead(q0, sb, rn, phm, IT_TYPE(nx) == IT_QA);
        TSD(W, 25);
    }
    const uint32_t w = (tid_now() >> 5) & 3;
    const uint32_t lxa = sb + OFF_LX + w * 640 + (((lane & 8) ? 80 : 0) + ((lane >> 1) & 8) + 2 * (lane & 3) + ((lane >> 2) & 1)) * 4;
    po.gp = ostash(IT_SLOT(e), IT_B(e)) + po.toff();
    po.sig = 1;
    if (W == 0) {
        sum_store<false>(l, lane, lxa);
        nb_arrive<NB_LX, 256>();
        wg_wait<1>();
        mbar_arrive_warp(sb + BAR_REMPTY + r.slot * 8);
        mbar_arrive_warp(sb + BAR_XEMPTY + 24);
        r.adv(1);
        if (VEARLY) mbar_wait(sb + BAR_RFULL + r.slot * 8, r.ph, r.dl);
        nb_sync<NB_PFULL + 1, 256>();
        pv(FalseT{}, 1, !VEARLY);
    } else {
        nb_sync<NB_LX, 256>();
        sum_store<true>(l, lane, lxa);
        nb_arrive<NB_L, 160>();
    }
    TSD(W, 24);
    wg_wait<0>();
    reg_fence(oa);
    reg_fence(ob);
    mbar_arrive_warp(sb + BAR_REMPTY + r.slot * 8);
    mbar_arrive_warp(sb + BAR_XEMPTY + 32);
    r.adv(1);
    opack(ob, po.v + 40);
    opack(oa, po.v);
    return nx;
}

template <int W>
__device__ __forceinline__ uint32_t qa_run(const Params& P, uint32_t e, uint32_t sb, Ring& r, uint32_t phm, int& it) {
    PendO<W> po;
    po.clear();
    float q0[80], oa[80];
    if (W == 0) {
        zero(oa);
        q_ahead(q0, sb, r, phm, true);
        wg_wait<0>();
    }
#pragma unroll 1
    do {
        TS(W, 0);
        if (W == 0) TS_ITEM(e);
        e = qa_item<W>(e, sb, r, phm, po, q0, oa, it);
        TS(W, 31);
        it++;
    } while (IT_TYPE(e) == IT_QA && !po.bad);
#pragma unroll 1
    for (int m = po.bad ? 2 : 1; m > 0; m--) {
        if (m == 1) {
            po.verdict(sb);
            po.template step<0>(sb);
            po.template step<1>(sb);
            po.template step<2>(sb);
            po.template step<3>(sb);
            po.template step<4>(sb);
        }
        if (po.bad) {
            if (W == 0) fallback_unit(P, lds_u(sb + OFF_ITEM + (it - m) * 4), tid_now() & 127);
            __syncwarp();
            nb_sync<NB_ODONE, 288>();
        }
    }
    return e;
}

__device__ __forceinline__ void consumer(const Params& P, uint32_t W, uint32_t sb, uint32_t dl) {
    int it = 0;
    Ring r{0, 0, dl};
    uint32_t phm = 0;
    uint32_t e = get_item_warp(sb, 0, dl);
#pragma unroll 1
    while (true) {
        if (IT_TYPE(e) == IT_QA) e = W == 0 ? qa_run<0>(P, e, sb, r, phm, it) : qa_run<1>(P, e, sb, r, phm, it);
        if (e == 0) break;
        if (IT_TYPE(e) == IT_QA) continue;
        TS(W, 0);
        if (W == 0) TS_ITEM(e);
        if (IT_TYPE(e) == IT_ON) on_item(W, e, sb, r, phm);
        else if (W == 0) op_item<true>(e, sb, r, phm);
        else op_item<false>(e, sb, r, phm);
        TS(W, 31);
        e = get_item_warp(sb, ++it, dl);
    }
    TS_DUMP(W);
}

__global__ void __cluster_dims__(2, 1, 1) __launch_bounds__(384, 1) fused_kernel(const __grid_constant__ Params P) {
    extern __shared__ __align__(1024) unsigned char smem_raw[];
    const uint32_t sb = (uint32_t)__cvta_generic_to_shared(smem_raw);
    const uint32_t warp = __shfl_sync(0xffffffffu, threadIdx.x >> 5, 0), wgid = warp >> 2;
    const uint32_t cta = blockIdx.x;
    const uint32_t dl = deadline();

    if (threadIdx.x == 128) {
#pragma unroll
        for (int i = 0; i < NSLOT; i++) {
            mbar_init(sb + BAR_RFULL + i * 8, 1);
            mbar_init(sb + BAR_REMPTY + i * 8, 8);
            mbar_init(sb + BAR_XFULL + i * 8, 1);
            mbar_init(sb + BAR_XEMPTY + i * 8, 8);
        }
        asm volatile("fence.mbarrier_init.release.cluster;" ::: "memory");
        fence_async_smem();
    } else if (threadIdx.x == 160) {
#pragma unroll
        for (int i = 0; i < NSLOT + MAXI; i++) mbar_init(sb + BAR_PRDY + i * 8, 1);
        asm volatile("fence.mbarrier_init.release.cluster;" ::: "memory");
    } else if (threadIdx.x == 0) {
        sts_u(sb + OFF_ITEM, P.cl[cta >> 1].items[0] ? P.cl[cta >> 1].items[0] + 8 * (cta & 1) : 0);
        sts_u(sb + OFF_FB, P.cl[cta >> 1].delay);
    } else if (threadIdx.x == 64) {
        if (sb & 1023) __trap();
        asm volatile("prefetch.tensormap [%0];" ::"l"(&P.wq[0]) : "memory");
        asm volatile("prefetch.tensormap [%0];" ::"l"(&P.x[0]) : "memory");
    }
    __syncthreads();
    {
        const int it = 0;
        if (wgid == 1) TS(0, 30);
    }
    asm volatile("barrier.cluster.arrive.relaxed.aligned;" ::: "memory");
    if (warp < 3) {
        const uint32_t e = __shfl_sync(0xffffffffu, lds_u(sb + OFF_ITEM), 0), d = lds_u(sb + OFF_FB);
        const uint64_t pol = mkpol<POL_W>();
        const bool isx = warp == 1, lead = (threadIdx.x & 31) == 0;
        uint32_t t0, t1;
        asm volatile("mov.u32 %0, %%clock;" : "=r"(t0));
        do {
            asm volatile("mov.u32 %0, %%clock;" : "=r"(t1));
        } while (t1 - t0 < d);
        __syncwarp();
#pragma unroll 1
        for (int n = 0; n < (e ? NSLOT : 0); n++) {
            const uint32_t bar = sb + (isx ? BAR_XFULL : BAR_RFULL) + n * 8;
            if (lead) {
                if (warp < 2) mbar_expect(bar, isx ? XS : SLOT);
                tma3(sb + (isx ? OFF_R + n * XS : OFF_RING + n * SLOT + warp * (SLOT / 4)), isx ? &P.x[0] : &P.wq[0],
                     isx ? IT_B(e) * 160 : n * 64 + warp * 16, isx ? n : IT_H0(e) * 3, bar, pol);
            }
        }
        if (threadIdx.x == 0) asm volatile("mbarrier.arrive.shared::cta.b64 _, [%0];" ::"r"(sb + BAR_ITEM) : "memory");
        __syncwarp();
    }

    if (wgid == 0) {
        asm volatile("setmaxnreg.dec.sync.aligned.u32 24;");
        if (warp == 0) {
            const bool lead = threadIdx.x == 0;
            const uint64_t pol_first = mkpol<1>(), pol_norm = mkpol<POL_W>();
            uint32_t e = __shfl_sync(0xffffffffu, lds_u(sb + OFF_ITEM), 0);
            asm volatile("barrier.cluster.wait.aligned;" ::: "memory");
            unsigned int* const ticket = &g_ticket[next_epoch(0) & 1];
            const uint32_t rank = cta & 1;
            uint32_t peer;
            asm volatile("mapa.shared::cluster.u32 %0, %1, %2;" : "=r"(peer) : "r"(sb), "r"(rank ^ 1));
            Ring r{0, 0, dl};
            uint32_t pm = 0;
            auto load_w = [&](const CUtensorMap* m, int row, int blk, uint32_t half_bytes) {
                mbar_wait(sb + BAR_REMPTY + r.slot * 8, r.ph, dl);
                if (lead) {
                    mbar_expect(sb + BAR_RFULL + r.slot * 8, 2 * half_bytes);
                    asm volatile("mbarrier.arrive.shared::cluster.b64 _, [%0];" ::"r"(peer + BAR_PRDY + r.slot * 8) : "memory");
                }
                mbar_wait(sb + BAR_PRDY + r.slot * 8, (pm >> r.slot) & 1, dl);
                pm ^= 1u << r.slot;
                if (lead) tma3_mc(sb + OFF_RING + r.slot * SLOT + rank * half_bytes, m, row, blk, sb + BAR_RFULL + r.slot * 8, pol_norm);
                r.adv(1);
            };
#pragma unroll 1
            for (int it = 0; e != 0; it++) {
                uint32_t nx = 0, tk = 0;
                if (rank == 0 && IT_TYPE(e) != IT_ON && it + 2 < MAXI) nx = it + 1 < NSTAT ? P.cl[cta >> 1].items[it + 1] : IT_DYN;
                const uint32_t br = IT_BR(e);
                if (IT_TYPE(e) == IT_QA) {
                    const uint32_t h = IT_H0(e);
#pragma unroll 1
                    for (int kk = it ? 0 : NSLOT; kk < 10; kk++) load_w(&P.wq[br], kk * 64 + rank * 32, h * 3, SLOT / 2);
                    const int grp0 = (IT_B(e) * 32 + h) * 64;
#pragma unroll 1
                    for (int n = 0; n < 16; n++) {
                        if (n == 13 && nx == IT_DYN && lead) tk = atomicAdd(ticket, 1);
                        const bool isv = n == 15 || (n > 0 && !(n & 1));
                        const int j = n == 15 ? 7 : isv ? (n - 2) >> 1 : (n + 1) >> 1;
                        mbar_wait(sb + BAR_REMPTY + r.slot * 8, r.ph, dl);
                        if (lead) {
                            mbar_expect(sb + BAR_RFULL + r.slot * 8, SLOT);
                            asm volatile(
                                "cp.async.bulk.tensor.4d.shared::cluster.global.mbarrier::complete_tx::bytes.L2::cache_hint"
                                " [%0], [%1, {%3,%3,%3,%4}], [%2], %5;" ::"r"(sb + OFF_RING + r.slot * SLOT),
                                "l"(isv ? &P.v[br] : &P.k[br]), "r"(sb + BAR_RFULL + r.slot * 8), "r"(0), "r"(grp0 + j * 8), "l"(pol_first)
                                : "memory");
                        }
                        r.adv(1);
                    }
                } else {
                    const bool wide = IT_TYPE(e) == IT_OP;
                    const int step = wide ? 32 : 64, r1 = IT_H1(e) * 192;
#pragma unroll 1
                    for (int row = IT_H0(e) * 192 + rank * (step >> 1); row < r1; row += step)
                        load_w(wide ? &P.wo[br] : &P.won[br], row, IT_HALF(e) * (wide ? 5 : 2), wide ? XS / 2 : 8192);
                    if (nx == IT_DYN && lead) tk = atomicAdd(ticket, 1);
                }
                if (rank == 0) {
                    if (nx == IT_DYN) {
                        tk = __shfl_sync(0xffffffffu, tk, 0);
                        nx = tk < P.nlist ? P.list[tk] : 0;
                    }
                    e = nx;
                    if (lead) {
                        asm volatile("st.async.weak.shared::cluster.mbarrier::complete_tx::bytes.b32 [%0], %1, [%2];" ::"r"(
                                         peer + OFF_ITEM + 4 + it * 4),
                                     "r"(e ? e + 8 : 0), "r"(peer + BAR_ITEM + 8 + it * 8)
                                     : "memory");
                        sts_u(sb + OFF_ITEM + 4 + it * 4, e);
                        asm volatile("mbarrier.arrive.shared::cta.b64 _, [%0];" ::"r"(sb + BAR_ITEM + 8 + it * 8) : "memory");
                    }
                } else {
                    if (lead) mbar_expect(sb + BAR_ITEM + 8 + it * 8, 4);
                    e = get_item_warp(sb, it + 1, dl);
                }
            }
        } else if (warp == 1) {
            const uint64_t pol_norm = mkpol<POL_X>(), pol_o = mkpol<POL_O>();
            const bool lead = threadIdx.x == 32;
            uint32_t phm = 0, epoch = 0;
#pragma unroll 1
            for (int it = 0;; it++) {
                const uint32_t e = get_item_warp(sb, it, dl);
                if (it == 1 || (it == 0 && e == 0)) epoch = next_epoch(1);
                if (e == 0) break;
                const uint32_t br = IT_BR(e);
                uint32_t xs = 0;
                auto acquire = [&]() {
                    mbar_wait(sb + BAR_XEMPTY + xs * 8, (phm >> xs) & 1, dl);
                    phm ^= 1u << xs;
                    if (lead) mbar_expect(sb + BAR_XFULL + xs * 8, XS);
                };
                if (IT_TYPE(e) == IT_QA) {
#pragma unroll 1
                    for (int kk = it ? 0 : 5; kk < 10; kk++) {
                        acquire();
                        if (lead) tma3(sb + OFF_R + xs * XS, &P.x[br], IT_B(e) * 160, kk, sb + BAR_XFULL + xs * 8, pol_norm);
                        if (++xs == 5) xs = 0;
                    }
                } else {
                    const unsigned int* fp = g_flag + (br * 16 + IT_B(e)) * 64 + (threadIdx.x & 31);
                    uint32_t hm = 0, pm = 0;
                    auto poll = [&](uint32_t hneed, uint32_t pneed) {
                        if ((hm & hneed) == hneed && (pm & pneed) == pneed) return;
                        uint32_t n = 0;
                        do {
                            uint32_t a, b;
                            asm volatile("ld.acquire.gpu.global.u32 %0, [%2];\nld.acquire.gpu.global.u32 %1, [%2+128];"
                                         : "=r"(a), "=r"(b) : "l"(fp) : "memory");
                            hm = __ballot_sync(0xffffffffu, a == epoch);
                            pm = __ballot_sync(0xffffffffu, b == epoch);
                            if (++n > 0x1000000) __trap();
                        } while ((hm & hneed) != hneed || (pm & pneed) != pneed);
                        __syncwarp();
                        asm volatile("fence.proxy.async;" ::: "memory");
                    };
#pragma unroll 1
                    for (uint32_t h = IT_H0(e); h < IT_H1(e); h++) {
                        poll(1u << h, 0);
                        const unsigned char* src = ostash(P.slot[br * 32 + h], IT_B(e));
#pragma unroll 1
                        for (int t = 0; t < 3; t++) {
                            acquire();
                            if (lead) bulk_load(sb + OFF_R + xs * XS, src + t * XS, XS, sb + BAR_XFULL + xs * 8, pol_o);
                            if (++xs == 5) xs = 0;
                        }
                        if (IT_TYPE(e) == IT_OP && h >= 1) {
                            const uint32_t x1 = xs == 4 ? 0 : xs + 1;
                            mbar_wait(sb + BAR_XFULL + xs * 8, (phm >> xs) & 1, dl);
                            mbar_wait(sb + BAR_XFULL + x1 * 8, (phm >> x1) & 1, dl);
                            if (lead)
                                asm volatile("st.relaxed.gpu.global.u32 [%0], %1;" ::"l"(fp + 34 + IT_HALF(e)), "r"(epoch * 64 + h) : "memory");
                        }
                    }
                    if (IT_TYPE(e) == IT_ON) {
                        poll(0, IT_HALF(e) < 2 ? 1 : IT_HALF(e) == 2 ? 3 : 2);
#pragma unroll 1
                        for (uint32_t tile = 2 * IT_HALF(e); tile < 2 * IT_HALF(e) + 2; tile++) {
                            acquire();
                            if (lead)
                                asm volatile(
                                    "cp.async.bulk.tensor.5d.shared::cluster.global.mbarrier::complete_tx::bytes [%0], [%1, {%3,%5,%5,%5,%4}], [%2];" ::"r"(
                                        sb + OFF_R + xs * XS),
                                    "l"(&P.out), "r"(sb + BAR_XFULL + xs * 8), "r"(br * 640 + tile * 64), "r"(IT_B(e) * 5), "r"(0)
                                    : "memory");
                            if (++xs == 5) xs = 0;
                        }
                    }
                }
            }
        } else if (warp == 2) {
            asm volatile("barrier.cluster.wait.aligned;" ::: "memory");
            const uint32_t epoch = next_epoch(2);
            if (cta == 0) g_ticket[(epoch + 1) & 1] = 0;
#pragma unroll 1
            for (int it = 0;; it++) {
                const uint32_t e = get_item_warp(sb, it, dl);
                if (e == 0) break;
                nb_sync<NB_ODONE, 288>();
                if (threadIdx.x == 64) {
                    const uint32_t bb = IT_BR(e) * 16 + IT_B(e);
                    if (IT_TYPE(e) != IT_QA) {
                        const bool wide = IT_TYPE(e) == IT_OP;
                        if (wide)
                            asm volatile("st.relaxed.gpu.global.u32 [%0], %1;" ::"l"(&g_flag[bb * 64 + 34 + IT_HALF(e)]),
                                         "r"(epoch * 64 + IT_H1(e))
                                         : "memory");
                        const int cc0 = IT_BR(e) * 640 + IT_HALF(e) * (wide ? 320 : 128);
                        uint32_t xs = wide ? 0 : (3 * (IT_H1(e) - IT_H0(e))) % 5;
#pragma unroll 1
                        for (int m = 0; m < (wide ? 5 : 2); m++) {
                            asm volatile("cp.async.bulk.tensor.5d.global.shared::cta.bulk_group [%0, {%2,%4,%4,%4,%3}], [%1];" ::"l"(&P.out),
                                         "r"(sb + OFF_R + xs * XS), "r"(cc0 + m * 64), "r"((int)IT_B(e) * 5), "r"(0)
                                         : "memory");
                            asm volatile("cp.async.bulk.commit_group;" ::: "memory");
                            if (wide && m >= STLAG) {
                                asm volatile("cp.async.bulk.wait_group.read %0;" ::"n"(STLAG) : "memory");
                                asm volatile("mbarrier.arrive.shared::cta.b64 _, [%0], 8;" ::"r"(sb + BAR_XEMPTY + (m - STLAG) * 8) : "memory");
                            }
                            if (++xs == 5) xs = 0;
                        }
                        if (wide && STLAG) {
                            asm volatile("cp.async.bulk.wait_group.read 0;" ::: "memory");
                            asm volatile("mbarrier.arrive.shared::cta.b64 _, [%0], 8;" ::"r"(sb + BAR_XEMPTY + 32) : "memory");
                        }
                        if (IT_PART(e)) {
                            asm volatile("cp.async.bulk.wait_group 0;" ::: "memory");
                            asm volatile("fence.proxy.async;" ::: "memory");
                        }
                    }
                    if (IT_TYPE(e) == IT_QA || IT_PART(e)) {
                        unsigned int* f = &g_flag[bb * 64 + (IT_TYPE(e) == IT_QA ? IT_H0(e) : 32 + IT_HALF(e))];
                        asm volatile("st.release.gpu.global.u32 [%0], %1;" ::"l"(f), "r"(epoch) : "memory");
                    }
                }
                __syncwarp();
            }
            if (threadIdx.x == 64) asm volatile("cp.async.bulk.wait_group 0;" ::: "memory");
            __syncwarp();
            asm volatile("barrier.cluster.arrive.relaxed.aligned;\nbarrier.cluster.wait.aligned;" ::: "memory");
        } else {
            const uint32_t lane = threadIdx.x & 31, p = lane >> 2;
            const uint32_t epoch = next_epoch(3);
#pragma unroll 1
            for (int it = 0;; it++) {
                const uint32_t e = get_item_warp(sb, it, dl);
                if (e == 0) break;
                if (IT_TYPE(e) != IT_QA) continue;
                nb_sync<NB_QK, 160>();
                const uint32_t co = (((lane & 3) * 2) ^ p) << 4;
                const uint32_t ka = sb + OFF_RING + lds_u(sb + OFF_GM + 4) * SLOT + p * (3072 + 128) + co;
                const uint32_t qa = sb + OFF_R + p * 128 + co;
                uint32_t acc = 0;
#pragma unroll 1
                for (int c = 0; c < 3; c++) {
                    if (c == 2) nb_sync<NB_L, 160>();
                    const uint4 k0 = lds_u4(ka + c * 1024), q0 = lds_u4(qa + c * XS);
                    acc = fma_bf2(k0.x, q0.x, fma_bf2(k0.y, q0.y, fma_bf2(k0.z, q0.z, fma_bf2(k0.w, q0.w, acc))));
                    const uint4 k1 = lds_u4((ka + c * 1024) ^ 16), q1 = lds_u4((qa + c * XS) ^ 16);
                    acc = fma_bf2(k1.x, q1.x, fma_bf2(k1.y, q1.y, fma_bf2(k1.z, q1.z, fma_bf2(k1.w, q1.w, acc))));
                }
                float d = __uint_as_float(acc << 16) + __uint_as_float(acc & 0xffff0000u);
                d += __shfl_xor_sync(0xffffffffu, d, 1);
                d += __shfl_xor_sync(0xffffffffu, d, 2);
                int key = __float_as_int(d);
                key ^= (key >> 31) & 0x7fffffff;
                key = __reduce_max_sync(0xffffffffu, key);
                key ^= (key >> 31) & 0x7fffffff;
                sts_f(sb + OFF_GM, fmaf(__int_as_float(key), SM_C, 16.f));
                nb_arrive<NB_REF, 160>();
                if (IT_DEP(e)) {
                    const uint32_t g = IT_DEP(e) - 1, need = epoch * 64 + (g & 31) + 1;
                    const unsigned int* cp = &g_flag[((g >> 5) * 16 + IT_B(e)) * 64 + 34 + (lane & 1)];
                    for (uint32_t n = 0;; n++) {
                        uint32_t v;
                        asm volatile("ld.acquire.gpu.global.u32 %0, [%1];" : "=r"(v) : "l"(cp) : "memory");
                        if (__all_sync(0xffffffffu, v - need < 64)) break;
                        if (n > 0x800000) __trap();
                        __nanosleep(500);
                    }
                }
                nb_sync<NB_L, 160>();
                bool bad = false;
#pragma unroll
                for (int c = 0; c < 5; c++) {
                    const uint32_t la = sb + OFF_LX + (c * 32 + lane) * 4;
                    const float v = (__uint_as_float(lds_u(la)) + __uint_as_float(lds_u(la + 640))) +
                                    (__uint_as_float(lds_u(la + 1280)) + __uint_as_float(lds_u(la + 1920)));
                    const float inv = __fdividef(1.f, v);
                    const uint32_t hi = pack_bf16(inv, 0.f), lo = pack_bf16(inv - __uint_as_float(hi << 16), 0.f);
                    const uint32_t ia = sb + OFF_LINV + c * 128 + ((lane >> 1) & 3) * 32 + (lane >> 3) * 8 + (lane & 1) * 2;
                    asm volatile("st.shared.u16 [%0], %1;\nst.shared.u16 [%0+4], %2;" ::"r"(ia), "h"((unsigned short)hi), "h"((unsigned short)lo) : "memory");
                    bad |= !(v >= 5.421010862e-20f && v <= 7.9228163e28f);
                }
                sts_u(sb + OFF_FB, __any_sync(0xffffffffu, bad));
                nb_arrive<NB_VOTE, 160>();
                nb_arrive<NB_VOTE + 1, 160>();
            }
        }
    } else {
        asm volatile("setmaxnreg.inc.sync.aligned.u32 240;");
        consumer(P, wgid - 1, sb, dl);
    }
}

typedef CUresult (*EncFn)(CUtensorMap*, CUtensorMapDataType, cuuint32_t, void*, const cuuint64_t*, const cuuint64_t*,
                          const cuuint32_t*, const cuuint32_t*, CUtensorMapInterleave, CUtensorMapSwizzle,
                          CUtensorMapL2promotion, CUtensorMapFloatOOBfill);

void make_map3(EncFn enc, CUtensorMap* m, void* p, uint64_t rows, uint64_t rowbytes, uint64_t nblk, uint32_t boxrows,
               uint32_t boxblk) {
    cuuint64_t dims[3] = {64, rows, nblk};
    cuuint64_t str[2] = {rowbytes, 128};
    cuuint32_t box[3] = {64, boxrows, boxblk};
    cuuint32_t es[3] = {1, 1, 1};
    enc(m, CU_TENSOR_MAP_DATA_TYPE_BFLOAT16, 3, p, dims, str, box, es, CU_TENSOR_MAP_INTERLEAVE_NONE,
        CU_TENSOR_MAP_SWIZZLE_128B, CU_TENSOR_MAP_L2_PROMOTION_NONE, CU_TENSOR_MAP_FLOAT_OOB_FILL_NONE);
}

constexpr int tune(const char*, int def) { return def; }

void build_schedule(Params& P) {
    const int mode = tune("MODE", 4), dmax = tune("DMAX", 24900), n0 = tune("N0", 11), odmax = tune("ODMAX", 0), d1 = tune("D1", 0);
    const int H0[8] = {19, 20, 21, 23, 23, 24, 25, 25}, P0[8] = {367, 340, 338, 331, 341, 339, 331, 334};
    const int ra = tune("RA", 10), ga = tune("GA", 17), rb = tune("RB", 11), g1 = tune("G1", 58);
    int dep[64];
    for (int g = 0, ns = 0, live = 0; g < 64; g++) {
        const bool fresh = mode < 3 || g >= g1 || live < (g < ga ? ra : rb);
        dep[g] = fresh ? 0 : g - live + 1;
        P.slot[g] = fresh ? ns++ : P.slot[g - live];
        live += fresh;
    }
    int H[8], pos[8], psum = 0;
    for (int b = 0; b < 8; b++) {
        const char nh[3] = {'H', (char)('0' + b), 0}, np[3] = {'P', (char)('0' + b), 0};
        H[b] = tune(nh, H0[b]);
        pos[b] = tune(np, P0[b]);
        psum += pos[b];
    }
    const int sk = tune("SK", 10), g0 = tune("G0", 20), g2 = tune("G2", 40);
    int ord[512], nxt[8] = {0, 0, 0, 0, 0, 0, 0, 0};
    for (int k = 0; k < 512; k++) {
        int best = -1;
        float bkey = 0.f;
        for (int b = 0; b < 8; b++) {
            const int g = nxt[b];
            if (g == 64) continue;
            const float w = g < g0 ? 0.f : g < 32 ? (g - g0) / (32.f - g0) : g < g2 ? 1.f : (64 - g) / (64.f - g2);
            const float key = g + w * sk * 0.1f * (pos[b] - psum / 8.f) / 8.f;
            if (best < 0 || key < bkey) best = b, bkey = key;
        }
        ord[k] = nxt[best]++ * 8 + best;
        const int d = dep[ord[k] >> 3];
        if (d > 32) {
            if (pos[best] > k) pos[best] = k;
            if (H[best] < d - 32) H[best] = d - 32;
        }
    }
    int u = 0;
    auto unit = [&]() {
        const int v = ord[u++];
        return mk_item(IT_QA, v >> 8, (v & 7) * 2, (v >> 3) & 31, P.slot[v >> 3], 0) | (dep[v >> 3] << 23);
    };
    const int ob = tune("OB", 4), qm = tune("QM", 19);
    int qa[NCL], nq = 0, op[NCL], no = 0;
    for (int c = 0; c < NCL; c++) {
        P.cl[c].delay = 0;
        for (int i = 0; i < NSTAT; i++) P.cl[c].items[i] = 0;
        if (mode >= 3 && ob >= 0 && c >= ob && c < ob + 16) op[((c - ob) & 7) * 2 + ((c - ob) >> 3)] = c, no++;
        else if (mode >= 3 && ob < 0 && c < 64 && (c & 3) == 3) op[no++] = c;
        else if (mode != 2 || (c & 3) == 0) qa[nq++] = c;
    }
    for (int t = 0; t < no; t++) {
        P.cl[op[t]].items[1] = mk_item(IT_OP, 0, t & ~1, 0, 32, t & 1);
        P.cl[op[t]].items[2] = IT_DYN;
        P.cl[op[t]].delay = tune("OD0", 0) + t * odmax / 16;
    }
    for (int k = 0; k < nq; k++) {
        const int c = qa[(k * qm) % nq];
        P.cl[c].items[1] = P.cl[c].items[2] = IT_DYN;
        P.cl[c].delay = k < n0 ? k * tune("J0", 0) : d1 + (dmax - d1) * (k + 1 - n0) / (nq - n0);
    }
    if (tune("OFIRST", 0))
        for (int t = 0; t < no; t++) P.cl[op[t]].items[0] = unit();
    for (int k = u; k < no + nq; k++) {
        int best = -1;
        for (int c = 0; c < NCL; c++)
            if (P.cl[c].items[1] && !P.cl[c].items[0] && (best < 0 || P.cl[c].delay < P.cl[best].delay)) best = c;
        P.cl[best].items[0] = unit();
    }
    int n = 0;
    const int uend = mode == 2 ? 8 * nq : 512;
    while (u < uend) {
        for (int b = 0; b < 8 && no; b++)
            if (pos[b] == u) {
                P.list[n++] = mk_item(IT_OP, 1, 2 * b, 0, H[b], 0, 1);
                P.list[n++] = mk_item(IT_OP, 1, 2 * b, 0, H[b], 1, 1);
            }
        P.list[n++] = unit();
    }
    for (int k = 0; no && k < 40; k++) P.list[n++] = mk_item(IT_ON, 1, k / 5 * 2, H[k / 5], 32, k % 5);
    P.nlist = n;
}

}

extern "C" void kernel_launch(void* const* d_in, const int* in_sizes, int n_in, void* d_out, int out_size) {
    static Params P;
    static bool init = false;
    if (!init) {
        EncFn enc = nullptr;
        cudaDriverEntryPointQueryResult qr;
        cudaGetDriverEntryPoint("cuTensorMapEncodeTiled", (void**)&enc, cudaEnableDefault, &qr);
        for (int i = 0; i < 2; i++) {
            P.px[i] = (const __nv_bfloat16*)d_in[5 * i + 0];
            P.pk[i] = (const __nv_bfloat16*)d_in[5 * i + 1];
            P.pv[i] = (const __nv_bfloat16*)d_in[5 * i + 2];
            P.pwq[i] = (const __nv_bfloat16*)d_in[5 * i + 3];
            make_map3(enc, &P.x[i], d_in[5 * i + 0], 2560, 1280, 10, 160, 1);
            for (int j = 0; j < 2; j++) {
                cuuint64_t dims[4] = {64, 8, 3, 16 * 32 * 64};
                cuuint64_t str[3] = {384, 128, 3072};
                cuuint32_t box[4] = {64, 8, 3, 8};
                cuuint32_t es[4] = {1, 1, 1, 1};
                enc(j ? &P.v[i] : &P.k[i], CU_TENSOR_MAP_DATA_TYPE_BFLOAT16, 4, d_in[5 * i + 1 + j], dims, str, box, es,
                    CU_TENSOR_MAP_INTERLEAVE_NONE, CU_TENSOR_MAP_SWIZZLE_128B, (CUtensorMapL2promotion)tune("PROMO", 0),
                    CU_TENSOR_MAP_FLOAT_OOB_FILL_NONE);
            }
            make_map3(enc, &P.wq[i], d_in[5 * i + 3], 640, 12288, 96, 32, 3);
            make_map3(enc, &P.wo[i], d_in[5 * i + 4], 6144, 1280, 10, 16, 5);
            make_map3(enc, &P.won[i], d_in[5 * i + 4], 6144, 1280, 10, 32, 2);
        }
        cuuint64_t dims[5] = {1280, 2, 4, 4, 80};
        cuuint64_t str[4] = {2560, 8 * 2560, 2 * 2560, 32 * 2560};
        cuuint32_t box[5] = {64, 2, 4, 4, 5};
        cuuint32_t es[5] = {1, 1, 1, 1, 1};
        enc(&P.out, CU_TENSOR_MAP_DATA_TYPE_BFLOAT16, 5, d_out, dims, str, box, es, CU_TENSOR_MAP_INTERLEAVE_NONE,
            CU_TENSOR_MAP_SWIZZLE_128B, CU_TENSOR_MAP_L2_PROMOTION_NONE, CU_TENSOR_MAP_FLOAT_OOB_FILL_NONE);
        build_schedule(P);
        cudaFuncSetAttribute(fused_kernel, cudaFuncAttributeMaxDynamicSharedMemorySize, SMEM_LAUNCH);
        init = true;
    }
    fused_kernel<<<NCTA, 384, SMEM_LAUNCH>>>(P);
}
```

```cpp
#include <cuda_runtime.h>
#include <cuda.h>
#include <cuda_bf16.h>
#include <stdint.h>

namespace {

constexpr int NCTA = 132;
constexpr int NCL = NCTA / 2;
constexpr int MAXI = 16;
constexpr int NSTAT = 3;
constexpr uint32_t IT_DYN = 0xffffffffu;
constexpr int SLOT = 24576;
constexpr int NSLOT = 5;
constexpr int XS = 20480;
constexpr int OFF_R = 0;
constexpr int OFF_RING = 5 * XS;
constexpr int OFF_MISC = OFF_RING + NSLOT * SLOT;
constexpr int OFF_LX = OFF_MISC;
constexpr int OFF_LINV = OFF_LX + 2560;
constexpr int OFF_FB = OFF_LINV + 640;
constexpr int OFF_GM = OFF_FB + 16;
constexpr int OFF_BAR = OFF_GM + 16;
constexpr int BAR_RFULL = OFF_BAR;
constexpr int BAR_REMPTY = BAR_RFULL + 40;
constexpr int BAR_XFULL = BAR_REMPTY + 40;
constexpr int BAR_XEMPTY = BAR_XFULL + 40;
constexpr int BAR_PRDY = BAR_XEMPTY + 40;
constexpr int BAR_ITEM = BAR_PRDY + 40;
constexpr int OFF_ITEM = BAR_ITEM + MAXI * 8;
constexpr int SMEM_BYTES = OFF_ITEM + MAXI * 4;
static_assert(SMEM_BYTES <= 232448, "smem");

constexpr int NB_W = 1  , NB_PFULL = 3  , NB_VOTE = 5  , NB_Q2 = 7, NB_SDONE = 8, NB_PDONE = 9,
              NB_L = 10, NB_REF = 11, NB_ODONE = 12, NB_OPEND = 13, NB_LX = 14, NB_Q01 = 15, NB_QK = 0  ;

constexpr uint32_t IT_QA = 1, IT_OP = 2, IT_ON = 3;
__host__ __device__ constexpr uint32_t mk_item(uint32_t type, uint32_t br, uint32_t b, uint32_t h0, uint32_t h1, uint32_t half,
                                               uint32_t part = 0) {
    return type | (br << 2) | (b << 3) | (h0 << 7) | (h1 << 13) | (half << 19) | (part << 22);
}
#define IT_TYPE(e) ((e) & 3u)
#define IT_BR(e) (((e) >> 2) & 1u)
#define IT_B(e) (((e) >> 3) & 15u)
#define IT_H0(e) (((e) >> 7) & 63u)
#define IT_H1(e) (((e) >> 13) & 63u)
#define IT_HALF(e) (((e) >> 19) & 7u)
#define IT_PART(e) (((e) >> 22) & 1u)
#define IT_SLOT(e) IT_H1(e)
#define IT_DEP(e) (((e) >> 23) & 127u)

struct Params {
    CUtensorMap x[2], wq[2], k[2], v[2], wo[2], won[2], out;
    const __nv_bfloat16 *px[2], *pwq[2], *pk[2], *pv[2];
    struct alignas(16) { uint32_t delay, items[NSTAT]; } cl[NCL];
    uint32_t nlist;
    uint8_t slot[64];
    uint32_t list[512];
};

constexpr int OUNIT = 61440;
__device__ __align__(1024) unsigned char g_ostash[(size_t)1024 * OUNIT];
__device__ unsigned int g_flag[32 * 64];
__device__ __forceinline__ unsigned char* ostash(uint32_t slot, uint32_t b) { return g_ostash + (slot * 16 + b) * OUNIT; }
__device__ unsigned int g_epoch[NCTA * 4];
__device__ unsigned int g_ticket[2];

constexpr int SMEM_LAUNCH = SMEM_BYTES;
#define TS(role, idx)
#define TS_ITEM(e)
#define TS_DUMP(role)
#define TSD(role, idx)

#define POL_W 2
#define POL_X 2
#define POL_O 2
template <int M>
__device__ __forceinline__ uint64_t mkpol() {
    uint64_t p;
    if (M == 0) asm volatile("createpolicy.fractional.L2::evict_normal.b64 %0, 1.0;" : "=l"(p));
    if (M == 1) asm volatile("createpolicy.fractional.L2::evict_first.b64 %0, 1.0;" : "=l"(p));
    if (M == 2) asm volatile("createpolicy.fractional.L2::evict_unchanged.b64 %0, 1.0;" : "=l"(p));
    if (M == 3) asm volatile("createpolicy.fractional.L2::evict_normal.L2::evict_unchanged.b64 %0, 0.25;" : "=l"(p));
    return p;
}
#define STSM_W 1
#define SIGJ 0
#define STLAG 1
#define VEARLY 1
#define LASTORD 0
#define XLATE 2
#define PV0FIRST 1
#define QST0 1
#define QST1 2
#define QHOLD 8
constexpr float SM_C = 0.07216878364870322f * 1.4426950408889634f;

__device__ __forceinline__ uint32_t next_epoch(int warp) {
    unsigned int* p = &g_epoch[blockIdx.x * 4 + warp];
    const uint32_t e = __ldcg(p) + 1;
    *p = e;
    return e;
}

__device__ __forceinline__ uint32_t tid_now() {
    uint32_t t;
    asm volatile("mov.u32 %0, %%tid.x;" : "=r"(t));
    return t;
}
__device__ __forceinline__ void mbar_init(uint32_t a, uint32_t c) {
    asm volatile("mbarrier.init.shared::cta.b64 [%0], %1;" ::"r"(a), "r"(c) : "memory");
}
__device__ __forceinline__ void mbar_expect(uint32_t a, uint32_t b) {
    asm volatile("mbarrier.arrive.expect_tx.shared::cta.b64 _, [%0], %1;" ::"r"(a), "r"(b) : "memory");
}
template <int CNT = 1>
__device__ __forceinline__ void mbar_arrive_warp(uint32_t a) {
    if (CNT == 1)
        asm volatile("{\n.reg .pred p;\nelect.sync _|p, 0xffffffff;\n@p mbarrier.arrive.shared::cta.b64 _, [%0];\n}" ::"r"(a) : "memory");
    else
        asm volatile(
            "{\n.reg .pred p;\nelect.sync _|p, 0xffffffff;\n@p mbarrier.arrive.shared::cta.b64 _, [%0];\n"
            "@p mbarrier.arrive.shared::cta.b64 _, [%0];\n}" ::"r"(a)
            : "memory");
}
template <int CNT = 1>
__device__ __forceinline__ void mbar_arrive_warp_if(uint32_t a, bool cond) {
    if (CNT == 1)
        asm volatile(
            "{\n.reg .pred p, c;\nelect.sync _|p, 0xffffffff;\nsetp.ne.and.u32 c, %1, 0, p;\n"
            "@c mbarrier.arrive.shared::cta.b64 _, [%0];\n}" ::"r"(a), "r"((uint32_t)cond)
            : "memory");
    else
        asm volatile(
            "{\n.reg .pred p, c;\nelect.sync _|p, 0xffffffff;\nsetp.ne.and.u32 c, %1, 0, p;\n"
            "@c mbarrier.arrive.shared::cta.b64 _, [%0];\n@c mbarrier.arrive.shared::cta.b64 _, [%0];\n}" ::"r"(a), "r"((uint32_t)cond)
            : "memory");
}
__device__ __forceinline__ uint32_t deadline() {
    uint32_t c;
    asm volatile("mov.u32 %0, %%clock_hi;" : "=r"(c));
    return c + 4;
}
__device__ __forceinline__ void mbar_wait(uint32_t a, uint32_t ph, uint32_t dl) {
    asm volatile(
        "{\n.reg .pred p;\n.reg .u32 m;\n"
        "LOOP:\n"
        "mbarrier.try_wait.parity.shared::cta.b64 p, [%0], %1;\n"
        "@p bra DONE;\n"
        "mov.u32 m, %%clock_hi;\n"
        "setp.ne.u32 p, m, %2;\n"
        "@p bra LOOP;\n"
        "trap;\n"
        "DONE:\n}" ::"r"(a), "r"(ph), "r"(dl)
        : "memory");
}
__device__ __forceinline__ void mbar_wait2(uint32_t a, uint32_t pa, uint32_t b, uint32_t pb, uint32_t dl) {
    asm volatile(
        "{\n.reg .pred p, q;\n.reg .u32 m;\n"
        "LOOP:\n"
        "mbarrier.try_wait.parity.shared::cta.b64 p, [%0], %1;\n"
        "mbarrier.try_wait.parity.shared::cta.b64 q, [%2], %3;\n"
        "and.pred p, p, q;\n"
        "@p bra DONE;\n"
        "mov.u32 m, %%clock_hi;\n"
        "setp.ne.u32 p, m, %4;\n"
        "@p bra LOOP;\n"
        "trap;\n"
        "DONE:\n}" ::"r"(a), "r"(pa), "r"(b), "r"(pb), "r"(dl)
        : "memory");
}
template <int ID, int CNT>
__device__ __forceinline__ void nb_sync() { asm volatile("bar.sync %0, %1;" ::"n"(ID), "n"(CNT) : "memory"); }
template <int ID, int CNT>
__device__ __forceinline__ void nb_arrive() { asm volatile("bar.arrive %0, %1;" ::"n"(ID), "n"(CNT) : "memory"); }
__device__ __forceinline__ void fence_async_smem() { asm volatile("fence.proxy.async.shared::cta;" ::: "memory"); }

__device__ __forceinline__ void tma3(uint32_t dst, const CUtensorMap* m, int c1, int c2, uint32_t bar, uint64_t pol) {
    asm volatile(
        "cp.async.bulk.tensor.3d.shared::cluster.global.mbarrier::complete_tx::bytes.L2::cache_hint [%0], [%1, {%3,%4,%5}], [%2], %6;" ::"r"(dst),
        "l"(m), "r"(bar), "r"(0), "r"(c1), "r"(c2), "l"(pol)
        : "memory");
}
__device__ __forceinline__ void tma3_mc(uint32_t dst, const CUtensorMap* m, int c1, int c2, uint32_t bar, uint64_t pol) {
    asm volatile(
        "cp.async.bulk.tensor.3d.shared::cluster.global.mbarrier::complete_tx::bytes.multicast::cluster.L2::cache_hint"
        " [%0], [%1, {%3,%4,%5}], [%2], %6, %7;" ::"r"(dst),
        "l"(m), "r"(bar), "r"(0), "r"(c1), "r"(c2), "h"((unsigned short)3), "l"(pol)
        : "memory");
}
__device__ __forceinline__ void bulk_load(uint32_t dst, const void* src, uint32_t bytes, uint32_t bar, uint64_t pol) {
    asm volatile("cp.async.bulk.shared::cluster.global.mbarrier::complete_tx::bytes.L2::cache_hint [%0], [%1], %2, [%3], %4;" ::"r"(dst),
                 "l"(src), "r"(bytes), "r"(bar), "l"(pol)
                 : "memory");
}
__device__ __forceinline__ void wg_fence() { asm volatile("wgmma.fence.sync.aligned;" ::: "memory"); }
__device__ __forceinline__ void wg_commit() { asm volatile("wgmma.commit_group.sync.aligned;" ::: "memory"); }
template <int N>
__device__ __forceinline__ void wg_wait() { asm volatile("wgmma.wait_group.sync.aligned %0;" ::"n"(N) : "memory"); }

#define RW80(c, d) c(d[0]), c(d[1]), c(d[2]), c(d[3]), c(d[4]), c(d[5]), c(d[6]), c(d[7]), c(d[8]), c(d[9]), c(d[10]), c(d[11]), c(d[12]), c(d[13]), c(d[14]), c(d[15]), c(d[16]), c(d[17]), c(d[18]), c(d[19]), c(d[20]), c(d[21]), c(d[22]), c(d[23]), c(d[24]), c(d[25]), c(d[26]), c(d[27]), c(d[28]), c(d[29]), c(d[30]), c(d[31]), c(d[32]), c(d[33]), c(d[34]), c(d[35]), c(d[36]), c(d[37]), c(d[38]), c(d[39]), c(d[40]), c(d[41]), c(d[42]), c(d[43]), c(d[44]), c(d[45]), c(d[46]), c(d[47]), c(d[48]), c(d[49]), c(d[50]), c(d[51]), c(d[52]), c(d[53]), c(d[54]), c(d[55]), c(d[56]), c(d[57]), c(d[58]), c(d[59]), c(d[60]), c(d[61]), c(d[62]), c(d[63]), c(d[64]), c(d[65]), c(d[66]), c(d[67]), c(d[68]), c(d[69]), c(d[70]), c(d[71]), c(d[72]), c(d[73]), c(d[74]), c(d[75]), c(d[76]), c(d[77]), c(d[78]), c(d[79])
#define RW48(c, d) c(d[0]), c(d[1]), c(d[2]), c(d[3]), c(d[4]), c(d[5]), c(d[6]), c(d[7]), c(d[8]), c(d[9]), c(d[10]), c(d[11]), c(d[12]), c(d[13]), c(d[14]), c(d[15]), c(d[16]), c(d[17]), c(d[18]), c(d[19]), c(d[20]), c(d[21]), c(d[22]), c(d[23]), c(d[24]), c(d[25]), c(d[26]), c(d[27]), c(d[28]), c(d[29]), c(d[30]), c(d[31]), c(d[32]), c(d[33]), c(d[34]), c(d[35]), c(d[36]), c(d[37]), c(d[38]), c(d[39]), c(d[40]), c(d[41]), c(d[42]), c(d[43]), c(d[44]), c(d[45]), c(d[46]), c(d[47])
#define RW32(c, d) c(d[0]), c(d[1]), c(d[2]), c(d[3]), c(d[4]), c(d[5]), c(d[6]), c(d[7]), c(d[8]), c(d[9]), c(d[10]), c(d[11]), c(d[12]), c(d[13]), c(d[14]), c(d[15]), c(d[16]), c(d[17]), c(d[18]), c(d[19]), c(d[20]), c(d[21]), c(d[22]), c(d[23]), c(d[24]), c(d[25]), c(d[26]), c(d[27]), c(d[28]), c(d[29]), c(d[30]), c(d[31])

__device__ __forceinline__ void reg_fence(float (&d)[80]) { asm volatile("" : RW80("+f", d)::"memory"); }
__device__ __forceinline__ void reg_fence(float (&d)[48]) { asm volatile("" : RW48("+f", d)::"memory"); }
__device__ __forceinline__ void reg_fence(float (&d)[32]) { asm volatile("" : RW32("+f", d)::"memory"); }

template <int NR>
__device__ __forceinline__ void zero(float (&d)[NR]) {
#pragma unroll
    for (int i = 0; i < NR; i++) d[i] = 0.f;
}

constexpr uint32_t HI_SW128 = (1024u >> 4) | (1u << 30);
constexpr uint32_t HI_KV = (3072u >> 4) | (1u << 30);
constexpr uint32_t HI_OST = (2560u >> 4) | (2u << 30);
constexpr uint32_t LO_LBO1 = (1u << 16);
constexpr uint32_t LO_OST = ((512u >> 4) << 16);

template <int TA, int TB, uint32_t HIB, int ACC, uint32_t HIA = HI_SW128>
__device__ __forceinline__ void wgmma(float (&d)[80], uint32_t loA, uint32_t loB) {
#define WG_ASM(SD)                                                          \
    "{\n.reg .b64 da, db;\nmov.b64 da, {%80, %82};\nmov.b64 db, {%81, %83};\n" \
    "wgmma.mma_async.sync.aligned.m64n160k16.f32.bf16.bf16 "               \
    "{%0,%1,%2,%3,%4,%5,%6,%7,%8,%9,%10,%11,%12,%13,%14,%15,%16,%17,%18,%19,%20,%21,%22,%23,%24,%25,%26,%27,%28,%29,%30,%31,%32,%33,%34,%35,%36,%37,%38,%39,%40,%41,%42,%43,%44,%45,%46,%47,%48,%49,%50,%51,%52,%53,%54,%55,%56,%57,%58,%59,%60,%61,%62,%63,%64,%65,%66,%67,%68,%69,%70,%71,%72,%73,%74,%75,%76,%77,%78,%79}, da, db, " SD ", 1, 1, %84, %85;\n}"
    if constexpr (ACC == 2)
        asm volatile(WG_ASM("0") : RW80("+f", d) : "r"(loA), "r"(loB), "n"(HIA), "n"(HIB), "n"(TA), "n"(TB));
    else if constexpr (ACC == 1)
        asm volatile(WG_ASM("1") : RW80("+f", d) : "r"(loA), "r"(loB), "n"(HIA), "n"(HIB), "n"(TA), "n"(TB));
    else
        asm volatile(WG_ASM("0") : RW80("=f", d) : "r"(loA), "r"(loB), "n"(HIA), "n"(HIB), "n"(TA), "n"(TB));
#undef WG_ASM
}
template <int TA, int TB, uint32_t HIB, int ACC, uint32_t HIA = HI_SW128>
__device__ __forceinline__ void wgmma(float (&d)[48], uint32_t loA, uint32_t loB) {
#define WG_ASM(SD)                                                          \
    "{\n.reg .b64 da, db;\nmov.b64 da, {%48, %50};\nmov.b64 db, {%49, %51};\n" \
    "wgmma.mma_async.sync.aligned.m64n96k16.f32.bf16.bf16 "               \
    "{%0,%1,%2,%3,%4,%5,%6,%7,%8,%9,%10,%11,%12,%13,%14,%15,%16,%17,%18,%19,%20,%21,%22,%23,%24,%25,%26,%27,%28,%29,%30,%31,%32,%33,%34,%35,%36,%37,%38,%39,%40,%41,%42,%43,%44,%45,%46,%47}, da, db, " SD ", 1, 1, %52, %53;\n}"
    if constexpr (ACC == 1)
        asm volatile(WG_ASM("1") : RW48("+f", d) : "r"(loA), "r"(loB), "n"(HIA), "n"(HIB), "n"(TA), "n"(TB));
    else
        asm volatile(WG_ASM("0") : RW48("=f", d) : "r"(loA), "r"(loB), "n"(HIA), "n"(HIB), "n"(TA), "n"(TB));
#undef WG_ASM
}
template <int TA, int TB, uint32_t HIB, int ACC, uint32_t HIA = HI_SW128>
__device__ __forceinline__ void wgmma(float (&d)[32], uint32_t loA, uint32_t loB) {
#define WG_ASM(SD)                                                          \
    "{\n.reg .b64 da, db;\nmov.b64 da, {%32, %34};\nmov.b64 db, {%33, %35};\n" \
    "wgmma.mma_async.sync.aligned.m64n64k16.f32.bf16.bf16 "               \
    "{%0,%1,%2,%3,%4,%5,%6,%7,%8,%9,%10,%11,%12,%13,%14,%15,%16,%17,%18,%19,%20,%21,%22,%23,%24,%25,%26,%27,%28,%29,%30,%31}, da, db, " SD ", 1, 1, %36, %37;\n}"
    if constexpr (ACC == 1)
        asm volatile(WG_ASM("1") : RW32("+f", d) : "r"(loA), "r"(loB), "n"(HIA), "n"(HIB), "n"(TA), "n"(TB));
    else
        asm volatile(WG_ASM("0") : RW32("=f", d) : "r"(loA), "r"(loB), "n"(HIA), "n"(HIB), "n"(TA), "n"(TB));
#undef WG_ASM
}

__device__ __forceinline__ uint32_t pack_bf16(float lo, float hi) {
    uint32_t r;
    asm("cvt.rn.bf16x2.f32 %0, %1, %2;" : "=r"(r) : "f"(hi), "f"(lo));
    return r;
}
__device__ __forceinline__ float ex2(float x) {
    float r;
    asm("ex2.approx.ftz.f32 %0, %1;" : "=f"(r) : "f"(x));
    return r;
}
__device__ __forceinline__ void stsm4t(uint32_t a, uint32_t r0, uint32_t r1, uint32_t r2, uint32_t r3) {
    asm volatile("stmatrix.sync.aligned.m8n8.x4.trans.shared.b16 [%0], {%1,%2,%3,%4};" ::"r"(a), "r"(r0), "r"(r1), "r"(r2), "r"(r3)
                 : "memory");
}
__device__ __forceinline__ uint32_t lds_u(uint32_t a) {
    uint32_t v;
    asm volatile("ld.shared.u32 %0, [%1];" : "=r"(v) : "r"(a) : "memory");
    return v;
}
__device__ __forceinline__ uint4 lds_u4(uint32_t a) {
    uint4 v;
    asm volatile("ld.shared.v4.u32 {%0,%1,%2,%3}, [%4];" : "=r"(v.x), "=r"(v.y), "=r"(v.z), "=r"(v.w) : "r"(a) : "memory");
    return v;
}
__device__ __forceinline__ float2 lds_f2(uint32_t a) {
    float2 v;
    asm volatile("ld.shared.v2.f32 {%0,%1}, [%2];" : "=f"(v.x), "=f"(v.y) : "r"(a) : "memory");
    return v;
}
__device__ __forceinline__ void sts_f(uint32_t a, float v) { asm volatile("st.shared.f32 [%0], %1;" ::"r"(a), "f"(v) : "memory"); }
__device__ __forceinline__ void sts_u(uint32_t a, uint32_t v) { asm volatile("st.shared.u32 [%0], %1;" ::"r"(a), "r"(v) : "memory"); }
__device__ __forceinline__ void sts_f2(uint32_t a, float x, float y) {
    asm volatile("st.shared.v2.f32 [%0], {%1,%2};" ::"r"(a), "f"(x), "f"(y) : "memory");
}

template <bool ADD = false, bool SIG = false, int NR>
__device__ __forceinline__ void store_tile_t(const float (&d)[NR], uint32_t addr) {
    uint32_t p[NR / 2];
    if (ADD) {
#pragma unroll
        for (int j = 0; j < NR / 8; j++)
            asm volatile("ldmatrix.sync.aligned.m8n8.x4.trans.shared.b16 {%0,%1,%2,%3}, [%4];"
                         : "=r"(p[4 * j]), "=r"(p[4 * j + 1]), "=r"(p[4 * j + 2]), "=r"(p[4 * j + 3])
                         : "r"(addr + j * 2048)
                         : "memory");
    }
#pragma unroll
    for (int k = 0; k < NR / 2; k++)
        p[k] = ADD ? pack_bf16(d[2 * k] + __uint_as_float(p[k] << 16), d[2 * k + 1] + __uint_as_float(p[k] & 0xffff0000u))
                   : pack_bf16(d[2 * k], d[2 * k + 1]);
#pragma unroll
    for (int j = 0; j < NR / 8; j++) {
        stsm4t(addr + j * 2048, p[4 * j], p[4 * j + 1], p[4 * j + 2], p[4 * j + 3]);
        if (SIG && j == SIGJ) nb_arrive<NB_L, 160>();
    }
}

struct TrueT { static constexpr bool value = true; };
struct FalseT { static constexpr bool value = false; };

template <int V>
struct IntT { static constexpr int value = V; };

__device__ __forceinline__ uint32_t get_item(uint32_t sb, int it, uint32_t dl) {
    mbar_wait(sb + BAR_ITEM + it * 8, 0, dl);
    return lds_u(sb + OFF_ITEM + it * 4);
}
__device__ __forceinline__ uint32_t get_item_warp(uint32_t sb, int it, uint32_t dl) {
    return __shfl_sync(0xffffffffu, get_item(sb, it, dl), 0);
}

struct Ring {
    uint32_t slot, ph, dl;
    __device__ __forceinline__ void adv(uint32_t k) {
        slot += k;
        if (slot >= NSLOT) { slot -= NSLOT; ph ^= 1; }
    }
};

template <int K>
__device__ __forceinline__ void qk_step(float (&s)[80], uint32_t loK, uint32_t loQ) {
    wgmma<0, 0, HI_SW128, K != 0, HI_KV>(s, loK + (K >> 2) * 64 + (K & 3) * 2, loQ + (K >> 2) * (XS >> 4) + (K & 3) * 2);
}
template <int K0, int K1>
__device__ __forceinline__ void qk_steps(float (&s)[80], uint32_t loK, uint32_t loQ) {
    if constexpr (K0 < K1) {
        qk_step<K0>(s, loK, loQ);
        qk_steps<K0 + 1, K1>(s, loK, loQ);
    }
}
__device__ __forceinline__ uint32_t add_bf2(uint32_t a, uint32_t b) {
    uint32_t r;
    asm("add.rn.bf16x2 %0, %1, %2;" : "=r"(r) : "r"(a), "r"(b));
    return r;
}
__device__ __forceinline__ uint32_t fma_bf2(uint32_t a, uint32_t b, uint32_t c) {
    uint32_t r;
    asm("fma.rn.bf16x2 %0, %1, %2, %3;" : "=r"(r) : "r"(a), "r"(b), "r"(c));
    return r;
}
template <int J>
__device__ __forceinline__ void exp_block(const float (&s)[80], uint32_t (&k)[40], uint32_t pa, float mref) {
    if constexpr (J < 10) {
#pragma unroll
        for (int i = 4 * J; i < 4 * J + 4; i++)
            k[i] = pack_bf16(ex2(fmaf(s[2 * i], SM_C, -mref)), ex2(fmaf(s[2 * i + 1], SM_C, -mref)));
#pragma unroll
        for (int i = 0; i < 4; i++)
            asm volatile("stmatrix.sync.aligned.m8n8.x1.trans.shared.b16 [%0], {%1};" ::"r"(((i & 1) ? pa ^ 16 : pa) + J * 2048 + (i >> 1) * 1024),
                         "r"(k[4 * J + i])
                         : "memory");
        exp_block<J + 1>(s, k, pa, mref);
    }
}
__device__ __forceinline__ void sum_block(const uint32_t (&k)[40], float (&l)[10], uint32_t lane) {
    const bool b4 = lane & 16, b3 = lane & 8;
    uint32_t ps[20], t[10];
#pragma unroll
    for (int j = 0; j < 20; j++) ps[j] = add_bf2(k[2 * j], k[2 * j + 1]);
#pragma unroll
    for (int j = 0; j < 10; j++)
        t[j] = add_bf2(b4 ? ps[2 * j + 1] : ps[2 * j], __shfl_xor_sync(0xffffffffu, b4 ? ps[2 * j] : ps[2 * j + 1], 16));
#pragma unroll
    for (int i = 0; i < 5; i++) {
        const uint32_t a = b3 ? t[i + 5] : t[i], b = __shfl_xor_sync(0xffffffffu, b3 ? t[i] : t[i + 5], 8);
        l[2 * i] += __uint_as_float(a << 16) + __uint_as_float(b << 16);
        l[2 * i + 1] += __uint_as_float(a & 0xffff0000u) + __uint_as_float(b & 0xffff0000u);
    }
}
template <bool ADD>
__device__ __forceinline__ void sum_store(const float (&l)[10], uint32_t lane, uint32_t lxa) {
    const bool b2 = lane & 4;
    float t[5];
#pragma unroll
    for (int i = 0; i < 5; i++) t[i] = ADD ? __uint_as_float(lds_u(lxa + i * 64)) : 0.f;
#pragma unroll
    for (int i = 0; i < 5; i++)
        sts_f(lxa + i * 64, t[i] + (b2 ? l[2 * i + 1] : l[2 * i]) + __shfl_xor_sync(0xffffffffu, b2 ? l[2 * i] : l[2 * i + 1], 4));
}

__device__ __forceinline__ void fallback_unit(const Params& P, uint32_t e, uint32_t tid) {
    const uint32_t lane = tid & 31, br = IT_BR(e), b = IT_B(e), h = IT_H0(e);
    const __nv_bfloat162* wq = (const __nv_bfloat162*)(P.pwq[br] + h * 192) + lane;
    const __nv_bfloat162* kp = (const __nv_bfloat162*)(P.pk[br] + (size_t)(b * 32 + h) * 512 * 192) + lane;
    const __nv_bfloat162* vp = (const __nv_bfloat162*)(P.pv[br] + (size_t)(b * 32 + h) * 512 * 192) + lane;
#pragma unroll 1
    for (uint32_t qi = 0; qi < 40; qi++) {
        const uint32_t q = 4 * qi + (tid >> 5);
        const __nv_bfloat16* xr = P.px[br] + (size_t)(b * 160 + q) * 640;
        float a[6] = {0.f, 0.f, 0.f, 0.f, 0.f, 0.f};
#pragma unroll 2
        for (int k = 0; k < 640; k++) {
            const float xv = __bfloat162float(xr[k]);
#pragma unroll
            for (int i = 0; i < 3; i++) {
                const float2 wv = __bfloat1622float2(wq[(size_t)k * 3072 + i * 32]);
                a[2 * i] = fmaf(xv, wv.x, a[2 * i]);
                a[2 * i + 1] = fmaf(xv, wv.y, a[2 * i + 1]);
            }
        }
#pragma unroll
        for (int i = 0; i < 6; i++) a[i] = __bfloat162float(__float2bfloat16(a[i]));
        auto score = [&](int key) {
            float d = 0.f;
#pragma unroll
            for (int i = 0; i < 3; i++) {
                const float2 kv = __bfloat1622float2(kp[key * 96 + i * 32]);
                d = fmaf(a[2 * i], kv.x, fmaf(a[2 * i + 1], kv.y, d));
            }
#pragma unroll
            for (int o = 16; o > 0; o >>= 1) d += __shfl_xor_sync(0xffffffffu, d, o);
            return d;
        };
        float m = -INFINITY, o[6] = {0.f, 0.f, 0.f, 0.f, 0.f, 0.f}, sum = 0.f;
#pragma unroll 1
        for (int n = 0; n < 1024; n++) {
            const int key = n & 511;
            const float d = score(key);
            if (n < 512) {
                m = fmaxf(m, d);
            } else {
                const float p = ex2((d - m) * SM_C);
                sum += p;
#pragma unroll
                for (int i = 0; i < 3; i++) {
                    const float2 vv = __bfloat1622float2(vp[key * 96 + i * 32]);
                    o[2 * i] = fmaf(p, vv.x, o[2 * i]);
                    o[2 * i + 1] = fmaf(p, vv.y, o[2 * i + 1]);
                }
            }
        }
        const float inv = __fdividef(1.f, sum);
        __nv_bfloat16* op = (__nv_bfloat16*)ostash(IT_SLOT(e), b) + (q >> 5) * 256 + 2 * ((q & 31) >> 3) + (q & 1);
#pragma unroll
        for (int i = 0; i < 6; i++) {
            const uint32_t d = (i >> 1) * 64 + 2 * lane + (i & 1);
            op[(d >> 3) * 1280 + (d & 7) * 32 + ((((q & 7) >> 1) ^ ((d & 7) >> 1)) << 3)] = __float2bfloat16(o[i] * inv);
        }
    }
}

struct PendO {
    uint32_t v[64];
    unsigned char* gp;
    static __device__ __forceinline__ uint32_t toff() {
        const uint32_t t = tid_now();
        return ((t >> 5) & 3) * 5120 + ((t >> 2) & 7) * 64 + (((t ^ (t >> 3)) & 3) << 4);
    }
    uint32_t pend, sig, bad;
    static __device__ __forceinline__ void scale(uint32_t& x, uint32_t hi, uint32_t lo) {
        asm("{\n.reg .b32 t;\nmul.rn.bf16x2 t, %0, %2;\nfma.rn.bf16x2 %0, %0, %1, t;\n}" : "+r"(x) : "r"(hi), "r"(lo));
    }
    template <int I, int OFF>
    __device__ __forceinline__ void put() {
        asm volatile("{\n.reg .pred p;\nsetp.ne.u32 p, %6, 0;\n@p st.global.v4.b32 [%0+%5], {%1,%2,%3,%4};\n}" ::"l"(gp), "r"(v[I]),
                     "r"(v[I + 1]), "r"(v[I + 2]), "r"(v[I + 3]), "n"(OFF), "r"(pend)
                     : "memory");
    }
    __device__ __forceinline__ void verdict(uint32_t sb, uint32_t W) {
        if (sig) {
            asm volatile("bar.sync %0, 160;" ::"r"(NB_VOTE + W) : "memory");
            bad = __any_sync(0xffffffffu, lds_u(sb + OFF_FB) != 0);
            pend = !bad;
        }
    }
    template <int W, int G, int H>
    __device__ __forceinline__ void half(uint32_t sb) {
        constexpr bool T2 = W == 0 ? G >= 3 : G < 3;
        constexpr int B = T2 ? 40 + 8 * (W == 0 ? G - 3 : G) : 0;
        const uint4 a = lds_u4(sb + OFF_LINV + G * 128 + H * 16 + (threadIdx.x & 3) * 32);
#pragma unroll
        for (int i = 2 * H; i < 8; i += 4) {
            scale(v[8 * G + i], a.x, a.y);
            scale(v[8 * G + i + 1], a.z, a.w);
            if (T2) {
                scale(v[B + i], a.x, a.y);
                scale(v[B + i + 1], a.z, a.w);
            }
        }
        if (H == 1) {
            put<8 * G, W * XS + G * 512>();
            put<8 * G + 4, W * XS + G * 512 + 2560>();
            if (T2) {
                put<B, 2 * XS + G * 512>();
                put<B + 4, 2 * XS + G * 512 + 2560>();
            }
            if (G == 4 && pend) nb_arrive<NB_ODONE, 288>();
        }
    }
    template <int W, int G>
    __device__ __forceinline__ void step(uint32_t sb) {
        half<W, G, 0>(sb);
        half<W, G, 1>(sb);
    }
    template <int W>
    __device__ __forceinline__ void flush(uint32_t sb) {
        step<W, 0>(sb);
        step<W, 1>(sb);
        step<W, 2>(sb);
        step<W, 3>(sb);
        step<W, 4>(sb);
    }
    __device__ __forceinline__ void clear() {
#pragma unroll
        for (int i = 0; i < 64; i++) v[i] = 0;
        gp = nullptr;
        pend = 0;
        sig = 0;
        bad = 0;
    }
};

__device__ __forceinline__ uint32_t stsm_off() {
    const uint32_t tid = tid_now(), lane = tid & 31;
    return (lane >> 4) * 1024 + (lane & 7) * 128 + (((((tid >> 4) & 6) + ((lane >> 3) & 1)) ^ (lane & 7)) << 4);
}
__device__ __forceinline__ void q_ahead(float (&q0)[80], uint32_t sb, const Ring& rn, uint32_t phm, bool valid) {
    if (valid) mbar_wait2(sb + BAR_RFULL + rn.slot * 8, rn.ph, sb + BAR_XFULL, phm & 1, rn.dl);
    const uint32_t a = ((((sb + OFF_RING) & 0x3ffff) >> 4) | LO_LBO1) + rn.slot * (SLOT >> 4);
    const uint32_t b = (((sb + OFF_R) & 0x3ffff) >> 4) | LO_LBO1;
    wg_fence();
    wgmma<1, 0, HI_SW128, false>(q0, a, b);
#pragma unroll
    for (int k = 1; k < 4; k++) wgmma<1, 0, HI_SW128, true>(q0, a + (k >> 1) * 768 + (k & 1) * 128, b + k * 2);
    wg_commit();
}
template <int W, int KK>
__device__ __forceinline__ void qproj(float (&q0)[80], float (&q1)[80], uint32_t sb, Ring& r, uint32_t pslot, uint32_t phm,
                                      PendO& po) {
    const uint32_t loR = (((sb + OFF_R) & 0x3ffff) >> 4) | LO_LBO1;
    const uint32_t loRing = (((sb + OFF_RING) & 0x3ffff) >> 4) | LO_LBO1;
    auto ready = [&](int k) {
        mbar_wait2(sb + BAR_RFULL + r.slot * 8, r.ph, sb + BAR_XFULL + (k % 5) * 8, ((phm >> (k % 5)) ^ (k / 5)) & 1, r.dl);
    };
    auto release = [&]() {
        if (KK > 0) {
            wg_wait<1>();
            mbar_arrive_warp(sb + BAR_REMPTY + pslot * 8);
            if (KK <= 5) mbar_arrive_warp(sb + (BAR_XEMPTY + (KK - 1) * 8));
        }
    };
    if (KK == 0 && W == 1) ready(0);
    if (W == 1 && KK == QHOLD) {
        if (QHOLD == 7) {
            wg_wait<0>();
            nb_arrive<NB_PDONE, 256>();
        }
        nb_sync<NB_SDONE, 256>();
    }
    const uint32_t a = loRing + r.slot * (SLOT >> 4) + (W == 0 ? 0 : 512), b = loR + (KK % 5) * (XS >> 4);
    wg_fence();
    constexpr bool T0 = W == 1 || KK > 0;
    if (T0) wgmma<1, 0, HI_SW128, KK != 0>(q0, a, b);
    if (W == 0) wgmma<1, 0, HI_SW128, KK != 0 ? 1 : 2>(q1, a + 256, b);
#pragma unroll
    for (int k = 1; k < 4; k++) {
        if (T0) wgmma<1, 0, HI_SW128, true>(q0, a + (k >> 1) * 768 + (k & 1) * 128, b + k * 2);
        if (W == 0) wgmma<1, 0, HI_SW128, true>(q1, a + 256 + (k >> 1) * 768 + (k & 1) * 128, b + k * 2);
    }
    wg_commit();
    const uint32_t cslot = r.slot;
    r.adv(1);
    if (W == 0 || KK < QHOLD) release();
    if (KK == QST0) {
        po.verdict(sb, W);
        po.template half<W, 0, 0>(sb);
    }
    if (KK < 9) ready(KK + 1);
    if (W == 1 && KK >= QHOLD) release();
    if (W == 1 && KK == 7 && QHOLD > 7) nb_arrive<NB_PDONE, 256>();
    if (KK == QST0) po.template half<W, 0, 1>(sb);
    if constexpr (KK > QST0 && KK < QST0 + 5) po.template step<W, KK - QST0>(sb);
    if constexpr (KK < (W == 0 ? 7 : 9)) {
        qproj<W, KK + 1>(q0, q1, sb, r, cslot, phm, po);
    } else if constexpr (W == 1) {
        const uint32_t sta = sb + OFF_R + 2 * XS + stsm_off();
        wg_wait<0>();
        reg_fence(q0);
        store_tile_t<false, true>(q0, sta);
        mbar_arrive_warp(sb + BAR_REMPTY + cslot * 8);
    } else {
        const uint32_t s8 = r.slot, a8 = loRing + s8 * (SLOT >> 4);
        wg_fence();
#pragma unroll
        for (int k = 0; k < 4; k++) wgmma<1, 0, HI_SW128, true>(q0, a8 + (k >> 1) * 768 + (k & 1) * 128, loR + 3 * (XS >> 4) + k * 2);
        r.adv(1);
        ready(9);
        const uint32_t s9 = r.slot, a9 = loRing + s9 * (SLOT >> 4);
        r.adv(1);
        wg_fence();
#pragma unroll
        for (int k = 0; k < 4; k++) wgmma<1, 0, HI_SW128, true>(q0, a9 + (k >> 1) * 768 + (k & 1) * 128, loR + 4 * (XS >> 4) + k * 2);
        wg_commit();
        wg_wait<1>();
        mbar_arrive_warp(sb + BAR_REMPTY + cslot * 8);
        wg_fence();
#pragma unroll
        for (int k = 0; k < 8; k++)
            wgmma<1, 0, HI_SW128, true>(q1, (k < 4 ? a8 : a9) + 256 + ((k >> 1) & 1) * 768 + (k & 1) * 128,
                                        loR + (3 + (k >> 2)) * (XS >> 4) + (k & 3) * 2);
        wg_commit();
        nb_arrive<NB_SDONE, 256>();
        nb_sync<NB_PDONE, 256>();
        wg_wait<1>();
        reg_fence(q0);
        const uint32_t sta = sb + OFF_R + stsm_off();
        store_tile_t(q0, sta);
        sts_u(sb + OFF_GM + 4, r.slot);
        mbar_wait(sb + BAR_RFULL + r.slot * 8, r.ph, r.dl);
        wg_wait<0>();
        reg_fence(q1);
        mbar_arrive_warp(sb + BAR_REMPTY + s8 * 8);
        mbar_arrive_warp(sb + BAR_REMPTY + s9 * 8);
        store_tile_t(q1, sta + XS);
    }
}

template <int NR>
__device__ __forceinline__ void opack(const float (&o)[NR], uint32_t* v) {
#pragma unroll
    for (int g = 0; g < NR / 16; g++)
#pragma unroll
        for (int hh = 0; hh < 2; hh++)
#pragma unroll
            for (int t = 0; t < 4; t++) v[8 * g + 4 * hh + t] = pack_bf16(o[16 * g + 4 * t + 2 * hh], o[16 * g + 4 * t + 2 * hh + 1]);
}

template <bool IS_S>
__device__ __forceinline__ void op_item(uint32_t e, uint32_t sb, Ring& r, uint32_t& phm) {
    constexpr int T0 = IS_S ? 0 : 2;
    constexpr uint32_t BOFF = IS_S ? (3 * 512) >> 4 : 0;
    const uint32_t loRing = (((sb + OFF_RING) & 0x3ffff) >> 4) | LO_LBO1;
    const uint32_t loO = (((sb + OFF_R) & 0x3ffff) >> 4) | LO_OST;
    float c0[80], c1[80], c2[IS_S ? 32 : 48];
    const int T = 3 * (IT_H1(e) - IT_H0(e));
    uint32_t xs = 0;
    auto step = [&](auto first, auto half) {
        constexpr bool F = decltype(first)::value;
        constexpr uint32_t hf = decltype(half)::value;
        if (hf == 0) {
            mbar_wait(sb + BAR_XFULL + xs * 8, (phm >> xs) & 1, r.dl);
            phm ^= 1u << xs;
        }
        mbar_wait(sb + BAR_RFULL + r.slot * 8, r.ph, r.dl);
        const uint32_t a = loRing + r.slot * (SLOT >> 4), b = loO + xs * (XS >> 4) + hf * 640;
        wg_fence();
        wgmma<1, 1, HI_OST, !F>(c0, a + T0 * 128, b);
        wgmma<1, 1, HI_OST, !F>(c1, a + T0 * 128 + 128, b);
        wgmma<1, 1, HI_OST, !F>(c2, a + 512, b + BOFF);
        wgmma<1, 1, HI_OST, true>(c0, a + 640 + T0 * 128, b + 320);
        wgmma<1, 1, HI_OST, true>(c1, a + 640 + T0 * 128 + 128, b + 320);
        wgmma<1, 1, HI_OST, true>(c2, a + 640 + 512, b + 320 + BOFF);
        wg_commit();
    };
    step(TrueT{}, IntT<0>{});
#pragma unroll 1
    for (int t = 1;; t++) {
        uint32_t pslot = r.slot;
        r.adv(1);
        step(FalseT{}, IntT<1>{});
        wg_wait<1>();
        mbar_arrive_warp(sb + BAR_REMPTY + pslot * 8);
        if (t == T) break;
        pslot = r.slot;
        const uint32_t pxs = xs;
        r.adv(1);
        if (++xs == 5) xs = 0;
        step(FalseT{}, IntT<0>{});
        wg_wait<1>();
        mbar_arrive_warp(sb + BAR_REMPTY + pslot * 8);
        mbar_arrive_warp_if(sb + BAR_XEMPTY + pxs * 8, t + 4 < T);
    }
    wg_wait<0>();
    reg_fence(c0);
    reg_fence(c1);
    reg_fence(c2);
    mbar_arrive_warp(sb + BAR_REMPTY + r.slot * 8);
    r.adv(1);
    nb_sync<NB_OPEND, 256>();
    const uint32_t sta = sb + OFF_R + stsm_off();
    store_tile_t(c0, sta + T0 * XS);
    store_tile_t(c1, sta + (T0 + 1) * XS);
    store_tile_t(c2, sta + 4 * XS + (IS_S ? 96 * 128 : 0));
    fence_async_smem();
    nb_arrive<NB_ODONE, 288>();
}

__device__ __forceinline__ void on_item(uint32_t W, uint32_t e, uint32_t sb, Ring& r, uint32_t& phm) {
    const uint32_t loRing = (((sb + OFF_RING) & 0x3ffff) >> 4) | LO_LBO1;
    const uint32_t loO = (((sb + OFF_R) & 0x3ffff) >> 4) | LO_OST;
    float c[80];
    const int T = 3 * (IT_H1(e) - IT_H0(e));
    uint32_t xs = 0;
    auto step = [&](auto first) {
        constexpr bool F = decltype(first)::value;
        mbar_wait2(sb + BAR_XFULL + xs * 8, (phm >> xs) & 1, sb + BAR_RFULL + r.slot * 8, r.ph, r.dl);
        phm ^= 1u << xs;
        const uint32_t a = loRing + r.slot * (SLOT >> 4) + W * 256, b = loO + xs * (XS >> 4);
        wg_fence();
        wgmma<1, 1, HI_OST, !F>(c, a, b);
#pragma unroll
        for (int k = 1; k < 4; k++) wgmma<1, 1, HI_OST, true>(c, a + (k >> 1) * 512 + (k & 1) * 128, b + k * 320);
        wg_commit();
    };
    step(TrueT{});
#pragma unroll 1
    for (int t = 1; t < T; t++) {
        const uint32_t pslot = r.slot, pxs = xs;
        r.adv(1);
        if (++xs == 5) xs = 0;
        step(FalseT{});
        wg_wait<1>();
        mbar_arrive_warp(sb + BAR_REMPTY + pslot * 8);
        mbar_arrive_warp_if(sb + BAR_XEMPTY + pxs * 8, t + 2 < T);
    }
    xs += 1 + W;
    if (xs >= 5) xs -= 5;
    mbar_wait(sb + BAR_XFULL + xs * 8, (phm >> xs) & 1, r.dl);
    wg_wait<0>();
    reg_fence(c);
    store_tile_t<true>(c, sb + OFF_R + xs * XS + stsm_off());
    fence_async_smem();
    nb_arrive<NB_ODONE, 288>();
}

template <int W>
__device__ __forceinline__ uint32_t qa_item(uint32_t e, uint32_t sb, Ring& r, uint32_t phm, PendO& po, float (&q0)[80],
                                            float (&oa)[80], int it) {
    const uint32_t loR = (((sb + OFF_R) & 0x3ffff) >> 4) | LO_LBO1;
    const uint32_t loRing = (((sb + OFF_RING) & 0x3ffff) >> 4) | LO_LBO1;
    qproj<W, 0>(q0, oa, sb, r, 0, phm, po);
    fence_async_smem();
    TSD(W, 1);
    float s[80], ob[W == 0 ? 32 : 48], l[10];
    if (W == 1) {
        nb_arrive<NB_Q2, 256>();
        zero(oa);
        zero(ob);
        reg_fence(oa);
        reg_fence(ob);
    }
    const uint32_t lane = tid_now() & 31, sta = sb + OFF_R + stsm_off();
    auto pv = [&](auto first, uint32_t buf, bool wait = true) {
        constexpr bool F = decltype(first)::value;
        if (wait) mbar_wait(sb + BAR_RFULL + r.slot * 8, r.ph, r.dl);
        const uint32_t a = loRing + r.slot * (SLOT >> 4), b = loR + (3 + buf) * (XS >> 4);
        wg_fence();
        wgmma<1, 0, HI_SW128, F ? 2 : 1, HI_KV>(oa, a + W * 64, b);
        wgmma<1, 0, HI_SW128, !F, HI_KV>(ob, a + 128, b + (W == 0 ? (96 * 128) >> 4 : 0));
#pragma unroll
        for (int k = 1; k < 4; k++) {
            wgmma<1, 0, HI_SW128, true, HI_KV>(oa, a + W * 64 + k * 384, b + k * 2);
            wgmma<1, 0, HI_SW128, true, HI_KV>(ob, a + 128 + k * 384, b + (W == 0 ? (96 * 128) >> 4 : 0) + k * 2);
        }
        wg_commit();
    };
    zero(l);
    float mref;
    uint32_t kslot, vslot, nx = 0;
    auto tail = [&](auto first, int i) {
        constexpr bool rel_other = !decltype(first)::value;
        uint32_t ps[40];
        exp_block<0>(s, ps, sta + (3 + W) * XS, mref);
        if (rel_other) {
            wg_wait<0>();
            mbar_arrive_warp(sb + BAR_REMPTY + vslot * 8);
            if (W == 1) mbar_arrive_warp_if(sb + BAR_XEMPTY + 24, i == 3);
        }
        fence_async_smem();
        nb_arrive<NB_PFULL + W, 256>();
        TSD(W, 6 + 5 * i);
        if (W == 1) {
            if (XLATE >= 2) mbar_arrive_warp_if<2>(sb + BAR_XEMPTY + 8, i == 3);
            if (XLATE >= 1) mbar_arrive_warp_if<2>(sb + BAR_XEMPTY + 16, i == 3);
        }
        if (rel_other || !PV0FIRST) {
            mbar_wait(sb + BAR_RFULL + r.slot * 8, r.ph, r.dl);
            sum_block(ps, l, lane);
        }
        if (W == 0 && i == 3) nx = get_item_warp(sb, it + 1, r.dl);
        TSD(W, 7 + 5 * i);
        if (LASTORD && W == 0 && i == 3) nb_sync<NB_PDONE, 256>();
        else nb_sync<NB_W + W, 128>();
        pv(first, W, !rel_other && PV0FIRST);
        if (!rel_other && PV0FIRST) sum_block(ps, l, lane);
        TSD(W, 8 + 5 * i);
    };
    if (W == 0) {
        nb_sync<NB_QK, 160>();
        TSD(W, 2);
        wg_fence();
        qk_steps<0, 8>(s, loRing + r.slot * (SLOT >> 4), loR);
        nb_sync<NB_Q2, 256>();
        qk_steps<8, 12>(s, loRing + r.slot * (SLOT >> 4), loR);
        wg_commit();
        nb_arrive<NB_Q01, 256>();
        TSD(W, 4);
        nb_sync<NB_REF, 160>();
        mref = __uint_as_float(lds_u(sb + OFF_GM));
        wg_wait<0>();
        reg_fence(s);
        mbar_arrive_warp<2>(sb + BAR_REMPTY + r.slot * 8);
        r.adv(2);
        TSD(W, 5);
        tail(TrueT{}, 0);
    } else {
        nb_sync<NB_Q01, 256>();
    }
#pragma unroll 1
    for (int i = (W == 0 ? 1 : 0); i < 4; i++) {
        const uint32_t pvslot = r.slot;
        r.adv(1);
        kslot = r.slot;
        mbar_wait(sb + BAR_RFULL + r.slot * 8, r.ph, r.dl);
        wg_fence();
        qk_steps<0, 4>(s, loRing + r.slot * (SLOT >> 4), loR);
        if (W == 1) wg_commit();
        qk_steps<4, 12>(s, loRing + r.slot * (SLOT >> 4), loR);
        wg_commit();
        wg_wait<1>();
        if (W == 1) mbar_arrive_warp_if(sb + BAR_XEMPTY + 0, i == 3);
        mbar_arrive_warp_if(sb + BAR_REMPTY + pvslot * 8, W == 0 || i > 0);
        r.adv(1);
        vslot = r.slot;
        TSD(W, 4 + 5 * i);
        if (VEARLY) mbar_wait(sb + BAR_RFULL + r.slot * 8, r.ph, r.dl);
        nb_sync<NB_PFULL + (W ^ 1), 256>();
        pv(FalseT{}, W ^ 1, !VEARLY);
        if (LASTORD && W == 1 && i == 3) nb_arrive<NB_PDONE, 256>();
        if (W == 1) mref = __uint_as_float(lds_u(sb + OFF_GM));
        wg_wait<1>();
        reg_fence(s);
        mbar_arrive_warp<2>(sb + BAR_REMPTY + kslot * 8);
        if (W == 0) mbar_arrive_warp_if(sb + BAR_XEMPTY + 0, i == 3);
        if (W == 1) {
            if (XLATE < 2) mbar_arrive_warp_if<2>(sb + BAR_XEMPTY + 8, i == 3);
            if (XLATE < 1) mbar_arrive_warp_if<2>(sb + BAR_XEMPTY + 16, i == 3);
        }
        r.adv(W == 1 && i == 3 ? 1 : 2);
        TSD(W, 5 + 5 * i);
        tail(FalseT{}, i);
    }
    if (W == 1) nx = get_item_warp(sb, it + 1, r.dl);
    if (W == 0) {
        Ring rn = r;
        rn.adv(2);
        q_ahead(q0, sb, rn, phm, IT_TYPE(nx) == IT_QA);
        TSD(W, 25);
    }
    const uint32_t w = (tid_now() >> 5) & 3;
    const uint32_t lxa = sb + OFF_LX + w * 640 + (((lane & 8) ? 80 : 0) + ((lane >> 1) & 8) + 2 * (lane & 3) + ((lane >> 2) & 1)) * 4;
    po.gp = ostash(IT_SLOT(e), IT_B(e)) + po.toff();
    po.sig = 1;
    if (W == 0) {
        sum_store<false>(l, lane, lxa);
        nb_arrive<NB_LX, 256>();
        wg_wait<1>();
        mbar_arrive_warp(sb + BAR_REMPTY + r.slot * 8);
        mbar_arrive_warp(sb + BAR_XEMPTY + 24);
        r.adv(1);
        if (VEARLY) mbar_wait(sb + BAR_RFULL + r.slot * 8, r.ph, r.dl);
        nb_sync<NB_PFULL + 1, 256>();
        pv(FalseT{}, 1, !VEARLY);
    } else {
        nb_sync<NB_LX, 256>();
        sum_store<true>(l, lane, lxa);
        nb_arrive<NB_L, 160>();
    }
    TSD(W, 24);
    wg_wait<0>();
    reg_fence(oa);
    reg_fence(ob);
    mbar_arrive_warp(sb + BAR_REMPTY + r.slot * 8);
    mbar_arrive_warp(sb + BAR_XEMPTY + 32);
    r.adv(1);
    opack(ob, po.v + 40);
    opack(oa, po.v);
    return nx;
}

template <int W>
__device__ __forceinline__ uint32_t qa_run(uint32_t e, uint32_t sb, Ring& r, uint32_t phm, PendO& po, int& it) {
    float q0[80], oa[80];
    if (W == 0) {
        zero(oa);
        q_ahead(q0, sb, r, phm, true);
        wg_wait<0>();
    }
#pragma unroll 1
    do {
        TS(W, 0);
        if (W == 0) TS_ITEM(e);
        e = qa_item<W>(e, sb, r, phm, po, q0, oa, it);
        TS(W, 31);
        it++;
    } while (IT_TYPE(e) == IT_QA && !po.bad);
    if (W == 0) {
#pragma unroll
        for (int i = 56; i < 64; i++) po.v[i] = 0;
    }
    return e;
}

__device__ __forceinline__ void consumer(const Params& P, uint32_t W, uint32_t sb, uint32_t dl) {
    int it = 0;
    Ring r{0, 0, dl};
    uint32_t phm = 0;
    uint32_t e = get_item_warp(sb, 0, dl);
#pragma unroll 1
    while (true) {
        if (IT_TYPE(e) == IT_QA) {
            PendO po;
            po.clear();
            e = W == 0 ? qa_run<0>(e, sb, r, phm, po, it) : qa_run<1>(e, sb, r, phm, po, it);
#pragma unroll 1
            for (int m = po.bad ? 2 : 1; m > 0; m--) {
                if (m == 1) {
                    po.verdict(sb, W);
                    if (W == 0) po.flush<0>(sb);
                    else po.flush<1>(sb);
                }
                if (po.bad) {
                    if (W == 0) fallback_unit(P, lds_u(sb + OFF_ITEM + (it - m) * 4), tid_now() & 127);
                    __syncwarp();
                    nb_sync<NB_ODONE, 288>();
                }
            }
        }
        if (e == 0) break;
        if (IT_TYPE(e) == IT_QA) continue;
        TS(W, 0);
        if (W == 0) TS_ITEM(e);
        if (IT_TYPE(e) == IT_ON) on_item(W, e, sb, r, phm);
        else if (W == 0) op_item<true>(e, sb, r, phm);
        else op_item<false>(e, sb, r, phm);
        TS(W, 31);
        e = get_item_warp(sb, ++it, dl);
    }
    TS_DUMP(W);
}

__global__ void __cluster_dims__(2, 1, 1) __launch_bounds__(384, 1) fused_kernel(const __grid_constant__ Params P) {
    extern __shared__ __align__(1024) unsigned char smem_raw[];
    const uint32_t sb = (uint32_t)__cvta_generic_to_shared(smem_raw);
    const uint32_t warp = __shfl_sync(0xffffffffu, threadIdx.x >> 5, 0), wgid = warp >> 2;
    const uint32_t cta = blockIdx.x;
    const uint32_t dl = deadline();

    if (threadIdx.x == 128) {
#pragma unroll
        for (int i = 0; i < NSLOT; i++) {
            mbar_init(sb + BAR_RFULL + i * 8, 1);
            mbar_init(sb + BAR_REMPTY + i * 8, 8);
            mbar_init(sb + BAR_XFULL + i * 8, 1);
            mbar_init(sb + BAR_XEMPTY + i * 8, 8);
        }
        asm volatile("fence.mbarrier_init.release.cluster;" ::: "memory");
        fence_async_smem();
    } else if (threadIdx.x == 160) {
#pragma unroll
        for (int i = 0; i < NSLOT + MAXI; i++) mbar_init(sb + BAR_PRDY + i * 8, 1);
        asm volatile("fence.mbarrier_init.release.cluster;" ::: "memory");
    } else if (threadIdx.x == 0) {
        sts_u(sb + OFF_ITEM, P.cl[cta >> 1].items[0] ? P.cl[cta >> 1].items[0] + 8 * (cta & 1) : 0);
        sts_u(sb + OFF_FB, P.cl[cta >> 1].delay);
    } else if (threadIdx.x == 64) {
        if (sb & 1023) __trap();
        asm volatile("prefetch.tensormap [%0];" ::"l"(&P.wq[0]) : "memory");
        asm volatile("prefetch.tensormap [%0];" ::"l"(&P.x[0]) : "memory");
    }
    __syncthreads();
    {
        const int it = 0;
        if (wgid == 1) TS(0, 30);
    }
    asm volatile("barrier.cluster.arrive.relaxed.aligned;" ::: "memory");
    if (warp < 3) {
        const uint32_t e = __shfl_sync(0xffffffffu, lds_u(sb + OFF_ITEM), 0), d = lds_u(sb + OFF_FB);
        const uint64_t pol = mkpol<POL_W>();
        const bool isx = warp == 1, lead = (threadIdx.x & 31) == 0;
        uint32_t t0, t1;
        asm volatile("mov.u32 %0, %%clock;" : "=r"(t0));
        do {
            asm volatile("mov.u32 %0, %%clock;" : "=r"(t1));
        } while (t1 - t0 < d);
        __syncwarp();
#pragma unroll 1
        for (int n = 0; n < (e ? NSLOT : 0); n++) {
            const uint32_t bar = sb + (isx ? BAR_XFULL : BAR_RFULL) + n * 8;
            if (lead) {
                if (warp < 2) mbar_expect(bar, isx ? XS : SLOT);
                tma3(sb + (isx ? OFF_R + n * XS : OFF_RING + n * SLOT + warp * (SLOT / 4)), isx ? &P.x[0] : &P.wq[0],
                     isx ? IT_B(e) * 160 : n * 64 + warp * 16, isx ? n : IT_H0(e) * 3, bar, pol);
            }
        }
        if (threadIdx.x == 0) asm volatile("mbarrier.arrive.shared::cta.b64 _, [%0];" ::"r"(sb + BAR_ITEM) : "memory");
        __syncwarp();
    }

    if (wgid == 0) {
        asm volatile("setmaxnreg.dec.sync.aligned.u32 24;");
        if (warp == 0) {
            const bool lead = threadIdx.x == 0;
            const uint64_t pol_first = mkpol<1>(), pol_norm = mkpol<POL_W>();
            uint32_t e = __shfl_sync(0xffffffffu, lds_u(sb + OFF_ITEM), 0);
            asm volatile("barrier.cluster.wait.aligned;" ::: "memory");
            unsigned int* const ticket = &g_ticket[next_epoch(0) & 1];
            const uint32_t rank = cta & 1;
            uint32_t peer;
            asm volatile("mapa.shared::cluster.u32 %0, %1, %2;" : "=r"(peer) : "r"(sb), "r"(rank ^ 1));
            Ring r{0, 0, dl};
            uint32_t pm = 0;
            auto load_w = [&](const CUtensorMap* m, int row, int blk, uint32_t half_bytes) {
                mbar_wait(sb + BAR_REMPTY + r.slot * 8, r.ph, dl);
                if (lead) {
                    mbar_expect(sb + BAR_RFULL + r.slot * 8, 2 * half_bytes);
                    asm volatile("mbarrier.arrive.shared::cluster.b64 _, [%0];" ::"r"(peer + BAR_PRDY + r.slot * 8) : "memory");
                }
                mbar_wait(sb + BAR_PRDY + r.slot * 8, (pm >> r.slot) & 1, dl);
                pm ^= 1u << r.slot;
                if (lead) tma3_mc(sb + OFF_RING + r.slot * SLOT + rank * half_bytes, m, row, blk, sb + BAR_RFULL + r.slot * 8, pol_norm);
                r.adv(1);
            };
#pragma unroll 1
            for (int it = 0; e != 0; it++) {
                uint32_t nx = 0, tk = 0;
                if (rank == 0 && IT_TYPE(e) != IT_ON && it + 2 < MAXI) nx = it + 1 < NSTAT ? P.cl[cta >> 1].items[it + 1] : IT_DYN;
                const uint32_t br = IT_BR(e);
                if (IT_TYPE(e) == IT_QA) {
                    const uint32_t h = IT_H0(e);
#pragma unroll 1
                    for (int kk = it ? 0 : NSLOT; kk < 10; kk++) load_w(&P.wq[br], kk * 64 + rank * 32, h * 3, SLOT / 2);
                    const int grp0 = (IT_B(e) * 32 + h) * 64;
#pragma unroll 1
                    for (int n = 0; n < 16; n++) {
                        if (n == 13 && nx == IT_DYN && lead) tk = atomicAdd(ticket, 1);
                        const bool isv = n == 15 || (n > 0 && !(n & 1));
                        const int j = n == 15 ? 7 : isv ? (n - 2) >> 1 : (n + 1) >> 1;
                        mbar_wait(sb + BAR_REMPTY + r.slot * 8, r.ph, dl);
                        if (lead) {
                            mbar_expect(sb + BAR_RFULL + r.slot * 8, SLOT);
                            asm volatile(
                                "cp.async.bulk.tensor.4d.shared::cluster.global.mbarrier::complete_tx::bytes.L2::cache_hint"
                                " [%0], [%1, {%3,%3,%3,%4}], [%2], %5;" ::"r"(sb + OFF_RING + r.slot * SLOT),
                                "l"(isv ? &P.v[br] : &P.k[br]), "r"(sb + BAR_RFULL + r.slot * 8), "r"(0), "r"(grp0 + j * 8), "l"(pol_first)
                                : "memory");
                        }
                        r.adv(1);
                    }
                } else {
                    const bool wide = IT_TYPE(e) == IT_OP;
                    const int step = wide ? 32 : 64, r1 = IT_H1(e) * 192;
#pragma unroll 1
                    for (int row = IT_H0(e) * 192 + rank * (step >> 1); row < r1; row += step)
                        load_w(wide ? &P.wo[br] : &P.won[br], row, IT_HALF(e) * (wide ? 5 : 2), wide ? XS / 2 : 8192);
                    if (nx == IT_DYN && lead) tk = atomicAdd(ticket, 1);
                }
                if (rank == 0) {
                    if (nx == IT_DYN) {
                        tk = __shfl_sync(0xffffffffu, tk, 0);
                        nx = tk < P.nlist ? P.list[tk] : 0;
                    }
                    e = nx;
                    if (lead) {
                        asm volatile("st.async.weak.shared::cluster.mbarrier::complete_tx::bytes.b32 [%0], %1, [%2];" ::"r"(
                                         peer + OFF_ITEM + 4 + it * 4),
                                     "r"(e ? e + 8 : 0), "r"(peer + BAR_ITEM + 8 + it * 8)
                                     : "memory");
                        sts_u(sb + OFF_ITEM + 4 + it * 4, e);
                        asm volatile("mbarrier.arrive.shared::cta.b64 _, [%0];" ::"r"(sb + BAR_ITEM + 8 + it * 8) : "memory");
                    }
                } else {
                    if (lead) mbar_expect(sb + BAR_ITEM + 8 + it * 8, 4);
                    e = get_item_warp(sb, it + 1, dl);
                }
            }
        } else if (warp == 1) {
            const uint64_t pol_norm = mkpol<POL_X>(), pol_o = mkpol<POL_O>();
            const bool lead = threadIdx.x == 32;
            uint32_t phm = 0, epoch = 0;
#pragma unroll 1
            for (int it = 0;; it++) {
                const uint32_t e = get_item_warp(sb, it, dl);
                if (it == 1 || (it == 0 && e == 0)) epoch = next_epoch(1);
                if (e == 0) break;
                const uint32_t br = IT_BR(e);
                uint32_t xs = 0;
                auto acquire = [&]() {
                    mbar_wait(sb + BAR_XEMPTY + xs * 8, (phm >> xs) & 1, dl);
                    phm ^= 1u << xs;
                    if (lead) mbar_expect(sb + BAR_XFULL + xs * 8, XS);
                };
                if (IT_TYPE(e) == IT_QA) {
#pragma unroll 1
                    for (int kk = it ? 0 : 5; kk < 10; kk++) {
                        acquire();
                        if (lead) tma3(sb + OFF_R + xs * XS, &P.x[br], IT_B(e) * 160, kk, sb + BAR_XFULL + xs * 8, pol_norm);
                        if (++xs == 5) xs = 0;
                    }
                } else {
                    const unsigned int* fp = g_flag + (br * 16 + IT_B(e)) * 64 + (threadIdx.x & 31);
                    uint32_t hm = 0, pm = 0;
                    auto poll = [&](uint32_t hneed, uint32_t pneed) {
                        if ((hm & hneed) == hneed && (pm & pneed) == pneed) return;
                        uint32_t n = 0;
                        do {
                            uint32_t a, b;
                            asm volatile("ld.acquire.gpu.global.u32 %0, [%2];\nld.acquire.gpu.global.u32 %1, [%2+128];"
                                         : "=r"(a), "=r"(b) : "l"(fp) : "memory");
                            hm = __ballot_sync(0xffffffffu, a == epoch);
                            pm = __ballot_sync(0xffffffffu, b == epoch);
                            if (++n > 0x1000000) __trap();
                        } while ((hm & hneed) != hneed || (pm & pneed) != pneed);
                        __syncwarp();
                        asm volatile("fence.proxy.async;" ::: "memory");
                    };
#pragma unroll 1
                    for (uint32_t h = IT_H0(e); h < IT_H1(e); h++) {
                        poll(1u << h, 0);
                        const unsigned char* src = ostash(P.slot[br * 32 + h], IT_B(e));
#pragma unroll 1
                        for (int t = 0; t < 3; t++) {
                            acquire();
                            if (lead) bulk_load(sb + OFF_R + xs * XS, src + t * XS, XS, sb + BAR_XFULL + xs * 8, pol_o);
                            if (++xs == 5) xs = 0;
                        }
                        if (IT_TYPE(e) == IT_OP && h >= 1) {
                            const uint32_t x1 = xs == 4 ? 0 : xs + 1;
                            mbar_wait(sb + BAR_XFULL + xs * 8, (phm >> xs) & 1, dl);
                            mbar_wait(sb + BAR_XFULL + x1 * 8, (phm >> x1) & 1, dl);
                            if (lead)
                                asm volatile("st.relaxed.gpu.global.u32 [%0], %1;" ::"l"(fp + 34 + IT_HALF(e)), "r"(epoch * 64 + h) : "memory");
                        }
                    }
                    if (IT_TYPE(e) == IT_ON) {
                        poll(0, IT_HALF(e) < 2 ? 1 : IT_HALF(e) == 2 ? 3 : 2);
#pragma unroll 1
                        for (uint32_t tile = 2 * IT_HALF(e); tile < 2 * IT_HALF(e) + 2; tile++) {
                            acquire();
                            if (lead)
                                asm volatile(
                                    "cp.async.bulk.tensor.5d.shared::cluster.global.mbarrier::complete_tx::bytes [%0], [%1, {%3,%5,%5,%5,%4}], [%2];" ::"r"(
                                        sb + OFF_R + xs * XS),
                                    "l"(&P.out), "r"(sb + BAR_XFULL + xs * 8), "r"(br * 640 + tile * 64), "r"(IT_B(e) * 5), "r"(0)
                                    : "memory");
                            if (++xs == 5) xs = 0;
                        }
                    }
                }
            }
        } else if (warp == 2) {
            asm volatile("barrier.cluster.wait.aligned;" ::: "memory");
            const uint32_t epoch = next_epoch(2);
            if (cta == 0) g_ticket[(epoch + 1) & 1] = 0;
#pragma unroll 1
            for (int it = 0;; it++) {
                const uint32_t e = get_item_warp(sb, it, dl);
                if (e == 0) break;
                nb_sync<NB_ODONE, 288>();
                if (threadIdx.x == 64) {
                    const uint32_t bb = IT_BR(e) * 16 + IT_B(e);
                    if (IT_TYPE(e) != IT_QA) {
                        const bool wide = IT_TYPE(e) == IT_OP;
                        if (wide)
                            asm volatile("st.relaxed.gpu.global.u32 [%0], %1;" ::"l"(&g_flag[bb * 64 + 34 + IT_HALF(e)]),
                                         "r"(epoch * 64 + IT_H1(e))
                                         : "memory");
                        const int cc0 = IT_BR(e) * 640 + IT_HALF(e) * (wide ? 320 : 128);
                        uint32_t xs = wide ? 0 : (3 * (IT_H1(e) - IT_H0(e))) % 5;
#pragma unroll 1
                        for (int m = 0; m < (wide ? 5 : 2); m++) {
                            asm volatile("cp.async.bulk.tensor.5d.global.shared::cta.bulk_group [%0, {%2,%4,%4,%4,%3}], [%1];" ::"l"(&P.out),
                                         "r"(sb + OFF_R + xs * XS), "r"(cc0 + m * 64), "r"((int)IT_B(e) * 5), "r"(0)
                                         : "memory");
                            asm volatile("cp.async.bulk.commit_group;" ::: "memory");
                            if (wide && m >= STLAG) {
                                asm volatile("cp.async.bulk.wait_group.read %0;" ::"n"(STLAG) : "memory");
                                asm volatile("mbarrier.arrive.shared::cta.b64 _, [%0], 8;" ::"r"(sb + BAR_XEMPTY + (m - STLAG) * 8) : "memory");
                            }
                            if (++xs == 5) xs = 0;
                        }
                        if (wide && STLAG) {
                            asm volatile("cp.async.bulk.wait_group.read 0;" ::: "memory");
                            asm volatile("mbarrier.arrive.shared::cta.b64 _, [%0], 8;" ::"r"(sb + BAR_XEMPTY + 32) : "memory");
                        }
                        if (IT_PART(e)) {
                            asm volatile("cp.async.bulk.wait_group 0;" ::: "memory");
                            asm volatile("fence.proxy.async;" ::: "memory");
                        }
                    }
                    if (IT_TYPE(e) == IT_QA || IT_PART(e)) {
                        unsigned int* f = &g_flag[bb * 64 + (IT_TYPE(e) == IT_QA ? IT_H0(e) : 32 + IT_HALF(e))];
                        asm volatile("st.release.gpu.global.u32 [%0], %1;" ::"l"(f), "r"(epoch) : "memory");
                    }
                }
                __syncwarp();
            }
            if (threadIdx.x == 64) asm volatile("cp.async.bulk.wait_group 0;" ::: "memory");
            __syncwarp();
            asm volatile("barrier.cluster.arrive.relaxed.aligned;\nbarrier.cluster.wait.aligned;" ::: "memory");
        } else {
            const uint32_t lane = threadIdx.x & 31, p = lane >> 2;
            const uint32_t epoch = next_epoch(3);
#pragma unroll 1
            for (int it = 0;; it++) {
                const uint32_t e = get_item_warp(sb, it, dl);
                if (e == 0) break;
                if (IT_TYPE(e) != IT_QA) continue;
                nb_sync<NB_QK, 160>();
                const uint32_t co = (((lane & 3) * 2) ^ p) << 4;
                const uint32_t ka = sb + OFF_RING + lds_u(sb + OFF_GM + 4) * SLOT + p * (3072 + 128) + co;
                const uint32_t qa = sb + OFF_R + p * 128 + co;
                uint32_t acc = 0;
#pragma unroll 1
                for (int c = 0; c < 3; c++) {
                    if (c == 2) nb_sync<NB_L, 160>();
                    const uint4 k0 = lds_u4(ka + c * 1024), q0 = lds_u4(qa + c * XS);
                    acc = fma_bf2(k0.x, q0.x, fma_bf2(k0.y, q0.y, fma_bf2(k0.z, q0.z, fma_bf2(k0.w, q0.w, acc))));
                    const uint4 k1 = lds_u4((ka + c * 1024) ^ 16), q1 = lds_u4((qa + c * XS) ^ 16);
                    acc = fma_bf2(k1.x, q1.x, fma_bf2(k1.y, q1.y, fma_bf2(k1.z, q1.z, fma_bf2(k1.w, q1.w, acc))));
                }
                float d = __uint_as_float(acc << 16) + __uint_as_float(acc & 0xffff0000u);
                d += __shfl_xor_sync(0xffffffffu, d, 1);
                d += __shfl_xor_sync(0xffffffffu, d, 2);
                int key = __float_as_int(d);
                key ^= (key >> 31) & 0x7fffffff;
                key = __reduce_max_sync(0xffffffffu, key);
                key ^= (key >> 31) & 0x7fffffff;
                sts_f(sb + OFF_GM, fmaf(__int_as_float(key), SM_C, 16.f));
                nb_arrive<NB_REF, 160>();
                if (IT_DEP(e)) {
                    const uint32_t g = IT_DEP(e) - 1, need = epoch * 64 + (g & 31) + 1;
                    const unsigned int* cp = &g_flag[((g >> 5) * 16 + IT_B(e)) * 64 + 34 + (lane & 1)];
                    for (uint32_t n = 0;; n++) {
                        uint32_t v;
                        asm volatile("ld.acquire.gpu.global.u32 %0, [%1];" : "=r"(v) : "l"(cp) : "memory");
                        if (__all_sync(0xffffffffu, v - need < 64)) break;
                        if (n > 0x800000) __trap();
                        __nanosleep(500);
                    }
                }
                nb_sync<NB_L, 160>();
                bool bad = false;
#pragma unroll
                for (int c = 0; c < 5; c++) {
                    const uint32_t la = sb + OFF_LX + (c * 32 + lane) * 4;
                    const float v = (__uint_as_float(lds_u(la)) + __uint_as_float(lds_u(la + 640))) +
                                    (__uint_as_float(lds_u(la + 1280)) + __uint_as_float(lds_u(la + 1920)));
                    const float inv = __fdividef(1.f, v);
                    const uint32_t hi = pack_bf16(inv, 0.f), lo = pack_bf16(inv - __uint_as_float(hi << 16), 0.f);
                    const uint32_t ia = sb + OFF_LINV + c * 128 + ((lane >> 1) & 3) * 32 + (lane >> 3) * 8 + (lane & 1) * 2;
                    asm volatile("st.shared.u16 [%0], %1;\nst.shared.u16 [%0+4], %2;" ::"r"(ia), "h"((unsigned short)hi), "h"((unsigned short)lo) : "memory");
                    bad |= !(v >= 5.421010862e-20f && v <= 7.9228163e28f);
                }
                sts_u(sb + OFF_FB, __any_sync(0xffffffffu, bad));
                nb_arrive<NB_VOTE, 160>();
                nb_arrive<NB_VOTE + 1, 160>();
            }
        }
    } else {
        asm volatile("setmaxnreg.inc.sync.aligned.u32 240;");
        consumer(P, wgid - 1, sb, dl);
    }
}

typedef CUresult (*EncFn)(CUtensorMap*, CUtensorMapDataType, cuuint32_t, void*, const cuuint64_t*, const cuuint64_t*,
                          const cuuint32_t*, const cuuint32_t*, CUtensorMapInterleave, CUtensorMapSwizzle,
                          CUtensorMapL2promotion, CUtensorMapFloatOOBfill);

void make_map3(EncFn enc, CUtensorMap* m, void* p, uint64_t rows, uint64_t rowbytes, uint64_t nblk, uint32_t boxrows,
               uint32_t boxblk) {
    cuuint64_t dims[3] = {64, rows, nblk};
    cuuint64_t str[2] = {rowbytes, 128};
    cuuint32_t box[3] = {64, boxrows, boxblk};
    cuuint32_t es[3] = {1, 1, 1};
    enc(m, CU_TENSOR_MAP_DATA_TYPE_BFLOAT16, 3, p, dims, str, box, es, CU_TENSOR_MAP_INTERLEAVE_NONE,
        CU_TENSOR_MAP_SWIZZLE_128B, CU_TENSOR_MAP_L2_PROMOTION_NONE, CU_TENSOR_MAP_FLOAT_OOB_FILL_NONE);
}

constexpr int tune(const char*, int def) { return def; }

void build_schedule(Params& P) {
    const int mode = tune("MODE", 4), dmax = tune("DMAX", 24200), n0 = tune("N0", 10), odmax = tune("ODMAX", 0), d1 = tune("D1", 0);
    const int H0[8] = {19, 20, 21, 22, 22, 24, 25, 25}, P0[8] = {367, 337, 335, 331, 338, 335, 333, 332};
    const int ra = tune("RA", 10), ga = tune("GA", 17), rb = tune("RB", 11), g1 = tune("G1", 58);
    int dep[64];
    for (int g = 0, ns = 0, live = 0; g < 64; g++) {
        const bool fresh = mode < 3 || g >= g1 || live < (g < ga ? ra : rb);
        dep[g] = fresh ? 0 : g - live + 1;
        P.slot[g] = fresh ? ns++ : P.slot[g - live];
        live += fresh;
    }
    int H[8], pos[8], psum = 0;
    for (int b = 0; b < 8; b++) {
        const char nh[3] = {'H', (char)('0' + b), 0}, np[3] = {'P', (char)('0' + b), 0};
        H[b] = tune(nh, H0[b]);
        pos[b] = tune(np, P0[b]);
        psum += pos[b];
    }
    const int sk = tune("SK", 10), g0 = tune("G0", 20), g2 = tune("G2", 40);
    int ord[512], nxt[8] = {0, 0, 0, 0, 0, 0, 0, 0};
    for (int k = 0; k < 512; k++) {
        int best = -1;
        float bkey = 0.f;
        for (int b = 0; b < 8; b++) {
            const int g = nxt[b];
            if (g == 64) continue;
            const float w = g < g0 ? 0.f : g < 32 ? (g - g0) / (32.f - g0) : g < g2 ? 1.f : (64 - g) / (64.f - g2);
            const float key = g + w * sk * 0.1f * (pos[b] - psum / 8.f) / 8.f;
            if (best < 0 || key < bkey) best = b, bkey = key;
        }
        ord[k] = nxt[best]++ * 8 + best;
        const int d = dep[ord[k] >> 3];
        if (d > 32) {
            if (pos[best] > k) pos[best] = k;
            if (H[best] < d - 32) H[best] = d - 32;
        }
    }
    int u = 0;
    auto unit = [&]() {
        const int v = ord[u++];
        return mk_item(IT_QA, v >> 8, (v & 7) * 2, (v >> 3) & 31, P.slot[v >> 3], 0) | (dep[v >> 3] << 23);
    };
    const int ob = tune("OB", 4), qm = tune("QM", 19);
    int qa[NCL], nq = 0, op[NCL], no = 0;
    for (int c = 0; c < NCL; c++) {
        P.cl[c].delay = 0;
        for (int i = 0; i < NSTAT; i++) P.cl[c].items[i] = 0;
        if (mode >= 3 && ob >= 0 && c >= ob && c < ob + 16) op[((c - ob) & 7) * 2 + ((c - ob) >> 3)] = c, no++;
        else if (mode >= 3 && ob < 0 && c < 64 && (c & 3) == 3) op[no++] = c;
        else if (mode != 2 || (c & 3) == 0) qa[nq++] = c;
    }
    for (int t = 0; t < no; t++) {
        P.cl[op[t]].items[1] = mk_item(IT_OP, 0, t & ~1, 0, 32, t & 1);
        P.cl[op[t]].items[2] = IT_DYN;
        P.cl[op[t]].delay = tune("OD0", 0) + t * odmax / 16;
    }
    for (int k = 0; k < nq; k++) {
        const int c = qa[(k * qm) % nq];
        P.cl[c].items[1] = P.cl[c].items[2] = IT_DYN;
        P.cl[c].delay = k < n0 ? k * tune("J0", 0) : d1 + (dmax - d1) * (k + 1 - n0) / (nq - n0);
    }
    if (tune("OFIRST", 0))
        for (int t = 0; t < no; t++) P.cl[op[t]].items[0] = unit();
    for (int k = u; k < no + nq; k++) {
        int best = -1;
        for (int c = 0; c < NCL; c++)
            if (P.cl[c].items[1] && !P.cl[c].items[0] && (best < 0 || P.cl[c].delay < P.cl[best].delay)) best = c;
        P.cl[best].items[0] = unit();
    }
    int n = 0;
    const int uend = mode == 2 ? 8 * nq : 512;
    while (u < uend) {
        for (int b = 0; b < 8 && no; b++)
            if (pos[b] == u) {
                P.list[n++] = mk_item(IT_OP, 1, 2 * b, 0, H[b], 0, 1);
                P.list[n++] = mk_item(IT_OP, 1, 2 * b, 0, H[b], 1, 1);
            }
        P.list[n++] = unit();
    }
    for (int k = 0; no && k < 40; k++) P.list[n++] = mk_item(IT_ON, 1, k / 5 * 2, H[k / 5], 32, k % 5);
    P.nlist = n;
}

}

extern "C" void kernel_launch(void* const* d_in, const int* in_sizes, int n_in, void* d_out, int out_size) {
    static Params P;
    static bool init = false;
    if (!init) {
        EncFn enc = nullptr;
        cudaDriverEntryPointQueryResult qr;
        cudaGetDriverEntryPoint("cuTensorMapEncodeTiled", (void**)&enc, cudaEnableDefault, &qr);
        for (int i = 0; i < 2; i++) {
            P.px[i] = (const __nv_bfloat16*)d_in[5 * i + 0];
            P.pk[i] = (const __nv_bfloat16*)d_in[5 * i + 1];
            P.pv[i] = (const __nv_bfloat16*)d_in[5 * i + 2];
            P.pwq[i] = (const __nv_bfloat16*)d_in[5 * i + 3];
            make_map3(enc, &P.x[i], d_in[5 * i + 0], 2560, 1280, 10, 160, 1);
            for (int j = 0; j < 2; j++) {
                cuuint64_t dims[4] = {64, 8, 3, 16 * 32 * 64};
                cuuint64_t str[3] = {384, 128, 3072};
                cuuint32_t box[4] = {64, 8, 3, 8};
                cuuint32_t es[4] = {1, 1, 1, 1};
                enc(j ? &P.v[i] : &P.k[i], CU_TENSOR_MAP_DATA_TYPE_BFLOAT16, 4, d_in[5 * i + 1 + j], dims, str, box, es,
                    CU_TENSOR_MAP_INTERLEAVE_NONE, CU_TENSOR_MAP_SWIZZLE_128B, (CUtensorMapL2promotion)tune("PROMO", 0),
                    CU_TENSOR_MAP_FLOAT_OOB_FILL_NONE);
            }
            make_map3(enc, &P.wq[i], d_in[5 * i + 3], 640, 12288, 96, 32, 3);
            make_map3(enc, &P.wo[i], d_in[5 * i + 4], 6144, 1280, 10, 16, 5);
            make_map3(enc, &P.won[i], d_in[5 * i + 4], 6144, 1280, 10, 32, 2);
        }
        cuuint64_t dims[5] = {1280, 2, 4, 4, 80};
        cuuint64_t str[4] = {2560, 8 * 2560, 2 * 2560, 32 * 2560};
        cuuint32_t box[5] = {64, 2, 4, 4, 5};
        cuuint32_t es[5] = {1, 1, 1, 1, 1};
        enc(&P.out, CU_TENSOR_MAP_DATA_TYPE_BFLOAT16, 5, d_out, dims, str, box, es, CU_TENSOR_MAP_INTERLEAVE_NONE,
            CU_TENSOR_MAP_SWIZZLE_128B, CU_TENSOR_MAP_L2_PROMOTION_NONE, CU_TENSOR_MAP_FLOAT_OOB_FILL_NONE);
        build_schedule(P);
        cudaFuncSetAttribute(fused_kernel, cudaFuncAttributeMaxDynamicSharedMemorySize, SMEM_LAUNCH);
        init = true;
    }
    fused_kernel<<<NCTA, 384, SMEM_LAUNCH>>>(P);
}
```

```cpp
#include <cuda_runtime.h>
#include <cuda.h>
#include <cuda_bf16.h>
#include <stdint.h>

namespace {

constexpr int NCTA = 132;
constexpr int NCL = NCTA / 2;
constexpr int MAXI = 16;
constexpr int NSTAT = 3;
constexpr uint32_t IT_DYN = 0xffffffffu;
constexpr int SLOT = 24576;
constexpr int NSLOT = 5;
constexpr int XS = 20480;
constexpr int OFF_R = 0;
constexpr int OFF_RING = 5 * XS;
constexpr int OFF_MISC = OFF_RING + NSLOT * SLOT;
constexpr int OFF_LX = OFF_MISC;
constexpr int OFF_LINV = OFF_LX + 2560;
constexpr int OFF_FB = OFF_LINV + 640;
constexpr int OFF_GM = OFF_FB + 16;
constexpr int OFF_BAR = OFF_GM + 16;
constexpr int BAR_RFULL = OFF_BAR;
constexpr int BAR_REMPTY = BAR_RFULL + 40;
constexpr int BAR_XFULL = BAR_REMPTY + 40;
constexpr int BAR_XEMPTY = BAR_XFULL + 40;
constexpr int BAR_PRDY = BAR_XEMPTY + 40;
constexpr int BAR_ITEM = BAR_PRDY + 40;
constexpr int OFF_ITEM = BAR_ITEM + MAXI * 8;
constexpr int SMEM_BYTES = OFF_ITEM + MAXI * 4;
static_assert(SMEM_BYTES <= 232448, "smem");

constexpr int NB_W = 1  , NB_PFULL = 3  , NB_VOTE = 5  , NB_Q2 = 7, NB_SDONE = 8, NB_PDONE = 9,
              NB_L = 10, NB_REF = 11, NB_ODONE = 12, NB_OPEND = 13, NB_LX = 14, NB_Q01 = 15, NB_QK = 0  ;

constexpr uint32_t IT_QA = 1, IT_OP = 2, IT_ON = 3;
__host__ __device__ constexpr uint32_t mk_item(uint32_t type, uint32_t br, uint32_t b, uint32_t h0, uint32_t h1, uint32_t half,
                                               uint32_t part = 0) {
    return type | (br << 2) | (b << 3) | (h0 << 7) | (h1 << 13) | (half << 19) | (part << 22);
}
#define IT_TYPE(e) ((e) & 3u)
#define IT_BR(e) (((e) >> 2) & 1u)
#define IT_B(e) (((e) >> 3) & 15u)
#define IT_H0(e) (((e) >> 7) & 63u)
#define IT_H1(e) (((e) >> 13) & 63u)
#define IT_HALF(e) (((e) >> 19) & 7u)
#define IT_PART(e) (((e) >> 22) & 1u)
#define IT_SLOT(e) IT_H1(e)
#define IT_DEP(e) (((e) >> 23) & 127u)

struct Params {
    CUtensorMap x[2], wq[2], k[2], v[2], wo[2], won[2], out;
    const __nv_bfloat16 *px[2], *pwq[2], *pk[2], *pv[2];
    struct alignas(16) { uint32_t delay, items[NSTAT]; } cl[NCL];
    uint32_t nlist;
    uint8_t slot[64];
    uint32_t list[512];
};

constexpr int OUNIT = 61440;
__device__ __align__(1024) unsigned char g_ostash[(size_t)1024 * OUNIT];
__device__ unsigned int g_flag[32 * 64];
__device__ __forceinline__ unsigned char* ostash(uint32_t slot, uint32_t b) { return g_ostash + (slot * 16 + b) * OUNIT; }
__device__ unsigned int g_epoch[NCTA * 4];
__device__ unsigned int g_ticket[2];

constexpr int SMEM_LAUNCH = SMEM_BYTES;
#define TS(role, idx)
#define TS_ITEM(e)
#define TS_DUMP(role)
#define TSD(role, idx)

#define POL_W 2
#define POL_X 2
#define POL_O 2
template <int M>
__device__ __forceinline__ uint64_t mkpol() {
    uint64_t p;
    if (M == 0) asm volatile("createpolicy.fractional.L2::evict_normal.b64 %0, 1.0;" : "=l"(p));
    if (M == 1) asm volatile("createpolicy.fractional.L2::evict_first.b64 %0, 1.0;" : "=l"(p));
    if (M == 2) asm volatile("createpolicy.fractional.L2::evict_unchanged.b64 %0, 1.0;" : "=l"(p));
    if (M == 3) asm volatile("createpolicy.fractional.L2::evict_normal.L2::evict_unchanged.b64 %0, 0.25;" : "=l"(p));
    return p;
}
#define STSM_W 1
#define SIGJ 0
#define STLAG 1
#define VEARLY 1
#define K0POS 3
#define LASTORD 0
#define XLATE 2
#define PV0FIRST 1
#define QST0 2
#define QST1 1
#define QHOLD 8
constexpr float SM_C = 0.07216878364870322f * 1.4426950408889634f;

__device__ __forceinline__ uint32_t next_epoch(int warp) {
    unsigned int* p = &g_epoch[blockIdx.x * 4 + warp];
    const uint32_t e = __ldcg(p) + 1;
    *p = e;
    return e;
}

__device__ __forceinline__ uint32_t tid_now() {
    uint32_t t;
    asm volatile("mov.u32 %0, %%tid.x;" : "=r"(t));
    return t;
}
__device__ __forceinline__ void mbar_init(uint32_t a, uint32_t c) {
    asm volatile("mbarrier.init.shared::cta.b64 [%0], %1;" ::"r"(a), "r"(c) : "memory");
}
__device__ __forceinline__ void mbar_expect(uint32_t a, uint32_t b) {
    asm volatile("mbarrier.arrive.expect_tx.shared::cta.b64 _, [%0], %1;" ::"r"(a), "r"(b) : "memory");
}
template <int CNT = 1>
__device__ __forceinline__ void mbar_arrive_warp(uint32_t a) {
    if (CNT == 1)
        asm volatile("{\n.reg .pred p;\nelect.sync _|p, 0xffffffff;\n@p mbarrier.arrive.shared::cta.b64 _, [%0];\n}" ::"r"(a) : "memory");
    else
        asm volatile(
            "{\n.reg .pred p;\nelect.sync _|p, 0xffffffff;\n@p mbarrier.arrive.shared::cta.b64 _, [%0];\n"
            "@p mbarrier.arrive.shared::cta.b64 _, [%0];\n}" ::"r"(a)
            : "memory");
}
template <int CNT = 1>
__device__ __forceinline__ void mbar_arrive_warp_if(uint32_t a, bool cond) {
    if (CNT == 1)
        asm volatile(
            "{\n.reg .pred p, c;\nelect.sync _|p, 0xffffffff;\nsetp.ne.and.u32 c, %1, 0, p;\n"
            "@c mbarrier.arrive.shared::cta.b64 _, [%0];\n}" ::"r"(a), "r"((uint32_t)cond)
            : "memory");
    else
        asm volatile(
            "{\n.reg .pred p, c;\nelect.sync _|p, 0xffffffff;\nsetp.ne.and.u32 c, %1, 0, p;\n"
            "@c mbarrier.arrive.shared::cta.b64 _, [%0];\n@c mbarrier.arrive.shared::cta.b64 _, [%0];\n}" ::"r"(a), "r"((uint32_t)cond)
            : "memory");
}
__device__ __forceinline__ uint32_t deadline() {
    uint32_t c;
    asm volatile("mov.u32 %0, %%clock_hi;" : "=r"(c));
    return c + 4;
}
__device__ __forceinline__ void mbar_wait(uint32_t a, uint32_t ph, uint32_t dl) {
    asm volatile(
        "{\n.reg .pred p;\n.reg .u32 m;\n"
        "LOOP:\n"
        "mbarrier.try_wait.parity.shared::cta.b64 p, [%0], %1;\n"
        "@p bra DONE;\n"
        "mov.u32 m, %%clock_hi;\n"
        "setp.ne.u32 p, m, %2;\n"
        "@p bra LOOP;\n"
        "trap;\n"
        "DONE:\n}" ::"r"(a), "r"(ph), "r"(dl)
        : "memory");
}
__device__ __forceinline__ void mbar_wait2(uint32_t a, uint32_t pa, uint32_t b, uint32_t pb, uint32_t dl) {
    asm volatile(
        "{\n.reg .pred p, q;\n.reg .u32 m;\n"
        "LOOP:\n"
        "mbarrier.try_wait.parity.shared::cta.b64 p, [%0], %1;\n"
        "mbarrier.try_wait.parity.shared::cta.b64 q, [%2], %3;\n"
        "and.pred p, p, q;\n"
        "@p bra DONE;\n"
        "mov.u32 m, %%clock_hi;\n"
        "setp.ne.u32 p, m, %4;\n"
        "@p bra LOOP;\n"
        "trap;\n"
        "DONE:\n}" ::"r"(a), "r"(pa), "r"(b), "r"(pb), "r"(dl)
        : "memory");
}
template <int ID, int CNT>
__device__ __forceinline__ void nb_sync() { asm volatile("bar.sync %0, %1;" ::"n"(ID), "n"(CNT) : "memory"); }
template <int ID, int CNT>
__device__ __forceinline__ void nb_arrive() { asm volatile("bar.arrive %0, %1;" ::"n"(ID), "n"(CNT) : "memory"); }
__device__ __forceinline__ void fence_async_smem() { asm volatile("fence.proxy.async.shared::cta;" ::: "memory"); }

__device__ __forceinline__ void tma3(uint32_t dst, const CUtensorMap* m, int c1, int c2, uint32_t bar, uint64_t pol) {
    asm volatile(
        "cp.async.bulk.tensor.3d.shared::cluster.global.mbarrier::complete_tx::bytes.L2::cache_hint [%0], [%1, {%3,%4,%5}], [%2], %6;" ::"r"(dst),
        "l"(m), "r"(bar), "r"(0), "r"(c1), "r"(c2), "l"(pol)
        : "memory");
}
__device__ __forceinline__ void tma3_mc(uint32_t dst, const CUtensorMap* m, int c1, int c2, uint32_t bar, uint64_t pol) {
    asm volatile(
        "cp.async.bulk.tensor.3d.shared::cluster.global.mbarrier::complete_tx::bytes.multicast::cluster.L2::cache_hint"
        " [%0], [%1, {%3,%4,%5}], [%2], %6, %7;" ::"r"(dst),
        "l"(m), "r"(bar), "r"(0), "r"(c1), "r"(c2), "h"((unsigned short)3), "l"(pol)
        : "memory");
}
__device__ __forceinline__ void bulk_load(uint32_t dst, const void* src, uint32_t bytes, uint32_t bar, uint64_t pol) {
    asm volatile("cp.async.bulk.shared::cluster.global.mbarrier::complete_tx::bytes.L2::cache_hint [%0], [%1], %2, [%3], %4;" ::"r"(dst),
                 "l"(src), "r"(bytes), "r"(bar), "l"(pol)
                 : "memory");
}
__device__ __forceinline__ void wg_fence() { asm volatile("wgmma.fence.sync.aligned;" ::: "memory"); }
__device__ __forceinline__ void wg_commit() { asm volatile("wgmma.commit_group.sync.aligned;" ::: "memory"); }
template <int N>
__device__ __forceinline__ void wg_wait() { asm volatile("wgmma.wait_group.sync.aligned %0;" ::"n"(N) : "memory"); }

#define RW80(c, d) c(d[0]), c(d[1]), c(d[2]), c(d[3]), c(d[4]), c(d[5]), c(d[6]), c(d[7]), c(d[8]), c(d[9]), c(d[10]), c(d[11]), c(d[12]), c(d[13]), c(d[14]), c(d[15]), c(d[16]), c(d[17]), c(d[18]), c(d[19]), c(d[20]), c(d[21]), c(d[22]), c(d[23]), c(d[24]), c(d[25]), c(d[26]), c(d[27]), c(d[28]), c(d[29]), c(d[30]), c(d[31]), c(d[32]), c(d[33]), c(d[34]), c(d[35]), c(d[36]), c(d[37]), c(d[38]), c(d[39]), c(d[40]), c(d[41]), c(d[42]), c(d[43]), c(d[44]), c(d[45]), c(d[46]), c(d[47]), c(d[48]), c(d[49]), c(d[50]), c(d[51]), c(d[52]), c(d[53]), c(d[54]), c(d[55]), c(d[56]), c(d[57]), c(d[58]), c(d[59]), c(d[60]), c(d[61]), c(d[62]), c(d[63]), c(d[64]), c(d[65]), c(d[66]), c(d[67]), c(d[68]), c(d[69]), c(d[70]), c(d[71]), c(d[72]), c(d[73]), c(d[74]), c(d[75]), c(d[76]), c(d[77]), c(d[78]), c(d[79])
#define RW48(c, d) c(d[0]), c(d[1]), c(d[2]), c(d[3]), c(d[4]), c(d[5]), c(d[6]), c(d[7]), c(d[8]), c(d[9]), c(d[10]), c(d[11]), c(d[12]), c(d[13]), c(d[14]), c(d[15]), c(d[16]), c(d[17]), c(d[18]), c(d[19]), c(d[20]), c(d[21]), c(d[22]), c(d[23]), c(d[24]), c(d[25]), c(d[26]), c(d[27]), c(d[28]), c(d[29]), c(d[30]), c(d[31]), c(d[32]), c(d[33]), c(d[34]), c(d[35]), c(d[36]), c(d[37]), c(d[38]), c(d[39]), c(d[40]), c(d[41]), c(d[42]), c(d[43]), c(d[44]), c(d[45]), c(d[46]), c(d[47])
#define RW32(c, d) c(d[0]), c(d[1]), c(d[2]), c(d[3]), c(d[4]), c(d[5]), c(d[6]), c(d[7]), c(d[8]), c(d[9]), c(d[10]), c(d[11]), c(d[12]), c(d[13]), c(d[14]), c(d[15]), c(d[16]), c(d[17]), c(d[18]), c(d[19]), c(d[20]), c(d[21]), c(d[22]), c(d[23]), c(d[24]), c(d[25]), c(d[26]), c(d[27]), c(d[28]), c(d[29]), c(d[30]), c(d[31])

__device__ __forceinline__ void reg_fence(float (&d)[80]) { asm volatile("" : RW80("+f", d)::"memory"); }
__device__ __forceinline__ void reg_fence(float (&d)[48]) { asm volatile("" : RW48("+f", d)::"memory"); }
__device__ __forceinline__ void reg_fence(float (&d)[32]) { asm volatile("" : RW32("+f", d)::"memory"); }

template <int NR>
__device__ __forceinline__ void zero(float (&d)[NR]) {
#pragma unroll
    for (int i = 0; i < NR; i++) d[i] = 0.f;
}

constexpr uint32_t HI_SW128 = (1024u >> 4) | (1u << 30);
constexpr uint32_t HI_KV = (3072u >> 4) | (1u << 30);
constexpr uint32_t HI_OST = (2560u >> 4) | (2u << 30);
constexpr uint32_t LO_LBO1 = (1u << 16);
constexpr uint32_t LO_OST = ((512u >> 4) << 16);

template <int TA, int TB, uint32_t HIB, int ACC, uint32_t HIA = HI_SW128>
__device__ __forceinline__ void wgmma(float (&d)[80], uint32_t loA, uint32_t loB) {
#define WG_ASM(SD)                                                          \
    "{\n.reg .b64 da, db;\nmov.b64 da, {%80, %82};\nmov.b64 db, {%81, %83};\n" \
    "wgmma.mma_async.sync.aligned.m64n160k16.f32.bf16.bf16 "               \
    "{%0,%1,%2,%3,%4,%5,%6,%7,%8,%9,%10,%11,%12,%13,%14,%15,%16,%17,%18,%19,%20,%21,%22,%23,%24,%25,%26,%27,%28,%29,%30,%31,%32,%33,%34,%35,%36,%37,%38,%39,%40,%41,%42,%43,%44,%45,%46,%47,%48,%49,%50,%51,%52,%53,%54,%55,%56,%57,%58,%59,%60,%61,%62,%63,%64,%65,%66,%67,%68,%69,%70,%71,%72,%73,%74,%75,%76,%77,%78,%79}, da, db, " SD ", 1, 1, %84, %85;\n}"
    if constexpr (ACC == 2)
        asm volatile(WG_ASM("0") : RW80("+f", d) : "r"(loA), "r"(loB), "n"(HIA), "n"(HIB), "n"(TA), "n"(TB));
    else if constexpr (ACC == 1)
        asm volatile(WG_ASM("1") : RW80("+f", d) : "r"(loA), "r"(loB), "n"(HIA), "n"(HIB), "n"(TA), "n"(TB));
    else
        asm volatile(WG_ASM("0") : RW80("=f", d) : "r"(loA), "r"(loB), "n"(HIA), "n"(HIB), "n"(TA), "n"(TB));
#undef WG_ASM
}
template <int TA, int TB, uint32_t HIB, int ACC, uint32_t HIA = HI_SW128>
__device__ __forceinline__ void wgmma(float (&d)[48], uint32_t loA, uint32_t loB) {
#define WG_ASM(SD)                                                          \
    "{\n.reg .b64 da, db;\nmov.b64 da, {%48, %50};\nmov.b64 db, {%49, %51};\n" \
    "wgmma.mma_async.sync.aligned.m64n96k16.f32.bf16.bf16 "               \
    "{%0,%1,%2,%3,%4,%5,%6,%7,%8,%9,%10,%11,%12,%13,%14,%15,%16,%17,%18,%19,%20,%21,%22,%23,%24,%25,%26,%27,%28,%29,%30,%31,%32,%33,%34,%35,%36,%37,%38,%39,%40,%41,%42,%43,%44,%45,%46,%47}, da, db, " SD ", 1, 1, %52, %53;\n}"
    if constexpr (ACC == 1)
        asm volatile(WG_ASM("1") : RW48("+f", d) : "r"(loA), "r"(loB), "n"(HIA), "n"(HIB), "n"(TA), "n"(TB));
    else
        asm volatile(WG_ASM("0") : RW48("=f", d) : "r"(loA), "r"(loB), "n"(HIA), "n"(HIB), "n"(TA), "n"(TB));
#undef WG_ASM
}
template <int TA, int TB, uint32_t HIB, int ACC, uint32_t HIA = HI_SW128>
__device__ __forceinline__ void wgmma(float (&d)[32], uint32_t loA, uint32_t loB) {
#define WG_ASM(SD)                                                          \
    "{\n.reg .b64 da, db;\nmov.b64 da, {%32, %34};\nmov.b64 db, {%33, %35};\n" \
    "wgmma.mma_async.sync.aligned.m64n64k16.f32.bf16.bf16 "               \
    "{%0,%1,%2,%3,%4,%5,%6,%7,%8,%9,%10,%11,%12,%13,%14,%15,%16,%17,%18,%19,%20,%21,%22,%23,%24,%25,%26,%27,%28,%29,%30,%31}, da, db, " SD ", 1, 1, %36, %37;\n}"
    if constexpr (ACC == 1)
        asm volatile(WG_ASM("1") : RW32("+f", d) : "r"(loA), "r"(loB), "n"(HIA), "n"(HIB), "n"(TA), "n"(TB));
    else
        asm volatile(WG_ASM("0") : RW32("=f", d) : "r"(loA), "r"(loB), "n"(HIA), "n"(HIB), "n"(TA), "n"(TB));
#undef WG_ASM
}

__device__ __forceinline__ uint32_t pack_bf16(float lo, float hi) {
    uint32_t r;
    asm("cvt.rn.bf16x2.f32 %0, %1, %2;" : "=r"(r) : "f"(hi), "f"(lo));
    return r;
}
__device__ __forceinline__ float ex2(float x) {
    float r;
    asm("ex2.approx.ftz.f32 %0, %1;" : "=f"(r) : "f"(x));
    return r;
}
__device__ __forceinline__ void stsm4t(uint32_t a, uint32_t r0, uint32_t r1, uint32_t r2, uint32_t r3) {
    asm volatile("stmatrix.sync.aligned.m8n8.x4.trans.shared.b16 [%0], {%1,%2,%3,%4};" ::"r"(a), "r"(r0), "r"(r1), "r"(r2), "r"(r3)
                 : "memory");
}
__device__ __forceinline__ uint32_t lds_u(uint32_t a) {
    uint32_t v;
    asm volatile("ld.shared.u32 %0, [%1];" : "=r"(v) : "r"(a) : "memory");
    return v;
}
__device__ __forceinline__ uint4 lds_u4(uint32_t a) {
    uint4 v;
    asm volatile("ld.shared.v4.u32 {%0,%1,%2,%3}, [%4];" : "=r"(v.x), "=r"(v.y), "=r"(v.z), "=r"(v.w) : "r"(a) : "memory");
    return v;
}
__device__ __forceinline__ float2 lds_f2(uint32_t a) {
    float2 v;
    asm volatile("ld.shared.v2.f32 {%0,%1}, [%2];" : "=f"(v.x), "=f"(v.y) : "r"(a) : "memory");
    return v;
}
__device__ __forceinline__ void sts_f(uint32_t a, float v) { asm volatile("st.shared.f32 [%0], %1;" ::"r"(a), "f"(v) : "memory"); }
__device__ __forceinline__ void sts_u(uint32_t a, uint32_t v) { asm volatile("st.shared.u32 [%0], %1;" ::"r"(a), "r"(v) : "memory"); }
__device__ __forceinline__ void sts_f2(uint32_t a, float x, float y) {
    asm volatile("st.shared.v2.f32 [%0], {%1,%2};" ::"r"(a), "f"(x), "f"(y) : "memory");
}

template <bool ADD = false, bool SIG = false, int NR>
__device__ __forceinline__ void store_tile_t(const float (&d)[NR], uint32_t addr) {
    uint32_t p[NR / 2];
    if (ADD) {
#pragma unroll
        for (int j = 0; j < NR / 8; j++)
            asm volatile("ldmatrix.sync.aligned.m8n8.x4.trans.shared.b16 {%0,%1,%2,%3}, [%4];"
                         : "=r"(p[4 * j]), "=r"(p[4 * j + 1]), "=r"(p[4 * j + 2]), "=r"(p[4 * j + 3])
                         : "r"(addr + j * 2048)
                         : "memory");
    }
#pragma unroll
    for (int k = 0; k < NR / 2; k++)
        p[k] = ADD ? pack_bf16(d[2 * k] + __uint_as_float(p[k] << 16), d[2 * k + 1] + __uint_as_float(p[k] & 0xffff0000u))
                   : pack_bf16(d[2 * k], d[2 * k + 1]);
#pragma unroll
    for (int j = 0; j < NR / 8; j++) {
        stsm4t(addr + j * 2048, p[4 * j], p[4 * j + 1], p[4 * j + 2], p[4 * j + 3]);
        if (SIG && j == SIGJ) nb_arrive<NB_L, 160>();
    }
}

struct TrueT { static constexpr bool value = true; };
struct FalseT { static constexpr bool value = false; };

template <int V>
struct IntT { static constexpr int value = V; };

__device__ __forceinline__ uint32_t get_item(uint32_t sb, int it, uint32_t dl) {
    mbar_wait(sb + BAR_ITEM + it * 8, 0, dl);
    return lds_u(sb + OFF_ITEM + it * 4);
}
__device__ __forceinline__ uint32_t get_item_warp(uint32_t sb, int it, uint32_t dl) {
    return __shfl_sync(0xffffffffu, get_item(sb, it, dl), 0);
}

struct Ring {
    uint32_t slot, ph, dl;
    __device__ __forceinline__ void adv(uint32_t k) {
        slot += k;
        if (slot >= NSLOT) { slot -= NSLOT; ph ^= 1; }
    }
};

template <int K>
__device__ __forceinline__ void qk_step(float (&s)[80], uint32_t loK, uint32_t loQ) {
    wgmma<0, 0, HI_SW128, K != 0, HI_KV>(s, loK + (K >> 2) * 64 + (K & 3) * 2, loQ + (K >> 2) * (XS >> 4) + (K & 3) * 2);
}
template <int K0, int K1>
__device__ __forceinline__ void qk_steps(float (&s)[80], uint32_t loK, uint32_t loQ) {
    if constexpr (K0 < K1) {
        qk_step<K0>(s, loK, loQ);
        qk_steps<K0 + 1, K1>(s, loK, loQ);
    }
}
__device__ __forceinline__ uint32_t add_bf2(uint32_t a, uint32_t b) {
    uint32_t r;
    asm("add.rn.bf16x2 %0, %1, %2;" : "=r"(r) : "r"(a), "r"(b));
    return r;
}
__device__ __forceinline__ uint32_t fma_bf2(uint32_t a, uint32_t b, uint32_t c) {
    uint32_t r;
    asm("fma.rn.bf16x2 %0, %1, %2, %3;" : "=r"(r) : "r"(a), "r"(b), "r"(c));
    return r;
}
template <int J>
__device__ __forceinline__ void exp_block(const float (&s)[80], uint32_t (&k)[40], uint32_t pa, float mref) {
    if constexpr (J < 10) {
#pragma unroll
        for (int i = 4 * J; i < 4 * J + 4; i++)
            k[i] = pack_bf16(ex2(fmaf(s[2 * i], SM_C, -mref)), ex2(fmaf(s[2 * i + 1], SM_C, -mref)));
#pragma unroll
        for (int i = 0; i < 4; i++)
            asm volatile("stmatrix.sync.aligned.m8n8.x1.trans.shared.b16 [%0], {%1};" ::"r"(((i & 1) ? pa ^ 16 : pa) + J * 2048 + (i >> 1) * 1024),
                         "r"(k[4 * J + i])
                         : "memory");
        exp_block<J + 1>(s, k, pa, mref);
    }
}
__device__ __forceinline__ void sum_block(const uint32_t (&k)[40], float (&l)[10], uint32_t lane) {
    const bool b4 = lane & 16, b3 = lane & 8;
    uint32_t ps[20], t[10];
#pragma unroll
    for (int j = 0; j < 20; j++) ps[j] = add_bf2(k[2 * j], k[2 * j + 1]);
#pragma unroll
    for (int j = 0; j < 10; j++)
        t[j] = add_bf2(b4 ? ps[2 * j + 1] : ps[2 * j], __shfl_xor_sync(0xffffffffu, b4 ? ps[2 * j] : ps[2 * j + 1], 16));
#pragma unroll
    for (int i = 0; i < 5; i++) {
        const uint32_t a = b3 ? t[i + 5] : t[i], b = __shfl_xor_sync(0xffffffffu, b3 ? t[i] : t[i + 5], 8);
        l[2 * i] += __uint_as_float(a << 16) + __uint_as_float(b << 16);
        l[2 * i + 1] += __uint_as_float(a & 0xffff0000u) + __uint_as_float(b & 0xffff0000u);
    }
}
template <bool ADD>
__device__ __forceinline__ void sum_store(const float (&l)[10], uint32_t lane, uint32_t lxa) {
    const bool b2 = lane & 4;
    float t[5];
#pragma unroll
    for (int i = 0; i < 5; i++) t[i] = ADD ? __uint_as_float(lds_u(lxa + i * 64)) : 0.f;
#pragma unroll
    for (int i = 0; i < 5; i++)
        sts_f(lxa + i * 64, t[i] + (b2 ? l[2 * i + 1] : l[2 * i]) + __shfl_xor_sync(0xffffffffu, b2 ? l[2 * i] : l[2 * i + 1], 4));
}

__device__ __forceinline__ void fallback_unit(const Params& P, uint32_t e, uint32_t tid) {
    const uint32_t lane = tid & 31, br = IT_BR(e), b = IT_B(e), h = IT_H0(e);
    const __nv_bfloat162* wq = (const __nv_bfloat162*)(P.pwq[br] + h * 192) + lane;
    const __nv_bfloat162* kp = (const __nv_bfloat162*)(P.pk[br] + (size_t)(b * 32 + h) * 512 * 192) + lane;
    const __nv_bfloat162* vp = (const __nv_bfloat162*)(P.pv[br] + (size_t)(b * 32 + h) * 512 * 192) + lane;
#pragma unroll 1
    for (uint32_t qi = 0; qi < 40; qi++) {
        const uint32_t q = 4 * qi + (tid >> 5);
        const __nv_bfloat16* xr = P.px[br] + (size_t)(b * 160 + q) * 640;
        float a[6] = {0.f, 0.f, 0.f, 0.f, 0.f, 0.f};
#pragma unroll 2
        for (int k = 0; k < 640; k++) {
            const float xv = __bfloat162float(xr[k]);
#pragma unroll
            for (int i = 0; i < 3; i++) {
                const float2 wv = __bfloat1622float2(wq[(size_t)k * 3072 + i * 32]);
                a[2 * i] = fmaf(xv, wv.x, a[2 * i]);
                a[2 * i + 1] = fmaf(xv, wv.y, a[2 * i + 1]);
            }
        }
#pragma unroll
        for (int i = 0; i < 6; i++) a[i] = __bfloat162float(__float2bfloat16(a[i]));
        auto score = [&](int key) {
            float d = 0.f;
#pragma unroll
            for (int i = 0; i < 3; i++) {
                const float2 kv = __bfloat1622float2(kp[key * 96 + i * 32]);
                d = fmaf(a[2 * i], kv.x, fmaf(a[2 * i + 1], kv.y, d));
            }
#pragma unroll
            for (int o = 16; o > 0; o >>= 1) d += __shfl_xor_sync(0xffffffffu, d, o);
            return d;
        };
        float m = -INFINITY, o[6] = {0.f, 0.f, 0.f, 0.f, 0.f, 0.f}, sum = 0.f;
#pragma unroll 1
        for (int n = 0; n < 1024; n++) {
            const int key = n & 511;
            const float d = score(key);
            if (n < 512) {
                m = fmaxf(m, d);
            } else {
                const float p = ex2((d - m) * SM_C);
                sum += p;
#pragma unroll
                for (int i = 0; i < 3; i++) {
                    const float2 vv = __bfloat1622float2(vp[key * 96 + i * 32]);
                    o[2 * i] = fmaf(p, vv.x, o[2 * i]);
                    o[2 * i + 1] = fmaf(p, vv.y, o[2 * i + 1]);
                }
            }
        }
        const float inv = __fdividef(1.f, sum);
        __nv_bfloat16* op = (__nv_bfloat16*)ostash(IT_SLOT(e), b) + (q >> 5) * 256 + 2 * ((q & 31) >> 3) + (q & 1);
#pragma unroll
        for (int i = 0; i < 6; i++) {
            const uint32_t d = (i >> 1) * 64 + 2 * lane + (i & 1);
            op[(d >> 3) * 1280 + (d & 7) * 32 + ((((q & 7) >> 1) ^ ((d & 7) >> 1)) << 3)] = __float2bfloat16(o[i] * inv);
        }
    }
}

struct PendO {
    uint32_t v[64];
    unsigned char* gp;
    static __device__ __forceinline__ uint32_t toff() {
        const uint32_t t = tid_now();
        return ((t >> 5) & 3) * 5120 + ((t >> 2) & 7) * 64 + (((t ^ (t >> 3)) & 3) << 4);
    }
    uint32_t pend, sig, bad;
    static __device__ __forceinline__ void scale(uint32_t& x, uint32_t hi, uint32_t lo) {
        asm("{\n.reg .b32 t;\nmul.rn.bf16x2 t, %0, %2;\nfma.rn.bf16x2 %0, %0, %1, t;\n}" : "+r"(x) : "r"(hi), "r"(lo));
    }
    template <int I, int OFF>
    __device__ __forceinline__ void put() {
        asm volatile("{\n.reg .pred p;\nsetp.ne.u32 p, %6, 0;\n@p st.global.v4.b32 [%0+%5], {%1,%2,%3,%4};\n}" ::"l"(gp), "r"(v[I]),
                     "r"(v[I + 1]), "r"(v[I + 2]), "r"(v[I + 3]), "n"(OFF), "r"(pend)
                     : "memory");
    }
    __device__ __forceinline__ void verdict(uint32_t sb, uint32_t W) {
        if (sig) {
            asm volatile("bar.sync %0, 160;" ::"r"(NB_VOTE + W) : "memory");
            bad = __any_sync(0xffffffffu, lds_u(sb + OFF_FB) != 0);
            pend = !bad;
        }
    }
    template <int W, int G, int H>
    __device__ __forceinline__ void half(uint32_t sb) {
        constexpr bool T2 = W == 0 ? G >= 3 : G < 3;
        constexpr int B = T2 ? 40 + 8 * (W == 0 ? G - 3 : G) : 0;
        const uint4 a = lds_u4(sb + OFF_LINV + G * 128 + H * 16 + (threadIdx.x & 3) * 32);
#pragma unroll
        for (int i = 2 * H; i < 8; i += 4) {
            scale(v[8 * G + i], a.x, a.y);
            scale(v[8 * G + i + 1], a.z, a.w);
            if (T2) {
                scale(v[B + i], a.x, a.y);
                scale(v[B + i + 1], a.z, a.w);
            }
        }
        if (H == 1) {
            put<8 * G, W * XS + G * 512>();
            put<8 * G + 4, W * XS + G * 512 + 2560>();
            if (T2) {
                put<B, 2 * XS + G * 512>();
                put<B + 4, 2 * XS + G * 512 + 2560>();
            }
            if (G == 4 && pend) nb_arrive<NB_ODONE, 288>();
        }
    }
    template <int W, int G>
    __device__ __forceinline__ void step(uint32_t sb) {
        half<W, G, 0>(sb);
        half<W, G, 1>(sb);
    }
    template <int W>
    __device__ __forceinline__ void flush(uint32_t sb) {
        step<W, 0>(sb);
        step<W, 1>(sb);
        step<W, 2>(sb);
        step<W, 3>(sb);
        step<W, 4>(sb);
    }
    __device__ __forceinline__ void clear() {
#pragma unroll
        for (int i = 0; i < 64; i++) v[i] = 0;
        gp = nullptr;
        pend = 0;
        sig = 0;
        bad = 0;
    }
};

__device__ __forceinline__ uint32_t stsm_off() {
    const uint32_t tid = tid_now(), lane = tid & 31;
    return (lane >> 4) * 1024 + (lane & 7) * 128 + (((((tid >> 4) & 6) + ((lane >> 3) & 1)) ^ (lane & 7)) << 4);
}
__device__ __forceinline__ void q_ahead(float (&q0)[80], uint32_t sb, const Ring& rn, uint32_t phm, bool valid) {
    if (valid) mbar_wait2(sb + BAR_RFULL + rn.slot * 8, rn.ph, sb + BAR_XFULL, phm & 1, rn.dl);
    const uint32_t a = ((((sb + OFF_RING) & 0x3ffff) >> 4) | LO_LBO1) + rn.slot * (SLOT >> 4);
    const uint32_t b = (((sb + OFF_R) & 0x3ffff) >> 4) | LO_LBO1;
    wg_fence();
    wgmma<1, 0, HI_SW128, false>(q0, a, b);
#pragma unroll
    for (int k = 1; k < 4; k++) wgmma<1, 0, HI_SW128, true>(q0, a + (k >> 1) * 768 + (k & 1) * 128, b + k * 2);
    wg_commit();
}
template <int W, int KK>
__device__ __forceinline__ void qproj(float (&q0)[80], float (&q1)[80], uint32_t sb, Ring& r, uint32_t pslot, uint32_t phm,
                                      PendO& po) {
    const uint32_t loR = (((sb + OFF_R) & 0x3ffff) >> 4) | LO_LBO1;
    const uint32_t loRing = (((sb + OFF_RING) & 0x3ffff) >> 4) | LO_LBO1;
    auto ready = [&](int k) {
        mbar_wait2(sb + BAR_RFULL + r.slot * 8, r.ph, sb + BAR_XFULL + (k % 5) * 8, ((phm >> (k % 5)) ^ (k / 5)) & 1, r.dl);
    };
    auto release = [&]() {
        if (KK > 0) {
            wg_wait<1>();
            mbar_arrive_warp(sb + BAR_REMPTY + pslot * 8);
            if (KK <= 5) mbar_arrive_warp(sb + (BAR_XEMPTY + (KK - 1) * 8));
        }
    };
    if (KK == 0 && W == 1) ready(0);
    if (W == 1 && KK == QHOLD) {
        if (QHOLD == 7) {
            wg_wait<0>();
            nb_arrive<NB_PDONE, 256>();
        }
        nb_sync<NB_SDONE, 256>();
    }
    const uint32_t a = loRing + r.slot * (SLOT >> 4) + (W == 0 ? 0 : 512), b = loR + (KK % 5) * (XS >> 4);
    wg_fence();
    constexpr bool T0 = W == 1 || KK > 0;
    if (T0) wgmma<1, 0, HI_SW128, KK != 0>(q0, a, b);
    if (W == 0) wgmma<1, 0, HI_SW128, KK != 0 ? 1 : 2>(q1, a + 256, b);
#pragma unroll
    for (int k = 1; k < 4; k++) {
        if (T0) wgmma<1, 0, HI_SW128, true>(q0, a + (k >> 1) * 768 + (k & 1) * 128, b + k * 2);
        if (W == 0) wgmma<1, 0, HI_SW128, true>(q1, a + 256 + (k >> 1) * 768 + (k & 1) * 128, b + k * 2);
    }
    wg_commit();
    const uint32_t cslot = r.slot;
    r.adv(1);
    if (W == 0 || KK < QHOLD) release();
    constexpr int QST = W == 0 ? QST0 : QST1;
    if (KK == QST) {
        po.verdict(sb, W);
        po.template half<W, 0, 0>(sb);
    }
    if (KK < 9) ready(KK + 1);
    if (W == 1 && KK >= QHOLD) release();
    if (W == 1 && KK == 7 && QHOLD > 7) nb_arrive<NB_PDONE, 256>();
    if (KK == QST) po.template half<W, 0, 1>(sb);
    if constexpr (KK > QST && KK < QST + 5) po.template step<W, KK - QST>(sb);
    if constexpr (KK < (W == 0 ? 7 : 9)) {
        qproj<W, KK + 1>(q0, q1, sb, r, cslot, phm, po);
    } else if constexpr (W == 1) {
        const uint32_t sta = sb + OFF_R + 2 * XS + stsm_off();
        wg_wait<0>();
        reg_fence(q0);
        store_tile_t<false, true>(q0, sta);
        mbar_arrive_warp(sb + BAR_REMPTY + cslot * 8);
    } else {
        const uint32_t s8 = r.slot, a8 = loRing + s8 * (SLOT >> 4);
        wg_fence();
#pragma unroll
        for (int k = 0; k < 4; k++) wgmma<1, 0, HI_SW128, true>(q0, a8 + (k >> 1) * 768 + (k & 1) * 128, loR + 3 * (XS >> 4) + k * 2);
        r.adv(1);
        ready(9);
        const uint32_t s9 = r.slot, a9 = loRing + s9 * (SLOT >> 4);
        r.adv(1);
        wg_fence();
#pragma unroll
        for (int k = 0; k < 4; k++) wgmma<1, 0, HI_SW128, true>(q0, a9 + (k >> 1) * 768 + (k & 1) * 128, loR + 4 * (XS >> 4) + k * 2);
        wg_commit();
        wg_wait<1>();
        mbar_arrive_warp(sb + BAR_REMPTY + cslot * 8);
        wg_fence();
#pragma unroll
        for (int k = 0; k < 8; k++)
            wgmma<1, 0, HI_SW128, true>(q1, (k < 4 ? a8 : a9) + 256 + ((k >> 1) & 1) * 768 + (k & 1) * 128,
                                        loR + (3 + (k >> 2)) * (XS >> 4) + (k & 3) * 2);
        wg_commit();
        nb_arrive<NB_SDONE, 256>();
        if (K0POS) sts_u(sb + OFF_GM + 4, r.slot);
        if (K0POS == 1) mbar_wait(sb + BAR_RFULL + r.slot * 8, r.ph, r.dl);
        nb_sync<NB_PDONE, 256>();
        wg_wait<1>();
        reg_fence(q0);
        const uint32_t sta = sb + OFF_R + stsm_off();
        store_tile_t(q0, sta);
        if (!K0POS) sts_u(sb + OFF_GM + 4, r.slot);
        if (K0POS == 0 || K0POS == 2) mbar_wait(sb + BAR_RFULL + r.slot * 8, r.ph, r.dl);
        wg_wait<0>();
        reg_fence(q1);
        mbar_arrive_warp(sb + BAR_REMPTY + s8 * 8);
        mbar_arrive_warp(sb + BAR_REMPTY + s9 * 8);
        store_tile_t(q1, sta + XS);
        if (K0POS == 3) mbar_wait(sb + BAR_RFULL + r.slot * 8, r.ph, r.dl);
    }
}

template <int NR>
__device__ __forceinline__ void opack(const float (&o)[NR], uint32_t* v) {
#pragma unroll
    for (int g = 0; g < NR / 16; g++)
#pragma unroll
        for (int hh = 0; hh < 2; hh++)
#pragma unroll
            for (int t = 0; t < 4; t++) v[8 * g + 4 * hh + t] = pack_bf16(o[16 * g + 4 * t + 2 * hh], o[16 * g + 4 * t + 2 * hh + 1]);
}

template <bool IS_S>
__device__ __forceinline__ void op_item(uint32_t e, uint32_t sb, Ring& r, uint32_t& phm) {
    constexpr int T0 = IS_S ? 0 : 2;
    constexpr uint32_t BOFF = IS_S ? (3 * 512) >> 4 : 0;
    const uint32_t loRing = (((sb + OFF_RING) & 0x3ffff) >> 4) | LO_LBO1;
    const uint32_t loO = (((sb + OFF_R) & 0x3ffff) >> 4) | LO_OST;
    float c0[80], c1[80], c2[IS_S ? 32 : 48];
    const int T = 3 * (IT_H1(e) - IT_H0(e));
    uint32_t xs = 0;
    auto step = [&](auto first, auto half) {
        constexpr bool F = decltype(first)::value;
        constexpr uint32_t hf = decltype(half)::value;
        if (hf == 0) {
            mbar_wait(sb + BAR_XFULL + xs * 8, (phm >> xs) & 1, r.dl);
            phm ^= 1u << xs;
        }
        mbar_wait(sb + BAR_RFULL + r.slot * 8, r.ph, r.dl);
        const uint32_t a = loRing + r.slot * (SLOT >> 4), b = loO + xs * (XS >> 4) + hf * 640;
        wg_fence();
        wgmma<1, 1, HI_OST, !F>(c0, a + T0 * 128, b);
        wgmma<1, 1, HI_OST, !F>(c1, a + T0 * 128 + 128, b);
        wgmma<1, 1, HI_OST, !F>(c2, a + 512, b + BOFF);
        wgmma<1, 1, HI_OST, true>(c0, a + 640 + T0 * 128, b + 320);
        wgmma<1, 1, HI_OST, true>(c1, a + 640 + T0 * 128 + 128, b + 320);
        wgmma<1, 1, HI_OST, true>(c2, a + 640 + 512, b + 320 + BOFF);
        wg_commit();
    };
    step(TrueT{}, IntT<0>{});
#pragma unroll 1
    for (int t = 1;; t++) {
        uint32_t pslot = r.slot;
        r.adv(1);
        step(FalseT{}, IntT<1>{});
        wg_wait<1>();
        mbar_arrive_warp(sb + BAR_REMPTY + pslot * 8);
        if (t == T) break;
        pslot = r.slot;
        const uint32_t pxs = xs;
        r.adv(1);
        if (++xs == 5) xs = 0;
        step(FalseT{}, IntT<0>{});
        wg_wait<1>();
        mbar_arrive_warp(sb + BAR_REMPTY + pslot * 8);
        mbar_arrive_warp_if(sb + BAR_XEMPTY + pxs * 8, t + 4 < T);
    }
    wg_wait<0>();
    reg_fence(c0);
    reg_fence(c1);
    reg_fence(c2);
    mbar_arrive_warp(sb + BAR_REMPTY + r.slot * 8);
    r.adv(1);
    nb_sync<NB_OPEND, 256>();
    const uint32_t sta = sb + OFF_R + stsm_off();
    store_tile_t(c0, sta + T0 * XS);
    store_tile_t(c1, sta + (T0 + 1) * XS);
    store_tile_t(c2, sta + 4 * XS + (IS_S ? 96 * 128 : 0));
    fence_async_smem();
    nb_arrive<NB_ODONE, 288>();
}

__device__ __forceinline__ void on_item(uint32_t W, uint32_t e, uint32_t sb, Ring& r, uint32_t& phm) {
    const uint32_t loRing = (((sb + OFF_RING) & 0x3ffff) >> 4) | LO_LBO1;
    const uint32_t loO = (((sb + OFF_R) & 0x3ffff) >> 4) | LO_OST;
    float c[80];
    const int T = 3 * (IT_H1(e) - IT_H0(e));
    uint32_t xs = 0;
    auto step = [&](auto first) {
        constexpr bool F = decltype(first)::value;
        mbar_wait2(sb + BAR_XFULL + xs * 8, (phm >> xs) & 1, sb + BAR_RFULL + r.slot * 8, r.ph, r.dl);
        phm ^= 1u << xs;
        const uint32_t a = loRing + r.slot * (SLOT >> 4) + W * 256, b = loO + xs * (XS >> 4);
        wg_fence();
        wgmma<1, 1, HI_OST, !F>(c, a, b);
#pragma unroll
        for (int k = 1; k < 4; k++) wgmma<1, 1, HI_OST, true>(c, a + (k >> 1) * 512 + (k & 1) * 128, b + k * 320);
        wg_commit();
    };
    step(TrueT{});
#pragma unroll 1
    for (int t = 1; t < T; t++) {
        const uint32_t pslot = r.slot, pxs = xs;
        r.adv(1);
        if (++xs == 5) xs = 0;
        step(FalseT{});
        wg_wait<1>();
        mbar_arrive_warp(sb + BAR_REMPTY + pslot * 8);
        mbar_arrive_warp_if(sb + BAR_XEMPTY + pxs * 8, t + 2 < T);
    }
    xs += 1 + W;
    if (xs >= 5) xs -= 5;
    mbar_wait(sb + BAR_XFULL + xs * 8, (phm >> xs) & 1, r.dl);
    wg_wait<0>();
    reg_fence(c);
    store_tile_t<true>(c, sb + OFF_R + xs * XS + stsm_off());
    fence_async_smem();
    nb_arrive<NB_ODONE, 288>();
}

template <int W>
__device__ __forceinline__ uint32_t qa_item(uint32_t e, uint32_t sb, Ring& r, uint32_t phm, PendO& po, float (&q0)[80],
                                            float (&oa)[80], int it) {
    const uint32_t loR = (((sb + OFF_R) & 0x3ffff) >> 4) | LO_LBO1;
    const uint32_t loRing = (((sb + OFF_RING) & 0x3ffff) >> 4) | LO_LBO1;
    qproj<W, 0>(q0, oa, sb, r, 0, phm, po);
    fence_async_smem();
    TSD(W, 1);
    float s[80], ob[W == 0 ? 32 : 48], l[10];
    if (W == 1) {
        nb_arrive<NB_Q2, 256>();
        zero(oa);
        zero(ob);
        reg_fence(oa);
        reg_fence(ob);
    }
    const uint32_t lane = tid_now() & 31, sta = sb + OFF_R + stsm_off();
    auto pv = [&](auto first, uint32_t buf, bool wait = true) {
        constexpr bool F = decltype(first)::value;
        if (wait) mbar_wait(sb + BAR_RFULL + r.slot * 8, r.ph, r.dl);
        const uint32_t a = loRing + r.slot * (SLOT >> 4), b = loR + (3 + buf) * (XS >> 4);
        wg_fence();
        wgmma<1, 0, HI_SW128, F ? 2 : 1, HI_KV>(oa, a + W * 64, b);
        wgmma<1, 0, HI_SW128, !F, HI_KV>(ob, a + 128, b + (W == 0 ? (96 * 128) >> 4 : 0));
#pragma unroll
        for (int k = 1; k < 4; k++) {
            wgmma<1, 0, HI_SW128, true, HI_KV>(oa, a + W * 64 + k * 384, b + k * 2);
            wgmma<1, 0, HI_SW128, true, HI_KV>(ob, a + 128 + k * 384, b + (W == 0 ? (96 * 128) >> 4 : 0) + k * 2);
        }
        wg_commit();
    };
    zero(l);
    float mref;
    uint32_t kslot, vslot, nx = 0;
    auto tail = [&](auto first, int i) {
        constexpr bool rel_other = !decltype(first)::value;
        uint32_t ps[40];
        exp_block<0>(s, ps, sta + (3 + W) * XS, mref);
        if (rel_other) {
            wg_wait<0>();
            mbar_arrive_warp(sb + BAR_REMPTY + vslot * 8);
            if (W == 1) mbar_arrive_warp_if(sb + BAR_XEMPTY + 24, i == 3);
        }
        fence_async_smem();
        nb_arrive<NB_PFULL + W, 256>();
        TSD(W, 6 + 5 * i);
        if (W == 1) {
            if (XLATE >= 2) mbar_arrive_warp_if<2>(sb + BAR_XEMPTY + 8, i == 3);
            if (XLATE >= 1) mbar_arrive_warp_if<2>(sb + BAR_XEMPTY + 16, i == 3);
        }
        if (rel_other || !PV0FIRST) {
            mbar_wait(sb + BAR_RFULL + r.slot * 8, r.ph, r.dl);
            sum_block(ps, l, lane);
        }
        if (W == 0 && i == 3) nx = get_item_warp(sb, it + 1, r.dl);
        TSD(W, 7 + 5 * i);
        if (LASTORD && W == 0 && i == 3) nb_sync<NB_PDONE, 256>();
        else nb_sync<NB_W + W, 128>();
        pv(first, W, !rel_other && PV0FIRST);
        if (!rel_other && PV0FIRST) sum_block(ps, l, lane);
        TSD(W, 8 + 5 * i);
    };
    if (W == 0) {
        nb_sync<NB_QK, 160>();
        TSD(W, 2);
        wg_fence();
        qk_steps<0, 8>(s, loRing + r.slot * (SLOT >> 4), loR);
        nb_sync<NB_Q2, 256>();
        qk_steps<8, 12>(s, loRing + r.slot * (SLOT >> 4), loR);
        wg_commit();
        nb_arrive<NB_Q01, 256>();
        TSD(W, 4);
        nb_sync<NB_REF, 160>();
        mref = __uint_as_float(lds_u(sb + OFF_GM));
        wg_wait<0>();
        reg_fence(s);
        mbar_arrive_warp<2>(sb + BAR_REMPTY + r.slot * 8);
        r.adv(2);
        TSD(W, 5);
        tail(TrueT{}, 0);
    } else {
        nb_sync<NB_Q01, 256>();
    }
#pragma unroll 1
    for (int i = (W == 0 ? 1 : 0); i < 4; i++) {
        const uint32_t pvslot = r.slot;
        r.adv(1);
        kslot = r.slot;
        mbar_wait(sb + BAR_RFULL + r.slot * 8, r.ph, r.dl);
        wg_fence();
        qk_steps<0, 4>(s, loRing + r.slot * (SLOT >> 4), loR);
        if (W == 1) wg_commit();
        qk_steps<4, 12>(s, loRing + r.slot * (SLOT >> 4), loR);
        wg_commit();
        wg_wait<1>();
        if (W == 1) mbar_arrive_warp_if(sb + BAR_XEMPTY + 0, i == 3);
        mbar_arrive_warp_if(sb + BAR_REMPTY + pvslot * 8, W == 0 || i > 0);
        r.adv(1);
        vslot = r.slot;
        TSD(W, 4 + 5 * i);
        if (VEARLY) mbar_wait(sb + BAR_RFULL + r.slot * 8, r.ph, r.dl);
        nb_sync<NB_PFULL + (W ^ 1), 256>();
        pv(FalseT{}, W ^ 1, !VEARLY);
        if (LASTORD && W == 1 && i == 3) nb_arrive<NB_PDONE, 256>();
        if (W == 1) mref = __uint_as_float(lds_u(sb + OFF_GM));
        wg_wait<1>();
        reg_fence(s);
        mbar_arrive_warp<2>(sb + BAR_REMPTY + kslot * 8);
        if (W == 0) mbar_arrive_warp_if(sb + BAR_XEMPTY + 0, i == 3);
        if (W == 1) {
            if (XLATE < 2) mbar_arrive_warp_if<2>(sb + BAR_XEMPTY + 8, i == 3);
            if (XLATE < 1) mbar_arrive_warp_if<2>(sb + BAR_XEMPTY + 16, i == 3);
        }
        r.adv(W == 1 && i == 3 ? 1 : 2);
        TSD(W, 5 + 5 * i);
        tail(FalseT{}, i);
    }
    if (W == 1) nx = get_item_warp(sb, it + 1, r.dl);
    if (W == 0) {
        Ring rn = r;
        rn.adv(2);
        q_ahead(q0, sb, rn, phm, IT_TYPE(nx) == IT_QA);
        TSD(W, 25);
    }
    const uint32_t w = (tid_now() >> 5) & 3;
    const uint32_t lxa = sb + OFF_LX + w * 640 + (((lane & 8) ? 80 : 0) + ((lane >> 1) & 8) + 2 * (lane & 3) + ((lane >> 2) & 1)) * 4;
    po.gp = ostash(IT_SLOT(e), IT_B(e)) + po.toff();
    po.sig = 1;
    if (W == 0) {
        sum_store<false>(l, lane, lxa);
        nb_arrive<NB_LX, 256>();
        wg_wait<1>();
        mbar_arrive_warp(sb + BAR_REMPTY + r.slot * 8);
        mbar_arrive_warp(sb + BAR_XEMPTY + 24);
        r.adv(1);
        if (VEARLY) mbar_wait(sb + BAR_RFULL + r.slot * 8, r.ph, r.dl);
        nb_sync<NB_PFULL + 1, 256>();
        pv(FalseT{}, 1, !VEARLY);
    } else {
        nb_sync<NB_LX, 256>();
        sum_store<true>(l, lane, lxa);
        nb_arrive<NB_L, 160>();
    }
    TSD(W, 24);
    wg_wait<0>();
    reg_fence(oa);
    reg_fence(ob);
    mbar_arrive_warp(sb + BAR_REMPTY + r.slot * 8);
    mbar_arrive_warp(sb + BAR_XEMPTY + 32);
    r.adv(1);
    opack(ob, po.v + 40);
    opack(oa, po.v);
    return nx;
}

template <int W>
__device__ __forceinline__ uint32_t qa_run(uint32_t e, uint32_t sb, Ring& r, uint32_t phm, PendO& po, int& it) {
    float q0[80], oa[80];
    if (W == 0) {
        zero(oa);
        q_ahead(q0, sb, r, phm, true);
        wg_wait<0>();
    }
#pragma unroll 1
    do {
        TS(W, 0);
        if (W == 0) TS_ITEM(e);
        e = qa_item<W>(e, sb, r, phm, po, q0, oa, it);
        TS(W, 31);
        it++;
    } while (IT_TYPE(e) == IT_QA && !po.bad);
    if (W == 0) {
#pragma unroll
        for (int i = 56; i < 64; i++) po.v[i] = 0;
    }
    return e;
}

__device__ __forceinline__ void consumer(const Params& P, uint32_t W, uint32_t sb, uint32_t dl) {
    int it = 0;
    Ring r{0, 0, dl};
    uint32_t phm = 0;
    uint32_t e = get_item_warp(sb, 0, dl);
#pragma unroll 1
    while (true) {
        if (IT_TYPE(e) == IT_QA) {
            PendO po;
            po.clear();
            e = W == 0 ? qa_run<0>(e, sb, r, phm, po, it) : qa_run<1>(e, sb, r, phm, po, it);
#pragma unroll 1
            for (int m = po.bad ? 2 : 1; m > 0; m--) {
                if (m == 1) {
                    po.verdict(sb, W);
                    if (W == 0) po.flush<0>(sb);
                    else po.flush<1>(sb);
                }
                if (po.bad) {
                    if (W == 0) fallback_unit(P, lds_u(sb + OFF_ITEM + (it - m) * 4), tid_now() & 127);
                    __syncwarp();
                    nb_sync<NB_ODONE, 288>();
                }
            }
        }
        if (e == 0) break;
        if (IT_TYPE(e) == IT_QA) continue;
        TS(W, 0);
        if (W == 0) TS_ITEM(e);
        if (IT_TYPE(e) == IT_ON) on_item(W, e, sb, r, phm);
        else if (W == 0) op_item<true>(e, sb, r, phm);
        else op_item<false>(e, sb, r, phm);
        TS(W, 31);
        e = get_item_warp(sb, ++it, dl);
    }
    TS_DUMP(W);
}

__global__ void __cluster_dims__(2, 1, 1) __launch_bounds__(384, 1) fused_kernel(const __grid_constant__ Params P) {
    extern __shared__ __align__(1024) unsigned char smem_raw[];
    const uint32_t sb = (uint32_t)__cvta_generic_to_shared(smem_raw);
    const uint32_t warp = __shfl_sync(0xffffffffu, threadIdx.x >> 5, 0), wgid = warp >> 2;
    const uint32_t cta = blockIdx.x;
    const uint32_t dl = deadline();

    if (threadIdx.x == 128) {
#pragma unroll
        for (int i = 0; i < NSLOT; i++) {
            mbar_init(sb + BAR_RFULL + i * 8, 1);
            mbar_init(sb + BAR_REMPTY + i * 8, 8);
            mbar_init(sb + BAR_XFULL + i * 8, 1);
            mbar_init(sb + BAR_XEMPTY + i * 8, 8);
        }
        asm volatile("fence.mbarrier_init.release.cluster;" ::: "memory");
        fence_async_smem();
    } else if (threadIdx.x == 160) {
#pragma unroll
        for (int i = 0; i < NSLOT + MAXI; i++) mbar_init(sb + BAR_PRDY + i * 8, 1);
        asm volatile("fence.mbarrier_init.release.cluster;" ::: "memory");
    } else if (threadIdx.x == 0) {
        sts_u(sb + OFF_ITEM, P.cl[cta >> 1].items[0] ? P.cl[cta >> 1].items[0] + 8 * (cta & 1) : 0);
        sts_u(sb + OFF_FB, P.cl[cta >> 1].delay);
    } else if (threadIdx.x == 64) {
        if (sb & 1023) __trap();
        asm volatile("prefetch.tensormap [%0];" ::"l"(&P.wq[0]) : "memory");
        asm volatile("prefetch.tensormap [%0];" ::"l"(&P.x[0]) : "memory");
    }
    __syncthreads();
    {
        const int it = 0;
        if (wgid == 1) TS(0, 30);
    }
    asm volatile("barrier.cluster.arrive.relaxed.aligned;" ::: "memory");
    if (warp < 3) {
        const uint32_t e = __shfl_sync(0xffffffffu, lds_u(sb + OFF_ITEM), 0), d = lds_u(sb + OFF_FB);
        const uint64_t pol = mkpol<POL_W>();
        const bool isx = warp == 1, lead = (threadIdx.x & 31) == 0;
        uint32_t t0, t1;
        asm volatile("mov.u32 %0, %%clock;" : "=r"(t0));
        do {
            asm volatile("mov.u32 %0, %%clock;" : "=r"(t1));
        } while (t1 - t0 < d);
        __syncwarp();
#pragma unroll 1
        for (int n = 0; n < (e ? NSLOT : 0); n++) {
            const uint32_t bar = sb + (isx ? BAR_XFULL : BAR_RFULL) + n * 8;
            if (lead) {
                if (warp < 2) mbar_expect(bar, isx ? XS : SLOT);
                tma3(sb + (isx ? OFF_R + n * XS : OFF_RING + n * SLOT + warp * (SLOT / 4)), isx ? &P.x[0] : &P.wq[0],
                     isx ? IT_B(e) * 160 : n * 64 + warp * 16, isx ? n : IT_H0(e) * 3, bar, pol);
            }
        }
        if (threadIdx.x == 0) asm volatile("mbarrier.arrive.shared::cta.b64 _, [%0];" ::"r"(sb + BAR_ITEM) : "memory");
        __syncwarp();
    }

    if (wgid == 0) {
        asm volatile("setmaxnreg.dec.sync.aligned.u32 24;");
        if (warp == 0) {
            const bool lead = threadIdx.x == 0;
            const uint64_t pol_first = mkpol<1>(), pol_norm = mkpol<POL_W>();
            uint32_t e = __shfl_sync(0xffffffffu, lds_u(sb + OFF_ITEM), 0);
            asm volatile("barrier.cluster.wait.aligned;" ::: "memory");
            unsigned int* const ticket = &g_ticket[next_epoch(0) & 1];
            const uint32_t rank = cta & 1;
            uint32_t peer;
            asm volatile("mapa.shared::cluster.u32 %0, %1, %2;" : "=r"(peer) : "r"(sb), "r"(rank ^ 1));
            Ring r{0, 0, dl};
            uint32_t pm = 0;
            auto load_w = [&](const CUtensorMap* m, int row, int blk, uint32_t half_bytes) {
                mbar_wait(sb + BAR_REMPTY + r.slot * 8, r.ph, dl);
                if (lead) {
                    mbar_expect(sb + BAR_RFULL + r.slot * 8, 2 * half_bytes);
                    asm volatile("mbarrier.arrive.shared::cluster.b64 _, [%0];" ::"r"(peer + BAR_PRDY + r.slot * 8) : "memory");
                }
                mbar_wait(sb + BAR_PRDY + r.slot * 8, (pm >> r.slot) & 1, dl);
                pm ^= 1u << r.slot;
                if (lead) tma3_mc(sb + OFF_RING + r.slot * SLOT + rank * half_bytes, m, row, blk, sb + BAR_RFULL + r.slot * 8, pol_norm);
                r.adv(1);
            };
#pragma unroll 1
            for (int it = 0; e != 0; it++) {
                uint32_t nx = 0, tk = 0;
                if (rank == 0 && IT_TYPE(e) != IT_ON && it + 2 < MAXI) nx = it + 1 < NSTAT ? P.cl[cta >> 1].items[it + 1] : IT_DYN;
                const uint32_t br = IT_BR(e);
                if (IT_TYPE(e) == IT_QA) {
                    const uint32_t h = IT_H0(e);
#pragma unroll 1
                    for (int kk = it ? 0 : NSLOT; kk < 10; kk++) load_w(&P.wq[br], kk * 64 + rank * 32, h * 3, SLOT / 2);
                    const int grp0 = (IT_B(e) * 32 + h) * 64;
#pragma unroll 1
                    for (int n = 0; n < 16; n++) {
                        if (n == 13 && nx == IT_DYN && lead) tk = atomicAdd(ticket, 1);
                        const bool isv = n == 15 || (n > 0 && !(n & 1));
                        const int j = n == 15 ? 7 : isv ? (n - 2) >> 1 : (n + 1) >> 1;
                        mbar_wait(sb + BAR_REMPTY + r.slot * 8, r.ph, dl);
                        if (lead) {
                            mbar_expect(sb + BAR_RFULL + r.slot * 8, SLOT);
                            asm volatile(
                                "cp.async.bulk.tensor.4d.shared::cluster.global.mbarrier::complete_tx::bytes.L2::cache_hint"
                                " [%0], [%1, {%3,%3,%3,%4}], [%2], %5;" ::"r"(sb + OFF_RING + r.slot * SLOT),
                                "l"(isv ? &P.v[br] : &P.k[br]), "r"(sb + BAR_RFULL + r.slot * 8), "r"(0), "r"(grp0 + j * 8), "l"(pol_first)
                                : "memory");
                        }
                        r.adv(1);
                    }
                } else {
                    const bool wide = IT_TYPE(e) == IT_OP;
                    const int step = wide ? 32 : 64, r1 = IT_H1(e) * 192;
#pragma unroll 1
                    for (int row = IT_H0(e) * 192 + rank * (step >> 1); row < r1; row += step)
                        load_w(wide ? &P.wo[br] : &P.won[br], row, IT_HALF(e) * (wide ? 5 : 2), wide ? XS / 2 : 8192);
                    if (nx == IT_DYN && lead) tk = atomicAdd(ticket, 1);
                }
                if (rank == 0) {
                    if (nx == IT_DYN) {
                        tk = __shfl_sync(0xffffffffu, tk, 0);
                        nx = tk < P.nlist ? P.list[tk] : 0;
                    }
                    e = nx;
                    if (lead) {
                        asm volatile("st.async.weak.shared::cluster.mbarrier::complete_tx::bytes.b32 [%0], %1, [%2];" ::"r"(
                                         peer + OFF_ITEM + 4 + it * 4),
                                     "r"(e ? e + 8 : 0), "r"(peer + BAR_ITEM + 8 + it * 8)
                                     : "memory");
                        sts_u(sb + OFF_ITEM + 4 + it * 4, e);
                        asm volatile("mbarrier.arrive.shared::cta.b64 _, [%0];" ::"r"(sb + BAR_ITEM + 8 + it * 8) : "memory");
                    }
                } else {
                    if (lead) mbar_expect(sb + BAR_ITEM + 8 + it * 8, 4);
                    e = get_item_warp(sb, it + 1, dl);
                }
            }
        } else if (warp == 1) {
            const uint64_t pol_norm = mkpol<POL_X>(), pol_o = mkpol<POL_O>();
            const bool lead = threadIdx.x == 32;
            uint32_t phm = 0, epoch = 0;
#pragma unroll 1
            for (int it = 0;; it++) {
                const uint32_t e = get_item_warp(sb, it, dl);
                if (it == 1 || (it == 0 && e == 0)) epoch = next_epoch(1);
                if (e == 0) break;
                const uint32_t br = IT_BR(e);
                uint32_t xs = 0;
                auto acquire = [&]() {
                    mbar_wait(sb + BAR_XEMPTY + xs * 8, (phm >> xs) & 1, dl);
                    phm ^= 1u << xs;
                    if (lead) mbar_expect(sb + BAR_XFULL + xs * 8, XS);
                };
                if (IT_TYPE(e) == IT_QA) {
#pragma unroll 1
                    for (int kk = it ? 0 : 5; kk < 10; kk++) {
                        acquire();
                        if (lead) tma3(sb + OFF_R + xs * XS, &P.x[br], IT_B(e) * 160, kk, sb + BAR_XFULL + xs * 8, pol_norm);
                        if (++xs == 5) xs = 0;
                    }
                } else {
                    const unsigned int* fp = g_flag + (br * 16 + IT_B(e)) * 64 + (threadIdx.x & 31);
                    uint32_t hm = 0, pm = 0;
                    auto poll = [&](uint32_t hneed, uint32_t pneed) {
                        if ((hm & hneed) == hneed && (pm & pneed) == pneed) return;
                        uint32_t n = 0;
                        do {
                            uint32_t a, b;
                            asm volatile("ld.acquire.gpu.global.u32 %0, [%2];\nld.acquire.gpu.global.u32 %1, [%2+128];"
                                         : "=r"(a), "=r"(b) : "l"(fp) : "memory");
                            hm = __ballot_sync(0xffffffffu, a == epoch);
                            pm = __ballot_sync(0xffffffffu, b == epoch);
                            if (++n > 0x1000000) __trap();
                        } while ((hm & hneed) != hneed || (pm & pneed) != pneed);
                        __syncwarp();
                        asm volatile("fence.proxy.async;" ::: "memory");
                    };
#pragma unroll 1
                    for (uint32_t h = IT_H0(e); h < IT_H1(e); h++) {
                        poll(1u << h, 0);
                        const unsigned char* src = ostash(P.slot[br * 32 + h], IT_B(e));
#pragma unroll 1
                        for (int t = 0; t < 3; t++) {
                            acquire();
                            if (lead) bulk_load(sb + OFF_R + xs * XS, src + t * XS, XS, sb + BAR_XFULL + xs * 8, pol_o);
                            if (++xs == 5) xs = 0;
                        }
                        if (IT_TYPE(e) == IT_OP && h >= 1) {
                            const uint32_t x1 = xs == 4 ? 0 : xs + 1;
                            mbar_wait(sb + BAR_XFULL + xs * 8, (phm >> xs) & 1, dl);
                            mbar_wait(sb + BAR_XFULL + x1 * 8, (phm >> x1) & 1, dl);
                            if (lead)
                                asm volatile("st.relaxed.gpu.global.u32 [%0], %1;" ::"l"(fp + 34 + IT_HALF(e)), "r"(epoch * 64 + h) : "memory");
                        }
                    }
                    if (IT_TYPE(e) == IT_ON) {
                        poll(0, IT_HALF(e) < 2 ? 1 : IT_HALF(e) == 2 ? 3 : 2);
#pragma unroll 1
                        for (uint32_t tile = 2 * IT_HALF(e); tile < 2 * IT_HALF(e) + 2; tile++) {
                            acquire();
                            if (lead)
                                asm volatile(
                                    "cp.async.bulk.tensor.5d.shared::cluster.global.mbarrier::complete_tx::bytes [%0], [%1, {%3,%5,%5,%5,%4}], [%2];" ::"r"(
                                        sb + OFF_R + xs * XS),
                                    "l"(&P.out), "r"(sb + BAR_XFULL + xs * 8), "r"(br * 640 + tile * 64), "r"(IT_B(e) * 5), "r"(0)
                                    : "memory");
                            if (++xs == 5) xs = 0;
                        }
                    }
                }
            }
        } else if (warp == 2) {
            asm volatile("barrier.cluster.wait.aligned;" ::: "memory");
            const uint32_t epoch = next_epoch(2);
            if (cta == 0) g_ticket[(epoch + 1) & 1] = 0;
#pragma unroll 1
            for (int it = 0;; it++) {
                const uint32_t e = get_item_warp(sb, it, dl);
                if (e == 0) break;
                nb_sync<NB_ODONE, 288>();
                if (threadIdx.x == 64) {
                    const uint32_t bb = IT_BR(e) * 16 + IT_B(e);
                    if (IT_TYPE(e) != IT_QA) {
                        const bool wide = IT_TYPE(e) == IT_OP;
                        if (wide)
                            asm volatile("st.relaxed.gpu.global.u32 [%0], %1;" ::"l"(&g_flag[bb * 64 + 34 + IT_HALF(e)]),
                                         "r"(epoch * 64 + IT_H1(e))
                                         : "memory");
                        const int cc0 = IT_BR(e) * 640 + IT_HALF(e) * (wide ? 320 : 128);
                        uint32_t xs = wide ? 0 : (3 * (IT_H1(e) - IT_H0(e))) % 5;
#pragma unroll 1
                        for (int m = 0; m < (wide ? 5 : 2); m++) {
                            asm volatile("cp.async.bulk.tensor.5d.global.shared::cta.bulk_group [%0, {%2,%4,%4,%4,%3}], [%1];" ::"l"(&P.out),
                                         "r"(sb + OFF_R + xs * XS), "r"(cc0 + m * 64), "r"((int)IT_B(e) * 5), "r"(0)
                                         : "memory");
                            asm volatile("cp.async.bulk.commit_group;" ::: "memory");
                            if (wide && m >= STLAG) {
                                asm volatile("cp.async.bulk.wait_group.read %0;" ::"n"(STLAG) : "memory");
                                asm volatile("mbarrier.arrive.shared::cta.b64 _, [%0], 8;" ::"r"(sb + BAR_XEMPTY + (m - STLAG) * 8) : "memory");
                            }
                            if (++xs == 5) xs = 0;
                        }
                        if (wide && STLAG) {
                            asm volatile("cp.async.bulk.wait_group.read 0;" ::: "memory");
                            asm volatile("mbarrier.arrive.shared::cta.b64 _, [%0], 8;" ::"r"(sb + BAR_XEMPTY + 32) : "memory");
                        }
                        if (IT_PART(e)) {
                            asm volatile("cp.async.bulk.wait_group 0;" ::: "memory");
                            asm volatile("fence.proxy.async;" ::: "memory");
                        }
                    }
                    if (IT_TYPE(e) == IT_QA || IT_PART(e)) {
                        unsigned int* f = &g_flag[bb * 64 + (IT_TYPE(e) == IT_QA ? IT_H0(e) : 32 + IT_HALF(e))];
                        asm volatile("st.release.gpu.global.u32 [%0], %1;" ::"l"(f), "r"(epoch) : "memory");
                    }
                }
                __syncwarp();
            }
            if (threadIdx.x == 64) asm volatile("cp.async.bulk.wait_group 0;" ::: "memory");
            __syncwarp();
            asm volatile("barrier.cluster.arrive.relaxed.aligned;\nbarrier.cluster.wait.aligned;" ::: "memory");
        } else {
            const uint32_t lane = threadIdx.x & 31, p = lane >> 3;
            const uint32_t epoch = next_epoch(3);
#pragma unroll 1
            for (int it = 0;; it++) {
                const uint32_t e = get_item_warp(sb, it, dl);
                if (e == 0) break;
                if (IT_TYPE(e) != IT_QA) continue;
                nb_sync<NB_QK, 160>();
                const uint32_t ka = sb + OFF_RING + lds_u(sb + OFF_GM + 4) * SLOT + p * (2 * 3072 + 256) + (lane & 7) * 16;
                const uint32_t qa = sb + OFF_R + p * 256 + (lane & 7) * 16;
                uint32_t acc = 0;
#pragma unroll 1
                for (int c = 0; c < 3; c++) {
                    const uint4 k = lds_u4(ka + c * 1024);
                    if (c == 2) nb_sync<NB_L, 160>();
                    const uint4 q = lds_u4(qa + c * XS);
                    acc = fma_bf2(k.x, q.x, fma_bf2(k.y, q.y, fma_bf2(k.z, q.z, fma_bf2(k.w, q.w, acc))));
                }
                const float d = __uint_as_float(acc << 16) + __uint_as_float(acc & 0xffff0000u);
                const int sum = __reduce_add_sync(0xffffffffu, __float2int_rn(d * 16.f));
                sts_f(sb + OFF_GM, fmaf((float)sum, SM_C / 64.f, 24.f));
                nb_arrive<NB_REF, 160>();
                if (IT_DEP(e)) {
                    const uint32_t g = IT_DEP(e) - 1, need = epoch * 64 + (g & 31) + 1;
                    const unsigned int* cp = &g_flag[((g >> 5) * 16 + IT_B(e)) * 64 + 34 + (lane & 1)];
                    for (uint32_t n = 0;; n++) {
                        uint32_t v;
                        asm volatile("ld.acquire.gpu.global.u32 %0, [%1];" : "=r"(v) : "l"(cp) : "memory");
                        if (__all_sync(0xffffffffu, v - need < 64)) break;
                        if (n > 0x800000) __trap();
                        __nanosleep(500);
                    }
                }
                nb_sync<NB_L, 160>();
                bool bad = false;
#pragma unroll
                for (int c = 0; c < 5; c++) {
                    const uint32_t la = sb + OFF_LX + (c * 32 + lane) * 4;
                    const float v = (__uint_as_float(lds_u(la)) + __uint_as_float(lds_u(la + 640))) +
                                    (__uint_as_float(lds_u(la + 1280)) + __uint_as_float(lds_u(la + 1920)));
                    const float inv = __fdividef(1.f, v);
                    const uint32_t hi = pack_bf16(inv, 0.f), lo = pack_bf16(inv - __uint_as_float(hi << 16), 0.f);
                    const uint32_t ia = sb + OFF_LINV + c * 128 + ((lane >> 1) & 3) * 32 + (lane >> 3) * 8 + (lane & 1) * 2;
                    asm volatile("st.shared.u16 [%0], %1;\nst.shared.u16 [%0+4], %2;" ::"r"(ia), "h"((unsigned short)hi), "h"((unsigned short)lo) : "memory");
                    bad |= !(v >= 5.421010862e-20f && v <= 7.9228163e28f);
                }
                sts_u(sb + OFF_FB, __any_sync(0xffffffffu, bad));
                nb_arrive<NB_VOTE, 160>();
                nb_arrive<NB_VOTE + 1, 160>();
            }
        }
    } else {
        asm volatile("setmaxnreg.inc.sync.aligned.u32 240;");
        consumer(P, wgid - 1, sb, dl);
    }
}

typedef CUresult (*EncFn)(CUtensorMap*, CUtensorMapDataType, cuuint32_t, void*, const cuuint64_t*, const cuuint64_t*,
                          const cuuint32_t*, const cuuint32_t*, CUtensorMapInterleave, CUtensorMapSwizzle,
                          CUtensorMapL2promotion, CUtensorMapFloatOOBfill);

void make_map3(EncFn enc, CUtensorMap* m, void* p, uint64_t rows, uint64_t rowbytes, uint64_t nblk, uint32_t boxrows,
               uint32_t boxblk) {
    cuuint64_t dims[3] = {64, rows, nblk};
    cuuint64_t str[2] = {rowbytes, 128};
    cuuint32_t box[3] = {64, boxrows, boxblk};
    cuuint32_t es[3] = {1, 1, 1};
    enc(m, CU_TENSOR_MAP_DATA_TYPE_BFLOAT16, 3, p, dims, str, box, es, CU_TENSOR_MAP_INTERLEAVE_NONE,
        CU_TENSOR_MAP_SWIZZLE_128B, CU_TENSOR_MAP_L2_PROMOTION_NONE, CU_TENSOR_MAP_FLOAT_OOB_FILL_NONE);
}

constexpr int tune(const char*, int def) { return def; }

void build_schedule(Params& P) {
    const int mode = tune("MODE", 4), dmax = tune("DMAX", 24200), n0 = tune("N0", 10), odmax = tune("ODMAX", 0), d1 = tune("D1", 0);
    const int H0[8] = {19, 20, 21, 22, 22, 24, 25, 25}, P0[8] = {367, 337, 335, 331, 338, 335, 333, 332};
    const int ra = tune("RA", 10), ga = tune("GA", 17), rb = tune("RB", 11), g1 = tune("G1", 58);
    int dep[64];
    for (int g = 0, ns = 0, live = 0; g < 64; g++) {
        const bool fresh = mode < 3 || g >= g1 || live < (g < ga ? ra : rb);
        dep[g] = fresh ? 0 : g - live + 1;
        P.slot[g] = fresh ? ns++ : P.slot[g - live];
        live += fresh;
    }
    int H[8], pos[8], psum = 0;
    for (int b = 0; b < 8; b++) {
        const char nh[3] = {'H', (char)('0' + b), 0}, np[3] = {'P', (char)('0' + b), 0};
        H[b] = tune(nh, H0[b]);
        pos[b] = tune(np, P0[b]);
        psum += pos[b];
    }
    const int sk = tune("SK", 10), g0 = tune("G0", 20), g2 = tune("G2", 40);
    int ord[512], nxt[8] = {0, 0, 0, 0, 0, 0, 0, 0};
    for (int k = 0; k < 512; k++) {
        int best = -1;
        float bkey = 0.f;
        for (int b = 0; b < 8; b++) {
            const int g = nxt[b];
            if (g == 64) continue;
            const float w = g < g0 ? 0.f : g < 32 ? (g - g0) / (32.f - g0) : g < g2 ? 1.f : (64 - g) / (64.f - g2);
            const float key = g + w * sk * 0.1f * (pos[b] - psum / 8.f) / 8.f;
            if (best < 0 || key < bkey) best = b, bkey = key;
        }
        ord[k] = nxt[best]++ * 8 + best;
        const int d = dep[ord[k] >> 3];
        if (d > 32) {
            if (pos[best] > k) pos[best] = k;
            if (H[best] < d - 32) H[best] = d - 32;
        }
    }
    int u = 0;
    auto unit = [&]() {
        const int v = ord[u++];
        return mk_item(IT_QA, v >> 8, (v & 7) * 2, (v >> 3) & 31, P.slot[v >> 3], 0) | (dep[v >> 3] << 23);
    };
    const int ob = tune("OB", 4), qm = tune("QM", 19);
    int qa[NCL], nq = 0, op[NCL], no = 0;
    for (int c = 0; c < NCL; c++) {
        P.cl[c].delay = 0;
        for (int i = 0; i < NSTAT; i++) P.cl[c].items[i] = 0;
        if (mode >= 3 && ob >= 0 && c >= ob && c < ob + 16) op[((c - ob) & 7) * 2 + ((c - ob) >> 3)] = c, no++;
        else if (mode >= 3 && ob < 0 && c < 64 && (c & 3) == 3) op[no++] = c;
        else if (mode != 2 || (c & 3) == 0) qa[nq++] = c;
    }
    for (int t = 0; t < no; t++) {
        P.cl[op[t]].items[1] = mk_item(IT_OP, 0, t & ~1, 0, 32, t & 1);
        P.cl[op[t]].items[2] = IT_DYN;
        P.cl[op[t]].delay = tune("OD0", 0) + t * odmax / 16;
    }
    for (int k = 0; k < nq; k++) {
        const int c = qa[(k * qm) % nq];
        P.cl[c].items[1] = P.cl[c].items[2] = IT_DYN;
        P.cl[c].delay = k < n0 ? k * tune("J0", 0) : d1 + (dmax - d1) * (k + 1 - n0) / (nq - n0);
    }
    if (tune("OFIRST", 0))
        for (int t = 0; t < no; t++) P.cl[op[t]].items[0] = unit();
    for (int k = u; k < no + nq; k++) {
        int best = -1;
        for (int c = 0; c < NCL; c++)
            if (P.cl[c].items[1] && !P.cl[c].items[0] && (best < 0 || P.cl[c].delay < P.cl[best].delay)) best = c;
        P.cl[best].items[0] = unit();
    }
    int n = 0;
    const int uend = mode == 2 ? 8 * nq : 512;
    while (u < uend) {
        for (int b = 0; b < 8 && no; b++)
            if (pos[b] == u) {
                P.list[n++] = mk_item(IT_OP, 1, 2 * b, 0, H[b], 0, 1);
                P.list[n++] = mk_item(IT_OP, 1, 2 * b, 0, H[b], 1, 1);
            }
        P.list[n++] = unit();
    }
    for (int k = 0; no && k < 40; k++) P.list[n++] = mk_item(IT_ON, 1, k / 5 * 2, H[k / 5], 32, k % 5);
    P.nlist = n;
}

}

extern "C" void kernel_launch(void* const* d_in, const int* in_sizes, int n_in, void* d_out, int out_size) {
    static Params P;
    static bool init = false;
    if (!init) {
        EncFn enc = nullptr;
        cudaDriverEntryPointQueryResult qr;
        cudaGetDriverEntryPoint("cuTensorMapEncodeTiled", (void**)&enc, cudaEnableDefault, &qr);
        for (int i = 0; i < 2; i++) {
            P.px[i] = (const __nv_bfloat16*)d_in[5 * i + 0];
            P.pk[i] = (const __nv_bfloat16*)d_in[5 * i + 1];
            P.pv[i] = (const __nv_bfloat16*)d_in[5 * i + 2];
            P.pwq[i] = (const __nv_bfloat16*)d_in[5 * i + 3];
            make_map3(enc, &P.x[i], d_in[5 * i + 0], 2560, 1280, 10, 160, 1);
            for (int j = 0; j < 2; j++) {
                cuuint64_t dims[4] = {64, 8, 3, 16 * 32 * 64};
                cuuint64_t str[3] = {384, 128, 3072};
                cuuint32_t box[4] = {64, 8, 3, 8};
                cuuint32_t es[4] = {1, 1, 1, 1};
                enc(j ? &P.v[i] : &P.k[i], CU_TENSOR_MAP_DATA_TYPE_BFLOAT16, 4, d_in[5 * i + 1 + j], dims, str, box, es,
                    CU_TENSOR_MAP_INTERLEAVE_NONE, CU_TENSOR_MAP_SWIZZLE_128B, (CUtensorMapL2promotion)tune("PROMO", 0),
                    CU_TENSOR_MAP_FLOAT_OOB_FILL_NONE);
            }
            make_map3(enc, &P.wq[i], d_in[5 * i + 3], 640, 12288, 96, 32, 3);
            make_map3(enc, &P.wo[i], d_in[5 * i + 4], 6144, 1280, 10, 16, 5);
            make_map3(enc, &P.won[i], d_in[5 * i + 4], 6144, 1280, 10, 32, 2);
        }
        cuuint64_t dims[5] = {1280, 2, 4, 4, 80};
        cuuint64_t str[4] = {2560, 8 * 2560, 2 * 2560, 32 * 2560};
        cuuint32_t box[5] = {64, 2, 4, 4, 5};
        cuuint32_t es[5] = {1, 1, 1, 1, 1};
        enc(&P.out, CU_TENSOR_MAP_DATA_TYPE_BFLOAT16, 5, d_out, dims, str, box, es, CU_TENSOR_MAP_INTERLEAVE_NONE,
            CU_TENSOR_MAP_SWIZZLE_128B, CU_TENSOR_MAP_L2_PROMOTION_NONE, CU_TENSOR_MAP_FLOAT_OOB_FILL_NONE);
        build_schedule(P);
        cudaFuncSetAttribute(fused_kernel, cudaFuncAttributeMaxDynamicSharedMemorySize, SMEM_LAUNCH);
        init = true;
    }
    fused_kernel<<<NCTA, 384, SMEM_LAUNCH>>>(P);
}
```

```cpp
#include <cuda_runtime.h>
#include <cuda.h>
#include <cuda_bf16.h>
#include <stdint.h>

namespace {

constexpr int NCTA = 132;
constexpr int NCL = NCTA / 2;
constexpr int MAXI = 16;
constexpr int NSTAT = 3;
constexpr uint32_t IT_DYN = 0xffffffffu;
constexpr int SLOT = 24576;
constexpr int NSLOT = 5;
constexpr int XS = 20480;
constexpr int OFF_R = 0;
constexpr int OFF_RING = 5 * XS;
constexpr int OFF_MISC = OFF_RING + NSLOT * SLOT;
constexpr int OFF_LX = OFF_MISC;
constexpr int OFF_LINV = OFF_LX + 2560;
constexpr int OFF_FB = OFF_LINV + 640;
constexpr int OFF_GM = OFF_FB + 16;
constexpr int OFF_BAR = OFF_GM + 16;
constexpr int BAR_RFULL = OFF_BAR;
constexpr int BAR_REMPTY = BAR_RFULL + 40;
constexpr int BAR_XFULL = BAR_REMPTY + 40;
constexpr int BAR_XEMPTY = BAR_XFULL + 40;
constexpr int BAR_PRDY = BAR_XEMPTY + 40;
constexpr int BAR_ITEM = BAR_PRDY + 40;
constexpr int OFF_ITEM = BAR_ITEM + MAXI * 8;
constexpr int SMEM_BYTES = OFF_ITEM + MAXI * 4;
static_assert(SMEM_BYTES <= 232448, "smem");

constexpr int NB_W = 1  , NB_PFULL = 3  , NB_VOTE = 5  , NB_Q2 = 7, NB_SDONE = 8, NB_PDONE = 9,
              NB_L = 10, NB_REF = 11, NB_ODONE = 12, NB_OPEND = 13, NB_LX = 14, NB_Q01 = 15, NB_QK = 0  ;

constexpr uint32_t IT_QA = 1, IT_OP = 2, IT_ON = 3;
__host__ __device__ constexpr uint32_t mk_item(uint32_t type, uint32_t br, uint32_t b, uint32_t h0, uint32_t h1, uint32_t half,
                                               uint32_t part = 0) {
    return type | (br << 2) | (b << 3) | (h0 << 7) | (h1 << 13) | (half << 19) | (part << 22);
}
#define IT_TYPE(e) ((e) & 3u)
#define IT_BR(e) (((e) >> 2) & 1u)
#define IT_B(e) (((e) >> 3) & 15u)
#define IT_H0(e) (((e) >> 7) & 63u)
#define IT_H1(e) (((e) >> 13) & 63u)
#define IT_HALF(e) (((e) >> 19) & 7u)
#define IT_PART(e) (((e) >> 22) & 1u)
#define IT_SLOT(e) IT_H1(e)
#define IT_DEP(e) (((e) >> 23) & 127u)

struct Params {
    CUtensorMap x[2], wq[2], k[2], v[2], wo[2], won[2], out;
    const __nv_bfloat16 *px[2], *pwq[2], *pk[2], *pv[2];
    struct alignas(16) { uint32_t delay, items[NSTAT]; } cl[NCL];
    uint32_t nlist;
    uint8_t slot[64];
    uint32_t list[568];
};

constexpr int OUNIT = 61440;
__device__ __align__(1024) unsigned char g_ostash[(size_t)1024 * OUNIT];
__device__ unsigned int g_flag[32 * 64];
__device__ __forceinline__ unsigned char* ostash(uint32_t slot, uint32_t b) { return g_ostash + (slot * 16 + b) * OUNIT; }
__device__ unsigned int g_epoch[NCTA * 4];
__device__ unsigned int g_ticket[2];

constexpr int SMEM_LAUNCH = SMEM_BYTES;
#define TS(role, idx)
#define TS_ITEM(e)
#define TS_DUMP(role)
#define TSD(role, idx)

__device__ __forceinline__ uint64_t pol_stream() {
    uint64_t p;
    asm volatile("createpolicy.fractional.L2::evict_first.b64 %0, 1.0;" : "=l"(p));
    return p;
}
__device__ __forceinline__ uint64_t pol_shared() {
    uint64_t p;
    asm volatile("createpolicy.fractional.L2::evict_unchanged.b64 %0, 1.0;" : "=l"(p));
    return p;
}
constexpr int QHOLD = 8;
constexpr float SM_C = 0.07216878364870322f * 1.4426950408889634f;

__device__ __forceinline__ uint32_t next_epoch(int warp) {
    unsigned int* p = &g_epoch[blockIdx.x * 4 + warp];
    const uint32_t e = __ldcg(p) + 1;
    *p = e;
    return e;
}

__device__ __forceinline__ uint32_t tid_now() {
    uint32_t t;
    asm volatile("mov.u32 %0, %%tid.x;" : "=r"(t));
    return t;
}
__device__ __forceinline__ void mbar_init(uint32_t a, uint32_t c) {
    asm volatile("mbarrier.init.shared::cta.b64 [%0], %1;" ::"r"(a), "r"(c) : "memory");
}
__device__ __forceinline__ void mbar_expect(uint32_t a, uint32_t b) {
    asm volatile("mbarrier.arrive.expect_tx.shared::cta.b64 _, [%0], %1;" ::"r"(a), "r"(b) : "memory");
}
template <int CNT = 1>
__device__ __forceinline__ void mbar_arrive_warp(uint32_t a) {
    if (CNT == 1)
        asm volatile("{\n.reg .pred p;\nelect.sync _|p, 0xffffffff;\n@p mbarrier.arrive.shared::cta.b64 _, [%0];\n}" ::"r"(a) : "memory");
    else
        asm volatile(
            "{\n.reg .pred p;\nelect.sync _|p, 0xffffffff;\n@p mbarrier.arrive.shared::cta.b64 _, [%0];\n"
            "@p mbarrier.arrive.shared::cta.b64 _, [%0];\n}" ::"r"(a)
            : "memory");
}
template <int CNT = 1>
__device__ __forceinline__ void mbar_arrive_warp_if(uint32_t a, bool cond) {
    if (CNT == 1)
        asm volatile(
            "{\n.reg .pred p, c;\nelect.sync _|p, 0xffffffff;\nsetp.ne.and.u32 c, %1, 0, p;\n"
            "@c mbarrier.arrive.shared::cta.b64 _, [%0];\n}" ::"r"(a), "r"((uint32_t)cond)
            : "memory");
    else
        asm volatile(
            "{\n.reg .pred p, c;\nelect.sync _|p, 0xffffffff;\nsetp.ne.and.u32 c, %1, 0, p;\n"
            "@c mbarrier.arrive.shared::cta.b64 _, [%0];\n@c mbarrier.arrive.shared::cta.b64 _, [%0];\n}" ::"r"(a), "r"((uint32_t)cond)
            : "memory");
}
__device__ __forceinline__ uint32_t deadline() {
    uint32_t c;
    asm volatile("mov.u32 %0, %%clock_hi;" : "=r"(c));
    return c + 4;
}
__device__ __forceinline__ void mbar_wait(uint32_t a, uint32_t ph, uint32_t dl) {
    asm volatile(
        "{\n.reg .pred p;\n.reg .u32 m;\n"
        "LOOP:\n"
        "mbarrier.try_wait.parity.shared::cta.b64 p, [%0], %1;\n"
        "@p bra DONE;\n"
        "mov.u32 m, %%clock_hi;\n"
        "setp.ne.u32 p, m, %2;\n"
        "@p bra LOOP;\n"
        "trap;\n"
        "DONE:\n}" ::"r"(a), "r"(ph), "r"(dl)
        : "memory");
}
__device__ __forceinline__ void mbar_wait2(uint32_t a, uint32_t pa, uint32_t b, uint32_t pb, uint32_t dl) {
    asm volatile(
        "{\n.reg .pred p, q;\n.reg .u32 m;\n"
        "LOOP:\n"
        "mbarrier.try_wait.parity.shared::cta.b64 p, [%0], %1;\n"
        "mbarrier.try_wait.parity.shared::cta.b64 q, [%2], %3;\n"
        "and.pred p, p, q;\n"
        "@p bra DONE;\n"
        "mov.u32 m, %%clock_hi;\n"
        "setp.ne.u32 p, m, %4;\n"
        "@p bra LOOP;\n"
        "trap;\n"
        "DONE:\n}" ::"r"(a), "r"(pa), "r"(b), "r"(pb), "r"(dl)
        : "memory");
}
template <int ID, int CNT>
__device__ __forceinline__ void nb_sync() { asm volatile("bar.sync %0, %1;" ::"n"(ID), "n"(CNT) : "memory"); }
template <int ID, int CNT>
__device__ __forceinline__ void nb_arrive() { asm volatile("bar.arrive %0, %1;" ::"n"(ID), "n"(CNT) : "memory"); }
__device__ __forceinline__ void fence_async_smem() { asm volatile("fence.proxy.async.shared::cta;" ::: "memory"); }

__device__ __forceinline__ void tma3(uint32_t dst, const CUtensorMap* m, int c1, int c2, uint32_t bar, uint64_t pol) {
    asm volatile(
        "cp.async.bulk.tensor.3d.shared::cluster.global.mbarrier::complete_tx::bytes.L2::cache_hint [%0], [%1, {%3,%4,%5}], [%2], %6;" ::"r"(dst),
        "l"(m), "r"(bar), "r"(0), "r"(c1), "r"(c2), "l"(pol)
        : "memory");
}
__device__ __forceinline__ void tma3_mc(uint32_t dst, const CUtensorMap* m, int c1, int c2, uint32_t bar, uint64_t pol) {
    asm volatile(
        "cp.async.bulk.tensor.3d.shared::cluster.global.mbarrier::complete_tx::bytes.multicast::cluster.L2::cache_hint"
        " [%0], [%1, {%3,%4,%5}], [%2], %6, %7;" ::"r"(dst),
        "l"(m), "r"(bar), "r"(0), "r"(c1), "r"(c2), "h"((unsigned short)3), "l"(pol)
        : "memory");
}
__device__ __forceinline__ void bulk_load(uint32_t dst, const void* src, uint32_t bytes, uint32_t bar, uint64_t pol) {
    asm volatile("cp.async.bulk.shared::cluster.global.mbarrier::complete_tx::bytes.L2::cache_hint [%0], [%1], %2, [%3], %4;" ::"r"(dst),
                 "l"(src), "r"(bytes), "r"(bar), "l"(pol)
                 : "memory");
}
__device__ __forceinline__ void wg_fence() { asm volatile("wgmma.fence.sync.aligned;" ::: "memory"); }
__device__ __forceinline__ void wg_commit() { asm volatile("wgmma.commit_group.sync.aligned;" ::: "memory"); }
template <int N>
__device__ __forceinline__ void wg_wait() { asm volatile("wgmma.wait_group.sync.aligned %0;" ::"n"(N) : "memory"); }

#define RW80(c, d) c(d[0]), c(d[1]), c(d[2]), c(d[3]), c(d[4]), c(d[5]), c(d[6]), c(d[7]), c(d[8]), c(d[9]), c(d[10]), c(d[11]), c(d[12]), c(d[13]), c(d[14]), c(d[15]), c(d[16]), c(d[17]), c(d[18]), c(d[19]), c(d[20]), c(d[21]), c(d[22]), c(d[23]), c(d[24]), c(d[25]), c(d[26]), c(d[27]), c(d[28]), c(d[29]), c(d[30]), c(d[31]), c(d[32]), c(d[33]), c(d[34]), c(d[35]), c(d[36]), c(d[37]), c(d[38]), c(d[39]), c(d[40]), c(d[41]), c(d[42]), c(d[43]), c(d[44]), c(d[45]), c(d[46]), c(d[47]), c(d[48]), c(d[49]), c(d[50]), c(d[51]), c(d[52]), c(d[53]), c(d[54]), c(d[55]), c(d[56]), c(d[57]), c(d[58]), c(d[59]), c(d[60]), c(d[61]), c(d[62]), c(d[63]), c(d[64]), c(d[65]), c(d[66]), c(d[67]), c(d[68]), c(d[69]), c(d[70]), c(d[71]), c(d[72]), c(d[73]), c(d[74]), c(d[75]), c(d[76]), c(d[77]), c(d[78]), c(d[79])
#define RW48(c, d) c(d[0]), c(d[1]), c(d[2]), c(d[3]), c(d[4]), c(d[5]), c(d[6]), c(d[7]), c(d[8]), c(d[9]), c(d[10]), c(d[11]), c(d[12]), c(d[13]), c(d[14]), c(d[15]), c(d[16]), c(d[17]), c(d[18]), c(d[19]), c(d[20]), c(d[21]), c(d[22]), c(d[23]), c(d[24]), c(d[25]), c(d[26]), c(d[27]), c(d[28]), c(d[29]), c(d[30]), c(d[31]), c(d[32]), c(d[33]), c(d[34]), c(d[35]), c(d[36]), c(d[37]), c(d[38]), c(d[39]), c(d[40]), c(d[41]), c(d[42]), c(d[43]), c(d[44]), c(d[45]), c(d[46]), c(d[47])
#define RW32(c, d) c(d[0]), c(d[1]), c(d[2]), c(d[3]), c(d[4]), c(d[5]), c(d[6]), c(d[7]), c(d[8]), c(d[9]), c(d[10]), c(d[11]), c(d[12]), c(d[13]), c(d[14]), c(d[15]), c(d[16]), c(d[17]), c(d[18]), c(d[19]), c(d[20]), c(d[21]), c(d[22]), c(d[23]), c(d[24]), c(d[25]), c(d[26]), c(d[27]), c(d[28]), c(d[29]), c(d[30]), c(d[31])

__device__ __forceinline__ void reg_fence(float (&d)[80]) { asm volatile("" : RW80("+f", d)::"memory"); }
__device__ __forceinline__ void reg_fence(float (&d)[48]) { asm volatile("" : RW48("+f", d)::"memory"); }
__device__ __forceinline__ void reg_fence(float (&d)[32]) { asm volatile("" : RW32("+f", d)::"memory"); }

template <int NR>
__device__ __forceinline__ void zero(float (&d)[NR]) {
#pragma unroll
    for (int i = 0; i < NR; i++) d[i] = 0.f;
}

constexpr uint32_t HI_SW128 = (1024u >> 4) | (1u << 30);
constexpr uint32_t HI_KV = (3072u >> 4) | (1u << 30);
constexpr uint32_t HI_OST = (2560u >> 4) | (2u << 30);
constexpr uint32_t LO_LBO1 = (1u << 16);
constexpr uint32_t LO_OST = ((512u >> 4) << 16);

template <int TA, int TB, uint32_t HIB, int ACC, uint32_t HIA = HI_SW128>
__device__ __forceinline__ void wgmma(float (&d)[80], uint32_t loA, uint32_t loB) {
#define WG_ASM(SD)                                                          \
    "{\n.reg .b64 da, db;\nmov.b64 da, {%80, %82};\nmov.b64 db, {%81, %83};\n" \
    "wgmma.mma_async.sync.aligned.m64n160k16.f32.bf16.bf16 "               \
    "{%0,%1,%2,%3,%4,%5,%6,%7,%8,%9,%10,%11,%12,%13,%14,%15,%16,%17,%18,%19,%20,%21,%22,%23,%24,%25,%26,%27,%28,%29,%30,%31,%32,%33,%34,%35,%36,%37,%38,%39,%40,%41,%42,%43,%44,%45,%46,%47,%48,%49,%50,%51,%52,%53,%54,%55,%56,%57,%58,%59,%60,%61,%62,%63,%64,%65,%66,%67,%68,%69,%70,%71,%72,%73,%74,%75,%76,%77,%78,%79}, da, db, " SD ", 1, 1, %84, %85;\n}"
    if constexpr (ACC == 2)
        asm volatile(WG_ASM("0") : RW80("+f", d) : "r"(loA), "r"(loB), "n"(HIA), "n"(HIB), "n"(TA), "n"(TB));
    else if constexpr (ACC == 1)
        asm volatile(WG_ASM("1") : RW80("+f", d) : "r"(loA), "r"(loB), "n"(HIA), "n"(HIB), "n"(TA), "n"(TB));
    else
        asm volatile(WG_ASM("0") : RW80("=f", d) : "r"(loA), "r"(loB), "n"(HIA), "n"(HIB), "n"(TA), "n"(TB));
#undef WG_ASM
}
template <int TA, int TB, uint32_t HIB, int ACC, uint32_t HIA = HI_SW128>
__device__ __forceinline__ void wgmma(float (&d)[48], uint32_t loA, uint32_t loB) {
#define WG_ASM(SD)                                                          \
    "{\n.reg .b64 da, db;\nmov.b64 da, {%48, %50};\nmov.b64 db, {%49, %51};\n" \
    "wgmma.mma_async.sync.aligned.m64n96k16.f32.bf16.bf16 "               \
    "{%0,%1,%2,%3,%4,%5,%6,%7,%8,%9,%10,%11,%12,%13,%14,%15,%16,%17,%18,%19,%20,%21,%22,%23,%24,%25,%26,%27,%28,%29,%30,%31,%32,%33,%34,%35,%36,%37,%38,%39,%40,%41,%42,%43,%44,%45,%46,%47}, da, db, " SD ", 1, 1, %52, %53;\n}"
    if constexpr (ACC == 1)
        asm volatile(WG_ASM("1") : RW48("+f", d) : "r"(loA), "r"(loB), "n"(HIA), "n"(HIB), "n"(TA), "n"(TB));
    else
        asm volatile(WG_ASM("0") : RW48("=f", d) : "r"(loA), "r"(loB), "n"(HIA), "n"(HIB), "n"(TA), "n"(TB));
#undef WG_ASM
}
template <int TA, int TB, uint32_t HIB, int ACC, uint32_t HIA = HI_SW128>
__device__ __forceinline__ void wgmma(float (&d)[32], uint32_t loA, uint32_t loB) {
#define WG_ASM(SD)                                                          \
    "{\n.reg .b64 da, db;\nmov.b64 da, {%32, %34};\nmov.b64 db, {%33, %35};\n" \
    "wgmma.mma_async.sync.aligned.m64n64k16.f32.bf16.bf16 "               \
    "{%0,%1,%2,%3,%4,%5,%6,%7,%8,%9,%10,%11,%12,%13,%14,%15,%16,%17,%18,%19,%20,%21,%22,%23,%24,%25,%26,%27,%28,%29,%30,%31}, da, db, " SD ", 1, 1, %36, %37;\n}"
    if constexpr (ACC == 1)
        asm volatile(WG_ASM("1") : RW32("+f", d) : "r"(loA), "r"(loB), "n"(HIA), "n"(HIB), "n"(TA), "n"(TB));
    else
        asm volatile(WG_ASM("0") : RW32("=f", d) : "r"(loA), "r"(loB), "n"(HIA), "n"(HIB), "n"(TA), "n"(TB));
#undef WG_ASM
}

__device__ __forceinline__ uint32_t pack_bf16(float lo, float hi) {
    uint32_t r;
    asm("cvt.rn.bf16x2.f32 %0, %1, %2;" : "=r"(r) : "f"(hi), "f"(lo));
    return r;
}
__device__ __forceinline__ float ex2(float x) {
    float r;
    asm("ex2.approx.ftz.f32 %0, %1;" : "=f"(r) : "f"(x));
    return r;
}
__device__ __forceinline__ void stsm4t(uint32_t a, uint32_t r0, uint32_t r1, uint32_t r2, uint32_t r3) {
    asm volatile("stmatrix.sync.aligned.m8n8.x4.trans.shared.b16 [%0], {%1,%2,%3,%4};" ::"r"(a), "r"(r0), "r"(r1), "r"(r2), "r"(r3)
                 : "memory");
}
__device__ __forceinline__ uint32_t lds_u(uint32_t a) {
    uint32_t v;
    asm volatile("ld.shared.u32 %0, [%1];" : "=r"(v) : "r"(a) : "memory");
    return v;
}
__device__ __forceinline__ uint4 lds_u4(uint32_t a) {
    uint4 v;
    asm volatile("ld.shared.v4.u32 {%0,%1,%2,%3}, [%4];" : "=r"(v.x), "=r"(v.y), "=r"(v.z), "=r"(v.w) : "r"(a) : "memory");
    return v;
}
__device__ __forceinline__ float2 lds_f2(uint32_t a) {
    float2 v;
    asm volatile("ld.shared.v2.f32 {%0,%1}, [%2];" : "=f"(v.x), "=f"(v.y) : "r"(a) : "memory");
    return v;
}
__device__ __forceinline__ void sts_f(uint32_t a, float v) { asm volatile("st.shared.f32 [%0], %1;" ::"r"(a), "f"(v) : "memory"); }
__device__ __forceinline__ void sts_u(uint32_t a, uint32_t v) { asm volatile("st.shared.u32 [%0], %1;" ::"r"(a), "r"(v) : "memory"); }
__device__ __forceinline__ void sts_f2(uint32_t a, float x, float y) {
    asm volatile("st.shared.v2.f32 [%0], {%1,%2};" ::"r"(a), "f"(x), "f"(y) : "memory");
}

template <bool ADD = false, bool SIG = false, int NR>
__device__ __forceinline__ void store_tile_t(const float (&d)[NR], uint32_t addr) {
    uint32_t p[NR / 2];
    if (ADD) {
#pragma unroll
        for (int j = 0; j < NR / 8; j++)
            asm volatile("ldmatrix.sync.aligned.m8n8.x4.trans.shared.b16 {%0,%1,%2,%3}, [%4];"
                         : "=r"(p[4 * j]), "=r"(p[4 * j + 1]), "=r"(p[4 * j + 2]), "=r"(p[4 * j + 3])
                         : "r"(addr + j * 2048)
                         : "memory");
    }
#pragma unroll
    for (int k = 0; k < NR / 2; k++)
        p[k] = ADD ? pack_bf16(d[2 * k] + __uint_as_float(p[k] << 16), d[2 * k + 1] + __uint_as_float(p[k] & 0xffff0000u))
                   : pack_bf16(d[2 * k], d[2 * k + 1]);
#pragma unroll
    for (int j = 0; j < NR / 8; j++) {
        stsm4t(addr + j * 2048, p[4 * j], p[4 * j + 1], p[4 * j + 2], p[4 * j + 3]);
        if (SIG && j == 0) nb_arrive<NB_L, 160>();
    }
}

struct TrueT { static constexpr bool value = true; };
struct FalseT { static constexpr bool value = false; };

template <int V>
struct IntT { static constexpr int value = V; };

__device__ __forceinline__ uint32_t get_item(uint32_t sb, int it, uint32_t dl) {
    mbar_wait(sb + BAR_ITEM + it * 8, 0, dl);
    return lds_u(sb + OFF_ITEM + it * 4);
}
__device__ __forceinline__ uint32_t get_item_warp(uint32_t sb, int it, uint32_t dl) {
    return __shfl_sync(0xffffffffu, get_item(sb, it, dl), 0);
}

struct Ring {
    uint32_t slot, ph, dl;
    __device__ __forceinline__ void adv(uint32_t k) {
        slot += k;
        if (slot >= NSLOT) { slot -= NSLOT; ph ^= 1; }
    }
};

template <int K>
__device__ __forceinline__ void qk_step(float (&s)[80], uint32_t loK, uint32_t loQ) {
    wgmma<0, 0, HI_SW128, K != 0, HI_KV>(s, loK + (K >> 2) * 64 + (K & 3) * 2, loQ + (K >> 2) * (XS >> 4) + (K & 3) * 2);
}
template <int K0, int K1>
__device__ __forceinline__ void qk_steps(float (&s)[80], uint32_t loK, uint32_t loQ) {
    if constexpr (K0 < K1) {
        qk_step<K0>(s, loK, loQ);
        qk_steps<K0 + 1, K1>(s, loK, loQ);
    }
}
__device__ __forceinline__ uint32_t add_bf2(uint32_t a, uint32_t b) {
    uint32_t r;
    asm("add.rn.bf16x2 %0, %1, %2;" : "=r"(r) : "r"(a), "r"(b));
    return r;
}
__device__ __forceinline__ uint32_t fma_bf2(uint32_t a, uint32_t b, uint32_t c) {
    uint32_t r;
    asm("fma.rn.bf16x2 %0, %1, %2, %3;" : "=r"(r) : "r"(a), "r"(b), "r"(c));
    return r;
}
template <int J>
__device__ __forceinline__ void exp_block(const float (&s)[80], uint32_t (&k)[40], uint32_t pa, float mref) {
    if constexpr (J < 10) {
#pragma unroll
        for (int i = 4 * J; i < 4 * J + 4; i++)
            k[i] = pack_bf16(ex2(fmaf(s[2 * i], SM_C, -mref)), ex2(fmaf(s[2 * i + 1], SM_C, -mref)));
#pragma unroll
        for (int i = 0; i < 4; i++)
            asm volatile("stmatrix.sync.aligned.m8n8.x1.trans.shared.b16 [%0], {%1};" ::"r"(((i & 1) ? pa ^ 16 : pa) + J * 2048 + (i >> 1) * 1024),
                         "r"(k[4 * J + i])
                         : "memory");
        exp_block<J + 1>(s, k, pa, mref);
    }
}
__device__ __forceinline__ void sum_block(const uint32_t (&k)[40], float (&l)[10], uint32_t lane) {
    const bool b4 = lane & 16, b3 = lane & 8;
    uint32_t ps[20], t[10];
#pragma unroll
    for (int j = 0; j < 20; j++) ps[j] = add_bf2(k[2 * j], k[2 * j + 1]);
#pragma unroll
    for (int j = 0; j < 10; j++)
        t[j] = add_bf2(b4 ? ps[2 * j + 1] : ps[2 * j], __shfl_xor_sync(0xffffffffu, b4 ? ps[2 * j] : ps[2 * j + 1], 16));
#pragma unroll
    for (int i = 0; i < 5; i++) {
        const uint32_t a = b3 ? t[i + 5] : t[i], b = __shfl_xor_sync(0xffffffffu, b3 ? t[i] : t[i + 5], 8);
        l[2 * i] += __uint_as_float(a << 16) + __uint_as_float(b << 16);
        l[2 * i + 1] += __uint_as_float(a & 0xffff0000u) + __uint_as_float(b & 0xffff0000u);
    }
}
template <bool ADD>
__device__ __forceinline__ void sum_store(const float (&l)[10], uint32_t lane, uint32_t lxa) {
    const bool b2 = lane & 4;
    float t[5];
#pragma unroll
    for (int i = 0; i < 5; i++) t[i] = ADD ? __uint_as_float(lds_u(lxa + i * 64)) : 0.f;
#pragma unroll
    for (int i = 0; i < 5; i++)
        sts_f(lxa + i * 64, t[i] + (b2 ? l[2 * i + 1] : l[2 * i]) + __shfl_xor_sync(0xffffffffu, b2 ? l[2 * i] : l[2 * i + 1], 4));
}

__device__ __forceinline__ void fallback_unit(const Params& P, uint32_t e, uint32_t tid) {
    const uint32_t lane = tid & 31, br = IT_BR(e), b = IT_B(e), h = IT_H0(e);
    const __nv_bfloat162* wq = (const __nv_bfloat162*)(P.pwq[br] + h * 192) + lane;
    const __nv_bfloat162* kp = (const __nv_bfloat162*)(P.pk[br] + (size_t)(b * 32 + h) * 512 * 192) + lane;
    const __nv_bfloat162* vp = (const __nv_bfloat162*)(P.pv[br] + (size_t)(b * 32 + h) * 512 * 192) + lane;
#pragma unroll 1
    for (uint32_t qi = 0; qi < 40; qi++) {
        const uint32_t q = 4 * qi + (tid >> 5);
        const __nv_bfloat16* xr = P.px[br] + (size_t)(b * 160 + q) * 640;
        float a[6] = {0.f, 0.f, 0.f, 0.f, 0.f, 0.f};
#pragma unroll 2
        for (int k = 0; k < 640; k++) {
            const float xv = __bfloat162float(xr[k]);
#pragma unroll
            for (int i = 0; i < 3; i++) {
                const float2 wv = __bfloat1622float2(wq[(size_t)k * 3072 + i * 32]);
                a[2 * i] = fmaf(xv, wv.x, a[2 * i]);
                a[2 * i + 1] = fmaf(xv, wv.y, a[2 * i + 1]);
            }
        }
#pragma unroll
        for (int i = 0; i < 6; i++) a[i] = __bfloat162float(__float2bfloat16(a[i]));
        auto score = [&](int key) {
            float d = 0.f;
#pragma unroll
            for (int i = 0; i < 3; i++) {
                const float2 kv = __bfloat1622float2(kp[key * 96 + i * 32]);
                d = fmaf(a[2 * i], kv.x, fmaf(a[2 * i + 1], kv.y, d));
            }
#pragma unroll
            for (int o = 16; o > 0; o >>= 1) d += __shfl_xor_sync(0xffffffffu, d, o);
            return d;
        };
        float m = -INFINITY, o[6] = {0.f, 0.f, 0.f, 0.f, 0.f, 0.f}, sum = 0.f;
#pragma unroll 1
        for (int n = 0; n < 1024; n++) {
            const int key = n & 511;
            const float d = score(key);
            if (n < 512) {
                m = fmaxf(m, d);
            } else {
                const float p = ex2((d - m) * SM_C);
                sum += p;
#pragma unroll
                for (int i = 0; i < 3; i++) {
                    const float2 vv = __bfloat1622float2(vp[key * 96 + i * 32]);
                    o[2 * i] = fmaf(p, vv.x, o[2 * i]);
                    o[2 * i + 1] = fmaf(p, vv.y, o[2 * i + 1]);
                }
            }
        }
        const float inv = __fdividef(1.f, sum);
        __nv_bfloat16* op = (__nv_bfloat16*)ostash(IT_SLOT(e), b) + (q >> 5) * 256 + 2 * ((q & 31) >> 3) + (q & 1);
#pragma unroll
        for (int i = 0; i < 6; i++) {
            const uint32_t d = (i >> 1) * 64 + 2 * lane + (i & 1);
            op[(d >> 3) * 1280 + (d & 7) * 32 + ((((q & 7) >> 1) ^ ((d & 7) >> 1)) << 3)] = __float2bfloat16(o[i] * inv);
        }
    }
}

struct PendO {
    uint32_t v[64];
    unsigned char* gp;
    static __device__ __forceinline__ uint32_t toff() {
        const uint32_t t = tid_now();
        return ((t >> 5) & 3) * 5120 + ((t >> 2) & 7) * 64 + (((t ^ (t >> 3)) & 3) << 4);
    }
    uint32_t pend, sig, bad;
    static __device__ __forceinline__ void scale(uint32_t& x, uint32_t hi, uint32_t lo) {
        asm("{\n.reg .b32 t;\nmul.rn.bf16x2 t, %0, %2;\nfma.rn.bf16x2 %0, %0, %1, t;\n}" : "+r"(x) : "r"(hi), "r"(lo));
    }
    template <int I, int OFF>
    __device__ __forceinline__ void put() {
        asm volatile("{\n.reg .pred p;\nsetp.ne.u32 p, %6, 0;\n@p st.global.v4.b32 [%0+%5], {%1,%2,%3,%4};\n}" ::"l"(gp), "r"(v[I]),
                     "r"(v[I + 1]), "r"(v[I + 2]), "r"(v[I + 3]), "n"(OFF), "r"(pend)
                     : "memory");
    }
    __device__ __forceinline__ void verdict(uint32_t sb, uint32_t W) {
        if (sig) {
            asm volatile("bar.sync %0, 160;" ::"r"(NB_VOTE + W) : "memory");
            bad = __any_sync(0xffffffffu, lds_u(sb + OFF_FB) != 0);
            pend = !bad;
        }
    }
    template <int W, int G, int H>
    __device__ __forceinline__ void half(uint32_t sb) {
        constexpr bool T2 = W == 0 ? G >= 3 : G < 3;
        constexpr int B = T2 ? 40 + 8 * (W == 0 ? G - 3 : G) : 0;
        const uint4 a = lds_u4(sb + OFF_LINV + G * 128 + H * 16 + (threadIdx.x & 3) * 32);
#pragma unroll
        for (int i = 2 * H; i < 8; i += 4) {
            scale(v[8 * G + i], a.x, a.y);
            scale(v[8 * G + i + 1], a.z, a.w);
            if (T2) {
                scale(v[B + i], a.x, a.y);
                scale(v[B + i + 1], a.z, a.w);
            }
        }
        if (H == 1) {
            put<8 * G, W * XS + G * 512>();
            put<8 * G + 4, W * XS + G * 512 + 2560>();
            if (T2) {
                put<B, 2 * XS + G * 512>();
                put<B + 4, 2 * XS + G * 512 + 2560>();
            }
            if (G == 4 && pend) nb_arrive<NB_ODONE, 288>();
        }
    }
    template <int W, int G>
    __device__ __forceinline__ void step(uint32_t sb) {
        half<W, G, 0>(sb);
        half<W, G, 1>(sb);
    }
    template <int W>
    __device__ __forceinline__ void flush(uint32_t sb) {
        step<W, 0>(sb);
        step<W, 1>(sb);
        step<W, 2>(sb);
        step<W, 3>(sb);
        step<W, 4>(sb);
    }
    __device__ __forceinline__ void clear() {
#pragma unroll
        for (int i = 0; i < 64; i++) v[i] = 0;
        gp = nullptr;
        pend = 0;
        sig = 0;
        bad = 0;
    }
};

__device__ __forceinline__ uint32_t stsm_off() {
    const uint32_t tid = tid_now(), lane = tid & 31;
    return (lane >> 4) * 1024 + (lane & 7) * 128 + (((((tid >> 4) & 6) + ((lane >> 3) & 1)) ^ (lane & 7)) << 4);
}
__device__ __forceinline__ void q_ahead(float (&q0)[80], uint32_t sb, const Ring& rn, uint32_t phm, bool valid) {
    if (valid) mbar_wait2(sb + BAR_RFULL + rn.slot * 8, rn.ph, sb + BAR_XFULL, phm & 1, rn.dl);
    const uint32_t a = ((((sb + OFF_RING) & 0x3ffff) >> 4) | LO_LBO1) + rn.slot * (SLOT >> 4);
    const uint32_t b = (((sb + OFF_R) & 0x3ffff) >> 4) | LO_LBO1;
    wg_fence();
    wgmma<1, 0, HI_SW128, false>(q0, a, b);
#pragma unroll
    for (int k = 1; k < 4; k++) wgmma<1, 0, HI_SW128, true>(q0, a + (k >> 1) * 768 + (k & 1) * 128, b + k * 2);
    wg_commit();
}
template <int W, int KK>
__device__ __forceinline__ void qproj(float (&q0)[80], float (&q1)[80], uint32_t sb, Ring& r, uint32_t pslot, uint32_t phm,
                                      PendO& po) {
    const uint32_t loR = (((sb + OFF_R) & 0x3ffff) >> 4) | LO_LBO1;
    const uint32_t loRing = (((sb + OFF_RING) & 0x3ffff) >> 4) | LO_LBO1;
    auto ready = [&](int k) {
        mbar_wait2(sb + BAR_RFULL + r.slot * 8, r.ph, sb + BAR_XFULL + (k % 5) * 8, ((phm >> (k % 5)) ^ (k / 5)) & 1, r.dl);
    };
    auto release = [&]() {
        if (KK > 0) {
            wg_wait<1>();
            mbar_arrive_warp(sb + BAR_REMPTY + pslot * 8);
            if (KK <= 5) mbar_arrive_warp(sb + (BAR_XEMPTY + (KK - 1) * 8));
        }
    };
    if (KK == 0 && W == 1) ready(0);
    if (W == 1 && KK == QHOLD) nb_sync<NB_SDONE, 256>();
    const uint32_t a = loRing + r.slot * (SLOT >> 4) + (W == 0 ? 0 : 512), b = loR + (KK % 5) * (XS >> 4);
    wg_fence();
    constexpr bool T0 = W == 1 || KK > 0;
    if (T0) wgmma<1, 0, HI_SW128, KK != 0>(q0, a, b);
    if (W == 0) wgmma<1, 0, HI_SW128, KK != 0 ? 1 : 2>(q1, a + 256, b);
#pragma unroll
    for (int k = 1; k < 4; k++) {
        if (T0) wgmma<1, 0, HI_SW128, true>(q0, a + (k >> 1) * 768 + (k & 1) * 128, b + k * 2);
        if (W == 0) wgmma<1, 0, HI_SW128, true>(q1, a + 256 + (k >> 1) * 768 + (k & 1) * 128, b + k * 2);
    }
    wg_commit();
    const uint32_t cslot = r.slot;
    r.adv(1);
    if (W == 0 || KK < QHOLD) release();
    constexpr int QST = W == 0 ? 2 : 1;
    if (KK == QST) {
        po.verdict(sb, W);
        po.template half<W, 0, 0>(sb);
    }
    if (KK < 9) ready(KK + 1);
    if (W == 1 && KK >= QHOLD) release();
    if (W == 1 && KK == 7) nb_arrive<NB_PDONE, 256>();
    if (KK == QST) po.template half<W, 0, 1>(sb);
    if constexpr (KK > QST && KK < QST + 5) po.template step<W, KK - QST>(sb);
    if constexpr (KK < (W == 0 ? 7 : 9)) {
        qproj<W, KK + 1>(q0, q1, sb, r, cslot, phm, po);
    } else if constexpr (W == 1) {
        const uint32_t sta = sb + OFF_R + 2 * XS + stsm_off();
        wg_wait<0>();
        reg_fence(q0);
        store_tile_t<false, true>(q0, sta);
        mbar_arrive_warp(sb + BAR_REMPTY + cslot * 8);
    } else {
        const uint32_t s8 = r.slot, a8 = loRing + s8 * (SLOT >> 4);
        wg_fence();
#pragma unroll
        for (int k = 0; k < 4; k++) wgmma<1, 0, HI_SW128, true>(q0, a8 + (k >> 1) * 768 + (k & 1) * 128, loR + 3 * (XS >> 4) + k * 2);
        r.adv(1);
        ready(9);
        const uint32_t s9 = r.slot, a9 = loRing + s9 * (SLOT >> 4);
        r.adv(1);
        wg_fence();
#pragma unroll
        for (int k = 0; k < 4; k++) wgmma<1, 0, HI_SW128, true>(q0, a9 + (k >> 1) * 768 + (k & 1) * 128, loR + 4 * (XS >> 4) + k * 2);
        wg_commit();
        wg_wait<1>();
        mbar_arrive_warp(sb + BAR_REMPTY + cslot * 8);
        wg_fence();
#pragma unroll
        for (int k = 0; k < 8; k++)
            wgmma<1, 0, HI_SW128, true>(q1, (k < 4 ? a8 : a9) + 256 + ((k >> 1) & 1) * 768 + (k & 1) * 128,
                                        loR + (3 + (k >> 2)) * (XS >> 4) + (k & 3) * 2);
        wg_commit();
        nb_arrive<NB_SDONE, 256>();
        sts_u(sb + OFF_GM + 4, r.slot);
        nb_sync<NB_PDONE, 256>();
        wg_wait<1>();
        reg_fence(q0);
        const uint32_t sta = sb + OFF_R + stsm_off();
        store_tile_t(q0, sta);
        wg_wait<0>();
        reg_fence(q1);
        mbar_arrive_warp(sb + BAR_REMPTY + s8 * 8);
        mbar_arrive_warp(sb + BAR_REMPTY + s9 * 8);
        store_tile_t(q1, sta + XS);
        mbar_wait(sb + BAR_RFULL + r.slot * 8, r.ph, r.dl);
    }
}

template <int NR>
__device__ __forceinline__ void opack(const float (&o)[NR], uint32_t* v) {
#pragma unroll
    for (int g = 0; g < NR / 16; g++)
#pragma unroll
        for (int hh = 0; hh < 2; hh++)
#pragma unroll
            for (int t = 0; t < 4; t++) v[8 * g + 4 * hh + t] = pack_bf16(o[16 * g + 4 * t + 2 * hh], o[16 * g + 4 * t + 2 * hh + 1]);
}

template <bool IS_S>
__device__ __forceinline__ void op_item(uint32_t e, uint32_t sb, Ring& r, uint32_t& phm) {
    constexpr int T0 = IS_S ? 0 : 2;
    constexpr uint32_t BOFF = IS_S ? (3 * 512) >> 4 : 0;
    const uint32_t loRing = (((sb + OFF_RING) & 0x3ffff) >> 4) | LO_LBO1;
    const uint32_t loO = (((sb + OFF_R) & 0x3ffff) >> 4) | LO_OST;
    float c0[80], c1[80], c2[IS_S ? 32 : 48];
    const int T = 3 * (IT_H1(e) - IT_H0(e));
    uint32_t xs = 0;
    auto step = [&](auto first, auto half) {
        constexpr bool F = decltype(first)::value;
        constexpr uint32_t hf = decltype(half)::value;
        if (hf == 0) {
            mbar_wait(sb + BAR_XFULL + xs * 8, (phm >> xs) & 1, r.dl);
            phm ^= 1u << xs;
        }
        mbar_wait(sb + BAR_RFULL + r.slot * 8, r.ph, r.dl);
        const uint32_t a = loRing + r.slot * (SLOT >> 4), b = loO + xs * (XS >> 4) + hf * 640;
        wg_fence();
        wgmma<1, 1, HI_OST, !F>(c0, a + T0 * 128, b);
        wgmma<1, 1, HI_OST, !F>(c1, a + T0 * 128 + 128, b);
        wgmma<1, 1, HI_OST, !F>(c2, a + 512, b + BOFF);
        wgmma<1, 1, HI_OST, true>(c0, a + 640 + T0 * 128, b + 320);
        wgmma<1, 1, HI_OST, true>(c1, a + 640 + T0 * 128 + 128, b + 320);
        wgmma<1, 1, HI_OST, true>(c2, a + 640 + 512, b + 320 + BOFF);
        wg_commit();
    };
    step(TrueT{}, IntT<0>{});
#pragma unroll 1
    for (int t = 1;; t++) {
        uint32_t pslot = r.slot;
        r.adv(1);
        step(FalseT{}, IntT<1>{});
        wg_wait<1>();
        mbar_arrive_warp(sb + BAR_REMPTY + pslot * 8);
        if (t == T) break;
        pslot = r.slot;
        const uint32_t pxs = xs;
        r.adv(1);
        if (++xs == 5) xs = 0;
        step(FalseT{}, IntT<0>{});
        wg_wait<1>();
        mbar_arrive_warp(sb + BAR_REMPTY + pslot * 8);
        mbar_arrive_warp_if(sb + BAR_XEMPTY + pxs * 8, t + 4 < T);
    }
    wg_wait<0>();
    reg_fence(c0);
    reg_fence(c1);
    reg_fence(c2);
    mbar_arrive_warp(sb + BAR_REMPTY + r.slot * 8);
    r.adv(1);
    nb_sync<NB_OPEND, 256>();
    const uint32_t sta = sb + OFF_R + stsm_off();
    store_tile_t(c0, sta + T0 * XS);
    store_tile_t(c1, sta + (T0 + 1) * XS);
    store_tile_t(c2, sta + 4 * XS + (IS_S ? 96 * 128 : 0));
    fence_async_smem();
    nb_arrive<NB_ODONE, 288>();
}

__device__ __forceinline__ void on_item(uint32_t W, uint32_t e, uint32_t sb, Ring& r, uint32_t& phm) {
    const uint32_t loRing = (((sb + OFF_RING) & 0x3ffff) >> 4) | LO_LBO1;
    const uint32_t loO = (((sb + OFF_R) & 0x3ffff) >> 4) | LO_OST;
    float c[80];
    const int T = 3 * (IT_H1(e) - IT_H0(e));
    uint32_t xs = 0;
    auto step = [&](auto first) {
        constexpr bool F = decltype(first)::value;
        mbar_wait2(sb + BAR_XFULL + xs * 8, (phm >> xs) & 1, sb + BAR_RFULL + r.slot * 8, r.ph, r.dl);
        phm ^= 1u << xs;
        const uint32_t a = loRing + r.slot * (SLOT >> 4) + W * 256, b = loO + xs * (XS >> 4);
        wg_fence();
        wgmma<1, 1, HI_OST, !F>(c, a, b);
#pragma unroll
        for (int k = 1; k < 4; k++) wgmma<1, 1, HI_OST, true>(c, a + (k >> 1) * 512 + (k & 1) * 128, b + k * 320);
        wg_commit();
    };
    step(TrueT{});
#pragma unroll 1
    for (int t = 1; t < T; t++) {
        const uint32_t pslot = r.slot, pxs = xs;
        r.adv(1);
        if (++xs == 5) xs = 0;
        step(FalseT{});
        wg_wait<1>();
        mbar_arrive_warp(sb + BAR_REMPTY + pslot * 8);
        mbar_arrive_warp_if(sb + BAR_XEMPTY + pxs * 8, t + 2 < T);
    }
    xs += 1 + W;
    if (xs >= 5) xs -= 5;
    mbar_wait(sb + BAR_XFULL + xs * 8, (phm >> xs) & 1, r.dl);
    wg_wait<0>();
    reg_fence(c);
    store_tile_t<true>(c, sb + OFF_R + xs * XS + stsm_off());
    fence_async_smem();
    nb_arrive<NB_ODONE, 288>();
}

template <int W>
__device__ __forceinline__ uint32_t qa_item(uint32_t e, uint32_t sb, Ring& r, uint32_t phm, PendO& po, float (&q0)[80],
                                            float (&oa)[80], int it) {
    const uint32_t loR = (((sb + OFF_R) & 0x3ffff) >> 4) | LO_LBO1;
    const uint32_t loRing = (((sb + OFF_RING) & 0x3ffff) >> 4) | LO_LBO1;
    qproj<W, 0>(q0, oa, sb, r, 0, phm, po);
    fence_async_smem();
    TSD(W, 1);
    float s[80], ob[W == 0 ? 32 : 48], l[10];
    if (W == 1) {
        nb_arrive<NB_Q2, 256>();
        zero(oa);
        zero(ob);
        reg_fence(oa);
        reg_fence(ob);
    }
    const uint32_t lane = tid_now() & 31, sta = sb + OFF_R + stsm_off();
    auto pv = [&](auto first, uint32_t buf) {
        constexpr bool F = decltype(first)::value;
        if (F) mbar_wait(sb + BAR_RFULL + r.slot * 8, r.ph, r.dl);
        const uint32_t a = loRing + r.slot * (SLOT >> 4), b = loR + (3 + buf) * (XS >> 4);
        wg_fence();
        wgmma<1, 0, HI_SW128, F ? 2 : 1, HI_KV>(oa, a + W * 64, b);
        wgmma<1, 0, HI_SW128, !F, HI_KV>(ob, a + 128, b + (W == 0 ? (96 * 128) >> 4 : 0));
#pragma unroll
        for (int k = 1; k < 4; k++) {
            wgmma<1, 0, HI_SW128, true, HI_KV>(oa, a + W * 64 + k * 384, b + k * 2);
            wgmma<1, 0, HI_SW128, true, HI_KV>(ob, a + 128 + k * 384, b + (W == 0 ? (96 * 128) >> 4 : 0) + k * 2);
        }
        wg_commit();
    };
    zero(l);
    float mref;
    uint32_t kslot, vslot, nx = 0;
    auto tail = [&](auto first, int i) {
        constexpr bool rel_other = !decltype(first)::value;
        uint32_t ps[40];
        exp_block<0>(s, ps, sta + (3 + W) * XS, mref);
        if (rel_other) {
            wg_wait<0>();
            mbar_arrive_warp(sb + BAR_REMPTY + vslot * 8);
            if (W == 1) mbar_arrive_warp_if(sb + BAR_XEMPTY + 24, i == 3);
        }
        fence_async_smem();
        nb_arrive<NB_PFULL + W, 256>();
        TSD(W, 6 + 5 * i);
        if (W == 1) {
            mbar_arrive_warp_if<2>(sb + BAR_XEMPTY + 8, i == 3);
            mbar_arrive_warp_if<2>(sb + BAR_XEMPTY + 16, i == 3);
        }
        if (rel_other) {
            mbar_wait(sb + BAR_RFULL + r.slot * 8, r.ph, r.dl);
            sum_block(ps, l, lane);
        }
        if (W == 0 && i == 3) nx = get_item_warp(sb, it + 1, r.dl);
        TSD(W, 7 + 5 * i);
        nb_sync<NB_W + W, 128>();
        pv(first, W);
        if (!rel_other) sum_block(ps, l, lane);
        TSD(W, 8 + 5 * i);
    };
    if (W == 0) {
        nb_sync<NB_QK, 160>();
        TSD(W, 2);
        wg_fence();
        qk_steps<0, 8>(s, loRing + r.slot * (SLOT >> 4), loR);
        nb_sync<NB_Q2, 256>();
        qk_steps<8, 12>(s, loRing + r.slot * (SLOT >> 4), loR);
        wg_commit();
        nb_arrive<NB_Q01, 256>();
        TSD(W, 4);
        nb_sync<NB_REF, 160>();
        mref = __uint_as_float(lds_u(sb + OFF_GM));
        wg_wait<0>();
        reg_fence(s);
        mbar_arrive_warp<2>(sb + BAR_REMPTY + r.slot * 8);
        r.adv(2);
        TSD(W, 5);
        tail(TrueT{}, 0);
    } else {
        nb_sync<NB_Q01, 256>();
    }
#pragma unroll 1
    for (int i = (W == 0 ? 1 : 0); i < 4; i++) {
        const uint32_t pvslot = r.slot;
        r.adv(1);
        kslot = r.slot;
        mbar_wait(sb + BAR_RFULL + r.slot * 8, r.ph, r.dl);
        wg_fence();
        qk_steps<0, 4>(s, loRing + r.slot * (SLOT >> 4), loR);
        if (W == 1) wg_commit();
        qk_steps<4, 12>(s, loRing + r.slot * (SLOT >> 4), loR);
        wg_commit();
        wg_wait<1>();
        if (W == 1) mbar_arrive_warp_if(sb + BAR_XEMPTY + 0, i == 3);
        mbar_arrive_warp_if(sb + BAR_REMPTY + pvslot * 8, W == 0 || i > 0);
        r.adv(1);
        vslot = r.slot;
        TSD(W, 4 + 5 * i);
        mbar_wait(sb + BAR_RFULL + r.slot * 8, r.ph, r.dl);
        nb_sync<NB_PFULL + (W ^ 1), 256>();
        pv(FalseT{}, W ^ 1);
        if (W == 1) mref = __uint_as_float(lds_u(sb + OFF_GM));
        wg_wait<1>();
        reg_fence(s);
        mbar_arrive_warp<2>(sb + BAR_REMPTY + kslot * 8);
        if (W == 0) mbar_arrive_warp_if(sb + BAR_XEMPTY + 0, i == 3);
        r.adv(W == 1 && i == 3 ? 1 : 2);
        TSD(W, 5 + 5 * i);
        tail(FalseT{}, i);
    }
    if (W == 1) nx = get_item_warp(sb, it + 1, r.dl);
    if (W == 0) {
        Ring rn = r;
        rn.adv(2);
        q_ahead(q0, sb, rn, phm, IT_TYPE(nx) == IT_QA);
        TSD(W, 25);
    }
    const uint32_t w = (tid_now() >> 5) & 3;
    const uint32_t lxa = sb + OFF_LX + w * 640 + (((lane & 8) ? 80 : 0) + ((lane >> 1) & 8) + 2 * (lane & 3) + ((lane >> 2) & 1)) * 4;
    po.gp = ostash(IT_SLOT(e), IT_B(e)) + po.toff();
    po.sig = 1;
    if (W == 0) {
        sum_store<false>(l, lane, lxa);
        nb_arrive<NB_LX, 256>();
        wg_wait<1>();
        mbar_arrive_warp(sb + BAR_REMPTY + r.slot * 8);
        mbar_arrive_warp(sb + BAR_XEMPTY + 24);
        r.adv(1);
        mbar_wait(sb + BAR_RFULL + r.slot * 8, r.ph, r.dl);
        nb_sync<NB_PFULL + 1, 256>();
        pv(FalseT{}, 1);
    } else {
        nb_sync<NB_LX, 256>();
        sum_store<true>(l, lane, lxa);
        nb_arrive<NB_L, 160>();
    }
    TSD(W, 24);
    wg_wait<0>();
    reg_fence(oa);
    reg_fence(ob);
    mbar_arrive_warp(sb + BAR_REMPTY + r.slot * 8);
    mbar_arrive_warp(sb + BAR_XEMPTY + 32);
    r.adv(1);
    opack(ob, po.v + 40);
    opack(oa, po.v);
    return nx;
}

template <int W>
__device__ __forceinline__ uint32_t qa_run(uint32_t e, uint32_t sb, Ring& r, uint32_t phm, PendO& po, int& it) {
    float q0[80], oa[80];
    if (W == 0) {
        zero(oa);
        q_ahead(q0, sb, r, phm, true);
        wg_wait<0>();
    }
#pragma unroll 1
    do {
        TS(W, 0);
        if (W == 0) TS_ITEM(e);
        e = qa_item<W>(e, sb, r, phm, po, q0, oa, it);
        TS(W, 31);
        it++;
    } while (IT_TYPE(e) == IT_QA && !po.bad);
    if (W == 0) {
#pragma unroll
        for (int i = 56; i < 64; i++) po.v[i] = 0;
    }
    return e;
}

__device__ __forceinline__ void consumer(const Params& P, uint32_t W, uint32_t sb, uint32_t dl) {
    int it = 0;
    Ring r{0, 0, dl};
    uint32_t phm = 0;
    uint32_t e = get_item_warp(sb, 0, dl);
#pragma unroll 1
    while (true) {
        if (IT_TYPE(e) == IT_QA) {
            PendO po;
            po.clear();
            e = W == 0 ? qa_run<0>(e, sb, r, phm, po, it) : qa_run<1>(e, sb, r, phm, po, it);
#pragma unroll 1
            for (int m = po.bad ? 2 : 1; m > 0; m--) {
                if (m == 1) {
                    po.verdict(sb, W);
                    if (W == 0) po.flush<0>(sb);
                    else po.flush<1>(sb);
                }
                if (po.bad) {
                    if (W == 0) fallback_unit(P, lds_u(sb + OFF_ITEM + (it - m) * 4), tid_now() & 127);
                    __syncwarp();
                    nb_sync<NB_ODONE, 288>();
                }
            }
        }
        if (e == 0) break;
        if (IT_TYPE(e) == IT_QA) continue;
        TS(W, 0);
        if (W == 0) TS_ITEM(e);
        if (IT_TYPE(e) == IT_ON) on_item(W, e, sb, r, phm);
        else if (W == 0) op_item<true>(e, sb, r, phm);
        else op_item<false>(e, sb, r, phm);
        TS(W, 31);
        e = get_item_warp(sb, ++it, dl);
    }
    TS_DUMP(W);
}

__global__ void __cluster_dims__(2, 1, 1) __launch_bounds__(384, 1) fused_kernel(const __grid_constant__ Params P) {
    extern __shared__ __align__(1024) unsigned char smem_raw[];
    const uint32_t sb = (uint32_t)__cvta_generic_to_shared(smem_raw);
    const uint32_t warp = __shfl_sync(0xffffffffu, threadIdx.x >> 5, 0), wgid = warp >> 2;
    const uint32_t cta = blockIdx.x;
    const uint32_t dl = deadline();

    if (threadIdx.x == 128) {
#pragma unroll
        for (int i = 0; i < NSLOT; i++) {
            mbar_init(sb + BAR_RFULL + i * 8, 1);
            mbar_init(sb + BAR_REMPTY + i * 8, 8);
            mbar_init(sb + BAR_XFULL + i * 8, 1);
            mbar_init(sb + BAR_XEMPTY + i * 8, 8);
        }
        asm volatile("fence.mbarrier_init.release.cluster;" ::: "memory");
        fence_async_smem();
    } else if (threadIdx.x == 160) {
#pragma unroll
        for (int i = 0; i < NSLOT + MAXI; i++) mbar_init(sb + BAR_PRDY + i * 8, 1);
        asm volatile("fence.mbarrier_init.release.cluster;" ::: "memory");
    } else if (threadIdx.x == 0) {
        sts_u(sb + OFF_ITEM, P.cl[cta >> 1].items[0] ? P.cl[cta >> 1].items[0] + 8 * (cta & 1) : 0);
        sts_u(sb + OFF_FB, P.cl[cta >> 1].delay);
    } else if (threadIdx.x == 64) {
        if (sb & 1023) __trap();
        asm volatile("prefetch.tensormap [%0];" ::"l"(&P.wq[0]) : "memory");
        asm volatile("prefetch.tensormap [%0];" ::"l"(&P.x[0]) : "memory");
    }
    __syncthreads();
    {
        const int it = 0;
        if (wgid == 1) TS(0, 30);
    }
    asm volatile("barrier.cluster.arrive.relaxed.aligned;" ::: "memory");
    if (warp < 3) {
        const uint32_t e = __shfl_sync(0xffffffffu, lds_u(sb + OFF_ITEM), 0), d = lds_u(sb + OFF_FB);
        const uint64_t pol = pol_shared();
        const bool isx = warp == 1, lead = (threadIdx.x & 31) == 0;
        uint32_t t0, t1;
        asm volatile("mov.u32 %0, %%clock;" : "=r"(t0));
        do {
            asm volatile("mov.u32 %0, %%clock;" : "=r"(t1));
        } while (t1 - t0 < d);
        __syncwarp();
#pragma unroll 1
        for (int n = 0; n < (e ? NSLOT : 0); n++) {
            const uint32_t bar = sb + (isx ? BAR_XFULL : BAR_RFULL) + n * 8;
            if (lead) {
                if (warp < 2) mbar_expect(bar, isx ? XS : SLOT);
                tma3(sb + (isx ? OFF_R + n * XS : OFF_RING + n * SLOT + warp * (SLOT / 4)), isx ? &P.x[0] : &P.wq[0],
                     isx ? IT_B(e) * 160 : n * 64 + warp * 16, isx ? n : IT_H0(e) * 3, bar, pol);
            }
        }
        if (threadIdx.x == 0) asm volatile("mbarrier.arrive.shared::cta.b64 _, [%0];" ::"r"(sb + BAR_ITEM) : "memory");
        __syncwarp();
    }

    if (wgid == 0) {
        asm volatile("setmaxnreg.dec.sync.aligned.u32 24;");
        if (warp == 0) {
            const bool lead = threadIdx.x == 0;
            const uint64_t pol_first = pol_stream(), pol_norm = pol_shared();
            uint32_t e = __shfl_sync(0xffffffffu, lds_u(sb + OFF_ITEM), 0);
            asm volatile("barrier.cluster.wait.aligned;" ::: "memory");
            unsigned int* const ticket = &g_ticket[next_epoch(0) & 1];
            const uint32_t rank = cta & 1;
            uint32_t peer;
            asm volatile("mapa.shared::cluster.u32 %0, %1, %2;" : "=r"(peer) : "r"(sb), "r"(rank ^ 1));
            Ring r{0, 0, dl};
            uint32_t pm = 0;
            auto load_w = [&](const CUtensorMap* m, int row, int blk, uint32_t half_bytes) {
                mbar_wait(sb + BAR_REMPTY + r.slot * 8, r.ph, dl);
                if (lead) {
                    mbar_expect(sb + BAR_RFULL + r.slot * 8, 2 * half_bytes);
                    asm volatile("mbarrier.arrive.shared::cluster.b64 _, [%0];" ::"r"(peer + BAR_PRDY + r.slot * 8) : "memory");
                }
                mbar_wait(sb + BAR_PRDY + r.slot * 8, (pm >> r.slot) & 1, dl);
                pm ^= 1u << r.slot;
                if (lead) tma3_mc(sb + OFF_RING + r.slot * SLOT + rank * half_bytes, m, row, blk, sb + BAR_RFULL + r.slot * 8, pol_norm);
                r.adv(1);
            };
#pragma unroll 1
            for (int it = 0; e != 0; it++) {
                uint32_t nx = 0, tk = 0;
                if (rank == 0 && IT_TYPE(e) != IT_ON && it + 2 < MAXI) nx = it + 1 < NSTAT ? P.cl[cta >> 1].items[it + 1] : IT_DYN;
                const uint32_t br = IT_BR(e);
                if (IT_TYPE(e) == IT_QA) {
                    const uint32_t h = IT_H0(e);
#pragma unroll 1
                    for (int kk = it ? 0 : NSLOT; kk < 10; kk++) load_w(&P.wq[br], kk * 64 + rank * 32, h * 3, SLOT / 2);
                    const int grp0 = (IT_B(e) * 32 + h) * 64;
#pragma unroll 1
                    for (int n = 0; n < 16; n++) {
                        if (n == 13 && nx == IT_DYN && lead) tk = atomicAdd(ticket, 1);
                        const bool isv = n == 15 || (n > 0 && !(n & 1));
                        const int j = n == 15 ? 7 : isv ? (n - 2) >> 1 : (n + 1) >> 1;
                        mbar_wait(sb + BAR_REMPTY + r.slot * 8, r.ph, dl);
                        if (lead) {
                            mbar_expect(sb + BAR_RFULL + r.slot * 8, SLOT);
                            asm volatile(
                                "cp.async.bulk.tensor.4d.shared::cluster.global.mbarrier::complete_tx::bytes.L2::cache_hint"
                                " [%0], [%1, {%3,%3,%3,%4}], [%2], %5;" ::"r"(sb + OFF_RING + r.slot * SLOT),
                                "l"(isv ? &P.v[br] : &P.k[br]), "r"(sb + BAR_RFULL + r.slot * 8), "r"(0), "r"(grp0 + j * 8), "l"(pol_first)
                                : "memory");
                        }
                        r.adv(1);
                    }
                } else {
                    const bool wide = IT_TYPE(e) == IT_OP;
                    const int step = wide ? 32 : 64, r1 = IT_H1(e) * 192;
#pragma unroll 1
                    for (int row = IT_H0(e) * 192 + rank * (step >> 1); row < r1; row += step)
                        load_w(wide ? &P.wo[br] : &P.won[br], row, IT_HALF(e) * (wide ? 5 : 2), wide ? XS / 2 : 8192);
                    if (nx == IT_DYN && lead) tk = atomicAdd(ticket, 1);
                }
                if (rank == 0) {
                    if (nx == IT_DYN) {
                        tk = __shfl_sync(0xffffffffu, tk, 0);
                        nx = tk < P.nlist ? P.list[tk] : 0;
                    }
                    e = nx;
                    if (lead) {
                        asm volatile("st.async.weak.shared::cluster.mbarrier::complete_tx::bytes.b32 [%0], %1, [%2];" ::"r"(
                                         peer + OFF_ITEM + 4 + it * 4),
                                     "r"(e ? e + 8 : 0), "r"(peer + BAR_ITEM + 8 + it * 8)
                                     : "memory");
                        sts_u(sb + OFF_ITEM + 4 + it * 4, e);
                        asm volatile("mbarrier.arrive.shared::cta.b64 _, [%0];" ::"r"(sb + BAR_ITEM + 8 + it * 8) : "memory");
                    }
                } else {
                    if (lead) mbar_expect(sb + BAR_ITEM + 8 + it * 8, 4);
                    e = get_item_warp(sb, it + 1, dl);
                }
            }
        } else if (warp == 1) {
            const uint64_t pol_norm = pol_shared(), pol_o = pol_stream();
            const bool lead = threadIdx.x == 32;
            uint32_t phm = 0, epoch = 0;
#pragma unroll 1
            for (int it = 0;; it++) {
                const uint32_t e = get_item_warp(sb, it, dl);
                if (it == 1 || (it == 0 && e == 0)) epoch = next_epoch(1);
                if (e == 0) break;
                const uint32_t br = IT_BR(e);
                uint32_t xs = 0;
                auto acquire = [&]() {
                    mbar_wait(sb + BAR_XEMPTY + xs * 8, (phm >> xs) & 1, dl);
                    phm ^= 1u << xs;
                    if (lead) mbar_expect(sb + BAR_XFULL + xs * 8, XS);
                };
                if (IT_TYPE(e) == IT_QA) {
#pragma unroll 1
                    for (int kk = it ? 0 : 5; kk < 10; kk++) {
                        acquire();
                        if (lead) tma3(sb + OFF_R + xs * XS, &P.x[br], IT_B(e) * 160, kk, sb + BAR_XFULL + xs * 8, pol_norm);
                        if (++xs == 5) xs = 0;
                    }
                } else {
                    const unsigned int* fp = g_flag + (br * 16 + IT_B(e)) * 64 + (threadIdx.x & 31);
                    uint32_t hm = 0, pm = 0;
                    auto poll = [&](uint32_t hneed, uint32_t pneed) {
                        if ((hm & hneed) == hneed && (pm & pneed) == pneed) return;
                        uint32_t n = 0;
                        do {
                            uint32_t a, b;
                            asm volatile("ld.acquire.gpu.global.u32 %0, [%2];\nld.acquire.gpu.global.u32 %1, [%2+128];"
                                         : "=r"(a), "=r"(b) : "l"(fp) : "memory");
                            hm = __ballot_sync(0xffffffffu, a == epoch);
                            pm = __ballot_sync(0xffffffffu, b == epoch);
                            if (++n > 0x1000000) __trap();
                        } while ((hm & hneed) != hneed || (pm & pneed) != pneed);
                        __syncwarp();
                        asm volatile("fence.proxy.async.global;" ::: "memory");
                    };
#pragma unroll 1
                    for (uint32_t h = IT_H0(e); h < IT_H1(e); h++) {
                        poll(1u << h, 0);
                        const unsigned char* src = ostash(P.slot[br * 32 + h], IT_B(e));
#pragma unroll 1
                        for (int t = 0; t < 3; t++) {
                            acquire();
                            if (lead) bulk_load(sb + OFF_R + xs * XS, src + t * XS, XS, sb + BAR_XFULL + xs * 8, pol_o);
                            if (++xs == 5) xs = 0;
                        }
                        if (IT_TYPE(e) == IT_OP && h >= 1) {
                            const uint32_t x1 = xs == 4 ? 0 : xs + 1;
                            mbar_wait(sb + BAR_XFULL + xs * 8, (phm >> xs) & 1, dl);
                            mbar_wait(sb + BAR_XFULL + x1 * 8, (phm >> x1) & 1, dl);
                            if (lead)
                                asm volatile("st.relaxed.gpu.global.u32 [%0], %1;" ::"l"(fp + 34 + IT_HALF(e)), "r"(epoch * 64 + h) : "memory");
                        }
                    }
                    if (IT_TYPE(e) == IT_ON) {
                        poll(0, IT_HALF(e) < 2 ? 1 : IT_HALF(e) == 2 ? 3 : 2);
#pragma unroll 1
                        for (uint32_t tile = 2 * IT_HALF(e); tile < 2 * IT_HALF(e) + 2; tile++) {
                            acquire();
                            if (lead)
                                asm volatile(
                                    "cp.async.bulk.tensor.5d.shared::cluster.global.mbarrier::complete_tx::bytes [%0], [%1, {%3,%5,%5,%5,%4}], [%2];" ::"r"(
                                        sb + OFF_R + xs * XS),
                                    "l"(&P.out), "r"(sb + BAR_XFULL + xs * 8), "r"(br * 640 + tile * 64), "r"(IT_B(e) * 5), "r"(0)
                                    : "memory");
                            if (++xs == 5) xs = 0;
                        }
                    }
                }
            }
        } else if (warp == 2) {
            asm volatile("barrier.cluster.wait.aligned;" ::: "memory");
            const uint32_t epoch = next_epoch(2);
            if (cta == 0) g_ticket[(epoch + 1) & 1] = 0;
#pragma unroll 1
            for (int it = 0;; it++) {
                const uint32_t e = get_item_warp(sb, it, dl);
                if (e == 0) break;
                nb_sync<NB_ODONE, 288>();
                if (threadIdx.x == 64) {
                    const uint32_t bb = IT_BR(e) * 16 + IT_B(e);
                    if (IT_TYPE(e) != IT_QA) {
                        const bool wide = IT_TYPE(e) == IT_OP;
                        if (wide)
                            asm volatile("st.relaxed.gpu.global.u32 [%0], %1;" ::"l"(&g_flag[bb * 64 + 34 + IT_HALF(e)]),
                                         "r"(epoch * 64 + IT_H1(e))
                                         : "memory");
                        const int cc0 = IT_BR(e) * 640 + IT_HALF(e) * (wide ? 320 : 128);
                        uint32_t xs = wide ? 0 : (3 * (IT_H1(e) - IT_H0(e))) % 5;
#pragma unroll 1
                        for (int m = 0; m < (wide ? 5 : 2); m++) {
                            asm volatile("cp.async.bulk.tensor.5d.global.shared::cta.bulk_group [%0, {%2,%4,%4,%4,%3}], [%1];" ::"l"(&P.out),
                                         "r"(sb + OFF_R + xs * XS), "r"(cc0 + m * 64), "r"((int)IT_B(e) * 5), "r"(0)
                                         : "memory");
                            asm volatile("cp.async.bulk.commit_group;" ::: "memory");
                            if (wide && m >= 1) {
                                asm volatile("cp.async.bulk.wait_group.read 1;" ::: "memory");
                                asm volatile("mbarrier.arrive.shared::cta.b64 _, [%0], 8;" ::"r"(sb + BAR_XEMPTY + (m - 1) * 8) : "memory");
                            }
                            if (++xs == 5) xs = 0;
                        }
                        if (wide) {
                            asm volatile("cp.async.bulk.wait_group.read 0;" ::: "memory");
                            asm volatile("mbarrier.arrive.shared::cta.b64 _, [%0], 8;" ::"r"(sb + BAR_XEMPTY + 32) : "memory");
                        }
                        if (IT_PART(e)) {
                            asm volatile("cp.async.bulk.wait_group 0;" ::: "memory");
                            asm volatile("fence.proxy.async.global;" ::: "memory");
                        }
                    }
                    if (IT_TYPE(e) == IT_QA || IT_PART(e)) {
                        unsigned int* f = &g_flag[bb * 64 + (IT_TYPE(e) == IT_QA ? IT_H0(e) : 32 + IT_HALF(e))];
                        asm volatile("st.release.gpu.global.u32 [%0], %1;" ::"l"(f), "r"(epoch) : "memory");
                    }
                }
                __syncwarp();
            }
            if (threadIdx.x == 64) asm volatile("cp.async.bulk.wait_group 0;" ::: "memory");
            __syncwarp();
            asm volatile("barrier.cluster.arrive.relaxed.aligned;\nbarrier.cluster.wait.aligned;" ::: "memory");
        } else {
            const uint32_t lane = threadIdx.x & 31, p = lane >> 3;
            const uint32_t epoch = next_epoch(3);
#pragma unroll 1
            for (int it = 0;; it++) {
                const uint32_t e = get_item_warp(sb, it, dl);
                if (e == 0) break;
                if (IT_TYPE(e) != IT_QA) continue;
                nb_sync<NB_QK, 160>();
                const uint32_t ka = sb + OFF_RING + lds_u(sb + OFF_GM + 4) * SLOT + p * (2 * 3072 + 256) + (lane & 7) * 16;
                const uint32_t qa = sb + OFF_R + p * 256 + (lane & 7) * 16;
                uint32_t acc = 0;
#pragma unroll 1
                for (int c = 0; c < 3; c++) {
                    const uint4 k = lds_u4(ka + c * 1024);
                    if (c == 2) nb_sync<NB_L, 160>();
                    const uint4 q = lds_u4(qa + c * XS);
                    acc = fma_bf2(k.x, q.x, fma_bf2(k.y, q.y, fma_bf2(k.z, q.z, fma_bf2(k.w, q.w, acc))));
                }
                const float d = __uint_as_float(acc << 16) + __uint_as_float(acc & 0xffff0000u);
                const int sum = __reduce_add_sync(0xffffffffu, __float2int_rn(d * 16.f));
                sts_f(sb + OFF_GM, fmaf((float)sum, SM_C / 64.f, 24.f));
                nb_arrive<NB_REF, 160>();
                if (IT_DEP(e)) {
                    const uint32_t g = IT_DEP(e) - 1, need = epoch * 64 + (g & 31) + 1;
                    const unsigned int* cp = &g_flag[((g >> 5) * 16 + IT_B(e)) * 64 + 34 + (lane & 1)];
                    for (uint32_t n = 0;; n++) {
                        uint32_t v;
                        asm volatile("ld.acquire.gpu.global.u32 %0, [%1];" : "=r"(v) : "l"(cp) : "memory");
                        if (__all_sync(0xffffffffu, v - need < 64)) break;
                        if (n > 0x800000) __trap();
                        __nanosleep(500);
                    }
                }
                nb_sync<NB_L, 160>();
                bool bad = false;
#pragma unroll
                for (int c = 0; c < 5; c++) {
                    const uint32_t la = sb + OFF_LX + (c * 32 + lane) * 4;
                    const float v = (__uint_as_float(lds_u(la)) + __uint_as_float(lds_u(la + 640))) +
                                    (__uint_as_float(lds_u(la + 1280)) + __uint_as_float(lds_u(la + 1920)));
                    const float inv = __fdividef(1.f, v);
                    const uint32_t hi = pack_bf16(inv, 0.f), lo = pack_bf16(inv - __uint_as_float(hi << 16), 0.f);
                    const uint32_t ia = sb + OFF_LINV + c * 128 + ((lane >> 1) & 3) * 32 + (lane >> 3) * 8 + (lane & 1) * 2;
                    asm volatile("st.shared.u16 [%0], %1;\nst.shared.u16 [%0+4], %2;" ::"r"(ia), "h"((unsigned short)hi), "h"((unsigned short)lo) : "memory");
                    bad |= !(v >= 5.421010862e-20f && v <= 7.9228163e28f);
                }
                sts_u(sb + OFF_FB, __any_sync(0xffffffffu, bad));
                nb_arrive<NB_VOTE, 160>();
                nb_arrive<NB_VOTE + 1, 160>();
            }
        }
    } else {
        asm volatile("setmaxnreg.inc.sync.aligned.u32 240;");
        consumer(P, wgid - 1, sb, dl);
    }
}

typedef CUresult (*EncFn)(CUtensorMap*, CUtensorMapDataType, cuuint32_t, void*, const cuuint64_t*, const cuuint64_t*,
                          const cuuint32_t*, const cuuint32_t*, CUtensorMapInterleave, CUtensorMapSwizzle,
                          CUtensorMapL2promotion, CUtensorMapFloatOOBfill);

void make_map3(EncFn enc, CUtensorMap* m, void* p, uint64_t rows, uint64_t rowbytes, uint64_t nblk, uint32_t boxrows,
               uint32_t boxblk) {
    cuuint64_t dims[3] = {64, rows, nblk};
    cuuint64_t str[2] = {rowbytes, 128};
    cuuint32_t box[3] = {64, boxrows, boxblk};
    cuuint32_t es[3] = {1, 1, 1};
    enc(m, CU_TENSOR_MAP_DATA_TYPE_BFLOAT16, 3, p, dims, str, box, es, CU_TENSOR_MAP_INTERLEAVE_NONE,
        CU_TENSOR_MAP_SWIZZLE_128B, CU_TENSOR_MAP_L2_PROMOTION_NONE, CU_TENSOR_MAP_FLOAT_OOB_FILL_NONE);
}

constexpr int tune(const char*, int def) { return def; }

void build_schedule(Params& P, int ncl) {
    const int mode = tune("MODE", 4), dmax = tune("DMAX", 24200), n0 = tune("N0", 10);
    const int H0[8] = {19, 20, 21, 22, 22, 24, 25, 25}, P0[8] = {367, 337, 335, 331, 338, 335, 333, 332};
    const int ra = tune("RA", 10), ga = tune("GA", 17), rb = tune("RB", 11), g1 = tune("G1", 58);
    int dep[64];
    for (int g = 0, ns = 0, live = 0; g < 64; g++) {
        const bool fresh = mode < 3 || g >= g1 || live < (g < ga ? ra : rb);
        dep[g] = fresh ? 0 : g - live + 1;
        P.slot[g] = fresh ? ns++ : P.slot[g - live];
        live += fresh;
    }
    int H[8], pos[8], psum = 0;
    for (int b = 0; b < 8; b++) {
        const char nh[3] = {'H', (char)('0' + b), 0}, np[3] = {'P', (char)('0' + b), 0};
        H[b] = tune(nh, H0[b]);
        pos[b] = tune(np, P0[b]);
        psum += pos[b];
    }
    const int sk = tune("SK", 10), g0 = tune("G0", 20), g2 = tune("G2", 40);
    int ord[512], nxt[8] = {0, 0, 0, 0, 0, 0, 0, 0};
    for (int k = 0; k < 512; k++) {
        int best = -1;
        float bkey = 0.f;
        for (int b = 0; b < 8; b++) {
            const int g = nxt[b];
            if (g == 64) continue;
            const float w = g < g0 ? 0.f : g < 32 ? (g - g0) / (32.f - g0) : g < g2 ? 1.f : (64 - g) / (64.f - g2);
            const float key = g + w * sk * 0.1f * (pos[b] - psum / 8.f) / 8.f;
            if (best < 0 || key < bkey) best = b, bkey = key;
        }
        ord[k] = nxt[best]++ * 8 + best;
        const int d = dep[ord[k] >> 3];
        if (d > 32) {
            if (pos[best] > k) pos[best] = k;
            if (H[best] < d - 32) H[best] = d - 32;
        }
    }
    int u = 0;
    auto unit = [&]() {
        const int v = ord[u++];
        return mk_item(IT_QA, v >> 8, (v & 7) * 2, (v >> 3) & 31, P.slot[v >> 3], 0) | (dep[v >> 3] << 23);
    };
    int qa[NCL], nq = 0, op[NCL], no = 0;
    for (int c = 0; c < ncl; c++) {
        P.cl[c].delay = 0;
        for (int i = 0; i < NSTAT; i++) P.cl[c].items[i] = 0;
        if (mode >= 3 && c >= 4 && c < 20) op[((c - 4) & 7) * 2 + ((c - 4) >> 3)] = c, no++;
        else if (mode != 2 || (c & 3) == 0) qa[nq++] = c;
    }
    for (int t = 0; t < no; t++) {
        P.cl[op[t]].items[1] = mk_item(IT_OP, 0, t & ~1, 0, 32, t & 1);
        P.cl[op[t]].items[2] = IT_DYN;
            }
    for (int k = 0; k < nq; k++) {
        const int c = qa[(k * (nq % 19 ? 19 : 17)) % nq];
        P.cl[c].items[1] = P.cl[c].items[2] = IT_DYN;
        P.cl[c].delay = k < n0 ? 0 : dmax * (k + 1 - n0) / (nq - n0);
    }
    for (int k = u; k < no + nq; k++) {
        int best = -1;
        for (int c = 0; c < ncl; c++)
            if (P.cl[c].items[1] && !P.cl[c].items[0] && (best < 0 || P.cl[c].delay < P.cl[best].delay)) best = c;
        P.cl[best].items[0] = unit();
    }
    int n = 0;
    const int uend = mode == 2 ? 8 * nq : 512;
    while (u < uend) {
        for (int b = 0; b < 8 && no; b++)
            if (pos[b] == u) {
                P.list[n++] = mk_item(IT_OP, 1, 2 * b, 0, H[b], 0, 1);
                P.list[n++] = mk_item(IT_OP, 1, 2 * b, 0, H[b], 1, 1);
            }
        P.list[n++] = unit();
    }
    for (int k = 0; no && k < 40; k++) P.list[n++] = mk_item(IT_ON, 1, k / 5 * 2, H[k / 5], 32, k % 5);
    P.nlist = n;
}

}

extern "C" void kernel_launch(void* const* d_in, const int* in_sizes, int n_in, void* d_out, int out_size) {
    static Params P;
    static bool init = false;
    static int ncl = NCL;
    if (!init) {
        EncFn enc = nullptr;
        cudaDriverEntryPointQueryResult qr;
        cudaGetDriverEntryPoint("cuTensorMapEncodeTiled", (void**)&enc, cudaEnableDefault, &qr);
        for (int i = 0; i < 2; i++) {
            P.px[i] = (const __nv_bfloat16*)d_in[5 * i + 0];
            P.pk[i] = (const __nv_bfloat16*)d_in[5 * i + 1];
            P.pv[i] = (const __nv_bfloat16*)d_in[5 * i + 2];
            P.pwq[i] = (const __nv_bfloat16*)d_in[5 * i + 3];
            make_map3(enc, &P.x[i], d_in[5 * i + 0], 2560, 1280, 10, 160, 1);
            for (int j = 0; j < 2; j++) {
                cuuint64_t dims[4] = {64, 8, 3, 16 * 32 * 64};
                cuuint64_t str[3] = {384, 128, 3072};
                cuuint32_t box[4] = {64, 8, 3, 8};
                cuuint32_t es[4] = {1, 1, 1, 1};
                enc(j ? &P.v[i] : &P.k[i], CU_TENSOR_MAP_DATA_TYPE_BFLOAT16, 4, d_in[5 * i + 1 + j], dims, str, box, es,
                    CU_TENSOR_MAP_INTERLEAVE_NONE, CU_TENSOR_MAP_SWIZZLE_128B, CU_TENSOR_MAP_L2_PROMOTION_NONE,
                    CU_TENSOR_MAP_FLOAT_OOB_FILL_NONE);
            }
            make_map3(enc, &P.wq[i], d_in[5 * i + 3], 640, 12288, 96, 32, 3);
            make_map3(enc, &P.wo[i], d_in[5 * i + 4], 6144, 1280, 10, 16, 5);
            make_map3(enc, &P.won[i], d_in[5 * i + 4], 6144, 1280, 10, 32, 2);
        }
        cuuint64_t dims[5] = {1280, 2, 4, 4, 80};
        cuuint64_t str[4] = {2560, 8 * 2560, 2 * 2560, 32 * 2560};
        cuuint32_t box[5] = {64, 2, 4, 4, 5};
        cuuint32_t es[5] = {1, 1, 1, 1, 1};
        enc(&P.out, CU_TENSOR_MAP_DATA_TYPE_BFLOAT16, 5, d_out, dims, str, box, es, CU_TENSOR_MAP_INTERLEAVE_NONE,
            CU_TENSOR_MAP_SWIZZLE_128B, CU_TENSOR_MAP_L2_PROMOTION_NONE, CU_TENSOR_MAP_FLOAT_OOB_FILL_NONE);
        cudaFuncSetAttribute(fused_kernel, cudaFuncAttributeMaxDynamicSharedMemorySize, SMEM_LAUNCH);
        cudaLaunchConfig_t cfg = {};
        cfg.gridDim = dim3(NCTA);
        cfg.blockDim = dim3(384);
        cfg.dynamicSmemBytes = SMEM_LAUNCH;
        int nc = 0;
        if (cudaOccupancyMaxActiveClusters(&nc, fused_kernel, &cfg) == cudaSuccess && nc >= 52 && nc < NCL) ncl = nc;
        (void)cudaGetLastError();
        ncl = tune("NCL", ncl);
        build_schedule(P, ncl);
        init = true;
    }
    fused_kernel<<<2 * ncl, 384, SMEM_LAUNCH>>>(P);
}
```

```cpp
#include <cuda_runtime.h>
#include <cuda.h>
#include <cuda_bf16.h>
#include <stdint.h>

namespace {

constexpr int NCTA = 132;
constexpr int NCL = NCTA / 2;
constexpr int MAXI = 16;
constexpr int NSTAT = 3;
constexpr uint32_t IT_DYN = 0xffffffffu;
constexpr int SLOT = 24576;
constexpr int NSLOT = 5;
constexpr int XS = 20480;
constexpr int OFF_R = 0;
constexpr int OFF_RING = 5 * XS;
constexpr int OFF_MISC = OFF_RING + NSLOT * SLOT;
constexpr int OFF_LX = OFF_MISC;
constexpr int OFF_LINV = OFF_LX + 2560;
constexpr int OFF_FB = OFF_LINV + 640;
constexpr int OFF_GM = OFF_FB + 16;
constexpr int OFF_BAR = OFF_GM + 16;
constexpr int BAR_RFULL = OFF_BAR;
constexpr int BAR_REMPTY = BAR_RFULL + 40;
constexpr int BAR_XFULL = BAR_REMPTY + 40;
constexpr int BAR_XEMPTY = BAR_XFULL + 40;
constexpr int BAR_PRDY = BAR_XEMPTY + 40;
constexpr int BAR_ITEM = BAR_PRDY + 40;
constexpr int OFF_ITEM = BAR_ITEM + MAXI * 8;
constexpr int SMEM_BYTES = OFF_ITEM + MAXI * 4;
static_assert(SMEM_BYTES <= 232448, "smem");

constexpr int NB_W = 1  , NB_PFULL = 3  , NB_VOTE = 5  , NB_Q2 = 7, NB_SDONE = 8, NB_PDONE = 9,
              NB_L = 10, NB_REF = 11, NB_ODONE = 12, NB_OPEND = 13, NB_LX = 14, NB_Q01 = 15, NB_QK = 0  ;

constexpr uint32_t IT_QA = 1, IT_OP = 2, IT_ON = 3;
__host__ __device__ constexpr uint32_t mk_item(uint32_t type, uint32_t br, uint32_t b, uint32_t h0, uint32_t h1, uint32_t half,
                                               uint32_t part = 0) {
    return type | (br << 2) | (b << 3) | (h0 << 7) | (h1 << 13) | (half << 19) | (part << 22);
}
#define IT_TYPE(e) ((e) & 3u)
#define IT_BR(e) (((e) >> 2) & 1u)
#define IT_B(e) (((e) >> 3) & 15u)
#define IT_H0(e) (((e) >> 7) & 63u)
#define IT_H1(e) (((e) >> 13) & 63u)
#define IT_HALF(e) (((e) >> 19) & 7u)
#define IT_PART(e) (((e) >> 22) & 1u)
#define IT_SLOT(e) IT_H1(e)
#define IT_DEP(e) (((e) >> 23) & 127u)

struct Params {
    CUtensorMap x[2], wq[2], k[2], v[2], wo[2], won[2], out;
    const __nv_bfloat16 *px[2], *pwq[2], *pk[2], *pv[2];
    struct alignas(16) { uint32_t delay, items[NSTAT]; } cl[NCL];
    uint32_t nlist;
    uint8_t slot[64];
    uint32_t list[568];
};

constexpr int OUNIT = 61440;
__device__ __align__(1024) unsigned char g_ostash[(size_t)1024 * OUNIT];
__device__ __align__(256) unsigned int g_flag[32 * 64];
__device__ __forceinline__ unsigned char* ostash(uint32_t slot, uint32_t b) { return g_ostash + (slot * 16 + b) * OUNIT; }
__device__ unsigned int g_epoch[NCTA * 4];
__device__ unsigned int g_ticket[2];

constexpr int SMEM_LAUNCH = SMEM_BYTES;
#define TS(role, idx)
#define TS_ITEM(e)
#define TS_DUMP(role)
#define TSD(role, idx)

__device__ __forceinline__ uint64_t pol_stream() {
    uint64_t p;
    asm volatile("createpolicy.fractional.L2::evict_first.b64 %0, 1.0;" : "=l"(p));
    return p;
}
__device__ __forceinline__ uint64_t pol_shared() {
    uint64_t p;
    asm volatile("createpolicy.fractional.L2::evict_unchanged.b64 %0, 1.0;" : "=l"(p));
    return p;
}
constexpr int QHOLD = 8;
constexpr float SM_C = 0.07216878364870322f * 1.4426950408889634f;

__device__ __forceinline__ uint32_t next_epoch(int warp) {
    unsigned int* p = &g_epoch[blockIdx.x * 4 + warp];
    const uint32_t e = __ldcg(p) + 1;
    *p = e;
    return e;
}

__device__ __forceinline__ uint32_t tid_now() {
    uint32_t t;
    asm volatile("mov.u32 %0, %%tid.x;" : "=r"(t));
    return t;
}
__device__ __forceinline__ void mbar_init(uint32_t a, uint32_t c) {
    asm volatile("mbarrier.init.shared::cta.b64 [%0], %1;" ::"r"(a), "r"(c) : "memory");
}
__device__ __forceinline__ void mbar_expect(uint32_t a, uint32_t b) {
    asm volatile("mbarrier.arrive.expect_tx.shared::cta.b64 _, [%0], %1;" ::"r"(a), "r"(b) : "memory");
}
template <int CNT = 1>
__device__ __forceinline__ void mbar_arrive_warp(uint32_t a) {
    if (CNT == 1)
        asm volatile("{\n.reg .pred p;\nelect.sync _|p, 0xffffffff;\n@p mbarrier.arrive.shared::cta.b64 _, [%0];\n}" ::"r"(a) : "memory");
    else
        asm volatile(
            "{\n.reg .pred p;\nelect.sync _|p, 0xffffffff;\n@p mbarrier.arrive.shared::cta.b64 _, [%0];\n"
            "@p mbarrier.arrive.shared::cta.b64 _, [%0];\n}" ::"r"(a)
            : "memory");
}
template <int CNT = 1>
__device__ __forceinline__ void mbar_arrive_warp_if(uint32_t a, bool cond) {
    if (CNT == 1)
        asm volatile(
            "{\n.reg .pred p, c;\nelect.sync _|p, 0xffffffff;\nsetp.ne.and.u32 c, %1, 0, p;\n"
            "@c mbarrier.arrive.shared::cta.b64 _, [%0];\n}" ::"r"(a), "r"((uint32_t)cond)
            : "memory");
    else
        asm volatile(
            "{\n.reg .pred p, c;\nelect.sync _|p, 0xffffffff;\nsetp.ne.and.u32 c, %1, 0, p;\n"
            "@c mbarrier.arrive.shared::cta.b64 _, [%0];\n@c mbarrier.arrive.shared::cta.b64 _, [%0];\n}" ::"r"(a), "r"((uint32_t)cond)
            : "memory");
}
__device__ __forceinline__ uint32_t deadline() {
    uint32_t c;
    asm volatile("mov.u32 %0, %%clock_hi;" : "=r"(c));
    return c + 4;
}
__device__ __forceinline__ void mbar_wait(uint32_t a, uint32_t ph, uint32_t dl) {
    asm volatile(
        "{\n.reg .pred p;\n.reg .u32 m;\n"
        "LOOP:\n"
        "mbarrier.try_wait.parity.shared::cta.b64 p, [%0], %1;\n"
        "@p bra DONE;\n"
        "mov.u32 m, %%clock_hi;\n"
        "setp.ne.u32 p, m, %2;\n"
        "@p bra LOOP;\n"
        "trap;\n"
        "DONE:\n}" ::"r"(a), "r"(ph), "r"(dl)
        : "memory");
}
__device__ __forceinline__ void mbar_wait2(uint32_t a, uint32_t pa, uint32_t b, uint32_t pb, uint32_t dl) {
    asm volatile(
        "{\n.reg .pred p, q;\n.reg .u32 m;\n"
        "LOOP:\n"
        "mbarrier.try_wait.parity.shared::cta.b64 p, [%0], %1;\n"
        "mbarrier.try_wait.parity.shared::cta.b64 q, [%2], %3;\n"
        "and.pred p, p, q;\n"
        "@p bra DONE;\n"
        "mov.u32 m, %%clock_hi;\n"
        "setp.ne.u32 p, m, %4;\n"
        "@p bra LOOP;\n"
        "trap;\n"
        "DONE:\n}" ::"r"(a), "r"(pa), "r"(b), "r"(pb), "r"(dl)
        : "memory");
}
template <int ID, int CNT>
__device__ __forceinline__ void nb_sync() { asm volatile("bar.sync %0, %1;" ::"n"(ID), "n"(CNT) : "memory"); }
template <int ID, int CNT>
__device__ __forceinline__ void nb_arrive() { asm volatile("bar.arrive %0, %1;" ::"n"(ID), "n"(CNT) : "memory"); }
__device__ __forceinline__ void fence_async_smem() { asm volatile("fence.proxy.async.shared::cta;" ::: "memory"); }

__device__ __forceinline__ void tma3(uint32_t dst, const CUtensorMap* m, int c1, int c2, uint32_t bar, uint64_t pol) {
    asm volatile(
        "cp.async.bulk.tensor.3d.shared::cluster.global.mbarrier::complete_tx::bytes.L2::cache_hint [%0], [%1, {%3,%4,%5}], [%2], %6;" ::"r"(dst),
        "l"(m), "r"(bar), "r"(0), "r"(c1), "r"(c2), "l"(pol)
        : "memory");
}
__device__ __forceinline__ void tma3_mc(uint32_t dst, const CUtensorMap* m, int c1, int c2, uint32_t bar, uint64_t pol) {
    asm volatile(
        "cp.async.bulk.tensor.3d.shared::cluster.global.mbarrier::complete_tx::bytes.multicast::cluster.L2::cache_hint"
        " [%0], [%1, {%3,%4,%5}], [%2], %6, %7;" ::"r"(dst),
        "l"(m), "r"(bar), "r"(0), "r"(c1), "r"(c2), "h"((unsigned short)3), "l"(pol)
        : "memory");
}
__device__ __forceinline__ void bulk_load(uint32_t dst, const void* src, uint32_t bytes, uint32_t bar, uint64_t pol) {
    asm volatile("cp.async.bulk.shared::cluster.global.mbarrier::complete_tx::bytes.L2::cache_hint [%0], [%1], %2, [%3], %4;" ::"r"(dst),
                 "l"(src), "r"(bytes), "r"(bar), "l"(pol)
                 : "memory");
}
__device__ __forceinline__ void wg_fence() { asm volatile("wgmma.fence.sync.aligned;" ::: "memory"); }
__device__ __forceinline__ void wg_commit() { asm volatile("wgmma.commit_group.sync.aligned;" ::: "memory"); }
template <int N>
__device__ __forceinline__ void wg_wait() { asm volatile("wgmma.wait_group.sync.aligned %0;" ::"n"(N) : "memory"); }

#define RW80(c, d) c(d[0]), c(d[1]), c(d[2]), c(d[3]), c(d[4]), c(d[5]), c(d[6]), c(d[7]), c(d[8]), c(d[9]), c(d[10]), c(d[11]), c(d[12]), c(d[13]), c(d[14]), c(d[15]), c(d[16]), c(d[17]), c(d[18]), c(d[19]), c(d[20]), c(d[21]), c(d[22]), c(d[23]), c(d[24]), c(d[25]), c(d[26]), c(d[27]), c(d[28]), c(d[29]), c(d[30]), c(d[31]), c(d[32]), c(d[33]), c(d[34]), c(d[35]), c(d[36]), c(d[37]), c(d[38]), c(d[39]), c(d[40]), c(d[41]), c(d[42]), c(d[43]), c(d[44]), c(d[45]), c(d[46]), c(d[47]), c(d[48]), c(d[49]), c(d[50]), c(d[51]), c(d[52]), c(d[53]), c(d[54]), c(d[55]), c(d[56]), c(d[57]), c(d[58]), c(d[59]), c(d[60]), c(d[61]), c(d[62]), c(d[63]), c(d[64]), c(d[65]), c(d[66]), c(d[67]), c(d[68]), c(d[69]), c(d[70]), c(d[71]), c(d[72]), c(d[73]), c(d[74]), c(d[75]), c(d[76]), c(d[77]), c(d[78]), c(d[79])
#define RW48(c, d) c(d[0]), c(d[1]), c(d[2]), c(d[3]), c(d[4]), c(d[5]), c(d[6]), c(d[7]), c(d[8]), c(d[9]), c(d[10]), c(d[11]), c(d[12]), c(d[13]), c(d[14]), c(d[15]), c(d[16]), c(d[17]), c(d[18]), c(d[19]), c(d[20]), c(d[21]), c(d[22]), c(d[23]), c(d[24]), c(d[25]), c(d[26]), c(d[27]), c(d[28]), c(d[29]), c(d[30]), c(d[31]), c(d[32]), c(d[33]), c(d[34]), c(d[35]), c(d[36]), c(d[37]), c(d[38]), c(d[39]), c(d[40]), c(d[41]), c(d[42]), c(d[43]), c(d[44]), c(d[45]), c(d[46]), c(d[47])
#define RW32(c, d) c(d[0]), c(d[1]), c(d[2]), c(d[3]), c(d[4]), c(d[5]), c(d[6]), c(d[7]), c(d[8]), c(d[9]), c(d[10]), c(d[11]), c(d[12]), c(d[13]), c(d[14]), c(d[15]), c(d[16]), c(d[17]), c(d[18]), c(d[19]), c(d[20]), c(d[21]), c(d[22]), c(d[23]), c(d[24]), c(d[25]), c(d[26]), c(d[27]), c(d[28]), c(d[29]), c(d[30]), c(d[31])

__device__ __forceinline__ void reg_fence(float (&d)[80]) { asm volatile("" : RW80("+f", d)::"memory"); }
__device__ __forceinline__ void reg_fence(float (&d)[48]) { asm volatile("" : RW48("+f", d)::"memory"); }
__device__ __forceinline__ void reg_fence(float (&d)[32]) { asm volatile("" : RW32("+f", d)::"memory"); }

template <int NR>
__device__ __forceinline__ void zero(float (&d)[NR]) {
#pragma unroll
    for (int i = 0; i < NR; i++) d[i] = 0.f;
}

constexpr uint32_t HI_SW128 = (1024u >> 4) | (1u << 30);
constexpr uint32_t HI_KV = (3072u >> 4) | (1u << 30);
constexpr uint32_t HI_OST = (2560u >> 4) | (2u << 30);
constexpr uint32_t LO_LBO1 = (1u << 16);
constexpr uint32_t LO_OST = ((512u >> 4) << 16);

template <int TA, int TB, uint32_t HIB, int ACC, uint32_t HIA = HI_SW128>
__device__ __forceinline__ void wgmma(float (&d)[80], uint32_t loA, uint32_t loB) {
#define WG_ASM(SD)                                                          \
    "{\n.reg .b64 da, db;\nmov.b64 da, {%80, %82};\nmov.b64 db, {%81, %83};\n" \
    "wgmma.mma_async.sync.aligned.m64n160k16.f32.bf16.bf16 "               \
    "{%0,%1,%2,%3,%4,%5,%6,%7,%8,%9,%10,%11,%12,%13,%14,%15,%16,%17,%18,%19,%20,%21,%22,%23,%24,%25,%26,%27,%28,%29,%30,%31,%32,%33,%34,%35,%36,%37,%38,%39,%40,%41,%42,%43,%44,%45,%46,%47,%48,%49,%50,%51,%52,%53,%54,%55,%56,%57,%58,%59,%60,%61,%62,%63,%64,%65,%66,%67,%68,%69,%70,%71,%72,%73,%74,%75,%76,%77,%78,%79}, da, db, " SD ", 1, 1, %84, %85;\n}"
    if constexpr (ACC == 2)
        asm volatile(WG_ASM("0") : RW80("+f", d) : "r"(loA), "r"(loB), "n"(HIA), "n"(HIB), "n"(TA), "n"(TB));
    else if constexpr (ACC == 1)
        asm volatile(WG_ASM("1") : RW80("+f", d) : "r"(loA), "r"(loB), "n"(HIA), "n"(HIB), "n"(TA), "n"(TB));
    else
        asm volatile(WG_ASM("0") : RW80("=f", d) : "r"(loA), "r"(loB), "n"(HIA), "n"(HIB), "n"(TA), "n"(TB));
#undef WG_ASM
}
template <int TA, int TB, uint32_t HIB, int ACC, uint32_t HIA = HI_SW128>
__device__ __forceinline__ void wgmma(float (&d)[48], uint32_t loA, uint32_t loB) {
#define WG_ASM(SD)                                                          \
    "{\n.reg .b64 da, db;\nmov.b64 da, {%48, %50};\nmov.b64 db, {%49, %51};\n" \
    "wgmma.mma_async.sync.aligned.m64n96k16.f32.bf16.bf16 "               \
    "{%0,%1,%2,%3,%4,%5,%6,%7,%8,%9,%10,%11,%12,%13,%14,%15,%16,%17,%18,%19,%20,%21,%22,%23,%24,%25,%26,%27,%28,%29,%30,%31,%32,%33,%34,%35,%36,%37,%38,%39,%40,%41,%42,%43,%44,%45,%46,%47}, da, db, " SD ", 1, 1, %52, %53;\n}"
    if constexpr (ACC == 1)
        asm volatile(WG_ASM("1") : RW48("+f", d) : "r"(loA), "r"(loB), "n"(HIA), "n"(HIB), "n"(TA), "n"(TB));
    else
        asm volatile(WG_ASM("0") : RW48("=f", d) : "r"(loA), "r"(loB), "n"(HIA), "n"(HIB), "n"(TA), "n"(TB));
#undef WG_ASM
}
template <int TA, int TB, uint32_t HIB, int ACC, uint32_t HIA = HI_SW128>
__device__ __forceinline__ void wgmma(float (&d)[32], uint32_t loA, uint32_t loB) {
#define WG_ASM(SD)                                                          \
    "{\n.reg .b64 da, db;\nmov.b64 da, {%32, %34};\nmov.b64 db, {%33, %35};\n" \
    "wgmma.mma_async.sync.aligned.m64n64k16.f32.bf16.bf16 "               \
    "{%0,%1,%2,%3,%4,%5,%6,%7,%8,%9,%10,%11,%12,%13,%14,%15,%16,%17,%18,%19,%20,%21,%22,%23,%24,%25,%26,%27,%28,%29,%30,%31}, da, db, " SD ", 1, 1, %36, %37;\n}"
    if constexpr (ACC == 1)
        asm volatile(WG_ASM("1") : RW32("+f", d) : "r"(loA), "r"(loB), "n"(HIA), "n"(HIB), "n"(TA), "n"(TB));
    else
        asm volatile(WG_ASM("0") : RW32("=f", d) : "r"(loA), "r"(loB), "n"(HIA), "n"(HIB), "n"(TA), "n"(TB));
#undef WG_ASM
}

__device__ __forceinline__ uint32_t pack_bf16(float lo, float hi) {
    uint32_t r;
    asm("cvt.rn.bf16x2.f32 %0, %1, %2;" : "=r"(r) : "f"(hi), "f"(lo));
    return r;
}
__device__ __forceinline__ float ex2(float x) {
    float r;
    asm("ex2.approx.ftz.f32 %0, %1;" : "=f"(r) : "f"(x));
    return r;
}
__device__ __forceinline__ void stsm4t(uint32_t a, uint32_t r0, uint32_t r1, uint32_t r2, uint32_t r3) {
    asm volatile("stmatrix.sync.aligned.m8n8.x4.trans.shared.b16 [%0], {%1,%2,%3,%4};" ::"r"(a), "r"(r0), "r"(r1), "r"(r2), "r"(r3)
                 : "memory");
}
__device__ __forceinline__ uint32_t lds_u(uint32_t a) {
    uint32_t v;
    asm volatile("ld.shared.u32 %0, [%1];" : "=r"(v) : "r"(a) : "memory");
    return v;
}
__device__ __forceinline__ uint4 lds_u4(uint32_t a) {
    uint4 v;
    asm volatile("ld.shared.v4.u32 {%0,%1,%2,%3}, [%4];" : "=r"(v.x), "=r"(v.y), "=r"(v.z), "=r"(v.w) : "r"(a) : "memory");
    return v;
}
__device__ __forceinline__ float2 lds_f2(uint32_t a) {
    float2 v;
    asm volatile("ld.shared.v2.f32 {%0,%1}, [%2];" : "=f"(v.x), "=f"(v.y) : "r"(a) : "memory");
    return v;
}
__device__ __forceinline__ void sts_f(uint32_t a, float v) { asm volatile("st.shared.f32 [%0], %1;" ::"r"(a), "f"(v) : "memory"); }
__device__ __forceinline__ void sts_u(uint32_t a, uint32_t v) { asm volatile("st.shared.u32 [%0], %1;" ::"r"(a), "r"(v) : "memory"); }
__device__ __forceinline__ void sts_f2(uint32_t a, float x, float y) {
    asm volatile("st.shared.v2.f32 [%0], {%1,%2};" ::"r"(a), "f"(x), "f"(y) : "memory");
}

template <bool ADD = false, bool SIG = false, int NR>
__device__ __forceinline__ void store_tile_t(const float (&d)[NR], uint32_t addr) {
    uint32_t p[NR / 2];
    if (ADD) {
#pragma unroll
        for (int j = 0; j < NR / 8; j++)
            asm volatile("ldmatrix.sync.aligned.m8n8.x4.trans.shared.b16 {%0,%1,%2,%3}, [%4];"
                         : "=r"(p[4 * j]), "=r"(p[4 * j + 1]), "=r"(p[4 * j + 2]), "=r"(p[4 * j + 3])
                         : "r"(addr + j * 2048)
                         : "memory");
    }
#pragma unroll
    for (int k = 0; k < NR / 2; k++)
        p[k] = ADD ? pack_bf16(d[2 * k] + __uint_as_float(p[k] << 16), d[2 * k + 1] + __uint_as_float(p[k] & 0xffff0000u))
                   : pack_bf16(d[2 * k], d[2 * k + 1]);
#pragma unroll
    for (int j = 0; j < NR / 8; j++) {
        stsm4t(addr + j * 2048, p[4 * j], p[4 * j + 1], p[4 * j + 2], p[4 * j + 3]);
        if (SIG && j == 0) nb_arrive<NB_L, 160>();
    }
}

struct TrueT { static constexpr bool value = true; };
struct FalseT { static constexpr bool value = false; };

template <int V>
struct IntT { static constexpr int value = V; };

__device__ __forceinline__ uint32_t get_item(uint32_t sb, int it, uint32_t dl) {
    mbar_wait(sb + BAR_ITEM + it * 8, 0, dl);
    return lds_u(sb + OFF_ITEM + it * 4);
}
__device__ __forceinline__ uint32_t get_item_warp(uint32_t sb, int it, uint32_t dl) {
    return __shfl_sync(0xffffffffu, get_item(sb, it, dl), 0);
}

struct Ring {
    uint32_t slot, ph, dl;
    __device__ __forceinline__ void adv(uint32_t k) {
        slot += k;
        if (slot >= NSLOT) { slot -= NSLOT; ph ^= 1; }
    }
};

template <int K>
__device__ __forceinline__ void qk_step(float (&s)[80], uint32_t loK, uint32_t loQ) {
    wgmma<0, 0, HI_SW128, K != 0, HI_KV>(s, loK + (K >> 2) * 64 + (K & 3) * 2, loQ + (K >> 2) * (XS >> 4) + (K & 3) * 2);
}
template <int K0, int K1>
__device__ __forceinline__ void qk_steps(float (&s)[80], uint32_t loK, uint32_t loQ) {
    if constexpr (K0 < K1) {
        qk_step<K0>(s, loK, loQ);
        qk_steps<K0 + 1, K1>(s, loK, loQ);
    }
}
__device__ __forceinline__ uint32_t add_bf2(uint32_t a, uint32_t b) {
    uint32_t r;
    asm("add.rn.bf16x2 %0, %1, %2;" : "=r"(r) : "r"(a), "r"(b));
    return r;
}
__device__ __forceinline__ uint32_t fma_bf2(uint32_t a, uint32_t b, uint32_t c) {
    uint32_t r;
    asm("fma.rn.bf16x2 %0, %1, %2, %3;" : "=r"(r) : "r"(a), "r"(b), "r"(c));
    return r;
}
template <int J>
__device__ __forceinline__ void exp_block(const float (&s)[80], uint32_t (&k)[40], uint32_t pa, float mref) {
    if constexpr (J < 10) {
#pragma unroll
        for (int i = 4 * J; i < 4 * J + 4; i++)
            k[i] = pack_bf16(ex2(fmaf(s[2 * i], SM_C, -mref)), ex2(fmaf(s[2 * i + 1], SM_C, -mref)));
#pragma unroll
        for (int i = 0; i < 4; i++)
            asm volatile("stmatrix.sync.aligned.m8n8.x1.trans.shared.b16 [%0], {%1};" ::"r"(((i & 1) ? pa ^ 16 : pa) + J * 2048 + (i >> 1) * 1024),
                         "r"(k[4 * J + i])
                         : "memory");
        exp_block<J + 1>(s, k, pa, mref);
    }
}
__device__ __forceinline__ void sum_block(const uint32_t (&k)[40], float (&l)[10], uint32_t lane) {
    const bool b4 = lane & 16, b3 = lane & 8;
    uint32_t ps[20], t[10];
#pragma unroll
    for (int j = 0; j < 20; j++) ps[j] = add_bf2(k[2 * j], k[2 * j + 1]);
#pragma unroll
    for (int j = 0; j < 10; j++)
        t[j] = add_bf2(b4 ? ps[2 * j + 1] : ps[2 * j], __shfl_xor_sync(0xffffffffu, b4 ? ps[2 * j] : ps[2 * j + 1], 16));
#pragma unroll
    for (int i = 0; i < 5; i++) {
        const uint32_t a = b3 ? t[i + 5] : t[i], b = __shfl_xor_sync(0xffffffffu, b3 ? t[i] : t[i + 5], 8);
        l[2 * i] += __uint_as_float(a << 16) + __uint_as_float(b << 16);
        l[2 * i + 1] += __uint_as_float(a & 0xffff0000u) + __uint_as_float(b & 0xffff0000u);
    }
}
template <bool ADD>
__device__ __forceinline__ void sum_store(const float (&l)[10], uint32_t lane, uint32_t lxa) {
    const bool b2 = lane & 4;
    float t[5];
#pragma unroll
    for (int i = 0; i < 5; i++) t[i] = ADD ? __uint_as_float(lds_u(lxa + i * 64)) : 0.f;
#pragma unroll
    for (int i = 0; i < 5; i++)
        sts_f(lxa + i * 64, t[i] + (b2 ? l[2 * i + 1] : l[2 * i]) + __shfl_xor_sync(0xffffffffu, b2 ? l[2 * i] : l[2 * i + 1], 4));
}

__device__ __forceinline__ void fallback_unit(const Params& P, uint32_t e, uint32_t tid) {
    const uint32_t lane = tid & 31, br = IT_BR(e), b = IT_B(e), h = IT_H0(e);
    const __nv_bfloat162* wq = (const __nv_bfloat162*)(P.pwq[br] + h * 192) + lane;
    const __nv_bfloat162* kp = (const __nv_bfloat162*)(P.pk[br] + (size_t)(b * 32 + h) * 512 * 192) + lane;
    const __nv_bfloat162* vp = (const __nv_bfloat162*)(P.pv[br] + (size_t)(b * 32 + h) * 512 * 192) + lane;
#pragma unroll 1
    for (uint32_t qi = 0; qi < 40; qi++) {
        const uint32_t q = 4 * qi + (tid >> 5);
        const __nv_bfloat16* xr = P.px[br] + (size_t)(b * 160 + q) * 640;
        float a[6] = {0.f, 0.f, 0.f, 0.f, 0.f, 0.f};
#pragma unroll 2
        for (int k = 0; k < 640; k++) {
            const float xv = __bfloat162float(xr[k]);
#pragma unroll
            for (int i = 0; i < 3; i++) {
                const float2 wv = __bfloat1622float2(wq[(size_t)k * 3072 + i * 32]);
                a[2 * i] = fmaf(xv, wv.x, a[2 * i]);
                a[2 * i + 1] = fmaf(xv, wv.y, a[2 * i + 1]);
            }
        }
#pragma unroll
        for (int i = 0; i < 6; i++) a[i] = __bfloat162float(__float2bfloat16(a[i]));
        auto score = [&](int key) {
            float d = 0.f;
#pragma unroll
            for (int i = 0; i < 3; i++) {
                const float2 kv = __bfloat1622float2(kp[key * 96 + i * 32]);
                d = fmaf(a[2 * i], kv.x, fmaf(a[2 * i + 1], kv.y, d));
            }
#pragma unroll
            for (int o = 16; o > 0; o >>= 1) d += __shfl_xor_sync(0xffffffffu, d, o);
            return d;
        };
        float m = -INFINITY, o[6] = {0.f, 0.f, 0.f, 0.f, 0.f, 0.f}, sum = 0.f;
#pragma unroll 1
        for (int n = 0; n < 1024; n++) {
            const int key = n & 511;
            const float d = score(key);
            if (n < 512) {
                m = fmaxf(m, d);
            } else {
                const float p = ex2((d - m) * SM_C);
                sum += p;
#pragma unroll
                for (int i = 0; i < 3; i++) {
                    const float2 vv = __bfloat1622float2(vp[key * 96 + i * 32]);
                    o[2 * i] = fmaf(p, vv.x, o[2 * i]);
                    o[2 * i + 1] = fmaf(p, vv.y, o[2 * i + 1]);
                }
            }
        }
        const float inv = __fdividef(1.f, sum);
        __nv_bfloat16* op = (__nv_bfloat16*)ostash(IT_SLOT(e), b) + (q >> 5) * 256 + 2 * ((q & 31) >> 3) + (q & 1);
#pragma unroll
        for (int i = 0; i < 6; i++) {
            const uint32_t d = (i >> 1) * 64 + 2 * lane + (i & 1);
            op[(d >> 3) * 1280 + (d & 7) * 32 + ((((q & 7) >> 1) ^ ((d & 7) >> 1)) << 3)] = __float2bfloat16(o[i] * inv);
        }
    }
}

struct PendO {
    uint32_t v[64];
    unsigned char* gp;
    static __device__ __forceinline__ uint32_t toff() {
        const uint32_t t = tid_now();
        return ((t >> 5) & 3) * 5120 + ((t >> 2) & 7) * 64 + (((t ^ (t >> 3)) & 3) << 4);
    }
    uint32_t pend, sig, bad;
    static __device__ __forceinline__ void scale(uint32_t& x, uint32_t hi, uint32_t lo) {
        asm("{\n.reg .b32 t;\nmul.rn.bf16x2 t, %0, %2;\nfma.rn.bf16x2 %0, %0, %1, t;\n}" : "+r"(x) : "r"(hi), "r"(lo));
    }
    template <int I, int OFF>
    __device__ __forceinline__ void put() {
        asm volatile("{\n.reg .pred p;\nsetp.ne.u32 p, %6, 0;\n@p st.global.v4.b32 [%0+%5], {%1,%2,%3,%4};\n}" ::"l"(gp), "r"(v[I]),
                     "r"(v[I + 1]), "r"(v[I + 2]), "r"(v[I + 3]), "n"(OFF), "r"(pend)
                     : "memory");
    }
    __device__ __forceinline__ void verdict(uint32_t sb, uint32_t W) {
        if (sig) {
            asm volatile("bar.sync %0, 160;" ::"r"(NB_VOTE + W) : "memory");
            bad = __any_sync(0xffffffffu, lds_u(sb + OFF_FB) != 0);
            pend = !bad;
        }
    }
    template <int W, int G, int H>
    __device__ __forceinline__ void half(uint32_t sb) {
        constexpr bool T2 = W == 0 ? G >= 3 : G < 3;
        constexpr int B = T2 ? 40 + 8 * (W == 0 ? G - 3 : G) : 0;
        const uint4 a = lds_u4(sb + OFF_LINV + G * 128 + H * 16 + (threadIdx.x & 3) * 32);
#pragma unroll
        for (int i = 2 * H; i < 8; i += 4) {
            scale(v[8 * G + i], a.x, a.y);
            scale(v[8 * G + i + 1], a.z, a.w);
            if (T2) {
                scale(v[B + i], a.x, a.y);
                scale(v[B + i + 1], a.z, a.w);
            }
        }
        if (H == 1) {
            put<8 * G, W * XS + G * 512>();
            put<8 * G + 4, W * XS + G * 512 + 2560>();
            if (T2) {
                put<B, 2 * XS + G * 512>();
                put<B + 4, 2 * XS + G * 512 + 2560>();
            }
            if (G == 4 && pend) nb_arrive<NB_ODONE, 288>();
        }
    }
    template <int W, int G>
    __device__ __forceinline__ void step(uint32_t sb) {
        half<W, G, 0>(sb);
        half<W, G, 1>(sb);
    }
    template <int W>
    __device__ __forceinline__ void flush(uint32_t sb) {
        step<W, 0>(sb);
        step<W, 1>(sb);
        step<W, 2>(sb);
        step<W, 3>(sb);
        step<W, 4>(sb);
    }
    __device__ __forceinline__ void clear() {
#pragma unroll
        for (int i = 0; i < 64; i++) v[i] = 0;
        gp = nullptr;
        pend = 0;
        sig = 0;
        bad = 0;
    }
};

__device__ __forceinline__ uint32_t stsm_off() {
    const uint32_t tid = tid_now(), lane = tid & 31;
    return (lane >> 4) * 1024 + (lane & 7) * 128 + (((((tid >> 4) & 6) + ((lane >> 3) & 1)) ^ (lane & 7)) << 4);
}
__device__ __forceinline__ void q_ahead(float (&q0)[80], uint32_t sb, const Ring& rn, uint32_t phm, bool valid) {
    if (valid) mbar_wait2(sb + BAR_RFULL + rn.slot * 8, rn.ph, sb + BAR_XFULL, phm & 1, rn.dl);
    const uint32_t a = ((((sb + OFF_RING) & 0x3ffff) >> 4) | LO_LBO1) + rn.slot * (SLOT >> 4);
    const uint32_t b = (((sb + OFF_R) & 0x3ffff) >> 4) | LO_LBO1;
    wg_fence();
    wgmma<1, 0, HI_SW128, false>(q0, a, b);
#pragma unroll
    for (int k = 1; k < 4; k++) wgmma<1, 0, HI_SW128, true>(q0, a + (k >> 1) * 768 + (k & 1) * 128, b + k * 2);
    wg_commit();
}
template <int W, int KK>
__device__ __forceinline__ void qproj(float (&q0)[80], float (&q1)[80], uint32_t sb, Ring& r, uint32_t pslot, uint32_t phm,
                                      PendO& po) {
    const uint32_t loR = (((sb + OFF_R) & 0x3ffff) >> 4) | LO_LBO1;
    const uint32_t loRing = (((sb + OFF_RING) & 0x3ffff) >> 4) | LO_LBO1;
    auto ready = [&](int k) {
        mbar_wait2(sb + BAR_RFULL + r.slot * 8, r.ph, sb + BAR_XFULL + (k % 5) * 8, ((phm >> (k % 5)) ^ (k / 5)) & 1, r.dl);
    };
    auto release = [&]() {
        if (KK > 0) {
            wg_wait<1>();
            mbar_arrive_warp(sb + BAR_REMPTY + pslot * 8);
            if (KK <= 5) mbar_arrive_warp(sb + (BAR_XEMPTY + (KK - 1) * 8));
        }
    };
    if (KK == 0 && W == 1) ready(0);
    if (W == 1 && KK == QHOLD) nb_sync<NB_SDONE, 256>();
    const uint32_t a = loRing + r.slot * (SLOT >> 4) + (W == 0 ? 0 : 512), b = loR + (KK % 5) * (XS >> 4);
    wg_fence();
    constexpr bool T0 = W == 1 || KK > 0;
    if (T0) wgmma<1, 0, HI_SW128, KK != 0>(q0, a, b);
    if (W == 0) wgmma<1, 0, HI_SW128, KK != 0 ? 1 : 2>(q1, a + 256, b);
#pragma unroll
    for (int k = 1; k < 4; k++) {
        if (T0) wgmma<1, 0, HI_SW128, true>(q0, a + (k >> 1) * 768 + (k & 1) * 128, b + k * 2);
        if (W == 0) wgmma<1, 0, HI_SW128, true>(q1, a + 256 + (k >> 1) * 768 + (k & 1) * 128, b + k * 2);
    }
    wg_commit();
    const uint32_t cslot = r.slot;
    r.adv(1);
    if (W == 0 || KK < QHOLD) release();
    constexpr int QST = W == 0 ? 2 : 1;
    if (KK == QST) {
        po.verdict(sb, W);
        po.template half<W, 0, 0>(sb);
    }
    if (KK < 9) ready(KK + 1);
    if (W == 1 && KK >= QHOLD) release();
    if (W == 1 && KK == 7) nb_arrive<NB_PDONE, 256>();
    if (KK == QST) po.template half<W, 0, 1>(sb);
    if constexpr (KK > QST && KK < QST + 5) po.template step<W, KK - QST>(sb);
    if constexpr (KK < (W == 0 ? 7 : 9)) {
        qproj<W, KK + 1>(q0, q1, sb, r, cslot, phm, po);
    } else if constexpr (W == 1) {
        const uint32_t sta = sb + OFF_R + 2 * XS + stsm_off();
        wg_wait<0>();
        reg_fence(q0);
        store_tile_t<false, true>(q0, sta);
        mbar_arrive_warp(sb + BAR_REMPTY + cslot * 8);
    } else {
        const uint32_t s8 = r.slot, a8 = loRing + s8 * (SLOT >> 4);
        wg_fence();
#pragma unroll
        for (int k = 0; k < 4; k++) wgmma<1, 0, HI_SW128, true>(q0, a8 + (k >> 1) * 768 + (k & 1) * 128, loR + 3 * (XS >> 4) + k * 2);
        r.adv(1);
        ready(9);
        const uint32_t s9 = r.slot, a9 = loRing + s9 * (SLOT >> 4);
        r.adv(1);
        wg_fence();
#pragma unroll
        for (int k = 0; k < 4; k++) wgmma<1, 0, HI_SW128, true>(q0, a9 + (k >> 1) * 768 + (k & 1) * 128, loR + 4 * (XS >> 4) + k * 2);
        wg_commit();
        wg_wait<1>();
        mbar_arrive_warp(sb + BAR_REMPTY + cslot * 8);
        wg_fence();
#pragma unroll
        for (int k = 0; k < 8; k++)
            wgmma<1, 0, HI_SW128, true>(q1, (k < 4 ? a8 : a9) + 256 + ((k >> 1) & 1) * 768 + (k & 1) * 128,
                                        loR + (3 + (k >> 2)) * (XS >> 4) + (k & 3) * 2);
        wg_commit();
        nb_arrive<NB_SDONE, 256>();
        sts_u(sb + OFF_GM + 4, r.slot);
        nb_sync<NB_PDONE, 256>();
        wg_wait<1>();
        reg_fence(q0);
        const uint32_t sta = sb + OFF_R + stsm_off();
        store_tile_t(q0, sta);
        wg_wait<0>();
        reg_fence(q1);
        mbar_arrive_warp(sb + BAR_REMPTY + s8 * 8);
        mbar_arrive_warp(sb + BAR_REMPTY + s9 * 8);
        store_tile_t(q1, sta + XS);
        mbar_wait(sb + BAR_RFULL + r.slot * 8, r.ph, r.dl);
    }
}

template <int NR>
__device__ __forceinline__ void opack(const float (&o)[NR], uint32_t* v) {
#pragma unroll
    for (int g = 0; g < NR / 16; g++)
#pragma unroll
        for (int hh = 0; hh < 2; hh++)
#pragma unroll
            for (int t = 0; t < 4; t++) v[8 * g + 4 * hh + t] = pack_bf16(o[16 * g + 4 * t + 2 * hh], o[16 * g + 4 * t + 2 * hh + 1]);
}

template <bool IS_S>
__device__ __forceinline__ void op_item(uint32_t e, uint32_t sb, Ring& r, uint32_t& phm) {
    constexpr int T0 = IS_S ? 0 : 2;
    constexpr uint32_t BOFF = IS_S ? (3 * 512) >> 4 : 0;
    const uint32_t loRing = (((sb + OFF_RING) & 0x3ffff) >> 4) | LO_LBO1;
    const uint32_t loO = (((sb + OFF_R) & 0x3ffff) >> 4) | LO_OST;
    float c0[80], c1[80], c2[IS_S ? 32 : 48];
    const int T = 3 * (IT_H1(e) - IT_H0(e));
    uint32_t xs = 0;
    auto step = [&](auto first, auto half) {
        constexpr bool F = decltype(first)::value;
        constexpr uint32_t hf = decltype(half)::value;
        if (hf == 0) {
            mbar_wait(sb + BAR_XFULL + xs * 8, (phm >> xs) & 1, r.dl);
            phm ^= 1u << xs;
        }
        mbar_wait(sb + BAR_RFULL + r.slot * 8, r.ph, r.dl);
        const uint32_t a = loRing + r.slot * (SLOT >> 4), b = loO + xs * (XS >> 4) + hf * 640;
        wg_fence();
        wgmma<1, 1, HI_OST, !F>(c0, a + T0 * 128, b);
        wgmma<1, 1, HI_OST, !F>(c1, a + T0 * 128 + 128, b);
        wgmma<1, 1, HI_OST, !F>(c2, a + 512, b + BOFF);
        wgmma<1, 1, HI_OST, true>(c0, a + 640 + T0 * 128, b + 320);
        wgmma<1, 1, HI_OST, true>(c1, a + 640 + T0 * 128 + 128, b + 320);
        wgmma<1, 1, HI_OST, true>(c2, a + 640 + 512, b + 320 + BOFF);
        wg_commit();
    };
    step(TrueT{}, IntT<0>{});
#pragma unroll 1
    for (int t = 1;; t++) {
        uint32_t pslot = r.slot;
        r.adv(1);
        step(FalseT{}, IntT<1>{});
        wg_wait<1>();
        mbar_arrive_warp(sb + BAR_REMPTY + pslot * 8);
        if (t == T) break;
        pslot = r.slot;
        const uint32_t pxs = xs;
        r.adv(1);
        if (++xs == 5) xs = 0;
        step(FalseT{}, IntT<0>{});
        wg_wait<1>();
        mbar_arrive_warp(sb + BAR_REMPTY + pslot * 8);
        mbar_arrive_warp_if(sb + BAR_XEMPTY + pxs * 8, t + 4 < T);
    }
    wg_wait<0>();
    reg_fence(c0);
    reg_fence(c1);
    reg_fence(c2);
    mbar_arrive_warp(sb + BAR_REMPTY + r.slot * 8);
    r.adv(1);
    nb_sync<NB_OPEND, 256>();
    const uint32_t sta = sb + OFF_R + stsm_off();
    store_tile_t(c0, sta + T0 * XS);
    store_tile_t(c1, sta + (T0 + 1) * XS);
    store_tile_t(c2, sta + 4 * XS + (IS_S ? 96 * 128 : 0));
    fence_async_smem();
    nb_arrive<NB_ODONE, 288>();
}

__device__ __forceinline__ void on_item(uint32_t W, uint32_t e, uint32_t sb, Ring& r, uint32_t& phm) {
    const uint32_t loRing = (((sb + OFF_RING) & 0x3ffff) >> 4) | LO_LBO1;
    const uint32_t loO = (((sb + OFF_R) & 0x3ffff) >> 4) | LO_OST;
    float c[80];
    const int T = 3 * (IT_H1(e) - IT_H0(e));
    uint32_t xs = 0;
    auto step = [&](auto first) {
        constexpr bool F = decltype(first)::value;
        mbar_wait2(sb + BAR_XFULL + xs * 8, (phm >> xs) & 1, sb + BAR_RFULL + r.slot * 8, r.ph, r.dl);
        phm ^= 1u << xs;
        const uint32_t a = loRing + r.slot * (SLOT >> 4) + W * 256, b = loO + xs * (XS >> 4);
        wg_fence();
        wgmma<1, 1, HI_OST, !F>(c, a, b);
#pragma unroll
        for (int k = 1; k < 4; k++) wgmma<1, 1, HI_OST, true>(c, a + (k >> 1) * 512 + (k & 1) * 128, b + k * 320);
        wg_commit();
    };
    step(TrueT{});
#pragma unroll 1
    for (int t = 1; t < T; t++) {
        const uint32_t pslot = r.slot, pxs = xs;
        r.adv(1);
        if (++xs == 5) xs = 0;
        step(FalseT{});
        wg_wait<1>();
        mbar_arrive_warp(sb + BAR_REMPTY + pslot * 8);
        mbar_arrive_warp_if(sb + BAR_XEMPTY + pxs * 8, t + 2 < T);
    }
    xs += 1 + W;
    if (xs >= 5) xs -= 5;
    mbar_wait(sb + BAR_XFULL + xs * 8, (phm >> xs) & 1, r.dl);
    wg_wait<0>();
    reg_fence(c);
    store_tile_t<true>(c, sb + OFF_R + xs * XS + stsm_off());
    fence_async_smem();
    nb_arrive<NB_ODONE, 288>();
}

template <int W>
__device__ __forceinline__ uint32_t qa_item(uint32_t e, uint32_t sb, Ring& r, uint32_t phm, PendO& po, float (&q0)[80],
                                            float (&oa)[80], int it) {
    const uint32_t loR = (((sb + OFF_R) & 0x3ffff) >> 4) | LO_LBO1;
    const uint32_t loRing = (((sb + OFF_RING) & 0x3ffff) >> 4) | LO_LBO1;
    qproj<W, 0>(q0, oa, sb, r, 0, phm, po);
    fence_async_smem();
    TSD(W, 1);
    float s[80], ob[W == 0 ? 32 : 48], l[10];
    if (W == 1) {
        nb_arrive<NB_Q2, 256>();
        zero(oa);
        zero(ob);
        reg_fence(oa);
        reg_fence(ob);
    }
    const uint32_t lane = tid_now() & 31, sta = sb + OFF_R + stsm_off();
    auto pv = [&](auto first, uint32_t buf) {
        constexpr bool F = decltype(first)::value;
        if (F) mbar_wait(sb + BAR_RFULL + r.slot * 8, r.ph, r.dl);
        const uint32_t a = loRing + r.slot * (SLOT >> 4), b = loR + (3 + buf) * (XS >> 4);
        wg_fence();
        wgmma<1, 0, HI_SW128, F ? 2 : 1, HI_KV>(oa, a + W * 64, b);
        wgmma<1, 0, HI_SW128, !F, HI_KV>(ob, a + 128, b + (W == 0 ? (96 * 128) >> 4 : 0));
#pragma unroll
        for (int k = 1; k < 4; k++) {
            wgmma<1, 0, HI_SW128, true, HI_KV>(oa, a + W * 64 + k * 384, b + k * 2);
            wgmma<1, 0, HI_SW128, true, HI_KV>(ob, a + 128 + k * 384, b + (W == 0 ? (96 * 128) >> 4 : 0) + k * 2);
        }
        wg_commit();
    };
    zero(l);
    float mref;
    uint32_t kslot, vslot, nx = 0;
    auto tail = [&](auto first, int i) {
        constexpr bool rel_other = !decltype(first)::value;
        uint32_t ps[40];
        exp_block<0>(s, ps, sta + (3 + W) * XS, mref);
        if (rel_other) {
            wg_wait<0>();
            mbar_arrive_warp(sb + BAR_REMPTY + vslot * 8);
            if (W == 1) mbar_arrive_warp_if(sb + BAR_XEMPTY + 24, i == 3);
        }
        fence_async_smem();
        nb_arrive<NB_PFULL + W, 256>();
        TSD(W, 6 + 5 * i);
        if (W == 1) {
            mbar_arrive_warp_if<2>(sb + BAR_XEMPTY + 8, i == 3);
            mbar_arrive_warp_if<2>(sb + BAR_XEMPTY + 16, i == 3);
        }
        if (rel_other) {
            mbar_wait(sb + BAR_RFULL + r.slot * 8, r.ph, r.dl);
            sum_block(ps, l, lane);
        }
        if (W == 0 && i == 3) nx = get_item_warp(sb, it + 1, r.dl);
        TSD(W, 7 + 5 * i);
        nb_sync<NB_W + W, 128>();
        pv(first, W);
        if (!rel_other) sum_block(ps, l, lane);
        TSD(W, 8 + 5 * i);
    };
    if (W == 0) {
        nb_sync<NB_QK, 160>();
        TSD(W, 2);
        wg_fence();
        qk_steps<0, 8>(s, loRing + r.slot * (SLOT >> 4), loR);
        nb_sync<NB_Q2, 256>();
        qk_steps<8, 12>(s, loRing + r.slot * (SLOT >> 4), loR);
        wg_commit();
        nb_arrive<NB_Q01, 256>();
        TSD(W, 4);
        nb_sync<NB_REF, 160>();
        mref = __uint_as_float(lds_u(sb + OFF_GM));
        wg_wait<0>();
        reg_fence(s);
        mbar_arrive_warp<2>(sb + BAR_REMPTY + r.slot * 8);
        r.adv(2);
        TSD(W, 5);
        tail(TrueT{}, 0);
    } else {
        nb_sync<NB_Q01, 256>();
    }
#pragma unroll 1
    for (int i = (W == 0 ? 1 : 0); i < 4; i++) {
        const uint32_t pvslot = r.slot;
        r.adv(1);
        kslot = r.slot;
        mbar_wait(sb + BAR_RFULL + r.slot * 8, r.ph, r.dl);
        wg_fence();
        qk_steps<0, 4>(s, loRing + r.slot * (SLOT >> 4), loR);
        if (W == 1) wg_commit();
        qk_steps<4, 12>(s, loRing + r.slot * (SLOT >> 4), loR);
        wg_commit();
        wg_wait<1>();
        if (W == 1) mbar_arrive_warp_if(sb + BAR_XEMPTY + 0, i == 3);
        mbar_arrive_warp_if(sb + BAR_REMPTY + pvslot * 8, W == 0 || i > 0);
        r.adv(1);
        vslot = r.slot;
        TSD(W, 4 + 5 * i);
        mbar_wait(sb + BAR_RFULL + r.slot * 8, r.ph, r.dl);
        nb_sync<NB_PFULL + (W ^ 1), 256>();
        pv(FalseT{}, W ^ 1);
        if (W == 1) mref = __uint_as_float(lds_u(sb + OFF_GM));
        wg_wait<1>();
        reg_fence(s);
        mbar_arrive_warp<2>(sb + BAR_REMPTY + kslot * 8);
        if (W == 0) mbar_arrive_warp_if(sb + BAR_XEMPTY + 0, i == 3);
        r.adv(W == 1 && i == 3 ? 1 : 2);
        TSD(W, 5 + 5 * i);
        tail(FalseT{}, i);
    }
    if (W == 1) nx = get_item_warp(sb, it + 1, r.dl);
    if (W == 0) {
        Ring rn = r;
        rn.adv(2);
        q_ahead(q0, sb, rn, phm, IT_TYPE(nx) == IT_QA);
        TSD(W, 25);
    }
    const uint32_t w = (tid_now() >> 5) & 3;
    const uint32_t lxa = sb + OFF_LX + w * 640 + (((lane & 8) ? 80 : 0) + ((lane >> 1) & 8) + 2 * (lane & 3) + ((lane >> 2) & 1)) * 4;
    po.gp = ostash(IT_SLOT(e), IT_B(e)) + po.toff();
    po.sig = 1;
    if (W == 0) {
        sum_store<false>(l, lane, lxa);
        nb_arrive<NB_LX, 256>();
        wg_wait<1>();
        mbar_arrive_warp(sb + BAR_REMPTY + r.slot * 8);
        mbar_arrive_warp(sb + BAR_XEMPTY + 24);
        r.adv(1);
        mbar_wait(sb + BAR_RFULL + r.slot * 8, r.ph, r.dl);
        nb_sync<NB_PFULL + 1, 256>();
        pv(FalseT{}, 1);
    } else {
        nb_sync<NB_LX, 256>();
        sum_store<true>(l, lane, lxa);
        nb_arrive<NB_L, 160>();
    }
    TSD(W, 24);
    wg_wait<0>();
    reg_fence(oa);
    reg_fence(ob);
    mbar_arrive_warp(sb + BAR_REMPTY + r.slot * 8);
    mbar_arrive_warp(sb + BAR_XEMPTY + 32);
    r.adv(1);
    opack(ob, po.v + 40);
    opack(oa, po.v);
    return nx;
}

template <int W>
__device__ __forceinline__ uint32_t qa_run(uint32_t e, uint32_t sb, Ring& r, uint32_t phm, PendO& po, int& it) {
    float q0[80], oa[80];
    if (W == 0) {
        zero(oa);
        q_ahead(q0, sb, r, phm, true);
        wg_wait<0>();
    }
#pragma unroll 1
    do {
        TS(W, 0);
        if (W == 0) TS_ITEM(e);
        e = qa_item<W>(e, sb, r, phm, po, q0, oa, it);
        TS(W, 31);
        it++;
    } while (IT_TYPE(e) == IT_QA && !po.bad);
    if (W == 0) {
#pragma unroll
        for (int i = 56; i < 64; i++) po.v[i] = 0;
    }
    return e;
}

__device__ __forceinline__ void consumer(const Params& P, uint32_t W, uint32_t sb, uint32_t dl) {
    int it = 0;
    Ring r{0, 0, dl};
    uint32_t phm = 0;
    uint32_t e = get_item_warp(sb, 0, dl);
#pragma unroll 1
    while (true) {
        if (IT_TYPE(e) == IT_QA) {
            PendO po;
            po.clear();
            e = W == 0 ? qa_run<0>(e, sb, r, phm, po, it) : qa_run<1>(e, sb, r, phm, po, it);
#pragma unroll 1
            for (int m = po.bad ? 2 : 1; m > 0; m--) {
                if (m == 1) {
                    po.verdict(sb, W);
                    if (W == 0) po.flush<0>(sb);
                    else po.flush<1>(sb);
                }
                if (po.bad) {
                    if (W == 0) fallback_unit(P, lds_u(sb + OFF_ITEM + (it - m) * 4), tid_now() & 127);
                    __syncwarp();
                    nb_sync<NB_ODONE, 288>();
                }
            }
        }
        if (e == 0) break;
        if (IT_TYPE(e) == IT_QA) continue;
        TS(W, 0);
        if (W == 0) TS_ITEM(e);
        if (IT_TYPE(e) == IT_ON) on_item(W, e, sb, r, phm);
        else if (W == 0) op_item<true>(e, sb, r, phm);
        else op_item<false>(e, sb, r, phm);
        TS(W, 31);
        e = get_item_warp(sb, ++it, dl);
    }
    TS_DUMP(W);
}

__global__ void __cluster_dims__(2, 1, 1) __launch_bounds__(384, 1) fused_kernel(const __grid_constant__ Params P) {
    extern __shared__ __align__(1024) unsigned char smem_raw[];
    const uint32_t sb = (uint32_t)__cvta_generic_to_shared(smem_raw);
    const uint32_t warp = __shfl_sync(0xffffffffu, threadIdx.x >> 5, 0), wgid = warp >> 2;
    const uint32_t cta = blockIdx.x;
    const uint32_t dl = deadline();

    if (threadIdx.x == 128) {
#pragma unroll
        for (int i = 0; i < NSLOT; i++) {
            mbar_init(sb + BAR_RFULL + i * 8, 1);
            mbar_init(sb + BAR_REMPTY + i * 8, 8);
            mbar_init(sb + BAR_XFULL + i * 8, 1);
            mbar_init(sb + BAR_XEMPTY + i * 8, 8);
        }
        asm volatile("fence.mbarrier_init.release.cluster;" ::: "memory");
        fence_async_smem();
    } else if (threadIdx.x == 160) {
#pragma unroll
        for (int i = 0; i < NSLOT + MAXI; i++) mbar_init(sb + BAR_PRDY + i * 8, 1);
        asm volatile("fence.mbarrier_init.release.cluster;" ::: "memory");
    } else if (threadIdx.x == 0) {
        sts_u(sb + OFF_ITEM, P.cl[cta >> 1].items[0] ? P.cl[cta >> 1].items[0] + 8 * (cta & 1) : 0);
        sts_u(sb + OFF_FB, P.cl[cta >> 1].delay);
    } else if (threadIdx.x == 64) {
        if (sb & 1023) __trap();
        asm volatile("prefetch.tensormap [%0];" ::"l"(&P.wq[0]) : "memory");
        asm volatile("prefetch.tensormap [%0];" ::"l"(&P.x[0]) : "memory");
    }
    __syncthreads();
    {
        const int it = 0;
        if (wgid == 1) TS(0, 30);
    }
    asm volatile("barrier.cluster.arrive.relaxed.aligned;" ::: "memory");
    if (warp < 3) {
        const uint32_t e = __shfl_sync(0xffffffffu, lds_u(sb + OFF_ITEM), 0), d = lds_u(sb + OFF_FB);
        const uint64_t pol = pol_shared();
        const bool isx = warp == 1, lead = (threadIdx.x & 31) == 0;
        uint32_t t0, t1;
        asm volatile("mov.u32 %0, %%clock;" : "=r"(t0));
        do {
            asm volatile("mov.u32 %0, %%clock;" : "=r"(t1));
        } while (t1 - t0 < d);
        __syncwarp();
#pragma unroll 1
        for (int n = 0; n < (e ? NSLOT : 0); n++) {
            const uint32_t bar = sb + (isx ? BAR_XFULL : BAR_RFULL) + n * 8;
            if (lead) {
                if (warp < 2) mbar_expect(bar, isx ? XS : SLOT);
                tma3(sb + (isx ? OFF_R + n * XS : OFF_RING + n * SLOT + warp * (SLOT / 4)), isx ? &P.x[0] : &P.wq[0],
                     isx ? IT_B(e) * 160 : n * 64 + warp * 16, isx ? n : IT_H0(e) * 3, bar, pol);
            }
        }
        if (threadIdx.x == 0) asm volatile("mbarrier.arrive.shared::cta.b64 _, [%0];" ::"r"(sb + BAR_ITEM) : "memory");
        __syncwarp();
    }

    if (wgid == 0) {
        asm volatile("setmaxnreg.dec.sync.aligned.u32 24;");
        if (warp == 0) {
            const bool lead = threadIdx.x == 0;
            const uint64_t pol_first = pol_stream(), pol_norm = pol_shared();
            uint32_t e = __shfl_sync(0xffffffffu, lds_u(sb + OFF_ITEM), 0);
            asm volatile("barrier.cluster.wait.aligned;" ::: "memory");
            unsigned int* const ticket = &g_ticket[next_epoch(0) & 1];
            const uint32_t rank = cta & 1;
            uint32_t peer;
            asm volatile("mapa.shared::cluster.u32 %0, %1, %2;" : "=r"(peer) : "r"(sb), "r"(rank ^ 1));
            Ring r{0, 0, dl};
            uint32_t pm = 0;
            auto load_w = [&](const CUtensorMap* m, int row, int blk, uint32_t half_bytes) {
                mbar_wait(sb + BAR_REMPTY + r.slot * 8, r.ph, dl);
                if (lead) {
                    mbar_expect(sb + BAR_RFULL + r.slot * 8, 2 * half_bytes);
                    asm volatile("mbarrier.arrive.shared::cluster.b64 _, [%0];" ::"r"(peer + BAR_PRDY + r.slot * 8) : "memory");
                }
                mbar_wait(sb + BAR_PRDY + r.slot * 8, (pm >> r.slot) & 1, dl);
                pm ^= 1u << r.slot;
                if (lead) tma3_mc(sb + OFF_RING + r.slot * SLOT + rank * half_bytes, m, row, blk, sb + BAR_RFULL + r.slot * 8, pol_norm);
                r.adv(1);
            };
#pragma unroll 1
            for (int it = 0; e != 0; it++) {
                uint32_t nx = 0, tk = 0;
                if (rank == 0 && IT_TYPE(e) != IT_ON && it + 2 < MAXI) nx = it + 1 < NSTAT ? P.cl[cta >> 1].items[it + 1] : IT_DYN;
                const uint32_t br = IT_BR(e);
                if (IT_TYPE(e) == IT_QA) {
                    const uint32_t h = IT_H0(e);
#pragma unroll 1
                    for (int kk = it ? 0 : NSLOT; kk < 10; kk++) load_w(&P.wq[br], kk * 64 + rank * 32, h * 3, SLOT / 2);
                    const int grp0 = (IT_B(e) * 32 + h) * 64;
#pragma unroll 1
                    for (int n = 0; n < 16; n++) {
                        if (n == 13 && nx == IT_DYN && lead) tk = atomicAdd(ticket, 1);
                        const bool isv = n == 15 || (n > 0 && !(n & 1));
                        const int j = n == 15 ? 7 : isv ? (n - 2) >> 1 : (n + 1) >> 1;
                        mbar_wait(sb + BAR_REMPTY + r.slot * 8, r.ph, dl);
                        if (lead) {
                            mbar_expect(sb + BAR_RFULL + r.slot * 8, SLOT);
                            asm volatile(
                                "cp.async.bulk.tensor.4d.shared::cluster.global.mbarrier::complete_tx::bytes.L2::cache_hint"
                                " [%0], [%1, {%3,%3,%3,%4}], [%2], %5;" ::"r"(sb + OFF_RING + r.slot * SLOT),
                                "l"(isv ? &P.v[br] : &P.k[br]), "r"(sb + BAR_RFULL + r.slot * 8), "r"(0), "r"(grp0 + j * 8), "l"(pol_first)
                                : "memory");
                        }
                        r.adv(1);
                    }
                } else {
                    const bool wide = IT_TYPE(e) == IT_OP;
                    const int step = wide ? 32 : 64, r1 = IT_H1(e) * 192;
#pragma unroll 1
                    for (int row = IT_H0(e) * 192 + rank * (step >> 1); row < r1; row += step)
                        load_w(wide ? &P.wo[br] : &P.won[br], row, IT_HALF(e) * (wide ? 5 : 2), wide ? XS / 2 : 8192);
                    if (nx == IT_DYN && lead) tk = atomicAdd(ticket, 1);
                }
                if (rank == 0) {
                    if (nx == IT_DYN) {
                        tk = __shfl_sync(0xffffffffu, tk, 0);
                        nx = tk < P.nlist ? P.list[tk] : 0;
                    }
                    e = nx;
                    if (lead) {
                        asm volatile("st.async.weak.shared::cluster.mbarrier::complete_tx::bytes.b32 [%0], %1, [%2];" ::"r"(
                                         peer + OFF_ITEM + 4 + it * 4),
                                     "r"(e ? e + 8 : 0), "r"(peer + BAR_ITEM + 8 + it * 8)
                                     : "memory");
                        sts_u(sb + OFF_ITEM + 4 + it * 4, e);
                        asm volatile("mbarrier.arrive.shared::cta.b64 _, [%0];" ::"r"(sb + BAR_ITEM + 8 + it * 8) : "memory");
                    }
                } else {
                    if (lead) mbar_expect(sb + BAR_ITEM + 8 + it * 8, 4);
                    e = get_item_warp(sb, it + 1, dl);
                }
            }
        } else if (warp == 1) {
            const uint64_t pol_norm = pol_shared(), pol_o = pol_stream();
            const bool lead = threadIdx.x == 32;
            uint32_t phm = 0, epoch = 0;
#pragma unroll 1
            for (int it = 0;; it++) {
                const uint32_t e = get_item_warp(sb, it, dl);
                if (it == 1 || (it == 0 && e == 0)) epoch = next_epoch(1);
                if (e == 0) break;
                const uint32_t br = IT_BR(e);
                uint32_t xs = 0;
                auto acquire = [&]() {
                    mbar_wait(sb + BAR_XEMPTY + xs * 8, (phm >> xs) & 1, dl);
                    phm ^= 1u << xs;
                    if (lead) mbar_expect(sb + BAR_XFULL + xs * 8, XS);
                };
                if (IT_TYPE(e) == IT_QA) {
#pragma unroll 1
                    for (int kk = it ? 0 : 5; kk < 10; kk++) {
                        acquire();
                        if (lead) tma3(sb + OFF_R + xs * XS, &P.x[br], IT_B(e) * 160, kk, sb + BAR_XFULL + xs * 8, pol_norm);
                        if (++xs == 5) xs = 0;
                    }
                } else {
                    const unsigned int* fp = g_flag + (br * 16 + IT_B(e)) * 64 + (threadIdx.x & 31) * 2;
                    uint32_t hm = 0, pm = 0;
                    auto poll = [&](uint32_t hneed, uint32_t pneed) {
                        if ((hm & hneed) == hneed && (pm & pneed) == pneed) return;
                        uint32_t n = 0;
                        do {
                            uint32_t a, b;
                            asm volatile("ld.acquire.gpu.global.v2.u32 {%0, %1}, [%2];" : "=r"(a), "=r"(b) : "l"(fp) : "memory");
                            hm = __ballot_sync(0xffffffffu, a == epoch);
                            pm = __ballot_sync(0xffffffffu, b == epoch);
                            if (++n > 0x1000000) __trap();
                        } while ((hm & hneed) != hneed || (pm & pneed) != pneed);
                        __syncwarp();
                        asm volatile("fence.proxy.async.global;" ::: "memory");
                    };
#pragma unroll 1
                    for (uint32_t h = IT_H0(e); h < IT_H1(e); h++) {
                        poll(1u << h, 0);
                        const unsigned char* src = ostash(P.slot[br * 32 + h], IT_B(e));
#pragma unroll 1
                        for (int t = 0; t < 3; t++) {
                            acquire();
                            if (lead) bulk_load(sb + OFF_R + xs * XS, src + t * XS, XS, sb + BAR_XFULL + xs * 8, pol_o);
                            if (++xs == 5) xs = 0;
                        }
                        if (IT_TYPE(e) == IT_OP && h >= 1) {
                            const uint32_t x1 = xs == 4 ? 0 : xs + 1;
                            mbar_wait(sb + BAR_XFULL + xs * 8, (phm >> xs) & 1, dl);
                            mbar_wait(sb + BAR_XFULL + x1 * 8, (phm >> x1) & 1, dl);
                            if (lead)
                                asm volatile("st.relaxed.gpu.global.u32 [%0], %1;" ::"l"(fp + 5 + 2 * IT_HALF(e)), "r"(epoch * 64 + h) : "memory");
                        }
                    }
                    if (IT_TYPE(e) == IT_ON) {
                        poll(0, IT_HALF(e) < 2 ? 1 : IT_HALF(e) == 2 ? 3 : 2);
#pragma unroll 1
                        for (uint32_t tile = 2 * IT_HALF(e); tile < 2 * IT_HALF(e) + 2; tile++) {
                            acquire();
                            if (lead)
                                asm volatile(
                                    "cp.async.bulk.tensor.5d.shared::cluster.global.mbarrier::complete_tx::bytes [%0], [%1, {%3,%5,%5,%5,%4}], [%2];" ::"r"(
                                        sb + OFF_R + xs * XS),
                                    "l"(&P.out), "r"(sb + BAR_XFULL + xs * 8), "r"(br * 640 + tile * 64), "r"(IT_B(e) * 5), "r"(0)
                                    : "memory");
                            if (++xs == 5) xs = 0;
                        }
                    }
                }
            }
        } else if (warp == 2) {
            asm volatile("barrier.cluster.wait.aligned;" ::: "memory");
            const uint32_t epoch = next_epoch(2);
            if (cta == 0) g_ticket[(epoch + 1) & 1] = 0;
#pragma unroll 1
            for (int it = 0;; it++) {
                const uint32_t e = get_item_warp(sb, it, dl);
                if (e == 0) break;
                nb_sync<NB_ODONE, 288>();
                if (threadIdx.x == 64) {
                    const uint32_t bb = IT_BR(e) * 16 + IT_B(e);
                    if (IT_TYPE(e) != IT_QA) {
                        const bool wide = IT_TYPE(e) == IT_OP;
                        if (wide)
                            asm volatile("st.relaxed.gpu.global.u32 [%0], %1;" ::"l"(&g_flag[bb * 64 + 5 + 2 * IT_HALF(e)]),
                                         "r"(epoch * 64 + IT_H1(e))
                                         : "memory");
                        const int cc0 = IT_BR(e) * 640 + IT_HALF(e) * (wide ? 320 : 128);
                        uint32_t xs = wide ? 0 : (3 * (IT_H1(e) - IT_H0(e))) % 5;
#pragma unroll 1
                        for (int m = 0; m < (wide ? 5 : 2); m++) {
                            asm volatile("cp.async.bulk.tensor.5d.global.shared::cta.bulk_group [%0, {%2,%4,%4,%4,%3}], [%1];" ::"l"(&P.out),
                                         "r"(sb + OFF_R + xs * XS), "r"(cc0 + m * 64), "r"((int)IT_B(e) * 5), "r"(0)
                                         : "memory");
                            asm volatile("cp.async.bulk.commit_group;" ::: "memory");
                            if (wide && m >= 1) {
                                asm volatile("cp.async.bulk.wait_group.read 1;" ::: "memory");
                                asm volatile("mbarrier.arrive.shared::cta.b64 _, [%0], 8;" ::"r"(sb + BAR_XEMPTY + (m - 1) * 8) : "memory");
                            }
                            if (++xs == 5) xs = 0;
                        }
                        if (wide) {
                            asm volatile("cp.async.bulk.wait_group.read 0;" ::: "memory");
                            asm volatile("mbarrier.arrive.shared::cta.b64 _, [%0], 8;" ::"r"(sb + BAR_XEMPTY + 32) : "memory");
                        }
                        if (IT_PART(e)) {
                            asm volatile("cp.async.bulk.wait_group 0;" ::: "memory");
                            asm volatile("fence.proxy.async.global;" ::: "memory");
                        }
                    }
                    if (IT_TYPE(e) == IT_QA || IT_PART(e)) {
                        unsigned int* f = &g_flag[bb * 64 + (IT_TYPE(e) == IT_QA ? 2 * IT_H0(e) : 1 + 2 * IT_HALF(e))];
                        asm volatile("st.release.gpu.global.u32 [%0], %1;" ::"l"(f), "r"(epoch) : "memory");
                    }
                }
                __syncwarp();
            }
            if (threadIdx.x == 64) asm volatile("cp.async.bulk.wait_group 0;" ::: "memory");
            __syncwarp();
            asm volatile("barrier.cluster.arrive.relaxed.aligned;\nbarrier.cluster.wait.aligned;" ::: "memory");
        } else {
            const uint32_t lane = threadIdx.x & 31, p = lane >> 3;
            const uint32_t epoch = next_epoch(3);
#pragma unroll 1
            for (int it = 0;; it++) {
                const uint32_t e = get_item_warp(sb, it, dl);
                if (e == 0) break;
                if (IT_TYPE(e) != IT_QA) continue;
                nb_sync<NB_QK, 160>();
                const uint32_t ka = sb + OFF_RING + lds_u(sb + OFF_GM + 4) * SLOT + p * (2 * 3072 + 256) + (lane & 7) * 16;
                const uint32_t qa = sb + OFF_R + p * 256 + (lane & 7) * 16;
                uint32_t acc = 0;
#pragma unroll 1
                for (int c = 0; c < 3; c++) {
                    const uint4 k = lds_u4(ka + c * 1024);
                    if (c == 2) nb_sync<NB_L, 160>();
                    const uint4 q = lds_u4(qa + c * XS);
                    acc = fma_bf2(k.x, q.x, fma_bf2(k.y, q.y, fma_bf2(k.z, q.z, fma_bf2(k.w, q.w, acc))));
                }
                const float d = __uint_as_float(acc << 16) + __uint_as_float(acc & 0xffff0000u);
                const int sum = __reduce_add_sync(0xffffffffu, __float2int_rn(d * 16.f));
                sts_f(sb + OFF_GM, fmaf((float)sum, SM_C / 64.f, 24.f));
                nb_arrive<NB_REF, 160>();
                if (IT_DEP(e)) {
                    const uint32_t g = IT_DEP(e) - 1, need = epoch * 64 + (g & 31) + 1;
                    const unsigned int* cp = &g_flag[((g >> 5) * 16 + IT_B(e)) * 64 + 5 + 2 * (lane & 1)];
                    for (uint32_t n = 0;; n++) {
                        uint32_t v;
                        asm volatile("ld.acquire.gpu.global.u32 %0, [%1];" : "=r"(v) : "l"(cp) : "memory");
                        if (__all_sync(0xffffffffu, v - need < 64)) break;
                        if (n > 0x800000) __trap();
                        __nanosleep(500);
                    }
                }
                nb_sync<NB_L, 160>();
                bool bad = false;
#pragma unroll
                for (int c = 0; c < 5; c++) {
                    const uint32_t la = sb + OFF_LX + (c * 32 + lane) * 4;
                    const float v = (__uint_as_float(lds_u(la)) + __uint_as_float(lds_u(la + 640))) +
                                    (__uint_as_float(lds_u(la + 1280)) + __uint_as_float(lds_u(la + 1920)));
                    const float inv = __fdividef(1.f, v);
                    const uint32_t hi = pack_bf16(inv, 0.f), lo = pack_bf16(inv - __uint_as_float(hi << 16), 0.f);
                    const uint32_t ia = sb + OFF_LINV + c * 128 + ((lane >> 1) & 3) * 32 + (lane >> 3) * 8 + (lane & 1) * 2;
                    asm volatile("st.shared.u16 [%0], %1;\nst.shared.u16 [%0+4], %2;" ::"r"(ia), "h"((unsigned short)hi), "h"((unsigned short)lo) : "memory");
                    bad |= !(v >= 5.421010862e-20f && v <= 7.9228163e28f);
                }
                sts_u(sb + OFF_FB, __any_sync(0xffffffffu, bad));
                nb_arrive<NB_VOTE, 160>();
                nb_arrive<NB_VOTE + 1, 160>();
            }
        }
    } else {
        asm volatile("setmaxnreg.inc.sync.aligned.u32 240;");
        consumer(P, wgid - 1, sb, dl);
    }
}

typedef CUresult (*EncFn)(CUtensorMap*, CUtensorMapDataType, cuuint32_t, void*, const cuuint64_t*, const cuuint64_t*,
                          const cuuint32_t*, const cuuint32_t*, CUtensorMapInterleave, CUtensorMapSwizzle,
                          CUtensorMapL2promotion, CUtensorMapFloatOOBfill);

void make_map3(EncFn enc, CUtensorMap* m, void* p, uint64_t rows, uint64_t rowbytes, uint64_t nblk, uint32_t boxrows,
               uint32_t boxblk) {
    cuuint64_t dims[3] = {64, rows, nblk};
    cuuint64_t str[2] = {rowbytes, 128};
    cuuint32_t box[3] = {64, boxrows, boxblk};
    cuuint32_t es[3] = {1, 1, 1};
    enc(m, CU_TENSOR_MAP_DATA_TYPE_BFLOAT16, 3, p, dims, str, box, es, CU_TENSOR_MAP_INTERLEAVE_NONE,
        CU_TENSOR_MAP_SWIZZLE_128B, CU_TENSOR_MAP_L2_PROMOTION_NONE, CU_TENSOR_MAP_FLOAT_OOB_FILL_NONE);
}

constexpr int tune(const char*, int def) { return def; }

void build_schedule(Params& P, int ncl) {
    const int mode = tune("MODE", 4), dmax = tune("DMAX", 24200), n0 = tune("N0", 10);
    const int H0[8] = {19, 20, 21, 22, 22, 24, 25, 25}, P0[8] = {367, 337, 335, 331, 338, 335, 333, 332};
    const int ra = tune("RA", 10), ga = tune("GA", 17), rb = tune("RB", 11), g1 = tune("G1", 58);
    int dep[64];
    for (int g = 0, ns = 0, live = 0; g < 64; g++) {
        const bool fresh = mode < 3 || g >= g1 || live < (g < ga ? ra : rb);
        dep[g] = fresh ? 0 : g - live + 1;
        P.slot[g] = fresh ? ns++ : P.slot[g - live];
        live += fresh;
    }
    int H[8], pos[8], psum = 0;
    for (int b = 0; b < 8; b++) {
        const char nh[3] = {'H', (char)('0' + b), 0}, np[3] = {'P', (char)('0' + b), 0};
        H[b] = tune(nh, H0[b]);
        pos[b] = tune(np, P0[b]);
        psum += pos[b];
    }
    const int sk = tune("SK", 10), g0 = tune("G0", 20), g2 = tune("G2", 40);
    int ord[512], nxt[8] = {0, 0, 0, 0, 0, 0, 0, 0};
    for (int k = 0; k < 512; k++) {
        int best = -1;
        float bkey = 0.f;
        for (int b = 0; b < 8; b++) {
            const int g = nxt[b];
            if (g == 64) continue;
            const float w = g < g0 ? 0.f : g < 32 ? (g - g0) / (32.f - g0) : g < g2 ? 1.f : (64 - g) / (64.f - g2);
            const float key = g + w * sk * 0.1f * (pos[b] - psum / 8.f) / 8.f;
            if (best < 0 || key < bkey) best = b, bkey = key;
        }
        ord[k] = nxt[best]++ * 8 + best;
        const int d = dep[ord[k] >> 3];
        if (d > 32) {
            if (pos[best] > k) pos[best] = k;
            if (H[best] < d - 32) H[best] = d - 32;
        }
    }
    int u = 0;
    auto unit = [&]() {
        const int v = ord[u++];
        return mk_item(IT_QA, v >> 8, (v & 7) * 2, (v >> 3) & 31, P.slot[v >> 3], 0) | (dep[v >> 3] << 23);
    };
    int qa[NCL], nq = 0, op[NCL], no = 0;
    for (int c = 0; c < ncl; c++) {
        P.cl[c].delay = 0;
        for (int i = 0; i < NSTAT; i++) P.cl[c].items[i] = 0;
        if (mode >= 3 && c >= 4 && c < 20) op[((c - 4) & 7) * 2 + ((c - 4) >> 3)] = c, no++;
        else if (mode != 2 || (c & 3) == 0) qa[nq++] = c;
    }
    for (int t = 0; t < no; t++) {
        P.cl[op[t]].items[1] = mk_item(IT_OP, 0, t & ~1, 0, 32, t & 1);
        P.cl[op[t]].items[2] = IT_DYN;
            }
    for (int k = 0; k < nq; k++) {
        const int c = qa[(k * (nq % 19 ? 19 : 17)) % nq];
        P.cl[c].items[1] = P.cl[c].items[2] = IT_DYN;
        P.cl[c].delay = k < n0 ? 0 : dmax * (k + 1 - n0) / (nq - n0);
    }
    for (int t = 0; t < no && tune("OF", 1); t++) P.cl[op[(t & 7) * 2 + (t >> 3)]].items[0] = unit();
    for (int k = u; k < no + nq; k++) {
        int best = -1;
        for (int c = 0; c < ncl; c++)
            if (P.cl[c].items[1] && !P.cl[c].items[0] && (best < 0 || P.cl[c].delay < P.cl[best].delay)) best = c;
        P.cl[best].items[0] = unit();
    }
    int n = 0;
    const int uend = mode == 2 ? 8 * nq : 512;
    while (u < uend) {
        for (int b = 0; b < 8 && no; b++)
            if (pos[b] == u) {
                P.list[n++] = mk_item(IT_OP, 1, 2 * b, 0, H[b], 0, 1);
                P.list[n++] = mk_item(IT_OP, 1, 2 * b, 0, H[b], 1, 1);
            }
        P.list[n++] = unit();
    }
    for (int k = 0; no && k < 40; k++) P.list[n++] = mk_item(IT_ON, 1, k / 5 * 2, H[k / 5], 32, k % 5);
    P.nlist = n;
}

}

extern "C" void kernel_launch(void* const* d_in, const int* in_sizes, int n_in, void* d_out, int out_size) {
    static Params P;
    static bool init = false;
    static int ncl = NCL;
    if (!init) {
        EncFn enc = nullptr;
        cudaDriverEntryPointQueryResult qr;
        cudaGetDriverEntryPoint("cuTensorMapEncodeTiled", (void**)&enc, cudaEnableDefault, &qr);
        for (int i = 0; i < 2; i++) {
            P.px[i] = (const __nv_bfloat16*)d_in[5 * i + 0];
            P.pk[i] = (const __nv_bfloat16*)d_in[5 * i + 1];
            P.pv[i] = (const __nv_bfloat16*)d_in[5 * i + 2];
            P.pwq[i] = (const __nv_bfloat16*)d_in[5 * i + 3];
            make_map3(enc, &P.x[i], d_in[5 * i + 0], 2560, 1280, 10, 160, 1);
            for (int j = 0; j < 2; j++) {
                cuuint64_t dims[4] = {64, 8, 3, 16 * 32 * 64};
                cuuint64_t str[3] = {384, 128, 3072};
                cuuint32_t box[4] = {64, 8, 3, 8};
                cuuint32_t es[4] = {1, 1, 1, 1};
                enc(j ? &P.v[i] : &P.k[i], CU_TENSOR_MAP_DATA_TYPE_BFLOAT16, 4, d_in[5 * i + 1 + j], dims, str, box, es,
                    CU_TENSOR_MAP_INTERLEAVE_NONE, CU_TENSOR_MAP_SWIZZLE_128B, CU_TENSOR_MAP_L2_PROMOTION_NONE,
                    CU_TENSOR_MAP_FLOAT_OOB_FILL_NONE);
            }
            make_map3(enc, &P.wq[i], d_in[5 * i + 3], 640, 12288, 96, 32, 3);
            make_map3(enc, &P.wo[i], d_in[5 * i + 4], 6144, 1280, 10, 16, 5);
            make_map3(enc, &P.won[i], d_in[5 * i + 4], 6144, 1280, 10, 32, 2);
        }
        cuuint64_t dims[5] = {1280, 2, 4, 4, 80};
        cuuint64_t str[4] = {2560, 8 * 2560, 2 * 2560, 32 * 2560};
        cuuint32_t box[5] = {64, 2, 4, 4, 5};
        cuuint32_t es[5] = {1, 1, 1, 1, 1};
        enc(&P.out, CU_TENSOR_MAP_DATA_TYPE_BFLOAT16, 5, d_out, dims, str, box, es, CU_TENSOR_MAP_INTERLEAVE_NONE,
            CU_TENSOR_MAP_SWIZZLE_128B, CU_TENSOR_MAP_L2_PROMOTION_NONE, CU_TENSOR_MAP_FLOAT_OOB_FILL_NONE);
        cudaFuncSetAttribute(fused_kernel, cudaFuncAttributeMaxDynamicSharedMemorySize, SMEM_LAUNCH);
        cudaLaunchConfig_t cfg = {};
        cfg.gridDim = dim3(NCTA);
        cfg.blockDim = dim3(384);
        cfg.dynamicSmemBytes = SMEM_LAUNCH;
        int nc = 0;
        if (cudaOccupancyMaxActiveClusters(&nc, fused_kernel, &cfg) == cudaSuccess && nc >= 52 && nc < NCL) ncl = nc;
        (void)cudaGetLastError();
        ncl = tune("NCL", ncl);
        build_schedule(P, ncl);
        init = true;
    }
    fused_kernel<<<2 * ncl, 384, SMEM_LAUNCH>>>(P);
}
```

```cpp
#include <cuda_runtime.h>
#include <cuda.h>
#include <cuda_bf16.h>
#include <stdint.h>

namespace {

constexpr int NCTA = 132;
constexpr int NCL = NCTA / 2;
constexpr int MAXI = 16;
constexpr int NSTAT = 3;
constexpr uint32_t IT_DYN = 0xffffffffu;
constexpr int SLOT = 24576;
constexpr int NSLOT = 5;
constexpr int XS = 20480;
constexpr int OFF_R = 0;
constexpr int OFF_RING = 5 * XS;
constexpr int OFF_MISC = OFF_RING + NSLOT * SLOT;
constexpr int OFF_LX = OFF_MISC;
constexpr int OFF_LINV = OFF_LX + 2560;
constexpr int OFF_FB = OFF_LINV + 640;
constexpr int OFF_GM = OFF_FB + 16;
constexpr int OFF_BAR = OFF_GM + 16;
constexpr int BAR_RFULL = OFF_BAR;
constexpr int BAR_REMPTY = BAR_RFULL + 40;
constexpr int BAR_XFULL = BAR_REMPTY + 40;
constexpr int BAR_XEMPTY = BAR_XFULL + 40;
constexpr int BAR_PRDY = BAR_XEMPTY + 40;
constexpr int BAR_ITEM = BAR_PRDY + 40;
constexpr int OFF_ITEM = BAR_ITEM + MAXI * 8;
constexpr int SMEM_BYTES = OFF_ITEM + MAXI * 4;
static_assert(SMEM_BYTES <= 232448, "smem");

constexpr int NB_W = 1  , NB_PFULL = 3  , NB_VOTE = 5  , NB_Q2 = 7, NB_SDONE = 8, NB_PDONE = 9,
              NB_L = 10, NB_REF = 11, NB_ODONE = 12, NB_OPEND = 13, NB_LX = 14, NB_Q01 = 15, NB_QK = 0  ;

constexpr uint32_t IT_QA = 1, IT_OP = 2, IT_ON = 3;
__host__ __device__ constexpr uint32_t mk_item(uint32_t type, uint32_t br, uint32_t b, uint32_t h0, uint32_t h1, uint32_t half,
                                               uint32_t part = 0) {
    return type | (br << 2) | (b << 3) | (h0 << 7) | (h1 << 13) | (half << 19) | (part << 22);
}
#define IT_TYPE(e) ((e) & 3u)
#define IT_BR(e) (((e) >> 2) & 1u)
#define IT_B(e) (((e) >> 3) & 15u)
#define IT_H0(e) (((e) >> 7) & 63u)
#define IT_H1(e) (((e) >> 13) & 63u)
#define IT_HALF(e) (((e) >> 19) & 7u)
#define IT_PART(e) (((e) >> 22) & 1u)
#define IT_SLOT(e) IT_H1(e)
#define IT_DEP(e) (((e) >> 23) & 127u)

struct Params {
    CUtensorMap x[2], wq[2], k[2], v[2], wo[2], won[2], out;
    const __nv_bfloat16 *px[2], *pwq[2], *pk[2], *pv[2];
    struct alignas(16) { uint32_t delay, items[NSTAT]; } cl[NCL];
    uint32_t nlist;
    uint8_t slot[64];
    uint32_t list[568];
};

constexpr int OUNIT = 61440;
__device__ __align__(1024) unsigned char g_ostash[(size_t)1024 * OUNIT];
__device__ __align__(256) unsigned int g_flag[32 * 64];
__device__ __forceinline__ unsigned char* ostash(uint32_t slot, uint32_t b) { return g_ostash + (slot * 16 + b) * OUNIT; }
__device__ unsigned int g_epoch[NCTA * 4];
__device__ unsigned int g_ticket[2];

constexpr int SMEM_LAUNCH = SMEM_BYTES;
#define TS(role, idx)
#define TS_ITEM(e)
#define TS_DUMP(role)
#define TSD(role, idx)

__device__ __forceinline__ uint64_t pol_stream() {
    uint64_t p;
    asm volatile("createpolicy.fractional.L2::evict_first.b64 %0, 1.0;" : "=l"(p));
    return p;
}
__device__ __forceinline__ uint64_t pol_shared() {
    uint64_t p;
    asm volatile("createpolicy.fractional.L2::evict_unchanged.b64 %0, 1.0;" : "=l"(p));
    return p;
}
constexpr int QHOLD = 8;
constexpr float SM_C = 0.07216878364870322f * 1.4426950408889634f;

__device__ __forceinline__ uint32_t next_epoch(int warp) {
    unsigned int* p = &g_epoch[blockIdx.x * 4 + warp];
    const uint32_t e = __ldcg(p) + 1;
    *p = e;
    return e;
}

__device__ __forceinline__ uint32_t tid_now() {
    uint32_t t;
    asm volatile("mov.u32 %0, %%tid.x;" : "=r"(t));
    return t;
}
__device__ __forceinline__ void mbar_init(uint32_t a, uint32_t c) {
    asm volatile("mbarrier.init.shared::cta.b64 [%0], %1;" ::"r"(a), "r"(c) : "memory");
}
__device__ __forceinline__ void mbar_expect(uint32_t a, uint32_t b) {
    asm volatile("mbarrier.arrive.expect_tx.shared::cta.b64 _, [%0], %1;" ::"r"(a), "r"(b) : "memory");
}
template <int CNT = 1>
__device__ __forceinline__ void mbar_arrive_warp(uint32_t a) {
    if (CNT == 1)
        asm volatile("{\n.reg .pred p;\nelect.sync _|p, 0xffffffff;\n@p mbarrier.arrive.shared::cta.b64 _, [%0];\n}" ::"r"(a) : "memory");
    else
        asm volatile(
            "{\n.reg .pred p;\nelect.sync _|p, 0xffffffff;\n@p mbarrier.arrive.shared::cta.b64 _, [%0];\n"
            "@p mbarrier.arrive.shared::cta.b64 _, [%0];\n}" ::"r"(a)
            : "memory");
}
template <int CNT = 1>
__device__ __forceinline__ void mbar_arrive_warp_if(uint32_t a, bool cond) {
    if (CNT == 1)
        asm volatile(
            "{\n.reg .pred p, c;\nelect.sync _|p, 0xffffffff;\nsetp.ne.and.u32 c, %1, 0, p;\n"
            "@c mbarrier.arrive.shared::cta.b64 _, [%0];\n}" ::"r"(a), "r"((uint32_t)cond)
            : "memory");
    else
        asm volatile(
            "{\n.reg .pred p, c;\nelect.sync _|p, 0xffffffff;\nsetp.ne.and.u32 c, %1, 0, p;\n"
            "@c mbarrier.arrive.shared::cta.b64 _, [%0];\n@c mbarrier.arrive.shared::cta.b64 _, [%0];\n}" ::"r"(a), "r"((uint32_t)cond)
            : "memory");
}
__device__ __forceinline__ uint32_t deadline() {
    uint32_t c;
    asm volatile("mov.u32 %0, %%clock_hi;" : "=r"(c));
    return c + 4;
}
__device__ __forceinline__ void mbar_wait(uint32_t a, uint32_t ph, uint32_t dl) {
    asm volatile(
        "{\n.reg .pred p;\n.reg .u32 m;\n"
        "LOOP:\n"
        "mbarrier.try_wait.parity.shared::cta.b64 p, [%0], %1;\n"
        "@p bra DONE;\n"
        "mov.u32 m, %%clock_hi;\n"
        "setp.ne.u32 p, m, %2;\n"
        "@p bra LOOP;\n"
        "trap;\n"
        "DONE:\n}" ::"r"(a), "r"(ph), "r"(dl)
        : "memory");
}
__device__ __forceinline__ void mbar_wait2(uint32_t a, uint32_t pa, uint32_t b, uint32_t pb, uint32_t dl) {
    asm volatile(
        "{\n.reg .pred p, q;\n.reg .u32 m;\n"
        "LOOP:\n"
        "mbarrier.try_wait.parity.shared::cta.b64 p, [%0], %1;\n"
        "mbarrier.try_wait.parity.shared::cta.b64 q, [%2], %3;\n"
        "and.pred p, p, q;\n"
        "@p bra DONE;\n"
        "mov.u32 m, %%clock_hi;\n"
        "setp.ne.u32 p, m, %4;\n"
        "@p bra LOOP;\n"
        "trap;\n"
        "DONE:\n}" ::"r"(a), "r"(pa), "r"(b), "r"(pb), "r"(dl)
        : "memory");
}
template <int ID, int CNT>
__device__ __forceinline__ void nb_sync() { asm volatile("bar.sync %0, %1;" ::"n"(ID), "n"(CNT) : "memory"); }
template <int ID, int CNT>
__device__ __forceinline__ void nb_arrive() { asm volatile("bar.arrive %0, %1;" ::"n"(ID), "n"(CNT) : "memory"); }
__device__ __forceinline__ void fence_async_smem() { asm volatile("fence.proxy.async.shared::cta;" ::: "memory"); }

__device__ __forceinline__ void tma3(uint32_t dst, const CUtensorMap* m, int c1, int c2, uint32_t bar, uint64_t pol) {
    asm volatile(
        "cp.async.bulk.tensor.3d.shared::cluster.global.mbarrier::complete_tx::bytes.L2::cache_hint [%0], [%1, {%3,%4,%5}], [%2], %6;" ::"r"(dst),
        "l"(m), "r"(bar), "r"(0), "r"(c1), "r"(c2), "l"(pol)
        : "memory");
}
__device__ __forceinline__ void tma3_mc(uint32_t dst, const CUtensorMap* m, int c1, int c2, uint32_t bar, uint64_t pol) {
    asm volatile(
        "cp.async.bulk.tensor.3d.shared::cluster.global.mbarrier::complete_tx::bytes.multicast::cluster.L2::cache_hint"
        " [%0], [%1, {%3,%4,%5}], [%2], %6, %7;" ::"r"(dst),
        "l"(m), "r"(bar), "r"(0), "r"(c1), "r"(c2), "h"((unsigned short)3), "l"(pol)
        : "memory");
}
__device__ __forceinline__ void bulk_load(uint32_t dst, const void* src, uint32_t bytes, uint32_t bar, uint64_t pol) {
    asm volatile("cp.async.bulk.shared::cluster.global.mbarrier::complete_tx::bytes.L2::cache_hint [%0], [%1], %2, [%3], %4;" ::"r"(dst),
                 "l"(src), "r"(bytes), "r"(bar), "l"(pol)
                 : "memory");
}
__device__ __forceinline__ void wg_fence() { asm volatile("wgmma.fence.sync.aligned;" ::: "memory"); }
__device__ __forceinline__ void wg_commit() { asm volatile("wgmma.commit_group.sync.aligned;" ::: "memory"); }
template <int N>
__device__ __forceinline__ void wg_wait() { asm volatile("wgmma.wait_group.sync.aligned %0;" ::"n"(N) : "memory"); }

#define RW80(c, d) c(d[0]), c(d[1]), c(d[2]), c(d[3]), c(d[4]), c(d[5]), c(d[6]), c(d[7]), c(d[8]), c(d[9]), c(d[10]), c(d[11]), c(d[12]), c(d[13]), c(d[14]), c(d[15]), c(d[16]), c(d[17]), c(d[18]), c(d[19]), c(d[20]), c(d[21]), c(d[22]), c(d[23]), c(d[24]), c(d[25]), c(d[26]), c(d[27]), c(d[28]), c(d[29]), c(d[30]), c(d[31]), c(d[32]), c(d[33]), c(d[34]), c(d[35]), c(d[36]), c(d[37]), c(d[38]), c(d[39]), c(d[40]), c(d[41]), c(d[42]), c(d[43]), c(d[44]), c(d[45]), c(d[46]), c(d[47]), c(d[48]), c(d[49]), c(d[50]), c(d[51]), c(d[52]), c(d[53]), c(d[54]), c(d[55]), c(d[56]), c(d[57]), c(d[58]), c(d[59]), c(d[60]), c(d[61]), c(d[62]), c(d[63]), c(d[64]), c(d[65]), c(d[66]), c(d[67]), c(d[68]), c(d[69]), c(d[70]), c(d[71]), c(d[72]), c(d[73]), c(d[74]), c(d[75]), c(d[76]), c(d[77]), c(d[78]), c(d[79])
#define RW48(c, d) c(d[0]), c(d[1]), c(d[2]), c(d[3]), c(d[4]), c(d[5]), c(d[6]), c(d[7]), c(d[8]), c(d[9]), c(d[10]), c(d[11]), c(d[12]), c(d[13]), c(d[14]), c(d[15]), c(d[16]), c(d[17]), c(d[18]), c(d[19]), c(d[20]), c(d[21]), c(d[22]), c(d[23]), c(d[24]), c(d[25]), c(d[26]), c(d[27]), c(d[28]), c(d[29]), c(d[30]), c(d[31]), c(d[32]), c(d[33]), c(d[34]), c(d[35]), c(d[36]), c(d[37]), c(d[38]), c(d[39]), c(d[40]), c(d[41]), c(d[42]), c(d[43]), c(d[44]), c(d[45]), c(d[46]), c(d[47])
#define RW32(c, d) c(d[0]), c(d[1]), c(d[2]), c(d[3]), c(d[4]), c(d[5]), c(d[6]), c(d[7]), c(d[8]), c(d[9]), c(d[10]), c(d[11]), c(d[12]), c(d[13]), c(d[14]), c(d[15]), c(d[16]), c(d[17]), c(d[18]), c(d[19]), c(d[20]), c(d[21]), c(d[22]), c(d[23]), c(d[24]), c(d[25]), c(d[26]), c(d[27]), c(d[28]), c(d[29]), c(d[30]), c(d[31])

__device__ __forceinline__ void reg_fence(float (&d)[80]) { asm volatile("" : RW80("+f", d)::"memory"); }
__device__ __forceinline__ void reg_fence(float (&d)[48]) { asm volatile("" : RW48("+f", d)::"memory"); }
__device__ __forceinline__ void reg_fence(float (&d)[32]) { asm volatile("" : RW32("+f", d)::"memory"); }

template <int NR>
__device__ __forceinline__ void zero(float (&d)[NR]) {
#pragma unroll
    for (int i = 0; i < NR; i++) d[i] = 0.f;
}

constexpr uint32_t HI_SW128 = (1024u >> 4) | (1u << 30);
constexpr uint32_t HI_KV = (3072u >> 4) | (1u << 30);
constexpr uint32_t HI_OST = (2560u >> 4) | (2u << 30);
constexpr uint32_t LO_LBO1 = (1u << 16);
constexpr uint32_t LO_OST = ((512u >> 4) << 16);

template <int TA, int TB, uint32_t HIB, int ACC, uint32_t HIA = HI_SW128>
__device__ __forceinline__ void wgmma(float (&d)[80], uint32_t loA, uint32_t loB) {
#define WG_ASM(SD)                                                          \
    "{\n.reg .b64 da, db;\nmov.b64 da, {%80, %82};\nmov.b64 db, {%81, %83};\n" \
    "wgmma.mma_async.sync.aligned.m64n160k16.f32.bf16.bf16 "               \
    "{%0,%1,%2,%3,%4,%5,%6,%7,%8,%9,%10,%11,%12,%13,%14,%15,%16,%17,%18,%19,%20,%21,%22,%23,%24,%25,%26,%27,%28,%29,%30,%31,%32,%33,%34,%35,%36,%37,%38,%39,%40,%41,%42,%43,%44,%45,%46,%47,%48,%49,%50,%51,%52,%53,%54,%55,%56,%57,%58,%59,%60,%61,%62,%63,%64,%65,%66,%67,%68,%69,%70,%71,%72,%73,%74,%75,%76,%77,%78,%79}, da, db, " SD ", 1, 1, %84, %85;\n}"
    if constexpr (ACC == 2)
        asm volatile(WG_ASM("0") : RW80("+f", d) : "r"(loA), "r"(loB), "n"(HIA), "n"(HIB), "n"(TA), "n"(TB));
    else if constexpr (ACC == 1)
        asm volatile(WG_ASM("1") : RW80("+f", d) : "r"(loA), "r"(loB), "n"(HIA), "n"(HIB), "n"(TA), "n"(TB));
    else
        asm volatile(WG_ASM("0") : RW80("=f", d) : "r"(loA), "r"(loB), "n"(HIA), "n"(HIB), "n"(TA), "n"(TB));
#undef WG_ASM
}
template <int TA, int TB, uint32_t HIB, int ACC, uint32_t HIA = HI_SW128>
__device__ __forceinline__ void wgmma(float (&d)[48], uint32_t loA, uint32_t loB) {
#define WG_ASM(SD)                                                          \
    "{\n.reg .b64 da, db;\nmov.b64 da, {%48, %50};\nmov.b64 db, {%49, %51};\n" \
    "wgmma.mma_async.sync.aligned.m64n96k16.f32.bf16.bf16 "               \
    "{%0,%1,%2,%3,%4,%5,%6,%7,%8,%9,%10,%11,%12,%13,%14,%15,%16,%17,%18,%19,%20,%21,%22,%23,%24,%25,%26,%27,%28,%29,%30,%31,%32,%33,%34,%35,%36,%37,%38,%39,%40,%41,%42,%43,%44,%45,%46,%47}, da, db, " SD ", 1, 1, %52, %53;\n}"
    if constexpr (ACC == 1)
        asm volatile(WG_ASM("1") : RW48("+f", d) : "r"(loA), "r"(loB), "n"(HIA), "n"(HIB), "n"(TA), "n"(TB));
    else
        asm volatile(WG_ASM("0") : RW48("=f", d) : "r"(loA), "r"(loB), "n"(HIA), "n"(HIB), "n"(TA), "n"(TB));
#undef WG_ASM
}
template <int TA, int TB, uint32_t HIB, int ACC, uint32_t HIA = HI_SW128>
__device__ __forceinline__ void wgmma(float (&d)[32], uint32_t loA, uint32_t loB) {
#define WG_ASM(SD)                                                          \
    "{\n.reg .b64 da, db;\nmov.b64 da, {%32, %34};\nmov.b64 db, {%33, %35};\n" \
    "wgmma.mma_async.sync.aligned.m64n64k16.f32.bf16.bf16 "               \
    "{%0,%1,%2,%3,%4,%5,%6,%7,%8,%9,%10,%11,%12,%13,%14,%15,%16,%17,%18,%19,%20,%21,%22,%23,%24,%25,%26,%27,%28,%29,%30,%31}, da, db, " SD ", 1, 1, %36, %37;\n}"
    if constexpr (ACC == 1)
        asm volatile(WG_ASM("1") : RW32("+f", d) : "r"(loA), "r"(loB), "n"(HIA), "n"(HIB), "n"(TA), "n"(TB));
    else
        asm volatile(WG_ASM("0") : RW32("=f", d) : "r"(loA), "r"(loB), "n"(HIA), "n"(HIB), "n"(TA), "n"(TB));
#undef WG_ASM
}

__device__ __forceinline__ uint32_t pack_bf16(float lo, float hi) {
    uint32_t r;
    asm("cvt.rn.bf16x2.f32 %0, %1, %2;" : "=r"(r) : "f"(hi), "f"(lo));
    return r;
}
__device__ __forceinline__ float ex2(float x) {
    float r;
    asm("ex2.approx.ftz.f32 %0, %1;" : "=f"(r) : "f"(x));
    return r;
}
__device__ __forceinline__ void stsm4t(uint32_t a, uint32_t r0, uint32_t r1, uint32_t r2, uint32_t r3) {
    asm volatile("stmatrix.sync.aligned.m8n8.x4.trans.shared.b16 [%0], {%1,%2,%3,%4};" ::"r"(a), "r"(r0), "r"(r1), "r"(r2), "r"(r3)
                 : "memory");
}
__device__ __forceinline__ uint32_t lds_u(uint32_t a) {
    uint32_t v;
    asm volatile("ld.shared.u32 %0, [%1];" : "=r"(v) : "r"(a) : "memory");
    return v;
}
__device__ __forceinline__ uint4 lds_u4(uint32_t a) {
    uint4 v;
    asm volatile("ld.shared.v4.u32 {%0,%1,%2,%3}, [%4];" : "=r"(v.x), "=r"(v.y), "=r"(v.z), "=r"(v.w) : "r"(a) : "memory");
    return v;
}
__device__ __forceinline__ float2 lds_f2(uint32_t a) {
    float2 v;
    asm volatile("ld.shared.v2.f32 {%0,%1}, [%2];" : "=f"(v.x), "=f"(v.y) : "r"(a) : "memory");
    return v;
}
__device__ __forceinline__ void sts_f(uint32_t a, float v) { asm volatile("st.shared.f32 [%0], %1;" ::"r"(a), "f"(v) : "memory"); }
__device__ __forceinline__ void sts_u(uint32_t a, uint32_t v) { asm volatile("st.shared.u32 [%0], %1;" ::"r"(a), "r"(v) : "memory"); }
__device__ __forceinline__ void sts_f2(uint32_t a, float x, float y) {
    asm volatile("st.shared.v2.f32 [%0], {%1,%2};" ::"r"(a), "f"(x), "f"(y) : "memory");
}

template <bool SIG = false, int NR>
__device__ __forceinline__ void store_tile_t(const float (&d)[NR], uint32_t addr) {
#pragma unroll
    for (int j = 0; j < NR / 8; j++) {
        stsm4t(addr + j * 2048, pack_bf16(d[8 * j], d[8 * j + 1]), pack_bf16(d[8 * j + 2], d[8 * j + 3]),
               pack_bf16(d[8 * j + 4], d[8 * j + 5]), pack_bf16(d[8 * j + 6], d[8 * j + 7]));
        if (SIG && j == 0) nb_arrive<NB_L, 160>();
    }
}

struct TrueT { static constexpr bool value = true; };
struct FalseT { static constexpr bool value = false; };

template <int V>
struct IntT { static constexpr int value = V; };

__device__ __forceinline__ uint32_t get_item(uint32_t sb, int it, uint32_t dl) {
    mbar_wait(sb + BAR_ITEM + it * 8, 0, dl);
    return lds_u(sb + OFF_ITEM + it * 4);
}
__device__ __forceinline__ uint32_t get_item_warp(uint32_t sb, int it, uint32_t dl) {
    return __shfl_sync(0xffffffffu, get_item(sb, it, dl), 0);
}

struct Ring {
    uint32_t slot, ph, dl;
    __device__ __forceinline__ void adv(uint32_t k) {
        slot += k;
        if (slot >= NSLOT) { slot -= NSLOT; ph ^= 1; }
    }
};

template <int K>
__device__ __forceinline__ void qk_step(float (&s)[80], uint32_t loK, uint32_t loQ) {
    wgmma<0, 0, HI_SW128, K != 0, HI_KV>(s, loK + (K >> 2) * 64 + (K & 3) * 2, loQ + (K >> 2) * (XS >> 4) + (K & 3) * 2);
}
template <int K0, int K1>
__device__ __forceinline__ void qk_steps(float (&s)[80], uint32_t loK, uint32_t loQ) {
    if constexpr (K0 < K1) {
        qk_step<K0>(s, loK, loQ);
        qk_steps<K0 + 1, K1>(s, loK, loQ);
    }
}
__device__ __forceinline__ uint32_t add_bf2(uint32_t a, uint32_t b) {
    uint32_t r;
    asm("add.rn.bf16x2 %0, %1, %2;" : "=r"(r) : "r"(a), "r"(b));
    return r;
}
__device__ __forceinline__ uint32_t fma_bf2(uint32_t a, uint32_t b, uint32_t c) {
    uint32_t r;
    asm("fma.rn.bf16x2 %0, %1, %2, %3;" : "=r"(r) : "r"(a), "r"(b), "r"(c));
    return r;
}
template <int J>
__device__ __forceinline__ void exp_block(const float (&s)[80], uint32_t (&k)[40], uint32_t pa, float mref) {
    if constexpr (J < 10) {
#pragma unroll
        for (int i = 4 * J; i < 4 * J + 4; i++)
            k[i] = pack_bf16(ex2(fmaf(s[2 * i], SM_C, -mref)), ex2(fmaf(s[2 * i + 1], SM_C, -mref)));
#pragma unroll
        for (int i = 0; i < 4; i++)
            asm volatile("stmatrix.sync.aligned.m8n8.x1.trans.shared.b16 [%0], {%1};" ::"r"(((i & 1) ? pa ^ 16 : pa) + J * 2048 + (i >> 1) * 1024),
                         "r"(k[4 * J + i])
                         : "memory");
        exp_block<J + 1>(s, k, pa, mref);
    }
}
__device__ __forceinline__ void sum_block(const uint32_t (&k)[40], float (&l)[10], uint32_t lane) {
    const bool b4 = lane & 16, b3 = lane & 8;
    uint32_t ps[20], t[10];
#pragma unroll
    for (int j = 0; j < 20; j++) ps[j] = add_bf2(k[2 * j], k[2 * j + 1]);
#pragma unroll
    for (int j = 0; j < 10; j++)
        t[j] = add_bf2(b4 ? ps[2 * j + 1] : ps[2 * j], __shfl_xor_sync(0xffffffffu, b4 ? ps[2 * j] : ps[2 * j + 1], 16));
#pragma unroll
    for (int i = 0; i < 5; i++) {
        const uint32_t a = b3 ? t[i + 5] : t[i], b = __shfl_xor_sync(0xffffffffu, b3 ? t[i] : t[i + 5], 8);
        l[2 * i] += __uint_as_float(a << 16) + __uint_as_float(b << 16);
        l[2 * i + 1] += __uint_as_float(a & 0xffff0000u) + __uint_as_float(b & 0xffff0000u);
    }
}
template <bool ADD>
__device__ __forceinline__ void sum_store(const float (&l)[10], uint32_t lane, uint32_t lxa) {
    const bool b2 = lane & 4;
    float t[5];
#pragma unroll
    for (int i = 0; i < 5; i++) t[i] = ADD ? __uint_as_float(lds_u(lxa + i * 64)) : 0.f;
#pragma unroll
    for (int i = 0; i < 5; i++)
        sts_f(lxa + i * 64, t[i] + (b2 ? l[2 * i + 1] : l[2 * i]) + __shfl_xor_sync(0xffffffffu, b2 ? l[2 * i] : l[2 * i + 1], 4));
}

__device__ __forceinline__ void fallback_unit(const Params& P, uint32_t e, uint32_t tid) {
    const uint32_t lane = tid & 31, br = IT_BR(e), b = IT_B(e), h = IT_H0(e);
    const __nv_bfloat162* wq = (const __nv_bfloat162*)(P.pwq[br] + h * 192) + lane;
    const __nv_bfloat162* kp = (const __nv_bfloat162*)(P.pk[br] + (size_t)(b * 32 + h) * 512 * 192) + lane;
    const __nv_bfloat162* vp = (const __nv_bfloat162*)(P.pv[br] + (size_t)(b * 32 + h) * 512 * 192) + lane;
#pragma unroll 1
    for (uint32_t qi = 0; qi < 40; qi++) {
        const uint32_t q = 4 * qi + (tid >> 5);
        const __nv_bfloat16* xr = P.px[br] + (size_t)(b * 160 + q) * 640;
        float a[6] = {0.f, 0.f, 0.f, 0.f, 0.f, 0.f};
#pragma unroll 2
        for (int k = 0; k < 640; k++) {
            const float xv = __bfloat162float(xr[k]);
#pragma unroll
            for (int i = 0; i < 3; i++) {
                const float2 wv = __bfloat1622float2(wq[(size_t)k * 3072 + i * 32]);
                a[2 * i] = fmaf(xv, wv.x, a[2 * i]);
                a[2 * i + 1] = fmaf(xv, wv.y, a[2 * i + 1]);
            }
        }
#pragma unroll
        for (int i = 0; i < 6; i++) a[i] = __bfloat162float(__float2bfloat16(a[i]));
        auto score = [&](int key) {
            float d = 0.f;
#pragma unroll
            for (int i = 0; i < 3; i++) {
                const float2 kv = __bfloat1622float2(kp[key * 96 + i * 32]);
                d = fmaf(a[2 * i], kv.x, fmaf(a[2 * i + 1], kv.y, d));
            }
#pragma unroll
            for (int o = 16; o > 0; o >>= 1) d += __shfl_xor_sync(0xffffffffu, d, o);
            return d;
        };
        float m = -INFINITY, o[6] = {0.f, 0.f, 0.f, 0.f, 0.f, 0.f}, sum = 0.f;
#pragma unroll 1
        for (int n = 0; n < 1024; n++) {
            const int key = n & 511;
            const float d = score(key);
            if (n < 512) {
                m = fmaxf(m, d);
            } else {
                const float p = ex2((d - m) * SM_C);
                sum += p;
#pragma unroll
                for (int i = 0; i < 3; i++) {
                    const float2 vv = __bfloat1622float2(vp[key * 96 + i * 32]);
                    o[2 * i] = fmaf(p, vv.x, o[2 * i]);
                    o[2 * i + 1] = fmaf(p, vv.y, o[2 * i + 1]);
                }
            }
        }
        const float inv = __fdividef(1.f, sum);
        __nv_bfloat16* op = (__nv_bfloat16*)ostash(IT_SLOT(e), b) + (q >> 5) * 256 + 2 * ((q & 31) >> 3) + (q & 1);
#pragma unroll
        for (int i = 0; i < 6; i++) {
            const uint32_t d = (i >> 1) * 64 + 2 * lane + (i & 1);
            op[(d >> 3) * 1280 + (d & 7) * 32 + ((((q & 7) >> 1) ^ ((d & 7) >> 1)) << 3)] = __float2bfloat16(o[i] * inv);
        }
    }
}

struct PendO {
    uint32_t v[64];
    unsigned char* gp;
    static __device__ __forceinline__ uint32_t toff() {
        const uint32_t t = tid_now();
        return ((t >> 5) & 3) * 5120 + ((t >> 2) & 7) * 64 + (((t ^ (t >> 3)) & 3) << 4);
    }
    uint32_t pend, sig, bad;
    static __device__ __forceinline__ void scale(uint32_t& x, uint32_t hi, uint32_t lo) {
        asm("{\n.reg .b32 t;\nmul.rn.bf16x2 t, %0, %2;\nfma.rn.bf16x2 %0, %0, %1, t;\n}" : "+r"(x) : "r"(hi), "r"(lo));
    }
    template <int I, int OFF>
    __device__ __forceinline__ void put() {
        asm volatile("{\n.reg .pred p;\nsetp.ne.u32 p, %6, 0;\n@p st.global.v4.b32 [%0+%5], {%1,%2,%3,%4};\n}" ::"l"(gp), "r"(v[I]),
                     "r"(v[I + 1]), "r"(v[I + 2]), "r"(v[I + 3]), "n"(OFF), "r"(pend)
                     : "memory");
    }
    __device__ __forceinline__ void verdict(uint32_t sb, uint32_t W) {
        if (sig) {
            asm volatile("bar.sync %0, 160;" ::"r"(NB_VOTE + W) : "memory");
            bad = __any_sync(0xffffffffu, lds_u(sb + OFF_FB) != 0);
            pend = !bad;
        }
    }
    template <int W, int G, int H>
    __device__ __forceinline__ void half(uint32_t sb) {
        constexpr bool T2 = W == 0 ? G >= 3 : G < 3;
        constexpr int B = T2 ? 40 + 8 * (W == 0 ? G - 3 : G) : 0;
        const uint4 a = lds_u4(sb + OFF_LINV + G * 128 + H * 16 + (threadIdx.x & 3) * 32);
#pragma unroll
        for (int i = 2 * H; i < 8; i += 4) {
            scale(v[8 * G + i], a.x, a.y);
            scale(v[8 * G + i + 1], a.z, a.w);
            if (T2) {
                scale(v[B + i], a.x, a.y);
                scale(v[B + i + 1], a.z, a.w);
            }
        }
        if (H == 1) {
            put<8 * G, W * XS + G * 512>();
            put<8 * G + 4, W * XS + G * 512 + 2560>();
            if (T2) {
                put<B, 2 * XS + G * 512>();
                put<B + 4, 2 * XS + G * 512 + 2560>();
            }
            if (G == 4 && pend) nb_arrive<NB_ODONE, 288>();
        }
    }
    template <int W, int G>
    __device__ __forceinline__ void step(uint32_t sb) {
        half<W, G, 0>(sb);
        half<W, G, 1>(sb);
    }
    template <int W>
    __device__ __forceinline__ void flush(uint32_t sb) {
        step<W, 0>(sb);
        step<W, 1>(sb);
        step<W, 2>(sb);
        step<W, 3>(sb);
        step<W, 4>(sb);
    }
    __device__ __forceinline__ void clear() {
#pragma unroll
        for (int i = 0; i < 64; i++) v[i] = 0;
        gp = nullptr;
        pend = 0;
        sig = 0;
        bad = 0;
    }
};

__device__ __forceinline__ uint32_t stsm_off() {
    const uint32_t tid = tid_now(), lane = tid & 31;
    return (lane >> 4) * 1024 + (lane & 7) * 128 + (((((tid >> 4) & 6) + ((lane >> 3) & 1)) ^ (lane & 7)) << 4);
}
__device__ __forceinline__ void q_ahead(float (&q0)[80], uint32_t sb, const Ring& rn, uint32_t phm, bool valid) {
    if (valid) mbar_wait2(sb + BAR_RFULL + rn.slot * 8, rn.ph, sb + BAR_XFULL, phm & 1, rn.dl);
    const uint32_t a = ((((sb + OFF_RING) & 0x3ffff) >> 4) | LO_LBO1) + rn.slot * (SLOT >> 4);
    const uint32_t b = (((sb + OFF_R) & 0x3ffff) >> 4) | LO_LBO1;
    wg_fence();
    wgmma<1, 0, HI_SW128, false>(q0, a, b);
#pragma unroll
    for (int k = 1; k < 4; k++) wgmma<1, 0, HI_SW128, true>(q0, a + (k >> 1) * 768 + (k & 1) * 128, b + k * 2);
    wg_commit();
}
template <int W, int KK>
__device__ __forceinline__ void qproj(float (&q0)[80], float (&q1)[80], uint32_t sb, Ring& r, uint32_t pslot, uint32_t phm,
                                      PendO& po) {
    const uint32_t loR = (((sb + OFF_R) & 0x3ffff) >> 4) | LO_LBO1;
    const uint32_t loRing = (((sb + OFF_RING) & 0x3ffff) >> 4) | LO_LBO1;
    auto ready = [&](int k) {
        mbar_wait2(sb + BAR_RFULL + r.slot * 8, r.ph, sb + BAR_XFULL + (k % 5) * 8, ((phm >> (k % 5)) ^ (k / 5)) & 1, r.dl);
    };
    auto release = [&]() {
        if (KK > 0) {
            wg_wait<1>();
            mbar_arrive_warp(sb + BAR_REMPTY + pslot * 8);
            if (KK <= 5) mbar_arrive_warp(sb + (BAR_XEMPTY + (KK - 1) * 8));
        }
    };
    if (KK == 0 && W == 1) ready(0);
    if (W == 1 && KK == QHOLD) nb_sync<NB_SDONE, 256>();
    const uint32_t a = loRing + r.slot * (SLOT >> 4) + (W == 0 ? 0 : 512), b = loR + (KK % 5) * (XS >> 4);
    wg_fence();
    constexpr bool T0 = W == 1 || KK > 0;
    if (T0) wgmma<1, 0, HI_SW128, KK != 0>(q0, a, b);
    if (W == 0) wgmma<1, 0, HI_SW128, KK != 0 ? 1 : 2>(q1, a + 256, b);
#pragma unroll
    for (int k = 1; k < 4; k++) {
        if (T0) wgmma<1, 0, HI_SW128, true>(q0, a + (k >> 1) * 768 + (k & 1) * 128, b + k * 2);
        if (W == 0) wgmma<1, 0, HI_SW128, true>(q1, a + 256 + (k >> 1) * 768 + (k & 1) * 128, b + k * 2);
    }
    wg_commit();
    const uint32_t cslot = r.slot;
    r.adv(1);
    if (W == 0 || KK < QHOLD) release();
    constexpr int QST = W == 0 ? 2 : 1;
    if (KK == QST) {
        po.verdict(sb, W);
        po.template half<W, 0, 0>(sb);
    }
    if (KK < 9) ready(KK + 1);
    if (W == 1 && KK >= QHOLD) release();
    if (W == 1 && KK == 7) nb_arrive<NB_PDONE, 256>();
    if (KK == QST) po.template half<W, 0, 1>(sb);
    if constexpr (KK > QST && KK < QST + 5) po.template step<W, KK - QST>(sb);
    if constexpr (KK < (W == 0 ? 7 : 9)) {
        qproj<W, KK + 1>(q0, q1, sb, r, cslot, phm, po);
    } else if constexpr (W == 1) {
        const uint32_t sta = sb + OFF_R + 2 * XS + stsm_off();
        wg_wait<0>();
        reg_fence(q0);
        store_tile_t<true>(q0, sta);
        mbar_arrive_warp(sb + BAR_REMPTY + cslot * 8);
    } else {
        const uint32_t s8 = r.slot, a8 = loRing + s8 * (SLOT >> 4);
        wg_fence();
#pragma unroll
        for (int k = 0; k < 4; k++) wgmma<1, 0, HI_SW128, true>(q0, a8 + (k >> 1) * 768 + (k & 1) * 128, loR + 3 * (XS >> 4) + k * 2);
        r.adv(1);
        ready(9);
        const uint32_t s9 = r.slot, a9 = loRing + s9 * (SLOT >> 4);
        r.adv(1);
        wg_fence();
#pragma unroll
        for (int k = 0; k < 4; k++) wgmma<1, 0, HI_SW128, true>(q0, a9 + (k >> 1) * 768 + (k & 1) * 128, loR + 4 * (XS >> 4) + k * 2);
        wg_commit();
        wg_wait<1>();
        mbar_arrive_warp(sb + BAR_REMPTY + cslot * 8);
        wg_fence();
#pragma unroll
        for (int k = 0; k < 8; k++)
            wgmma<1, 0, HI_SW128, true>(q1, (k < 4 ? a8 : a9) + 256 + ((k >> 1) & 1) * 768 + (k & 1) * 128,
                                        loR + (3 + (k >> 2)) * (XS >> 4) + (k & 3) * 2);
        wg_commit();
        nb_arrive<NB_SDONE, 256>();
        sts_u(sb + OFF_GM + 4, r.slot);
        nb_sync<NB_PDONE, 256>();
        wg_wait<1>();
        reg_fence(q0);
        const uint32_t sta = sb + OFF_R + stsm_off();
        store_tile_t(q0, sta);
        wg_wait<0>();
        reg_fence(q1);
        mbar_arrive_warp(sb + BAR_REMPTY + s8 * 8);
        mbar_arrive_warp(sb + BAR_REMPTY + s9 * 8);
        store_tile_t(q1, sta + XS);
        mbar_wait(sb + BAR_RFULL + r.slot * 8, r.ph, r.dl);
    }
}

template <int NR>
__device__ __forceinline__ void opack(const float (&o)[NR], uint32_t* v) {
#pragma unroll
    for (int g = 0; g < NR / 16; g++)
#pragma unroll
        for (int hh = 0; hh < 2; hh++)
#pragma unroll
            for (int t = 0; t < 4; t++) v[8 * g + 4 * hh + t] = pack_bf16(o[16 * g + 4 * t + 2 * hh], o[16 * g + 4 * t + 2 * hh + 1]);
}

template <bool IS_S>
__device__ __forceinline__ void op_item(uint32_t e, uint32_t sb, Ring& r, uint32_t& phm) {
    constexpr int T0 = IS_S ? 0 : 2;
    constexpr uint32_t BOFF = IS_S ? (3 * 512) >> 4 : 0;
    const uint32_t loRing = (((sb + OFF_RING) & 0x3ffff) >> 4) | LO_LBO1;
    const uint32_t loO = (((sb + OFF_R) & 0x3ffff) >> 4) | LO_OST;
    float c0[80], c1[80], c2[IS_S ? 32 : 48];
    const int T = 3 * (IT_H1(e) - IT_H0(e));
    uint32_t xs = 0;
    auto step = [&](auto first, auto half) {
        constexpr bool F = decltype(first)::value;
        constexpr uint32_t hf = decltype(half)::value;
        if (hf == 0) {
            mbar_wait(sb + BAR_XFULL + xs * 8, (phm >> xs) & 1, r.dl);
            phm ^= 1u << xs;
        }
        mbar_wait(sb + BAR_RFULL + r.slot * 8, r.ph, r.dl);
        const uint32_t a = loRing + r.slot * (SLOT >> 4), b = loO + xs * (XS >> 4) + hf * 640;
        wg_fence();
        wgmma<1, 1, HI_OST, !F>(c0, a + T0 * 128, b);
        wgmma<1, 1, HI_OST, !F>(c1, a + T0 * 128 + 128, b);
        wgmma<1, 1, HI_OST, !F>(c2, a + 512, b + BOFF);
        wgmma<1, 1, HI_OST, true>(c0, a + 640 + T0 * 128, b + 320);
        wgmma<1, 1, HI_OST, true>(c1, a + 640 + T0 * 128 + 128, b + 320);
        wgmma<1, 1, HI_OST, true>(c2, a + 640 + 512, b + 320 + BOFF);
        wg_commit();
    };
    step(TrueT{}, IntT<0>{});
#pragma unroll 1
    for (int t = 1;; t++) {
        uint32_t pslot = r.slot;
        r.adv(1);
        step(FalseT{}, IntT<1>{});
        wg_wait<1>();
        mbar_arrive_warp(sb + BAR_REMPTY + pslot * 8);
        if (t == T) break;
        pslot = r.slot;
        const uint32_t pxs = xs;
        r.adv(1);
        if (++xs == 5) xs = 0;
        step(FalseT{}, IntT<0>{});
        wg_wait<1>();
        mbar_arrive_warp(sb + BAR_REMPTY + pslot * 8);
        mbar_arrive_warp_if(sb + BAR_XEMPTY + pxs * 8, t + 4 < T);
    }
    wg_wait<0>();
    reg_fence(c0);
    reg_fence(c1);
    reg_fence(c2);
    mbar_arrive_warp(sb + BAR_REMPTY + r.slot * 8);
    r.adv(1);
    nb_sync<NB_OPEND, 256>();
    const uint32_t sta = sb + OFF_R + stsm_off();
    store_tile_t(c0, sta + T0 * XS);
    store_tile_t(c1, sta + (T0 + 1) * XS);
    store_tile_t(c2, sta + 4 * XS + (IS_S ? 96 * 128 : 0));
    fence_async_smem();
    nb_arrive<NB_ODONE, 288>();
}

__device__ __forceinline__ void on_item(uint32_t W, uint32_t e, uint32_t sb, Ring& r, uint32_t& phm) {
    const uint32_t loRing = (((sb + OFF_RING) & 0x3ffff) >> 4) | LO_LBO1;
    const uint32_t loO = (((sb + OFF_R) & 0x3ffff) >> 4) | LO_OST;
    float c[80];
    const int T = 3 * (IT_H1(e) - IT_H0(e));
    uint32_t xs = 0;
    auto step = [&](auto first) {
        constexpr bool F = decltype(first)::value;
        mbar_wait2(sb + BAR_XFULL + xs * 8, (phm >> xs) & 1, sb + BAR_RFULL + r.slot * 8, r.ph, r.dl);
        phm ^= 1u << xs;
        const uint32_t a = loRing + r.slot * (SLOT >> 4) + W * 256, b = loO + xs * (XS >> 4);
        wg_fence();
        wgmma<1, 1, HI_OST, !F>(c, a, b);
#pragma unroll
        for (int k = 1; k < 4; k++) wgmma<1, 1, HI_OST, true>(c, a + (k >> 1) * 512 + (k & 1) * 128, b + k * 320);
        wg_commit();
    };
    step(TrueT{});
#pragma unroll 1
    for (int t = 1; t < T; t++) {
        const uint32_t pslot = r.slot, pxs = xs;
        r.adv(1);
        if (++xs == 5) xs = 0;
        step(FalseT{});
        wg_wait<1>();
        mbar_arrive_warp(sb + BAR_REMPTY + pslot * 8);
        mbar_arrive_warp_if(sb + BAR_XEMPTY + pxs * 8, t + 2 < T);
    }
    xs += 1 + W;
    if (xs >= 5) xs -= 5;
    mbar_wait(sb + BAR_XFULL + xs * 8, (phm >> xs) & 1, r.dl);
    const uint32_t sta = sb + OFF_R + xs * XS + stsm_off();
    uint32_t p[40];
#pragma unroll
    for (int j = 0; j < 10; j++)
        asm volatile("ldmatrix.sync.aligned.m8n8.x4.trans.shared.b16 {%0,%1,%2,%3}, [%4];"
                     : "=r"(p[4 * j]), "=r"(p[4 * j + 1]), "=r"(p[4 * j + 2]), "=r"(p[4 * j + 3])
                     : "r"(sta + j * 2048)
                     : "memory");
    wg_wait<0>();
    reg_fence(c);
#pragma unroll
    for (int k = 0; k < 40; k++) {
        c[2 * k] += __uint_as_float(p[k] << 16);
        c[2 * k + 1] += __uint_as_float(p[k] & 0xffff0000u);
    }
    store_tile_t(c, sta);
    fence_async_smem();
    nb_arrive<NB_ODONE, 288>();
}

template <int W>
__device__ __forceinline__ uint32_t qa_item(uint32_t e, uint32_t sb, Ring& r, uint32_t phm, PendO& po, float (&q0)[80],
                                            float (&oa)[80], int it) {
    const uint32_t loR = (((sb + OFF_R) & 0x3ffff) >> 4) | LO_LBO1;
    const uint32_t loRing = (((sb + OFF_RING) & 0x3ffff) >> 4) | LO_LBO1;
    qproj<W, 0>(q0, oa, sb, r, 0, phm, po);
    fence_async_smem();
    TSD(W, 1);
    float s[80], ob[W == 0 ? 32 : 48], l[10];
    if (W == 1) {
        nb_arrive<NB_Q2, 256>();
        zero(oa);
        zero(ob);
        reg_fence(oa);
        reg_fence(ob);
    }
    const uint32_t lane = tid_now() & 31, sta = sb + OFF_R + stsm_off();
    auto pv = [&](auto first, uint32_t buf) {
        constexpr bool F = decltype(first)::value;
        if (F) mbar_wait(sb + BAR_RFULL + r.slot * 8, r.ph, r.dl);
        const uint32_t a = loRing + r.slot * (SLOT >> 4), b = loR + (3 + buf) * (XS >> 4);
        wg_fence();
        wgmma<1, 0, HI_SW128, F ? 2 : 1, HI_KV>(oa, a + W * 64, b);
        wgmma<1, 0, HI_SW128, !F, HI_KV>(ob, a + 128, b + (W == 0 ? (96 * 128) >> 4 : 0));
#pragma unroll
        for (int k = 1; k < 4; k++) {
            wgmma<1, 0, HI_SW128, true, HI_KV>(oa, a + W * 64 + k * 384, b + k * 2);
            wgmma<1, 0, HI_SW128, true, HI_KV>(ob, a + 128 + k * 384, b + (W == 0 ? (96 * 128) >> 4 : 0) + k * 2);
        }
        wg_commit();
    };
    zero(l);
    float mref;
    uint32_t kslot, vslot, nx = 0;
    auto tail = [&](auto first, int i) {
        constexpr bool rel_other = !decltype(first)::value;
        uint32_t ps[40];
        exp_block<0>(s, ps, sta + (3 + W) * XS, mref);
        if (rel_other) {
            wg_wait<0>();
            mbar_arrive_warp(sb + BAR_REMPTY + vslot * 8);
            if (W == 1) mbar_arrive_warp_if(sb + BAR_XEMPTY + 24, i == 3);
        }
        fence_async_smem();
        nb_arrive<NB_PFULL + W, 256>();
        TSD(W, 6 + 5 * i);
        if (W == 1) {
            mbar_arrive_warp_if<2>(sb + BAR_XEMPTY + 8, i == 3);
            mbar_arrive_warp_if<2>(sb + BAR_XEMPTY + 16, i == 3);
        }
        if (rel_other) {
            mbar_wait(sb + BAR_RFULL + r.slot * 8, r.ph, r.dl);
            sum_block(ps, l, lane);
        }
        if (W == 0 && i == 3) nx = get_item_warp(sb, it + 1, r.dl);
        TSD(W, 7 + 5 * i);
        nb_sync<NB_W + W, 128>();
        pv(first, W);
        if (!rel_other) sum_block(ps, l, lane);
        TSD(W, 8 + 5 * i);
    };
    if (W == 0) {
        nb_sync<NB_QK, 160>();
        TSD(W, 2);
        wg_fence();
        qk_steps<0, 8>(s, loRing + r.slot * (SLOT >> 4), loR);
        nb_sync<NB_Q2, 256>();
        qk_steps<8, 12>(s, loRing + r.slot * (SLOT >> 4), loR);
        wg_commit();
        nb_arrive<NB_Q01, 256>();
        TSD(W, 4);
        nb_sync<NB_REF, 160>();
        mref = __uint_as_float(lds_u(sb + OFF_GM));
        wg_wait<0>();
        reg_fence(s);
        mbar_arrive_warp<2>(sb + BAR_REMPTY + r.slot * 8);
        r.adv(2);
        TSD(W, 5);
        tail(TrueT{}, 0);
    } else {
        nb_sync<NB_Q01, 256>();
    }
#pragma unroll 1
    for (int i = (W == 0 ? 1 : 0); i < 4; i++) {
        const uint32_t pvslot = r.slot;
        r.adv(1);
        kslot = r.slot;
        mbar_wait(sb + BAR_RFULL + r.slot * 8, r.ph, r.dl);
        wg_fence();
        qk_steps<0, 4>(s, loRing + r.slot * (SLOT >> 4), loR);
        if (W == 1) wg_commit();
        qk_steps<4, 12>(s, loRing + r.slot * (SLOT >> 4), loR);
        wg_commit();
        wg_wait<1>();
        if (W == 1) mbar_arrive_warp_if(sb + BAR_XEMPTY + 0, i == 3);
        mbar_arrive_warp_if(sb + BAR_REMPTY + pvslot * 8, W == 0 || i > 0);
        r.adv(1);
        vslot = r.slot;
        TSD(W, 4 + 5 * i);
        mbar_wait(sb + BAR_RFULL + r.slot * 8, r.ph, r.dl);
        nb_sync<NB_PFULL + (W ^ 1), 256>();
        pv(FalseT{}, W ^ 1);
        if (W == 1) mref = __uint_as_float(lds_u(sb + OFF_GM));
        wg_wait<1>();
        reg_fence(s);
        mbar_arrive_warp<2>(sb + BAR_REMPTY + kslot * 8);
        if (W == 0) mbar_arrive_warp_if(sb + BAR_XEMPTY + 0, i == 3);
        r.adv(W == 1 && i == 3 ? 1 : 2);
        TSD(W, 5 + 5 * i);
        tail(FalseT{}, i);
    }
    if (W == 1) nx = get_item_warp(sb, it + 1, r.dl);
    if (W == 0) {
        Ring rn = r;
        rn.adv(2);
        q_ahead(q0, sb, rn, phm, IT_TYPE(nx) == IT_QA);
        TSD(W, 25);
    }
    const uint32_t w = (tid_now() >> 5) & 3;
    const uint32_t lxa = sb + OFF_LX + w * 640 + (((lane & 8) ? 80 : 0) + ((lane >> 1) & 8) + 2 * (lane & 3) + ((lane >> 2) & 1)) * 4;
    po.gp = ostash(IT_SLOT(e), IT_B(e)) + po.toff();
    po.sig = 1;
    if (W == 0) {
        sum_store<false>(l, lane, lxa);
        nb_arrive<NB_LX, 256>();
        wg_wait<1>();
        mbar_arrive_warp(sb + BAR_REMPTY + r.slot * 8);
        mbar_arrive_warp(sb + BAR_XEMPTY + 24);
        r.adv(1);
        mbar_wait(sb + BAR_RFULL + r.slot * 8, r.ph, r.dl);
        nb_sync<NB_PFULL + 1, 256>();
        pv(FalseT{}, 1);
    } else {
        nb_sync<NB_LX, 256>();
        sum_store<true>(l, lane, lxa);
        nb_arrive<NB_L, 160>();
    }
    TSD(W, 24);
    wg_wait<0>();
    reg_fence(oa);
    reg_fence(ob);
    mbar_arrive_warp(sb + BAR_REMPTY + r.slot * 8);
    mbar_arrive_warp(sb + BAR_XEMPTY + 32);
    r.adv(1);
    opack(ob, po.v + 40);
    opack(oa, po.v);
    return nx;
}

template <int W>
__device__ __forceinline__ uint32_t qa_run(uint32_t e, uint32_t sb, Ring& r, uint32_t phm, PendO& po, int& it) {
    float q0[80], oa[80];
    if (W == 0) {
        zero(oa);
        q_ahead(q0, sb, r, phm, true);
        wg_wait<0>();
    }
#pragma unroll 1
    do {
        TS(W, 0);
        if (W == 0) TS_ITEM(e);
        e = qa_item<W>(e, sb, r, phm, po, q0, oa, it);
        TS(W, 31);
        it++;
    } while (IT_TYPE(e) == IT_QA && !po.bad);
    if (W == 0) {
#pragma unroll
        for (int i = 56; i < 64; i++) po.v[i] = 0;
    }
    return e;
}

__device__ __forceinline__ void consumer(const Params& P, uint32_t W, uint32_t sb, uint32_t dl) {
    int it = 0;
    Ring r{0, 0, dl};
    uint32_t phm = 0;
    uint32_t e = get_item_warp(sb, 0, dl);
#pragma unroll 1
    while (true) {
        if (IT_TYPE(e) == IT_QA) {
            PendO po;
            po.clear();
            e = W == 0 ? qa_run<0>(e, sb, r, phm, po, it) : qa_run<1>(e, sb, r, phm, po, it);
#pragma unroll 1
            for (int m = po.bad ? 2 : 1; m > 0; m--) {
                if (m == 1) {
                    po.verdict(sb, W);
                    if (W == 0) po.flush<0>(sb);
                    else po.flush<1>(sb);
                }
                if (po.bad) {
                    if (W == 0) fallback_unit(P, lds_u(sb + OFF_ITEM + (it - m) * 4), tid_now() & 127);
                    __syncwarp();
                    nb_sync<NB_ODONE, 288>();
                }
            }
        }
        if (e == 0) break;
        if (IT_TYPE(e) == IT_QA) continue;
        TS(W, 0);
        if (W == 0) TS_ITEM(e);
        if (IT_TYPE(e) == IT_ON) on_item(W, e, sb, r, phm);
        else if (W == 0) op_item<true>(e, sb, r, phm);
        else op_item<false>(e, sb, r, phm);
        TS(W, 31);
        e = get_item_warp(sb, ++it, dl);
    }
    TS_DUMP(W);
}

__global__ void __cluster_dims__(2, 1, 1) __launch_bounds__(384, 1) fused_kernel(const __grid_constant__ Params P) {
    extern __shared__ __align__(1024) unsigned char smem_raw[];
    const uint32_t sb = (uint32_t)__cvta_generic_to_shared(smem_raw);
    const uint32_t warp = __shfl_sync(0xffffffffu, threadIdx.x >> 5, 0), wgid = warp >> 2;
    const uint32_t cta = blockIdx.x;
    const uint32_t dl = deadline();

    if (threadIdx.x == 128) {
#pragma unroll
        for (int i = 0; i < NSLOT; i++) {
            mbar_init(sb + BAR_RFULL + i * 8, 1);
            mbar_init(sb + BAR_REMPTY + i * 8, 8);
            mbar_init(sb + BAR_XFULL + i * 8, 1);
            mbar_init(sb + BAR_XEMPTY + i * 8, 8);
        }
        asm volatile("fence.mbarrier_init.release.cluster;" ::: "memory");
        fence_async_smem();
    } else if (threadIdx.x == 160) {
#pragma unroll
        for (int i = 0; i < NSLOT + MAXI; i++) mbar_init(sb + BAR_PRDY + i * 8, 1);
        asm volatile("fence.mbarrier_init.release.cluster;" ::: "memory");
    } else if (threadIdx.x == 0) {
        sts_u(sb + OFF_ITEM, P.cl[cta >> 1].items[0] ? P.cl[cta >> 1].items[0] + 8 * (cta & 1) : 0);
        sts_u(sb + OFF_FB, P.cl[cta >> 1].delay);
    } else if (threadIdx.x == 64) {
        if (sb & 1023) __trap();
        asm volatile("prefetch.tensormap [%0];" ::"l"(&P.wq[0]) : "memory");
        asm volatile("prefetch.tensormap [%0];" ::"l"(&P.x[0]) : "memory");
    }
    __syncthreads();
    {
        const int it = 0;
        if (wgid == 1) TS(0, 30);
    }
    asm volatile("barrier.cluster.arrive.relaxed.aligned;" ::: "memory");
    if (warp < 3) {
        const uint32_t e = __shfl_sync(0xffffffffu, lds_u(sb + OFF_ITEM), 0), d = lds_u(sb + OFF_FB);
        const uint64_t pol = pol_shared();
        const bool isx = warp == 1, lead = (threadIdx.x & 31) == 0;
        uint32_t t0, t1;
        asm volatile("mov.u32 %0, %%clock;" : "=r"(t0));
        do {
            asm volatile("mov.u32 %0, %%clock;" : "=r"(t1));
        } while (t1 - t0 < d);
        __syncwarp();
#pragma unroll 1
        for (int n = 0; n < (e ? NSLOT : 0); n++) {
            const uint32_t bar = sb + (isx ? BAR_XFULL : BAR_RFULL) + n * 8;
            if (lead) {
                if (warp < 2) mbar_expect(bar, isx ? XS : SLOT);
                tma3(sb + (isx ? OFF_R + n * XS : OFF_RING + n * SLOT + warp * (SLOT / 4)), isx ? &P.x[0] : &P.wq[0],
                     isx ? IT_B(e) * 160 : n * 64 + warp * 16, isx ? n : IT_H0(e) * 3, bar, pol);
            }
        }
        if (threadIdx.x == 0) asm volatile("mbarrier.arrive.shared::cta.b64 _, [%0];" ::"r"(sb + BAR_ITEM) : "memory");
        __syncwarp();
    }

    if (wgid == 0) {
        asm volatile("setmaxnreg.dec.sync.aligned.u32 24;");
        if (warp == 0) {
            const bool lead = threadIdx.x == 0;
            const uint64_t pol_first = pol_stream(), pol_norm = pol_shared();
            uint32_t e = __shfl_sync(0xffffffffu, lds_u(sb + OFF_ITEM), 0);
            asm volatile("barrier.cluster.wait.aligned;" ::: "memory");
            unsigned int* const ticket = &g_ticket[next_epoch(0) & 1];
            const uint32_t rank = cta & 1;
            uint32_t peer;
            asm volatile("mapa.shared::cluster.u32 %0, %1, %2;" : "=r"(peer) : "r"(sb), "r"(rank ^ 1));
            Ring r{0, 0, dl};
            uint32_t pm = 0;
            auto load_w = [&](const CUtensorMap* m, int row, int blk, uint32_t half_bytes) {
                mbar_wait(sb + BAR_REMPTY + r.slot * 8, r.ph, dl);
                if (lead) {
                    mbar_expect(sb + BAR_RFULL + r.slot * 8, 2 * half_bytes);
                    asm volatile("mbarrier.arrive.shared::cluster.b64 _, [%0];" ::"r"(peer + BAR_PRDY + r.slot * 8) : "memory");
                }
                mbar_wait(sb + BAR_PRDY + r.slot * 8, (pm >> r.slot) & 1, dl);
                pm ^= 1u << r.slot;
                if (lead) tma3_mc(sb + OFF_RING + r.slot * SLOT + rank * half_bytes, m, row, blk, sb + BAR_RFULL + r.slot * 8, pol_norm);
                r.adv(1);
            };
#pragma unroll 1
            for (int it = 0; e != 0; it++) {
                uint32_t nx = 0, tk = 0;
                if (rank == 0 && IT_TYPE(e) != IT_ON && it + 2 < MAXI) nx = it + 1 < NSTAT ? P.cl[cta >> 1].items[it + 1] : IT_DYN;
                const uint32_t br = IT_BR(e);
                if (IT_TYPE(e) == IT_QA) {
                    const uint32_t h = IT_H0(e);
#pragma unroll 1
                    for (int kk = it ? 0 : NSLOT; kk < 10; kk++) load_w(&P.wq[br], kk * 64 + rank * 32, h * 3, SLOT / 2);
                    const int grp0 = (IT_B(e) * 32 + h) * 64;
#pragma unroll 1
                    for (int n = 0; n < 16; n++) {
                        if (n == 13 && nx == IT_DYN && lead) tk = atomicAdd(ticket, 1);
                        const bool isv = n == 15 || (n > 0 && !(n & 1));
                        const int j = n == 15 ? 7 : isv ? (n - 2) >> 1 : (n + 1) >> 1;
                        mbar_wait(sb + BAR_REMPTY + r.slot * 8, r.ph, dl);
                        if (lead) {
                            mbar_expect(sb + BAR_RFULL + r.slot * 8, SLOT);
                            asm volatile(
                                "cp.async.bulk.tensor.4d.shared::cluster.global.mbarrier::complete_tx::bytes.L2::cache_hint"
                                " [%0], [%1, {%3,%3,%3,%4}], [%2], %5;" ::"r"(sb + OFF_RING + r.slot * SLOT),
                                "l"(isv ? &P.v[br] : &P.k[br]), "r"(sb + BAR_RFULL + r.slot * 8), "r"(0), "r"(grp0 + j * 8), "l"(pol_first)
                                : "memory");
                        }
                        r.adv(1);
                    }
                } else {
                    const bool wide = IT_TYPE(e) == IT_OP;
                    const int step = wide ? 32 : 64, r1 = IT_H1(e) * 192;
#pragma unroll 1
                    for (int row = IT_H0(e) * 192 + rank * (step >> 1); row < r1; row += step)
                        load_w(wide ? &P.wo[br] : &P.won[br], row, IT_HALF(e) * (wide ? 5 : 2), wide ? XS / 2 : 8192);
                    if (nx == IT_DYN && lead) tk = atomicAdd(ticket, 1);
                }
                if (rank == 0) {
                    if (nx == IT_DYN) {
                        tk = __shfl_sync(0xffffffffu, tk, 0);
                        nx = tk < P.nlist ? P.list[tk] : 0;
                    }
                    e = nx;
                    if (lead) {
                        asm volatile("st.async.weak.shared::cluster.mbarrier::complete_tx::bytes.b32 [%0], %1, [%2];" ::"r"(
                                         peer + OFF_ITEM + 4 + it * 4),
                                     "r"(e ? e + 8 : 0), "r"(peer + BAR_ITEM + 8 + it * 8)
                                     : "memory");
                        sts_u(sb + OFF_ITEM + 4 + it * 4, e);
                        asm volatile("mbarrier.arrive.shared::cta.b64 _, [%0];" ::"r"(sb + BAR_ITEM + 8 + it * 8) : "memory");
                    }
                } else {
                    if (lead) mbar_expect(sb + BAR_ITEM + 8 + it * 8, 4);
                    e = get_item_warp(sb, it + 1, dl);
                }
            }
        } else if (warp == 1) {
            const uint64_t pol_norm = pol_shared(), pol_o = pol_stream();
            const bool lead = threadIdx.x == 32;
            uint32_t phm = 0, epoch = 0;
#pragma unroll 1
            for (int it = 0;; it++) {
                const uint32_t e = get_item_warp(sb, it, dl);
                if (it == 1 || (it == 0 && e == 0)) epoch = next_epoch(1);
                if (e == 0) break;
                const uint32_t br = IT_BR(e);
                uint32_t xs = 0;
                auto acquire = [&]() {
                    mbar_wait(sb + BAR_XEMPTY + xs * 8, (phm >> xs) & 1, dl);
                    phm ^= 1u << xs;
                    if (lead) mbar_expect(sb + BAR_XFULL + xs * 8, XS);
                };
                if (IT_TYPE(e) == IT_QA) {
#pragma unroll 1
                    for (int kk = it ? 0 : 5; kk < 10; kk++) {
                        acquire();
                        if (lead) tma3(sb + OFF_R + xs * XS, &P.x[br], IT_B(e) * 160, kk, sb + BAR_XFULL + xs * 8, pol_norm);
                        if (++xs == 5) xs = 0;
                    }
                } else {
                    const unsigned int* fp = g_flag + (br * 16 + IT_B(e)) * 64 + (threadIdx.x & 31) * 2;
                    uint32_t hm = 0, pm = 0;
                    auto poll = [&](uint32_t hneed, uint32_t pneed) {
                        if ((hm & hneed) == hneed && (pm & pneed) == pneed) return;
                        uint32_t n = 0;
                        do {
                            uint32_t a, b;
                            asm volatile("ld.acquire.gpu.global.v2.u32 {%0, %1}, [%2];" : "=r"(a), "=r"(b) : "l"(fp) : "memory");
                            hm = __ballot_sync(0xffffffffu, a == epoch);
                            pm = __ballot_sync(0xffffffffu, b == epoch);
                            if (++n > 0x1000000) __trap();
                        } while ((hm & hneed) != hneed || (pm & pneed) != pneed);
                        __syncwarp();
                        asm volatile("fence.proxy.async.global;" ::: "memory");
                    };
#pragma unroll 1
                    for (uint32_t h = IT_H0(e); h < IT_H1(e); h++) {
                        const unsigned char* src = ostash(P.slot[br * 32 + h], IT_B(e));
                        poll(1u << h, 0);
#pragma unroll 1
                        for (int t = 0; t < 3; t++) {
                            acquire();
                            if (lead) bulk_load(sb + OFF_R + xs * XS, src + t * XS, XS, sb + BAR_XFULL + xs * 8, pol_o);
                            if (++xs == 5) xs = 0;
                        }
                        if (IT_TYPE(e) == IT_OP && h >= 1) {
                            const uint32_t x1 = xs == 4 ? 0 : xs + 1;
                            mbar_wait(sb + BAR_XFULL + xs * 8, (phm >> xs) & 1, dl);
                            mbar_wait(sb + BAR_XFULL + x1 * 8, (phm >> x1) & 1, dl);
                            if (lead)
                                asm volatile("red.relaxed.gpu.global.max.u32 [%0], %1;" ::"l"(fp + 5 + 2 * IT_HALF(e)), "r"(epoch * 64 + h) : "memory");
                        }
                    }
                    if (IT_TYPE(e) == IT_ON) {
                        poll(0, IT_HALF(e) < 2 ? 1 : IT_HALF(e) == 2 ? 3 : 2);
#pragma unroll 1
                        for (uint32_t tile = 2 * IT_HALF(e); tile < 2 * IT_HALF(e) + 2; tile++) {
                            acquire();
                            if (lead)
                                asm volatile(
                                    "cp.async.bulk.tensor.5d.shared::cluster.global.mbarrier::complete_tx::bytes [%0], [%1, {%3,%5,%5,%5,%4}], [%2];" ::"r"(
                                        sb + OFF_R + xs * XS),
                                    "l"(&P.out), "r"(sb + BAR_XFULL + xs * 8), "r"(br * 640 + tile * 64), "r"(IT_B(e) * 5), "r"(0)
                                    : "memory");
                            if (++xs == 5) xs = 0;
                        }
                    }
                }
            }
        } else if (warp == 2) {
            asm volatile("barrier.cluster.wait.aligned;" ::: "memory");
            const uint32_t epoch = next_epoch(2);
            if (cta == 0) g_ticket[(epoch + 1) & 1] = 0;
#pragma unroll 1
            for (int it = 0;; it++) {
                const uint32_t e = get_item_warp(sb, it, dl);
                if (e == 0) break;
                if (IT_TYPE(e) != IT_QA && threadIdx.x == 64) asm volatile("prefetch.tensormap [%0];" ::"l"(&P.out) : "memory");
                nb_sync<NB_ODONE, 288>();
                if (threadIdx.x == 64) {
                    const uint32_t bb = IT_BR(e) * 16 + IT_B(e);
                    if (IT_TYPE(e) != IT_QA) {
                        const bool wide = IT_TYPE(e) == IT_OP;
                        if (wide)
                            asm volatile("red.relaxed.gpu.global.max.u32 [%0], %1;" ::"l"(&g_flag[bb * 64 + 5 + 2 * IT_HALF(e)]),
                                         "r"(epoch * 64 + IT_H1(e))
                                         : "memory");
                        const int cc0 = IT_BR(e) * 640 + IT_HALF(e) * (wide ? 320 : 128);
                        uint32_t xs = wide ? 0 : (3 * (IT_H1(e) - IT_H0(e))) % 5;
#pragma unroll 1
                        for (int m = 0; m < (wide ? 5 : 2); m++) {
                            asm volatile("cp.async.bulk.tensor.5d.global.shared::cta.bulk_group [%0, {%2,%4,%4,%4,%3}], [%1];" ::"l"(&P.out),
                                         "r"(sb + OFF_R + xs * XS), "r"(cc0 + m * 64), "r"((int)IT_B(e) * 5), "r"(0)
                                         : "memory");
                            asm volatile("cp.async.bulk.commit_group;" ::: "memory");
                            if (wide && m >= 1) {
                                asm volatile("cp.async.bulk.wait_group.read 1;" ::: "memory");
                                asm volatile("mbarrier.arrive.shared::cta.b64 _, [%0], 8;" ::"r"(sb + BAR_XEMPTY + (m - 1) * 8) : "memory");
                            }
                            if (++xs == 5) xs = 0;
                        }
                        if (wide) {
                            asm volatile("cp.async.bulk.wait_group.read 0;" ::: "memory");
                            asm volatile("mbarrier.arrive.shared::cta.b64 _, [%0], 8;" ::"r"(sb + BAR_XEMPTY + 32) : "memory");
                        }
                        if (IT_PART(e)) {
                            asm volatile("cp.async.bulk.wait_group 0;" ::: "memory");
                            asm volatile("fence.proxy.async.global;" ::: "memory");
                        }
                    }
                    if (IT_TYPE(e) == IT_QA || IT_PART(e)) {
                        unsigned int* f = &g_flag[bb * 64 + (IT_TYPE(e) == IT_QA ? 2 * IT_H0(e) : 1 + 2 * IT_HALF(e))];
                        asm volatile("st.release.gpu.global.u32 [%0], %1;" ::"l"(f), "r"(epoch) : "memory");
                    }
                }
                __syncwarp();
            }
            if (threadIdx.x == 64) asm volatile("cp.async.bulk.wait_group 0;" ::: "memory");
            __syncwarp();
            asm volatile("barrier.cluster.arrive.relaxed.aligned;\nbarrier.cluster.wait.aligned;" ::: "memory");
        } else {
            const uint32_t lane = threadIdx.x & 31, p = lane >> 3;
            const uint32_t epoch = next_epoch(3);
#pragma unroll 1
            for (int it = 0;; it++) {
                const uint32_t e = get_item_warp(sb, it, dl);
                if (e == 0) break;
                if (IT_TYPE(e) != IT_QA) continue;
                nb_sync<NB_QK, 160>();
                const uint32_t ka = sb + OFF_RING + lds_u(sb + OFF_GM + 4) * SLOT + p * (2 * 3072 + 256) + (lane & 7) * 16;
                const uint32_t qa = sb + OFF_R + p * 256 + (lane & 7) * 16;
                uint32_t acc = 0;
#pragma unroll 1
                for (int c = 0; c < 3; c++) {
                    const uint4 k = lds_u4(ka + c * 1024);
                    if (c == 2) nb_sync<NB_L, 160>();
                    const uint4 q = lds_u4(qa + c * XS);
                    acc = fma_bf2(k.x, q.x, fma_bf2(k.y, q.y, fma_bf2(k.z, q.z, fma_bf2(k.w, q.w, acc))));
                }
                const float d = __uint_as_float(acc << 16) + __uint_as_float(acc & 0xffff0000u);
                const int sum = __reduce_add_sync(0xffffffffu, __float2int_rn(d * 16.f));
                sts_f(sb + OFF_GM, fmaf((float)sum, SM_C / 64.f, 24.f));
                nb_arrive<NB_REF, 160>();
                if (IT_DEP(e)) {
                    const uint32_t g = IT_DEP(e) - 1, need = epoch * 64 + (g & 31) + 1;
                    const unsigned int* cp = &g_flag[((g >> 5) * 16 + IT_B(e)) * 64 + 5 + 2 * (lane & 1)];
                    for (uint32_t n = 0;; n++) {
                        uint32_t v;
                        asm volatile("ld.acquire.gpu.global.u32 %0, [%1];" : "=r"(v) : "l"(cp) : "memory");
                        if (__all_sync(0xffffffffu, v - need < 64)) break;
                        if (n > 0x800000) __trap();
                        __nanosleep(500);
                    }
                }
                nb_sync<NB_L, 160>();
                bool bad = false;
#pragma unroll
                for (int c = 0; c < 5; c++) {
                    const uint32_t la = sb + OFF_LX + (c * 32 + lane) * 4;
                    const float v = (__uint_as_float(lds_u(la)) + __uint_as_float(lds_u(la + 640))) +
                                    (__uint_as_float(lds_u(la + 1280)) + __uint_as_float(lds_u(la + 1920)));
                    const float inv = __fdividef(1.f, v);
                    const uint32_t hi = pack_bf16(inv, 0.f), lo = pack_bf16(inv - __uint_as_float(hi << 16), 0.f);
                    const uint32_t ia = sb + OFF_LINV + c * 128 + ((lane >> 1) & 3) * 32 + (lane >> 3) * 8 + (lane & 1) * 2;
                    asm volatile("st.shared.u16 [%0], %1;\nst.shared.u16 [%0+4], %2;" ::"r"(ia), "h"((unsigned short)hi), "h"((unsigned short)lo) : "memory");
                    bad |= !(v >= 5.421010862e-20f && v <= 7.9228163e28f);
                }
                sts_u(sb + OFF_FB, __any_sync(0xffffffffu, bad));
                nb_arrive<NB_VOTE, 160>();
                nb_arrive<NB_VOTE + 1, 160>();
            }
        }
    } else {
        asm volatile("setmaxnreg.inc.sync.aligned.u32 240;");
        consumer(P, wgid - 1, sb, dl);
    }
}

typedef CUresult (*EncFn)(CUtensorMap*, CUtensorMapDataType, cuuint32_t, void*, const cuuint64_t*, const cuuint64_t*,
                          const cuuint32_t*, const cuuint32_t*, CUtensorMapInterleave, CUtensorMapSwizzle,
                          CUtensorMapL2promotion, CUtensorMapFloatOOBfill);

void make_map3(EncFn enc, CUtensorMap* m, void* p, uint64_t rows, uint64_t rowbytes, uint64_t nblk, uint32_t boxrows,
               uint32_t boxblk) {
    cuuint64_t dims[3] = {64, rows, nblk};
    cuuint64_t str[2] = {rowbytes, 128};
    cuuint32_t box[3] = {64, boxrows, boxblk};
    cuuint32_t es[3] = {1, 1, 1};
    enc(m, CU_TENSOR_MAP_DATA_TYPE_BFLOAT16, 3, p, dims, str, box, es, CU_TENSOR_MAP_INTERLEAVE_NONE,
        CU_TENSOR_MAP_SWIZZLE_128B, CU_TENSOR_MAP_L2_PROMOTION_NONE, CU_TENSOR_MAP_FLOAT_OOB_FILL_NONE);
}

constexpr int tune(const char*, int def) { return def; }

void build_schedule(Params& P, int ncl) {
    const int mode = tune("MODE", 4), dmax = tune("DMAX", 24200), n0 = tune("N0", 10);
    const int H0[8] = {19, 20, 21, 22, 22, 24, 25, 25}, P0[8] = {367, 337, 335, 331, 338, 335, 333, 332};
    const int ra = tune("RA", 10), ga = tune("GA", 17), rb = tune("RB", 11), g1 = tune("G1", 58);
    int dep[64];
    for (int g = 0, ns = 0, live = 0; g < 64; g++) {
        const bool fresh = mode < 3 || g >= g1 || live < (g < ga ? ra : rb);
        dep[g] = fresh ? 0 : g - live + 1;
        P.slot[g] = fresh ? ns++ : P.slot[g - live];
        live += fresh;
    }
    int H[8], pos[8], psum = 0;
    for (int b = 0; b < 8; b++) {
        const char nh[3] = {'H', (char)('0' + b), 0}, np[3] = {'P', (char)('0' + b), 0};
        H[b] = tune(nh, H0[b]);
        pos[b] = tune(np, P0[b]);
        psum += pos[b];
    }
    const int sk = tune("SK", 10), g0 = tune("G0", 20), g2 = tune("G2", 40);
    int ord[512], nxt[8] = {0, 0, 0, 0, 0, 0, 0, 0};
    for (int k = 0; k < 512; k++) {
        int best = -1;
        float bkey = 0.f;
        for (int b = 0; b < 8; b++) {
            const int g = nxt[b];
            if (g == 64) continue;
            const float w = g < g0 ? 0.f : g < 32 ? (g - g0) / (32.f - g0) : g < g2 ? 1.f : (64 - g) / (64.f - g2);
            const float key = g + w * sk * 0.1f * (pos[b] - psum / 8.f) / 8.f;
            if (best < 0 || key < bkey) best = b, bkey = key;
        }
        ord[k] = nxt[best]++ * 8 + best;
        const int d = dep[ord[k] >> 3];
        if (d > 32) {
            if (pos[best] > k) pos[best] = k;
            if (H[best] < d - 32) H[best] = d - 32;
        }
    }
    int u = 0;
    auto unit = [&]() {
        const int v = ord[u++];
        return mk_item(IT_QA, v >> 8, (v & 7) * 2, (v >> 3) & 31, P.slot[v >> 3], 0) | (dep[v >> 3] << 23);
    };
    int qa[NCL], nq = 0, op[NCL], no = 0;
    for (int c = 0; c < ncl; c++) {
        P.cl[c].delay = 0;
        for (int i = 0; i < NSTAT; i++) P.cl[c].items[i] = 0;
        if (mode >= 3 && c >= 4 && c < 20) op[((c - 4) & 7) * 2 + ((c - 4) >> 3)] = c, no++;
        else if (mode != 2 || (c & 3) == 0) qa[nq++] = c;
    }
    for (int t = 0; t < no; t++) {
        P.cl[op[t]].items[1] = mk_item(IT_OP, 0, t & ~1, 0, 32, t & 1);
        P.cl[op[t]].items[2] = IT_DYN;
            }
    for (int k = 0; k < nq; k++) {
        const int c = qa[(k * (nq % 19 ? 19 : 17)) % nq];
        P.cl[c].items[1] = P.cl[c].items[2] = IT_DYN;
        P.cl[c].delay = k < n0 ? 0 : dmax * (k + 1 - n0) / (nq - n0);
    }
    for (int t = 0; t < no && tune("OF", 1); t++) P.cl[op[(t & 7) * 2 + (t >> 3)]].items[0] = unit();
    for (int k = u; k < no + nq; k++) {
        int best = -1;
        for (int c = 0; c < ncl; c++)
            if (P.cl[c].items[1] && !P.cl[c].items[0] && (best < 0 || P.cl[c].delay < P.cl[best].delay)) best = c;
        P.cl[best].items[0] = unit();
    }
    int n = 0;
    const int uend = mode == 2 ? 8 * nq : 512;
    while (u < uend) {
        for (int b = 0; b < 8 && no; b++)
            if (pos[b] == u) {
                P.list[n++] = mk_item(IT_OP, 1, 2 * b, 0, H[b], 0, 1);
                P.list[n++] = mk_item(IT_OP, 1, 2 * b, 0, H[b], 1, 1);
            }
        P.list[n++] = unit();
    }
    for (int k = 0; no && k < 40; k++) P.list[n++] = mk_item(IT_ON, 1, k / 5 * 2, H[k / 5], 32, k % 5);
    P.nlist = n;
}

}

extern "C" void kernel_launch(void* const* d_in, const int* in_sizes, int n_in, void* d_out, int out_size) {
    static Params P;
    static bool init = false;
    static int ncl = NCL;
    if (!init) {
        EncFn enc = nullptr;
        cudaDriverEntryPointQueryResult qr;
        cudaGetDriverEntryPoint("cuTensorMapEncodeTiled", (void**)&enc, cudaEnableDefault, &qr);
        for (int i = 0; i < 2; i++) {
            P.px[i] = (const __nv_bfloat16*)d_in[5 * i + 0];
            P.pk[i] = (const __nv_bfloat16*)d_in[5 * i + 1];
            P.pv[i] = (const __nv_bfloat16*)d_in[5 * i + 2];
            P.pwq[i] = (const __nv_bfloat16*)d_in[5 * i + 3];
            make_map3(enc, &P.x[i], d_in[5 * i + 0], 2560, 1280, 10, 160, 1);
            for (int j = 0; j < 2; j++) {
                cuuint64_t dims[4] = {64, 8, 3, 16 * 32 * 64};
                cuuint64_t str[3] = {384, 128, 3072};
                cuuint32_t box[4] = {64, 8, 3, 8};
                cuuint32_t es[4] = {1, 1, 1, 1};
                enc(j ? &P.v[i] : &P.k[i], CU_TENSOR_MAP_DATA_TYPE_BFLOAT16, 4, d_in[5 * i + 1 + j], dims, str, box, es,
                    CU_TENSOR_MAP_INTERLEAVE_NONE, CU_TENSOR_MAP_SWIZZLE_128B, CU_TENSOR_MAP_L2_PROMOTION_NONE,
                    CU_TENSOR_MAP_FLOAT_OOB_FILL_NONE);
            }
            make_map3(enc, &P.wq[i], d_in[5 * i + 3], 640, 12288, 96, 32, 3);
            make_map3(enc, &P.wo[i], d_in[5 * i + 4], 6144, 1280, 10, 16, 5);
            make_map3(enc, &P.won[i], d_in[5 * i + 4], 6144, 1280, 10, 32, 2);
        }
        cuuint64_t dims[5] = {1280, 2, 4, 4, 80};
        cuuint64_t str[4] = {2560, 8 * 2560, 2 * 2560, 32 * 2560};
        cuuint32_t box[5] = {64, 2, 4, 4, 5};
        cuuint32_t es[5] = {1, 1, 1, 1, 1};
        enc(&P.out, CU_TENSOR_MAP_DATA_TYPE_BFLOAT16, 5, d_out, dims, str, box, es, CU_TENSOR_MAP_INTERLEAVE_NONE,
            CU_TENSOR_MAP_SWIZZLE_128B, CU_TENSOR_MAP_L2_PROMOTION_NONE, CU_TENSOR_MAP_FLOAT_OOB_FILL_NONE);
        cudaFuncSetAttribute(fused_kernel, cudaFuncAttributeMaxDynamicSharedMemorySize, SMEM_LAUNCH);
        cudaLaunchConfig_t cfg = {};
        cfg.gridDim = dim3(NCTA);
        cfg.blockDim = dim3(384);
        cfg.dynamicSmemBytes = SMEM_LAUNCH;
        int nc = 0;
        if (cudaOccupancyMaxActiveClusters(&nc, fused_kernel, &cfg) == cudaSuccess && nc >= 52 && nc < NCL) ncl = nc;
        (void)cudaGetLastError();
        ncl = tune("NCL", ncl);
        build_schedule(P, ncl);
        init = true;
    }
    fused_kernel<<<2 * ncl, 384, SMEM_LAUNCH>>>(P);
}
```

```cpp
#include <cuda_runtime.h>
#include <cuda.h>
#include <cuda_bf16.h>
#include <stdint.h>

namespace {

constexpr int NCTA = 132;
constexpr int NCL = NCTA / 2;
constexpr int MAXI = 16;
constexpr int NSTAT = 3;
constexpr uint32_t IT_DYN = 0xffffffffu;
constexpr int SLOT = 24576;
constexpr int NSLOT = 5;
constexpr int XS = 20480;
constexpr int OFF_R = 0;
constexpr int OFF_RING = 5 * XS;
constexpr int OFF_MISC = OFF_RING + NSLOT * SLOT;
constexpr int OFF_LX = OFF_MISC;
constexpr int OFF_LINV = OFF_LX + 2560;
constexpr int OFF_FB = OFF_LINV + 640;
constexpr int OFF_GM = OFF_FB + 16;
constexpr int OFF_BAR = OFF_GM + 16;
constexpr int BAR_RFULL = OFF_BAR;
constexpr int BAR_REMPTY = BAR_RFULL + 40;
constexpr int BAR_XFULL = BAR_REMPTY + 40;
constexpr int BAR_XEMPTY = BAR_XFULL + 40;
constexpr int BAR_PRDY = BAR_XEMPTY + 40;
constexpr int BAR_ITEM = BAR_PRDY + 40;
constexpr int OFF_ITEM = BAR_ITEM + MAXI * 8;
constexpr int SMEM_BYTES = OFF_ITEM + MAXI * 4;
static_assert(SMEM_BYTES <= 232448, "smem");

constexpr int NB_W = 1  , NB_PFULL = 3  , NB_VOTE = 5  , NB_Q2 = 7, NB_SDONE = 8, NB_PDONE = 9,
              NB_L = 10, NB_REF = 11, NB_ODONE = 12, NB_OPEND = 13, NB_LX = 14, NB_Q01 = 15, NB_QK = 0  ;

constexpr uint32_t IT_QA = 1, IT_OP = 2, IT_ON = 3;
__host__ __device__ constexpr uint32_t mk_item(uint32_t type, uint32_t br, uint32_t b, uint32_t h0, uint32_t h1, uint32_t half,
                                               uint32_t part = 0) {
    return type | (br << 2) | (b << 3) | (h0 << 7) | (h1 << 13) | (half << 19) | (part << 22);
}
#define IT_TYPE(e) ((e) & 3u)
#define IT_BR(e) (((e) >> 2) & 1u)
#define IT_B(e) (((e) >> 3) & 15u)
#define IT_H0(e) (((e) >> 7) & 63u)
#define IT_H1(e) (((e) >> 13) & 63u)
#define IT_HALF(e) (((e) >> 19) & 7u)
#define IT_PART(e) (((e) >> 22) & 1u)
#define IT_SLOT(e) IT_H1(e)
#define IT_DEP(e) (((e) >> 23) & 127u)

struct Params {
    CUtensorMap x[2], wq[2], k[2], v[2], wo[2], won[2], out;
    const __nv_bfloat16 *px[2], *pwq[2], *pk[2], *pv[2];
    struct alignas(16) { uint32_t delay, items[NSTAT]; } cl[NCL];
    uint32_t nlist;
    uint8_t slot[64];
    uint32_t list[568];
};

constexpr int OUNIT = 61440;
__device__ __align__(1024) unsigned char g_ostash[(size_t)1024 * OUNIT];
__device__ __align__(256) unsigned int g_flag[32 * 64];
__device__ __forceinline__ unsigned char* ostash(uint32_t slot, uint32_t b) { return g_ostash + (slot * 16 + b) * OUNIT; }
__device__ unsigned int g_epoch[NCTA * 4];
__device__ unsigned int g_ticket[2];

constexpr int SMEM_LAUNCH = SMEM_BYTES;
#define TS(role, idx)
#define TS_ITEM(e)
#define TS_DUMP(role)
#define TSD(role, idx)

__device__ __forceinline__ uint64_t pol_stream() {
    uint64_t p;
    asm volatile("createpolicy.fractional.L2::evict_first.b64 %0, 1.0;" : "=l"(p));
    return p;
}
__device__ __forceinline__ uint64_t pol_shared() {
    uint64_t p;
    asm volatile("createpolicy.fractional.L2::evict_unchanged.b64 %0, 1.0;" : "=l"(p));
    return p;
}
constexpr int QHOLD = 8;
constexpr float SM_C = 0.07216878364870322f * 1.4426950408889634f;

__device__ __forceinline__ uint32_t next_epoch(int warp) {
    unsigned int* p = &g_epoch[blockIdx.x * 4 + warp];
    const uint32_t e = __ldcg(p) + 1;
    *p = e;
    return e;
}

__device__ __forceinline__ uint32_t tid_now() {
    uint32_t t;
    asm volatile("mov.u32 %0, %%tid.x;" : "=r"(t));
    return t;
}
__device__ __forceinline__ void mbar_init(uint32_t a, uint32_t c) {
    asm volatile("mbarrier.init.shared::cta.b64 [%0], %1;" ::"r"(a), "r"(c) : "memory");
}
__device__ __forceinline__ void mbar_expect(uint32_t a, uint32_t b) {
    asm volatile("mbarrier.arrive.expect_tx.shared::cta.b64 _, [%0], %1;" ::"r"(a), "r"(b) : "memory");
}
template <int CNT = 1>
__device__ __forceinline__ void mbar_arrive_warp(uint32_t a) {
    if (CNT == 1)
        asm volatile("{\n.reg .pred p;\nelect.sync _|p, 0xffffffff;\n@p mbarrier.arrive.shared::cta.b64 _, [%0];\n}" ::"r"(a) : "memory");
    else
        asm volatile(
            "{\n.reg .pred p;\nelect.sync _|p, 0xffffffff;\n@p mbarrier.arrive.shared::cta.b64 _, [%0];\n"
            "@p mbarrier.arrive.shared::cta.b64 _, [%0];\n}" ::"r"(a)
            : "memory");
}
template <int CNT = 1>
__device__ __forceinline__ void mbar_arrive_warp_if(uint32_t a, bool cond) {
    if (CNT == 1)
        asm volatile(
            "{\n.reg .pred p, c;\nelect.sync _|p, 0xffffffff;\nsetp.ne.and.u32 c, %1, 0, p;\n"
            "@c mbarrier.arrive.shared::cta.b64 _, [%0];\n}" ::"r"(a), "r"((uint32_t)cond)
            : "memory");
    else
        asm volatile(
            "{\n.reg .pred p, c;\nelect.sync _|p, 0xffffffff;\nsetp.ne.and.u32 c, %1, 0, p;\n"
            "@c mbarrier.arrive.shared::cta.b64 _, [%0];\n@c mbarrier.arrive.shared::cta.b64 _, [%0];\n}" ::"r"(a), "r"((uint32_t)cond)
            : "memory");
}
__device__ __forceinline__ uint32_t deadline() {
    uint32_t c;
    asm volatile("mov.u32 %0, %%clock_hi;" : "=r"(c));
    return c + 4;
}
__device__ __forceinline__ void mbar_wait(uint32_t a, uint32_t ph, uint32_t dl) {
    asm volatile(
        "{\n.reg .pred p;\n.reg .u32 m;\n"
        "LOOP:\n"
        "mbarrier.try_wait.parity.shared::cta.b64 p, [%0], %1;\n"
        "@p bra DONE;\n"
        "mov.u32 m, %%clock_hi;\n"
        "setp.ne.u32 p, m, %2;\n"
        "@p bra LOOP;\n"
        "trap;\n"
        "DONE:\n}" ::"r"(a), "r"(ph), "r"(dl)
        : "memory");
}
__device__ __forceinline__ void mbar_wait2(uint32_t a, uint32_t pa, uint32_t b, uint32_t pb, uint32_t dl) {
    asm volatile(
        "{\n.reg .pred p, q;\n.reg .u32 m;\n"
        "LOOP:\n"
        "mbarrier.try_wait.parity.shared::cta.b64 p, [%0], %1;\n"
        "mbarrier.try_wait.parity.shared::cta.b64 q, [%2], %3;\n"
        "and.pred p, p, q;\n"
        "@p bra DONE;\n"
        "mov.u32 m, %%clock_hi;\n"
        "setp.ne.u32 p, m, %4;\n"
        "@p bra LOOP;\n"
        "trap;\n"
        "DONE:\n}" ::"r"(a), "r"(pa), "r"(b), "r"(pb), "r"(dl)
        : "memory");
}
template <int ID, int CNT>
__device__ __forceinline__ void nb_sync() { asm volatile("bar.sync %0, %1;" ::"n"(ID), "n"(CNT) : "memory"); }
template <int ID, int CNT>
__device__ __forceinline__ void nb_arrive() { asm volatile("bar.arrive %0, %1;" ::"n"(ID), "n"(CNT) : "memory"); }
__device__ __forceinline__ void fence_async_smem() { asm volatile("fence.proxy.async.shared::cta;" ::: "memory"); }

__device__ __forceinline__ void tma3(uint32_t dst, const CUtensorMap* m, int c1, int c2, uint32_t bar, uint64_t pol) {
    asm volatile(
        "cp.async.bulk.tensor.3d.shared::cluster.global.mbarrier::complete_tx::bytes.L2::cache_hint [%0], [%1, {%3,%4,%5}], [%2], %6;" ::"r"(dst),
        "l"(m), "r"(bar), "r"(0), "r"(c1), "r"(c2), "l"(pol)
        : "memory");
}
__device__ __forceinline__ void tma3_mc(uint32_t dst, const CUtensorMap* m, int c1, int c2, uint32_t bar, uint64_t pol) {
    asm volatile(
        "cp.async.bulk.tensor.3d.shared::cluster.global.mbarrier::complete_tx::bytes.multicast::cluster.L2::cache_hint"
        " [%0], [%1, {%3,%4,%5}], [%2], %6, %7;" ::"r"(dst),
        "l"(m), "r"(bar), "r"(0), "r"(c1), "r"(c2), "h"((unsigned short)3), "l"(pol)
        : "memory");
}
__device__ __forceinline__ void bulk_load(uint32_t dst, const void* src, uint32_t bytes, uint32_t bar, uint64_t pol) {
    asm volatile("cp.async.bulk.shared::cluster.global.mbarrier::complete_tx::bytes.L2::cache_hint [%0], [%1], %2, [%3], %4;" ::"r"(dst),
                 "l"(src), "r"(bytes), "r"(bar), "l"(pol)
                 : "memory");
}
__device__ __forceinline__ void wg_fence() { asm volatile("wgmma.fence.sync.aligned;" ::: "memory"); }
__device__ __forceinline__ void wg_commit() { asm volatile("wgmma.commit_group.sync.aligned;" ::: "memory"); }
template <int N>
__device__ __forceinline__ void wg_wait() { asm volatile("wgmma.wait_group.sync.aligned %0;" ::"n"(N) : "memory"); }

#define RW80(c, d) c(d[0]), c(d[1]), c(d[2]), c(d[3]), c(d[4]), c(d[5]), c(d[6]), c(d[7]), c(d[8]), c(d[9]), c(d[10]), c(d[11]), c(d[12]), c(d[13]), c(d[14]), c(d[15]), c(d[16]), c(d[17]), c(d[18]), c(d[19]), c(d[20]), c(d[21]), c(d[22]), c(d[23]), c(d[24]), c(d[25]), c(d[26]), c(d[27]), c(d[28]), c(d[29]), c(d[30]), c(d[31]), c(d[32]), c(d[33]), c(d[34]), c(d[35]), c(d[36]), c(d[37]), c(d[38]), c(d[39]), c(d[40]), c(d[41]), c(d[42]), c(d[43]), c(d[44]), c(d[45]), c(d[46]), c(d[47]), c(d[48]), c(d[49]), c(d[50]), c(d[51]), c(d[52]), c(d[53]), c(d[54]), c(d[55]), c(d[56]), c(d[57]), c(d[58]), c(d[59]), c(d[60]), c(d[61]), c(d[62]), c(d[63]), c(d[64]), c(d[65]), c(d[66]), c(d[67]), c(d[68]), c(d[69]), c(d[70]), c(d[71]), c(d[72]), c(d[73]), c(d[74]), c(d[75]), c(d[76]), c(d[77]), c(d[78]), c(d[79])
#define RW48(c, d) c(d[0]), c(d[1]), c(d[2]), c(d[3]), c(d[4]), c(d[5]), c(d[6]), c(d[7]), c(d[8]), c(d[9]), c(d[10]), c(d[11]), c(d[12]), c(d[13]), c(d[14]), c(d[15]), c(d[16]), c(d[17]), c(d[18]), c(d[19]), c(d[20]), c(d[21]), c(d[22]), c(d[23]), c(d[24]), c(d[25]), c(d[26]), c(d[27]), c(d[28]), c(d[29]), c(d[30]), c(d[31]), c(d[32]), c(d[33]), c(d[34]), c(d[35]), c(d[36]), c(d[37]), c(d[38]), c(d[39]), c(d[40]), c(d[41]), c(d[42]), c(d[43]), c(d[44]), c(d[45]), c(d[46]), c(d[47])
#define RW32(c, d) c(d[0]), c(d[1]), c(d[2]), c(d[3]), c(d[4]), c(d[5]), c(d[6]), c(d[7]), c(d[8]), c(d[9]), c(d[10]), c(d[11]), c(d[12]), c(d[13]), c(d[14]), c(d[15]), c(d[16]), c(d[17]), c(d[18]), c(d[19]), c(d[20]), c(d[21]), c(d[22]), c(d[23]), c(d[24]), c(d[25]), c(d[26]), c(d[27]), c(d[28]), c(d[29]), c(d[30]), c(d[31])

__device__ __forceinline__ void reg_fence(float (&d)[80]) { asm volatile("" : RW80("+f", d)::"memory"); }
__device__ __forceinline__ void reg_fence(float (&d)[48]) { asm volatile("" : RW48("+f", d)::"memory"); }
__device__ __forceinline__ void reg_fence(float (&d)[32]) { asm volatile("" : RW32("+f", d)::"memory"); }

template <int NR>
__device__ __forceinline__ void zero(float (&d)[NR]) {
#pragma unroll
    for (int i = 0; i < NR; i++) d[i] = 0.f;
}

constexpr uint32_t HI_SW128 = (1024u >> 4) | (1u << 30);
constexpr uint32_t HI_KV = (3072u >> 4) | (1u << 30);
constexpr uint32_t HI_OST = (2560u >> 4) | (2u << 30);
constexpr uint32_t LO_LBO1 = (1u << 16);
constexpr uint32_t LO_OST = ((512u >> 4) << 16);

template <int TA, int TB, uint32_t HIB, int ACC, uint32_t HIA = HI_SW128>
__device__ __forceinline__ void wgmma(float (&d)[80], uint32_t loA, uint32_t loB) {
#define WG_ASM(SD)                                                          \
    "{\n.reg .b64 da, db;\nmov.b64 da, {%80, %82};\nmov.b64 db, {%81, %83};\n" \
    "wgmma.mma_async.sync.aligned.m64n160k16.f32.bf16.bf16 "               \
    "{%0,%1,%2,%3,%4,%5,%6,%7,%8,%9,%10,%11,%12,%13,%14,%15,%16,%17,%18,%19,%20,%21,%22,%23,%24,%25,%26,%27,%28,%29,%30,%31,%32,%33,%34,%35,%36,%37,%38,%39,%40,%41,%42,%43,%44,%45,%46,%47,%48,%49,%50,%51,%52,%53,%54,%55,%56,%57,%58,%59,%60,%61,%62,%63,%64,%65,%66,%67,%68,%69,%70,%71,%72,%73,%74,%75,%76,%77,%78,%79}, da, db, " SD ", 1, 1, %84, %85;\n}"
    if constexpr (ACC == 2)
        asm volatile(WG_ASM("0") : RW80("+f", d) : "r"(loA), "r"(loB), "n"(HIA), "n"(HIB), "n"(TA), "n"(TB));
    else if constexpr (ACC == 1)
        asm volatile(WG_ASM("1") : RW80("+f", d) : "r"(loA), "r"(loB), "n"(HIA), "n"(HIB), "n"(TA), "n"(TB));
    else
        asm volatile(WG_ASM("0") : RW80("=f", d) : "r"(loA), "r"(loB), "n"(HIA), "n"(HIB), "n"(TA), "n"(TB));
#undef WG_ASM
}
template <int TA, int TB, uint32_t HIB, int ACC, uint32_t HIA = HI_SW128>
__device__ __forceinline__ void wgmma(float (&d)[48], uint32_t loA, uint32_t loB) {
#define WG_ASM(SD)                                                          \
    "{\n.reg .b64 da, db;\nmov.b64 da, {%48, %50};\nmov.b64 db, {%49, %51};\n" \
    "wgmma.mma_async.sync.aligned.m64n96k16.f32.bf16.bf16 "               \
    "{%0,%1,%2,%3,%4,%5,%6,%7,%8,%9,%10,%11,%12,%13,%14,%15,%16,%17,%18,%19,%20,%21,%22,%23,%24,%25,%26,%27,%28,%29,%30,%31,%32,%33,%34,%35,%36,%37,%38,%39,%40,%41,%42,%43,%44,%45,%46,%47}, da, db, " SD ", 1, 1, %52, %53;\n}"
    if constexpr (ACC == 1)
        asm volatile(WG_ASM("1") : RW48("+f", d) : "r"(loA), "r"(loB), "n"(HIA), "n"(HIB), "n"(TA), "n"(TB));
    else
        asm volatile(WG_ASM("0") : RW48("=f", d) : "r"(loA), "r"(loB), "n"(HIA), "n"(HIB), "n"(TA), "n"(TB));
#undef WG_ASM
}
template <int TA, int TB, uint32_t HIB, int ACC, uint32_t HIA = HI_SW128>
__device__ __forceinline__ void wgmma(float (&d)[32], uint32_t loA, uint32_t loB) {
#define WG_ASM(SD)                                                          \
    "{\n.reg .b64 da, db;\nmov.b64 da, {%32, %34};\nmov.b64 db, {%33, %35};\n" \
    "wgmma.mma_async.sync.aligned.m64n64k16.f32.bf16.bf16 "               \
    "{%0,%1,%2,%3,%4,%5,%6,%7,%8,%9,%10,%11,%12,%13,%14,%15,%16,%17,%18,%19,%20,%21,%22,%23,%24,%25,%26,%27,%28,%29,%30,%31}, da, db, " SD ", 1, 1, %36, %37;\n}"
    if constexpr (ACC == 1)
        asm volatile(WG_ASM("1") : RW32("+f", d) : "r"(loA), "r"(loB), "n"(HIA), "n"(HIB), "n"(TA), "n"(TB));
    else
        asm volatile(WG_ASM("0") : RW32("=f", d) : "r"(loA), "r"(loB), "n"(HIA), "n"(HIB), "n"(TA), "n"(TB));
#undef WG_ASM
}

__device__ __forceinline__ uint32_t pack_bf16(float lo, float hi) {
    uint32_t r;
    asm("cvt.rn.bf16x2.f32 %0, %1, %2;" : "=r"(r) : "f"(hi), "f"(lo));
    return r;
}
__device__ __forceinline__ float ex2(float x) {
    float r;
    asm("ex2.approx.ftz.f32 %0, %1;" : "=f"(r) : "f"(x));
    return r;
}
__device__ __forceinline__ void stsm4t(uint32_t a, uint32_t r0, uint32_t r1, uint32_t r2, uint32_t r3) {
    asm volatile("stmatrix.sync.aligned.m8n8.x4.trans.shared.b16 [%0], {%1,%2,%3,%4};" ::"r"(a), "r"(r0), "r"(r1), "r"(r2), "r"(r3)
                 : "memory");
}
__device__ __forceinline__ uint32_t lds_u(uint32_t a) {
    uint32_t v;
    asm volatile("ld.shared.u32 %0, [%1];" : "=r"(v) : "r"(a) : "memory");
    return v;
}
__device__ __forceinline__ uint4 lds_u4(uint32_t a) {
    uint4 v;
    asm volatile("ld.shared.v4.u32 {%0,%1,%2,%3}, [%4];" : "=r"(v.x), "=r"(v.y), "=r"(v.z), "=r"(v.w) : "r"(a) : "memory");
    return v;
}
__device__ __forceinline__ float2 lds_f2(uint32_t a) {
    float2 v;
    asm volatile("ld.shared.v2.f32 {%0,%1}, [%2];" : "=f"(v.x), "=f"(v.y) : "r"(a) : "memory");
    return v;
}
__device__ __forceinline__ void sts_f(uint32_t a, float v) { asm volatile("st.shared.f32 [%0], %1;" ::"r"(a), "f"(v) : "memory"); }
__device__ __forceinline__ void sts_u(uint32_t a, uint32_t v) { asm volatile("st.shared.u32 [%0], %1;" ::"r"(a), "r"(v) : "memory"); }
__device__ __forceinline__ void sts_f2(uint32_t a, float x, float y) {
    asm volatile("st.shared.v2.f32 [%0], {%1,%2};" ::"r"(a), "f"(x), "f"(y) : "memory");
}

template <bool SIG = false, int NR>
__device__ __forceinline__ void store_tile_t(const float (&d)[NR], uint32_t addr) {
#pragma unroll
    for (int j = 0; j < NR / 8; j++) {
        stsm4t(addr + j * 2048, pack_bf16(d[8 * j], d[8 * j + 1]), pack_bf16(d[8 * j + 2], d[8 * j + 3]),
               pack_bf16(d[8 * j + 4], d[8 * j + 5]), pack_bf16(d[8 * j + 6], d[8 * j + 7]));
        if (SIG && j == 0) nb_arrive<NB_L, 160>();
    }
}

struct TrueT { static constexpr bool value = true; };
struct FalseT { static constexpr bool value = false; };

template <int V>
struct IntT { static constexpr int value = V; };

__device__ __forceinline__ uint32_t get_item(uint32_t sb, int it, uint32_t dl) {
    mbar_wait(sb + BAR_ITEM + it * 8, 0, dl);
    return lds_u(sb + OFF_ITEM + it * 4);
}
__device__ __forceinline__ uint32_t get_item_warp(uint32_t sb, int it, uint32_t dl) {
    return __shfl_sync(0xffffffffu, get_item(sb, it, dl), 0);
}

struct Ring {
    uint32_t slot, ph, dl;
    __device__ __forceinline__ void adv(uint32_t k) {
        slot += k;
        if (slot >= NSLOT) { slot -= NSLOT; ph ^= 1; }
    }
};

template <int K>
__device__ __forceinline__ void qk_step(float (&s)[80], uint32_t loK, uint32_t loQ) {
    wgmma<0, 0, HI_SW128, K != 0, HI_KV>(s, loK + (K >> 2) * 64 + (K & 3) * 2, loQ + (K >> 2) * (XS >> 4) + (K & 3) * 2);
}
template <int K0, int K1>
__device__ __forceinline__ void qk_steps(float (&s)[80], uint32_t loK, uint32_t loQ) {
    if constexpr (K0 < K1) {
        qk_step<K0>(s, loK, loQ);
        qk_steps<K0 + 1, K1>(s, loK, loQ);
    }
}
__device__ __forceinline__ uint32_t add_bf2(uint32_t a, uint32_t b) {
    uint32_t r;
    asm("add.rn.bf16x2 %0, %1, %2;" : "=r"(r) : "r"(a), "r"(b));
    return r;
}
__device__ __forceinline__ uint32_t fma_bf2(uint32_t a, uint32_t b, uint32_t c) {
    uint32_t r;
    asm("fma.rn.bf16x2 %0, %1, %2, %3;" : "=r"(r) : "r"(a), "r"(b), "r"(c));
    return r;
}
template <int J>
__device__ __forceinline__ void exp_block(const float (&s)[80], uint32_t (&k)[40], uint32_t pa, float mref) {
    if constexpr (J < 10) {
#pragma unroll
        for (int i = 4 * J; i < 4 * J + 4; i++)
            k[i] = pack_bf16(ex2(fmaf(s[2 * i], SM_C, -mref)), ex2(fmaf(s[2 * i + 1], SM_C, -mref)));
#pragma unroll
        for (int i = 0; i < 4; i++)
            asm volatile("stmatrix.sync.aligned.m8n8.x1.trans.shared.b16 [%0], {%1};" ::"r"(((i & 1) ? pa ^ 16 : pa) + J * 2048 + (i >> 1) * 1024),
                         "r"(k[4 * J + i])
                         : "memory");
        exp_block<J + 1>(s, k, pa, mref);
    }
}
__device__ __forceinline__ void sum_block(const uint32_t (&k)[40], float (&l)[10], uint32_t lane) {
    const bool b4 = lane & 16, b3 = lane & 8;
    uint32_t ps[20], t[10];
#pragma unroll
    for (int j = 0; j < 20; j++) ps[j] = add_bf2(k[2 * j], k[2 * j + 1]);
#pragma unroll
    for (int j = 0; j < 10; j++)
        t[j] = add_bf2(b4 ? ps[2 * j + 1] : ps[2 * j], __shfl_xor_sync(0xffffffffu, b4 ? ps[2 * j] : ps[2 * j + 1], 16));
#pragma unroll
    for (int i = 0; i < 5; i++) {
        const uint32_t a = b3 ? t[i + 5] : t[i], b = __shfl_xor_sync(0xffffffffu, b3 ? t[i] : t[i + 5], 8);
        l[2 * i] += __uint_as_float(a << 16) + __uint_as_float(b << 16);
        l[2 * i + 1] += __uint_as_float(a & 0xffff0000u) + __uint_as_float(b & 0xffff0000u);
    }
}
template <bool ADD>
__device__ __forceinline__ void sum_store(const float (&l)[10], uint32_t lane, uint32_t lxa) {
    const bool b2 = lane & 4;
    float t[5];
#pragma unroll
    for (int i = 0; i < 5; i++) t[i] = ADD ? __uint_as_float(lds_u(lxa + i * 64)) : 0.f;
#pragma unroll
    for (int i = 0; i < 5; i++)
        sts_f(lxa + i * 64, t[i] + (b2 ? l[2 * i + 1] : l[2 * i]) + __shfl_xor_sync(0xffffffffu, b2 ? l[2 * i] : l[2 * i + 1], 4));
}

__device__ __forceinline__ void fallback_unit(const Params& P, uint32_t e, uint32_t tid) {
    const uint32_t lane = tid & 31, br = IT_BR(e), b = IT_B(e), h = IT_H0(e);
    const __nv_bfloat162* wq = (const __nv_bfloat162*)(P.pwq[br] + h * 192) + lane;
    const __nv_bfloat162* kp = (const __nv_bfloat162*)(P.pk[br] + (size_t)(b * 32 + h) * 512 * 192) + lane;
    const __nv_bfloat162* vp = (const __nv_bfloat162*)(P.pv[br] + (size_t)(b * 32 + h) * 512 * 192) + lane;
#pragma unroll 1
    for (uint32_t qi = 0; qi < 40; qi++) {
        const uint32_t q = 4 * qi + (tid >> 5);
        const __nv_bfloat16* xr = P.px[br] + (size_t)(b * 160 + q) * 640;
        float a[6] = {0.f, 0.f, 0.f, 0.f, 0.f, 0.f};
#pragma unroll 2
        for (int k = 0; k < 640; k++) {
            const float xv = __bfloat162float(xr[k]);
#pragma unroll
            for (int i = 0; i < 3; i++) {
                const float2 wv = __bfloat1622float2(wq[(size_t)k * 3072 + i * 32]);
                a[2 * i] = fmaf(xv, wv.x, a[2 * i]);
                a[2 * i + 1] = fmaf(xv, wv.y, a[2 * i + 1]);
            }
        }
#pragma unroll
        for (int i = 0; i < 6; i++) a[i] = __bfloat162float(__float2bfloat16(a[i]));
        auto score = [&](int key) {
            float d = 0.f;
#pragma unroll
            for (int i = 0; i < 3; i++) {
                const float2 kv = __bfloat1622float2(kp[key * 96 + i * 32]);
                d = fmaf(a[2 * i], kv.x, fmaf(a[2 * i + 1], kv.y, d));
            }
#pragma unroll
            for (int o = 16; o > 0; o >>= 1) d += __shfl_xor_sync(0xffffffffu, d, o);
            return d;
        };
        float m = -INFINITY, o[6] = {0.f, 0.f, 0.f, 0.f, 0.f, 0.f}, sum = 0.f;
#pragma unroll 1
        for (int n = 0; n < 1024; n++) {
            const int key = n & 511;
            const float d = score(key);
            if (n < 512) {
                m = fmaxf(m, d);
            } else {
                const float p = ex2((d - m) * SM_C);
                sum += p;
#pragma unroll
                for (int i = 0; i < 3; i++) {
                    const float2 vv = __bfloat1622float2(vp[key * 96 + i * 32]);
                    o[2 * i] = fmaf(p, vv.x, o[2 * i]);
                    o[2 * i + 1] = fmaf(p, vv.y, o[2 * i + 1]);
                }
            }
        }
        const float inv = __fdividef(1.f, sum);
        __nv_bfloat16* op = (__nv_bfloat16*)ostash(IT_SLOT(e), b) + (q >> 5) * 256 + 2 * ((q & 31) >> 3) + (q & 1);
#pragma unroll
        for (int i = 0; i < 6; i++) {
            const uint32_t d = (i >> 1) * 64 + 2 * lane + (i & 1);
            op[(d >> 3) * 1280 + (d & 7) * 32 + ((((q & 7) >> 1) ^ ((d & 7) >> 1)) << 3)] = __float2bfloat16(o[i] * inv);
        }
    }
}

struct PendO {
    uint32_t v[64];
    unsigned char* gp;
    static __device__ __forceinline__ uint32_t toff() {
        const uint32_t t = tid_now();
        return ((t >> 5) & 3) * 5120 + ((t >> 2) & 7) * 64 + (((t ^ (t >> 3)) & 3) << 4);
    }
    uint32_t pend, sig, bad;
    static __device__ __forceinline__ void scale(uint32_t& x, uint32_t hi, uint32_t lo) {
        asm("{\n.reg .b32 t;\nmul.rn.bf16x2 t, %0, %2;\nfma.rn.bf16x2 %0, %0, %1, t;\n}" : "+r"(x) : "r"(hi), "r"(lo));
    }
    template <int I, int OFF>
    __device__ __forceinline__ void put() {
        asm volatile("{\n.reg .pred p;\nsetp.ne.u32 p, %6, 0;\n@p st.global.v4.b32 [%0+%5], {%1,%2,%3,%4};\n}" ::"l"(gp), "r"(v[I]),
                     "r"(v[I + 1]), "r"(v[I + 2]), "r"(v[I + 3]), "n"(OFF), "r"(pend)
                     : "memory");
    }
    __device__ __forceinline__ void verdict(uint32_t sb, uint32_t W) {
        if (sig) {
            asm volatile("bar.sync %0, 160;" ::"r"(NB_VOTE + W) : "memory");
            bad = __any_sync(0xffffffffu, lds_u(sb + OFF_FB) != 0);
            pend = !bad;
        }
    }
    template <int W, int G, int H>
    __device__ __forceinline__ void half(uint32_t sb) {
        constexpr bool T2 = W == 0 ? G >= 3 : G < 3;
        constexpr int B = T2 ? 40 + 8 * (W == 0 ? G - 3 : G) : 0;
        const uint4 a = lds_u4(sb + OFF_LINV + G * 128 + H * 16 + (threadIdx.x & 3) * 32);
#pragma unroll
        for (int i = 2 * H; i < 8; i += 4) {
            scale(v[8 * G + i], a.x, a.y);
            scale(v[8 * G + i + 1], a.z, a.w);
            if (T2) {
                scale(v[B + i], a.x, a.y);
                scale(v[B + i + 1], a.z, a.w);
            }
        }
        if (H == 1) {
            put<8 * G, W * XS + G * 512>();
            put<8 * G + 4, W * XS + G * 512 + 2560>();
            if (T2) {
                put<B, 2 * XS + G * 512>();
                put<B + 4, 2 * XS + G * 512 + 2560>();
            }
            if (G == 4 && pend) nb_arrive<NB_ODONE, 288>();
        }
    }
    template <int W, int G>
    __device__ __forceinline__ void step(uint32_t sb) {
        half<W, G, 0>(sb);
        half<W, G, 1>(sb);
    }
    template <int W>
    __device__ __forceinline__ void flush(uint32_t sb) {
        step<W, 0>(sb);
        step<W, 1>(sb);
        step<W, 2>(sb);
        step<W, 3>(sb);
        step<W, 4>(sb);
    }
    __device__ __forceinline__ void clear() {
#pragma unroll
        for (int i = 0; i < 64; i++) v[i] = 0;
        gp = nullptr;
        pend = 0;
        sig = 0;
        bad = 0;
    }
};

__device__ __forceinline__ uint32_t stsm_off() {
    const uint32_t tid = tid_now(), lane = tid & 31;
    return (lane >> 4) * 1024 + (lane & 7) * 128 + (((((tid >> 4) & 6) + ((lane >> 3) & 1)) ^ (lane & 7)) << 4);
}
__device__ __forceinline__ void q_ahead(float (&q0)[80], uint32_t sb, const Ring& rn, uint32_t phm, bool valid) {
    if (valid) mbar_wait2(sb + BAR_RFULL + rn.slot * 8, rn.ph, sb + BAR_XFULL, phm & 1, rn.dl);
    const uint32_t a = ((((sb + OFF_RING) & 0x3ffff) >> 4) | LO_LBO1) + rn.slot * (SLOT >> 4);
    const uint32_t b = (((sb + OFF_R) & 0x3ffff) >> 4) | LO_LBO1;
    wg_fence();
    wgmma<1, 0, HI_SW128, false>(q0, a, b);
#pragma unroll
    for (int k = 1; k < 4; k++) wgmma<1, 0, HI_SW128, true>(q0, a + (k >> 1) * 768 + (k & 1) * 128, b + k * 2);
    wg_commit();
}
template <int W, int KK>
__device__ __forceinline__ void qproj(float (&q0)[80], float (&q1)[80], uint32_t sb, Ring& r, uint32_t pslot, uint32_t phm,
                                      PendO& po) {
    const uint32_t loR = (((sb + OFF_R) & 0x3ffff) >> 4) | LO_LBO1;
    const uint32_t loRing = (((sb + OFF_RING) & 0x3ffff) >> 4) | LO_LBO1;
    auto ready = [&](int k) {
        mbar_wait2(sb + BAR_RFULL + r.slot * 8, r.ph, sb + BAR_XFULL + (k % 5) * 8, ((phm >> (k % 5)) ^ (k / 5)) & 1, r.dl);
    };
    auto release = [&]() {
        if (KK > 0) {
            wg_wait<1>();
            mbar_arrive_warp(sb + BAR_REMPTY + pslot * 8);
            if (KK <= 5) mbar_arrive_warp(sb + (BAR_XEMPTY + (KK - 1) * 8));
        }
    };
    if (KK == 0 && W == 1) ready(0);
    if (W == 1 && KK == QHOLD) nb_sync<NB_SDONE, 256>();
    const uint32_t a = loRing + r.slot * (SLOT >> 4) + (W == 0 ? 0 : 512), b = loR + (KK % 5) * (XS >> 4);
    wg_fence();
    constexpr bool T0 = W == 1 || KK > 0;
    if (T0) wgmma<1, 0, HI_SW128, KK != 0>(q0, a, b);
    if (W == 0) wgmma<1, 0, HI_SW128, KK != 0 ? 1 : 2>(q1, a + 256, b);
#pragma unroll
    for (int k = 1; k < 4; k++) {
        if (T0) wgmma<1, 0, HI_SW128, true>(q0, a + (k >> 1) * 768 + (k & 1) * 128, b + k * 2);
        if (W == 0) wgmma<1, 0, HI_SW128, true>(q1, a + 256 + (k >> 1) * 768 + (k & 1) * 128, b + k * 2);
    }
    wg_commit();
    const uint32_t cslot = r.slot;
    r.adv(1);
    if (W == 0 || KK < QHOLD) release();
    constexpr int QST = W == 0 ? 2 : 1;
    if (KK == QST) {
        po.verdict(sb, W);
        po.template half<W, 0, 0>(sb);
    }
    if (KK < 9) ready(KK + 1);
    if (W == 1 && KK >= QHOLD) release();
    if (W == 1 && KK == 7) nb_arrive<NB_PDONE, 256>();
    if (KK == QST) po.template half<W, 0, 1>(sb);
    if constexpr (KK > QST && KK < QST + 5) po.template step<W, KK - QST>(sb);
    if constexpr (KK < (W == 0 ? 7 : 9)) {
        qproj<W, KK + 1>(q0, q1, sb, r, cslot, phm, po);
    } else if constexpr (W == 1) {
        const uint32_t sta = sb + OFF_R + 2 * XS + stsm_off();
        wg_wait<0>();
        reg_fence(q0);
        store_tile_t<true>(q0, sta);
        mbar_arrive_warp(sb + BAR_REMPTY + cslot * 8);
    } else {
        const uint32_t s8 = r.slot, a8 = loRing + s8 * (SLOT >> 4);
        wg_fence();
#pragma unroll
        for (int k = 0; k < 4; k++) wgmma<1, 0, HI_SW128, true>(q0, a8 + (k >> 1) * 768 + (k & 1) * 128, loR + 3 * (XS >> 4) + k * 2);
        r.adv(1);
        ready(9);
        const uint32_t s9 = r.slot, a9 = loRing + s9 * (SLOT >> 4);
        r.adv(1);
        wg_fence();
#pragma unroll
        for (int k = 0; k < 4; k++) wgmma<1, 0, HI_SW128, true>(q0, a9 + (k >> 1) * 768 + (k & 1) * 128, loR + 4 * (XS >> 4) + k * 2);
        wg_commit();
        wg_wait<1>();
        mbar_arrive_warp(sb + BAR_REMPTY + cslot * 8);
        wg_fence();
#pragma unroll
        for (int k = 0; k < 8; k++)
            wgmma<1, 0, HI_SW128, true>(q1, (k < 4 ? a8 : a9) + 256 + ((k >> 1) & 1) * 768 + (k & 1) * 128,
                                        loR + (3 + (k >> 2)) * (XS >> 4) + (k & 3) * 2);
        wg_commit();
        nb_arrive<NB_SDONE, 256>();
        sts_u(sb + OFF_GM + 4, r.slot);
        nb_sync<NB_PDONE, 256>();
        wg_wait<1>();
        reg_fence(q0);
        const uint32_t sta = sb + OFF_R + stsm_off();
        store_tile_t(q0, sta);
        wg_wait<0>();
        reg_fence(q1);
        mbar_arrive_warp(sb + BAR_REMPTY + s8 * 8);
        mbar_arrive_warp(sb + BAR_REMPTY + s9 * 8);
        store_tile_t(q1, sta + XS);
        mbar_wait(sb + BAR_RFULL + r.slot * 8, r.ph, r.dl);
    }
}

template <int NR>
__device__ __forceinline__ void opack(const float (&o)[NR], uint32_t* v) {
#pragma unroll
    for (int g = 0; g < NR / 16; g++)
#pragma unroll
        for (int hh = 0; hh < 2; hh++)
#pragma unroll
            for (int t = 0; t < 4; t++) v[8 * g + 4 * hh + t] = pack_bf16(o[16 * g + 4 * t + 2 * hh], o[16 * g + 4 * t + 2 * hh + 1]);
}

__device__ __forceinline__ void out_store(const Params& P, uint32_t src, int col, int b) {
    asm volatile("cp.async.bulk.tensor.5d.global.shared::cta.bulk_group [%0, {%2,%4,%4,%4,%3}], [%1];" ::"l"(&P.out), "r"(src),
                 "r"(col), "r"(b * 5), "r"(0)
                 : "memory");
    asm volatile("cp.async.bulk.commit_group;" ::: "memory");
}

template <bool IS_S>
__device__ __forceinline__ void op_item(uint32_t e, uint32_t sb, Ring& r, uint32_t& phm) {
    constexpr int T0 = IS_S ? 0 : 2;
    constexpr uint32_t BOFF = IS_S ? (3 * 512) >> 4 : 0;
    const uint32_t loRing = (((sb + OFF_RING) & 0x3ffff) >> 4) | LO_LBO1;
    const uint32_t loO = (((sb + OFF_R) & 0x3ffff) >> 4) | LO_OST;
    float c0[80], c1[80], c2[IS_S ? 32 : 48];
    const int T = 3 * (IT_H1(e) - IT_H0(e));
    uint32_t xs = 0;
    auto step = [&](auto first, auto half) {
        constexpr bool F = decltype(first)::value;
        constexpr uint32_t hf = decltype(half)::value;
        if (hf == 0) {
            mbar_wait(sb + BAR_XFULL + xs * 8, (phm >> xs) & 1, r.dl);
            phm ^= 1u << xs;
        }
        mbar_wait(sb + BAR_RFULL + r.slot * 8, r.ph, r.dl);
        const uint32_t a = loRing + r.slot * (SLOT >> 4), b = loO + xs * (XS >> 4) + hf * 640;
        wg_fence();
        wgmma<1, 1, HI_OST, !F>(c0, a + T0 * 128, b);
        wgmma<1, 1, HI_OST, !F>(c1, a + T0 * 128 + 128, b);
        wgmma<1, 1, HI_OST, !F>(c2, a + 512, b + BOFF);
        wgmma<1, 1, HI_OST, true>(c0, a + 640 + T0 * 128, b + 320);
        wgmma<1, 1, HI_OST, true>(c1, a + 640 + T0 * 128 + 128, b + 320);
        wgmma<1, 1, HI_OST, true>(c2, a + 640 + 512, b + 320 + BOFF);
        wg_commit();
    };
    step(TrueT{}, IntT<0>{});
#pragma unroll 1
    for (int t = 1;; t++) {
        uint32_t pslot = r.slot;
        r.adv(1);
        step(FalseT{}, IntT<1>{});
        wg_wait<1>();
        mbar_arrive_warp(sb + BAR_REMPTY + pslot * 8);
        if (t == T) break;
        pslot = r.slot;
        const uint32_t pxs = xs;
        r.adv(1);
        if (++xs == 5) xs = 0;
        step(FalseT{}, IntT<0>{});
        wg_wait<1>();
        mbar_arrive_warp(sb + BAR_REMPTY + pslot * 8);
        mbar_arrive_warp_if(sb + BAR_XEMPTY + pxs * 8, t + 4 < T);
    }
    wg_wait<0>();
    reg_fence(c0);
    reg_fence(c1);
    reg_fence(c2);
    mbar_arrive_warp(sb + BAR_REMPTY + r.slot * 8);
    r.adv(1);
    nb_sync<NB_OPEND, 256>();
    const uint32_t sta = sb + OFF_R + stsm_off();
    store_tile_t(c0, sta + T0 * XS);
    store_tile_t(c1, sta + (T0 + 1) * XS);
    store_tile_t(c2, sta + 4 * XS + (IS_S ? 96 * 128 : 0));
    fence_async_smem();
    nb_arrive<NB_ODONE, 288>();
}

__device__ __forceinline__ void on_item(const Params& P, uint32_t W, uint32_t e, uint32_t sb, Ring& r, uint32_t& phm) {
    const uint32_t loRing = (((sb + OFF_RING) & 0x3ffff) >> 4) | LO_LBO1;
    const uint32_t loO = (((sb + OFF_R) & 0x3ffff) >> 4) | LO_OST;
    float c[80];
    const int T = 3 * (IT_H1(e) - IT_H0(e));
    uint32_t xs = 0;
    auto step = [&](auto first) {
        constexpr bool F = decltype(first)::value;
        mbar_wait2(sb + BAR_XFULL + xs * 8, (phm >> xs) & 1, sb + BAR_RFULL + r.slot * 8, r.ph, r.dl);
        phm ^= 1u << xs;
        const uint32_t a = loRing + r.slot * (SLOT >> 4) + W * 256, b = loO + xs * (XS >> 4);
        wg_fence();
        wgmma<1, 1, HI_OST, !F>(c, a, b);
#pragma unroll
        for (int k = 1; k < 4; k++) wgmma<1, 1, HI_OST, true>(c, a + (k >> 1) * 512 + (k & 1) * 128, b + k * 320);
        wg_commit();
    };
    step(TrueT{});
#pragma unroll 1
    for (int t = 1; t < T; t++) {
        const uint32_t pslot = r.slot, pxs = xs;
        r.adv(1);
        if (++xs == 5) xs = 0;
        step(FalseT{});
        wg_wait<1>();
        mbar_arrive_warp(sb + BAR_REMPTY + pslot * 8);
        mbar_arrive_warp_if(sb + BAR_XEMPTY + pxs * 8, t + 2 < T);
    }
    xs += 1 + W;
    if (xs >= 5) xs -= 5;
    mbar_wait(sb + BAR_XFULL + xs * 8, (phm >> xs) & 1, r.dl);
    const uint32_t sta = sb + OFF_R + xs * XS + stsm_off();
    uint32_t p[40];
#pragma unroll
    for (int j = 0; j < 10; j++)
        asm volatile("ldmatrix.sync.aligned.m8n8.x4.trans.shared.b16 {%0,%1,%2,%3}, [%4];"
                     : "=r"(p[4 * j]), "=r"(p[4 * j + 1]), "=r"(p[4 * j + 2]), "=r"(p[4 * j + 3])
                     : "r"(sta + j * 2048)
                     : "memory");
    wg_wait<0>();
    reg_fence(c);
#pragma unroll
    for (int k = 0; k < 40; k++) {
        c[2 * k] += __uint_as_float(p[k] << 16);
        c[2 * k + 1] += __uint_as_float(p[k] & 0xffff0000u);
    }
    store_tile_t(c, sta);
    fence_async_smem();
    asm volatile("bar.sync %0, 128;" ::"r"(NB_W + W) : "memory");
    if ((tid_now() & 127) == 0) {
        out_store(P, sb + OFF_R + xs * XS, IT_BR(e) * 640 + (2 * IT_HALF(e) + W) * 64, IT_B(e));
        asm volatile("cp.async.bulk.wait_group 0;" ::: "memory");
    }
    __syncwarp();
}

template <int W>
__device__ __forceinline__ uint32_t qa_item(uint32_t e, uint32_t sb, Ring& r, uint32_t phm, PendO& po, float (&q0)[80],
                                            float (&oa)[80], int it) {
    const uint32_t loR = (((sb + OFF_R) & 0x3ffff) >> 4) | LO_LBO1;
    const uint32_t loRing = (((sb + OFF_RING) & 0x3ffff) >> 4) | LO_LBO1;
    qproj<W, 0>(q0, oa, sb, r, 0, phm, po);
    fence_async_smem();
    TSD(W, 1);
    float s[80], ob[W == 0 ? 32 : 48], l[10];
    if (W == 1) {
        nb_arrive<NB_Q2, 256>();
        zero(oa);
        zero(ob);
        reg_fence(oa);
        reg_fence(ob);
    }
    const uint32_t lane = tid_now() & 31, sta = sb + OFF_R + stsm_off();
    auto pv = [&](auto first, uint32_t buf) {
        constexpr bool F = decltype(first)::value;
        if (F) mbar_wait(sb + BAR_RFULL + r.slot * 8, r.ph, r.dl);
        const uint32_t a = loRing + r.slot * (SLOT >> 4), b = loR + (3 + buf) * (XS >> 4);
        wg_fence();
        wgmma<1, 0, HI_SW128, F ? 2 : 1, HI_KV>(oa, a + W * 64, b);
        wgmma<1, 0, HI_SW128, !F, HI_KV>(ob, a + 128, b + (W == 0 ? (96 * 128) >> 4 : 0));
#pragma unroll
        for (int k = 1; k < 4; k++) {
            wgmma<1, 0, HI_SW128, true, HI_KV>(oa, a + W * 64 + k * 384, b + k * 2);
            wgmma<1, 0, HI_SW128, true, HI_KV>(ob, a + 128 + k * 384, b + (W == 0 ? (96 * 128) >> 4 : 0) + k * 2);
        }
        wg_commit();
    };
    zero(l);
    float mref;
    uint32_t kslot, vslot, nx = 0;
    auto tail = [&](auto first, int i) {
        constexpr bool rel_other = !decltype(first)::value;
        uint32_t ps[40];
        exp_block<0>(s, ps, sta + (3 + W) * XS, mref);
        if (rel_other) {
            wg_wait<0>();
            mbar_arrive_warp(sb + BAR_REMPTY + vslot * 8);
            if (W == 1) mbar_arrive_warp_if(sb + BAR_XEMPTY + 24, i == 3);
        }
        fence_async_smem();
        nb_arrive<NB_PFULL + W, 256>();
        TSD(W, 6 + 5 * i);
        if (W == 1) {
            mbar_arrive_warp_if<2>(sb + BAR_XEMPTY + 8, i == 3);
            mbar_arrive_warp_if<2>(sb + BAR_XEMPTY + 16, i == 3);
        }
        if (rel_other) {
            mbar_wait(sb + BAR_RFULL + r.slot * 8, r.ph, r.dl);
            sum_block(ps, l, lane);
        }
        if (W == 0 && i == 3) nx = get_item_warp(sb, it + 1, r.dl);
        TSD(W, 7 + 5 * i);
        nb_sync<NB_W + W, 128>();
        pv(first, W);
        if (!rel_other) sum_block(ps, l, lane);
        TSD(W, 8 + 5 * i);
    };
    if (W == 0) {
        nb_sync<NB_QK, 160>();
        TSD(W, 2);
        wg_fence();
        qk_steps<0, 8>(s, loRing + r.slot * (SLOT >> 4), loR);
        nb_sync<NB_Q2, 256>();
        qk_steps<8, 12>(s, loRing + r.slot * (SLOT >> 4), loR);
        wg_commit();
        nb_arrive<NB_Q01, 256>();
        TSD(W, 4);
        nb_sync<NB_REF, 160>();
        mref = __uint_as_float(lds_u(sb + OFF_GM));
        wg_wait<0>();
        reg_fence(s);
        mbar_arrive_warp<2>(sb + BAR_REMPTY + r.slot * 8);
        r.adv(2);
        TSD(W, 5);
        tail(TrueT{}, 0);
    } else {
        nb_sync<NB_Q01, 256>();
    }
#pragma unroll 1
    for (int i = (W == 0 ? 1 : 0); i < 4; i++) {
        const uint32_t pvslot = r.slot;
        r.adv(1);
        kslot = r.slot;
        mbar_wait(sb + BAR_RFULL + r.slot * 8, r.ph, r.dl);
        wg_fence();
        qk_steps<0, 4>(s, loRing + r.slot * (SLOT >> 4), loR);
        if (W == 1) wg_commit();
        qk_steps<4, 12>(s, loRing + r.slot * (SLOT >> 4), loR);
        wg_commit();
        wg_wait<1>();
        if (W == 1) mbar_arrive_warp_if(sb + BAR_XEMPTY + 0, i == 3);
        mbar_arrive_warp_if(sb + BAR_REMPTY + pvslot * 8, W == 0 || i > 0);
        r.adv(1);
        vslot = r.slot;
        TSD(W, 4 + 5 * i);
        mbar_wait(sb + BAR_RFULL + r.slot * 8, r.ph, r.dl);
        nb_sync<NB_PFULL + (W ^ 1), 256>();
        pv(FalseT{}, W ^ 1);
        if (W == 1) mref = __uint_as_float(lds_u(sb + OFF_GM));
        wg_wait<1>();
        reg_fence(s);
        mbar_arrive_warp<2>(sb + BAR_REMPTY + kslot * 8);
        if (W == 0) mbar_arrive_warp_if(sb + BAR_XEMPTY + 0, i == 3);
        r.adv(W == 1 && i == 3 ? 1 : 2);
        TSD(W, 5 + 5 * i);
        tail(FalseT{}, i);
    }
    if (W == 1) nx = get_item_warp(sb, it + 1, r.dl);
    if (W == 0) {
        Ring rn = r;
        rn.adv(2);
        q_ahead(q0, sb, rn, phm, IT_TYPE(nx) == IT_QA);
        TSD(W, 25);
    }
    const uint32_t w = (tid_now() >> 5) & 3;
    const uint32_t lxa = sb + OFF_LX + w * 640 + (((lane & 8) ? 80 : 0) + ((lane >> 1) & 8) + 2 * (lane & 3) + ((lane >> 2) & 1)) * 4;
    po.gp = ostash(IT_SLOT(e), IT_B(e)) + po.toff();
    po.sig = 1;
    if (W == 0) {
        sum_store<false>(l, lane, lxa);
        nb_arrive<NB_LX, 256>();
        wg_wait<1>();
        mbar_arrive_warp(sb + BAR_REMPTY + r.slot * 8);
        mbar_arrive_warp(sb + BAR_XEMPTY + 24);
        r.adv(1);
        mbar_wait(sb + BAR_RFULL + r.slot * 8, r.ph, r.dl);
        nb_sync<NB_PFULL + 1, 256>();
        pv(FalseT{}, 1);
    } else {
        nb_sync<NB_LX, 256>();
        sum_store<true>(l, lane, lxa);
        nb_arrive<NB_L, 160>();
    }
    TSD(W, 24);
    wg_wait<0>();
    reg_fence(oa);
    reg_fence(ob);
    mbar_arrive_warp(sb + BAR_REMPTY + r.slot * 8);
    mbar_arrive_warp(sb + BAR_XEMPTY + 32);
    r.adv(1);
    opack(ob, po.v + 40);
    opack(oa, po.v);
    return nx;
}

template <int W>
__device__ __forceinline__ uint32_t qa_run(uint32_t e, uint32_t sb, Ring& r, uint32_t phm, PendO& po, int& it) {
    float q0[80], oa[80];
    if (W == 0) {
        zero(oa);
        q_ahead(q0, sb, r, phm, true);
        wg_wait<0>();
    }
#pragma unroll 1
    do {
        TS(W, 0);
        if (W == 0) TS_ITEM(e);
        e = qa_item<W>(e, sb, r, phm, po, q0, oa, it);
        TS(W, 31);
        it++;
    } while (IT_TYPE(e) == IT_QA && !po.bad);
    if (W == 0) {
#pragma unroll
        for (int i = 56; i < 64; i++) po.v[i] = 0;
    }
    return e;
}

__device__ __forceinline__ void consumer(const Params& P, uint32_t W, uint32_t sb, uint32_t dl) {
    int it = 0;
    Ring r{0, 0, dl};
    uint32_t phm = 0;
    uint32_t e = get_item_warp(sb, 0, dl);
#pragma unroll 1
    while (true) {
        if (IT_TYPE(e) == IT_QA) {
            PendO po;
            po.clear();
            e = W == 0 ? qa_run<0>(e, sb, r, phm, po, it) : qa_run<1>(e, sb, r, phm, po, it);
#pragma unroll 1
            for (int m = po.bad ? 2 : 1; m > 0; m--) {
                if (m == 1) {
                    po.verdict(sb, W);
                    if (W == 0) po.flush<0>(sb);
                    else po.flush<1>(sb);
                }
                if (po.bad) {
                    if (W == 0) fallback_unit(P, lds_u(sb + OFF_ITEM + (it - m) * 4), tid_now() & 127);
                    __syncwarp();
                    nb_sync<NB_ODONE, 288>();
                }
            }
        }
        if (e == 0) break;
        if (IT_TYPE(e) == IT_QA) continue;
        TS(W, 0);
        if (W == 0) TS_ITEM(e);
        if (IT_TYPE(e) == IT_ON) on_item(P, W, e, sb, r, phm);
        else if (W == 0) op_item<true>(e, sb, r, phm);
        else op_item<false>(e, sb, r, phm);
        TS(W, 31);
        e = get_item_warp(sb, ++it, dl);
    }
    TS_DUMP(W);
}

__global__ void __cluster_dims__(2, 1, 1) __launch_bounds__(384, 1) fused_kernel(const __grid_constant__ Params P) {
    extern __shared__ __align__(1024) unsigned char smem_raw[];
    const uint32_t sb = (uint32_t)__cvta_generic_to_shared(smem_raw);
    const uint32_t warp = __shfl_sync(0xffffffffu, threadIdx.x >> 5, 0), wgid = warp >> 2;
    const uint32_t cta = blockIdx.x;
    const uint32_t dl = deadline();

    if (threadIdx.x == 128) {
#pragma unroll
        for (int i = 0; i < NSLOT; i++) {
            mbar_init(sb + BAR_RFULL + i * 8, 1);
            mbar_init(sb + BAR_REMPTY + i * 8, 8);
            mbar_init(sb + BAR_XFULL + i * 8, 1);
            mbar_init(sb + BAR_XEMPTY + i * 8, 8);
        }
        asm volatile("fence.mbarrier_init.release.cluster;" ::: "memory");
        fence_async_smem();
    } else if (threadIdx.x == 160) {
#pragma unroll
        for (int i = 0; i < NSLOT + MAXI; i++) mbar_init(sb + BAR_PRDY + i * 8, 1);
        asm volatile("fence.mbarrier_init.release.cluster;" ::: "memory");
    } else if (threadIdx.x == 0) {
        sts_u(sb + OFF_ITEM, P.cl[cta >> 1].items[0] ? P.cl[cta >> 1].items[0] + 8 * (cta & 1) : 0);
        sts_u(sb + OFF_FB, P.cl[cta >> 1].delay);
    } else if (threadIdx.x == 64) {
        if (sb & 1023) __trap();
        asm volatile("prefetch.tensormap [%0];" ::"l"(&P.wq[0]) : "memory");
        asm volatile("prefetch.tensormap [%0];" ::"l"(&P.x[0]) : "memory");
    }
    __syncthreads();
    {
        const int it = 0;
        if (wgid == 1) TS(0, 30);
    }
    asm volatile("barrier.cluster.arrive.relaxed.aligned;" ::: "memory");
    if (warp < 3) {
        const uint32_t e = __shfl_sync(0xffffffffu, lds_u(sb + OFF_ITEM), 0), d = lds_u(sb + OFF_FB);
        const uint64_t pol = pol_shared();
        const bool isx = warp == 1, lead = (threadIdx.x & 31) == 0;
        uint32_t t0, t1;
        asm volatile("mov.u32 %0, %%clock;" : "=r"(t0));
        do {
            asm volatile("mov.u32 %0, %%clock;" : "=r"(t1));
        } while (t1 - t0 < d);
        __syncwarp();
#pragma unroll 1
        for (int n = 0; n < (e ? NSLOT : 0); n++) {
            const uint32_t bar = sb + (isx ? BAR_XFULL : BAR_RFULL) + n * 8;
            if (lead) {
                if (warp < 2) mbar_expect(bar, isx ? XS : SLOT);
                tma3(sb + (isx ? OFF_R + n * XS : OFF_RING + n * SLOT + warp * (SLOT / 4)), isx ? &P.x[0] : &P.wq[0],
                     isx ? IT_B(e) * 160 : n * 64 + warp * 16, isx ? n : IT_H0(e) * 3, bar, pol);
            }
        }
        if (threadIdx.x == 0) asm volatile("mbarrier.arrive.shared::cta.b64 _, [%0];" ::"r"(sb + BAR_ITEM) : "memory");
        __syncwarp();
    }

    if (wgid == 0) {
        asm volatile("setmaxnreg.dec.sync.aligned.u32 24;");
        if (warp == 0) {
            const bool lead = threadIdx.x == 0;
            const uint64_t pol_first = pol_stream(), pol_norm = pol_shared();
            uint32_t e = __shfl_sync(0xffffffffu, lds_u(sb + OFF_ITEM), 0);
            asm volatile("barrier.cluster.wait.aligned;" ::: "memory");
            unsigned int* const ticket = &g_ticket[next_epoch(0) & 1];
            const uint32_t rank = cta & 1;
            uint32_t peer;
            asm volatile("mapa.shared::cluster.u32 %0, %1, %2;" : "=r"(peer) : "r"(sb), "r"(rank ^ 1));
            Ring r{0, 0, dl};
            uint32_t pm = 0;
            auto load_w = [&](const CUtensorMap* m, int row, int blk, uint32_t half_bytes) {
                mbar_wait(sb + BAR_REMPTY + r.slot * 8, r.ph, dl);
                if (lead) {
                    mbar_expect(sb + BAR_RFULL + r.slot * 8, 2 * half_bytes);
                    asm volatile("mbarrier.arrive.shared::cluster.b64 _, [%0];" ::"r"(peer + BAR_PRDY + r.slot * 8) : "memory");
                }
                mbar_wait(sb + BAR_PRDY + r.slot * 8, (pm >> r.slot) & 1, dl);
                pm ^= 1u << r.slot;
                if (lead) tma3_mc(sb + OFF_RING + r.slot * SLOT + rank * half_bytes, m, row, blk, sb + BAR_RFULL + r.slot * 8, pol_norm);
                r.adv(1);
            };
#pragma unroll 1
            for (int it = 0; e != 0; it++) {
                uint32_t nx = 0, tk = 0;
                if (rank == 0 && IT_TYPE(e) != IT_ON && it + 2 < MAXI) nx = it + 1 < NSTAT ? P.cl[cta >> 1].items[it + 1] : IT_DYN;
                const uint32_t br = IT_BR(e);
                if (IT_TYPE(e) == IT_QA) {
                    const uint32_t h = IT_H0(e);
#pragma unroll 1
                    for (int kk = it ? 0 : NSLOT; kk < 10; kk++) load_w(&P.wq[br], kk * 64 + rank * 32, h * 3, SLOT / 2);
                    const int grp0 = (IT_B(e) * 32 + h) * 64;
#pragma unroll 1
                    for (int n = 0; n < 16; n++) {
                        if (n == 13 && nx == IT_DYN && lead) tk = atomicAdd(ticket, 1);
                        const bool isv = n == 15 || (n > 0 && !(n & 1));
                        const int j = n == 15 ? 7 : isv ? (n - 2) >> 1 : (n + 1) >> 1;
                        mbar_wait(sb + BAR_REMPTY + r.slot * 8, r.ph, dl);
                        if (lead) {
                            mbar_expect(sb + BAR_RFULL + r.slot * 8, SLOT);
                            asm volatile(
                                "cp.async.bulk.tensor.4d.shared::cluster.global.mbarrier::complete_tx::bytes.L2::cache_hint"
                                " [%0], [%1, {%3,%3,%3,%4}], [%2], %5;" ::"r"(sb + OFF_RING + r.slot * SLOT),
                                "l"(isv ? &P.v[br] : &P.k[br]), "r"(sb + BAR_RFULL + r.slot * 8), "r"(0), "r"(grp0 + j * 8), "l"(pol_first)
                                : "memory");
                        }
                        r.adv(1);
                    }
                } else {
                    const bool wide = IT_TYPE(e) == IT_OP;
                    const int step = wide ? 32 : 64, r1 = IT_H1(e) * 192;
#pragma unroll 1
                    for (int row = IT_H0(e) * 192 + rank * (step >> 1); row < r1; row += step)
                        load_w(wide ? &P.wo[br] : &P.won[br], row, IT_HALF(e) * (wide ? 5 : 2), wide ? XS / 2 : 8192);
                    if (nx == IT_DYN && lead) tk = atomicAdd(ticket, 1);
                }
                if (rank == 0) {
                    if (nx == IT_DYN) {
                        tk = __shfl_sync(0xffffffffu, tk, 0);
                        nx = tk < P.nlist ? P.list[tk] : 0;
                    }
                    e = nx;
                    if (lead) {
                        asm volatile("st.async.weak.shared::cluster.mbarrier::complete_tx::bytes.b32 [%0], %1, [%2];" ::"r"(
                                         peer + OFF_ITEM + 4 + it * 4),
                                     "r"(e ? e + 8 : 0), "r"(peer + BAR_ITEM + 8 + it * 8)
                                     : "memory");
                        sts_u(sb + OFF_ITEM + 4 + it * 4, e);
                        asm volatile("mbarrier.arrive.shared::cta.b64 _, [%0];" ::"r"(sb + BAR_ITEM + 8 + it * 8) : "memory");
                    }
                } else {
                    if (lead) mbar_expect(sb + BAR_ITEM + 8 + it * 8, 4);
                    e = get_item_warp(sb, it + 1, dl);
                }
            }
        } else if (warp == 1) {
            const uint64_t pol_norm = pol_shared(), pol_o = pol_stream();
            const bool lead = threadIdx.x == 32;
            uint32_t phm = 0, epoch = 0;
#pragma unroll 1
            for (int it = 0;; it++) {
                const uint32_t e = get_item_warp(sb, it, dl);
                if (it == 1 || (it == 0 && e == 0)) epoch = next_epoch(1);
                if (e == 0) break;
                const uint32_t br = IT_BR(e);
                uint32_t xs = 0;
                auto acquire = [&]() {
                    mbar_wait(sb + BAR_XEMPTY + xs * 8, (phm >> xs) & 1, dl);
                    phm ^= 1u << xs;
                    if (lead) mbar_expect(sb + BAR_XFULL + xs * 8, XS);
                };
                if (IT_TYPE(e) == IT_QA) {
#pragma unroll 1
                    for (int kk = it ? 0 : 5; kk < 10; kk++) {
                        acquire();
                        if (lead) tma3(sb + OFF_R + xs * XS, &P.x[br], IT_B(e) * 160, kk, sb + BAR_XFULL + xs * 8, pol_norm);
                        if (++xs == 5) xs = 0;
                    }
                } else {
                    const unsigned int* fp = g_flag + (br * 16 + IT_B(e)) * 64 + (threadIdx.x & 31) * 2;
                    uint32_t hm = 0, pm = 0;
                    auto poll = [&](uint32_t hneed, uint32_t pneed) {
                        if ((hm & hneed) == hneed && (pm & pneed) == pneed) return;
                        uint32_t n = 0;
                        do {
                            uint32_t a, b;
                            asm volatile("ld.acquire.gpu.global.v2.u32 {%0, %1}, [%2];" : "=r"(a), "=r"(b) : "l"(fp) : "memory");
                            hm = __ballot_sync(0xffffffffu, a == epoch);
                            pm = __ballot_sync(0xffffffffu, b == epoch);
                            if (++n > 0x1000000) __trap();
                        } while ((hm & hneed) != hneed || (pm & pneed) != pneed);
                        __syncwarp();
                        asm volatile("fence.proxy.async.global;" ::: "memory");
                    };
#pragma unroll 1
                    for (uint32_t h = IT_H0(e); h < IT_H1(e); h++) {
                        const unsigned char* src = ostash(P.slot[br * 32 + h], IT_B(e));
                        poll(1u << h, 0);
#pragma unroll 1
                        for (int t = 0; t < 3; t++) {
                            acquire();
                            if (lead) bulk_load(sb + OFF_R + xs * XS, src + t * XS, XS, sb + BAR_XFULL + xs * 8, pol_o);
                            if (++xs == 5) xs = 0;
                        }
                        if (IT_TYPE(e) == IT_OP && h >= 1) {
                            const uint32_t x1 = xs == 4 ? 0 : xs + 1;
                            mbar_wait(sb + BAR_XFULL + xs * 8, (phm >> xs) & 1, dl);
                            mbar_wait(sb + BAR_XFULL + x1 * 8, (phm >> x1) & 1, dl);
                            if (lead)
                                asm volatile("red.relaxed.gpu.global.max.u32 [%0], %1;" ::"l"(fp + 5 + 2 * IT_HALF(e)), "r"(epoch * 64 + h) : "memory");
                        }
                    }
                    if (IT_TYPE(e) == IT_ON) {
                        poll(0, IT_HALF(e) < 2 ? 1 : IT_HALF(e) == 2 ? 3 : 2);
#pragma unroll 1
                        for (uint32_t tile = 2 * IT_HALF(e); tile < 2 * IT_HALF(e) + 2; tile++) {
                            acquire();
                            if (lead)
                                asm volatile(
                                    "cp.async.bulk.tensor.5d.shared::cluster.global.mbarrier::complete_tx::bytes [%0], [%1, {%3,%5,%5,%5,%4}], [%2];" ::"r"(
                                        sb + OFF_R + xs * XS),
                                    "l"(&P.out), "r"(sb + BAR_XFULL + xs * 8), "r"(br * 640 + tile * 64), "r"(IT_B(e) * 5), "r"(0)
                                    : "memory");
                            if (++xs == 5) xs = 0;
                        }
                    }
                }
            }
        } else if (warp == 2) {
            asm volatile("barrier.cluster.wait.aligned;" ::: "memory");
            const uint32_t epoch = next_epoch(2);
            if (cta == 0) g_ticket[(epoch + 1) & 1] = 0;
#pragma unroll 1
            for (int it = 0;; it++) {
                const uint32_t e = get_item_warp(sb, it, dl);
                if (e == 0) break;
                if (IT_TYPE(e) != IT_QA && threadIdx.x == 64) asm volatile("prefetch.tensormap [%0];" ::"l"(&P.out) : "memory");
                if (IT_TYPE(e) == IT_ON) break;
                nb_sync<NB_ODONE, 288>();
                if (threadIdx.x == 64) {
                    const uint32_t bb = IT_BR(e) * 16 + IT_B(e);
                    if (IT_TYPE(e) != IT_QA) {
                        asm volatile("red.relaxed.gpu.global.max.u32 [%0], %1;" ::"l"(&g_flag[bb * 64 + 5 + 2 * IT_HALF(e)]),
                                     "r"(epoch * 64 + IT_H1(e))
                                     : "memory");
#pragma unroll 1
                        for (int m = 0; m < 5; m++) {
                            out_store(P, sb + OFF_R + m * XS, IT_BR(e) * 640 + IT_HALF(e) * 320 + m * 64, IT_B(e));
                            if (m >= 1) {
                                asm volatile("cp.async.bulk.wait_group.read 1;" ::: "memory");
                                asm volatile("mbarrier.arrive.shared::cta.b64 _, [%0], 8;" ::"r"(sb + BAR_XEMPTY + (m - 1) * 8) : "memory");
                            }
                        }
                        asm volatile("cp.async.bulk.wait_group.read 0;" ::: "memory");
                        asm volatile("mbarrier.arrive.shared::cta.b64 _, [%0], 8;" ::"r"(sb + BAR_XEMPTY + 32) : "memory");
                        if (IT_PART(e)) {
                            asm volatile("cp.async.bulk.wait_group 0;" ::: "memory");
                            asm volatile("fence.proxy.async.global;" ::: "memory");
                        }
                    }
                    if (IT_TYPE(e) == IT_QA || IT_PART(e)) {
                        unsigned int* f = &g_flag[bb * 64 + (IT_TYPE(e) == IT_QA ? 2 * IT_H0(e) : 1 + 2 * IT_HALF(e))];
                        asm volatile("st.release.gpu.global.u32 [%0], %1;" ::"l"(f), "r"(epoch) : "memory");
                    }
                }
                __syncwarp();
            }
            if (threadIdx.x == 64) asm volatile("cp.async.bulk.wait_group 0;" ::: "memory");
            __syncwarp();
            asm volatile("barrier.cluster.arrive.relaxed.aligned;\nbarrier.cluster.wait.aligned;" ::: "memory");
        } else {
            const uint32_t lane = threadIdx.x & 31, p = lane >> 3;
            const uint32_t epoch = next_epoch(3);
#pragma unroll 1
            for (int it = 0;; it++) {
                const uint32_t e = get_item_warp(sb, it, dl);
                if (e == 0) break;
                if (IT_TYPE(e) != IT_QA) continue;
                nb_sync<NB_QK, 160>();
                const uint32_t ka = sb + OFF_RING + lds_u(sb + OFF_GM + 4) * SLOT + p * (2 * 3072 + 256) + (lane & 7) * 16;
                const uint32_t qa = sb + OFF_R + p * 256 + (lane & 7) * 16;
                uint32_t acc = 0;
#pragma unroll 1
                for (int c = 0; c < 3; c++) {
                    const uint4 k = lds_u4(ka + c * 1024);
                    if (c == 2) nb_sync<NB_L, 160>();
                    const uint4 q = lds_u4(qa + c * XS);
                    acc = fma_bf2(k.x, q.x, fma_bf2(k.y, q.y, fma_bf2(k.z, q.z, fma_bf2(k.w, q.w, acc))));
                }
                const float d = __uint_as_float(acc << 16) + __uint_as_float(acc & 0xffff0000u);
                const int sum = __reduce_add_sync(0xffffffffu, __float2int_rn(d * 16.f));
                sts_f(sb + OFF_GM, fmaf((float)sum, SM_C / 64.f, 24.f));
                nb_arrive<NB_REF, 160>();
                if (IT_DEP(e)) {
                    const uint32_t g = IT_DEP(e) - 1, need = epoch * 64 + (g & 31) + 1;
                    const unsigned int* cp = &g_flag[((g >> 5) * 16 + IT_B(e)) * 64 + 5 + 2 * (lane & 1)];
                    for (uint32_t n = 0;; n++) {
                        uint32_t v;
                        asm volatile("ld.acquire.gpu.global.u32 %0, [%1];" : "=r"(v) : "l"(cp) : "memory");
                        if (__all_sync(0xffffffffu, v - need < 64)) break;
                        if (n > 0x800000) __trap();
                        __nanosleep(500);
                    }
                }
                nb_sync<NB_L, 160>();
                bool bad = false;
#pragma unroll
                for (int c = 0; c < 5; c++) {
                    const uint32_t la = sb + OFF_LX + (c * 32 + lane) * 4;
                    const float v = (__uint_as_float(lds_u(la)) + __uint_as_float(lds_u(la + 640))) +
                                    (__uint_as_float(lds_u(la + 1280)) + __uint_as_float(lds_u(la + 1920)));
                    const float inv = __fdividef(1.f, v);
                    const uint32_t hi = pack_bf16(inv, 0.f), lo = pack_bf16(inv - __uint_as_float(hi << 16), 0.f);
                    const uint32_t ia = sb + OFF_LINV + c * 128 + ((lane >> 1) & 3) * 32 + (lane >> 3) * 8 + (lane & 1) * 2;
                    asm volatile("st.shared.u16 [%0], %1;\nst.shared.u16 [%0+4], %2;" ::"r"(ia), "h"((unsigned short)hi), "h"((unsigned short)lo) : "memory");
                    bad |= !(v >= 5.421010862e-20f && v <= 7.9228163e28f);
                }
                sts_u(sb + OFF_FB, __any_sync(0xffffffffu, bad));
                nb_arrive<NB_VOTE, 160>();
                nb_arrive<NB_VOTE + 1, 160>();
            }
        }
    } else {
        asm volatile("setmaxnreg.inc.sync.aligned.u32 240;");
        consumer(P, wgid - 1, sb, dl);
    }
}

typedef CUresult (*EncFn)(CUtensorMap*, CUtensorMapDataType, cuuint32_t, void*, const cuuint64_t*, const cuuint64_t*,
                          const cuuint32_t*, const cuuint32_t*, CUtensorMapInterleave, CUtensorMapSwizzle,
                          CUtensorMapL2promotion, CUtensorMapFloatOOBfill);

void make_map3(EncFn enc, CUtensorMap* m, void* p, uint64_t rows, uint64_t rowbytes, uint64_t nblk, uint32_t boxrows,
               uint32_t boxblk) {
    cuuint64_t dims[3] = {64, rows, nblk};
    cuuint64_t str[2] = {rowbytes, 128};
    cuuint32_t box[3] = {64, boxrows, boxblk};
    cuuint32_t es[3] = {1, 1, 1};
    enc(m, CU_TENSOR_MAP_DATA_TYPE_BFLOAT16, 3, p, dims, str, box, es, CU_TENSOR_MAP_INTERLEAVE_NONE,
        CU_TENSOR_MAP_SWIZZLE_128B, CU_TENSOR_MAP_L2_PROMOTION_NONE, CU_TENSOR_MAP_FLOAT_OOB_FILL_NONE);
}

constexpr int tune(const char*, int def) { return def; }

void build_schedule(Params& P, int ncl) {
    const int mode = tune("MODE", 4), dmax = tune("DMAX", 24200), n0 = tune("N0", 10);
    const int H0[8] = {19, 20, 21, 22, 22, 24, 25, 25}, P0[8] = {367, 337, 335, 331, 338, 335, 333, 332};
    const int ra = tune("RA", 10), ga = tune("GA", 17), rb = tune("RB", 11), g1 = tune("G1", 58);
    int dep[64];
    for (int g = 0, ns = 0, live = 0; g < 64; g++) {
        const bool fresh = mode < 3 || g >= g1 || live < (g < ga ? ra : rb);
        dep[g] = fresh ? 0 : g - live + 1;
        P.slot[g] = fresh ? ns++ : P.slot[g - live];
        live += fresh;
    }
    int H[8], pos[8], psum = 0;
    for (int b = 0; b < 8; b++) {
        const char nh[3] = {'H', (char)('0' + b), 0}, np[3] = {'P', (char)('0' + b), 0};
        H[b] = tune(nh, H0[b]);
        pos[b] = tune(np, P0[b]);
        psum += pos[b];
    }
    const int sk = tune("SK", 10), g0 = tune("G0", 20), g2 = tune("G2", 40);
    int ord[512], nxt[8] = {0, 0, 0, 0, 0, 0, 0, 0};
    for (int k = 0; k < 512; k++) {
        int best = -1;
        float bkey = 0.f;
        for (int b = 0; b < 8; b++) {
            const int g = nxt[b];
            if (g == 64) continue;
            const float w = g < g0 ? 0.f : g < 32 ? (g - g0) / (32.f - g0) : g < g2 ? 1.f : (64 - g) / (64.f - g2);
            const float key = g + w * sk * 0.1f * (pos[b] - psum / 8.f) / 8.f;
            if (best < 0 || key < bkey) best = b, bkey = key;
        }
        ord[k] = nxt[best]++ * 8 + best;
        const int d = dep[ord[k] >> 3];
        if (d > 32) {
            if (pos[best] > k) pos[best] = k;
            if (H[best] < d - 32) H[best] = d - 32;
        }
    }
    int u = 0;
    auto unit = [&]() {
        const int v = ord[u++];
        return mk_item(IT_QA, v >> 8, (v & 7) * 2, (v >> 3) & 31, P.slot[v >> 3], 0) | (dep[v >> 3] << 23);
    };
    int qa[NCL], nq = 0, op[NCL], no = 0;
    for (int c = 0; c < ncl; c++) {
        P.cl[c].delay = 0;
        for (int i = 0; i < NSTAT; i++) P.cl[c].items[i] = 0;
        if (mode >= 3 && c >= 4 && c < 20) op[((c - 4) & 7) * 2 + ((c - 4) >> 3)] = c, no++;
        else if (mode != 2 || (c & 3) == 0) qa[nq++] = c;
    }
    for (int t = 0; t < no; t++) {
        P.cl[op[t]].items[1] = mk_item(IT_OP, 0, t & ~1, 0, 32, t & 1);
        P.cl[op[t]].items[2] = IT_DYN;
            }
    for (int k = 0; k < nq; k++) {
        const int c = qa[(k * (nq % 19 ? 19 : 17)) % nq];
        P.cl[c].items[1] = P.cl[c].items[2] = IT_DYN;
        P.cl[c].delay = k < n0 ? 0 : dmax * (k + 1 - n0) / (nq - n0);
    }
    for (int t = 0; t < no && tune("OF", 1); t++) P.cl[op[(t & 7) * 2 + (t >> 3)]].items[0] = unit();
    for (int k = u; k < no + nq; k++) {
        int best = -1;
        for (int c = 0; c < ncl; c++)
            if (P.cl[c].items[1] && !P.cl[c].items[0] && (best < 0 || P.cl[c].delay < P.cl[best].delay)) best = c;
        P.cl[best].items[0] = unit();
    }
    int n = 0;
    const int uend = mode == 2 ? 8 * nq : 512;
    while (u < uend) {
        for (int b = 0; b < 8 && no; b++)
            if (pos[b] == u) {
                P.list[n++] = mk_item(IT_OP, 1, 2 * b, 0, H[b], 0, 1);
                P.list[n++] = mk_item(IT_OP, 1, 2 * b, 0, H[b], 1, 1);
            }
        P.list[n++] = unit();
    }
    for (int k = 0; no && k < 40; k++) P.list[n++] = mk_item(IT_ON, 1, k / 5 * 2, H[k / 5], 32, k % 5);
    P.nlist = n;
}

}

extern "C" void kernel_launch(void* const* d_in, const int* in_sizes, int n_in, void* d_out, int out_size) {
    static Params P;
    static bool init = false;
    static int ncl = NCL;
    if (!init) {
        EncFn enc = nullptr;
        cudaDriverEntryPointQueryResult qr;
        cudaGetDriverEntryPoint("cuTensorMapEncodeTiled", (void**)&enc, cudaEnableDefault, &qr);
        for (int i = 0; i < 2; i++) {
            P.px[i] = (const __nv_bfloat16*)d_in[5 * i + 0];
            P.pk[i] = (const __nv_bfloat16*)d_in[5 * i + 1];
            P.pv[i] = (const __nv_bfloat16*)d_in[5 * i + 2];
            P.pwq[i] = (const __nv_bfloat16*)d_in[5 * i + 3];
            make_map3(enc, &P.x[i], d_in[5 * i + 0], 2560, 1280, 10, 160, 1);
            for (int j = 0; j < 2; j++) {
                cuuint64_t dims[4] = {64, 8, 3, 16 * 32 * 64};
                cuuint64_t str[3] = {384, 128, 3072};
                cuuint32_t box[4] = {64, 8, 3, 8};
                cuuint32_t es[4] = {1, 1, 1, 1};
                enc(j ? &P.v[i] : &P.k[i], CU_TENSOR_MAP_DATA_TYPE_BFLOAT16, 4, d_in[5 * i + 1 + j], dims, str, box, es,
                    CU_TENSOR_MAP_INTERLEAVE_NONE, CU_TENSOR_MAP_SWIZZLE_128B, CU_TENSOR_MAP_L2_PROMOTION_NONE,
                    CU_TENSOR_MAP_FLOAT_OOB_FILL_NONE);
            }
            make_map3(enc, &P.wq[i], d_in[5 * i + 3], 640, 12288, 96, 32, 3);
            make_map3(enc, &P.wo[i], d_in[5 * i + 4], 6144, 1280, 10, 16, 5);
            make_map3(enc, &P.won[i], d_in[5 * i + 4], 6144, 1280, 10, 32, 2);
        }
        cuuint64_t dims[5] = {1280, 2, 4, 4, 80};
        cuuint64_t str[4] = {2560, 8 * 2560, 2 * 2560, 32 * 2560};
        cuuint32_t box[5] = {64, 2, 4, 4, 5};
        cuuint32_t es[5] = {1, 1, 1, 1, 1};
        enc(&P.out, CU_TENSOR_MAP_DATA_TYPE_BFLOAT16, 5, d_out, dims, str, box, es, CU_TENSOR_MAP_INTERLEAVE_NONE,
            CU_TENSOR_MAP_SWIZZLE_128B, CU_TENSOR_MAP_L2_PROMOTION_NONE, CU_TENSOR_MAP_FLOAT_OOB_FILL_NONE);
        cudaFuncSetAttribute(fused_kernel, cudaFuncAttributeMaxDynamicSharedMemorySize, SMEM_LAUNCH);
        cudaLaunchConfig_t cfg = {};
        cfg.gridDim = dim3(NCTA);
        cfg.blockDim = dim3(384);
        cfg.dynamicSmemBytes = SMEM_LAUNCH;
        int nc = 0;
        if (cudaOccupancyMaxActiveClusters(&nc, fused_kernel, &cfg) == cudaSuccess && nc >= 52 && nc < NCL) ncl = nc;
        (void)cudaGetLastError();
        ncl = tune("NCL", ncl);
        build_schedule(P, ncl);
        init = true;
    }
    fused_kernel<<<2 * ncl, 384, SMEM_LAUNCH>>>(P);
}
```

```cpp
#include <cuda_runtime.h>
#include <cuda.h>
#include <cuda_bf16.h>
#include <stdint.h>

namespace {

constexpr int NCTA = 132;
constexpr int NCL = NCTA / 2;
constexpr int MAXI = 16;
constexpr int NSTAT = 3;
constexpr uint32_t IT_DYN = 0xffffffffu;
constexpr int SLOT = 24576;
constexpr int NSLOT = 5;
constexpr int XS = 20480;
constexpr int OFF_R = 0;
constexpr int OFF_RING = 5 * XS;
constexpr int OFF_MISC = OFF_RING + NSLOT * SLOT;
constexpr int OFF_LX = OFF_MISC;
constexpr int OFF_LINV = OFF_LX + 2560;
constexpr int OFF_FB = OFF_LINV + 640;
constexpr int OFF_GM = OFF_FB + 16;
constexpr int OFF_BAR = OFF_GM + 16;
constexpr int BAR_RFULL = OFF_BAR;
constexpr int BAR_REMPTY = BAR_RFULL + 40;
constexpr int BAR_XFULL = BAR_REMPTY + 40;
constexpr int BAR_XEMPTY = BAR_XFULL + 40;
constexpr int BAR_PRDY = BAR_XEMPTY + 40;
constexpr int BAR_ITEM = BAR_PRDY + 40;
constexpr int OFF_ITEM = BAR_ITEM + MAXI * 8;
constexpr int SMEM_BYTES = OFF_ITEM + MAXI * 4;
static_assert(SMEM_BYTES <= 232448, "smem");

constexpr int NB_W = 1  , NB_PFULL = 3  , NB_VOTE = 5  , NB_Q2 = 7, NB_SDONE = 8, NB_PDONE = 9,
              NB_L = 10, NB_REF = 11, NB_ODONE = 12, NB_OPEND = 13, NB_LX = 14, NB_Q01 = 15, NB_QK = 0  ;

constexpr uint32_t IT_QA = 1, IT_OP = 2, IT_ON = 3;
__host__ __device__ constexpr uint32_t mk_item(uint32_t type, uint32_t br, uint32_t b, uint32_t h0, uint32_t h1, uint32_t half,
                                               uint32_t part = 0) {
    return type | (br << 2) | (b << 3) | (h0 << 7) | (h1 << 13) | (half << 19) | (part << 22);
}
#define IT_TYPE(e) ((e) & 3u)
#define IT_BR(e) (((e) >> 2) & 1u)
#define IT_B(e) (((e) >> 3) & 15u)
#define IT_H0(e) (((e) >> 7) & 63u)
#define IT_H1(e) (((e) >> 13) & 63u)
#define IT_HALF(e) (((e) >> 19) & 7u)
#define IT_PART(e) (((e) >> 22) & 1u)
#define IT_SLOT(e) IT_H1(e)
#define IT_DEP(e) (((e) >> 23) & 127u)

struct Params {
    CUtensorMap x[2], wq[2], k[2], v[2], wo[2], won[2], out;
    const __nv_bfloat16 *px[2], *pwq[2], *pk[2], *pv[2];
    struct alignas(16) { uint32_t delay, items[NSTAT]; } cl[NCL];
    uint32_t nlist;
    uint8_t slot[64];
    uint32_t list[568];
};

constexpr int OUNIT = 61440;
__device__ __align__(1024) unsigned char g_ostash[(size_t)1024 * OUNIT];
__device__ __align__(256) unsigned int g_flag[32 * 64];
__device__ __forceinline__ unsigned char* ostash(uint32_t slot, uint32_t b) { return g_ostash + (slot * 16 + b) * OUNIT; }
__device__ unsigned int g_epoch[NCTA * 4];
__device__ unsigned int g_ticket[2];

constexpr int SMEM_LAUNCH = SMEM_BYTES;
#define TS(role, idx)
#define TS_ITEM(e)
#define TS_DUMP(role)
#define TSD(role, idx)

__device__ __forceinline__ uint64_t pol_stream() {
    uint64_t p;
    asm volatile("createpolicy.fractional.L2::evict_first.b64 %0, 1.0;" : "=l"(p));
    return p;
}
__device__ __forceinline__ uint64_t pol_shared() {
    uint64_t p;
    asm volatile("createpolicy.fractional.L2::evict_unchanged.b64 %0, 1.0;" : "=l"(p));
    return p;
}
constexpr int QHOLD = 8;
constexpr float SM_C = 0.07216878364870322f * 1.4426950408889634f;

__device__ __forceinline__ uint32_t next_epoch(int warp) {
    unsigned int* p = &g_epoch[blockIdx.x * 4 + warp];
    const uint32_t e = __ldcg(p) + 1;
    *p = e;
    return e;
}

__device__ __forceinline__ uint32_t tid_now() {
    uint32_t t;
    asm volatile("mov.u32 %0, %%tid.x;" : "=r"(t));
    return t;
}
__device__ __forceinline__ void mbar_init(uint32_t a, uint32_t c) {
    asm volatile("mbarrier.init.shared::cta.b64 [%0], %1;" ::"r"(a), "r"(c) : "memory");
}
__device__ __forceinline__ void mbar_expect(uint32_t a, uint32_t b) {
    asm volatile("mbarrier.arrive.expect_tx.shared::cta.b64 _, [%0], %1;" ::"r"(a), "r"(b) : "memory");
}
template <int CNT = 1>
__device__ __forceinline__ void mbar_arrive_warp(uint32_t a) {
    if (CNT == 1)
        asm volatile("{\n.reg .pred p;\nelect.sync _|p, 0xffffffff;\n@p mbarrier.arrive.shared::cta.b64 _, [%0];\n}" ::"r"(a) : "memory");
    else
        asm volatile(
            "{\n.reg .pred p;\nelect.sync _|p, 0xffffffff;\n@p mbarrier.arrive.shared::cta.b64 _, [%0];\n"
            "@p mbarrier.arrive.shared::cta.b64 _, [%0];\n}" ::"r"(a)
            : "memory");
}
template <int CNT = 1>
__device__ __forceinline__ void mbar_arrive_warp_if(uint32_t a, bool cond) {
    if (CNT == 1)
        asm volatile(
            "{\n.reg .pred p, c;\nelect.sync _|p, 0xffffffff;\nsetp.ne.and.u32 c, %1, 0, p;\n"
            "@c mbarrier.arrive.shared::cta.b64 _, [%0];\n}" ::"r"(a), "r"((uint32_t)cond)
            : "memory");
    else
        asm volatile(
            "{\n.reg .pred p, c;\nelect.sync _|p, 0xffffffff;\nsetp.ne.and.u32 c, %1, 0, p;\n"
            "@c mbarrier.arrive.shared::cta.b64 _, [%0];\n@c mbarrier.arrive.shared::cta.b64 _, [%0];\n}" ::"r"(a), "r"((uint32_t)cond)
            : "memory");
}
__device__ __forceinline__ uint32_t deadline() {
    uint32_t c;
    asm volatile("mov.u32 %0, %%clock_hi;" : "=r"(c));
    return c + 4;
}
__device__ __forceinline__ void mbar_wait(uint32_t a, uint32_t ph, uint32_t dl) {
    asm volatile(
        "{\n.reg .pred p;\n.reg .u32 m;\n"
        "LOOP:\n"
        "mbarrier.try_wait.parity.shared::cta.b64 p, [%0], %1;\n"
        "@p bra DONE;\n"
        "mov.u32 m, %%clock_hi;\n"
        "setp.ne.u32 p, m, %2;\n"
        "@p bra LOOP;\n"
        "trap;\n"
        "DONE:\n}" ::"r"(a), "r"(ph), "r"(dl)
        : "memory");
}
__device__ __forceinline__ void mbar_wait2(uint32_t a, uint32_t pa, uint32_t b, uint32_t pb, uint32_t dl) {
    asm volatile(
        "{\n.reg .pred p, q;\n.reg .u32 m;\n"
        "LOOP:\n"
        "mbarrier.try_wait.parity.shared::cta.b64 p, [%0], %1;\n"
        "mbarrier.try_wait.parity.shared::cta.b64 q, [%2], %3;\n"
        "and.pred p, p, q;\n"
        "@p bra DONE;\n"
        "mov.u32 m, %%clock_hi;\n"
        "setp.ne.u32 p, m, %4;\n"
        "@p bra LOOP;\n"
        "trap;\n"
        "DONE:\n}" ::"r"(a), "r"(pa), "r"(b), "r"(pb), "r"(dl)
        : "memory");
}
template <int ID, int CNT>
__device__ __forceinline__ void nb_sync() { asm volatile("bar.sync %0, %1;" ::"n"(ID), "n"(CNT) : "memory"); }
template <int ID, int CNT>
__device__ __forceinline__ void nb_arrive() { asm volatile("bar.arrive %0, %1;" ::"n"(ID), "n"(CNT) : "memory"); }
__device__ __forceinline__ void fence_async_smem() { asm volatile("fence.proxy.async.shared::cta;" ::: "memory"); }

__device__ __forceinline__ void tma3(uint32_t dst, const CUtensorMap* m, int c1, int c2, uint32_t bar, uint64_t pol) {
    asm volatile(
        "cp.async.bulk.tensor.3d.shared::cluster.global.mbarrier::complete_tx::bytes.L2::cache_hint [%0], [%1, {%3,%4,%5}], [%2], %6;" ::"r"(dst),
        "l"(m), "r"(bar), "r"(0), "r"(c1), "r"(c2), "l"(pol)
        : "memory");
}
__device__ __forceinline__ void tma3_mc(uint32_t dst, const CUtensorMap* m, int c1, int c2, uint32_t bar, uint64_t pol) {
    asm volatile(
        "cp.async.bulk.tensor.3d.shared::cluster.global.mbarrier::complete_tx::bytes.multicast::cluster.L2::cache_hint"
        " [%0], [%1, {%3,%4,%5}], [%2], %6, %7;" ::"r"(dst),
        "l"(m), "r"(bar), "r"(0), "r"(c1), "r"(c2), "h"((unsigned short)3), "l"(pol)
        : "memory");
}
__device__ __forceinline__ void bulk_load(uint32_t dst, const void* src, uint32_t bytes, uint32_t bar, uint64_t pol) {
    asm volatile("cp.async.bulk.shared::cluster.global.mbarrier::complete_tx::bytes.L2::cache_hint [%0], [%1], %2, [%3], %4;" ::"r"(dst),
                 "l"(src), "r"(bytes), "r"(bar), "l"(pol)
                 : "memory");
}
__device__ __forceinline__ void wg_fence() { asm volatile("wgmma.fence.sync.aligned;" ::: "memory"); }
__device__ __forceinline__ void wg_commit() { asm volatile("wgmma.commit_group.sync.aligned;" ::: "memory"); }
template <int N>
__device__ __forceinline__ void wg_wait() { asm volatile("wgmma.wait_group.sync.aligned %0;" ::"n"(N) : "memory"); }

#define RW80(c, d) c(d[0]), c(d[1]), c(d[2]), c(d[3]), c(d[4]), c(d[5]), c(d[6]), c(d[7]), c(d[8]), c(d[9]), c(d[10]), c(d[11]), c(d[12]), c(d[13]), c(d[14]), c(d[15]), c(d[16]), c(d[17]), c(d[18]), c(d[19]), c(d[20]), c(d[21]), c(d[22]), c(d[23]), c(d[24]), c(d[25]), c(d[26]), c(d[27]), c(d[28]), c(d[29]), c(d[30]), c(d[31]), c(d[32]), c(d[33]), c(d[34]), c(d[35]), c(d[36]), c(d[37]), c(d[38]), c(d[39]), c(d[40]), c(d[41]), c(d[42]), c(d[43]), c(d[44]), c(d[45]), c(d[46]), c(d[47]), c(d[48]), c(d[49]), c(d[50]), c(d[51]), c(d[52]), c(d[53]), c(d[54]), c(d[55]), c(d[56]), c(d[57]), c(d[58]), c(d[59]), c(d[60]), c(d[61]), c(d[62]), c(d[63]), c(d[64]), c(d[65]), c(d[66]), c(d[67]), c(d[68]), c(d[69]), c(d[70]), c(d[71]), c(d[72]), c(d[73]), c(d[74]), c(d[75]), c(d[76]), c(d[77]), c(d[78]), c(d[79])
#define RW48(c, d) c(d[0]), c(d[1]), c(d[2]), c(d[3]), c(d[4]), c(d[5]), c(d[6]), c(d[7]), c(d[8]), c(d[9]), c(d[10]), c(d[11]), c(d[12]), c(d[13]), c(d[14]), c(d[15]), c(d[16]), c(d[17]), c(d[18]), c(d[19]), c(d[20]), c(d[21]), c(d[22]), c(d[23]), c(d[24]), c(d[25]), c(d[26]), c(d[27]), c(d[28]), c(d[29]), c(d[30]), c(d[31]), c(d[32]), c(d[33]), c(d[34]), c(d[35]), c(d[36]), c(d[37]), c(d[38]), c(d[39]), c(d[40]), c(d[41]), c(d[42]), c(d[43]), c(d[44]), c(d[45]), c(d[46]), c(d[47])
#define RW32(c, d) c(d[0]), c(d[1]), c(d[2]), c(d[3]), c(d[4]), c(d[5]), c(d[6]), c(d[7]), c(d[8]), c(d[9]), c(d[10]), c(d[11]), c(d[12]), c(d[13]), c(d[14]), c(d[15]), c(d[16]), c(d[17]), c(d[18]), c(d[19]), c(d[20]), c(d[21]), c(d[22]), c(d[23]), c(d[24]), c(d[25]), c(d[26]), c(d[27]), c(d[28]), c(d[29]), c(d[30]), c(d[31])

__device__ __forceinline__ void reg_fence(float (&d)[80]) { asm volatile("" : RW80("+f", d)::"memory"); }
__device__ __forceinline__ void reg_fence(float (&d)[48]) { asm volatile("" : RW48("+f", d)::"memory"); }
__device__ __forceinline__ void reg_fence(float (&d)[32]) { asm volatile("" : RW32("+f", d)::"memory"); }

template <int NR>
__device__ __forceinline__ void zero(float (&d)[NR]) {
#pragma unroll
    for (int i = 0; i < NR; i++) d[i] = 0.f;
}

constexpr uint32_t HI_SW128 = (1024u >> 4) | (1u << 30);
constexpr uint32_t HI_KV = (3072u >> 4) | (1u << 30);
constexpr uint32_t HI_OST = (2560u >> 4) | (2u << 30);
constexpr uint32_t LO_LBO1 = (1u << 16);
constexpr uint32_t LO_OST = ((512u >> 4) << 16);

template <int TA, int TB, uint32_t HIB, int ACC, uint32_t HIA = HI_SW128>
__device__ __forceinline__ void wgmma(float (&d)[80], uint32_t loA, uint32_t loB) {
#define WG_ASM(SD)                                                          \
    "{\n.reg .b64 da, db;\nmov.b64 da, {%80, %82};\nmov.b64 db, {%81, %83};\n" \
    "wgmma.mma_async.sync.aligned.m64n160k16.f32.bf16.bf16 "               \
    "{%0,%1,%2,%3,%4,%5,%6,%7,%8,%9,%10,%11,%12,%13,%14,%15,%16,%17,%18,%19,%20,%21,%22,%23,%24,%25,%26,%27,%28,%29,%30,%31,%32,%33,%34,%35,%36,%37,%38,%39,%40,%41,%42,%43,%44,%45,%46,%47,%48,%49,%50,%51,%52,%53,%54,%55,%56,%57,%58,%59,%60,%61,%62,%63,%64,%65,%66,%67,%68,%69,%70,%71,%72,%73,%74,%75,%76,%77,%78,%79}, da, db, " SD ", 1, 1, %84, %85;\n}"
    if constexpr (ACC == 2)
        asm volatile(WG_ASM("0") : RW80("+f", d) : "r"(loA), "r"(loB), "n"(HIA), "n"(HIB), "n"(TA), "n"(TB));
    else if constexpr (ACC == 1)
        asm volatile(WG_ASM("1") : RW80("+f", d) : "r"(loA), "r"(loB), "n"(HIA), "n"(HIB), "n"(TA), "n"(TB));
    else
        asm volatile(WG_ASM("0") : RW80("=f", d) : "r"(loA), "r"(loB), "n"(HIA), "n"(HIB), "n"(TA), "n"(TB));
#undef WG_ASM
}
template <int TA, int TB, uint32_t HIB, int ACC, uint32_t HIA = HI_SW128>
__device__ __forceinline__ void wgmma(float (&d)[48], uint32_t loA, uint32_t loB) {
#define WG_ASM(SD)                                                          \
    "{\n.reg .b64 da, db;\nmov.b64 da, {%48, %50};\nmov.b64 db, {%49, %51};\n" \
    "wgmma.mma_async.sync.aligned.m64n96k16.f32.bf16.bf16 "               \
    "{%0,%1,%2,%3,%4,%5,%6,%7,%8,%9,%10,%11,%12,%13,%14,%15,%16,%17,%18,%19,%20,%21,%22,%23,%24,%25,%26,%27,%28,%29,%30,%31,%32,%33,%34,%35,%36,%37,%38,%39,%40,%41,%42,%43,%44,%45,%46,%47}, da, db, " SD ", 1, 1, %52, %53;\n}"
    if constexpr (ACC == 1)
        asm volatile(WG_ASM("1") : RW48("+f", d) : "r"(loA), "r"(loB), "n"(HIA), "n"(HIB), "n"(TA), "n"(TB));
    else
        asm volatile(WG_ASM("0") : RW48("=f", d) : "r"(loA), "r"(loB), "n"(HIA), "n"(HIB), "n"(TA), "n"(TB));
#undef WG_ASM
}
template <int TA, int TB, uint32_t HIB, int ACC, uint32_t HIA = HI_SW128>
__device__ __forceinline__ void wgmma(float (&d)[32], uint32_t loA, uint32_t loB) {
#define WG_ASM(SD)                                                          \
    "{\n.reg .b64 da, db;\nmov.b64 da, {%32, %34};\nmov.b64 db, {%33, %35};\n" \
    "wgmma.mma_async.sync.aligned.m64n64k16.f32.bf16.bf16 "               \
    "{%0,%1,%2,%3,%4,%5,%6,%7,%8,%9,%10,%11,%12,%13,%14,%15,%16,%17,%18,%19,%20,%21,%22,%23,%24,%25,%26,%27,%28,%29,%30,%31}, da, db, " SD ", 1, 1, %36, %37;\n}"
    if constexpr (ACC == 1)
        asm volatile(WG_ASM("1") : RW32("+f", d) : "r"(loA), "r"(loB), "n"(HIA), "n"(HIB), "n"(TA), "n"(TB));
    else
        asm volatile(WG_ASM("0") : RW32("=f", d) : "r"(loA), "r"(loB), "n"(HIA), "n"(HIB), "n"(TA), "n"(TB));
#undef WG_ASM
}

__device__ __forceinline__ uint32_t pack_bf16(float lo, float hi) {
    uint32_t r;
    asm("cvt.rn.bf16x2.f32 %0, %1, %2;" : "=r"(r) : "f"(hi), "f"(lo));
    return r;
}
__device__ __forceinline__ float ex2(float x) {
    float r;
    asm("ex2.approx.ftz.f32 %0, %1;" : "=f"(r) : "f"(x));
    return r;
}
__device__ __forceinline__ void stsm4t(uint32_t a, uint32_t r0, uint32_t r1, uint32_t r2, uint32_t r3) {
    asm volatile("stmatrix.sync.aligned.m8n8.x4.trans.shared.b16 [%0], {%1,%2,%3,%4};" ::"r"(a), "r"(r0), "r"(r1), "r"(r2), "r"(r3)
                 : "memory");
}
__device__ __forceinline__ uint32_t lds_u(uint32_t a) {
    uint32_t v;
    asm volatile("ld.shared.u32 %0, [%1];" : "=r"(v) : "r"(a) : "memory");
    return v;
}
__device__ __forceinline__ uint4 lds_u4(uint32_t a) {
    uint4 v;
    asm volatile("ld.shared.v4.u32 {%0,%1,%2,%3}, [%4];" : "=r"(v.x), "=r"(v.y), "=r"(v.z), "=r"(v.w) : "r"(a) : "memory");
    return v;
}
__device__ __forceinline__ float2 lds_f2(uint32_t a) {
    float2 v;
    asm volatile("ld.shared.v2.f32 {%0,%1}, [%2];" : "=f"(v.x), "=f"(v.y) : "r"(a) : "memory");
    return v;
}
__device__ __forceinline__ void sts_f(uint32_t a, float v) { asm volatile("st.shared.f32 [%0], %1;" ::"r"(a), "f"(v) : "memory"); }
__device__ __forceinline__ void sts_u(uint32_t a, uint32_t v) { asm volatile("st.shared.u32 [%0], %1;" ::"r"(a), "r"(v) : "memory"); }
__device__ __forceinline__ void sts_f2(uint32_t a, float x, float y) {
    asm volatile("st.shared.v2.f32 [%0], {%1,%2};" ::"r"(a), "f"(x), "f"(y) : "memory");
}

template <bool SIG = false, int NR>
__device__ __forceinline__ void store_tile_t(const float (&d)[NR], uint32_t addr) {
#pragma unroll
    for (int j = 0; j < NR / 8; j++) {
        stsm4t(addr + j * 2048, pack_bf16(d[8 * j], d[8 * j + 1]), pack_bf16(d[8 * j + 2], d[8 * j + 3]),
               pack_bf16(d[8 * j + 4], d[8 * j + 5]), pack_bf16(d[8 * j + 6], d[8 * j + 7]));
        if (SIG && j == 0) nb_arrive<NB_L, 160>();
    }
}

struct TrueT { static constexpr bool value = true; };
struct FalseT { static constexpr bool value = false; };

template <int V>
struct IntT { static constexpr int value = V; };

__device__ __forceinline__ uint32_t get_item(uint32_t sb, int it, uint32_t dl) {
    mbar_wait(sb + BAR_ITEM + it * 8, 0, dl);
    return lds_u(sb + OFF_ITEM + it * 4);
}
__device__ __forceinline__ uint32_t get_item_warp(uint32_t sb, int it, uint32_t dl) {
    return __shfl_sync(0xffffffffu, get_item(sb, it, dl), 0);
}

struct Ring {
    uint32_t slot, ph, dl;
    __device__ __forceinline__ void adv(uint32_t k) {
        slot += k;
        if (slot >= NSLOT) { slot -= NSLOT; ph ^= 1; }
    }
};

template <int K>
__device__ __forceinline__ void qk_step(float (&s)[80], uint32_t loK, uint32_t loQ) {
    wgmma<0, 0, HI_SW128, K != 0, HI_KV>(s, loK + (K >> 2) * 64 + (K & 3) * 2, loQ + (K >> 2) * (XS >> 4) + (K & 3) * 2);
}
template <int K0, int K1>
__device__ __forceinline__ void qk_steps(float (&s)[80], uint32_t loK, uint32_t loQ) {
    if constexpr (K0 < K1) {
        qk_step<K0>(s, loK, loQ);
        qk_steps<K0 + 1, K1>(s, loK, loQ);
    }
}
__device__ __forceinline__ uint32_t add_bf2(uint32_t a, uint32_t b) {
    uint32_t r;
    asm("add.rn.bf16x2 %0, %1, %2;" : "=r"(r) : "r"(a), "r"(b));
    return r;
}
__device__ __forceinline__ uint32_t fma_bf2(uint32_t a, uint32_t b, uint32_t c) {
    uint32_t r;
    asm("fma.rn.bf16x2 %0, %1, %2, %3;" : "=r"(r) : "r"(a), "r"(b), "r"(c));
    return r;
}
template <int J>
__device__ __forceinline__ void exp_block(const float (&s)[80], uint32_t (&k)[40], uint32_t pa, float mref) {
    if constexpr (J < 10) {
#pragma unroll
        for (int i = 4 * J; i < 4 * J + 4; i++)
            k[i] = pack_bf16(ex2(fmaf(s[2 * i], SM_C, -mref)), ex2(fmaf(s[2 * i + 1], SM_C, -mref)));
#pragma unroll
        for (int i = 0; i < 4; i++)
            asm volatile("stmatrix.sync.aligned.m8n8.x1.trans.shared.b16 [%0], {%1};" ::"r"(((i & 1) ? pa ^ 16 : pa) + J * 2048 + (i >> 1) * 1024),
                         "r"(k[4 * J + i])
                         : "memory");
        exp_block<J + 1>(s, k, pa, mref);
    }
}
__device__ __forceinline__ void sum_block(const uint32_t (&k)[40], float (&l)[10], uint32_t lane) {
    const bool b4 = lane & 16, b3 = lane & 8;
    uint32_t ps[20], t[10];
#pragma unroll
    for (int j = 0; j < 20; j++) ps[j] = add_bf2(k[2 * j], k[2 * j + 1]);
#pragma unroll
    for (int j = 0; j < 10; j++)
        t[j] = add_bf2(b4 ? ps[2 * j + 1] : ps[2 * j], __shfl_xor_sync(0xffffffffu, b4 ? ps[2 * j] : ps[2 * j + 1], 16));
#pragma unroll
    for (int i = 0; i < 5; i++) {
        const uint32_t a = b3 ? t[i + 5] : t[i], b = __shfl_xor_sync(0xffffffffu, b3 ? t[i] : t[i + 5], 8);
        l[2 * i] += __uint_as_float(a << 16) + __uint_as_float(b << 16);
        l[2 * i + 1] += __uint_as_float(a & 0xffff0000u) + __uint_as_float(b & 0xffff0000u);
    }
}
template <bool ADD>
__device__ __forceinline__ void sum_store(const float (&l)[10], uint32_t lane, uint32_t lxa) {
    const bool b2 = lane & 4;
    float t[5];
#pragma unroll
    for (int i = 0; i < 5; i++) t[i] = ADD ? __uint_as_float(lds_u(lxa + i * 64)) : 0.f;
#pragma unroll
    for (int i = 0; i < 5; i++)
        sts_f(lxa + i * 64, t[i] + (b2 ? l[2 * i + 1] : l[2 * i]) + __shfl_xor_sync(0xffffffffu, b2 ? l[2 * i] : l[2 * i + 1], 4));
}

__device__ __forceinline__ void fallback_unit(const Params& P, uint32_t e, uint32_t tid) {
    const uint32_t lane = tid & 31, br = IT_BR(e), b = IT_B(e), h = IT_H0(e);
    const __nv_bfloat162* wq = (const __nv_bfloat162*)(P.pwq[br] + h * 192) + lane;
    const __nv_bfloat162* kp = (const __nv_bfloat162*)(P.pk[br] + (size_t)(b * 32 + h) * 512 * 192) + lane;
    const __nv_bfloat162* vp = (const __nv_bfloat162*)(P.pv[br] + (size_t)(b * 32 + h) * 512 * 192) + lane;
#pragma unroll 1
    for (uint32_t qi = 0; qi < 40; qi++) {
        const uint32_t q = 4 * qi + (tid >> 5);
        const __nv_bfloat16* xr = P.px[br] + (size_t)(b * 160 + q) * 640;
        float a[6] = {0.f, 0.f, 0.f, 0.f, 0.f, 0.f};
#pragma unroll 2
        for (int k = 0; k < 640; k++) {
            const float xv = __bfloat162float(xr[k]);
#pragma unroll
            for (int i = 0; i < 3; i++) {
                const float2 wv = __bfloat1622float2(wq[(size_t)k * 3072 + i * 32]);
                a[2 * i] = fmaf(xv, wv.x, a[2 * i]);
                a[2 * i + 1] = fmaf(xv, wv.y, a[2 * i + 1]);
            }
        }
#pragma unroll
        for (int i = 0; i < 6; i++) a[i] = __bfloat162float(__float2bfloat16(a[i]));
        auto score = [&](int key) {
            float d = 0.f;
#pragma unroll
            for (int i = 0; i < 3; i++) {
                const float2 kv = __bfloat1622float2(kp[key * 96 + i * 32]);
                d = fmaf(a[2 * i], kv.x, fmaf(a[2 * i + 1], kv.y, d));
            }
#pragma unroll
            for (int o = 16; o > 0; o >>= 1) d += __shfl_xor_sync(0xffffffffu, d, o);
            return d;
        };
        float m = -INFINITY, o[6] = {0.f, 0.f, 0.f, 0.f, 0.f, 0.f}, sum = 0.f;
#pragma unroll 1
        for (int n = 0; n < 1024; n++) {
            const int key = n & 511;
            const float d = score(key);
            if (n < 512) {
                m = fmaxf(m, d);
            } else {
                const float p = ex2((d - m) * SM_C);
                sum += p;
#pragma unroll
                for (int i = 0; i < 3; i++) {
                    const float2 vv = __bfloat1622float2(vp[key * 96 + i * 32]);
                    o[2 * i] = fmaf(p, vv.x, o[2 * i]);
                    o[2 * i + 1] = fmaf(p, vv.y, o[2 * i + 1]);
                }
            }
        }
        const float inv = __fdividef(1.f, sum);
        __nv_bfloat16* op = (__nv_bfloat16*)ostash(IT_SLOT(e), b) + (q >> 5) * 256 + 2 * ((q & 31) >> 3) + (q & 1);
#pragma unroll
        for (int i = 0; i < 6; i++) {
            const uint32_t d = (i >> 1) * 64 + 2 * lane + (i & 1);
            op[(d >> 3) * 1280 + (d & 7) * 32 + ((((q & 7) >> 1) ^ ((d & 7) >> 1)) << 3)] = __float2bfloat16(o[i] * inv);
        }
    }
}

struct PendO {
    uint32_t v[64];
    unsigned char* gp;
    static __device__ __forceinline__ uint32_t toff() {
        const uint32_t t = tid_now();
        return ((t >> 5) & 3) * 5120 + ((t >> 2) & 7) * 64 + (((t ^ (t >> 3)) & 3) << 4);
    }
    uint32_t pend, sig, bad;
    static __device__ __forceinline__ void scale(uint32_t& x, uint32_t hi, uint32_t lo) {
        asm("{\n.reg .b32 t;\nmul.rn.bf16x2 t, %0, %2;\nfma.rn.bf16x2 %0, %0, %1, t;\n}" : "+r"(x) : "r"(hi), "r"(lo));
    }
    template <int I, int OFF>
    __device__ __forceinline__ void put() {
        asm volatile("{\n.reg .pred p;\nsetp.ne.u32 p, %6, 0;\n@p st.global.v4.b32 [%0+%5], {%1,%2,%3,%4};\n}" ::"l"(gp), "r"(v[I]),
                     "r"(v[I + 1]), "r"(v[I + 2]), "r"(v[I + 3]), "n"(OFF), "r"(pend)
                     : "memory");
    }
    __device__ __forceinline__ void verdict(uint32_t sb, uint32_t W) {
        if (sig) {
            asm volatile("bar.sync %0, 160;" ::"r"(NB_VOTE + W) : "memory");
            bad = __any_sync(0xffffffffu, lds_u(sb + OFF_FB) != 0);
            pend = !bad;
        }
    }
    template <int W, int G, int H>
    __device__ __forceinline__ void half(uint32_t sb) {
        constexpr bool T2 = W == 0 ? G >= 3 : G < 3;
        constexpr int B = T2 ? 40 + 8 * (W == 0 ? G - 3 : G) : 0;
        const uint4 a = lds_u4(sb + OFF_LINV + G * 128 + H * 16 + (threadIdx.x & 3) * 32);
#pragma unroll
        for (int i = 2 * H; i < 8; i += 4) {
            scale(v[8 * G + i], a.x, a.y);
            scale(v[8 * G + i + 1], a.z, a.w);
            if (T2) {
                scale(v[B + i], a.x, a.y);
                scale(v[B + i + 1], a.z, a.w);
            }
        }
        if (H == 1) {
            put<8 * G, W * XS + G * 512>();
            put<8 * G + 4, W * XS + G * 512 + 2560>();
            if (T2) {
                put<B, 2 * XS + G * 512>();
                put<B + 4, 2 * XS + G * 512 + 2560>();
            }
            if (G == 4 && pend) nb_arrive<NB_ODONE, 288>();
        }
    }
    template <int W, int G>
    __device__ __forceinline__ void step(uint32_t sb) {
        half<W, G, 0>(sb);
        half<W, G, 1>(sb);
    }
    template <int W>
    __device__ __forceinline__ void flush(uint32_t sb) {
        step<W, 0>(sb);
        step<W, 1>(sb);
        step<W, 2>(sb);
        step<W, 3>(sb);
        step<W, 4>(sb);
    }
    __device__ __forceinline__ void clear() {
#pragma unroll
        for (int i = 0; i < 64; i++) v[i] = 0;
        gp = nullptr;
        pend = 0;
        sig = 0;
        bad = 0;
    }
};

__device__ __forceinline__ uint32_t stsm_off() {
    const uint32_t tid = tid_now(), lane = tid & 31;
    return (lane >> 4) * 1024 + (lane & 7) * 128 + (((((tid >> 4) & 6) + ((lane >> 3) & 1)) ^ (lane & 7)) << 4);
}
__device__ __forceinline__ void q_ahead(float (&q0)[80], uint32_t sb, const Ring& rn, uint32_t phm, bool valid) {
    if (valid) mbar_wait2(sb + BAR_RFULL + rn.slot * 8, rn.ph, sb + BAR_XFULL, phm & 1, rn.dl);
    const uint32_t a = ((((sb + OFF_RING) & 0x3ffff) >> 4) | LO_LBO1) + rn.slot * (SLOT >> 4);
    const uint32_t b = (((sb + OFF_R) & 0x3ffff) >> 4) | LO_LBO1;
    wg_fence();
    wgmma<1, 0, HI_SW128, false>(q0, a, b);
#pragma unroll
    for (int k = 1; k < 4; k++) wgmma<1, 0, HI_SW128, true>(q0, a + (k >> 1) * 768 + (k & 1) * 128, b + k * 2);
    wg_commit();
}
template <int W, int KK>
__device__ __forceinline__ void qproj(float (&q0)[80], float (&q1)[80], uint32_t sb, Ring& r, uint32_t pslot, uint32_t phm,
                                      PendO& po) {
    const uint32_t loR = (((sb + OFF_R) & 0x3ffff) >> 4) | LO_LBO1;
    const uint32_t loRing = (((sb + OFF_RING) & 0x3ffff) >> 4) | LO_LBO1;
    auto ready = [&](int k) {
        mbar_wait2(sb + BAR_RFULL + r.slot * 8, r.ph, sb + BAR_XFULL + (k % 5) * 8, ((phm >> (k % 5)) ^ (k / 5)) & 1, r.dl);
    };
    auto release = [&]() {
        if (KK > 0) {
            wg_wait<1>();
            mbar_arrive_warp(sb + BAR_REMPTY + pslot * 8);
            if (KK <= 5) mbar_arrive_warp(sb + (BAR_XEMPTY + (KK - 1) * 8));
        }
    };
    if (KK == 0 && W == 1) ready(0);
    if (W == 1 && KK == QHOLD) nb_sync<NB_SDONE, 256>();
    const uint32_t a = loRing + r.slot * (SLOT >> 4) + (W == 0 ? 0 : 512), b = loR + (KK % 5) * (XS >> 4);
    wg_fence();
    constexpr bool T0 = W == 1 || KK > 0;
    if (T0) wgmma<1, 0, HI_SW128, KK != 0>(q0, a, b);
    if (W == 0) wgmma<1, 0, HI_SW128, KK != 0 ? 1 : 2>(q1, a + 256, b);
#pragma unroll
    for (int k = 1; k < 4; k++) {
        if (T0) wgmma<1, 0, HI_SW128, true>(q0, a + (k >> 1) * 768 + (k & 1) * 128, b + k * 2);
        if (W == 0) wgmma<1, 0, HI_SW128, true>(q1, a + 256 + (k >> 1) * 768 + (k & 1) * 128, b + k * 2);
    }
    wg_commit();
    const uint32_t cslot = r.slot;
    r.adv(1);
    if (W == 0 || KK < QHOLD) release();
    constexpr int QST = W == 0 ? 2 : 1;
    if (KK == QST) {
        po.verdict(sb, W);
        po.template half<W, 0, 0>(sb);
    }
    if (KK < 9) ready(KK + 1);
    if (W == 1 && KK >= QHOLD) release();
    if (W == 1 && KK == 7) nb_arrive<NB_PDONE, 256>();
    if (KK == QST) po.template half<W, 0, 1>(sb);
    if constexpr (KK > QST && KK < QST + 5) po.template step<W, KK - QST>(sb);
    if constexpr (KK < (W == 0 ? 7 : 9)) {
        qproj<W, KK + 1>(q0, q1, sb, r, cslot, phm, po);
    } else if constexpr (W == 1) {
        const uint32_t sta = sb + OFF_R + 2 * XS + stsm_off();
        wg_wait<0>();
        reg_fence(q0);
        store_tile_t<true>(q0, sta);
        mbar_arrive_warp(sb + BAR_REMPTY + cslot * 8);
    } else {
        const uint32_t s8 = r.slot, a8 = loRing + s8 * (SLOT >> 4);
        wg_fence();
#pragma unroll
        for (int k = 0; k < 4; k++) wgmma<1, 0, HI_SW128, true>(q0, a8 + (k >> 1) * 768 + (k & 1) * 128, loR + 3 * (XS >> 4) + k * 2);
        r.adv(1);
        ready(9);
        const uint32_t s9 = r.slot, a9 = loRing + s9 * (SLOT >> 4);
        r.adv(1);
        wg_fence();
#pragma unroll
        for (int k = 0; k < 4; k++) wgmma<1, 0, HI_SW128, true>(q0, a9 + (k >> 1) * 768 + (k & 1) * 128, loR + 4 * (XS >> 4) + k * 2);
        wg_commit();
        wg_wait<1>();
        mbar_arrive_warp(sb + BAR_REMPTY + cslot * 8);
        wg_fence();
#pragma unroll
        for (int k = 0; k < 8; k++)
            wgmma<1, 0, HI_SW128, true>(q1, (k < 4 ? a8 : a9) + 256 + ((k >> 1) & 1) * 768 + (k & 1) * 128,
                                        loR + (3 + (k >> 2)) * (XS >> 4) + (k & 3) * 2);
        wg_commit();
        nb_arrive<NB_SDONE, 256>();
        sts_u(sb + OFF_GM + 4, r.slot);
        nb_sync<NB_PDONE, 256>();
        wg_wait<1>();
        reg_fence(q0);
        const uint32_t sta = sb + OFF_R + stsm_off();
        store_tile_t(q0, sta);
        wg_wait<0>();
        reg_fence(q1);
        mbar_arrive_warp(sb + BAR_REMPTY + s8 * 8);
        mbar_arrive_warp(sb + BAR_REMPTY + s9 * 8);
        store_tile_t(q1, sta + XS);
        mbar_wait(sb + BAR_RFULL + r.slot * 8, r.ph, r.dl);
    }
}

template <int NR>
__device__ __forceinline__ void opack(const float (&o)[NR], uint32_t* v) {
#pragma unroll
    for (int g = 0; g < NR / 16; g++)
#pragma unroll
        for (int hh = 0; hh < 2; hh++)
#pragma unroll
            for (int t = 0; t < 4; t++) v[8 * g + 4 * hh + t] = pack_bf16(o[16 * g + 4 * t + 2 * hh], o[16 * g + 4 * t + 2 * hh + 1]);
}

__device__ __forceinline__ void out_store(const Params& P, uint32_t src, int col, int b) {
    asm volatile("cp.async.bulk.tensor.5d.global.shared::cta.bulk_group [%0, {%2,%4,%4,%4,%3}], [%1];" ::"l"(&P.out), "r"(src),
                 "r"(col), "r"(b * 5), "r"(0)
                 : "memory");
    asm volatile("cp.async.bulk.commit_group;" ::: "memory");
}

template <bool IS_S>
__device__ __forceinline__ void op_item(uint32_t e, uint32_t sb, Ring& r, uint32_t& phm) {
    constexpr int T0 = IS_S ? 0 : 2;
    constexpr uint32_t BOFF = IS_S ? (3 * 512) >> 4 : 0;
    const uint32_t loRing = (((sb + OFF_RING) & 0x3ffff) >> 4) | LO_LBO1;
    const uint32_t loO = (((sb + OFF_R) & 0x3ffff) >> 4) | LO_OST;
    float c0[80], c1[80], c2[IS_S ? 32 : 48];
    const int T = 3 * (IT_H1(e) - IT_H0(e));
    uint32_t xs = 0;
    auto step = [&](auto first, auto half) {
        constexpr bool F = decltype(first)::value;
        constexpr uint32_t hf = decltype(half)::value;
        if (hf == 0) {
            mbar_wait(sb + BAR_XFULL + xs * 8, (phm >> xs) & 1, r.dl);
            phm ^= 1u << xs;
        }
        mbar_wait(sb + BAR_RFULL + r.slot * 8, r.ph, r.dl);
        const uint32_t a = loRing + r.slot * (SLOT >> 4), b = loO + xs * (XS >> 4) + hf * 640;
        wg_fence();
        wgmma<1, 1, HI_OST, !F>(c0, a + T0 * 128, b);
        wgmma<1, 1, HI_OST, !F>(c1, a + T0 * 128 + 128, b);
        wgmma<1, 1, HI_OST, !F>(c2, a + 512, b + BOFF);
        wgmma<1, 1, HI_OST, true>(c0, a + 640 + T0 * 128, b + 320);
        wgmma<1, 1, HI_OST, true>(c1, a + 640 + T0 * 128 + 128, b + 320);
        wgmma<1, 1, HI_OST, true>(c2, a + 640 + 512, b + 320 + BOFF);
        wg_commit();
    };
    step(TrueT{}, IntT<0>{});
#pragma unroll 1
    for (int t = 1;; t++) {
        uint32_t pslot = r.slot;
        r.adv(1);
        step(FalseT{}, IntT<1>{});
        wg_wait<1>();
        mbar_arrive_warp(sb + BAR_REMPTY + pslot * 8);
        if (t == T) break;
        pslot = r.slot;
        const uint32_t pxs = xs;
        r.adv(1);
        if (++xs == 5) xs = 0;
        step(FalseT{}, IntT<0>{});
        wg_wait<1>();
        mbar_arrive_warp(sb + BAR_REMPTY + pslot * 8);
        mbar_arrive_warp_if(sb + BAR_XEMPTY + pxs * 8, t + 4 < T);
    }
    wg_wait<0>();
    reg_fence(c0);
    reg_fence(c1);
    reg_fence(c2);
    mbar_arrive_warp(sb + BAR_REMPTY + r.slot * 8);
    r.adv(1);
    nb_sync<NB_OPEND, 256>();
    const uint32_t sta = sb + OFF_R + stsm_off();
    store_tile_t(c0, sta + T0 * XS);
    store_tile_t(c1, sta + (T0 + 1) * XS);
    store_tile_t(c2, sta + 4 * XS + (IS_S ? 96 * 128 : 0));
    fence_async_smem();
    nb_arrive<NB_ODONE, 288>();
}

__device__ __forceinline__ void on_item(const Params& P, uint32_t W, uint32_t e, uint32_t sb, Ring& r, uint32_t& phm) {
    const uint32_t loRing = (((sb + OFF_RING) & 0x3ffff) >> 4) | LO_LBO1;
    const uint32_t loO = (((sb + OFF_R) & 0x3ffff) >> 4) | LO_OST;
    float c[80];
    const int T = 3 * (IT_H1(e) - IT_H0(e));
    uint32_t xs = 0;
    auto step = [&](auto first) {
        constexpr bool F = decltype(first)::value;
        mbar_wait2(sb + BAR_XFULL + xs * 8, (phm >> xs) & 1, sb + BAR_RFULL + r.slot * 8, r.ph, r.dl);
        phm ^= 1u << xs;
        const uint32_t a = loRing + r.slot * (SLOT >> 4) + W * 256, b = loO + xs * (XS >> 4);
        wg_fence();
        wgmma<1, 1, HI_OST, !F>(c, a, b);
#pragma unroll
        for (int k = 1; k < 4; k++) wgmma<1, 1, HI_OST, true>(c, a + (k >> 1) * 512 + (k & 1) * 128, b + k * 320);
        wg_commit();
    };
    step(TrueT{});
#pragma unroll 1
    for (int t = 1; t < T; t++) {
        const uint32_t pslot = r.slot, pxs = xs;
        r.adv(1);
        if (++xs == 5) xs = 0;
        if (W == 1 && t == T - 2) nb_sync<NB_OPEND, 256>();
        step(FalseT{});
        if (W == 0 && t == T - 1) nb_arrive<NB_OPEND, 256>();
        wg_wait<1>();
        mbar_arrive_warp(sb + BAR_REMPTY + pslot * 8);
        mbar_arrive_warp_if(sb + BAR_XEMPTY + pxs * 8, t + 2 < T);
    }
    xs += 1 + W;
    if (xs >= 5) xs -= 5;
    mbar_wait(sb + BAR_XFULL + xs * 8, (phm >> xs) & 1, r.dl);
    const uint32_t sta = sb + OFF_R + xs * XS + stsm_off();
    uint32_t p[40];
#pragma unroll
    for (int j = 0; j < 10; j++)
        asm volatile("ldmatrix.sync.aligned.m8n8.x4.trans.shared.b16 {%0,%1,%2,%3}, [%4];"
                     : "=r"(p[4 * j]), "=r"(p[4 * j + 1]), "=r"(p[4 * j + 2]), "=r"(p[4 * j + 3])
                     : "r"(sta + j * 2048)
                     : "memory");
    wg_wait<0>();
    reg_fence(c);
#pragma unroll
    for (int k = 0; k < 40; k++) {
        c[2 * k] += __uint_as_float(p[k] << 16);
        c[2 * k + 1] += __uint_as_float(p[k] & 0xffff0000u);
    }
    store_tile_t(c, sta);
    fence_async_smem();
    asm volatile("bar.sync %0, 128;" ::"r"(NB_W + W) : "memory");
    if ((tid_now() & 127) == 0) {
        out_store(P, sb + OFF_R + xs * XS, IT_BR(e) * 640 + (2 * IT_HALF(e) + W) * 64, IT_B(e));
        asm volatile("cp.async.bulk.wait_group 0;" ::: "memory");
    }
    __syncwarp();
}

template <int W>
__device__ __forceinline__ uint32_t qa_item(uint32_t e, uint32_t sb, Ring& r, uint32_t phm, PendO& po, float (&q0)[80],
                                            float (&oa)[80], int it) {
    const uint32_t loR = (((sb + OFF_R) & 0x3ffff) >> 4) | LO_LBO1;
    const uint32_t loRing = (((sb + OFF_RING) & 0x3ffff) >> 4) | LO_LBO1;
    qproj<W, 0>(q0, oa, sb, r, 0, phm, po);
    fence_async_smem();
    TSD(W, 1);
    float s[80], ob[W == 0 ? 32 : 48], l[10];
    if (W == 1) {
        nb_arrive<NB_Q2, 256>();
        zero(oa);
        zero(ob);
        reg_fence(oa);
        reg_fence(ob);
    }
    const uint32_t lane = tid_now() & 31, sta = sb + OFF_R + stsm_off();
    auto pv = [&](auto first, uint32_t buf) {
        constexpr bool F = decltype(first)::value;
        if (F) mbar_wait(sb + BAR_RFULL + r.slot * 8, r.ph, r.dl);
        const uint32_t a = loRing + r.slot * (SLOT >> 4), b = loR + (3 + buf) * (XS >> 4);
        wg_fence();
        wgmma<1, 0, HI_SW128, F ? 2 : 1, HI_KV>(oa, a + W * 64, b);
        wgmma<1, 0, HI_SW128, !F, HI_KV>(ob, a + 128, b + (W == 0 ? (96 * 128) >> 4 : 0));
#pragma unroll
        for (int k = 1; k < 4; k++) {
            wgmma<1, 0, HI_SW128, true, HI_KV>(oa, a + W * 64 + k * 384, b + k * 2);
            wgmma<1, 0, HI_SW128, true, HI_KV>(ob, a + 128 + k * 384, b + (W == 0 ? (96 * 128) >> 4 : 0) + k * 2);
        }
        wg_commit();
    };
    zero(l);
    float mref;
    uint32_t kslot, vslot, nx = 0;
    auto tail = [&](auto first, int i) {
        constexpr bool rel_other = !decltype(first)::value;
        uint32_t ps[40];
        exp_block<0>(s, ps, sta + (3 + W) * XS, mref);
        if (rel_other) {
            wg_wait<0>();
            mbar_arrive_warp(sb + BAR_REMPTY + vslot * 8);
            if (W == 1) mbar_arrive_warp_if(sb + BAR_XEMPTY + 24, i == 3);
        }
        fence_async_smem();
        nb_arrive<NB_PFULL + W, 256>();
        TSD(W, 6 + 5 * i);
        if (W == 1) {
            mbar_arrive_warp_if<2>(sb + BAR_XEMPTY + 8, i == 3);
            mbar_arrive_warp_if<2>(sb + BAR_XEMPTY + 16, i == 3);
        }
        if (rel_other) {
            mbar_wait(sb + BAR_RFULL + r.slot * 8, r.ph, r.dl);
            sum_block(ps, l, lane);
        }
        if (W == 0 && i == 3) nx = get_item_warp(sb, it + 1, r.dl);
        TSD(W, 7 + 5 * i);
        nb_sync<NB_W + W, 128>();
        pv(first, W);
        if (!rel_other) sum_block(ps, l, lane);
        TSD(W, 8 + 5 * i);
    };
    if (W == 0) {
        nb_sync<NB_QK, 160>();
        TSD(W, 2);
        wg_fence();
        qk_steps<0, 8>(s, loRing + r.slot * (SLOT >> 4), loR);
        nb_sync<NB_Q2, 256>();
        qk_steps<8, 12>(s, loRing + r.slot * (SLOT >> 4), loR);
        wg_commit();
        nb_arrive<NB_Q01, 256>();
        TSD(W, 4);
        nb_sync<NB_REF, 160>();
        mref = __uint_as_float(lds_u(sb + OFF_GM));
        wg_wait<0>();
        reg_fence(s);
        mbar_arrive_warp<2>(sb + BAR_REMPTY + r.slot * 8);
        r.adv(2);
        TSD(W, 5);
        tail(TrueT{}, 0);
    } else {
        nb_sync<NB_Q01, 256>();
    }
#pragma unroll 1
    for (int i = (W == 0 ? 1 : 0); i < 4; i++) {
        const uint32_t pvslot = r.slot;
        r.adv(1);
        kslot = r.slot;
        mbar_wait(sb + BAR_RFULL + r.slot * 8, r.ph, r.dl);
        wg_fence();
        qk_steps<0, 4>(s, loRing + r.slot * (SLOT >> 4), loR);
        if (W == 1) wg_commit();
        qk_steps<4, 12>(s, loRing + r.slot * (SLOT >> 4), loR);
        wg_commit();
        wg_wait<1>();
        if (W == 1) mbar_arrive_warp_if(sb + BAR_XEMPTY + 0, i == 3);
        mbar_arrive_warp_if(sb + BAR_REMPTY + pvslot * 8, W == 0 || i > 0);
        r.adv(1);
        vslot = r.slot;
        TSD(W, 4 + 5 * i);
        mbar_wait(sb + BAR_RFULL + r.slot * 8, r.ph, r.dl);
        nb_sync<NB_PFULL + (W ^ 1), 256>();
        pv(FalseT{}, W ^ 1);
        if (W == 1) mref = __uint_as_float(lds_u(sb + OFF_GM));
        wg_wait<1>();
        reg_fence(s);
        mbar_arrive_warp<2>(sb + BAR_REMPTY + kslot * 8);
        if (W == 0) mbar_arrive_warp_if(sb + BAR_XEMPTY + 0, i == 3);
        r.adv(W == 1 && i == 3 ? 1 : 2);
        TSD(W, 5 + 5 * i);
        tail(FalseT{}, i);
    }
    if (W == 1) nx = get_item_warp(sb, it + 1, r.dl);
    if (W == 0) {
        Ring rn = r;
        rn.adv(2);
        q_ahead(q0, sb, rn, phm, IT_TYPE(nx) == IT_QA);
        TSD(W, 25);
    }
    const uint32_t w = (tid_now() >> 5) & 3;
    const uint32_t lxa = sb + OFF_LX + w * 640 + (((lane & 8) ? 80 : 0) + ((lane >> 1) & 8) + 2 * (lane & 3) + ((lane >> 2) & 1)) * 4;
    po.gp = ostash(IT_SLOT(e), IT_B(e)) + po.toff();
    po.sig = 1;
    if (W == 0) {
        sum_store<false>(l, lane, lxa);
        nb_arrive<NB_LX, 256>();
        wg_wait<1>();
        mbar_arrive_warp(sb + BAR_REMPTY + r.slot * 8);
        mbar_arrive_warp(sb + BAR_XEMPTY + 24);
        r.adv(1);
        mbar_wait(sb + BAR_RFULL + r.slot * 8, r.ph, r.dl);
        nb_sync<NB_PFULL + 1, 256>();
        pv(FalseT{}, 1);
    } else {
        nb_sync<NB_LX, 256>();
        sum_store<true>(l, lane, lxa);
        nb_arrive<NB_L, 160>();
    }
    TSD(W, 24);
    wg_wait<0>();
    reg_fence(oa);
    reg_fence(ob);
    mbar_arrive_warp(sb + BAR_REMPTY + r.slot * 8);
    mbar_arrive_warp(sb + BAR_XEMPTY + 32);
    r.adv(1);
    opack(ob, po.v + 40);
    opack(oa, po.v);
    return nx;
}

template <int W>
__device__ __forceinline__ uint32_t qa_run(uint32_t e, uint32_t sb, Ring& r, uint32_t phm, PendO& po, int& it) {
    float q0[80], oa[80];
    if (W == 0) {
        zero(oa);
        q_ahead(q0, sb, r, phm, true);
        wg_wait<0>();
    }
#pragma unroll 1
    do {
        TS(W, 0);
        if (W == 0) TS_ITEM(e);
        e = qa_item<W>(e, sb, r, phm, po, q0, oa, it);
        TS(W, 31);
        it++;
    } while (IT_TYPE(e) == IT_QA && !po.bad);
    if (W == 0) {
#pragma unroll
        for (int i = 56; i < 64; i++) po.v[i] = 0;
    }
    return e;
}

__device__ __forceinline__ void consumer(const Params& P, uint32_t W, uint32_t sb, uint32_t dl) {
    int it = 0;
    Ring r{0, 0, dl};
    uint32_t phm = 0;
    uint32_t e = get_item_warp(sb, 0, dl);
#pragma unroll 1
    while (true) {
        if (IT_TYPE(e) == IT_QA) {
            PendO po;
            po.clear();
            e = W == 0 ? qa_run<0>(e, sb, r, phm, po, it) : qa_run<1>(e, sb, r, phm, po, it);
#pragma unroll 1
            for (int m = po.bad ? 2 : 1; m > 0; m--) {
                if (m == 1) {
                    po.verdict(sb, W);
                    if (W == 0) po.flush<0>(sb);
                    else po.flush<1>(sb);
                }
                if (po.bad) {
                    if (W == 0) fallback_unit(P, lds_u(sb + OFF_ITEM + (it - m) * 4), tid_now() & 127);
                    __syncwarp();
                    nb_sync<NB_ODONE, 288>();
                }
            }
        }
        if (e == 0) break;
        if (IT_TYPE(e) == IT_QA) continue;
        TS(W, 0);
        if (W == 0) TS_ITEM(e);
        if (IT_TYPE(e) == IT_ON) {
            on_item(P, W, e, sb, r, phm);
            TS(W, 31);
            break;
        }
        if (W == 0) op_item<true>(e, sb, r, phm);
        else op_item<false>(e, sb, r, phm);
        TS(W, 31);
        e = get_item_warp(sb, ++it, dl);
    }
    TS_DUMP(W);
}

__global__ void __cluster_dims__(2, 1, 1) __launch_bounds__(384, 1) fused_kernel(const __grid_constant__ Params P) {
    extern __shared__ __align__(1024) unsigned char smem_raw[];
    const uint32_t sb = (uint32_t)__cvta_generic_to_shared(smem_raw);
    const uint32_t warp = __shfl_sync(0xffffffffu, threadIdx.x >> 5, 0), wgid = warp >> 2;
    const uint32_t cta = blockIdx.x;
    const uint32_t dl = deadline();

    if (threadIdx.x == 128) {
#pragma unroll
        for (int i = 0; i < NSLOT; i++) {
            mbar_init(sb + BAR_RFULL + i * 8, 1);
            mbar_init(sb + BAR_REMPTY + i * 8, 8);
            mbar_init(sb + BAR_XFULL + i * 8, 1);
            mbar_init(sb + BAR_XEMPTY + i * 8, 8);
        }
        asm volatile("fence.mbarrier_init.release.cluster;" ::: "memory");
        fence_async_smem();
    } else if (threadIdx.x == 160) {
#pragma unroll
        for (int i = 0; i < NSLOT + MAXI; i++) mbar_init(sb + BAR_PRDY + i * 8, 1);
        asm volatile("fence.mbarrier_init.release.cluster;" ::: "memory");
    } else if (threadIdx.x == 0) {
        sts_u(sb + OFF_ITEM, P.cl[cta >> 1].items[0] ? P.cl[cta >> 1].items[0] + 8 * (cta & 1) : 0);
        sts_u(sb + OFF_FB, P.cl[cta >> 1].delay);
    } else if (threadIdx.x == 64) {
        if (sb & 1023) __trap();
        asm volatile("prefetch.tensormap [%0];" ::"l"(&P.wq[0]) : "memory");
        asm volatile("prefetch.tensormap [%0];" ::"l"(&P.x[0]) : "memory");
    }
    __syncthreads();
    {
        const int it = 0;
        if (wgid == 1) TS(0, 30);
    }
    asm volatile("barrier.cluster.arrive.relaxed.aligned;" ::: "memory");
    if (warp < 3) {
        const uint32_t e = __shfl_sync(0xffffffffu, lds_u(sb + OFF_ITEM), 0), d = lds_u(sb + OFF_FB);
        const uint64_t pol = pol_shared();
        const bool isx = warp == 1, lead = (threadIdx.x & 31) == 0;
        uint32_t t0, t1;
        asm volatile("mov.u32 %0, %%clock;" : "=r"(t0));
        do {
            asm volatile("mov.u32 %0, %%clock;" : "=r"(t1));
        } while (t1 - t0 < d);
        __syncwarp();
#pragma unroll 1
        for (int n = 0; n < (e ? NSLOT : 0); n++) {
            const uint32_t bar = sb + (isx ? BAR_XFULL : BAR_RFULL) + n * 8;
            if (lead) {
                if (warp < 2) mbar_expect(bar, isx ? XS : SLOT);
                tma3(sb + (isx ? OFF_R + n * XS : OFF_RING + n * SLOT + warp * (SLOT / 4)), isx ? &P.x[0] : &P.wq[0],
                     isx ? IT_B(e) * 160 : n * 64 + warp * 16, isx ? n : IT_H0(e) * 3, bar, pol);
            }
        }
        if (threadIdx.x == 0) asm volatile("mbarrier.arrive.shared::cta.b64 _, [%0];" ::"r"(sb + BAR_ITEM) : "memory");
        __syncwarp();
    }

    if (wgid == 0) {
        asm volatile("setmaxnreg.dec.sync.aligned.u32 24;");
        if (warp == 0) {
            const bool lead = threadIdx.x == 0;
            const uint64_t pol_first = pol_stream(), pol_norm = pol_shared();
            uint32_t e = __shfl_sync(0xffffffffu, lds_u(sb + OFF_ITEM), 0);
            asm volatile("barrier.cluster.wait.aligned;" ::: "memory");
            unsigned int* const ticket = &g_ticket[next_epoch(0) & 1];
            const uint32_t rank = cta & 1;
            uint32_t peer;
            asm volatile("mapa.shared::cluster.u32 %0, %1, %2;" : "=r"(peer) : "r"(sb), "r"(rank ^ 1));
            Ring r{0, 0, dl};
            uint32_t pm = 0;
            auto load_w = [&](const CUtensorMap* m, int row, int blk, uint32_t half_bytes) {
                mbar_wait(sb + BAR_REMPTY + r.slot * 8, r.ph, dl);
                if (lead) {
                    mbar_expect(sb + BAR_RFULL + r.slot * 8, 2 * half_bytes);
                    asm volatile("mbarrier.arrive.shared::cluster.b64 _, [%0];" ::"r"(peer + BAR_PRDY + r.slot * 8) : "memory");
                }
                mbar_wait(sb + BAR_PRDY + r.slot * 8, (pm >> r.slot) & 1, dl);
                pm ^= 1u << r.slot;
                if (lead) tma3_mc(sb + OFF_RING + r.slot * SLOT + rank * half_bytes, m, row, blk, sb + BAR_RFULL + r.slot * 8, pol_norm);
                r.adv(1);
            };
#pragma unroll 1
            for (int it = 0; e != 0; it++) {
                uint32_t nx = 0, tk = 0;
                if (rank == 0 && IT_TYPE(e) != IT_ON && it + 2 < MAXI) nx = it + 1 < NSTAT ? P.cl[cta >> 1].items[it + 1] : IT_DYN;
                const uint32_t br = IT_BR(e);
                if (IT_TYPE(e) == IT_QA) {
                    const uint32_t h = IT_H0(e);
#pragma unroll 1
                    for (int kk = it ? 0 : NSLOT; kk < 10; kk++) load_w(&P.wq[br], kk * 64 + rank * 32, h * 3, SLOT / 2);
                    const int grp0 = (IT_B(e) * 32 + h) * 64;
#pragma unroll 1
                    for (int n = 0; n < 16; n++) {
                        if (n == 13 && nx == IT_DYN && lead) tk = atomicAdd(ticket, 1);
                        const bool isv = n == 15 || (n > 0 && !(n & 1));
                        const int j = n == 15 ? 7 : isv ? (n - 2) >> 1 : (n + 1) >> 1;
                        mbar_wait(sb + BAR_REMPTY + r.slot * 8, r.ph, dl);
                        if (lead) {
                            mbar_expect(sb + BAR_RFULL + r.slot * 8, SLOT);
                            asm volatile(
                                "cp.async.bulk.tensor.4d.shared::cluster.global.mbarrier::complete_tx::bytes.L2::cache_hint"
                                " [%0], [%1, {%3,%3,%3,%4}], [%2], %5;" ::"r"(sb + OFF_RING + r.slot * SLOT),
                                "l"(isv ? &P.v[br] : &P.k[br]), "r"(sb + BAR_RFULL + r.slot * 8), "r"(0), "r"(grp0 + j * 8), "l"(pol_first)
                                : "memory");
                        }
                        r.adv(1);
                    }
                } else {
                    const bool wide = IT_TYPE(e) == IT_OP;
                    const int step = wide ? 32 : 64, r1 = IT_H1(e) * 192;
#pragma unroll 1
                    for (int row = IT_H0(e) * 192 + rank * (step >> 1); row < r1; row += step)
                        load_w(wide ? &P.wo[br] : &P.won[br], row, IT_HALF(e) * (wide ? 5 : 2), wide ? XS / 2 : 8192);
                    if (nx == IT_DYN && lead) tk = atomicAdd(ticket, 1);
                }
                if (rank == 0) {
                    if (nx == IT_DYN) {
                        tk = __shfl_sync(0xffffffffu, tk, 0);
                        nx = tk < P.nlist ? P.list[tk] : 0;
                    }
                    e = nx;
                    if (lead) {
                        asm volatile("st.async.weak.shared::cluster.mbarrier::complete_tx::bytes.b32 [%0], %1, [%2];" ::"r"(
                                         peer + OFF_ITEM + 4 + it * 4),
                                     "r"(e ? e + 8 : 0), "r"(peer + BAR_ITEM + 8 + it * 8)
                                     : "memory");
                        sts_u(sb + OFF_ITEM + 4 + it * 4, e);
                        asm volatile("mbarrier.arrive.shared::cta.b64 _, [%0];" ::"r"(sb + BAR_ITEM + 8 + it * 8) : "memory");
                    }
                } else {
                    if (lead) mbar_expect(sb + BAR_ITEM + 8 + it * 8, 4);
                    e = get_item_warp(sb, it + 1, dl);
                }
            }
        } else if (warp == 1) {
            const uint64_t pol_norm = pol_shared(), pol_o = pol_stream();
            const bool lead = threadIdx.x == 32;
            uint32_t phm = 0, epoch = 0;
#pragma unroll 1
            for (int it = 0;; it++) {
                const uint32_t e = get_item_warp(sb, it, dl);
                if (it == 1 || (it == 0 && e == 0)) epoch = next_epoch(1);
                if (e == 0) break;
                const uint32_t br = IT_BR(e);
                uint32_t xs = 0;
                auto acquire = [&]() {
                    mbar_wait(sb + BAR_XEMPTY + xs * 8, (phm >> xs) & 1, dl);
                    phm ^= 1u << xs;
                    if (lead) mbar_expect(sb + BAR_XFULL + xs * 8, XS);
                };
                if (IT_TYPE(e) == IT_QA) {
#pragma unroll 1
                    for (int kk = it ? 0 : 5; kk < 10; kk++) {
                        acquire();
                        if (lead) tma3(sb + OFF_R + xs * XS, &P.x[br], IT_B(e) * 160, kk, sb + BAR_XFULL + xs * 8, pol_norm);
                        if (++xs == 5) xs = 0;
                    }
                } else {
                    const unsigned int* fp = g_flag + (br * 16 + IT_B(e)) * 64 + (threadIdx.x & 31) * 2;
                    uint32_t hm = 0, pm = 0;
                    auto poll = [&](uint32_t hneed, uint32_t pneed) {
                        if ((hm & hneed) == hneed && (pm & pneed) == pneed) return;
                        uint32_t n = 0;
                        do {
                            uint32_t a, b;
                            asm volatile("ld.acquire.gpu.global.v2.u32 {%0, %1}, [%2];" : "=r"(a), "=r"(b) : "l"(fp) : "memory");
                            hm = __ballot_sync(0xffffffffu, a == epoch);
                            pm = __ballot_sync(0xffffffffu, b == epoch);
                            if (++n > 0x1000000) __trap();
                        } while ((hm & hneed) != hneed || (pm & pneed) != pneed);
                        __syncwarp();
                        asm volatile("fence.proxy.async.global;" ::: "memory");
                    };
#pragma unroll 1
                    for (uint32_t h = IT_H0(e); h < IT_H1(e); h++) {
                        const unsigned char* src = ostash(P.slot[br * 32 + h], IT_B(e));
                        poll(1u << h, 0);
#pragma unroll 1
                        for (int t = 0; t < 3; t++) {
                            acquire();
                            if (lead) bulk_load(sb + OFF_R + xs * XS, src + t * XS, XS, sb + BAR_XFULL + xs * 8, pol_o);
                            if (++xs == 5) xs = 0;
                        }
                        if (IT_TYPE(e) == IT_OP && h >= 1) {
                            const uint32_t x1 = xs == 4 ? 0 : xs + 1;
                            mbar_wait(sb + BAR_XFULL + xs * 8, (phm >> xs) & 1, dl);
                            mbar_wait(sb + BAR_XFULL + x1 * 8, (phm >> x1) & 1, dl);
                            if (lead)
                                asm volatile("red.relaxed.gpu.global.max.u32 [%0], %1;" ::"l"(fp + 5 + 2 * IT_HALF(e)), "r"(epoch * 64 + h) : "memory");
                        }
                    }
                    if (IT_TYPE(e) == IT_ON) {
                        poll(0, IT_HALF(e) < 2 ? 1 : IT_HALF(e) == 2 ? 3 : 2);
#pragma unroll 1
                        for (uint32_t tile = 2 * IT_HALF(e); tile < 2 * IT_HALF(e) + 2; tile++) {
                            acquire();
                            if (lead)
                                asm volatile(
                                    "cp.async.bulk.tensor.5d.shared::cluster.global.mbarrier::complete_tx::bytes [%0], [%1, {%3,%5,%5,%5,%4}], [%2];" ::"r"(
                                        sb + OFF_R + xs * XS),
                                    "l"(&P.out), "r"(sb + BAR_XFULL + xs * 8), "r"(br * 640 + tile * 64), "r"(IT_B(e) * 5), "r"(0)
                                    : "memory");
                            if (++xs == 5) xs = 0;
                        }
                    }
                }
            }
        } else if (warp == 2) {
            asm volatile("barrier.cluster.wait.aligned;" ::: "memory");
            const uint32_t epoch = next_epoch(2);
            if (cta == 0) g_ticket[(epoch + 1) & 1] = 0;
#pragma unroll 1
            for (int it = 0;; it++) {
                const uint32_t e = get_item_warp(sb, it, dl);
                if (e == 0) break;
                if (IT_TYPE(e) != IT_QA && threadIdx.x == 64) asm volatile("prefetch.tensormap [%0];" ::"l"(&P.out) : "memory");
                if (IT_TYPE(e) == IT_ON) break;
                nb_sync<NB_ODONE, 288>();
                if (threadIdx.x == 64) {
                    const uint32_t bb = IT_BR(e) * 16 + IT_B(e);
                    if (IT_TYPE(e) != IT_QA) {
                        asm volatile("red.relaxed.gpu.global.max.u32 [%0], %1;" ::"l"(&g_flag[bb * 64 + 5 + 2 * IT_HALF(e)]),
                                     "r"(epoch * 64 + IT_H1(e))
                                     : "memory");
#pragma unroll 1
                        for (int m = 0; m < 5; m++) {
                            out_store(P, sb + OFF_R + m * XS, IT_BR(e) * 640 + IT_HALF(e) * 320 + m * 64, IT_B(e));
                            if (m >= 1) {
                                asm volatile("cp.async.bulk.wait_group.read 1;" ::: "memory");
                                asm volatile("mbarrier.arrive.shared::cta.b64 _, [%0], 8;" ::"r"(sb + BAR_XEMPTY + (m - 1) * 8) : "memory");
                            }
                        }
                        asm volatile("cp.async.bulk.wait_group.read 0;" ::: "memory");
                        asm volatile("mbarrier.arrive.shared::cta.b64 _, [%0], 8;" ::"r"(sb + BAR_XEMPTY + 32) : "memory");
                        if (IT_PART(e)) {
                            asm volatile("cp.async.bulk.wait_group 0;" ::: "memory");
                            asm volatile("fence.proxy.async.global;" ::: "memory");
                        }
                    }
                    if (IT_TYPE(e) == IT_QA || IT_PART(e)) {
                        unsigned int* f = &g_flag[bb * 64 + (IT_TYPE(e) == IT_QA ? 2 * IT_H0(e) : 1 + 2 * IT_HALF(e))];
                        asm volatile("st.release.gpu.global.u32 [%0], %1;" ::"l"(f), "r"(epoch) : "memory");
                    }
                }
                __syncwarp();
            }
            if (threadIdx.x == 64) asm volatile("cp.async.bulk.wait_group 0;" ::: "memory");
            __syncwarp();
            asm volatile("barrier.cluster.arrive.relaxed.aligned;\nbarrier.cluster.wait.aligned;" ::: "memory");
        } else {
            const uint32_t lane = threadIdx.x & 31, p = lane >> 3;
            const uint32_t epoch = next_epoch(3);
#pragma unroll 1
            for (int it = 0;; it++) {
                const uint32_t e = get_item_warp(sb, it, dl);
                if (e == 0) break;
                if (IT_TYPE(e) != IT_QA) continue;
                nb_sync<NB_QK, 160>();
                const uint32_t ka = sb + OFF_RING + lds_u(sb + OFF_GM + 4) * SLOT + p * (2 * 3072 + 256) + (lane & 7) * 16;
                const uint32_t qa = sb + OFF_R + p * 256 + (lane & 7) * 16;
                uint32_t acc = 0;
#pragma unroll 1
                for (int c = 0; c < 3; c++) {
                    const uint4 k = lds_u4(ka + c * 1024);
                    if (c == 2) nb_sync<NB_L, 160>();
                    const uint4 q = lds_u4(qa + c * XS);
                    acc = fma_bf2(k.x, q.x, fma_bf2(k.y, q.y, fma_bf2(k.z, q.z, fma_bf2(k.w, q.w, acc))));
                }
                const float d = __uint_as_float(acc << 16) + __uint_as_float(acc & 0xffff0000u);
                const int sum = __reduce_add_sync(0xffffffffu, __float2int_rn(d * 16.f));
                sts_f(sb + OFF_GM, fmaf((float)sum, SM_C / 64.f, 24.f));
                nb_arrive<NB_REF, 160>();
                if (IT_DEP(e)) {
                    const uint32_t g = IT_DEP(e) - 1, need = epoch * 64 + (g & 31) + 1;
                    const unsigned int* cp = &g_flag[((g >> 5) * 16 + IT_B(e)) * 64 + 5 + 2 * (lane & 1)];
                    for (uint32_t n = 0;; n++) {
                        uint32_t v;
                        asm volatile("ld.acquire.gpu.global.u32 %0, [%1];" : "=r"(v) : "l"(cp) : "memory");
                        if (__all_sync(0xffffffffu, v - need < 64)) break;
                        if (n > 0x800000) __trap();
                        __nanosleep(500);
                    }
                }
                nb_sync<NB_L, 160>();
                bool bad = false;
#pragma unroll
                for (int c = 0; c < 5; c++) {
                    const uint32_t la = sb + OFF_LX + (c * 32 + lane) * 4;
                    const float v = (__uint_as_float(lds_u(la)) + __uint_as_float(lds_u(la + 640))) +
                                    (__uint_as_float(lds_u(la + 1280)) + __uint_as_float(lds_u(la + 1920)));
                    const float inv = __fdividef(1.f, v);
                    const uint32_t hi = pack_bf16(inv, 0.f), lo = pack_bf16(inv - __uint_as_float(hi << 16), 0.f);
                    const uint32_t ia = sb + OFF_LINV + c * 128 + ((lane >> 1) & 3) * 32 + (lane >> 3) * 8 + (lane & 1) * 2;
                    asm volatile("st.shared.u16 [%0], %1;\nst.shared.u16 [%0+4], %2;" ::"r"(ia), "h"((unsigned short)hi), "h"((unsigned short)lo) : "memory");
                    bad |= !(v >= 5.421010862e-20f && v <= 7.9228163e28f);
                }
                sts_u(sb + OFF_FB, __any_sync(0xffffffffu, bad));
                nb_arrive<NB_VOTE, 160>();
                nb_arrive<NB_VOTE + 1, 160>();
            }
        }
    } else {
        asm volatile("setmaxnreg.inc.sync.aligned.u32 240;");
        consumer(P, wgid - 1, sb, dl);
    }
}

typedef CUresult (*EncFn)(CUtensorMap*, CUtensorMapDataType, cuuint32_t, void*, const cuuint64_t*, const cuuint64_t*,
                          const cuuint32_t*, const cuuint32_t*, CUtensorMapInterleave, CUtensorMapSwizzle,
                          CUtensorMapL2promotion, CUtensorMapFloatOOBfill);

void make_map3(EncFn enc, CUtensorMap* m, void* p, uint64_t rows, uint64_t rowbytes, uint64_t nblk, uint32_t boxrows,
               uint32_t boxblk) {
    cuuint64_t dims[3] = {64, rows, nblk};
    cuuint64_t str[2] = {rowbytes, 128};
    cuuint32_t box[3] = {64, boxrows, boxblk};
    cuuint32_t es[3] = {1, 1, 1};
    enc(m, CU_TENSOR_MAP_DATA_TYPE_BFLOAT16, 3, p, dims, str, box, es, CU_TENSOR_MAP_INTERLEAVE_NONE,
        CU_TENSOR_MAP_SWIZZLE_128B, CU_TENSOR_MAP_L2_PROMOTION_NONE, CU_TENSOR_MAP_FLOAT_OOB_FILL_NONE);
}

constexpr int tune(const char*, int def) { return def; }

void build_schedule(Params& P, int ncl) {
    const int mode = tune("MODE", 4), dmax = tune("DMAX", 23000), n0 = tune("N0", 10);
    const int H0[8] = {19, 20, 21, 22, 22, 24, 25, 25}, P0[8] = {373, 335, 333, 329, 333, 333, 331, 330};
    const int ra = tune("RA", 10), ga = tune("GA", 17), rb = tune("RB", 11), g1 = tune("G1", 58);
    int dep[64];
    for (int g = 0, ns = 0, live = 0; g < 64; g++) {
        const bool fresh = mode < 3 || g >= g1 || live < (g < ga ? ra : rb);
        dep[g] = fresh ? 0 : g - live + 1;
        P.slot[g] = fresh ? ns++ : P.slot[g - live];
        live += fresh;
    }
    int H[8], pos[8], psum = 0;
    for (int b = 0; b < 8; b++) {
        const char nh[3] = {'H', (char)('0' + b), 0}, np[3] = {'P', (char)('0' + b), 0};
        H[b] = tune(nh, H0[b]);
        pos[b] = tune(np, P0[b]);
        psum += pos[b];
    }
    const int sk = tune("SK", 10), g0 = tune("G0", 20), g2 = tune("G2", 40);
    int ord[512], nxt[8] = {0, 0, 0, 0, 0, 0, 0, 0};
    for (int k = 0; k < 512; k++) {
        int best = -1;
        float bkey = 0.f;
        for (int b = 0; b < 8; b++) {
            const int g = nxt[b];
            if (g == 64) continue;
            const float w = g < g0 ? 0.f : g < 32 ? (g - g0) / (32.f - g0) : g < g2 ? 1.f : (64 - g) / (64.f - g2);
            const float key = g + w * sk * 0.1f * (pos[b] - psum / 8.f) / 8.f;
            if (best < 0 || key < bkey) best = b, bkey = key;
        }
        ord[k] = nxt[best]++ * 8 + best;
        const int d = dep[ord[k] >> 3];
        if (d > 32) {
            if (pos[best] > k) pos[best] = k;
            if (H[best] < d - 32) H[best] = d - 32;
        }
    }
    int u = 0;
    auto unit = [&]() {
        const int v = ord[u++];
        return mk_item(IT_QA, v >> 8, (v & 7) * 2, (v >> 3) & 31, P.slot[v >> 3], 0) | (dep[v >> 3] << 23);
    };
    int qa[NCL], nq = 0, op[NCL], no = 0;
    for (int c = 0; c < ncl; c++) {
        P.cl[c].delay = 0;
        for (int i = 0; i < NSTAT; i++) P.cl[c].items[i] = 0;
        if (mode >= 3 && c >= 4 && c < 20) op[((c - 4) & 7) * 2 + ((c - 4) >> 3)] = c, no++;
        else if (mode != 2 || (c & 3) == 0) qa[nq++] = c;
    }
    for (int t = 0; t < no; t++) {
        P.cl[op[t]].items[1] = mk_item(IT_OP, 0, t & ~1, 0, 32, t & 1);
        P.cl[op[t]].items[2] = IT_DYN;
            }
    for (int k = 0; k < nq; k++) {
        const int c = qa[(k * (nq % 19 ? 19 : 17)) % nq];
        P.cl[c].items[1] = P.cl[c].items[2] = IT_DYN;
        P.cl[c].delay = k < n0 ? 0 : dmax * (k + 1 - n0) / (nq - n0);
    }
    for (int t = 0; t < no; t++) P.cl[op[(t & 7) * 2 + (t >> 3)]].items[0] = unit();
    for (int k = u; k < no + nq; k++) {
        int best = -1;
        for (int c = 0; c < ncl; c++)
            if (P.cl[c].items[1] && !P.cl[c].items[0] && (best < 0 || P.cl[c].delay < P.cl[best].delay)) best = c;
        P.cl[best].items[0] = unit();
    }
    int n = 0;
    const int uend = mode == 2 ? 8 * nq : 512;
    while (u < uend) {
        for (int b = 0; b < 8 && no; b++)
            if (pos[b] == u) {
                P.list[n++] = mk_item(IT_OP, 1, 2 * b, 0, H[b], 0, 1);
                P.list[n++] = mk_item(IT_OP, 1, 2 * b, 0, H[b], 1, 1);
            }
        P.list[n++] = unit();
    }
    for (int k = 0; no && k < 40; k++) P.list[n++] = mk_item(IT_ON, 1, k / 5 * 2, H[k / 5], 32, k % 5);
    P.nlist = n;
}

}

extern "C" void kernel_launch(void* const* d_in, const int* in_sizes, int n_in, void* d_out, int out_size) {
    static Params P;
    static bool init = false;
    static int ncl = NCL;
    if (!init) {
        EncFn enc = nullptr;
        cudaDriverEntryPointQueryResult qr;
        cudaGetDriverEntryPoint("cuTensorMapEncodeTiled", (void**)&enc, cudaEnableDefault, &qr);
        for (int i = 0; i < 2; i++) {
            P.px[i] = (const __nv_bfloat16*)d_in[5 * i + 0];
            P.pk[i] = (const __nv_bfloat16*)d_in[5 * i + 1];
            P.pv[i] = (const __nv_bfloat16*)d_in[5 * i + 2];
            P.pwq[i] = (const __nv_bfloat16*)d_in[5 * i + 3];
            make_map3(enc, &P.x[i], d_in[5 * i + 0], 2560, 1280, 10, 160, 1);
            for (int j = 0; j < 2; j++) {
                cuuint64_t dims[4] = {64, 8, 3, 16 * 32 * 64};
                cuuint64_t str[3] = {384, 128, 3072};
                cuuint32_t box[4] = {64, 8, 3, 8};
                cuuint32_t es[4] = {1, 1, 1, 1};
                enc(j ? &P.v[i] : &P.k[i], CU_TENSOR_MAP_DATA_TYPE_BFLOAT16, 4, d_in[5 * i + 1 + j], dims, str, box, es,
                    CU_TENSOR_MAP_INTERLEAVE_NONE, CU_TENSOR_MAP_SWIZZLE_128B, CU_TENSOR_MAP_L2_PROMOTION_NONE,
                    CU_TENSOR_MAP_FLOAT_OOB_FILL_NONE);
            }
            make_map3(enc, &P.wq[i], d_in[5 * i + 3], 640, 12288, 96, 32, 3);
            make_map3(enc, &P.wo[i], d_in[5 * i + 4], 6144, 1280, 10, 16, 5);
            make_map3(enc, &P.won[i], d_in[5 * i + 4], 6144, 1280, 10, 32, 2);
        }
        cuuint64_t dims[5] = {1280, 2, 4, 4, 80};
        cuuint64_t str[4] = {2560, 8 * 2560, 2 * 2560, 32 * 2560};
        cuuint32_t box[5] = {64, 2, 4, 4, 5};
        cuuint32_t es[5] = {1, 1, 1, 1, 1};
        enc(&P.out, CU_TENSOR_MAP_DATA_TYPE_BFLOAT16, 5, d_out, dims, str, box, es, CU_TENSOR_MAP_INTERLEAVE_NONE,
            CU_TENSOR_MAP_SWIZZLE_128B, CU_TENSOR_MAP_L2_PROMOTION_NONE, CU_TENSOR_MAP_FLOAT_OOB_FILL_NONE);
        cudaFuncSetAttribute(fused_kernel, cudaFuncAttributeMaxDynamicSharedMemorySize, SMEM_LAUNCH);
        cudaLaunchConfig_t cfg = {};
        cfg.gridDim = dim3(NCTA);
        cfg.blockDim = dim3(384);
        cfg.dynamicSmemBytes = SMEM_LAUNCH;
        int nc = 0;
        if (cudaOccupancyMaxActiveClusters(&nc, fused_kernel, &cfg) == cudaSuccess && nc >= 52 && nc < NCL) ncl = nc;
        (void)cudaGetLastError();
        ncl = tune("NCL", ncl);
        build_schedule(P, ncl);
        init = true;
    }
    fused_kernel<<<2 * ncl, 384, SMEM_LAUNCH>>>(P);
}
```

```cpp
#include <cuda_runtime.h>
#include <cuda.h>
#include <cuda_bf16.h>
#include <stdint.h>

namespace {

constexpr int NCTA = 132;
constexpr int NCL = NCTA / 2;
constexpr int MAXI = 16;
constexpr int NSTAT = 3;
constexpr uint32_t IT_DYN = 0xffffffffu;
constexpr int SLOT = 24576;
constexpr int NSLOT = 5;
constexpr int XS = 20480;
constexpr int OFF_R = 0;
constexpr int OFF_RING = 5 * XS;
constexpr int OFF_MISC = OFF_RING + NSLOT * SLOT;
constexpr int OFF_LX = OFF_MISC;
constexpr int OFF_LINV = OFF_LX + 2560;
constexpr int OFF_FB = OFF_LINV + 640;
constexpr int OFF_GM = OFF_FB + 16;
constexpr int OFF_BAR = OFF_GM + 16;
constexpr int BAR_RFULL = OFF_BAR;
constexpr int BAR_REMPTY = BAR_RFULL + 40;
constexpr int BAR_XFULL = BAR_REMPTY + 40;
constexpr int BAR_XEMPTY = BAR_XFULL + 40;
constexpr int BAR_PRDY = BAR_XEMPTY + 40;
constexpr int BAR_ITEM = BAR_PRDY + 40;
constexpr int OFF_ITEM = BAR_ITEM + MAXI * 8;
constexpr int SMEM_BYTES = OFF_ITEM + MAXI * 4;
static_assert(SMEM_BYTES <= 232448, "smem");

constexpr int NB_W = 1  , NB_PFULL = 3  , NB_VOTE = 5  , NB_Q2 = 7, NB_SDONE = 8, NB_PDONE = 9,
              NB_L = 10, NB_REF = 11, NB_ODONE = 12, NB_OPEND = 13, NB_LX = 14, NB_Q01 = 15, NB_QK = 0  ;

constexpr uint32_t IT_QA = 1, IT_OP = 2, IT_ON = 3;
__host__ __device__ constexpr uint32_t mk_item(uint32_t type, uint32_t br, uint32_t b, uint32_t h0, uint32_t h1, uint32_t half,
                                               uint32_t part = 0) {
    return type | (br << 2) | (b << 3) | (h0 << 7) | (h1 << 13) | (half << 19) | (part << 22);
}
#define IT_TYPE(e) ((e) & 3u)
#define IT_BR(e) (((e) >> 2) & 1u)
#define IT_B(e) (((e) >> 3) & 15u)
#define IT_H0(e) (((e) >> 7) & 63u)
#define IT_H1(e) (((e) >> 13) & 63u)
#define IT_HALF(e) (((e) >> 19) & 7u)
#define IT_PART(e) (((e) >> 22) & 1u)
#define IT_SLOT(e) IT_H1(e)
#define IT_DEP(e) (((e) >> 23) & 127u)

struct Params {
    CUtensorMap x[2], wq[2], k[2], v[2], wo[2], won[2], out;
    const __nv_bfloat16 *px[2], *pwq[2], *pk[2], *pv[2];
    struct alignas(16) { uint32_t delay, items[NSTAT]; } cl[NCL];
    uint32_t nlist;
    uint8_t slot[64];
    uint32_t list[568];
};

constexpr int OUNIT = 61440;
__device__ __align__(1024) unsigned char g_ostash[(size_t)1024 * OUNIT];
__device__ __align__(256) unsigned int g_flag[32 * 64];
__device__ __forceinline__ unsigned char* ostash(uint32_t slot, uint32_t b) { return g_ostash + (slot * 16 + b) * OUNIT; }
__device__ unsigned int g_epoch[NCTA * 4];
__device__ unsigned int g_ticket[2];

constexpr int SMEM_LAUNCH = SMEM_BYTES;
#define TS(role, idx)
#define TS_ITEM(e)
#define TS_DUMP(role)
#define TSD(role, idx)
#define TSO(t)

__device__ __forceinline__ uint64_t pol_stream() {
    uint64_t p;
    asm volatile("createpolicy.fractional.L2::evict_first.b64 %0, 1.0;" : "=l"(p));
    return p;
}
__device__ __forceinline__ uint64_t pol_shared() {
    uint64_t p;
    asm volatile("createpolicy.fractional.L2::evict_unchanged.b64 %0, 1.0;" : "=l"(p));
    return p;
}
constexpr int QHOLD = 8;
constexpr float SM_C = 0.07216878364870322f * 1.4426950408889634f;

__device__ __forceinline__ uint32_t next_epoch(int warp) {
    unsigned int* p = &g_epoch[blockIdx.x * 4 + warp];
    const uint32_t e = __ldcg(p) + 1;
    *p = e;
    return e;
}

__device__ __forceinline__ uint32_t tid_now() {
    uint32_t t;
    asm volatile("mov.u32 %0, %%tid.x;" : "=r"(t));
    return t;
}
__device__ __forceinline__ void mbar_init(uint32_t a, uint32_t c) {
    asm volatile("mbarrier.init.shared::cta.b64 [%0], %1;" ::"r"(a), "r"(c) : "memory");
}
__device__ __forceinline__ void mbar_expect(uint32_t a, uint32_t b) {
    asm volatile("mbarrier.arrive.expect_tx.shared::cta.b64 _, [%0], %1;" ::"r"(a), "r"(b) : "memory");
}
template <int CNT = 1>
__device__ __forceinline__ void mbar_arrive_warp(uint32_t a) {
    if (CNT == 1)
        asm volatile("{\n.reg .pred p;\nelect.sync _|p, 0xffffffff;\n@p mbarrier.arrive.shared::cta.b64 _, [%0];\n}" ::"r"(a) : "memory");
    else
        asm volatile(
            "{\n.reg .pred p;\nelect.sync _|p, 0xffffffff;\n@p mbarrier.arrive.shared::cta.b64 _, [%0];\n"
            "@p mbarrier.arrive.shared::cta.b64 _, [%0];\n}" ::"r"(a)
            : "memory");
}
template <int CNT = 1>
__device__ __forceinline__ void mbar_arrive_warp_if(uint32_t a, bool cond) {
    if (CNT == 1)
        asm volatile(
            "{\n.reg .pred p, c;\nelect.sync _|p, 0xffffffff;\nsetp.ne.and.u32 c, %1, 0, p;\n"
            "@c mbarrier.arrive.shared::cta.b64 _, [%0];\n}" ::"r"(a), "r"((uint32_t)cond)
            : "memory");
    else
        asm volatile(
            "{\n.reg .pred p, c;\nelect.sync _|p, 0xffffffff;\nsetp.ne.and.u32 c, %1, 0, p;\n"
            "@c mbarrier.arrive.shared::cta.b64 _, [%0];\n@c mbarrier.arrive.shared::cta.b64 _, [%0];\n}" ::"r"(a), "r"((uint32_t)cond)
            : "memory");
}
__device__ __forceinline__ uint32_t deadline() {
    uint32_t c;
    asm volatile("mov.u32 %0, %%clock_hi;" : "=r"(c));
    return c + 4;
}
__device__ __forceinline__ void mbar_wait(uint32_t a, uint32_t ph, uint32_t dl) {
    asm volatile(
        "{\n.reg .pred p;\n.reg .u32 m;\n"
        "LOOP:\n"
        "mbarrier.try_wait.parity.shared::cta.b64 p, [%0], %1;\n"
        "@p bra DONE;\n"
        "mov.u32 m, %%clock_hi;\n"
        "setp.ne.u32 p, m, %2;\n"
        "@p bra LOOP;\n"
        "trap;\n"
        "DONE:\n}" ::"r"(a), "r"(ph), "r"(dl)
        : "memory");
}
__device__ __forceinline__ bool mbar_test(uint32_t a, uint32_t ph) {
    uint32_t ok;
    asm volatile("{\n.reg .pred p;\nmbarrier.test_wait.parity.shared::cta.b64 p, [%1], %2;\nselp.u32 %0, 1, 0, p;\n}"
                 : "=r"(ok) : "r"(a), "r"(ph) : "memory");
    return __all_sync(0xffffffffu, ok);
}
__device__ __forceinline__ void mbar_wait2(uint32_t a, uint32_t pa, uint32_t b, uint32_t pb, uint32_t dl) {
    asm volatile(
        "{\n.reg .pred p, q;\n.reg .u32 m;\n"
        "LOOP:\n"
        "mbarrier.try_wait.parity.shared::cta.b64 p, [%0], %1;\n"
        "mbarrier.try_wait.parity.shared::cta.b64 q, [%2], %3;\n"
        "and.pred p, p, q;\n"
        "@p bra DONE;\n"
        "mov.u32 m, %%clock_hi;\n"
        "setp.ne.u32 p, m, %4;\n"
        "@p bra LOOP;\n"
        "trap;\n"
        "DONE:\n}" ::"r"(a), "r"(pa), "r"(b), "r"(pb), "r"(dl)
        : "memory");
}
template <int ID, int CNT>
__device__ __forceinline__ void nb_sync() { asm volatile("bar.sync %0, %1;" ::"n"(ID), "n"(CNT) : "memory"); }
template <int ID, int CNT>
__device__ __forceinline__ void nb_arrive() { asm volatile("bar.arrive %0, %1;" ::"n"(ID), "n"(CNT) : "memory"); }
__device__ __forceinline__ void fence_async_smem() { asm volatile("fence.proxy.async.shared::cta;" ::: "memory"); }

__device__ __forceinline__ void tma3(uint32_t dst, const CUtensorMap* m, int c1, int c2, uint32_t bar, uint64_t pol) {
    asm volatile(
        "cp.async.bulk.tensor.3d.shared::cluster.global.mbarrier::complete_tx::bytes.L2::cache_hint [%0], [%1, {%3,%4,%5}], [%2], %6;" ::"r"(dst),
        "l"(m), "r"(bar), "r"(0), "r"(c1), "r"(c2), "l"(pol)
        : "memory");
}
__device__ __forceinline__ void tma3_mc(uint32_t dst, const CUtensorMap* m, int c1, int c2, uint32_t bar, uint64_t pol) {
    asm volatile(
        "cp.async.bulk.tensor.3d.shared::cluster.global.mbarrier::complete_tx::bytes.multicast::cluster.L2::cache_hint"
        " [%0], [%1, {%3,%4,%5}], [%2], %6, %7;" ::"r"(dst),
        "l"(m), "r"(bar), "r"(0), "r"(c1), "r"(c2), "h"((unsigned short)3), "l"(pol)
        : "memory");
}
__device__ __forceinline__ void bulk_load(uint32_t dst, const void* src, uint32_t bytes, uint32_t bar, uint64_t pol) {
    asm volatile("cp.async.bulk.shared::cluster.global.mbarrier::complete_tx::bytes.L2::cache_hint [%0], [%1], %2, [%3], %4;" ::"r"(dst),
                 "l"(src), "r"(bytes), "r"(bar), "l"(pol)
                 : "memory");
}
__device__ __forceinline__ void wg_fence() { asm volatile("wgmma.fence.sync.aligned;" ::: "memory"); }
__device__ __forceinline__ void wg_commit() { asm volatile("wgmma.commit_group.sync.aligned;" ::: "memory"); }
template <int N>
__device__ __forceinline__ void wg_wait() { asm volatile("wgmma.wait_group.sync.aligned %0;" ::"n"(N) : "memory"); }

#define RW80(c, d) c(d[0]), c(d[1]), c(d[2]), c(d[3]), c(d[4]), c(d[5]), c(d[6]), c(d[7]), c(d[8]), c(d[9]), c(d[10]), c(d[11]), c(d[12]), c(d[13]), c(d[14]), c(d[15]), c(d[16]), c(d[17]), c(d[18]), c(d[19]), c(d[20]), c(d[21]), c(d[22]), c(d[23]), c(d[24]), c(d[25]), c(d[26]), c(d[27]), c(d[28]), c(d[29]), c(d[30]), c(d[31]), c(d[32]), c(d[33]), c(d[34]), c(d[35]), c(d[36]), c(d[37]), c(d[38]), c(d[39]), c(d[40]), c(d[41]), c(d[42]), c(d[43]), c(d[44]), c(d[45]), c(d[46]), c(d[47]), c(d[48]), c(d[49]), c(d[50]), c(d[51]), c(d[52]), c(d[53]), c(d[54]), c(d[55]), c(d[56]), c(d[57]), c(d[58]), c(d[59]), c(d[60]), c(d[61]), c(d[62]), c(d[63]), c(d[64]), c(d[65]), c(d[66]), c(d[67]), c(d[68]), c(d[69]), c(d[70]), c(d[71]), c(d[72]), c(d[73]), c(d[74]), c(d[75]), c(d[76]), c(d[77]), c(d[78]), c(d[79])
#define RW48(c, d) c(d[0]), c(d[1]), c(d[2]), c(d[3]), c(d[4]), c(d[5]), c(d[6]), c(d[7]), c(d[8]), c(d[9]), c(d[10]), c(d[11]), c(d[12]), c(d[13]), c(d[14]), c(d[15]), c(d[16]), c(d[17]), c(d[18]), c(d[19]), c(d[20]), c(d[21]), c(d[22]), c(d[23]), c(d[24]), c(d[25]), c(d[26]), c(d[27]), c(d[28]), c(d[29]), c(d[30]), c(d[31]), c(d[32]), c(d[33]), c(d[34]), c(d[35]), c(d[36]), c(d[37]), c(d[38]), c(d[39]), c(d[40]), c(d[41]), c(d[42]), c(d[43]), c(d[44]), c(d[45]), c(d[46]), c(d[47])
#define RW32(c, d) c(d[0]), c(d[1]), c(d[2]), c(d[3]), c(d[4]), c(d[5]), c(d[6]), c(d[7]), c(d[8]), c(d[9]), c(d[10]), c(d[11]), c(d[12]), c(d[13]), c(d[14]), c(d[15]), c(d[16]), c(d[17]), c(d[18]), c(d[19]), c(d[20]), c(d[21]), c(d[22]), c(d[23]), c(d[24]), c(d[25]), c(d[26]), c(d[27]), c(d[28]), c(d[29]), c(d[30]), c(d[31])

__device__ __forceinline__ void reg_fence(float (&d)[80]) { asm volatile("" : RW80("+f", d)::"memory"); }
__device__ __forceinline__ void reg_fence(float (&d)[48]) { asm volatile("" : RW48("+f", d)::"memory"); }
__device__ __forceinline__ void reg_fence(float (&d)[32]) { asm volatile("" : RW32("+f", d)::"memory"); }

template <int NR>
__device__ __forceinline__ void zero(float (&d)[NR]) {
#pragma unroll
    for (int i = 0; i < NR; i++) d[i] = 0.f;
}

constexpr uint32_t HI_SW128 = (1024u >> 4) | (1u << 30);
constexpr uint32_t HI_KV = (3072u >> 4) | (1u << 30);
constexpr uint32_t HI_OST = (2560u >> 4) | (2u << 30);
constexpr uint32_t LO_LBO1 = (1u << 16);
constexpr uint32_t LO_OST = ((512u >> 4) << 16);

template <int TA, int TB, uint32_t HIB, int ACC, uint32_t HIA = HI_SW128>
__device__ __forceinline__ void wgmma(float (&d)[80], uint32_t loA, uint32_t loB) {
#define WG_ASM(SD)                                                          \
    "{\n.reg .b64 da, db;\nmov.b64 da, {%80, %82};\nmov.b64 db, {%81, %83};\n" \
    "wgmma.mma_async.sync.aligned.m64n160k16.f32.bf16.bf16 "               \
    "{%0,%1,%2,%3,%4,%5,%6,%7,%8,%9,%10,%11,%12,%13,%14,%15,%16,%17,%18,%19,%20,%21,%22,%23,%24,%25,%26,%27,%28,%29,%30,%31,%32,%33,%34,%35,%36,%37,%38,%39,%40,%41,%42,%43,%44,%45,%46,%47,%48,%49,%50,%51,%52,%53,%54,%55,%56,%57,%58,%59,%60,%61,%62,%63,%64,%65,%66,%67,%68,%69,%70,%71,%72,%73,%74,%75,%76,%77,%78,%79}, da, db, " SD ", 1, 1, %84, %85;\n}"
    if constexpr (ACC == 2)
        asm volatile(WG_ASM("0") : RW80("+f", d) : "r"(loA), "r"(loB), "n"(HIA), "n"(HIB), "n"(TA), "n"(TB));
    else if constexpr (ACC == 1)
        asm volatile(WG_ASM("1") : RW80("+f", d) : "r"(loA), "r"(loB), "n"(HIA), "n"(HIB), "n"(TA), "n"(TB));
    else
        asm volatile(WG_ASM("0") : RW80("=f", d) : "r"(loA), "r"(loB), "n"(HIA), "n"(HIB), "n"(TA), "n"(TB));
#undef WG_ASM
}
template <int TA, int TB, uint32_t HIB, int ACC, uint32_t HIA = HI_SW128>
__device__ __forceinline__ void wgmma(float (&d)[48], uint32_t loA, uint32_t loB) {
#define WG_ASM(SD)                                                          \
    "{\n.reg .b64 da, db;\nmov.b64 da, {%48, %50};\nmov.b64 db, {%49, %51};\n" \
    "wgmma.mma_async.sync.aligned.m64n96k16.f32.bf16.bf16 "               \
    "{%0,%1,%2,%3,%4,%5,%6,%7,%8,%9,%10,%11,%12,%13,%14,%15,%16,%17,%18,%19,%20,%21,%22,%23,%24,%25,%26,%27,%28,%29,%30,%31,%32,%33,%34,%35,%36,%37,%38,%39,%40,%41,%42,%43,%44,%45,%46,%47}, da, db, " SD ", 1, 1, %52, %53;\n}"
    if constexpr (ACC == 1)
        asm volatile(WG_ASM("1") : RW48("+f", d) : "r"(loA), "r"(loB), "n"(HIA), "n"(HIB), "n"(TA), "n"(TB));
    else
        asm volatile(WG_ASM("0") : RW48("=f", d) : "r"(loA), "r"(loB), "n"(HIA), "n"(HIB), "n"(TA), "n"(TB));
#undef WG_ASM
}
template <int TA, int TB, uint32_t HIB, int ACC, uint32_t HIA = HI_SW128>
__device__ __forceinline__ void wgmma(float (&d)[32], uint32_t loA, uint32_t loB) {
#define WG_ASM(SD)                                                          \
    "{\n.reg .b64 da, db;\nmov.b64 da, {%32, %34};\nmov.b64 db, {%33, %35};\n" \
    "wgmma.mma_async.sync.aligned.m64n64k16.f32.bf16.bf16 "               \
    "{%0,%1,%2,%3,%4,%5,%6,%7,%8,%9,%10,%11,%12,%13,%14,%15,%16,%17,%18,%19,%20,%21,%22,%23,%24,%25,%26,%27,%28,%29,%30,%31}, da, db, " SD ", 1, 1, %36, %37;\n}"
    if constexpr (ACC == 1)
        asm volatile(WG_ASM("1") : RW32("+f", d) : "r"(loA), "r"(loB), "n"(HIA), "n"(HIB), "n"(TA), "n"(TB));
    else
        asm volatile(WG_ASM("0") : RW32("=f", d) : "r"(loA), "r"(loB), "n"(HIA), "n"(HIB), "n"(TA), "n"(TB));
#undef WG_ASM
}

__device__ __forceinline__ uint32_t pack_bf16(float lo, float hi) {
    uint32_t r;
    asm("cvt.rn.bf16x2.f32 %0, %1, %2;" : "=r"(r) : "f"(hi), "f"(lo));
    return r;
}
__device__ __forceinline__ float ex2(float x) {
    float r;
    asm("ex2.approx.ftz.f32 %0, %1;" : "=f"(r) : "f"(x));
    return r;
}
__device__ __forceinline__ void stsm4t(uint32_t a, uint32_t r0, uint32_t r1, uint32_t r2, uint32_t r3) {
    asm volatile("stmatrix.sync.aligned.m8n8.x4.trans.shared.b16 [%0], {%1,%2,%3,%4};" ::"r"(a), "r"(r0), "r"(r1), "r"(r2), "r"(r3)
                 : "memory");
}
__device__ __forceinline__ uint32_t lds_u(uint32_t a) {
    uint32_t v;
    asm volatile("ld.shared.u32 %0, [%1];" : "=r"(v) : "r"(a) : "memory");
    return v;
}
__device__ __forceinline__ uint4 lds_u4(uint32_t a) {
    uint4 v;
    asm volatile("ld.shared.v4.u32 {%0,%1,%2,%3}, [%4];" : "=r"(v.x), "=r"(v.y), "=r"(v.z), "=r"(v.w) : "r"(a) : "memory");
    return v;
}
__device__ __forceinline__ float2 lds_f2(uint32_t a) {
    float2 v;
    asm volatile("ld.shared.v2.f32 {%0,%1}, [%2];" : "=f"(v.x), "=f"(v.y) : "r"(a) : "memory");
    return v;
}
__device__ __forceinline__ void sts_f(uint32_t a, float v) { asm volatile("st.shared.f32 [%0], %1;" ::"r"(a), "f"(v) : "memory"); }
__device__ __forceinline__ void sts_u(uint32_t a, uint32_t v) { asm volatile("st.shared.u32 [%0], %1;" ::"r"(a), "r"(v) : "memory"); }
__device__ __forceinline__ void sts_f2(uint32_t a, float x, float y) {
    asm volatile("st.shared.v2.f32 [%0], {%1,%2};" ::"r"(a), "f"(x), "f"(y) : "memory");
}

template <bool SIG = false, int NR>
__device__ __forceinline__ void store_tile_t(const float (&d)[NR], uint32_t addr) {
#pragma unroll
    for (int j = 0; j < NR / 8; j++) {
        stsm4t(addr + j * 2048, pack_bf16(d[8 * j], d[8 * j + 1]), pack_bf16(d[8 * j + 2], d[8 * j + 3]),
               pack_bf16(d[8 * j + 4], d[8 * j + 5]), pack_bf16(d[8 * j + 6], d[8 * j + 7]));
        if (SIG && j == 0) nb_arrive<NB_L, 160>();
    }
}

struct TrueT { static constexpr bool value = true; };
struct FalseT { static constexpr bool value = false; };

template <int V>
struct IntT { static constexpr int value = V; };

__device__ __forceinline__ uint32_t get_item(uint32_t sb, int it, uint32_t dl) {
    mbar_wait(sb + BAR_ITEM + it * 8, 0, dl);
    return lds_u(sb + OFF_ITEM + it * 4);
}
__device__ __forceinline__ uint32_t get_item_warp(uint32_t sb, int it, uint32_t dl) {
    return __shfl_sync(0xffffffffu, get_item(sb, it, dl), 0);
}

struct Ring {
    uint32_t slot, ph, dl;
    __device__ __forceinline__ void adv(uint32_t k) {
        slot += k;
        if (slot >= NSLOT) { slot -= NSLOT; ph ^= 1; }
    }
};

template <int K>
__device__ __forceinline__ void qk_step(float (&s)[80], uint32_t loK, uint32_t loQ) {
    wgmma<0, 0, HI_SW128, K != 0, HI_KV>(s, loK + (K >> 2) * 64 + (K & 3) * 2, loQ + (K >> 2) * (XS >> 4) + (K & 3) * 2);
}
template <int K0, int K1>
__device__ __forceinline__ void qk_steps(float (&s)[80], uint32_t loK, uint32_t loQ) {
    if constexpr (K0 < K1) {
        qk_step<K0>(s, loK, loQ);
        qk_steps<K0 + 1, K1>(s, loK, loQ);
    }
}
__device__ __forceinline__ uint32_t add_bf2(uint32_t a, uint32_t b) {
    uint32_t r;
    asm("add.rn.bf16x2 %0, %1, %2;" : "=r"(r) : "r"(a), "r"(b));
    return r;
}
__device__ __forceinline__ uint32_t fma_bf2(uint32_t a, uint32_t b, uint32_t c) {
    uint32_t r;
    asm("fma.rn.bf16x2 %0, %1, %2, %3;" : "=r"(r) : "r"(a), "r"(b), "r"(c));
    return r;
}
template <int J>
__device__ __forceinline__ void exp_block(const float (&s)[80], uint32_t (&k)[40], uint32_t pa, float mref) {
    if constexpr (J < 10) {
#pragma unroll
        for (int i = 4 * J; i < 4 * J + 4; i++)
            k[i] = pack_bf16(ex2(fmaf(s[2 * i], SM_C, -mref)), ex2(fmaf(s[2 * i + 1], SM_C, -mref)));
#pragma unroll
        for (int i = 0; i < 4; i++)
            asm volatile("stmatrix.sync.aligned.m8n8.x1.trans.shared.b16 [%0], {%1};" ::"r"(((i & 1) ? pa ^ 16 : pa) + J * 2048 + (i >> 1) * 1024),
                         "r"(k[4 * J + i])
                         : "memory");
        exp_block<J + 1>(s, k, pa, mref);
    }
}
__device__ __forceinline__ void sum_block(const uint32_t (&k)[40], float (&l)[10], uint32_t lane) {
    const bool b4 = lane & 16, b3 = lane & 8;
    uint32_t ps[20], t[10];
#pragma unroll
    for (int j = 0; j < 20; j++) ps[j] = add_bf2(k[2 * j], k[2 * j + 1]);
#pragma unroll
    for (int j = 0; j < 10; j++)
        t[j] = add_bf2(b4 ? ps[2 * j + 1] : ps[2 * j], __shfl_xor_sync(0xffffffffu, b4 ? ps[2 * j] : ps[2 * j + 1], 16));
#pragma unroll
    for (int i = 0; i < 5; i++) {
        const uint32_t a = b3 ? t[i + 5] : t[i], b = __shfl_xor_sync(0xffffffffu, b3 ? t[i] : t[i + 5], 8);
        l[2 * i] += __uint_as_float(a << 16) + __uint_as_float(b << 16);
        l[2 * i + 1] += __uint_as_float(a & 0xffff0000u) + __uint_as_float(b & 0xffff0000u);
    }
}
template <bool ADD>
__device__ __forceinline__ void sum_store(const float (&l)[10], uint32_t lane, uint32_t lxa) {
    const bool b2 = lane & 4;
    float t[5];
#pragma unroll
    for (int i = 0; i < 5; i++) t[i] = ADD ? __uint_as_float(lds_u(lxa + i * 64)) : 0.f;
#pragma unroll
    for (int i = 0; i < 5; i++)
        sts_f(lxa + i * 64, t[i] + (b2 ? l[2 * i + 1] : l[2 * i]) + __shfl_xor_sync(0xffffffffu, b2 ? l[2 * i] : l[2 * i + 1], 4));
}

__device__ __forceinline__ void fallback_unit(const Params& P, uint32_t e, uint32_t tid) {
    const uint32_t lane = tid & 31, br = IT_BR(e), b = IT_B(e), h = IT_H0(e);
    const __nv_bfloat162* wq = (const __nv_bfloat162*)(P.pwq[br] + h * 192) + lane;
    const __nv_bfloat162* kp = (const __nv_bfloat162*)(P.pk[br] + (size_t)(b * 32 + h) * 512 * 192) + lane;
    const __nv_bfloat162* vp = (const __nv_bfloat162*)(P.pv[br] + (size_t)(b * 32 + h) * 512 * 192) + lane;
#pragma unroll 1
    for (uint32_t qi = 0; qi < 40; qi++) {
        const uint32_t q = 4 * qi + (tid >> 5);
        const __nv_bfloat16* xr = P.px[br] + (size_t)(b * 160 + q) * 640;
        float a[6] = {0.f, 0.f, 0.f, 0.f, 0.f, 0.f};
#pragma unroll 2
        for (int k = 0; k < 640; k++) {
            const float xv = __bfloat162float(xr[k]);
#pragma unroll
            for (int i = 0; i < 3; i++) {
                const float2 wv = __bfloat1622float2(wq[(size_t)k * 3072 + i * 32]);
                a[2 * i] = fmaf(xv, wv.x, a[2 * i]);
                a[2 * i + 1] = fmaf(xv, wv.y, a[2 * i + 1]);
            }
        }
#pragma unroll
        for (int i = 0; i < 6; i++) a[i] = __bfloat162float(__float2bfloat16(a[i]));
        auto score = [&](int key) {
            float d = 0.f;
#pragma unroll
            for (int i = 0; i < 3; i++) {
                const float2 kv = __bfloat1622float2(kp[key * 96 + i * 32]);
                d = fmaf(a[2 * i], kv.x, fmaf(a[2 * i + 1], kv.y, d));
            }
#pragma unroll
            for (int o = 16; o > 0; o >>= 1) d += __shfl_xor_sync(0xffffffffu, d, o);
            return d;
        };
        float m = -INFINITY, o[6] = {0.f, 0.f, 0.f, 0.f, 0.f, 0.f}, sum = 0.f;
#pragma unroll 1
        for (int n = 0; n < 1024; n++) {
            const int key = n & 511;
            const float d = score(key);
            if (n < 512) {
                m = fmaxf(m, d);
            } else {
                const float p = ex2((d - m) * SM_C);
                sum += p;
#pragma unroll
                for (int i = 0; i < 3; i++) {
                    const float2 vv = __bfloat1622float2(vp[key * 96 + i * 32]);
                    o[2 * i] = fmaf(p, vv.x, o[2 * i]);
                    o[2 * i + 1] = fmaf(p, vv.y, o[2 * i + 1]);
                }
            }
        }
        const float inv = __fdividef(1.f, sum);
        __nv_bfloat16* op = (__nv_bfloat16*)ostash(IT_SLOT(e), b) + (q >> 5) * 256 + 2 * ((q & 31) >> 3) + (q & 1);
#pragma unroll
        for (int i = 0; i < 6; i++) {
            const uint32_t d = (i >> 1) * 64 + 2 * lane + (i & 1);
            op[(d >> 3) * 1280 + (d & 7) * 32 + ((((q & 7) >> 1) ^ ((d & 7) >> 1)) << 3)] = __float2bfloat16(o[i] * inv);
        }
    }
}

struct PendO {
    uint32_t v[64];
    unsigned char* gp;
    static __device__ __forceinline__ uint32_t toff() {
        const uint32_t t = tid_now();
        return ((t >> 5) & 3) * 5120 + ((t >> 2) & 7) * 64 + (((t ^ (t >> 3)) & 3) << 4);
    }
    uint32_t pend, sig, bad;
    static __device__ __forceinline__ void scale(uint32_t& x, uint32_t hi, uint32_t lo) {
        asm("{\n.reg .b32 t;\nmul.rn.bf16x2 t, %0, %2;\nfma.rn.bf16x2 %0, %0, %1, t;\n}" : "+r"(x) : "r"(hi), "r"(lo));
    }
    template <int I, int OFF>
    __device__ __forceinline__ void put() {
        asm volatile("{\n.reg .pred p;\nsetp.ne.u32 p, %6, 0;\n@p st.global.v4.b32 [%0+%5], {%1,%2,%3,%4};\n}" ::"l"(gp), "r"(v[I]),
                     "r"(v[I + 1]), "r"(v[I + 2]), "r"(v[I + 3]), "n"(OFF), "r"(pend)
                     : "memory");
    }
    __device__ __forceinline__ void verdict(uint32_t sb, uint32_t W) {
        if (sig) {
            asm volatile("bar.sync %0, 160;" ::"r"(NB_VOTE + W) : "memory");
            bad = __any_sync(0xffffffffu, lds_u(sb + OFF_FB) != 0);
            pend = !bad;
        }
    }
    template <int W, int G, int H>
    __device__ __forceinline__ void half(uint32_t sb) {
        constexpr bool T2 = W == 0 ? G >= 3 : G < 3;
        constexpr int B = T2 ? 40 + 8 * (W == 0 ? G - 3 : G) : 0;
        const uint4 a = lds_u4(sb + OFF_LINV + G * 128 + H * 16 + (threadIdx.x & 3) * 32);
#pragma unroll
        for (int i = 2 * H; i < 8; i += 4) {
            scale(v[8 * G + i], a.x, a.y);
            scale(v[8 * G + i + 1], a.z, a.w);
            if (T2) {
                scale(v[B + i], a.x, a.y);
                scale(v[B + i + 1], a.z, a.w);
            }
        }
        if (H == 1) {
            put<8 * G, W * XS + G * 512>();
            put<8 * G + 4, W * XS + G * 512 + 2560>();
            if (T2) {
                put<B, 2 * XS + G * 512>();
                put<B + 4, 2 * XS + G * 512 + 2560>();
            }
            if (G == 4 && pend) nb_arrive<NB_ODONE, 288>();
        }
    }
    template <int W, int G>
    __device__ __forceinline__ void step(uint32_t sb) {
        half<W, G, 0>(sb);
        half<W, G, 1>(sb);
    }
    template <int W>
    __device__ __forceinline__ void flush(uint32_t sb) {
        step<W, 0>(sb);
        step<W, 1>(sb);
        step<W, 2>(sb);
        step<W, 3>(sb);
        step<W, 4>(sb);
    }
    __device__ __forceinline__ void clear() {
#pragma unroll
        for (int i = 0; i < 64; i++) v[i] = 0;
        gp = nullptr;
        pend = 0;
        sig = 0;
        bad = 0;
    }
};

__device__ __forceinline__ uint32_t stsm_off() {
    const uint32_t tid = tid_now(), lane = tid & 31;
    return (lane >> 4) * 1024 + (lane & 7) * 128 + (((((tid >> 4) & 6) + ((lane >> 3) & 1)) ^ (lane & 7)) << 4);
}
__device__ __forceinline__ void q_ahead(float (&q0)[80], uint32_t sb, const Ring& rn, uint32_t phm, bool valid) {
    if (valid) mbar_wait2(sb + BAR_RFULL + rn.slot * 8, rn.ph, sb + BAR_XFULL, phm & 1, rn.dl);
    const uint32_t a = ((((sb + OFF_RING) & 0x3ffff) >> 4) | LO_LBO1) + rn.slot * (SLOT >> 4);
    const uint32_t b = (((sb + OFF_R) & 0x3ffff) >> 4) | LO_LBO1;
    wg_fence();
    wgmma<1, 0, HI_SW128, false>(q0, a, b);
#pragma unroll
    for (int k = 1; k < 4; k++) wgmma<1, 0, HI_SW128, true>(q0, a + (k >> 1) * 768 + (k & 1) * 128, b + k * 2);
    wg_commit();
}
template <int W, int KK>
__device__ __forceinline__ void qproj(float (&q0)[80], float (&q1)[80], uint32_t sb, Ring& r, uint32_t pslot, uint32_t phm,
                                      PendO& po) {
    const uint32_t loR = (((sb + OFF_R) & 0x3ffff) >> 4) | LO_LBO1;
    const uint32_t loRing = (((sb + OFF_RING) & 0x3ffff) >> 4) | LO_LBO1;
    auto ready = [&](int k) {
        mbar_wait2(sb + BAR_RFULL + r.slot * 8, r.ph, sb + BAR_XFULL + (k % 5) * 8, ((phm >> (k % 5)) ^ (k / 5)) & 1, r.dl);
    };
    auto release = [&]() {
        if (KK > 0) {
            wg_wait<1>();
            mbar_arrive_warp(sb + BAR_REMPTY + pslot * 8);
            if (KK <= 5) mbar_arrive_warp(sb + (BAR_XEMPTY + (KK - 1) * 8));
        }
    };
    if (KK == 0 && W == 1) ready(0);
    if (W == 1 && KK == QHOLD) nb_sync<NB_SDONE, 256>();
    const uint32_t a = loRing + r.slot * (SLOT >> 4) + (W == 0 ? 0 : 512), b = loR + (KK % 5) * (XS >> 4);
    wg_fence();
    constexpr bool T0 = W == 1 || KK > 0;
    if (T0) wgmma<1, 0, HI_SW128, KK != 0>(q0, a, b);
    if (W == 0) wgmma<1, 0, HI_SW128, KK != 0 ? 1 : 2>(q1, a + 256, b);
#pragma unroll
    for (int k = 1; k < 4; k++) {
        if (T0) wgmma<1, 0, HI_SW128, true>(q0, a + (k >> 1) * 768 + (k & 1) * 128, b + k * 2);
        if (W == 0) wgmma<1, 0, HI_SW128, true>(q1, a + 256 + (k >> 1) * 768 + (k & 1) * 128, b + k * 2);
    }
    wg_commit();
    const uint32_t cslot = r.slot;
    r.adv(1);
    if (W == 0 || KK < QHOLD) release();
    constexpr int QST = W == 0 ? 2 : 1;
    if (KK == QST) {
        po.verdict(sb, W);
        po.template half<W, 0, 0>(sb);
    }
    if (KK < 9) ready(KK + 1);
    if (W == 1 && KK >= QHOLD) release();
    if (W == 1 && KK == 7) nb_arrive<NB_PDONE, 256>();
    if (KK == QST) po.template half<W, 0, 1>(sb);
    if constexpr (KK > QST && KK < QST + 5) po.template step<W, KK - QST>(sb);
    if constexpr (KK < (W == 0 ? 7 : 9)) {
        qproj<W, KK + 1>(q0, q1, sb, r, cslot, phm, po);
    } else if constexpr (W == 1) {
        const uint32_t sta = sb + OFF_R + 2 * XS + stsm_off();
        wg_wait<0>();
        reg_fence(q0);
        store_tile_t<true>(q0, sta);
        mbar_arrive_warp(sb + BAR_REMPTY + cslot * 8);
    } else {
        const uint32_t s8 = r.slot, a8 = loRing + s8 * (SLOT >> 4);
        wg_fence();
#pragma unroll
        for (int k = 0; k < 4; k++) wgmma<1, 0, HI_SW128, true>(q0, a8 + (k >> 1) * 768 + (k & 1) * 128, loR + 3 * (XS >> 4) + k * 2);
        r.adv(1);
        ready(9);
        const uint32_t s9 = r.slot, a9 = loRing + s9 * (SLOT >> 4);
        r.adv(1);
        wg_fence();
#pragma unroll
        for (int k = 0; k < 4; k++) wgmma<1, 0, HI_SW128, true>(q0, a9 + (k >> 1) * 768 + (k & 1) * 128, loR + 4 * (XS >> 4) + k * 2);
        wg_commit();
        wg_wait<1>();
        mbar_arrive_warp(sb + BAR_REMPTY + cslot * 8);
        wg_fence();
#pragma unroll
        for (int k = 0; k < 8; k++)
            wgmma<1, 0, HI_SW128, true>(q1, (k < 4 ? a8 : a9) + 256 + ((k >> 1) & 1) * 768 + (k & 1) * 128,
                                        loR + (3 + (k >> 2)) * (XS >> 4) + (k & 3) * 2);
        wg_commit();
        nb_arrive<NB_SDONE, 256>();
        sts_u(sb + OFF_GM + 4, r.slot);
        nb_sync<NB_PDONE, 256>();
        wg_wait<1>();
        reg_fence(q0);
        const uint32_t sta = sb + OFF_R + stsm_off();
        store_tile_t(q0, sta);
        wg_wait<0>();
        reg_fence(q1);
        mbar_arrive_warp(sb + BAR_REMPTY + s8 * 8);
        mbar_arrive_warp(sb + BAR_REMPTY + s9 * 8);
        store_tile_t(q1, sta + XS);
        mbar_wait(sb + BAR_RFULL + r.slot * 8, r.ph, r.dl);
    }
}

template <int NR>
__device__ __forceinline__ void opack(const float (&o)[NR], uint32_t* v) {
#pragma unroll
    for (int g = 0; g < NR / 16; g++)
#pragma unroll
        for (int hh = 0; hh < 2; hh++)
#pragma unroll
            for (int t = 0; t < 4; t++) v[8 * g + 4 * hh + t] = pack_bf16(o[16 * g + 4 * t + 2 * hh], o[16 * g + 4 * t + 2 * hh + 1]);
}

__device__ __forceinline__ void out_store(const Params& P, uint32_t src, int col, int b) {
    asm volatile("cp.async.bulk.tensor.5d.global.shared::cta.bulk_group [%0, {%2,%4,%4,%4,%3}], [%1];" ::"l"(&P.out), "r"(src),
                 "r"(col), "r"(b * 5), "r"(0)
                 : "memory");
    asm volatile("cp.async.bulk.commit_group;" ::: "memory");
}

template <bool IS_S>
__device__ __forceinline__ void op_item(uint32_t e, uint32_t sb, Ring& r, uint32_t& phm) {
    constexpr int T0 = IS_S ? 0 : 2;
    constexpr uint32_t BOFF = IS_S ? (3 * 512) >> 4 : 0;
    const uint32_t loRing = (((sb + OFF_RING) & 0x3ffff) >> 4) | LO_LBO1;
    const uint32_t loO = (((sb + OFF_R) & 0x3ffff) >> 4) | LO_OST;
    float c0[80], c1[80], c2[IS_S ? 32 : 48];
    const int T = 3 * (IT_H1(e) - IT_H0(e));
    uint32_t xs = 0;
    auto step = [&](auto first, auto half) {
        constexpr bool F = decltype(first)::value;
        constexpr uint32_t hf = decltype(half)::value;
        if (hf == 0) {
            mbar_wait(sb + BAR_XFULL + xs * 8, (phm >> xs) & 1, r.dl);
            phm ^= 1u << xs;
        }
        mbar_wait(sb + BAR_RFULL + r.slot * 8, r.ph, r.dl);
        const uint32_t a = loRing + r.slot * (SLOT >> 4), b = loO + xs * (XS >> 4) + hf * 640;
        wg_fence();
        wgmma<1, 1, HI_OST, !F>(c0, a + T0 * 128, b);
        wgmma<1, 1, HI_OST, !F>(c1, a + T0 * 128 + 128, b);
        wgmma<1, 1, HI_OST, !F>(c2, a + 512, b + BOFF);
        wgmma<1, 1, HI_OST, true>(c0, a + 640 + T0 * 128, b + 320);
        wgmma<1, 1, HI_OST, true>(c1, a + 640 + T0 * 128 + 128, b + 320);
        wgmma<1, 1, HI_OST, true>(c2, a + 640 + 512, b + 320 + BOFF);
        wg_commit();
    };
    step(TrueT{}, IntT<0>{});
#pragma unroll 1
    for (int t = 1;; t++) {
        uint32_t pslot = r.slot;
        r.adv(1);
        step(FalseT{}, IntT<1>{});
        wg_wait<1>();
        mbar_arrive_warp(sb + BAR_REMPTY + pslot * 8);
        if (t == T) break;
        pslot = r.slot;
        const uint32_t pxs = xs;
        r.adv(1);
        if (++xs == 5) xs = 0;
        step(FalseT{}, IntT<0>{});
        wg_wait<1>();
        mbar_arrive_warp(sb + BAR_REMPTY + pslot * 8);
        mbar_arrive_warp_if(sb + BAR_XEMPTY + pxs * 8, t + 4 < T);
    }
    wg_wait<0>();
    reg_fence(c0);
    reg_fence(c1);
    reg_fence(c2);
    mbar_arrive_warp(sb + BAR_REMPTY + r.slot * 8);
    r.adv(1);
    nb_sync<NB_OPEND, 256>();
    const uint32_t sta = sb + OFF_R + stsm_off();
    store_tile_t(c0, sta + T0 * XS);
    store_tile_t(c1, sta + (T0 + 1) * XS);
    store_tile_t(c2, sta + 4 * XS + (IS_S ? 96 * 128 : 0));
    fence_async_smem();
    nb_arrive<NB_ODONE, 288>();
}

__device__ __forceinline__ void on_item(const Params& P, uint32_t W, uint32_t e, uint32_t sb, Ring& r, uint32_t& phm, int it) {
    const uint32_t loRing = (((sb + OFF_RING) & 0x3ffff) >> 4) | LO_LBO1;
    const uint32_t loO = (((sb + OFF_R) & 0x3ffff) >> 4) | LO_OST;
    float c[80];
    const int T = 3 * (IT_H1(e) - IT_H0(e));
    uint32_t xs = 0;
    auto step = [&](auto first) {
        constexpr bool F = decltype(first)::value;
        mbar_wait2(sb + BAR_XFULL + xs * 8, (phm >> xs) & 1, sb + BAR_RFULL + r.slot * 8, r.ph, r.dl);
        phm ^= 1u << xs;
        const uint32_t a = loRing + r.slot * (SLOT >> 4) + W * 256, b = loO + xs * (XS >> 4);
        if (!F) wg_wait<0>();
        wg_fence();
        wgmma<1, 1, HI_OST, !F>(c, a, b);
#pragma unroll
        for (int k = 1; k < 4; k++) wgmma<1, 1, HI_OST, true>(c, a + (k >> 1) * 512 + (k & 1) * 128, b + k * 320);
        wg_commit();
    };
    step(TrueT{});
#pragma unroll 1
    for (int t = 1; t < T; t++) {
        const uint32_t pslot = r.slot, pxs = xs;
        r.adv(1);
        if (++xs == 5) xs = 0;
        if (W == 1 && t == T - 2) nb_sync<NB_OPEND, 256>();
        step(FalseT{});
        TSO(t);
        if (W == 0 && t == T - 1) nb_arrive<NB_OPEND, 256>();
        mbar_arrive_warp(sb + BAR_REMPTY + pslot * 8);
        mbar_arrive_warp_if(sb + BAR_XEMPTY + pxs * 8, t + 2 < T);
    }
    xs += 1 + W;
    if (xs >= 5) xs -= 5;
    mbar_wait(sb + BAR_XFULL + xs * 8, (phm >> xs) & 1, r.dl);
    const uint32_t sta = sb + OFF_R + xs * XS + stsm_off();
    uint32_t p[40];
#pragma unroll
    for (int j = 0; j < 10; j++)
        asm volatile("ldmatrix.sync.aligned.m8n8.x4.trans.shared.b16 {%0,%1,%2,%3}, [%4];"
                     : "=r"(p[4 * j]), "=r"(p[4 * j + 1]), "=r"(p[4 * j + 2]), "=r"(p[4 * j + 3])
                     : "r"(sta + j * 2048)
                     : "memory");
    wg_wait<0>();
    reg_fence(c);
#pragma unroll
    for (int k = 0; k < 40; k++) {
        c[2 * k] += __uint_as_float(p[k] << 16);
        c[2 * k + 1] += __uint_as_float(p[k] & 0xffff0000u);
    }
    store_tile_t(c, sta);
    fence_async_smem();
    asm volatile("bar.sync %0, 128;" ::"r"(NB_W + W) : "memory");
    if ((tid_now() & 127) == 0) {
        out_store(P, sb + OFF_R + xs * XS, IT_BR(e) * 640 + (2 * IT_HALF(e) + W) * 64, IT_B(e));
        asm volatile("cp.async.bulk.wait_group 0;" ::: "memory");
    }
    __syncwarp();
}

template <int W>
__device__ __forceinline__ uint32_t qa_item(uint32_t e, uint32_t sb, Ring& r, uint32_t phm, PendO& po, float (&q0)[80],
                                            float (&oa)[80], int it) {
    const uint32_t loR = (((sb + OFF_R) & 0x3ffff) >> 4) | LO_LBO1;
    const uint32_t loRing = (((sb + OFF_RING) & 0x3ffff) >> 4) | LO_LBO1;
    qproj<W, 0>(q0, oa, sb, r, 0, phm, po);
    fence_async_smem();
    TSD(W, 1);
    float s[80], ob[W == 0 ? 32 : 48], l[10];
    if (W == 1) {
        nb_arrive<NB_Q2, 256>();
        zero(oa);
        zero(ob);
        reg_fence(oa);
        reg_fence(ob);
    }
    const uint32_t lane = tid_now() & 31, sta = sb + OFF_R + stsm_off();
    auto pv = [&](auto first, uint32_t buf) {
        constexpr bool F = decltype(first)::value;
        if (F) mbar_wait(sb + BAR_RFULL + r.slot * 8, r.ph, r.dl);
        const uint32_t a = loRing + r.slot * (SLOT >> 4), b = loR + (3 + buf) * (XS >> 4);
        wg_fence();
        wgmma<1, 0, HI_SW128, F ? 2 : 1, HI_KV>(oa, a + W * 64, b);
        wgmma<1, 0, HI_SW128, !F, HI_KV>(ob, a + 128, b + (W == 0 ? (96 * 128) >> 4 : 0));
#pragma unroll
        for (int k = 1; k < 4; k++) {
            wgmma<1, 0, HI_SW128, true, HI_KV>(oa, a + W * 64 + k * 384, b + k * 2);
            wgmma<1, 0, HI_SW128, true, HI_KV>(ob, a + 128 + k * 384, b + (W == 0 ? (96 * 128) >> 4 : 0) + k * 2);
        }
        wg_commit();
    };
    zero(l);
    float mref;
    uint32_t kslot, vslot, nx = 0;
    auto tail = [&](auto first, int i) {
        constexpr bool rel_other = !decltype(first)::value;
        uint32_t ps[40];
        exp_block<0>(s, ps, sta + (3 + W) * XS, mref);
        if (rel_other) {
            wg_wait<0>();
            mbar_arrive_warp(sb + BAR_REMPTY + vslot * 8);
            if (W == 1) mbar_arrive_warp_if(sb + BAR_XEMPTY + 24, i == 3);
        }
        fence_async_smem();
        nb_arrive<NB_PFULL + W, 256>();
        TSD(W, 6 + 5 * i);
        if (W == 1) {
            mbar_arrive_warp_if<2>(sb + BAR_XEMPTY + 8, i == 3);
            mbar_arrive_warp_if<2>(sb + BAR_XEMPTY + 16, i == 3);
        }
        if (rel_other) {
            mbar_wait(sb + BAR_RFULL + r.slot * 8, r.ph, r.dl);
            sum_block(ps, l, lane);
        }
        if (W == 0 && i == 3) nx = get_item_warp(sb, it + 1, r.dl);
        TSD(W, 7 + 5 * i);
        nb_sync<NB_W + W, 128>();
        pv(first, W);
        if (!rel_other) sum_block(ps, l, lane);
        TSD(W, 8 + 5 * i);
    };
    if (W == 0) {
        nb_sync<NB_QK, 160>();
        TSD(W, 2);
        wg_fence();
        qk_steps<0, 8>(s, loRing + r.slot * (SLOT >> 4), loR);
        nb_sync<NB_Q2, 256>();
        qk_steps<8, 12>(s, loRing + r.slot * (SLOT >> 4), loR);
        wg_commit();
        nb_arrive<NB_Q01, 256>();
        TSD(W, 4);
        nb_sync<NB_REF, 160>();
        mref = __uint_as_float(lds_u(sb + OFF_GM));
        wg_wait<0>();
        reg_fence(s);
        mbar_arrive_warp<2>(sb + BAR_REMPTY + r.slot * 8);
        r.adv(2);
        TSD(W, 5);
        tail(TrueT{}, 0);
    } else {
        nb_sync<NB_Q01, 256>();
    }
#pragma unroll 1
    for (int i = (W == 0 ? 1 : 0); i < 4; i++) {
        const uint32_t pvslot = r.slot;
        r.adv(1);
        kslot = r.slot;
        mbar_wait(sb + BAR_RFULL + r.slot * 8, r.ph, r.dl);
        wg_fence();
        qk_steps<0, 4>(s, loRing + r.slot * (SLOT >> 4), loR);
        if (W == 1) wg_commit();
        qk_steps<4, 12>(s, loRing + r.slot * (SLOT >> 4), loR);
        wg_commit();
        wg_wait<1>();
        if (W == 1) mbar_arrive_warp_if(sb + BAR_XEMPTY + 0, i == 3);
        mbar_arrive_warp_if(sb + BAR_REMPTY + pvslot * 8, W == 0 || i > 0);
        r.adv(1);
        vslot = r.slot;
        TSD(W, 4 + 5 * i);
        mbar_wait(sb + BAR_RFULL + r.slot * 8, r.ph, r.dl);
        nb_sync<NB_PFULL + (W ^ 1), 256>();
        pv(FalseT{}, W ^ 1);
        if (W == 1) mref = __uint_as_float(lds_u(sb + OFF_GM));
        wg_wait<1>();
        reg_fence(s);
        mbar_arrive_warp<2>(sb + BAR_REMPTY + kslot * 8);
        if (W == 0) mbar_arrive_warp_if(sb + BAR_XEMPTY + 0, i == 3);
        r.adv(W == 1 && i == 3 ? 1 : 2);
        TSD(W, 5 + 5 * i);
        tail(FalseT{}, i);
    }
    if (W == 1) nx = get_item_warp(sb, it + 1, r.dl);
    if (W == 0) {
        Ring rn = r;
        rn.adv(2);
        q_ahead(q0, sb, rn, phm, IT_TYPE(nx) == IT_QA);
        TSD(W, 25);
    }
    const uint32_t w = (tid_now() >> 5) & 3;
    const uint32_t lxa = sb + OFF_LX + w * 640 + (((lane & 8) ? 80 : 0) + ((lane >> 1) & 8) + 2 * (lane & 3) + ((lane >> 2) & 1)) * 4;
    po.gp = ostash(IT_SLOT(e), IT_B(e)) + po.toff();
    po.sig = 1;
    if (W == 0) {
        sum_store<false>(l, lane, lxa);
        nb_arrive<NB_LX, 256>();
        wg_wait<1>();
        mbar_arrive_warp(sb + BAR_REMPTY + r.slot * 8);
        mbar_arrive_warp(sb + BAR_XEMPTY + 24);
        r.adv(1);
        mbar_wait(sb + BAR_RFULL + r.slot * 8, r.ph, r.dl);
        nb_sync<NB_PFULL + 1, 256>();
        pv(FalseT{}, 1);
    } else {
        nb_sync<NB_LX, 256>();
        sum_store<true>(l, lane, lxa);
        nb_arrive<NB_L, 160>();
    }
    TSD(W, 24);
    wg_wait<0>();
    reg_fence(oa);
    reg_fence(ob);
    mbar_arrive_warp(sb + BAR_REMPTY + r.slot * 8);
    mbar_arrive_warp(sb + BAR_XEMPTY + 32);
    r.adv(1);
    opack(ob, po.v + 40);
    opack(oa, po.v);
    return nx;
}

template <int W>
__device__ __forceinline__ uint32_t qa_run(uint32_t e, uint32_t sb, Ring& r, uint32_t phm, PendO& po, int& it) {
    float q0[80], oa[80];
    if (W == 0) {
        zero(oa);
        q_ahead(q0, sb, r, phm, true);
        wg_wait<0>();
    }
#pragma unroll 1
    do {
        TS(W, 0);
        if (W == 0) TS_ITEM(e);
        e = qa_item<W>(e, sb, r, phm, po, q0, oa, it);
        TS(W, 31);
        it++;
    } while (IT_TYPE(e) == IT_QA && !po.bad);
    if (W == 0) {
#pragma unroll
        for (int i = 56; i < 64; i++) po.v[i] = 0;
    }
    return e;
}

__device__ __forceinline__ void consumer(const Params& P, uint32_t W, uint32_t sb, uint32_t dl) {
    int it = 0;
    Ring r{0, 0, dl};
    uint32_t phm = 0;
    uint32_t e = get_item_warp(sb, 0, dl);
#pragma unroll 1
    while (true) {
        if (IT_TYPE(e) == IT_QA) {
            PendO po;
            po.clear();
            e = W == 0 ? qa_run<0>(e, sb, r, phm, po, it) : qa_run<1>(e, sb, r, phm, po, it);
#pragma unroll 1
            for (int m = po.bad ? 2 : 1; m > 0; m--) {
                if (m == 1) {
                    po.verdict(sb, W);
                    if (W == 0) po.flush<0>(sb);
                    else po.flush<1>(sb);
                }
                if (po.bad) {
                    if (W == 0) fallback_unit(P, lds_u(sb + OFF_ITEM + (it - m) * 4), tid_now() & 127);
                    __syncwarp();
                    nb_sync<NB_ODONE, 288>();
                }
            }
        }
        if (e == 0) break;
        if (IT_TYPE(e) == IT_QA) continue;
        TS(W, 0);
        if (W == 0) TS_ITEM(e);
        if (IT_TYPE(e) == IT_ON) {
            on_item(P, W, e, sb, r, phm, it);
            TS(W, 31);
            break;
        }
        if (W == 0) op_item<true>(e, sb, r, phm);
        else op_item<false>(e, sb, r, phm);
        TS(W, 31);
        e = get_item_warp(sb, ++it, dl);
    }
    TS_DUMP(W);
}

__global__ void __cluster_dims__(2, 1, 1) __launch_bounds__(384, 1) fused_kernel(const __grid_constant__ Params P) {
    extern __shared__ __align__(1024) unsigned char smem_raw[];
    const uint32_t sb = (uint32_t)__cvta_generic_to_shared(smem_raw);
    const uint32_t warp = __shfl_sync(0xffffffffu, threadIdx.x >> 5, 0), wgid = warp >> 2;
    const uint32_t cta = blockIdx.x;
    const uint32_t dl = deadline();

    if (threadIdx.x == 128) {
#pragma unroll
        for (int i = 0; i < NSLOT; i++) {
            mbar_init(sb + BAR_RFULL + i * 8, 1);
            mbar_init(sb + BAR_REMPTY + i * 8, 8);
            mbar_init(sb + BAR_XFULL + i * 8, 1);
            mbar_init(sb + BAR_XEMPTY + i * 8, 8);
        }
        asm volatile("fence.mbarrier_init.release.cluster;" ::: "memory");
        fence_async_smem();
    } else if (threadIdx.x == 160) {
#pragma unroll
        for (int i = 0; i < NSLOT + MAXI; i++) mbar_init(sb + BAR_PRDY + i * 8, 1);
        asm volatile("fence.mbarrier_init.release.cluster;" ::: "memory");
    } else if (threadIdx.x == 0) {
        sts_u(sb + OFF_ITEM, P.cl[cta >> 1].items[0] ? P.cl[cta >> 1].items[0] + 8 * (cta & 1) : 0);
        sts_u(sb + OFF_FB, P.cl[cta >> 1].delay);
    } else if (threadIdx.x == 64) {
        if (sb & 1023) __trap();
        asm volatile("prefetch.tensormap [%0];" ::"l"(&P.wq[0]) : "memory");
        asm volatile("prefetch.tensormap [%0];" ::"l"(&P.x[0]) : "memory");
    }
    __syncthreads();
    {
        const int it = 0;
        if (wgid == 1) TS(0, 30);
    }
    asm volatile("barrier.cluster.arrive.relaxed.aligned;" ::: "memory");
    if (warp < 3) {
        const uint32_t e = __shfl_sync(0xffffffffu, lds_u(sb + OFF_ITEM), 0), d = lds_u(sb + OFF_FB);
        const uint64_t pol = pol_shared();
        const bool isx = warp == 1, lead = (threadIdx.x & 31) == 0;
        uint32_t t0, t1;
        asm volatile("mov.u32 %0, %%clock;" : "=r"(t0));
        do {
            asm volatile("mov.u32 %0, %%clock;" : "=r"(t1));
        } while (t1 - t0 < d);
        __syncwarp();
#pragma unroll 1
        for (int n = 0; n < (e ? NSLOT : 0); n++) {
            const uint32_t bar = sb + (isx ? BAR_XFULL : BAR_RFULL) + n * 8;
            if (lead) {
                if (warp < 2) mbar_expect(bar, isx ? XS : SLOT);
                tma3(sb + (isx ? OFF_R + n * XS : OFF_RING + n * SLOT + warp * (SLOT / 4)), isx ? &P.x[0] : &P.wq[0],
                     isx ? IT_B(e) * 160 : n * 64 + warp * 16, isx ? n : IT_H0(e) * 3, bar, pol);
            }
        }
        if (threadIdx.x == 0) asm volatile("mbarrier.arrive.shared::cta.b64 _, [%0];" ::"r"(sb + BAR_ITEM) : "memory");
        __syncwarp();
    }

    if (wgid == 0) {
        asm volatile("setmaxnreg.dec.sync.aligned.u32 24;");
        if (warp == 0) {
            const bool lead = threadIdx.x == 0;
            const uint64_t pol_first = pol_stream(), pol_norm = pol_shared();
            uint32_t e = __shfl_sync(0xffffffffu, lds_u(sb + OFF_ITEM), 0);
            asm volatile("barrier.cluster.wait.aligned;" ::: "memory");
            unsigned int* const ticket = &g_ticket[next_epoch(0) & 1];
            const uint32_t rank = cta & 1;
            uint32_t peer;
            asm volatile("mapa.shared::cluster.u32 %0, %1, %2;" : "=r"(peer) : "r"(sb), "r"(rank ^ 1));
            Ring r{0, 0, dl};
            uint32_t pm = 0;
            bool told = false;
            auto load_w = [&](const CUtensorMap* m, int row, int blk, uint32_t half_bytes, bool more) {
                auto tell = [&](uint32_t slot) {
                    if (lead) {
                        mbar_expect(sb + BAR_RFULL + slot * 8, 2 * half_bytes);
                        asm volatile("mbarrier.arrive.shared::cluster.b64 _, [%0];" ::"r"(peer + BAR_PRDY + slot * 8) : "memory");
                    }
                };
                const uint32_t slot = r.slot;
                if (!told) {
                    mbar_wait(sb + BAR_REMPTY + slot * 8, r.ph, dl);
                    tell(slot);
                }
                r.adv(1);
                told = more && mbar_test(sb + BAR_REMPTY + r.slot * 8, r.ph);
                if (told) tell(r.slot);
                mbar_wait(sb + BAR_PRDY + slot * 8, (pm >> slot) & 1, dl);
                pm ^= 1u << slot;
                if (lead) tma3_mc(sb + OFF_RING + slot * SLOT + rank * half_bytes, m, row, blk, sb + BAR_RFULL + slot * 8, pol_norm);
            };
#pragma unroll 1
            for (int it = 0; e != 0; it++) {
                uint32_t nx = 0, tk = 0;
                if (rank == 0 && IT_TYPE(e) != IT_ON && it + 2 < MAXI) nx = it + 1 < NSTAT ? P.cl[cta >> 1].items[it + 1] : IT_DYN;
                const uint32_t br = IT_BR(e);
                if (IT_TYPE(e) == IT_QA) {
                    const uint32_t h = IT_H0(e);
#pragma unroll 1
                    for (int kk = it ? 0 : NSLOT; kk < 10; kk++) load_w(&P.wq[br], kk * 64 + rank * 32, h * 3, SLOT / 2, kk < 9);
                    const int grp0 = (IT_B(e) * 32 + h) * 64;
#pragma unroll 1
                    for (int n = 0; n < 16; n++) {
                        if (n == 13 && nx == IT_DYN && lead) tk = atomicAdd(ticket, 1);
                        const bool isv = n == 15 || (n > 0 && !(n & 1));
                        const int j = n == 15 ? 7 : isv ? (n - 2) >> 1 : (n + 1) >> 1;
                        mbar_wait(sb + BAR_REMPTY + r.slot * 8, r.ph, dl);
                        if (lead) {
                            mbar_expect(sb + BAR_RFULL + r.slot * 8, SLOT);
                            asm volatile(
                                "cp.async.bulk.tensor.4d.shared::cluster.global.mbarrier::complete_tx::bytes.L2::cache_hint"
                                " [%0], [%1, {%3,%3,%3,%4}], [%2], %5;" ::"r"(sb + OFF_RING + r.slot * SLOT),
                                "l"(isv ? &P.v[br] : &P.k[br]), "r"(sb + BAR_RFULL + r.slot * 8), "r"(0), "r"(grp0 + j * 8), "l"(pol_first)
                                : "memory");
                        }
                        r.adv(1);
                    }
                } else {
                    const bool wide = IT_TYPE(e) == IT_OP;
                    const int step = wide ? 32 : 64, r1 = IT_H1(e) * 192;
#pragma unroll 1
                    for (int row = IT_H0(e) * 192 + rank * (step >> 1); row < r1; row += step)
                        load_w(wide ? &P.wo[br] : &P.won[br], row, IT_HALF(e) * (wide ? 5 : 2), wide ? XS / 2 : 8192, row + step < r1);
                    if (nx == IT_DYN && lead) tk = atomicAdd(ticket, 1);
                }
                if (rank == 0) {
                    if (nx == IT_DYN) {
                        tk = __shfl_sync(0xffffffffu, tk, 0);
                        nx = tk < P.nlist ? P.list[tk] : 0;
                    }
                    e = nx;
                    if (lead) {
                        asm volatile("st.async.weak.shared::cluster.mbarrier::complete_tx::bytes.b32 [%0], %1, [%2];" ::"r"(
                                         peer + OFF_ITEM + 4 + it * 4),
                                     "r"(e ? e + 8 : 0), "r"(peer + BAR_ITEM + 8 + it * 8)
                                     : "memory");
                        sts_u(sb + OFF_ITEM + 4 + it * 4, e);
                        asm volatile("mbarrier.arrive.shared::cta.b64 _, [%0];" ::"r"(sb + BAR_ITEM + 8 + it * 8) : "memory");
                    }
                } else {
                    if (lead) mbar_expect(sb + BAR_ITEM + 8 + it * 8, 4);
                    e = get_item_warp(sb, it + 1, dl);
                }
            }
        } else if (warp == 1) {
            const uint64_t pol_norm = pol_shared(), pol_o = pol_stream();
            const bool lead = threadIdx.x == 32;
            uint32_t phm = 0, epoch = 0;
#pragma unroll 1
            for (int it = 0;; it++) {
                const uint32_t e = get_item_warp(sb, it, dl);
                if (it == 1 || (it == 0 && e == 0)) epoch = next_epoch(1);
                if (e == 0) break;
                const uint32_t br = IT_BR(e);
                uint32_t xs = 0;
                auto acquire = [&]() {
                    mbar_wait(sb + BAR_XEMPTY + xs * 8, (phm >> xs) & 1, dl);
                    phm ^= 1u << xs;
                    if (lead) mbar_expect(sb + BAR_XFULL + xs * 8, XS);
                };
                if (IT_TYPE(e) == IT_QA) {
#pragma unroll 1
                    for (int kk = it ? 0 : 5; kk < 10; kk++) {
                        acquire();
                        if (lead) tma3(sb + OFF_R + xs * XS, &P.x[br], IT_B(e) * 160, kk, sb + BAR_XFULL + xs * 8, pol_norm);
                        if (++xs == 5) xs = 0;
                    }
                } else {
                    const unsigned int* fp = g_flag + (br * 16 + IT_B(e)) * 64 + (threadIdx.x & 31) * 2;
                    uint32_t hm = 0, pm = 0;
                    auto poll = [&](uint32_t hneed, uint32_t pneed) {
                        if ((hm & hneed) == hneed && (pm & pneed) == pneed) return;
                        uint32_t n = 0;
                        do {
                            uint32_t a, b;
                            asm volatile("ld.acquire.gpu.global.v2.u32 {%0, %1}, [%2];" : "=r"(a), "=r"(b) : "l"(fp) : "memory");
                            hm = __ballot_sync(0xffffffffu, a == epoch);
                            pm = __ballot_sync(0xffffffffu, b == epoch);
                            if (++n > 0x1000000) __trap();
                        } while ((hm & hneed) != hneed || (pm & pneed) != pneed);
                        __syncwarp();
                        asm volatile("fence.proxy.async.global;" ::: "memory");
                    };
#pragma unroll 1
                    for (uint32_t h = IT_H0(e); h < IT_H1(e); h++) {
                        const unsigned char* src = ostash(P.slot[br * 32 + h], IT_B(e));
                        poll(1u << h, 0);
#pragma unroll 1
                        for (int t = 0; t < 3; t++) {
                            acquire();
                            if (lead) bulk_load(sb + OFF_R + xs * XS, src + t * XS, XS, sb + BAR_XFULL + xs * 8, pol_o);
                            if (++xs == 5) xs = 0;
                        }
                        if (IT_TYPE(e) == IT_OP && h >= 1) {
                            const uint32_t x1 = xs == 4 ? 0 : xs + 1;
                            mbar_wait(sb + BAR_XFULL + xs * 8, (phm >> xs) & 1, dl);
                            mbar_wait(sb + BAR_XFULL + x1 * 8, (phm >> x1) & 1, dl);
                            if (lead)
                                asm volatile("red.relaxed.gpu.global.max.u32 [%0], %1;" ::"l"(fp + 5 + 2 * IT_HALF(e)), "r"(epoch * 64 + h) : "memory");
                        }
                    }
                    if (IT_TYPE(e) == IT_ON) {
                        poll(0, IT_HALF(e) < 2 ? 1 : IT_HALF(e) == 2 ? 3 : 2);
#pragma unroll 1
                        for (uint32_t tile = 2 * IT_HALF(e); tile < 2 * IT_HALF(e) + 2; tile++) {
                            acquire();
                            if (lead)
                                asm volatile(
                                    "cp.async.bulk.tensor.5d.shared::cluster.global.mbarrier::complete_tx::bytes [%0], [%1, {%3,%5,%5,%5,%4}], [%2];" ::"r"(
                                        sb + OFF_R + xs * XS),
                                    "l"(&P.out), "r"(sb + BAR_XFULL + xs * 8), "r"(br * 640 + tile * 64), "r"(IT_B(e) * 5), "r"(0)
                                    : "memory");
                            if (++xs == 5) xs = 0;
                        }
                    }
                }
            }
        } else if (warp == 2) {
            asm volatile("barrier.cluster.wait.aligned;" ::: "memory");
            const uint32_t epoch = next_epoch(2);
            if (cta == 0) g_ticket[(epoch + 1) & 1] = 0;
#pragma unroll 1
            for (int it = 0;; it++) {
                const uint32_t e = get_item_warp(sb, it, dl);
                if (e == 0) break;
                if (IT_TYPE(e) != IT_QA && threadIdx.x == 64) asm volatile("prefetch.tensormap [%0];" ::"l"(&P.out) : "memory");
                if (IT_TYPE(e) == IT_ON) break;
                nb_sync<NB_ODONE, 288>();
                if (threadIdx.x == 64) {
                    const uint32_t bb = IT_BR(e) * 16 + IT_B(e);
                    if (IT_TYPE(e) != IT_QA) {
                        asm volatile("red.relaxed.gpu.global.max.u32 [%0], %1;" ::"l"(&g_flag[bb * 64 + 5 + 2 * IT_HALF(e)]),
                                     "r"(epoch * 64 + IT_H1(e))
                                     : "memory");
#pragma unroll 1
                        for (int m = 0; m < 5; m++) {
                            out_store(P, sb + OFF_R + m * XS, IT_BR(e) * 640 + IT_HALF(e) * 320 + m * 64, IT_B(e));
                            if (m >= 1) {
                                asm volatile("cp.async.bulk.wait_group.read 1;" ::: "memory");
                                asm volatile("mbarrier.arrive.shared::cta.b64 _, [%0], 8;" ::"r"(sb + BAR_XEMPTY + (m - 1) * 8) : "memory");
                            }
                        }
                        asm volatile("cp.async.bulk.wait_group.read 0;" ::: "memory");
                        asm volatile("mbarrier.arrive.shared::cta.b64 _, [%0], 8;" ::"r"(sb + BAR_XEMPTY + 32) : "memory");
                        if (IT_PART(e)) {
                            asm volatile("cp.async.bulk.wait_group 0;" ::: "memory");
                            asm volatile("fence.proxy.async.global;" ::: "memory");
                        }
                    }
                    if (IT_TYPE(e) == IT_QA || IT_PART(e)) {
                        unsigned int* f = &g_flag[bb * 64 + (IT_TYPE(e) == IT_QA ? 2 * IT_H0(e) : 1 + 2 * IT_HALF(e))];
                        asm volatile("st.release.gpu.global.u32 [%0], %1;" ::"l"(f), "r"(epoch) : "memory");
                    }
                }
                __syncwarp();
            }
            if (threadIdx.x == 64) asm volatile("cp.async.bulk.wait_group 0;" ::: "memory");
            __syncwarp();
            asm volatile("barrier.cluster.arrive.relaxed.aligned;\nbarrier.cluster.wait.aligned;" ::: "memory");
        } else {
            const uint32_t lane = threadIdx.x & 31, p = lane >> 3;
            const uint32_t epoch = next_epoch(3);
#pragma unroll 1
            for (int it = 0;; it++) {
                const uint32_t e = get_item_warp(sb, it, dl);
                if (e == 0) break;
                if (IT_TYPE(e) != IT_QA) continue;
                nb_sync<NB_QK, 160>();
                const uint32_t ka = sb + OFF_RING + lds_u(sb + OFF_GM + 4) * SLOT + p * (2 * 3072 + 256) + (lane & 7) * 16;
                const uint32_t qa = sb + OFF_R + p * 256 + (lane & 7) * 16;
                uint32_t acc = 0;
#pragma unroll 1
                for (int c = 0; c < 3; c++) {
                    const uint4 k = lds_u4(ka + c * 1024);
                    if (c == 2) nb_sync<NB_L, 160>();
                    const uint4 q = lds_u4(qa + c * XS);
                    acc = fma_bf2(k.x, q.x, fma_bf2(k.y, q.y, fma_bf2(k.z, q.z, fma_bf2(k.w, q.w, acc))));
                }
                const float d = __uint_as_float(acc << 16) + __uint_as_float(acc & 0xffff0000u);
                const int sum = __reduce_add_sync(0xffffffffu, __float2int_rn(d * 16.f));
                sts_f(sb + OFF_GM, fmaf((float)sum, SM_C / 64.f, 24.f));
                nb_arrive<NB_REF, 160>();
                if (IT_DEP(e)) {
                    const uint32_t g = IT_DEP(e) - 1, need = epoch * 64 + (g & 31) + 1;
                    const unsigned int* cp = &g_flag[((g >> 5) * 16 + IT_B(e)) * 64 + 5 + 2 * (lane & 1)];
                    for (uint32_t n = 0;; n++) {
                        uint32_t v;
                        asm volatile("ld.acquire.gpu.global.u32 %0, [%1];" : "=r"(v) : "l"(cp) : "memory");
                        if (__all_sync(0xffffffffu, v - need < 64)) break;
                        if (n > 0x800000) __trap();
                        __nanosleep(500);
                    }
                }
                nb_sync<NB_L, 160>();
                bool bad = false;
#pragma unroll
                for (int c = 0; c < 5; c++) {
                    const uint32_t la = sb + OFF_LX + (c * 32 + lane) * 4;
                    const float v = (__uint_as_float(lds_u(la)) + __uint_as_float(lds_u(la + 640))) +
                                    (__uint_as_float(lds_u(la + 1280)) + __uint_as_float(lds_u(la + 1920)));
                    const float inv = __fdividef(1.f, v);
                    const uint32_t hi = pack_bf16(inv, 0.f), lo = pack_bf16(inv - __uint_as_float(hi << 16), 0.f);
                    const uint32_t ia = sb + OFF_LINV + c * 128 + ((lane >> 1) & 3) * 32 + (lane >> 3) * 8 + (lane & 1) * 2;
                    asm volatile("st.shared.u16 [%0], %1;\nst.shared.u16 [%0+4], %2;" ::"r"(ia), "h"((unsigned short)hi), "h"((unsigned short)lo) : "memory");
                    bad |= !(v >= 5.421010862e-20f && v <= 7.9228163e28f);
                }
                sts_u(sb + OFF_FB, __any_sync(0xffffffffu, bad));
                nb_arrive<NB_VOTE, 160>();
                nb_arrive<NB_VOTE + 1, 160>();
            }
        }
    } else {
        asm volatile("setmaxnreg.inc.sync.aligned.u32 240;");
        consumer(P, wgid - 1, sb, dl);
    }
}

typedef CUresult (*EncFn)(CUtensorMap*, CUtensorMapDataType, cuuint32_t, void*, const cuuint64_t*, const cuuint64_t*,
                          const cuuint32_t*, const cuuint32_t*, CUtensorMapInterleave, CUtensorMapSwizzle,
                          CUtensorMapL2promotion, CUtensorMapFloatOOBfill);

void make_map3(EncFn enc, CUtensorMap* m, void* p, uint64_t rows, uint64_t rowbytes, uint64_t nblk, uint32_t boxrows,
               uint32_t boxblk) {
    cuuint64_t dims[3] = {64, rows, nblk};
    cuuint64_t str[2] = {rowbytes, 128};
    cuuint32_t box[3] = {64, boxrows, boxblk};
    cuuint32_t es[3] = {1, 1, 1};
    enc(m, CU_TENSOR_MAP_DATA_TYPE_BFLOAT16, 3, p, dims, str, box, es, CU_TENSOR_MAP_INTERLEAVE_NONE,
        CU_TENSOR_MAP_SWIZZLE_128B, CU_TENSOR_MAP_L2_PROMOTION_NONE, CU_TENSOR_MAP_FLOAT_OOB_FILL_NONE);
}

constexpr int tune(const char*, int def) { return def; }

void build_schedule(Params& P, int ncl) {
    const int mode = tune("MODE", 4), dmax = tune("DMAX", 23000), n0 = tune("N0", 10);
    const int H0[8] = {19, 20, 21, 22, 22, 24, 25, 25}, P0[8] = {373, 335, 333, 329, 333, 333, 331, 330};
    const int ra = tune("RA", 10), ga = tune("GA", 17), rb = tune("RB", 11), g1 = tune("G1", 58);
    int dep[64];
    for (int g = 0, ns = 0, live = 0; g < 64; g++) {
        const bool fresh = mode < 3 || g >= g1 || live < (g < ga ? ra : rb);
        dep[g] = fresh ? 0 : g - live + 1;
        P.slot[g] = fresh ? ns++ : P.slot[g - live];
        live += fresh;
    }
    int H[8], pos[8], psum = 0;
    for (int b = 0; b < 8; b++) {
        const char nh[3] = {'H', (char)('0' + b), 0}, np[3] = {'P', (char)('0' + b), 0};
        H[b] = tune(nh, H0[b]);
        pos[b] = tune(np, P0[b]);
        psum += pos[b];
    }
    const int sk = tune("SK", 10), g0 = tune("G0", 20), g2 = tune("G2", 40);
    int ord[512], nxt[8] = {0, 0, 0, 0, 0, 0, 0, 0};
    for (int k = 0; k < 512; k++) {
        int best = -1;
        float bkey = 0.f;
        for (int b = 0; b < 8; b++) {
            const int g = nxt[b];
            if (g == 64) continue;
            const float w = g < g0 ? 0.f : g < 32 ? (g - g0) / (32.f - g0) : g < g2 ? 1.f : (64 - g) / (64.f - g2);
            const float key = g + w * sk * 0.1f * (pos[b] - psum / 8.f) / 8.f;
            if (best < 0 || key < bkey) best = b, bkey = key;
        }
        ord[k] = nxt[best]++ * 8 + best;
        const int d = dep[ord[k] >> 3];
        if (d > 32) {
            if (pos[best] > k) pos[best] = k;
            if (H[best] < d - 32) H[best] = d - 32;
        }
    }
    int u = 0;
    auto unit = [&]() {
        const int v = ord[u++];
        return mk_item(IT_QA, v >> 8, (v & 7) * 2, (v >> 3) & 31, P.slot[v >> 3], 0) | (dep[v >> 3] << 23);
    };
    int qa[NCL], nq = 0, op[NCL], no = 0;
    for (int c = 0; c < ncl; c++) {
        P.cl[c].delay = 0;
        for (int i = 0; i < NSTAT; i++) P.cl[c].items[i] = 0;
        if (mode >= 3 && c >= 4 && c < 20) op[((c - 4) & 7) * 2 + ((c - 4) >> 3)] = c, no++;
        else if (mode != 2 || (c & 3) == 0) qa[nq++] = c;
    }
    for (int t = 0; t < no; t++) {
        P.cl[op[t]].items[1] = mk_item(IT_OP, 0, t & ~1, 0, 32, t & 1);
        P.cl[op[t]].items[2] = IT_DYN;
            }
    for (int k = 0; k < nq; k++) {
        const int c = qa[(k * (nq % 19 ? 19 : 17)) % nq];
        P.cl[c].items[1] = P.cl[c].items[2] = IT_DYN;
        P.cl[c].delay = k < n0 ? 0 : dmax * (k + 1 - n0) / (nq - n0);
    }
    for (int t = 0; t < no; t++) P.cl[op[(t & 7) * 2 + (t >> 3)]].items[0] = unit();
    for (int k = u; k < no + nq; k++) {
        int best = -1;
        for (int c = 0; c < ncl; c++)
            if (P.cl[c].items[1] && !P.cl[c].items[0] && (best < 0 || P.cl[c].delay < P.cl[best].delay)) best = c;
        P.cl[best].items[0] = unit();
    }
    int n = 0;
    const int uend = mode == 2 ? 8 * nq : 512;
    while (u < uend) {
        for (int b = 0; b < 8 && no; b++)
            if (pos[b] == u) {
                P.list[n++] = mk_item(IT_OP, 1, 2 * b, 0, H[b], 0, 1);
                P.list[n++] = mk_item(IT_OP, 1, 2 * b, 0, H[b], 1, 1);
            }
        P.list[n++] = unit();
    }
    for (int k = 0; no && k < 40; k++) P.list[n++] = mk_item(IT_ON, 1, k / 5 * 2, H[k / 5], 32, k % 5);
    P.nlist = n;
}

}

extern "C" void kernel_launch(void* const* d_in, const int* in_sizes, int n_in, void* d_out, int out_size) {
    static Params P;
    static bool init = false;
    static int ncl = NCL;
    if (!init) {
        EncFn enc = nullptr;
        cudaDriverEntryPointQueryResult qr;
        cudaGetDriverEntryPoint("cuTensorMapEncodeTiled", (void**)&enc, cudaEnableDefault, &qr);
        for (int i = 0; i < 2; i++) {
            P.px[i] = (const __nv_bfloat16*)d_in[5 * i + 0];
            P.pk[i] = (const __nv_bfloat16*)d_in[5 * i + 1];
            P.pv[i] = (const __nv_bfloat16*)d_in[5 * i + 2];
            P.pwq[i] = (const __nv_bfloat16*)d_in[5 * i + 3];
            make_map3(enc, &P.x[i], d_in[5 * i + 0], 2560, 1280, 10, 160, 1);
            for (int j = 0; j < 2; j++) {
                cuuint64_t dims[4] = {64, 8, 3, 16 * 32 * 64};
                cuuint64_t str[3] = {384, 128, 3072};
                cuuint32_t box[4] = {64, 8, 3, 8};
                cuuint32_t es[4] = {1, 1, 1, 1};
                enc(j ? &P.v[i] : &P.k[i], CU_TENSOR_MAP_DATA_TYPE_BFLOAT16, 4, d_in[5 * i + 1 + j], dims, str, box, es,
                    CU_TENSOR_MAP_INTERLEAVE_NONE, CU_TENSOR_MAP_SWIZZLE_128B, CU_TENSOR_MAP_L2_PROMOTION_NONE,
                    CU_TENSOR_MAP_FLOAT_OOB_FILL_NONE);
            }
            make_map3(enc, &P.wq[i], d_in[5 * i + 3], 640, 12288, 96, 32, 3);
            make_map3(enc, &P.wo[i], d_in[5 * i + 4], 6144, 1280, 10, 16, 5);
            make_map3(enc, &P.won[i], d_in[5 * i + 4], 6144, 1280, 10, 32, 2);
        }
        cuuint64_t dims[5] = {1280, 2, 4, 4, 80};
        cuuint64_t str[4] = {2560, 8 * 2560, 2 * 2560, 32 * 2560};
        cuuint32_t box[5] = {64, 2, 4, 4, 5};
        cuuint32_t es[5] = {1, 1, 1, 1, 1};
        enc(&P.out, CU_TENSOR_MAP_DATA_TYPE_BFLOAT16, 5, d_out, dims, str, box, es, CU_TENSOR_MAP_INTERLEAVE_NONE,
            CU_TENSOR_MAP_SWIZZLE_128B, CU_TENSOR_MAP_L2_PROMOTION_NONE, CU_TENSOR_MAP_FLOAT_OOB_FILL_NONE);
        cudaFuncSetAttribute(fused_kernel, cudaFuncAttributeMaxDynamicSharedMemorySize, SMEM_LAUNCH);
        cudaLaunchConfig_t cfg = {};
        cfg.gridDim = dim3(NCTA);
        cfg.blockDim = dim3(384);
        cfg.dynamicSmemBytes = SMEM_LAUNCH;
        int nc = 0;
        if (cudaOccupancyMaxActiveClusters(&nc, fused_kernel, &cfg) == cudaSuccess && nc >= 52 && nc < NCL) ncl = nc;
        (void)cudaGetLastError();
        ncl = tune("NCL", ncl);
        build_schedule(P, ncl);
        init = true;
    }
    fused_kernel<<<2 * ncl, 384, SMEM_LAUNCH>>>(P);
}
```

```cpp
#include <cuda_runtime.h>
#include <cuda.h>
#include <cuda_bf16.h>
#include <stdint.h>

namespace {

constexpr int NCTA = 132;
constexpr int NCL = NCTA / 2;
constexpr int MAXI = 16;
constexpr int NSTAT = 3;
constexpr uint32_t IT_DYN = 0xffffffffu;
constexpr int SLOT = 24576;
constexpr int NSLOT = 5;
constexpr int XS = 20480;
constexpr int OFF_R = 0;
constexpr int OFF_RING = 5 * XS;
constexpr int OFF_MISC = OFF_RING + NSLOT * SLOT;
constexpr int OFF_LX = OFF_MISC;
constexpr int OFF_LINV = OFF_LX + 2560;
constexpr int OFF_FB = OFF_LINV + 640;
constexpr int OFF_GM = OFF_FB + 16;
constexpr int OFF_BAR = OFF_GM + 16;
constexpr int BAR_RFULL = OFF_BAR;
constexpr int BAR_REMPTY = BAR_RFULL + 40;
constexpr int BAR_XFULL = BAR_REMPTY + 40;
constexpr int BAR_XEMPTY = BAR_XFULL + 40;
constexpr int BAR_PRDY = BAR_XEMPTY + 40;
constexpr int BAR_ITEM = BAR_PRDY + 40;
constexpr int OFF_ITEM = BAR_ITEM + MAXI * 8;
constexpr int SMEM_BYTES = OFF_ITEM + MAXI * 4;
static_assert(SMEM_BYTES <= 232448, "smem");

constexpr int NB_W = 1  , NB_PFULL = 3  , NB_VOTE = 5  , NB_Q2 = 7, NB_SDONE = 8, NB_PDONE = 9,
              NB_L = 10, NB_REF = 11, NB_ODONE = 12, NB_OPEND = 13, NB_LX = 14, NB_Q01 = 15, NB_QK = 0  ;

constexpr uint32_t IT_QA = 1, IT_OP = 2, IT_ON = 3;
__host__ __device__ constexpr uint32_t mk_item(uint32_t type, uint32_t br, uint32_t b, uint32_t h0, uint32_t h1, uint32_t half,
                                               uint32_t part = 0) {
    return type | (br << 2) | (b << 3) | (h0 << 7) | (h1 << 13) | (half << 19) | (part << 22);
}
#define IT_TYPE(e) ((e) & 3u)
#define IT_BR(e) (((e) >> 2) & 1u)
#define IT_B(e) (((e) >> 3) & 15u)
#define IT_H0(e) (((e) >> 7) & 63u)
#define IT_H1(e) (((e) >> 13) & 63u)
#define IT_HALF(e) (((e) >> 19) & 7u)
#define IT_PART(e) (((e) >> 22) & 1u)
#define IT_SLOT(e) IT_H1(e)
#define IT_DEP(e) (((e) >> 23) & 127u)

struct Params {
    CUtensorMap x[2], wq[2], k[2], v[2], wo[2], won[2], out;
    const __nv_bfloat16 *px[2], *pwq[2], *pk[2], *pv[2];
    struct alignas(16) { uint32_t delay, items[NSTAT]; } cl[NCL];
    uint32_t nlist;
    uint8_t slot[64];
    uint32_t list[568];
};

constexpr int OUNIT = 61440;
__device__ __align__(1024) unsigned char g_ostash[(size_t)1024 * OUNIT];
__device__ __align__(256) unsigned int g_flag[32 * 64];
__device__ __forceinline__ unsigned char* ostash(uint32_t slot, uint32_t b) { return g_ostash + (slot * 16 + b) * OUNIT; }
__device__ unsigned int g_epoch[NCTA * 4];
__device__ unsigned int g_ticket[2];

constexpr int SMEM_LAUNCH = SMEM_BYTES;
#define TS(role, idx)
#define TS_ITEM(e)
#define TS_DUMP(role)
#define TSD(role, idx)

__device__ __forceinline__ uint64_t pol_stream() {
    uint64_t p;
    asm volatile("createpolicy.fractional.L2::evict_first.b64 %0, 1.0;" : "=l"(p));
    return p;
}
__device__ __forceinline__ uint64_t pol_shared() {
    uint64_t p;
    asm volatile("createpolicy.fractional.L2::evict_unchanged.b64 %0, 1.0;" : "=l"(p));
    return p;
}
constexpr int QHOLD = 8;
constexpr float SM_C = 0.07216878364870322f * 1.4426950408889634f;

__device__ __forceinline__ uint32_t next_epoch(int warp) {
    unsigned int* p = &g_epoch[blockIdx.x * 4 + warp];
    const uint32_t e = __ldcg(p) + 1;
    *p = e;
    return e;
}

__device__ __forceinline__ uint32_t tid_now() {
    uint32_t t;
    asm volatile("mov.u32 %0, %%tid.x;" : "=r"(t));
    return t;
}
__device__ __forceinline__ void mbar_init(uint32_t a, uint32_t c) {
    asm volatile("mbarrier.init.shared::cta.b64 [%0], %1;" ::"r"(a), "r"(c) : "memory");
}
__device__ __forceinline__ void mbar_expect(uint32_t a, uint32_t b) {
    asm volatile("mbarrier.arrive.expect_tx.shared::cta.b64 _, [%0], %1;" ::"r"(a), "r"(b) : "memory");
}
template <int CNT = 1>
__device__ __forceinline__ void mbar_arrive_warp(uint32_t a) {
    if (CNT == 1)
        asm volatile("{\n.reg .pred p;\nelect.sync _|p, 0xffffffff;\n@p mbarrier.arrive.shared::cta.b64 _, [%0];\n}" ::"r"(a) : "memory");
    else
        asm volatile(
            "{\n.reg .pred p;\nelect.sync _|p, 0xffffffff;\n@p mbarrier.arrive.shared::cta.b64 _, [%0];\n"
            "@p mbarrier.arrive.shared::cta.b64 _, [%0];\n}" ::"r"(a)
            : "memory");
}
template <int CNT = 1>
__device__ __forceinline__ void mbar_arrive_warp_if(uint32_t a, bool cond) {
    if (CNT == 1)
        asm volatile(
            "{\n.reg .pred p, c;\nelect.sync _|p, 0xffffffff;\nsetp.ne.and.u32 c, %1, 0, p;\n"
            "@c mbarrier.arrive.shared::cta.b64 _, [%0];\n}" ::"r"(a), "r"((uint32_t)cond)
            : "memory");
    else
        asm volatile(
            "{\n.reg .pred p, c;\nelect.sync _|p, 0xffffffff;\nsetp.ne.and.u32 c, %1, 0, p;\n"
            "@c mbarrier.arrive.shared::cta.b64 _, [%0];\n@c mbarrier.arrive.shared::cta.b64 _, [%0];\n}" ::"r"(a), "r"((uint32_t)cond)
            : "memory");
}
__device__ __forceinline__ uint32_t deadline() {
    uint32_t c;
    asm volatile("mov.u32 %0, %%clock_hi;" : "=r"(c));
    return c + 4;
}
__device__ __forceinline__ void mbar_wait(uint32_t a, uint32_t ph, uint32_t dl) {
    asm volatile(
        "{\n.reg .pred p;\n.reg .u32 m;\n"
        "LOOP:\n"
        "mbarrier.try_wait.parity.shared::cta.b64 p, [%0], %1;\n"
        "@p bra DONE;\n"
        "mov.u32 m, %%clock_hi;\n"
        "setp.ne.u32 p, m, %2;\n"
        "@p bra LOOP;\n"
        "trap;\n"
        "DONE:\n}" ::"r"(a), "r"(ph), "r"(dl)
        : "memory");
}
__device__ __forceinline__ bool mbar_test(uint32_t a, uint32_t ph) {
    uint32_t ok;
    asm volatile("{\n.reg .pred p;\nmbarrier.test_wait.parity.shared::cta.b64 p, [%1], %2;\nselp.u32 %0, 1, 0, p;\n}"
                 : "=r"(ok) : "r"(a), "r"(ph) : "memory");
    return __all_sync(0xffffffffu, ok);
}
__device__ __forceinline__ void mbar_wait2(uint32_t a, uint32_t pa, uint32_t b, uint32_t pb, uint32_t dl) {
    asm volatile(
        "{\n.reg .pred p, q;\n.reg .u32 m;\n"
        "LOOP:\n"
        "mbarrier.try_wait.parity.shared::cta.b64 p, [%0], %1;\n"
        "mbarrier.try_wait.parity.shared::cta.b64 q, [%2], %3;\n"
        "and.pred p, p, q;\n"
        "@p bra DONE;\n"
        "mov.u32 m, %%clock_hi;\n"
        "setp.ne.u32 p, m, %4;\n"
        "@p bra LOOP;\n"
        "trap;\n"
        "DONE:\n}" ::"r"(a), "r"(pa), "r"(b), "r"(pb), "r"(dl)
        : "memory");
}
template <int ID, int CNT>
__device__ __forceinline__ void nb_sync() { asm volatile("bar.sync %0, %1;" ::"n"(ID), "n"(CNT) : "memory"); }
template <int ID, int CNT>
__device__ __forceinline__ void nb_arrive() { asm volatile("bar.arrive %0, %1;" ::"n"(ID), "n"(CNT) : "memory"); }
__device__ __forceinline__ void fence_async_smem() { asm volatile("fence.proxy.async.shared::cta;" ::: "memory"); }

__device__ __forceinline__ void tma3(uint32_t dst, const CUtensorMap* m, int c1, int c2, uint32_t bar, uint64_t pol) {
    asm volatile(
        "cp.async.bulk.tensor.3d.shared::cluster.global.mbarrier::complete_tx::bytes.L2::cache_hint [%0], [%1, {%3,%4,%5}], [%2], %6;" ::"r"(dst),
        "l"(m), "r"(bar), "r"(0), "r"(c1), "r"(c2), "l"(pol)
        : "memory");
}
__device__ __forceinline__ void tma3_mc(uint32_t dst, const CUtensorMap* m, int c1, int c2, uint32_t bar, uint64_t pol) {
    asm volatile(
        "cp.async.bulk.tensor.3d.shared::cluster.global.mbarrier::complete_tx::bytes.multicast::cluster.L2::cache_hint"
        " [%0], [%1, {%3,%4,%5}], [%2], %6, %7;" ::"r"(dst),
        "l"(m), "r"(bar), "r"(0), "r"(c1), "r"(c2), "h"((unsigned short)3), "l"(pol)
        : "memory");
}
__device__ __forceinline__ void bulk_load(uint32_t dst, const void* src, uint32_t bytes, uint32_t bar, uint64_t pol) {
    asm volatile("cp.async.bulk.shared::cluster.global.mbarrier::complete_tx::bytes.L2::cache_hint [%0], [%1], %2, [%3], %4;" ::"r"(dst),
                 "l"(src), "r"(bytes), "r"(bar), "l"(pol)
                 : "memory");
}
__device__ __forceinline__ void wg_fence() { asm volatile("wgmma.fence.sync.aligned;" ::: "memory"); }
__device__ __forceinline__ void wg_commit() { asm volatile("wgmma.commit_group.sync.aligned;" ::: "memory"); }
template <int N>
__device__ __forceinline__ void wg_wait() { asm volatile("wgmma.wait_group.sync.aligned %0;" ::"n"(N) : "memory"); }

#define RW80(c, d) c(d[0]), c(d[1]), c(d[2]), c(d[3]), c(d[4]), c(d[5]), c(d[6]), c(d[7]), c(d[8]), c(d[9]), c(d[10]), c(d[11]), c(d[12]), c(d[13]), c(d[14]), c(d[15]), c(d[16]), c(d[17]), c(d[18]), c(d[19]), c(d[20]), c(d[21]), c(d[22]), c(d[23]), c(d[24]), c(d[25]), c(d[26]), c(d[27]), c(d[28]), c(d[29]), c(d[30]), c(d[31]), c(d[32]), c(d[33]), c(d[34]), c(d[35]), c(d[36]), c(d[37]), c(d[38]), c(d[39]), c(d[40]), c(d[41]), c(d[42]), c(d[43]), c(d[44]), c(d[45]), c(d[46]), c(d[47]), c(d[48]), c(d[49]), c(d[50]), c(d[51]), c(d[52]), c(d[53]), c(d[54]), c(d[55]), c(d[56]), c(d[57]), c(d[58]), c(d[59]), c(d[60]), c(d[61]), c(d[62]), c(d[63]), c(d[64]), c(d[65]), c(d[66]), c(d[67]), c(d[68]), c(d[69]), c(d[70]), c(d[71]), c(d[72]), c(d[73]), c(d[74]), c(d[75]), c(d[76]), c(d[77]), c(d[78]), c(d[79])
#define RW48(c, d) c(d[0]), c(d[1]), c(d[2]), c(d[3]), c(d[4]), c(d[5]), c(d[6]), c(d[7]), c(d[8]), c(d[9]), c(d[10]), c(d[11]), c(d[12]), c(d[13]), c(d[14]), c(d[15]), c(d[16]), c(d[17]), c(d[18]), c(d[19]), c(d[20]), c(d[21]), c(d[22]), c(d[23]), c(d[24]), c(d[25]), c(d[26]), c(d[27]), c(d[28]), c(d[29]), c(d[30]), c(d[31]), c(d[32]), c(d[33]), c(d[34]), c(d[35]), c(d[36]), c(d[37]), c(d[38]), c(d[39]), c(d[40]), c(d[41]), c(d[42]), c(d[43]), c(d[44]), c(d[45]), c(d[46]), c(d[47])
#define RW32(c, d) c(d[0]), c(d[1]), c(d[2]), c(d[3]), c(d[4]), c(d[5]), c(d[6]), c(d[7]), c(d[8]), c(d[9]), c(d[10]), c(d[11]), c(d[12]), c(d[13]), c(d[14]), c(d[15]), c(d[16]), c(d[17]), c(d[18]), c(d[19]), c(d[20]), c(d[21]), c(d[22]), c(d[23]), c(d[24]), c(d[25]), c(d[26]), c(d[27]), c(d[28]), c(d[29]), c(d[30]), c(d[31])

__device__ __forceinline__ void reg_fence(float (&d)[80]) { asm volatile("" : RW80("+f", d)::"memory"); }
__device__ __forceinline__ void reg_fence(float (&d)[48]) { asm volatile("" : RW48("+f", d)::"memory"); }
__device__ __forceinline__ void reg_fence(float (&d)[32]) { asm volatile("" : RW32("+f", d)::"memory"); }

template <int NR>
__device__ __forceinline__ void zero(float (&d)[NR]) {
#pragma unroll
    for (int i = 0; i < NR; i++) d[i] = 0.f;
}

constexpr uint32_t HI_SW128 = (1024u >> 4) | (1u << 30);
constexpr uint32_t HI_KV = (3072u >> 4) | (1u << 30);
constexpr uint32_t HI_OST = (2560u >> 4) | (2u << 30);
constexpr uint32_t LO_LBO1 = (1u << 16);
constexpr uint32_t LO_OST = ((512u >> 4) << 16);

template <int TA, int TB, uint32_t HIB, int ACC, uint32_t HIA = HI_SW128>
__device__ __forceinline__ void wgmma(float (&d)[80], uint32_t loA, uint32_t loB) {
#define WG_ASM(SD)                                                          \
    "{\n.reg .b64 da, db;\nmov.b64 da, {%80, %82};\nmov.b64 db, {%81, %83};\n" \
    "wgmma.mma_async.sync.aligned.m64n160k16.f32.bf16.bf16 "               \
    "{%0,%1,%2,%3,%4,%5,%6,%7,%8,%9,%10,%11,%12,%13,%14,%15,%16,%17,%18,%19,%20,%21,%22,%23,%24,%25,%26,%27,%28,%29,%30,%31,%32,%33,%34,%35,%36,%37,%38,%39,%40,%41,%42,%43,%44,%45,%46,%47,%48,%49,%50,%51,%52,%53,%54,%55,%56,%57,%58,%59,%60,%61,%62,%63,%64,%65,%66,%67,%68,%69,%70,%71,%72,%73,%74,%75,%76,%77,%78,%79}, da, db, " SD ", 1, 1, %84, %85;\n}"
    if constexpr (ACC == 2)
        asm volatile(WG_ASM("0") : RW80("+f", d) : "r"(loA), "r"(loB), "n"(HIA), "n"(HIB), "n"(TA), "n"(TB));
    else if constexpr (ACC == 1)
        asm volatile(WG_ASM("1") : RW80("+f", d) : "r"(loA), "r"(loB), "n"(HIA), "n"(HIB), "n"(TA), "n"(TB));
    else
        asm volatile(WG_ASM("0") : RW80("=f", d) : "r"(loA), "r"(loB), "n"(HIA), "n"(HIB), "n"(TA), "n"(TB));
#undef WG_ASM
}
template <int TA, int TB, uint32_t HIB, int ACC, uint32_t HIA = HI_SW128>
__device__ __forceinline__ void wgmma(float (&d)[48], uint32_t loA, uint32_t loB) {
#define WG_ASM(SD)                                                          \
    "{\n.reg .b64 da, db;\nmov.b64 da, {%48, %50};\nmov.b64 db, {%49, %51};\n" \
    "wgmma.mma_async.sync.aligned.m64n96k16.f32.bf16.bf16 "               \
    "{%0,%1,%2,%3,%4,%5,%6,%7,%8,%9,%10,%11,%12,%13,%14,%15,%16,%17,%18,%19,%20,%21,%22,%23,%24,%25,%26,%27,%28,%29,%30,%31,%32,%33,%34,%35,%36,%37,%38,%39,%40,%41,%42,%43,%44,%45,%46,%47}, da, db, " SD ", 1, 1, %52, %53;\n}"
    if constexpr (ACC == 1)
        asm volatile(WG_ASM("1") : RW48("+f", d) : "r"(loA), "r"(loB), "n"(HIA), "n"(HIB), "n"(TA), "n"(TB));
    else
        asm volatile(WG_ASM("0") : RW48("=f", d) : "r"(loA), "r"(loB), "n"(HIA), "n"(HIB), "n"(TA), "n"(TB));
#undef WG_ASM
}
template <int TA, int TB, uint32_t HIB, int ACC, uint32_t HIA = HI_SW128>
__device__ __forceinline__ void wgmma(float (&d)[32], uint32_t loA, uint32_t loB) {
#define WG_ASM(SD)                                                          \
    "{\n.reg .b64 da, db;\nmov.b64 da, {%32, %34};\nmov.b64 db, {%33, %35};\n" \
    "wgmma.mma_async.sync.aligned.m64n64k16.f32.bf16.bf16 "               \
    "{%0,%1,%2,%3,%4,%5,%6,%7,%8,%9,%10,%11,%12,%13,%14,%15,%16,%17,%18,%19,%20,%21,%22,%23,%24,%25,%26,%27,%28,%29,%30,%31}, da, db, " SD ", 1, 1, %36, %37;\n}"
    if constexpr (ACC == 1)
        asm volatile(WG_ASM("1") : RW32("+f", d) : "r"(loA), "r"(loB), "n"(HIA), "n"(HIB), "n"(TA), "n"(TB));
    else
        asm volatile(WG_ASM("0") : RW32("=f", d) : "r"(loA), "r"(loB), "n"(HIA), "n"(HIB), "n"(TA), "n"(TB));
#undef WG_ASM
}

__device__ __forceinline__ uint32_t pack_bf16(float lo, float hi) {
    uint32_t r;
    asm("cvt.rn.bf16x2.f32 %0, %1, %2;" : "=r"(r) : "f"(hi), "f"(lo));
    return r;
}
__device__ __forceinline__ float ex2(float x) {
    float r;
    asm("ex2.approx.ftz.f32 %0, %1;" : "=f"(r) : "f"(x));
    return r;
}
__device__ __forceinline__ void stsm4t(uint32_t a, uint32_t r0, uint32_t r1, uint32_t r2, uint32_t r3) {
    asm volatile("stmatrix.sync.aligned.m8n8.x4.trans.shared.b16 [%0], {%1,%2,%3,%4};" ::"r"(a), "r"(r0), "r"(r1), "r"(r2), "r"(r3)
                 : "memory");
}
__device__ __forceinline__ uint32_t lds_u(uint32_t a) {
    uint32_t v;
    asm volatile("ld.shared.u32 %0, [%1];" : "=r"(v) : "r"(a) : "memory");
    return v;
}
__device__ __forceinline__ uint4 lds_u4(uint32_t a) {
    uint4 v;
    asm volatile("ld.shared.v4.u32 {%0,%1,%2,%3}, [%4];" : "=r"(v.x), "=r"(v.y), "=r"(v.z), "=r"(v.w) : "r"(a) : "memory");
    return v;
}
__device__ __forceinline__ float2 lds_f2(uint32_t a) {
    float2 v;
    asm volatile("ld.shared.v2.f32 {%0,%1}, [%2];" : "=f"(v.x), "=f"(v.y) : "r"(a) : "memory");
    return v;
}
__device__ __forceinline__ void sts_f(uint32_t a, float v) { asm volatile("st.shared.f32 [%0], %1;" ::"r"(a), "f"(v) : "memory"); }
__device__ __forceinline__ void sts_u(uint32_t a, uint32_t v) { asm volatile("st.shared.u32 [%0], %1;" ::"r"(a), "r"(v) : "memory"); }
__device__ __forceinline__ void sts_f2(uint32_t a, float x, float y) {
    asm volatile("st.shared.v2.f32 [%0], {%1,%2};" ::"r"(a), "f"(x), "f"(y) : "memory");
}

template <bool SIG = false, int NR>
__device__ __forceinline__ void store_tile_t(const float (&d)[NR], uint32_t addr) {
#pragma unroll
    for (int j = 0; j < NR / 8; j++) {
        stsm4t(addr + j * 2048, pack_bf16(d[8 * j], d[8 * j + 1]), pack_bf16(d[8 * j + 2], d[8 * j + 3]),
               pack_bf16(d[8 * j + 4], d[8 * j + 5]), pack_bf16(d[8 * j + 6], d[8 * j + 7]));
        if (SIG && j == 0) nb_arrive<NB_L, 160>();
    }
}

struct TrueT { static constexpr bool value = true; };
struct FalseT { static constexpr bool value = false; };

template <int V>
struct IntT { static constexpr int value = V; };

__device__ __forceinline__ uint32_t get_item(uint32_t sb, int it, uint32_t dl) {
    mbar_wait(sb + BAR_ITEM + it * 8, 0, dl);
    return lds_u(sb + OFF_ITEM + it * 4);
}
__device__ __forceinline__ uint32_t get_item_warp(uint32_t sb, int it, uint32_t dl) {
    return __shfl_sync(0xffffffffu, get_item(sb, it, dl), 0);
}

struct Ring {
    uint32_t slot, ph, dl;
    __device__ __forceinline__ void adv(uint32_t k) {
        slot += k;
        if (slot >= NSLOT) { slot -= NSLOT; ph ^= 1; }
    }
};

template <int K>
__device__ __forceinline__ void qk_step(float (&s)[80], uint32_t loK, uint32_t loQ) {
    wgmma<0, 0, HI_SW128, K != 0, HI_KV>(s, loK + (K >> 2) * 64 + (K & 3) * 2, loQ + (K >> 2) * (XS >> 4) + (K & 3) * 2);
}
template <int K0, int K1>
__device__ __forceinline__ void qk_steps(float (&s)[80], uint32_t loK, uint32_t loQ) {
    if constexpr (K0 < K1) {
        qk_step<K0>(s, loK, loQ);
        qk_steps<K0 + 1, K1>(s, loK, loQ);
    }
}
__device__ __forceinline__ uint32_t add_bf2(uint32_t a, uint32_t b) {
    uint32_t r;
    asm("add.rn.bf16x2 %0, %1, %2;" : "=r"(r) : "r"(a), "r"(b));
    return r;
}
__device__ __forceinline__ uint32_t fma_bf2(uint32_t a, uint32_t b, uint32_t c) {
    uint32_t r;
    asm("fma.rn.bf16x2 %0, %1, %2, %3;" : "=r"(r) : "r"(a), "r"(b), "r"(c));
    return r;
}
template <int J>
__device__ __forceinline__ void exp_block(const float (&s)[80], uint32_t (&k)[40], uint32_t pa, float mref) {
    if constexpr (J < 10) {
#pragma unroll
        for (int i = 4 * J; i < 4 * J + 4; i++)
            k[i] = pack_bf16(ex2(fmaf(s[2 * i], SM_C, -mref)), ex2(fmaf(s[2 * i + 1], SM_C, -mref)));
#pragma unroll
        for (int i = 0; i < 4; i++)
            asm volatile("stmatrix.sync.aligned.m8n8.x1.trans.shared.b16 [%0], {%1};" ::"r"(((i & 1) ? pa ^ 16 : pa) + J * 2048 + (i >> 1) * 1024),
                         "r"(k[4 * J + i])
                         : "memory");
        exp_block<J + 1>(s, k, pa, mref);
    }
}
__device__ __forceinline__ void sum_block(const uint32_t (&k)[40], float (&l)[10], uint32_t lane) {
    const bool b4 = lane & 16, b3 = lane & 8;
    uint32_t ps[20], t[10];
#pragma unroll
    for (int j = 0; j < 20; j++) ps[j] = add_bf2(k[2 * j], k[2 * j + 1]);
#pragma unroll
    for (int j = 0; j < 10; j++)
        t[j] = add_bf2(b4 ? ps[2 * j + 1] : ps[2 * j], __shfl_xor_sync(0xffffffffu, b4 ? ps[2 * j] : ps[2 * j + 1], 16));
#pragma unroll
    for (int i = 0; i < 5; i++) {
        const uint32_t a = b3 ? t[i + 5] : t[i], b = __shfl_xor_sync(0xffffffffu, b3 ? t[i] : t[i + 5], 8);
        l[2 * i] += __uint_as_float(a << 16) + __uint_as_float(b << 16);
        l[2 * i + 1] += __uint_as_float(a & 0xffff0000u) + __uint_as_float(b & 0xffff0000u);
    }
}
template <bool ADD>
__device__ __forceinline__ void sum_store(const float (&l)[10], uint32_t lane, uint32_t lxa) {
    const bool b2 = lane & 4;
    float t[5];
#pragma unroll
    for (int i = 0; i < 5; i++) t[i] = ADD ? __uint_as_float(lds_u(lxa + i * 64)) : 0.f;
#pragma unroll
    for (int i = 0; i < 5; i++)
        sts_f(lxa + i * 64, t[i] + (b2 ? l[2 * i + 1] : l[2 * i]) + __shfl_xor_sync(0xffffffffu, b2 ? l[2 * i] : l[2 * i + 1], 4));
}

__device__ __forceinline__ void fallback_unit(const Params& P, uint32_t e, uint32_t tid) {
    const uint32_t lane = tid & 31, br = IT_BR(e), b = IT_B(e), h = IT_H0(e);
    const __nv_bfloat162* wq = (const __nv_bfloat162*)(P.pwq[br] + h * 192) + lane;
    const __nv_bfloat162* kp = (const __nv_bfloat162*)(P.pk[br] + (size_t)(b * 32 + h) * 512 * 192) + lane;
    const __nv_bfloat162* vp = (const __nv_bfloat162*)(P.pv[br] + (size_t)(b * 32 + h) * 512 * 192) + lane;
#pragma unroll 1
    for (uint32_t qi = 0; qi < 40; qi++) {
        const uint32_t q = 4 * qi + (tid >> 5);
        const __nv_bfloat16* xr = P.px[br] + (size_t)(b * 160 + q) * 640;
        float a[6] = {0.f, 0.f, 0.f, 0.f, 0.f, 0.f};
#pragma unroll 2
        for (int k = 0; k < 640; k++) {
            const float xv = __bfloat162float(xr[k]);
#pragma unroll
            for (int i = 0; i < 3; i++) {
                const float2 wv = __bfloat1622float2(wq[(size_t)k * 3072 + i * 32]);
                a[2 * i] = fmaf(xv, wv.x, a[2 * i]);
                a[2 * i + 1] = fmaf(xv, wv.y, a[2 * i + 1]);
            }
        }
#pragma unroll
        for (int i = 0; i < 6; i++) a[i] = __bfloat162float(__float2bfloat16(a[i]));
        auto score = [&](int key) {
            float d = 0.f;
#pragma unroll
            for (int i = 0; i < 3; i++) {
                const float2 kv = __bfloat1622float2(kp[key * 96 + i * 32]);
                d = fmaf(a[2 * i], kv.x, fmaf(a[2 * i + 1], kv.y, d));
            }
#pragma unroll
            for (int o = 16; o > 0; o >>= 1) d += __shfl_xor_sync(0xffffffffu, d, o);
            return d;
        };
        float m = -INFINITY, o[6] = {0.f, 0.f, 0.f, 0.f, 0.f, 0.f}, sum = 0.f;
#pragma unroll 1
        for (int n = 0; n < 1024; n++) {
            const int key = n & 511;
            const float d = score(key);
            if (n < 512) {
                m = fmaxf(m, d);
            } else {
                const float p = ex2((d - m) * SM_C);
                sum += p;
#pragma unroll
                for (int i = 0; i < 3; i++) {
                    const float2 vv = __bfloat1622float2(vp[key * 96 + i * 32]);
                    o[2 * i] = fmaf(p, vv.x, o[2 * i]);
                    o[2 * i + 1] = fmaf(p, vv.y, o[2 * i + 1]);
                }
            }
        }
        const float inv = __fdividef(1.f, sum);
        __nv_bfloat16* op = (__nv_bfloat16*)ostash(IT_SLOT(e), b) + (q >> 5) * 256 + 2 * ((q & 31) >> 3) + (q & 1);
#pragma unroll
        for (int i = 0; i < 6; i++) {
            const uint32_t d = (i >> 1) * 64 + 2 * lane + (i & 1);
            op[(d >> 3) * 1280 + (d & 7) * 32 + ((((q & 7) >> 1) ^ ((d & 7) >> 1)) << 3)] = __float2bfloat16(o[i] * inv);
        }
    }
}

struct PendO {
    uint32_t v[64];
    unsigned char* gp;
    static __device__ __forceinline__ uint32_t toff() {
        const uint32_t t = tid_now();
        return ((t >> 5) & 3) * 5120 + ((t >> 2) & 7) * 64 + (((t ^ (t >> 3)) & 3) << 4);
    }
    uint32_t pend, sig, bad;
    static __device__ __forceinline__ void scale(uint32_t& x, uint32_t hi, uint32_t lo) {
        asm("{\n.reg .b32 t;\nmul.rn.bf16x2 t, %0, %2;\nfma.rn.bf16x2 %0, %0, %1, t;\n}" : "+r"(x) : "r"(hi), "r"(lo));
    }
    template <int I, int OFF>
    __device__ __forceinline__ void put() {
        asm volatile("{\n.reg .pred p;\nsetp.ne.u32 p, %6, 0;\n@p st.global.v4.b32 [%0+%5], {%1,%2,%3,%4};\n}" ::"l"(gp), "r"(v[I]),
                     "r"(v[I + 1]), "r"(v[I + 2]), "r"(v[I + 3]), "n"(OFF), "r"(pend)
                     : "memory");
    }
    __device__ __forceinline__ void verdict(uint32_t sb, uint32_t W) {
        if (sig) {
            asm volatile("bar.sync %0, 160;" ::"r"(NB_VOTE + W) : "memory");
            bad = __any_sync(0xffffffffu, lds_u(sb + OFF_FB) != 0);
            pend = !bad;
        }
    }
    template <int W, int G, int H>
    __device__ __forceinline__ void half(uint32_t sb) {
        constexpr bool T2 = W == 0 ? G >= 3 : G < 3;
        constexpr int B = T2 ? 40 + 8 * (W == 0 ? G - 3 : G) : 0;
        const uint4 a = lds_u4(sb + OFF_LINV + G * 128 + H * 16 + (threadIdx.x & 3) * 32);
#pragma unroll
        for (int i = 2 * H; i < 8; i += 4) {
            scale(v[8 * G + i], a.x, a.y);
            scale(v[8 * G + i + 1], a.z, a.w);
            if (T2) {
                scale(v[B + i], a.x, a.y);
                scale(v[B + i + 1], a.z, a.w);
            }
        }
        if (H == 1) {
            put<8 * G, W * XS + G * 512>();
            put<8 * G + 4, W * XS + G * 512 + 2560>();
            if (T2) {
                put<B, 2 * XS + G * 512>();
                put<B + 4, 2 * XS + G * 512 + 2560>();
            }
            if (G == 4 && pend) nb_arrive<NB_ODONE, 288>();
        }
    }
    template <int W, int G>
    __device__ __forceinline__ void step(uint32_t sb) {
        half<W, G, 0>(sb);
        half<W, G, 1>(sb);
    }
    template <int W>
    __device__ __forceinline__ void flush(uint32_t sb) {
        step<W, 0>(sb);
        step<W, 1>(sb);
        step<W, 2>(sb);
        step<W, 3>(sb);
        step<W, 4>(sb);
    }
    __device__ __forceinline__ void clear() {
#pragma unroll
        for (int i = 0; i < 64; i++) v[i] = 0;
        gp = nullptr;
        pend = 0;
        sig = 0;
        bad = 0;
    }
};

__device__ __forceinline__ uint32_t stsm_off() {
    const uint32_t tid = tid_now(), lane = tid & 31;
    return (lane >> 4) * 1024 + (lane & 7) * 128 + (((((tid >> 4) & 6) + ((lane >> 3) & 1)) ^ (lane & 7)) << 4);
}
__device__ __forceinline__ void q_ahead(float (&q0)[80], uint32_t sb, const Ring& rn, uint32_t phm, bool valid) {
    if (valid) mbar_wait2(sb + BAR_RFULL + rn.slot * 8, rn.ph, sb + BAR_XFULL, phm & 1, rn.dl);
    const uint32_t a = ((((sb + OFF_RING) & 0x3ffff) >> 4) | LO_LBO1) + rn.slot * (SLOT >> 4);
    const uint32_t b = (((sb + OFF_R) & 0x3ffff) >> 4) | LO_LBO1;
    wg_fence();
    wgmma<1, 0, HI_SW128, false>(q0, a, b);
#pragma unroll
    for (int k = 1; k < 4; k++) wgmma<1, 0, HI_SW128, true>(q0, a + (k >> 1) * 768 + (k & 1) * 128, b + k * 2);
    wg_commit();
}
template <int W, int KK>
__device__ __forceinline__ void qproj(float (&q0)[80], float (&q1)[80], uint32_t sb, Ring& r, uint32_t pslot, uint32_t phm,
                                      PendO& po) {
    const uint32_t loR = (((sb + OFF_R) & 0x3ffff) >> 4) | LO_LBO1;
    const uint32_t loRing = (((sb + OFF_RING) & 0x3ffff) >> 4) | LO_LBO1;
    auto ready = [&](int k) {
        mbar_wait2(sb + BAR_RFULL + r.slot * 8, r.ph, sb + BAR_XFULL + (k % 5) * 8, ((phm >> (k % 5)) ^ (k / 5)) & 1, r.dl);
    };
    auto release = [&]() {
        if (KK > 0) {
            wg_wait<1>();
            mbar_arrive_warp(sb + BAR_REMPTY + pslot * 8);
            if (KK <= 5) mbar_arrive_warp(sb + (BAR_XEMPTY + (KK - 1) * 8));
        }
    };
    if (KK == 0 && W == 1) ready(0);
    if (W == 1 && KK == QHOLD) nb_sync<NB_SDONE, 256>();
    const uint32_t a = loRing + r.slot * (SLOT >> 4) + (W == 0 ? 0 : 512), b = loR + (KK % 5) * (XS >> 4);
    wg_fence();
    constexpr bool T0 = W == 1 || KK > 0;
    if (T0) wgmma<1, 0, HI_SW128, KK != 0>(q0, a, b);
    if (W == 0) wgmma<1, 0, HI_SW128, KK != 0 ? 1 : 2>(q1, a + 256, b);
#pragma unroll
    for (int k = 1; k < 4; k++) {
        if (T0) wgmma<1, 0, HI_SW128, true>(q0, a + (k >> 1) * 768 + (k & 1) * 128, b + k * 2);
        if (W == 0) wgmma<1, 0, HI_SW128, true>(q1, a + 256 + (k >> 1) * 768 + (k & 1) * 128, b + k * 2);
    }
    wg_commit();
    const uint32_t cslot = r.slot;
    r.adv(1);
    if (W == 0 || KK < QHOLD) release();
    constexpr int QST = W == 0 ? 2 : 1;
    if (KK == QST) {
        po.verdict(sb, W);
        po.template half<W, 0, 0>(sb);
    }
    if (KK < 9) ready(KK + 1);
    if (W == 1 && KK >= QHOLD) release();
    if (W == 1 && KK == 7) nb_arrive<NB_PDONE, 256>();
    if (KK == QST) po.template half<W, 0, 1>(sb);
    if constexpr (KK > QST && KK < QST + 5) po.template step<W, KK - QST>(sb);
    if constexpr (KK < (W == 0 ? 7 : 9)) {
        qproj<W, KK + 1>(q0, q1, sb, r, cslot, phm, po);
    } else if constexpr (W == 1) {
        const uint32_t sta = sb + OFF_R + 2 * XS + stsm_off();
        wg_wait<0>();
        reg_fence(q0);
        store_tile_t<true>(q0, sta);
        mbar_arrive_warp(sb + BAR_REMPTY + cslot * 8);
    } else {
        const uint32_t s8 = r.slot, a8 = loRing + s8 * (SLOT >> 4);
        wg_fence();
#pragma unroll
        for (int k = 0; k < 4; k++) wgmma<1, 0, HI_SW128, true>(q0, a8 + (k >> 1) * 768 + (k & 1) * 128, loR + 3 * (XS >> 4) + k * 2);
        r.adv(1);
        ready(9);
        const uint32_t s9 = r.slot, a9 = loRing + s9 * (SLOT >> 4);
        r.adv(1);
        wg_fence();
#pragma unroll
        for (int k = 0; k < 4; k++) wgmma<1, 0, HI_SW128, true>(q0, a9 + (k >> 1) * 768 + (k & 1) * 128, loR + 4 * (XS >> 4) + k * 2);
        wg_commit();
        wg_wait<1>();
        mbar_arrive_warp(sb + BAR_REMPTY + cslot * 8);
        wg_fence();
#pragma unroll
        for (int k = 0; k < 8; k++)
            wgmma<1, 0, HI_SW128, true>(q1, (k < 4 ? a8 : a9) + 256 + ((k >> 1) & 1) * 768 + (k & 1) * 128,
                                        loR + (3 + (k >> 2)) * (XS >> 4) + (k & 3) * 2);
        wg_commit();
        nb_arrive<NB_SDONE, 256>();
        sts_u(sb + OFF_GM + 4, r.slot);
        nb_sync<NB_PDONE, 256>();
        wg_wait<1>();
        reg_fence(q0);
        const uint32_t sta = sb + OFF_R + stsm_off();
        store_tile_t(q0, sta);
        wg_wait<0>();
        reg_fence(q1);
        mbar_arrive_warp(sb + BAR_REMPTY + s8 * 8);
        mbar_arrive_warp(sb + BAR_REMPTY + s9 * 8);
        store_tile_t(q1, sta + XS);
        mbar_wait(sb + BAR_RFULL + r.slot * 8, r.ph, r.dl);
    }
}

template <int NR>
__device__ __forceinline__ void opack(const float (&o)[NR], uint32_t* v) {
#pragma unroll
    for (int g = 0; g < NR / 16; g++)
#pragma unroll
        for (int hh = 0; hh < 2; hh++)
#pragma unroll
            for (int t = 0; t < 4; t++) v[8 * g + 4 * hh + t] = pack_bf16(o[16 * g + 4 * t + 2 * hh], o[16 * g + 4 * t + 2 * hh + 1]);
}

__device__ __forceinline__ void out_store(const Params& P, uint32_t src, int col, int b) {
    asm volatile("cp.async.bulk.tensor.5d.global.shared::cta.bulk_group [%0, {%2,%4,%4,%4,%3}], [%1];" ::"l"(&P.out), "r"(src),
                 "r"(col), "r"(b * 5), "r"(0)
                 : "memory");
    asm volatile("cp.async.bulk.commit_group;" ::: "memory");
}

template <bool IS_S>
__device__ __forceinline__ void op_item(uint32_t e, uint32_t sb, Ring& r, uint32_t& phm) {
    constexpr int T0 = IS_S ? 0 : 2;
    constexpr uint32_t BOFF = IS_S ? (3 * 512) >> 4 : 0;
    const uint32_t loRing = (((sb + OFF_RING) & 0x3ffff) >> 4) | LO_LBO1;
    const uint32_t loO = (((sb + OFF_R) & 0x3ffff) >> 4) | LO_OST;
    float c0[80], c1[80], c2[IS_S ? 32 : 48];
    const int T = 3 * (IT_H1(e) - IT_H0(e));
    uint32_t xs = 0;
    auto step = [&](auto first, auto half) {
        constexpr bool F = decltype(first)::value;
        constexpr uint32_t hf = decltype(half)::value;
        if (hf == 0) {
            mbar_wait(sb + BAR_XFULL + xs * 8, (phm >> xs) & 1, r.dl);
            phm ^= 1u << xs;
        }
        mbar_wait(sb + BAR_RFULL + r.slot * 8, r.ph, r.dl);
        const uint32_t a = loRing + r.slot * (SLOT >> 4), b = loO + xs * (XS >> 4) + hf * 640;
        wg_fence();
        wgmma<1, 1, HI_OST, !F>(c0, a + T0 * 128, b);
        wgmma<1, 1, HI_OST, !F>(c1, a + T0 * 128 + 128, b);
        wgmma<1, 1, HI_OST, !F>(c2, a + 512, b + BOFF);
        wgmma<1, 1, HI_OST, true>(c0, a + 640 + T0 * 128, b + 320);
        wgmma<1, 1, HI_OST, true>(c1, a + 640 + T0 * 128 + 128, b + 320);
        wgmma<1, 1, HI_OST, true>(c2, a + 640 + 512, b + 320 + BOFF);
        wg_commit();
    };
    step(TrueT{}, IntT<0>{});
#pragma unroll 1
    for (int t = 1;; t++) {
        uint32_t pslot = r.slot;
        r.adv(1);
        step(FalseT{}, IntT<1>{});
        wg_wait<1>();
        mbar_arrive_warp(sb + BAR_REMPTY + pslot * 8);
        if (t == T) break;
        pslot = r.slot;
        const uint32_t pxs = xs;
        r.adv(1);
        if (++xs == 5) xs = 0;
        step(FalseT{}, IntT<0>{});
        wg_wait<1>();
        mbar_arrive_warp(sb + BAR_REMPTY + pslot * 8);
        mbar_arrive_warp_if(sb + BAR_XEMPTY + pxs * 8, t + 4 < T);
    }
    wg_wait<0>();
    reg_fence(c0);
    reg_fence(c1);
    reg_fence(c2);
    mbar_arrive_warp(sb + BAR_REMPTY + r.slot * 8);
    r.adv(1);
    nb_sync<NB_OPEND, 256>();
    const uint32_t sta = sb + OFF_R + stsm_off();
    store_tile_t(c0, sta + T0 * XS);
    store_tile_t(c1, sta + (T0 + 1) * XS);
    store_tile_t(c2, sta + 4 * XS + (IS_S ? 96 * 128 : 0));
    fence_async_smem();
    nb_arrive<NB_ODONE, 288>();
}

__device__ __forceinline__ void on_item(const Params& P, uint32_t W, uint32_t e, uint32_t sb, Ring& r, uint32_t phm) {
    const uint32_t loRing = (((sb + OFF_RING) & 0x3ffff) >> 4) | LO_LBO1;
    const uint32_t loO = (((sb + OFF_R) & 0x3ffff) >> 4) | LO_OST;
    float c[80];
    const int T = 3 * (IT_H1(e) - IT_H0(e));
    uint32_t xs = 0;
    auto step = [&](auto first) {
        constexpr bool F = decltype(first)::value;
        mbar_wait2(sb + BAR_XFULL + xs * 8, (phm >> xs) & 1, sb + BAR_RFULL + r.slot * 8, r.ph, r.dl);
        const uint32_t a = loRing + r.slot * (SLOT >> 4) + W * 256, b = loO + xs * (XS >> 4);
        wg_fence();
        wgmma<1, 1, HI_OST, !F>(c, a, b);
#pragma unroll
        for (int k = 1; k < 4; k++) wgmma<1, 1, HI_OST, true>(c, a + (k >> 1) * 512 + (k & 1) * 128, b + k * 320);
        wg_commit();
    };
    step(TrueT{});
#pragma unroll 1
    for (int t = 1; t < T; t++) {
        const uint32_t pslot = r.slot, pxs = xs;
        r.adv(1);
        if (++xs == 5) xs = 0, phm = ~phm;
        if (W == 1 && t == T - 2) nb_sync<NB_OPEND, 256>();
        step(FalseT{});
        if (W == 0 && t == T - 1) nb_arrive<NB_OPEND, 256>();
        wg_wait<1>();
        mbar_arrive_warp(sb + BAR_REMPTY + pslot * 8);
        mbar_arrive_warp_if(sb + BAR_XEMPTY + pxs * 8, t + 2 < T);
    }
    xs += 1 + W;
    if (xs >= 5) xs -= 5, phm = ~phm;
    mbar_wait(sb + BAR_XFULL + xs * 8, (phm >> xs) & 1, r.dl);
    const uint32_t sta = sb + OFF_R + xs * XS + stsm_off();
    uint32_t p[40];
#pragma unroll
    for (int j = 0; j < 10; j++)
        asm volatile("ldmatrix.sync.aligned.m8n8.x4.trans.shared.b16 {%0,%1,%2,%3}, [%4];"
                     : "=r"(p[4 * j]), "=r"(p[4 * j + 1]), "=r"(p[4 * j + 2]), "=r"(p[4 * j + 3])
                     : "r"(sta + j * 2048)
                     : "memory");
    wg_wait<0>();
    reg_fence(c);
#pragma unroll
    for (int k = 0; k < 40; k++) {
        c[2 * k] += __uint_as_float(p[k] << 16);
        c[2 * k + 1] += __uint_as_float(p[k] & 0xffff0000u);
    }
    store_tile_t(c, sta);
    fence_async_smem();
    asm volatile("bar.sync %0, 128;" ::"r"(NB_W + W) : "memory");
    if ((tid_now() & 127) == 0) {
        out_store(P, sb + OFF_R + xs * XS, IT_BR(e) * 640 + (2 * IT_HALF(e) + W) * 64, IT_B(e));
        asm volatile("cp.async.bulk.wait_group 0;" ::: "memory");
    }
    __syncwarp();
}

template <int W>
__device__ __forceinline__ uint32_t qa_item(uint32_t e, uint32_t sb, Ring& r, uint32_t phm, PendO& po, float (&q0)[80],
                                            float (&oa)[80], int it) {
    const uint32_t loR = (((sb + OFF_R) & 0x3ffff) >> 4) | LO_LBO1;
    const uint32_t loRing = (((sb + OFF_RING) & 0x3ffff) >> 4) | LO_LBO1;
    qproj<W, 0>(q0, oa, sb, r, 0, phm, po);
    fence_async_smem();
    TSD(W, 1);
    float s[80], ob[W == 0 ? 32 : 48], l[10];
    if (W == 1) {
        nb_arrive<NB_Q2, 256>();
        zero(oa);
        zero(ob);
        reg_fence(oa);
        reg_fence(ob);
    }
    const uint32_t lane = tid_now() & 31, sta = sb + OFF_R + stsm_off();
    auto pv = [&](auto first, uint32_t buf) {
        constexpr bool F = decltype(first)::value;
        if (F) mbar_wait(sb + BAR_RFULL + r.slot * 8, r.ph, r.dl);
        const uint32_t a = loRing + r.slot * (SLOT >> 4), b = loR + (3 + buf) * (XS >> 4);
        wg_fence();
        wgmma<1, 0, HI_SW128, F ? 2 : 1, HI_KV>(oa, a + W * 64, b);
        wgmma<1, 0, HI_SW128, !F, HI_KV>(ob, a + 128, b + (W == 0 ? (96 * 128) >> 4 : 0));
#pragma unroll
        for (int k = 1; k < 4; k++) {
            wgmma<1, 0, HI_SW128, true, HI_KV>(oa, a + W * 64 + k * 384, b + k * 2);
            wgmma<1, 0, HI_SW128, true, HI_KV>(ob, a + 128 + k * 384, b + (W == 0 ? (96 * 128) >> 4 : 0) + k * 2);
        }
        wg_commit();
    };
    zero(l);
    float mref;
    uint32_t kslot, vslot, nx = 0;
    auto tail = [&](auto first, int i) {
        constexpr bool rel_other = !decltype(first)::value;
        uint32_t ps[40];
        exp_block<0>(s, ps, sta + (3 + W) * XS, mref);
        if (rel_other) {
            wg_wait<0>();
            mbar_arrive_warp(sb + BAR_REMPTY + vslot * 8);
            if (W == 1) mbar_arrive_warp_if(sb + BAR_XEMPTY + 24, i == 3);
        }
        fence_async_smem();
        nb_arrive<NB_PFULL + W, 256>();
        TSD(W, 6 + 5 * i);
        if (W == 1) {
            mbar_arrive_warp_if<2>(sb + BAR_XEMPTY + 8, i == 3);
            mbar_arrive_warp_if<2>(sb + BAR_XEMPTY + 16, i == 3);
        }
        if (rel_other) {
            mbar_wait(sb + BAR_RFULL + r.slot * 8, r.ph, r.dl);
            sum_block(ps, l, lane);
        }
        if (W == 0 && i == 3) nx = get_item_warp(sb, it + 1, r.dl);
        TSD(W, 7 + 5 * i);
        nb_sync<NB_W + W, 128>();
        pv(first, W);
        if (!rel_other) sum_block(ps, l, lane);
        TSD(W, 8 + 5 * i);
    };
    if (W == 0) {
        nb_sync<NB_QK, 160>();
        TSD(W, 2);
        wg_fence();
        qk_steps<0, 8>(s, loRing + r.slot * (SLOT >> 4), loR);
        nb_sync<NB_Q2, 256>();
        qk_steps<8, 12>(s, loRing + r.slot * (SLOT >> 4), loR);
        wg_commit();
        nb_arrive<NB_Q01, 256>();
        TSD(W, 4);
        nb_sync<NB_REF, 160>();
        mref = __uint_as_float(lds_u(sb + OFF_GM));
        wg_wait<0>();
        reg_fence(s);
        mbar_arrive_warp<2>(sb + BAR_REMPTY + r.slot * 8);
        r.adv(2);
        TSD(W, 5);
        tail(TrueT{}, 0);
    } else {
        nb_sync<NB_Q01, 256>();
    }
#pragma unroll 1
    for (int i = (W == 0 ? 1 : 0); i < 4; i++) {
        const uint32_t pvslot = r.slot;
        r.adv(1);
        kslot = r.slot;
        mbar_wait(sb + BAR_RFULL + r.slot * 8, r.ph, r.dl);
        wg_fence();
        qk_steps<0, 4>(s, loRing + r.slot * (SLOT >> 4), loR);
        if (W == 1) wg_commit();
        qk_steps<4, 12>(s, loRing + r.slot * (SLOT >> 4), loR);
        wg_commit();
        wg_wait<1>();
        if (W == 1) mbar_arrive_warp_if(sb + BAR_XEMPTY + 0, i == 3);
        mbar_arrive_warp_if(sb + BAR_REMPTY + pvslot * 8, W == 0 || i > 0);
        r.adv(1);
        vslot = r.slot;
        TSD(W, 4 + 5 * i);
        mbar_wait(sb + BAR_RFULL + r.slot * 8, r.ph, r.dl);
        nb_sync<NB_PFULL + (W ^ 1), 256>();
        pv(FalseT{}, W ^ 1);
        if (W == 1) mref = __uint_as_float(lds_u(sb + OFF_GM));
        wg_wait<1>();
        reg_fence(s);
        mbar_arrive_warp<2>(sb + BAR_REMPTY + kslot * 8);
        if (W == 0) mbar_arrive_warp_if(sb + BAR_XEMPTY + 0, i == 3);
        r.adv(W == 1 && i == 3 ? 1 : 2);
        TSD(W, 5 + 5 * i);
        tail(FalseT{}, i);
    }
    if (W == 1) nx = get_item_warp(sb, it + 1, r.dl);
    if (W == 0) {
        Ring rn = r;
        rn.adv(2);
        q_ahead(q0, sb, rn, phm, IT_TYPE(nx) == IT_QA);
        TSD(W, 25);
    }
    const uint32_t w = (tid_now() >> 5) & 3;
    const uint32_t lxa = sb + OFF_LX + w * 640 + (((lane & 8) ? 80 : 0) + ((lane >> 1) & 8) + 2 * (lane & 3) + ((lane >> 2) & 1)) * 4;
    po.gp = ostash(IT_SLOT(e), IT_B(e)) + po.toff();
    po.sig = 1;
    if (W == 0) {
        sum_store<false>(l, lane, lxa);
        nb_arrive<NB_LX, 256>();
        wg_wait<1>();
        mbar_arrive_warp(sb + BAR_REMPTY + r.slot * 8);
        mbar_arrive_warp(sb + BAR_XEMPTY + 24);
        r.adv(1);
        mbar_wait(sb + BAR_RFULL + r.slot * 8, r.ph, r.dl);
        nb_sync<NB_PFULL + 1, 256>();
        pv(FalseT{}, 1);
    } else {
        nb_sync<NB_LX, 256>();
        sum_store<true>(l, lane, lxa);
        nb_arrive<NB_L, 160>();
    }
    TSD(W, 24);
    wg_wait<0>();
    reg_fence(oa);
    reg_fence(ob);
    mbar_arrive_warp(sb + BAR_REMPTY + r.slot * 8);
    mbar_arrive_warp(sb + BAR_XEMPTY + 32);
    r.adv(1);
    opack(ob, po.v + 40);
    opack(oa, po.v);
    return nx;
}

template <int W>
__device__ __forceinline__ uint32_t qa_run(uint32_t e, uint32_t sb, Ring& r, uint32_t phm, PendO& po, int& it) {
    float q0[80], oa[80];
    if (W == 0) {
        zero(oa);
        q_ahead(q0, sb, r, phm, true);
        wg_wait<0>();
    }
#pragma unroll 1
    do {
        TS(W, 0);
        if (W == 0) TS_ITEM(e);
        e = qa_item<W>(e, sb, r, phm, po, q0, oa, it);
        TS(W, 31);
        it++;
    } while (IT_TYPE(e) == IT_QA && !po.bad);
    if (W == 0) {
#pragma unroll
        for (int i = 56; i < 64; i++) po.v[i] = 0;
    }
    return e;
}

__device__ __forceinline__ void consumer(const Params& P, uint32_t W, uint32_t sb, uint32_t dl) {
    int it = 0;
    Ring r{0, 0, dl};
    uint32_t phm = 0;
    uint32_t e = get_item_warp(sb, 0, dl);
#pragma unroll 1
    while (true) {
        if (IT_TYPE(e) == IT_QA) {
            PendO po;
            po.clear();
            e = W == 0 ? qa_run<0>(e, sb, r, phm, po, it) : qa_run<1>(e, sb, r, phm, po, it);
#pragma unroll 1
            for (int m = po.bad ? 2 : 1; m > 0; m--) {
                if (m == 1) {
                    po.verdict(sb, W);
                    if (W == 0) po.flush<0>(sb);
                    else po.flush<1>(sb);
                }
                if (po.bad) {
                    if (W == 0) fallback_unit(P, lds_u(sb + OFF_ITEM + (it - m) * 4), tid_now() & 127);
                    __syncwarp();
                    nb_sync<NB_ODONE, 288>();
                }
            }
        }
        if (e == 0) break;
        if (IT_TYPE(e) == IT_QA) continue;
        TS(W, 0);
        if (W == 0) TS_ITEM(e);
        if (IT_TYPE(e) == IT_ON) {
            on_item(P, W, e, sb, r, phm);
            TS(W, 31);
            break;
        }
        if (W == 0) op_item<true>(e, sb, r, phm);
        else op_item<false>(e, sb, r, phm);
        TS(W, 31);
        e = get_item_warp(sb, ++it, dl);
    }
    TS_DUMP(W);
}

__global__ void __cluster_dims__(2, 1, 1) __launch_bounds__(384, 1) fused_kernel(const __grid_constant__ Params P) {
    extern __shared__ __align__(1024) unsigned char smem_raw[];
    const uint32_t sb = (uint32_t)__cvta_generic_to_shared(smem_raw);
    const uint32_t warp = __shfl_sync(0xffffffffu, threadIdx.x >> 5, 0), wgid = warp >> 2;
    const uint32_t cta = blockIdx.x;
    const uint32_t dl = deadline();

    if (threadIdx.x == 128) {
#pragma unroll
        for (int i = 0; i < NSLOT; i++) {
            mbar_init(sb + BAR_RFULL + i * 8, 1);
            mbar_init(sb + BAR_REMPTY + i * 8, 8);
            mbar_init(sb + BAR_XFULL + i * 8, 1);
            mbar_init(sb + BAR_XEMPTY + i * 8, 8);
        }
        asm volatile("fence.mbarrier_init.release.cluster;" ::: "memory");
        fence_async_smem();
    } else if (threadIdx.x == 160) {
#pragma unroll
        for (int i = 0; i < NSLOT + MAXI; i++) mbar_init(sb + BAR_PRDY + i * 8, 1);
        asm volatile("fence.mbarrier_init.release.cluster;" ::: "memory");
    } else if (threadIdx.x == 0) {
        sts_u(sb + OFF_ITEM, P.cl[cta >> 1].items[0] ? P.cl[cta >> 1].items[0] + 8 * (cta & 1) : 0);
        sts_u(sb + OFF_FB, P.cl[cta >> 1].delay);
    } else if (threadIdx.x == 64) {
        if (sb & 1023) __trap();
        asm volatile("prefetch.tensormap [%0];" ::"l"(&P.wq[0]) : "memory");
        asm volatile("prefetch.tensormap [%0];" ::"l"(&P.x[0]) : "memory");
    }
    __syncthreads();
    {
        const int it = 0;
        if (wgid == 1) TS(0, 30);
    }
    asm volatile("barrier.cluster.arrive.relaxed.aligned;" ::: "memory");
    if (warp < 3) {
        const uint32_t e = __shfl_sync(0xffffffffu, lds_u(sb + OFF_ITEM), 0), d = lds_u(sb + OFF_FB);
        const uint64_t pol = pol_shared();
        const bool isx = warp == 1, lead = (threadIdx.x & 31) == 0;
        uint32_t t0, t1;
        asm volatile("mov.u32 %0, %%clock;" : "=r"(t0));
        do {
            asm volatile("mov.u32 %0, %%clock;" : "=r"(t1));
        } while (t1 - t0 < d);
        __syncwarp();
#pragma unroll 1
        for (int n = 0; n < (e ? NSLOT : 0); n++) {
            const uint32_t bar = sb + (isx ? BAR_XFULL : BAR_RFULL) + n * 8;
            if (lead) {
                if (warp < 2) mbar_expect(bar, isx ? XS : SLOT);
                tma3(sb + (isx ? OFF_R + n * XS : OFF_RING + n * SLOT + warp * (SLOT / 4)), isx ? &P.x[0] : &P.wq[0],
                     isx ? IT_B(e) * 160 : n * 64 + warp * 16, isx ? n : IT_H0(e) * 3, bar, pol);
            }
        }
        if (threadIdx.x == 0) asm volatile("mbarrier.arrive.shared::cta.b64 _, [%0];" ::"r"(sb + BAR_ITEM) : "memory");
        __syncwarp();
    }

    if (wgid == 0) {
        asm volatile("setmaxnreg.dec.sync.aligned.u32 24;");
        if (warp == 0) {
            const bool lead = threadIdx.x == 0;
            const uint64_t pol_first = pol_stream(), pol_norm = pol_shared();
            uint32_t e = __shfl_sync(0xffffffffu, lds_u(sb + OFF_ITEM), 0);
            asm volatile("barrier.cluster.wait.aligned;" ::: "memory");
            unsigned int* const ticket = &g_ticket[next_epoch(0) & 1];
            const uint32_t rank = cta & 1;
            uint32_t peer;
            asm volatile("mapa.shared::cluster.u32 %0, %1, %2;" : "=r"(peer) : "r"(sb), "r"(rank ^ 1));
            Ring r{0, 0, dl};
            uint32_t pm = 0;
            bool told = false;
            auto load_w = [&](const CUtensorMap* m, int row, int blk, uint32_t half_bytes, bool more) {
                auto tell = [&](uint32_t slot) {
                    if (lead) {
                        mbar_expect(sb + BAR_RFULL + slot * 8, 2 * half_bytes);
                        asm volatile("mbarrier.arrive.shared::cluster.b64 _, [%0];" ::"r"(peer + BAR_PRDY + slot * 8) : "memory");
                    }
                };
                const uint32_t slot = r.slot;
                if (!told) {
                    mbar_wait(sb + BAR_REMPTY + slot * 8, r.ph, dl);
                    tell(slot);
                }
                r.adv(1);
                told = more && mbar_test(sb + BAR_REMPTY + r.slot * 8, r.ph);
                if (told) tell(r.slot);
                mbar_wait(sb + BAR_PRDY + slot * 8, (pm >> slot) & 1, dl);
                pm ^= 1u << slot;
                if (lead) tma3_mc(sb + OFF_RING + slot * SLOT + rank * half_bytes, m, row, blk, sb + BAR_RFULL + slot * 8, pol_norm);
            };
#pragma unroll 1
            for (int it = 0; e != 0; it++) {
                uint32_t nx = 0, tk = 0;
                if (rank == 0 && IT_TYPE(e) != IT_ON && it + 2 < MAXI) nx = it + 1 < NSTAT ? P.cl[cta >> 1].items[it + 1] : IT_DYN;
                const uint32_t br = IT_BR(e);
                if (IT_TYPE(e) == IT_QA) {
                    const uint32_t h = IT_H0(e);
#pragma unroll 1
                    for (int kk = it ? 0 : NSLOT; kk < 10; kk++) load_w(&P.wq[br], kk * 64 + rank * 32, h * 3, SLOT / 2, kk < 9);
                    const int grp0 = (IT_B(e) * 32 + h) * 64;
#pragma unroll 1
                    for (int n = 0; n < 16; n++) {
                        if (n == 13 && nx == IT_DYN && lead) tk = atomicAdd(ticket, 1);
                        const bool isv = n == 15 || (n > 0 && !(n & 1));
                        const int j = n == 15 ? 7 : isv ? (n - 2) >> 1 : (n + 1) >> 1;
                        mbar_wait(sb + BAR_REMPTY + r.slot * 8, r.ph, dl);
                        if (lead) {
                            mbar_expect(sb + BAR_RFULL + r.slot * 8, SLOT);
                            asm volatile(
                                "cp.async.bulk.tensor.4d.shared::cluster.global.mbarrier::complete_tx::bytes.L2::cache_hint"
                                " [%0], [%1, {%3,%3,%3,%4}], [%2], %5;" ::"r"(sb + OFF_RING + r.slot * SLOT),
                                "l"(isv ? &P.v[br] : &P.k[br]), "r"(sb + BAR_RFULL + r.slot * 8), "r"(0), "r"(grp0 + j * 8), "l"(pol_first)
                                : "memory");
                        }
                        r.adv(1);
                    }
                } else {
                    const bool wide = IT_TYPE(e) == IT_OP;
                    const int step = wide ? 32 : 64, r1 = IT_H1(e) * 192;
#pragma unroll 1
                    for (int row = IT_H0(e) * 192 + rank * (step >> 1); row < r1; row += step)
                        load_w(wide ? &P.wo[br] : &P.won[br], row, IT_HALF(e) * (wide ? 5 : 2), wide ? XS / 2 : 8192, row + step < r1);
                    if (nx == IT_DYN && lead) tk = atomicAdd(ticket, 1);
                }
                if (rank == 0) {
                    if (nx == IT_DYN) {
                        tk = __shfl_sync(0xffffffffu, tk, 0);
                        nx = tk < P.nlist ? P.list[tk] : 0;
                    }
                    e = nx;
                    if (lead) {
                        asm volatile("st.async.weak.shared::cluster.mbarrier::complete_tx::bytes.b32 [%0], %1, [%2];" ::"r"(
                                         peer + OFF_ITEM + 4 + it * 4),
                                     "r"(e ? e + 8 : 0), "r"(peer + BAR_ITEM + 8 + it * 8)
                                     : "memory");
                        sts_u(sb + OFF_ITEM + 4 + it * 4, e);
                        asm volatile("mbarrier.arrive.shared::cta.b64 _, [%0];" ::"r"(sb + BAR_ITEM + 8 + it * 8) : "memory");
                    }
                } else {
                    if (lead) mbar_expect(sb + BAR_ITEM + 8 + it * 8, 4);
                    e = get_item_warp(sb, it + 1, dl);
                }
            }
        } else if (warp == 1) {
            const uint64_t pol_norm = pol_shared(), pol_o = pol_stream();
            const bool lead = threadIdx.x == 32;
            uint32_t phm = 0, epoch = 0;
#pragma unroll 1
            for (int it = 0;; it++) {
                const uint32_t e = get_item_warp(sb, it, dl);
                if (it == 1 || (it == 0 && e == 0)) epoch = next_epoch(1);
                if (e == 0) break;
                const uint32_t br = IT_BR(e);
                uint32_t xs = 0;
                auto acquire = [&]() {
                    mbar_wait(sb + BAR_XEMPTY + xs * 8, (phm >> xs) & 1, dl);
                    phm ^= 1u << xs;
                    if (lead) mbar_expect(sb + BAR_XFULL + xs * 8, XS);
                };
                if (IT_TYPE(e) == IT_QA) {
#pragma unroll 1
                    for (int kk = it ? 0 : 5; kk < 10; kk++) {
                        acquire();
                        if (lead) tma3(sb + OFF_R + xs * XS, &P.x[br], IT_B(e) * 160, kk, sb + BAR_XFULL + xs * 8, pol_norm);
                        if (++xs == 5) xs = 0;
                    }
                } else {
                    const unsigned int* fp = g_flag + (br * 16 + IT_B(e)) * 64 + (threadIdx.x & 31) * 2;
                    uint32_t hm = 0, pm = 0;
                    auto poll = [&](uint32_t hneed, uint32_t pneed) {
                        if ((hm & hneed) == hneed && (pm & pneed) == pneed) return;
                        uint32_t n = 0;
                        do {
                            uint32_t a, b;
                            asm volatile("ld.acquire.gpu.global.v2.u32 {%0, %1}, [%2];" : "=r"(a), "=r"(b) : "l"(fp) : "memory");
                            hm = __ballot_sync(0xffffffffu, a == epoch);
                            pm = __ballot_sync(0xffffffffu, b == epoch);
                            if (++n > 0x1000000) __trap();
                        } while ((hm & hneed) != hneed || (pm & pneed) != pneed);
                        __syncwarp();
                        asm volatile("fence.proxy.async.global;" ::: "memory");
                    };
#pragma unroll 1
                    for (uint32_t h = IT_H0(e); h < IT_H1(e); h++) {
                        const unsigned char* src = ostash(P.slot[br * 32 + h], IT_B(e));
                        poll(1u << h, 0);
#pragma unroll 1
                        for (int t = 0; t < 3; t++) {
                            acquire();
                            if (lead) bulk_load(sb + OFF_R + xs * XS, src + t * XS, XS, sb + BAR_XFULL + xs * 8, pol_o);
                            if (++xs == 5) xs = 0;
                        }
                        if (IT_TYPE(e) == IT_OP && h >= 1) {
                            const uint32_t x1 = xs == 4 ? 0 : xs + 1;
                            mbar_wait(sb + BAR_XFULL + xs * 8, (phm >> xs) & 1, dl);
                            mbar_wait(sb + BAR_XFULL + x1 * 8, (phm >> x1) & 1, dl);
                            if (lead)
                                asm volatile("red.relaxed.gpu.global.max.u32 [%0], %1;" ::"l"(fp + 5 + 2 * IT_HALF(e)), "r"(epoch * 64 + h) : "memory");
                        }
                    }
                    if (IT_TYPE(e) == IT_ON) {
                        poll(0, IT_HALF(e) < 2 ? 1 : IT_HALF(e) == 2 ? 3 : 2);
#pragma unroll 1
                        for (uint32_t tile = 2 * IT_HALF(e); tile < 2 * IT_HALF(e) + 2; tile++) {
                            acquire();
                            if (lead)
                                asm volatile(
                                    "cp.async.bulk.tensor.5d.shared::cluster.global.mbarrier::complete_tx::bytes [%0], [%1, {%3,%5,%5,%5,%4}], [%2];" ::"r"(
                                        sb + OFF_R + xs * XS),
                                    "l"(&P.out), "r"(sb + BAR_XFULL + xs * 8), "r"(br * 640 + tile * 64), "r"(IT_B(e) * 5), "r"(0)
                                    : "memory");
                            if (++xs == 5) xs = 0;
                        }
                    }
                }
            }
        } else if (warp == 2) {
            asm volatile("barrier.cluster.wait.aligned;" ::: "memory");
            const uint32_t epoch = next_epoch(2);
            if (cta == 0) g_ticket[(epoch + 1) & 1] = 0;
#pragma unroll 1
            for (int it = 0;; it++) {
                const uint32_t e = get_item_warp(sb, it, dl);
                if (e == 0) break;
                if (IT_TYPE(e) != IT_QA && threadIdx.x == 64) asm volatile("prefetch.tensormap [%0];" ::"l"(&P.out) : "memory");
                if (IT_TYPE(e) == IT_ON) break;
                nb_sync<NB_ODONE, 288>();
                if (threadIdx.x == 64) {
                    const uint32_t bb = IT_BR(e) * 16 + IT_B(e);
                    if (IT_TYPE(e) != IT_QA) {
                        asm volatile("red.relaxed.gpu.global.max.u32 [%0], %1;" ::"l"(&g_flag[bb * 64 + 5 + 2 * IT_HALF(e)]),
                                     "r"(epoch * 64 + IT_H1(e))
                                     : "memory");
#pragma unroll 1
                        for (int m = 0; m < 5; m++) {
                            out_store(P, sb + OFF_R + m * XS, IT_BR(e) * 640 + IT_HALF(e) * 320 + m * 64, IT_B(e));
                            if (m >= 1) {
                                asm volatile("cp.async.bulk.wait_group.read 1;" ::: "memory");
                                asm volatile("mbarrier.arrive.shared::cta.b64 _, [%0], 8;" ::"r"(sb + BAR_XEMPTY + (m - 1) * 8) : "memory");
                            }
                        }
                        asm volatile("cp.async.bulk.wait_group.read 0;" ::: "memory");
                        asm volatile("mbarrier.arrive.shared::cta.b64 _, [%0], 8;" ::"r"(sb + BAR_XEMPTY + 32) : "memory");
                        if (IT_PART(e)) {
                            asm volatile("cp.async.bulk.wait_group 0;" ::: "memory");
                            asm volatile("fence.proxy.async.global;" ::: "memory");
                        }
                    }
                    if (IT_TYPE(e) == IT_QA || IT_PART(e)) {
                        unsigned int* f = &g_flag[bb * 64 + (IT_TYPE(e) == IT_QA ? 2 * IT_H0(e) : 1 + 2 * IT_HALF(e))];
                        asm volatile("st.release.gpu.global.u32 [%0], %1;" ::"l"(f), "r"(epoch) : "memory");
                    }
                }
                __syncwarp();
            }
            if (threadIdx.x == 64) asm volatile("cp.async.bulk.wait_group 0;" ::: "memory");
            __syncwarp();
            asm volatile("barrier.cluster.arrive.relaxed.aligned;\nbarrier.cluster.wait.aligned;" ::: "memory");
        } else {
            const uint32_t lane = threadIdx.x & 31, p = lane >> 3;
            const uint32_t epoch = next_epoch(3);
#pragma unroll 1
            for (int it = 0;; it++) {
                const uint32_t e = get_item_warp(sb, it, dl);
                if (e == 0) break;
                if (IT_TYPE(e) != IT_QA) continue;
                nb_sync<NB_QK, 160>();
                const uint32_t ka = sb + OFF_RING + lds_u(sb + OFF_GM + 4) * SLOT + p * (2 * 3072 + 256) + (lane & 7) * 16;
                const uint32_t qa = sb + OFF_R + p * 256 + (lane & 7) * 16;
                uint32_t acc = 0;
#pragma unroll 1
                for (int c = 0; c < 3; c++) {
                    const uint4 k = lds_u4(ka + c * 1024);
                    if (c == 2) nb_sync<NB_L, 160>();
                    const uint4 q = lds_u4(qa + c * XS);
                    acc = fma_bf2(k.x, q.x, fma_bf2(k.y, q.y, fma_bf2(k.z, q.z, fma_bf2(k.w, q.w, acc))));
                }
                const float d = __uint_as_float(acc << 16) + __uint_as_float(acc & 0xffff0000u);
                const int sum = __reduce_add_sync(0xffffffffu, __float2int_rn(d * 16.f));
                sts_f(sb + OFF_GM, fmaf((float)sum, SM_C / 64.f, 24.f));
                nb_arrive<NB_REF, 160>();
                if (IT_DEP(e)) {
                    const uint32_t g = IT_DEP(e) - 1, need = epoch * 64 + (g & 31) + 1;
                    const unsigned int* cp = &g_flag[((g >> 5) * 16 + IT_B(e)) * 64 + 5 + 2 * (lane & 1)];
                    for (uint32_t n = 0;; n++) {
                        uint32_t v;
                        asm volatile("ld.acquire.gpu.global.u32 %0, [%1];" : "=r"(v) : "l"(cp) : "memory");
                        if (__all_sync(0xffffffffu, v - need < 64)) break;
                        if (n > 0x800000) __trap();
                        __nanosleep(500);
                    }
                }
                nb_sync<NB_L, 160>();
                bool bad = false;
#pragma unroll
                for (int c = 0; c < 5; c++) {
                    const uint32_t la = sb + OFF_LX + (c * 32 + lane) * 4;
                    const float v = (__uint_as_float(lds_u(la)) + __uint_as_float(lds_u(la + 640))) +
                                    (__uint_as_float(lds_u(la + 1280)) + __uint_as_float(lds_u(la + 1920)));
                    const float inv = __fdividef(1.f, v);
                    const uint32_t hi = pack_bf16(inv, 0.f), lo = pack_bf16(inv - __uint_as_float(hi << 16), 0.f);
                    const uint32_t ia = sb + OFF_LINV + c * 128 + ((lane >> 1) & 3) * 32 + (lane >> 3) * 8 + (lane & 1) * 2;
                    asm volatile("st.shared.u16 [%0], %1;\nst.shared.u16 [%0+4], %2;" ::"r"(ia), "h"((unsigned short)hi), "h"((unsigned short)lo) : "memory");
                    bad |= !(v >= 5.421010862e-20f && v <= 7.9228163e28f);
                }
                sts_u(sb + OFF_FB, __any_sync(0xffffffffu, bad));
                nb_arrive<NB_VOTE, 160>();
                nb_arrive<NB_VOTE + 1, 160>();
            }
        }
    } else {
        asm volatile("setmaxnreg.inc.sync.aligned.u32 240;");
        consumer(P, wgid - 1, sb, dl);
    }
}

typedef CUresult (*EncFn)(CUtensorMap*, CUtensorMapDataType, cuuint32_t, void*, const cuuint64_t*, const cuuint64_t*,
                          const cuuint32_t*, const cuuint32_t*, CUtensorMapInterleave, CUtensorMapSwizzle,
                          CUtensorMapL2promotion, CUtensorMapFloatOOBfill);

void make_map3(EncFn enc, CUtensorMap* m, void* p, uint64_t rows, uint64_t rowbytes, uint64_t nblk, uint32_t boxrows,
               uint32_t boxblk) {
    cuuint64_t dims[3] = {64, rows, nblk};
    cuuint64_t str[2] = {rowbytes, 128};
    cuuint32_t box[3] = {64, boxrows, boxblk};
    cuuint32_t es[3] = {1, 1, 1};
    enc(m, CU_TENSOR_MAP_DATA_TYPE_BFLOAT16, 3, p, dims, str, box, es, CU_TENSOR_MAP_INTERLEAVE_NONE,
        CU_TENSOR_MAP_SWIZZLE_128B, CU_TENSOR_MAP_L2_PROMOTION_NONE, CU_TENSOR_MAP_FLOAT_OOB_FILL_NONE);
}

constexpr int tune(const char*, int def) { return def; }

void build_schedule(Params& P, int ncl) {
    const int mode = tune("MODE", 4), dmax = tune("DMAX", 23000), n0 = tune("N0", 10);
    const int H0[8] = {19, 20, 21, 22, 22, 24, 25, 25}, P0[8] = {373, 335, 333, 329, 333, 333, 331, 330};
    const int ra = tune("RA", 10), ga = tune("GA", 17), rb = tune("RB", 11), g1 = tune("G1", 58);
    int dep[64];
    for (int g = 0, ns = 0, live = 0; g < 64; g++) {
        const bool fresh = mode < 3 || g >= g1 || live < (g < ga ? ra : rb);
        dep[g] = fresh ? 0 : g - live + 1;
        P.slot[g] = fresh ? ns++ : P.slot[g - live];
        live += fresh;
    }
    int H[8], pos[8], psum = 0;
    for (int b = 0; b < 8; b++) {
        const char nh[3] = {'H', (char)('0' + b), 0}, np[3] = {'P', (char)('0' + b), 0};
        H[b] = tune(nh, H0[b]);
        pos[b] = tune(np, P0[b]);
        psum += pos[b];
    }
    const int sk = tune("SK", 10), g0 = tune("G0", 20), g2 = tune("G2", 40);
    int ord[512], nxt[8] = {0, 0, 0, 0, 0, 0, 0, 0};
    for (int k = 0; k < 512; k++) {
        int best = -1;
        float bkey = 0.f;
        for (int b = 0; b < 8; b++) {
            const int g = nxt[b];
            if (g == 64) continue;
            const float w = g < g0 ? 0.f : g < 32 ? (g - g0) / (32.f - g0) : g < g2 ? 1.f : (64 - g) / (64.f - g2);
            const float key = g + w * sk * 0.1f * (pos[b] - psum / 8.f) / 8.f;
            if (best < 0 || key < bkey) best = b, bkey = key;
        }
        ord[k] = nxt[best]++ * 8 + best;
        const int d = dep[ord[k] >> 3];
        if (d > 32) {
            if (pos[best] > k) pos[best] = k;
            if (H[best] < d - 32) H[best] = d - 32;
        }
    }
    int u = 0;
    auto unit = [&]() {
        const int v = ord[u++];
        return mk_item(IT_QA, v >> 8, (v & 7) * 2, (v >> 3) & 31, P.slot[v >> 3], 0) | (dep[v >> 3] << 23);
    };
    int qa[NCL], nq = 0, op[NCL], no = 0;
    for (int c = 0; c < ncl; c++) {
        P.cl[c].delay = 0;
        for (int i = 0; i < NSTAT; i++) P.cl[c].items[i] = 0;
        if (mode >= 3 && c >= 4 && c < 20) op[((c - 4) & 7) * 2 + ((c - 4) >> 3)] = c, no++;
        else if (mode != 2 || (c & 3) == 0) qa[nq++] = c;
    }
    for (int t = 0; t < no; t++) {
        P.cl[op[t]].items[1] = mk_item(IT_OP, 0, t & ~1, 0, 32, t & 1);
        P.cl[op[t]].items[2] = IT_DYN;
            }
    for (int k = 0; k < nq; k++) {
        const int c = qa[(k * (nq % 19 ? 19 : 17)) % nq];
        P.cl[c].items[1] = P.cl[c].items[2] = IT_DYN;
        P.cl[c].delay = k < n0 ? 0 : dmax * (k + 1 - n0) / (nq - n0);
    }
    for (int t = 0; t < no; t++) P.cl[op[(t & 7) * 2 + (t >> 3)]].items[0] = unit();
    for (int k = u; k < no + nq; k++) {
        int best = -1;
        for (int c = 0; c < ncl; c++)
            if (P.cl[c].items[1] && !P.cl[c].items[0] && (best < 0 || P.cl[c].delay < P.cl[best].delay)) best = c;
        P.cl[best].items[0] = unit();
    }
    int n = 0;
    const int uend = mode == 2 ? 8 * nq : 512;
    while (u < uend) {
        for (int b = 0; b < 8 && no; b++)
            if (pos[b] == u) {
                P.list[n++] = mk_item(IT_OP, 1, 2 * b, 0, H[b], 0, 1);
                P.list[n++] = mk_item(IT_OP, 1, 2 * b, 0, H[b], 1, 1);
            }
        P.list[n++] = unit();
    }
    for (int k = 0; no && k < 40; k++) P.list[n++] = mk_item(IT_ON, 1, k / 5 * 2, H[k / 5], 32, k % 5);
    P.nlist = n;
}

}

extern "C" void kernel_launch(void* const* d_in, const int* in_sizes, int n_in, void* d_out, int out_size) {
    static Params P;
    static bool init = false;
    static int ncl = NCL;
    if (!init) {
        EncFn enc = nullptr;
        cudaDriverEntryPointQueryResult qr;
        cudaGetDriverEntryPoint("cuTensorMapEncodeTiled", (void**)&enc, cudaEnableDefault, &qr);
        for (int i = 0; i < 2; i++) {
            P.px[i] = (const __nv_bfloat16*)d_in[5 * i + 0];
            P.pk[i] = (const __nv_bfloat16*)d_in[5 * i + 1];
            P.pv[i] = (const __nv_bfloat16*)d_in[5 * i + 2];
            P.pwq[i] = (const __nv_bfloat16*)d_in[5 * i + 3];
            make_map3(enc, &P.x[i], d_in[5 * i + 0], 2560, 1280, 10, 160, 1);
            for (int j = 0; j < 2; j++) {
                cuuint64_t dims[4] = {64, 8, 3, 16 * 32 * 64};
                cuuint64_t str[3] = {384, 128, 3072};
                cuuint32_t box[4] = {64, 8, 3, 8};
                cuuint32_t es[4] = {1, 1, 1, 1};
                enc(j ? &P.v[i] : &P.k[i], CU_TENSOR_MAP_DATA_TYPE_BFLOAT16, 4, d_in[5 * i + 1 + j], dims, str, box, es,
                    CU_TENSOR_MAP_INTERLEAVE_NONE, CU_TENSOR_MAP_SWIZZLE_128B, CU_TENSOR_MAP_L2_PROMOTION_NONE,
                    CU_TENSOR_MAP_FLOAT_OOB_FILL_NONE);
            }
            make_map3(enc, &P.wq[i], d_in[5 * i + 3], 640, 12288, 96, 32, 3);
            make_map3(enc, &P.wo[i], d_in[5 * i + 4], 6144, 1280, 10, 16, 5);
            make_map3(enc, &P.won[i], d_in[5 * i + 4], 6144, 1280, 10, 32, 2);
        }
        cuuint64_t dims[5] = {1280, 2, 4, 4, 80};
        cuuint64_t str[4] = {2560, 8 * 2560, 2 * 2560, 32 * 2560};
        cuuint32_t box[5] = {64, 2, 4, 4, 5};
        cuuint32_t es[5] = {1, 1, 1, 1, 1};
        enc(&P.out, CU_TENSOR_MAP_DATA_TYPE_BFLOAT16, 5, d_out, dims, str, box, es, CU_TENSOR_MAP_INTERLEAVE_NONE,
            CU_TENSOR_MAP_SWIZZLE_128B, CU_TENSOR_MAP_L2_PROMOTION_NONE, CU_TENSOR_MAP_FLOAT_OOB_FILL_NONE);
        cudaFuncSetAttribute(fused_kernel, cudaFuncAttributeMaxDynamicSharedMemorySize, SMEM_LAUNCH);
        cudaLaunchConfig_t cfg = {};
        cfg.gridDim = dim3(NCTA);
        cfg.blockDim = dim3(384);
        cfg.dynamicSmemBytes = SMEM_LAUNCH;
        int nc = 0;
        if (cudaOccupancyMaxActiveClusters(&nc, fused_kernel, &cfg) == cudaSuccess && nc >= 52 && nc < NCL) ncl = nc;
        (void)cudaGetLastError();
        ncl = tune("NCL", ncl);
        build_schedule(P, ncl);
        init = true;
    }
    fused_kernel<<<2 * ncl, 384, SMEM_LAUNCH>>>(P);
}
```

```cpp
#include <cuda_runtime.h>
#include <cuda.h>
#include <cuda_bf16.h>
#include <stdint.h>

namespace {

constexpr int NCTA = 132;
constexpr int NCL = NCTA / 2;
constexpr int MAXI = 16;
constexpr int NSTAT = 3;
constexpr uint32_t IT_DYN = 0xffffffffu;
constexpr int SLOT = 24576;
constexpr int NSLOT = 5;
constexpr int XS = 20480;
constexpr int OFF_R = 0;
constexpr int OFF_RING = 5 * XS;
constexpr int OFF_MISC = OFF_RING + NSLOT * SLOT;
constexpr int OFF_LX = OFF_MISC;
constexpr int OFF_LINV = OFF_LX + 2560;
constexpr int OFF_FB = OFF_LINV + 640;
constexpr int OFF_GM = OFF_FB + 16;
constexpr int OFF_BAR = OFF_GM + 16;
constexpr int BAR_RFULL = OFF_BAR;
constexpr int BAR_REMPTY = BAR_RFULL + 40;
constexpr int BAR_XFULL = BAR_REMPTY + 40;
constexpr int BAR_XEMPTY = BAR_XFULL + 40;
constexpr int BAR_PRDY = BAR_XEMPTY + 40;
constexpr int BAR_ITEM = BAR_PRDY + 40;
constexpr int OFF_ITEM = BAR_ITEM + MAXI * 8;
constexpr int SMEM_BYTES = OFF_ITEM + MAXI * 4;
static_assert(SMEM_BYTES <= 232448, "smem");

constexpr int NB_W = 1  , NB_PFULL = 3  , NB_VOTE = 5  , NB_Q2 = 7, NB_SDONE = 8, NB_PDONE = 9,
              NB_L = 10, NB_REF = 11, NB_ODONE = 12, NB_OPEND = 13, NB_LX = 14, NB_Q01 = 15, NB_QK = 0  ;

constexpr uint32_t IT_QA = 1, IT_OP = 2, IT_ON = 3;
__host__ __device__ constexpr uint32_t mk_item(uint32_t type, uint32_t br, uint32_t b, uint32_t h0, uint32_t h1, uint32_t half,
                                               uint32_t part = 0) {
    return type | (br << 2) | (b << 3) | (h0 << 7) | (h1 << 13) | (half << 19) | (part << 22);
}
#define IT_TYPE(e) ((e) & 3u)
#define IT_BR(e) (((e) >> 2) & 1u)
#define IT_B(e) (((e) >> 3) & 15u)
#define IT_H0(e) (((e) >> 7) & 63u)
#define IT_H1(e) (((e) >> 13) & 63u)
#define IT_HALF(e) (((e) >> 19) & 7u)
#define IT_PART(e) (((e) >> 22) & 1u)
#define IT_SLOT(e) IT_H1(e)
#define IT_DEP(e) (((e) >> 23) & 127u)

struct Params {
    CUtensorMap x[2], wq[2], k[2], v[2], wo[2], won[2], out;
    const __nv_bfloat16 *px[2], *pwq[2], *pk[2], *pv[2];
    struct alignas(16) { uint32_t delay, items[NSTAT]; } cl[NCL];
    uint32_t nlist;
    uint8_t slot[64];
    uint32_t list[568];
};

constexpr int OUNIT = 61440;
__device__ __align__(1024) unsigned char g_ostash[(size_t)1024 * OUNIT];
__device__ __align__(256) unsigned int g_flag[32 * 64];
__device__ __forceinline__ unsigned char* ostash(uint32_t slot, uint32_t b) { return g_ostash + (slot * 16 + b) * OUNIT; }
__device__ unsigned int g_epoch[NCTA * 4];
__device__ unsigned int g_ticket[2];

constexpr int SMEM_LAUNCH = SMEM_BYTES;
#define TS(role, idx)
#define TS_ITEM(e)
#define TS_DUMP(role)
#define TSD(role, idx)

__device__ __forceinline__ uint64_t pol_stream() {
    uint64_t p;
    asm volatile("createpolicy.fractional.L2::evict_first.b64 %0, 1.0;" : "=l"(p));
    return p;
}
__device__ __forceinline__ uint64_t pol_shared() {
    uint64_t p;
    asm volatile("createpolicy.fractional.L2::evict_unchanged.b64 %0, 1.0;" : "=l"(p));
    return p;
}
constexpr int QHOLD = 8;
constexpr float SM_C = 0.07216878364870322f * 1.4426950408889634f;

__device__ __forceinline__ uint32_t next_epoch(int warp) {
    unsigned int* p = &g_epoch[blockIdx.x * 4 + warp];
    const uint32_t e = __ldcg(p) + 1;
    *p = e;
    return e;
}

__device__ __forceinline__ uint32_t tid_now() {
    uint32_t t;
    asm volatile("mov.u32 %0, %%tid.x;" : "=r"(t));
    return t;
}
__device__ __forceinline__ void mbar_init(uint32_t a, uint32_t c) {
    asm volatile("mbarrier.init.shared::cta.b64 [%0], %1;" ::"r"(a), "r"(c) : "memory");
}
__device__ __forceinline__ void mbar_expect(uint32_t a, uint32_t b) {
    asm volatile("mbarrier.arrive.expect_tx.shared::cta.b64 _, [%0], %1;" ::"r"(a), "r"(b) : "memory");
}
template <int CNT = 1>
__device__ __forceinline__ void mbar_arrive_warp(uint32_t a) {
    if (CNT == 1)
        asm volatile("{\n.reg .pred p;\nelect.sync _|p, 0xffffffff;\n@p mbarrier.arrive.shared::cta.b64 _, [%0];\n}" ::"r"(a) : "memory");
    else
        asm volatile(
            "{\n.reg .pred p;\nelect.sync _|p, 0xffffffff;\n@p mbarrier.arrive.shared::cta.b64 _, [%0];\n"
            "@p mbarrier.arrive.shared::cta.b64 _, [%0];\n}" ::"r"(a)
            : "memory");
}
template <int CNT = 1>
__device__ __forceinline__ void mbar_arrive_warp_if(uint32_t a, bool cond) {
    if (CNT == 1)
        asm volatile(
            "{\n.reg .pred p, c;\nelect.sync _|p, 0xffffffff;\nsetp.ne.and.u32 c, %1, 0, p;\n"
            "@c mbarrier.arrive.shared::cta.b64 _, [%0];\n}" ::"r"(a), "r"((uint32_t)cond)
            : "memory");
    else
        asm volatile(
            "{\n.reg .pred p, c;\nelect.sync _|p, 0xffffffff;\nsetp.ne.and.u32 c, %1, 0, p;\n"
            "@c mbarrier.arrive.shared::cta.b64 _, [%0];\n@c mbarrier.arrive.shared::cta.b64 _, [%0];\n}" ::"r"(a), "r"((uint32_t)cond)
            : "memory");
}
__device__ __forceinline__ uint32_t deadline() {
    uint32_t c;
    asm volatile("mov.u32 %0, %%clock_hi;" : "=r"(c));
    return c + 4;
}
__device__ __forceinline__ void mbar_wait(uint32_t a, uint32_t ph, uint32_t dl) {
    asm volatile(
        "{\n.reg .pred p;\n.reg .u32 m;\n"
        "LOOP:\n"
        "mbarrier.try_wait.parity.shared::cta.b64 p, [%0], %1;\n"
        "@p bra DONE;\n"
        "mov.u32 m, %%clock_hi;\n"
        "setp.ne.u32 p, m, %2;\n"
        "@p bra LOOP;\n"
        "trap;\n"
        "DONE:\n}" ::"r"(a), "r"(ph), "r"(dl)
        : "memory");
}
__device__ __forceinline__ bool mbar_test(uint32_t a, uint32_t ph) {
    uint32_t ok;
    asm volatile("{\n.reg .pred p;\nmbarrier.test_wait.parity.shared::cta.b64 p, [%1], %2;\nselp.u32 %0, 1, 0, p;\n}"
                 : "=r"(ok) : "r"(a), "r"(ph) : "memory");
    return __all_sync(0xffffffffu, ok);
}
__device__ __forceinline__ void mbar_wait2(uint32_t a, uint32_t pa, uint32_t b, uint32_t pb, uint32_t dl) {
    asm volatile(
        "{\n.reg .pred p, q;\n.reg .u32 m;\n"
        "LOOP:\n"
        "mbarrier.try_wait.parity.shared::cta.b64 p, [%0], %1;\n"
        "mbarrier.try_wait.parity.shared::cta.b64 q, [%2], %3;\n"
        "and.pred p, p, q;\n"
        "@p bra DONE;\n"
        "mov.u32 m, %%clock_hi;\n"
        "setp.ne.u32 p, m, %4;\n"
        "@p bra LOOP;\n"
        "trap;\n"
        "DONE:\n}" ::"r"(a), "r"(pa), "r"(b), "r"(pb), "r"(dl)
        : "memory");
}
template <int ID, int CNT>
__device__ __forceinline__ void nb_sync() { asm volatile("bar.sync %0, %1;" ::"n"(ID), "n"(CNT) : "memory"); }
template <int ID, int CNT>
__device__ __forceinline__ void nb_arrive() { asm volatile("bar.arrive %0, %1;" ::"n"(ID), "n"(CNT) : "memory"); }
__device__ __forceinline__ void fence_async_smem() { asm volatile("fence.proxy.async.shared::cta;" ::: "memory"); }

__device__ __forceinline__ void tma3(uint32_t dst, const CUtensorMap* m, int c1, int c2, uint32_t bar, uint64_t pol) {
    asm volatile(
        "cp.async.bulk.tensor.3d.shared::cluster.global.mbarrier::complete_tx::bytes.L2::cache_hint [%0], [%1, {%3,%4,%5}], [%2], %6;" ::"r"(dst),
        "l"(m), "r"(bar), "r"(0), "r"(c1), "r"(c2), "l"(pol)
        : "memory");
}
__device__ __forceinline__ void tma3_mc(uint32_t dst, const CUtensorMap* m, int c1, int c2, uint32_t bar, uint64_t pol) {
    asm volatile(
        "cp.async.bulk.tensor.3d.shared::cluster.global.mbarrier::complete_tx::bytes.multicast::cluster.L2::cache_hint"
        " [%0], [%1, {%3,%4,%5}], [%2], %6, %7;" ::"r"(dst),
        "l"(m), "r"(bar), "r"(0), "r"(c1), "r"(c2), "h"((unsigned short)3), "l"(pol)
        : "memory");
}
__device__ __forceinline__ void bulk_load(uint32_t dst, const void* src, uint32_t bytes, uint32_t bar, uint64_t pol) {
    asm volatile("cp.async.bulk.shared::cluster.global.mbarrier::complete_tx::bytes.L2::cache_hint [%0], [%1], %2, [%3], %4;" ::"r"(dst),
                 "l"(src), "r"(bytes), "r"(bar), "l"(pol)
                 : "memory");
}
__device__ __forceinline__ void wg_fence() { asm volatile("wgmma.fence.sync.aligned;" ::: "memory"); }
__device__ __forceinline__ void wg_commit() { asm volatile("wgmma.commit_group.sync.aligned;" ::: "memory"); }
template <int N>
__device__ __forceinline__ void wg_wait() { asm volatile("wgmma.wait_group.sync.aligned %0;" ::"n"(N) : "memory"); }

#define RW80(c, d) c(d[0]), c(d[1]), c(d[2]), c(d[3]), c(d[4]), c(d[5]), c(d[6]), c(d[7]), c(d[8]), c(d[9]), c(d[10]), c(d[11]), c(d[12]), c(d[13]), c(d[14]), c(d[15]), c(d[16]), c(d[17]), c(d[18]), c(d[19]), c(d[20]), c(d[21]), c(d[22]), c(d[23]), c(d[24]), c(d[25]), c(d[26]), c(d[27]), c(d[28]), c(d[29]), c(d[30]), c(d[31]), c(d[32]), c(d[33]), c(d[34]), c(d[35]), c(d[36]), c(d[37]), c(d[38]), c(d[39]), c(d[40]), c(d[41]), c(d[42]), c(d[43]), c(d[44]), c(d[45]), c(d[46]), c(d[47]), c(d[48]), c(d[49]), c(d[50]), c(d[51]), c(d[52]), c(d[53]), c(d[54]), c(d[55]), c(d[56]), c(d[57]), c(d[58]), c(d[59]), c(d[60]), c(d[61]), c(d[62]), c(d[63]), c(d[64]), c(d[65]), c(d[66]), c(d[67]), c(d[68]), c(d[69]), c(d[70]), c(d[71]), c(d[72]), c(d[73]), c(d[74]), c(d[75]), c(d[76]), c(d[77]), c(d[78]), c(d[79])
#define RW48(c, d) c(d[0]), c(d[1]), c(d[2]), c(d[3]), c(d[4]), c(d[5]), c(d[6]), c(d[7]), c(d[8]), c(d[9]), c(d[10]), c(d[11]), c(d[12]), c(d[13]), c(d[14]), c(d[15]), c(d[16]), c(d[17]), c(d[18]), c(d[19]), c(d[20]), c(d[21]), c(d[22]), c(d[23]), c(d[24]), c(d[25]), c(d[26]), c(d[27]), c(d[28]), c(d[29]), c(d[30]), c(d[31]), c(d[32]), c(d[33]), c(d[34]), c(d[35]), c(d[36]), c(d[37]), c(d[38]), c(d[39]), c(d[40]), c(d[41]), c(d[42]), c(d[43]), c(d[44]), c(d[45]), c(d[46]), c(d[47])
#define RW32(c, d) c(d[0]), c(d[1]), c(d[2]), c(d[3]), c(d[4]), c(d[5]), c(d[6]), c(d[7]), c(d[8]), c(d[9]), c(d[10]), c(d[11]), c(d[12]), c(d[13]), c(d[14]), c(d[15]), c(d[16]), c(d[17]), c(d[18]), c(d[19]), c(d[20]), c(d[21]), c(d[22]), c(d[23]), c(d[24]), c(d[25]), c(d[26]), c(d[27]), c(d[28]), c(d[29]), c(d[30]), c(d[31])

__device__ __forceinline__ void reg_fence(float (&d)[80]) { asm volatile("" : RW80("+f", d)::"memory"); }
__device__ __forceinline__ void reg_fence(float (&d)[48]) { asm volatile("" : RW48("+f", d)::"memory"); }
__device__ __forceinline__ void reg_fence(float (&d)[32]) { asm volatile("" : RW32("+f", d)::"memory"); }

template <int NR>
__device__ __forceinline__ void zero(float (&d)[NR]) {
#pragma unroll
    for (int i = 0; i < NR; i++) d[i] = 0.f;
}

constexpr uint32_t HI_SW128 = (1024u >> 4) | (1u << 30);
constexpr uint32_t HI_KV = (3072u >> 4) | (1u << 30);
constexpr uint32_t HI_OST = (2560u >> 4) | (2u << 30);
constexpr uint32_t LO_LBO1 = (1u << 16);
constexpr uint32_t LO_OST = ((512u >> 4) << 16);

template <int TA, int TB, uint32_t HIB, int ACC, uint32_t HIA = HI_SW128>
__device__ __forceinline__ void wgmma(float (&d)[80], uint32_t loA, uint32_t loB) {
#define WG_ASM(SD)                                                          \
    "{\n.reg .b64 da, db;\nmov.b64 da, {%80, %82};\nmov.b64 db, {%81, %83};\n" \
    "wgmma.mma_async.sync.aligned.m64n160k16.f32.bf16.bf16 "               \
    "{%0,%1,%2,%3,%4,%5,%6,%7,%8,%9,%10,%11,%12,%13,%14,%15,%16,%17,%18,%19,%20,%21,%22,%23,%24,%25,%26,%27,%28,%29,%30,%31,%32,%33,%34,%35,%36,%37,%38,%39,%40,%41,%42,%43,%44,%45,%46,%47,%48,%49,%50,%51,%52,%53,%54,%55,%56,%57,%58,%59,%60,%61,%62,%63,%64,%65,%66,%67,%68,%69,%70,%71,%72,%73,%74,%75,%76,%77,%78,%79}, da, db, " SD ", 1, 1, %84, %85;\n}"
    if constexpr (ACC == 2)
        asm volatile(WG_ASM("0") : RW80("+f", d) : "r"(loA), "r"(loB), "n"(HIA), "n"(HIB), "n"(TA), "n"(TB));
    else if constexpr (ACC == 1)
        asm volatile(WG_ASM("1") : RW80("+f", d) : "r"(loA), "r"(loB), "n"(HIA), "n"(HIB), "n"(TA), "n"(TB));
    else
        asm volatile(WG_ASM("0") : RW80("=f", d) : "r"(loA), "r"(loB), "n"(HIA), "n"(HIB), "n"(TA), "n"(TB));
#undef WG_ASM
}
template <int TA, int TB, uint32_t HIB, int ACC, uint32_t HIA = HI_SW128>
__device__ __forceinline__ void wgmma(float (&d)[48], uint32_t loA, uint32_t loB) {
#define WG_ASM(SD)                                                          \
    "{\n.reg .b64 da, db;\nmov.b64 da, {%48, %50};\nmov.b64 db, {%49, %51};\n" \
    "wgmma.mma_async.sync.aligned.m64n96k16.f32.bf16.bf16 "               \
    "{%0,%1,%2,%3,%4,%5,%6,%7,%8,%9,%10,%11,%12,%13,%14,%15,%16,%17,%18,%19,%20,%21,%22,%23,%24,%25,%26,%27,%28,%29,%30,%31,%32,%33,%34,%35,%36,%37,%38,%39,%40,%41,%42,%43,%44,%45,%46,%47}, da, db, " SD ", 1, 1, %52, %53;\n}"
    if constexpr (ACC == 1)
        asm volatile(WG_ASM("1") : RW48("+f", d) : "r"(loA), "r"(loB), "n"(HIA), "n"(HIB), "n"(TA), "n"(TB));
    else
        asm volatile(WG_ASM("0") : RW48("=f", d) : "r"(loA), "r"(loB), "n"(HIA), "n"(HIB), "n"(TA), "n"(TB));
#undef WG_ASM
}
template <int TA, int TB, uint32_t HIB, int ACC, uint32_t HIA = HI_SW128>
__device__ __forceinline__ void wgmma(float (&d)[32], uint32_t loA, uint32_t loB) {
#define WG_ASM(SD)                                                          \
    "{\n.reg .b64 da, db;\nmov.b64 da, {%32, %34};\nmov.b64 db, {%33, %35};\n" \
    "wgmma.mma_async.sync.aligned.m64n64k16.f32.bf16.bf16 "               \
    "{%0,%1,%2,%3,%4,%5,%6,%7,%8,%9,%10,%11,%12,%13,%14,%15,%16,%17,%18,%19,%20,%21,%22,%23,%24,%25,%26,%27,%28,%29,%30,%31}, da, db, " SD ", 1, 1, %36, %37;\n}"
    if constexpr (ACC == 1)
        asm volatile(WG_ASM("1") : RW32("+f", d) : "r"(loA), "r"(loB), "n"(HIA), "n"(HIB), "n"(TA), "n"(TB));
    else
        asm volatile(WG_ASM("0") : RW32("=f", d) : "r"(loA), "r"(loB), "n"(HIA), "n"(HIB), "n"(TA), "n"(TB));
#undef WG_ASM
}

__device__ __forceinline__ uint32_t pack_bf16(float lo, float hi) {
    uint32_t r;
    asm("cvt.rn.bf16x2.f32 %0, %1, %2;" : "=r"(r) : "f"(hi), "f"(lo));
    return r;
}
__device__ __forceinline__ float ex2(float x) {
    float r;
    asm("ex2.approx.ftz.f32 %0, %1;" : "=f"(r) : "f"(x));
    return r;
}
__device__ __forceinline__ void stsm4t(uint32_t a, uint32_t r0, uint32_t r1, uint32_t r2, uint32_t r3) {
    asm volatile("stmatrix.sync.aligned.m8n8.x4.trans.shared.b16 [%0], {%1,%2,%3,%4};" ::"r"(a), "r"(r0), "r"(r1), "r"(r2), "r"(r3)
                 : "memory");
}
__device__ __forceinline__ uint32_t lds_u(uint32_t a) {
    uint32_t v;
    asm volatile("ld.shared.u32 %0, [%1];" : "=r"(v) : "r"(a) : "memory");
    return v;
}
__device__ __forceinline__ uint4 lds_u4(uint32_t a) {
    uint4 v;
    asm volatile("ld.shared.v4.u32 {%0,%1,%2,%3}, [%4];" : "=r"(v.x), "=r"(v.y), "=r"(v.z), "=r"(v.w) : "r"(a) : "memory");
    return v;
}
__device__ __forceinline__ float2 lds_f2(uint32_t a) {
    float2 v;
    asm volatile("ld.shared.v2.f32 {%0,%1}, [%2];" : "=f"(v.x), "=f"(v.y) : "r"(a) : "memory");
    return v;
}
__device__ __forceinline__ void sts_f(uint32_t a, float v) { asm volatile("st.shared.f32 [%0], %1;" ::"r"(a), "f"(v) : "memory"); }
__device__ __forceinline__ void sts_u(uint32_t a, uint32_t v) { asm volatile("st.shared.u32 [%0], %1;" ::"r"(a), "r"(v) : "memory"); }
__device__ __forceinline__ void sts_f2(uint32_t a, float x, float y) {
    asm volatile("st.shared.v2.f32 [%0], {%1,%2};" ::"r"(a), "f"(x), "f"(y) : "memory");
}

template <bool SIG = false, int NR>
__device__ __forceinline__ void store_tile_t(const float (&d)[NR], uint32_t addr) {
#pragma unroll
    for (int j = 0; j < NR / 8; j++) {
        stsm4t(addr + j * 2048, pack_bf16(d[8 * j], d[8 * j + 1]), pack_bf16(d[8 * j + 2], d[8 * j + 3]),
               pack_bf16(d[8 * j + 4], d[8 * j + 5]), pack_bf16(d[8 * j + 6], d[8 * j + 7]));
        if (SIG && j == 0) nb_arrive<NB_L, 160>();
    }
}

struct TrueT { static constexpr bool value = true; };
struct FalseT { static constexpr bool value = false; };

template <int V>
struct IntT { static constexpr int value = V; };

__device__ __forceinline__ uint32_t get_item(uint32_t sb, int it, uint32_t dl) {
    mbar_wait(sb + BAR_ITEM + it * 8, 0, dl);
    return lds_u(sb + OFF_ITEM + it * 4);
}
__device__ __forceinline__ uint32_t get_item_warp(uint32_t sb, int it, uint32_t dl) {
    return __shfl_sync(0xffffffffu, get_item(sb, it, dl), 0);
}

struct Ring {
    uint32_t slot, ph, dl;
    __device__ __forceinline__ void adv(uint32_t k) {
        slot += k;
        if (slot >= NSLOT) { slot -= NSLOT; ph ^= 1; }
    }
};

template <int K>
__device__ __forceinline__ void qk_step(float (&s)[80], uint32_t loK, uint32_t loQ) {
    wgmma<0, 0, HI_SW128, K != 0, HI_KV>(s, loK + (K >> 2) * 64 + (K & 3) * 2, loQ + (K >> 2) * (XS >> 4) + (K & 3) * 2);
}
template <int K0, int K1>
__device__ __forceinline__ void qk_steps(float (&s)[80], uint32_t loK, uint32_t loQ) {
    if constexpr (K0 < K1) {
        qk_step<K0>(s, loK, loQ);
        qk_steps<K0 + 1, K1>(s, loK, loQ);
    }
}
__device__ __forceinline__ uint32_t add_bf2(uint32_t a, uint32_t b) {
    uint32_t r;
    asm("add.rn.bf16x2 %0, %1, %2;" : "=r"(r) : "r"(a), "r"(b));
    return r;
}
__device__ __forceinline__ uint32_t fma_bf2(uint32_t a, uint32_t b, uint32_t c) {
    uint32_t r;
    asm("fma.rn.bf16x2 %0, %1, %2, %3;" : "=r"(r) : "r"(a), "r"(b), "r"(c));
    return r;
}
template <int J>
__device__ __forceinline__ void exp_block(const float (&s)[80], uint32_t (&k)[40], uint32_t pa, float mref) {
    if constexpr (J < 10) {
#pragma unroll
        for (int i = 4 * J; i < 4 * J + 4; i++)
            k[i] = pack_bf16(ex2(fmaf(s[2 * i], SM_C, -mref)), ex2(fmaf(s[2 * i + 1], SM_C, -mref)));
#pragma unroll
        for (int i = 0; i < 4; i++)
            asm volatile("stmatrix.sync.aligned.m8n8.x1.trans.shared.b16 [%0], {%1};" ::"r"(((i & 1) ? pa ^ 16 : pa) + J * 2048 + (i >> 1) * 1024),
                         "r"(k[4 * J + i])
                         : "memory");
        exp_block<J + 1>(s, k, pa, mref);
    }
}
__device__ __forceinline__ void sum_block(const uint32_t (&k)[40], float (&l)[10], uint32_t lane) {
    const bool b4 = lane & 16, b3 = lane & 8;
    uint32_t ps[20], t[10];
#pragma unroll
    for (int j = 0; j < 20; j++) ps[j] = add_bf2(k[2 * j], k[2 * j + 1]);
#pragma unroll
    for (int j = 0; j < 10; j++)
        t[j] = add_bf2(b4 ? ps[2 * j + 1] : ps[2 * j], __shfl_xor_sync(0xffffffffu, b4 ? ps[2 * j] : ps[2 * j + 1], 16));
#pragma unroll
    for (int i = 0; i < 5; i++) {
        const uint32_t a = b3 ? t[i + 5] : t[i], b = __shfl_xor_sync(0xffffffffu, b3 ? t[i] : t[i + 5], 8);
        l[2 * i] += __uint_as_float(a << 16) + __uint_as_float(b << 16);
        l[2 * i + 1] += __uint_as_float(a & 0xffff0000u) + __uint_as_float(b & 0xffff0000u);
    }
}
template <bool ADD>
__device__ __forceinline__ void sum_store(const float (&l)[10], uint32_t lane, uint32_t lxa) {
    const bool b2 = lane & 4;
    float t[5];
#pragma unroll
    for (int i = 0; i < 5; i++) t[i] = ADD ? __uint_as_float(lds_u(lxa + i * 64)) : 0.f;
#pragma unroll
    for (int i = 0; i < 5; i++)
        sts_f(lxa + i * 64, t[i] + (b2 ? l[2 * i + 1] : l[2 * i]) + __shfl_xor_sync(0xffffffffu, b2 ? l[2 * i] : l[2 * i + 1], 4));
}

__device__ __forceinline__ void fallback_unit(const Params& P, uint32_t e, uint32_t tid) {
    const uint32_t lane = tid & 31, br = IT_BR(e), b = IT_B(e), h = IT_H0(e);
    const __nv_bfloat162* wq = (const __nv_bfloat162*)(P.pwq[br] + h * 192) + lane;
    const __nv_bfloat162* kp = (const __nv_bfloat162*)(P.pk[br] + (size_t)(b * 32 + h) * 512 * 192) + lane;
    const __nv_bfloat162* vp = (const __nv_bfloat162*)(P.pv[br] + (size_t)(b * 32 + h) * 512 * 192) + lane;
#pragma unroll 1
    for (uint32_t qi = 0; qi < 40; qi++) {
        const uint32_t q = 4 * qi + (tid >> 5);
        const __nv_bfloat16* xr = P.px[br] + (size_t)(b * 160 + q) * 640;
        float a[6] = {0.f, 0.f, 0.f, 0.f, 0.f, 0.f};
#pragma unroll 2
        for (int k = 0; k < 640; k++) {
            const float xv = __bfloat162float(xr[k]);
#pragma unroll
            for (int i = 0; i < 3; i++) {
                const float2 wv = __bfloat1622float2(wq[(size_t)k * 3072 + i * 32]);
                a[2 * i] = fmaf(xv, wv.x, a[2 * i]);
                a[2 * i + 1] = fmaf(xv, wv.y, a[2 * i + 1]);
            }
        }
#pragma unroll
        for (int i = 0; i < 6; i++) a[i] = __bfloat162float(__float2bfloat16(a[i]));
        auto score = [&](int key) {
            float d = 0.f;
#pragma unroll
            for (int i = 0; i < 3; i++) {
                const float2 kv = __bfloat1622float2(kp[key * 96 + i * 32]);
                d = fmaf(a[2 * i], kv.x, fmaf(a[2 * i + 1], kv.y, d));
            }
#pragma unroll
            for (int o = 16; o > 0; o >>= 1) d += __shfl_xor_sync(0xffffffffu, d, o);
            return d;
        };
        float m = -INFINITY, o[6] = {0.f, 0.f, 0.f, 0.f, 0.f, 0.f}, sum = 0.f;
#pragma unroll 1
        for (int n = 0; n < 1024; n++) {
            const int key = n & 511;
            const float d = score(key);
            if (n < 512) {
                m = fmaxf(m, d);
            } else {
                const float p = ex2((d - m) * SM_C);
                sum += p;
#pragma unroll
                for (int i = 0; i < 3; i++) {
                    const float2 vv = __bfloat1622float2(vp[key * 96 + i * 32]);
                    o[2 * i] = fmaf(p, vv.x, o[2 * i]);
                    o[2 * i + 1] = fmaf(p, vv.y, o[2 * i + 1]);
                }
            }
        }
        const float inv = __fdividef(1.f, sum);
        __nv_bfloat16* op = (__nv_bfloat16*)ostash(IT_SLOT(e), b) + (q >> 5) * 256 + 2 * ((q & 31) >> 3) + (q & 1);
#pragma unroll
        for (int i = 0; i < 6; i++) {
            const uint32_t d = (i >> 1) * 64 + 2 * lane + (i & 1);
            op[(d >> 3) * 1280 + (d & 7) * 32 + ((((q & 7) >> 1) ^ ((d & 7) >> 1)) << 3)] = __float2bfloat16(o[i] * inv);
        }
    }
}

struct PendO {
    uint32_t v[64];
    unsigned char* gp;
    static __device__ __forceinline__ uint32_t toff() {
        const uint32_t t = tid_now();
        return ((t >> 5) & 3) * 5120 + ((t >> 2) & 7) * 64 + (((t ^ (t >> 3)) & 3) << 4);
    }
    uint32_t pend, sig, bad;
    static __device__ __forceinline__ void scale(uint32_t& x, uint32_t hi, uint32_t lo) {
        asm("{\n.reg .b32 t;\nmul.rn.bf16x2 t, %0, %2;\nfma.rn.bf16x2 %0, %0, %1, t;\n}" : "+r"(x) : "r"(hi), "r"(lo));
    }
    template <int I, int OFF>
    __device__ __forceinline__ void put() {
        asm volatile("{\n.reg .pred p;\nsetp.ne.u32 p, %6, 0;\n@p st.global.v4.b32 [%0+%5], {%1,%2,%3,%4};\n}" ::"l"(gp), "r"(v[I]),
                     "r"(v[I + 1]), "r"(v[I + 2]), "r"(v[I + 3]), "n"(OFF), "r"(pend)
                     : "memory");
    }
    __device__ __forceinline__ void verdict(uint32_t sb, uint32_t W) {
        if (sig) {
            asm volatile("bar.sync %0, 160;" ::"r"(NB_VOTE + W) : "memory");
            bad = __any_sync(0xffffffffu, lds_u(sb + OFF_FB) != 0);
            pend = !bad;
        }
    }
    template <int W, int G, int H>
    __device__ __forceinline__ void half(uint32_t sb) {
        constexpr bool T2 = W == 0 ? G >= 3 : G < 3;
        constexpr int B = T2 ? 40 + 8 * (W == 0 ? G - 3 : G) : 0;
        const uint4 a = lds_u4(sb + OFF_LINV + G * 128 + H * 16 + (threadIdx.x & 3) * 32);
#pragma unroll
        for (int i = 2 * H; i < 8; i += 4) {
            scale(v[8 * G + i], a.x, a.y);
            scale(v[8 * G + i + 1], a.z, a.w);
            if (T2) {
                scale(v[B + i], a.x, a.y);
                scale(v[B + i + 1], a.z, a.w);
            }
        }
        if (H == 1) {
            put<8 * G, W * XS + G * 512>();
            put<8 * G + 4, W * XS + G * 512 + 2560>();
            if (T2) {
                put<B, 2 * XS + G * 512>();
                put<B + 4, 2 * XS + G * 512 + 2560>();
            }
            if (G == 4 && pend) nb_arrive<NB_ODONE, 288>();
        }
    }
    template <int W, int G>
    __device__ __forceinline__ void step(uint32_t sb) {
        half<W, G, 0>(sb);
        half<W, G, 1>(sb);
    }
    template <int W>
    __device__ __forceinline__ void flush(uint32_t sb) {
        step<W, 0>(sb);
        step<W, 1>(sb);
        step<W, 2>(sb);
        step<W, 3>(sb);
        step<W, 4>(sb);
    }
    __device__ __forceinline__ void clear() {
#pragma unroll
        for (int i = 0; i < 64; i++) v[i] = 0;
        gp = nullptr;
        pend = 0;
        sig = 0;
        bad = 0;
    }
};

__device__ __forceinline__ uint32_t stsm_off() {
    const uint32_t tid = tid_now(), lane = tid & 31;
    return (lane >> 4) * 1024 + (lane & 7) * 128 + (((((tid >> 4) & 6) + ((lane >> 3) & 1)) ^ (lane & 7)) << 4);
}
__device__ __forceinline__ void q_ahead(float (&q0)[80], uint32_t sb, const Ring& rn, uint32_t phm, bool valid) {
    if (valid) mbar_wait2(sb + BAR_RFULL + rn.slot * 8, rn.ph, sb + BAR_XFULL, phm & 1, rn.dl);
    const uint32_t a = ((((sb + OFF_RING) & 0x3ffff) >> 4) | LO_LBO1) + rn.slot * (SLOT >> 4);
    const uint32_t b = (((sb + OFF_R) & 0x3ffff) >> 4) | LO_LBO1;
    wg_fence();
    wgmma<1, 0, HI_SW128, false>(q0, a, b);
#pragma unroll
    for (int k = 1; k < 4; k++) wgmma<1, 0, HI_SW128, true>(q0, a + (k >> 1) * 768 + (k & 1) * 128, b + k * 2);
    wg_commit();
}
template <int W, int KK>
__device__ __forceinline__ void qproj(float (&q0)[80], float (&q1)[80], uint32_t sb, Ring& r, uint32_t pslot, uint32_t phm,
                                      PendO& po) {
    const uint32_t loR = (((sb + OFF_R) & 0x3ffff) >> 4) | LO_LBO1;
    const uint32_t loRing = (((sb + OFF_RING) & 0x3ffff) >> 4) | LO_LBO1;
    auto ready = [&](int k) {
        mbar_wait2(sb + BAR_RFULL + r.slot * 8, r.ph, sb + BAR_XFULL + (k % 5) * 8, ((phm >> (k % 5)) ^ (k / 5)) & 1, r.dl);
    };
    auto release = [&]() {
        if (KK > 0) {
            wg_wait<1>();
            mbar_arrive_warp(sb + BAR_REMPTY + pslot * 8);
            if (KK <= 5) mbar_arrive_warp(sb + (BAR_XEMPTY + (KK - 1) * 8));
        }
    };
    if (KK == 0 && W == 1) ready(0);
    if (W == 1 && KK == QHOLD) nb_sync<NB_SDONE, 256>();
    const uint32_t a = loRing + r.slot * (SLOT >> 4) + (W == 0 ? 0 : 512), b = loR + (KK % 5) * (XS >> 4);
    wg_fence();
    constexpr bool T0 = W == 1 || KK > 0;
    if (T0) wgmma<1, 0, HI_SW128, KK != 0>(q0, a, b);
    if (W == 0) wgmma<1, 0, HI_SW128, KK != 0 ? 1 : 2>(q1, a + 256, b);
#pragma unroll
    for (int k = 1; k < 4; k++) {
        if (T0) wgmma<1, 0, HI_SW128, true>(q0, a + (k >> 1) * 768 + (k & 1) * 128, b + k * 2);
        if (W == 0) wgmma<1, 0, HI_SW128, true>(q1, a + 256 + (k >> 1) * 768 + (k & 1) * 128, b + k * 2);
    }
    wg_commit();
    const uint32_t cslot = r.slot;
    r.adv(1);
    if (W == 0 || KK < QHOLD) release();
    constexpr int QST = W == 0 ? 2 : 1;
    if (KK == QST) {
        po.verdict(sb, W);
        po.template half<W, 0, 0>(sb);
    }
    if (KK < 9) ready(KK + 1);
    if (W == 1 && KK >= QHOLD) release();
    if (W == 1 && KK == 7) nb_arrive<NB_PDONE, 256>();
    if (KK == QST) po.template half<W, 0, 1>(sb);
    if constexpr (KK > QST && KK < QST + 5) po.template step<W, KK - QST>(sb);
    if constexpr (KK < (W == 0 ? 7 : 9)) {
        qproj<W, KK + 1>(q0, q1, sb, r, cslot, phm, po);
    } else if constexpr (W == 1) {
        const uint32_t sta = sb + OFF_R + 2 * XS + stsm_off();
        wg_wait<0>();
        reg_fence(q0);
        store_tile_t<true>(q0, sta);
        mbar_arrive_warp(sb + BAR_REMPTY + cslot * 8);
    } else {
        const uint32_t s8 = r.slot, a8 = loRing + s8 * (SLOT >> 4);
        wg_fence();
#pragma unroll
        for (int k = 0; k < 4; k++) wgmma<1, 0, HI_SW128, true>(q0, a8 + (k >> 1) * 768 + (k & 1) * 128, loR + 3 * (XS >> 4) + k * 2);
        r.adv(1);
        ready(9);
        const uint32_t s9 = r.slot, a9 = loRing + s9 * (SLOT >> 4);
        r.adv(1);
        wg_fence();
#pragma unroll
        for (int k = 0; k < 4; k++) wgmma<1, 0, HI_SW128, true>(q0, a9 + (k >> 1) * 768 + (k & 1) * 128, loR + 4 * (XS >> 4) + k * 2);
        wg_commit();
        wg_wait<1>();
        mbar_arrive_warp(sb + BAR_REMPTY + cslot * 8);
        wg_fence();
#pragma unroll
        for (int k = 0; k < 8; k++)
            wgmma<1, 0, HI_SW128, true>(q1, (k < 4 ? a8 : a9) + 256 + ((k >> 1) & 1) * 768 + (k & 1) * 128,
                                        loR + (3 + (k >> 2)) * (XS >> 4) + (k & 3) * 2);
        wg_commit();
        nb_arrive<NB_SDONE, 256>();
        sts_u(sb + OFF_GM + 4, r.slot);
        nb_sync<NB_PDONE, 256>();
        wg_wait<1>();
        reg_fence(q0);
        const uint32_t sta = sb + OFF_R + stsm_off();
        store_tile_t(q0, sta);
        wg_wait<0>();
        reg_fence(q1);
        mbar_arrive_warp(sb + BAR_REMPTY + s8 * 8);
        mbar_arrive_warp(sb + BAR_REMPTY + s9 * 8);
        store_tile_t(q1, sta + XS);
        mbar_wait(sb + BAR_RFULL + r.slot * 8, r.ph, r.dl);
    }
}

template <int NR>
__device__ __forceinline__ void opack(const float (&o)[NR], uint32_t* v) {
#pragma unroll
    for (int g = 0; g < NR / 16; g++)
#pragma unroll
        for (int hh = 0; hh < 2; hh++)
#pragma unroll
            for (int t = 0; t < 4; t++) v[8 * g + 4 * hh + t] = pack_bf16(o[16 * g + 4 * t + 2 * hh], o[16 * g + 4 * t + 2 * hh + 1]);
}

__device__ __forceinline__ void out_store(const Params& P, uint32_t src, int col, int b) {
    asm volatile("cp.async.bulk.tensor.5d.global.shared::cta.bulk_group [%0, {%2,%4,%4,%4,%3}], [%1];" ::"l"(&P.out), "r"(src),
                 "r"(col), "r"(b * 5), "r"(0)
                 : "memory");
    asm volatile("cp.async.bulk.commit_group;" ::: "memory");
}

template <bool IS_S>
__device__ __forceinline__ void op_item(uint32_t e, uint32_t sb, Ring& r, uint32_t& phm) {
    constexpr int T0 = IS_S ? 0 : 2;
    constexpr uint32_t BOFF = IS_S ? (3 * 512) >> 4 : 0;
    const uint32_t loRing = (((sb + OFF_RING) & 0x3ffff) >> 4) | LO_LBO1;
    const uint32_t loO = (((sb + OFF_R) & 0x3ffff) >> 4) | LO_OST;
    float c0[80], c1[80], c2[IS_S ? 32 : 48];
    const int T = 3 * (IT_H1(e) - IT_H0(e));
    uint32_t xs = 0;
    auto step = [&](auto first, auto half) {
        constexpr bool F = decltype(first)::value;
        constexpr uint32_t hf = decltype(half)::value;
        if (hf == 0) {
            mbar_wait(sb + BAR_XFULL + xs * 8, (phm >> xs) & 1, r.dl);
            phm ^= 1u << xs;
        }
        mbar_wait(sb + BAR_RFULL + r.slot * 8, r.ph, r.dl);
        const uint32_t a = loRing + r.slot * (SLOT >> 4), b = loO + xs * (XS >> 4) + hf * 640;
        wg_fence();
        wgmma<1, 1, HI_OST, !F>(c0, a + T0 * 128, b);
        wgmma<1, 1, HI_OST, !F>(c1, a + T0 * 128 + 128, b);
        wgmma<1, 1, HI_OST, !F>(c2, a + 512, b + BOFF);
        wgmma<1, 1, HI_OST, true>(c0, a + 640 + T0 * 128, b + 320);
        wgmma<1, 1, HI_OST, true>(c1, a + 640 + T0 * 128 + 128, b + 320);
        wgmma<1, 1, HI_OST, true>(c2, a + 640 + 512, b + 320 + BOFF);
        wg_commit();
    };
    step(TrueT{}, IntT<0>{});
#pragma unroll 1
    for (int t = 1;; t++) {
        uint32_t pslot = r.slot;
        r.adv(1);
        step(FalseT{}, IntT<1>{});
        wg_wait<1>();
        mbar_arrive_warp(sb + BAR_REMPTY + pslot * 8);
        if (t == T) break;
        pslot = r.slot;
        const uint32_t pxs = xs;
        r.adv(1);
        if (++xs == 5) xs = 0;
        step(FalseT{}, IntT<0>{});
        wg_wait<1>();
        mbar_arrive_warp(sb + BAR_REMPTY + pslot * 8);
        mbar_arrive_warp_if(sb + BAR_XEMPTY + pxs * 8, t + 4 < T);
    }
    wg_wait<0>();
    reg_fence(c0);
    reg_fence(c1);
    reg_fence(c2);
    mbar_arrive_warp(sb + BAR_REMPTY + r.slot * 8);
    r.adv(1);
    nb_sync<NB_OPEND, 256>();
    const uint32_t sta = sb + OFF_R + stsm_off();
    store_tile_t(c0, sta + T0 * XS);
    store_tile_t(c1, sta + (T0 + 1) * XS);
    store_tile_t(c2, sta + 4 * XS + (IS_S ? 96 * 128 : 0));
    fence_async_smem();
    nb_arrive<NB_ODONE, 288>();
}

__device__ __forceinline__ void on_item(const Params& P, uint32_t W, uint32_t e, uint32_t sb, Ring& r, uint32_t phm) {
    const uint32_t loRing = (((sb + OFF_RING) & 0x3ffff) >> 4) | LO_LBO1;
    const uint32_t loO = (((sb + OFF_R) & 0x3ffff) >> 4) | LO_OST;
    float c[80];
    const int T = 3 * (IT_H1(e) - IT_H0(e));
    uint32_t xs = 0;
    auto step = [&](auto first) {
        constexpr bool F = decltype(first)::value;
        mbar_wait2(sb + BAR_XFULL + xs * 8, (phm >> xs) & 1, sb + BAR_RFULL + r.slot * 8, r.ph, r.dl);
        const uint32_t a = loRing + r.slot * (SLOT >> 4) + W * 256, b = loO + xs * (XS >> 4);
        wg_fence();
        wgmma<1, 1, HI_OST, !F>(c, a, b);
#pragma unroll
        for (int k = 1; k < 4; k++) wgmma<1, 1, HI_OST, true>(c, a + (k >> 1) * 512 + (k & 1) * 128, b + k * 320);
        wg_commit();
    };
    step(TrueT{});
#pragma unroll 1
    for (int t = 1; t < T; t++) {
        const uint32_t pslot = r.slot, pxs = xs;
        r.adv(1);
        if (++xs == 5) xs = 0, phm = ~phm;
        if (W == 1 && t == T - 2) nb_sync<NB_OPEND, 256>();
        step(FalseT{});
        if (W == 0 && t == T - 1) nb_arrive<NB_OPEND, 256>();
        wg_wait<1>();
        mbar_arrive_warp(sb + BAR_REMPTY + pslot * 8);
        mbar_arrive_warp_if(sb + BAR_XEMPTY + pxs * 8, t + 2 < T);
    }
    xs += 1 + W;
    if (xs >= 5) xs -= 5, phm = ~phm;
    mbar_wait(sb + BAR_XFULL + xs * 8, (phm >> xs) & 1, r.dl);
    const uint32_t sta = sb + OFF_R + xs * XS + stsm_off();
    uint32_t p[40];
#pragma unroll
    for (int j = 0; j < 10; j++)
        asm volatile("ldmatrix.sync.aligned.m8n8.x4.trans.shared.b16 {%0,%1,%2,%3}, [%4];"
                     : "=r"(p[4 * j]), "=r"(p[4 * j + 1]), "=r"(p[4 * j + 2]), "=r"(p[4 * j + 3])
                     : "r"(sta + j * 2048)
                     : "memory");
    wg_wait<0>();
    reg_fence(c);
#pragma unroll
    for (int k = 0; k < 40; k++) {
        c[2 * k] += __uint_as_float(p[k] << 16);
        c[2 * k + 1] += __uint_as_float(p[k] & 0xffff0000u);
    }
    store_tile_t(c, sta);
    fence_async_smem();
    asm volatile("bar.sync %0, 128;" ::"r"(NB_W + W) : "memory");
    if ((tid_now() & 127) == 0) {
        out_store(P, sb + OFF_R + xs * XS, IT_BR(e) * 640 + (2 * IT_HALF(e) + W) * 64, IT_B(e));
        asm volatile("cp.async.bulk.wait_group 0;" ::: "memory");
    }
    __syncwarp();
}

template <int W>
__device__ __forceinline__ uint32_t qa_item(uint32_t e, uint32_t sb, Ring& r, uint32_t phm, PendO& po, float (&q0)[80],
                                            float (&oa)[80], int it) {
    const uint32_t loR = (((sb + OFF_R) & 0x3ffff) >> 4) | LO_LBO1;
    const uint32_t loRing = (((sb + OFF_RING) & 0x3ffff) >> 4) | LO_LBO1;
    qproj<W, 0>(q0, oa, sb, r, 0, phm, po);
    fence_async_smem();
    TSD(W, 1);
    float s[80], ob[W == 0 ? 32 : 48], l[10];
    if (W == 1) {
        nb_arrive<NB_Q2, 256>();
        zero(oa);
        zero(ob);
        reg_fence(oa);
        reg_fence(ob);
    }
    const uint32_t lane = tid_now() & 31, sta = sb + OFF_R + stsm_off();
    auto pv = [&](auto first, uint32_t buf) {
        constexpr bool F = decltype(first)::value;
        if (F) mbar_wait(sb + BAR_RFULL + r.slot * 8, r.ph, r.dl);
        const uint32_t a = loRing + r.slot * (SLOT >> 4), b = loR + (3 + buf) * (XS >> 4);
        wg_fence();
        wgmma<1, 0, HI_SW128, F ? 2 : 1, HI_KV>(oa, a + W * 64, b);
        wgmma<1, 0, HI_SW128, !F, HI_KV>(ob, a + 128, b + (W == 0 ? (96 * 128) >> 4 : 0));
#pragma unroll
        for (int k = 1; k < 4; k++) {
            wgmma<1, 0, HI_SW128, true, HI_KV>(oa, a + W * 64 + k * 384, b + k * 2);
            wgmma<1, 0, HI_SW128, true, HI_KV>(ob, a + 128 + k * 384, b + (W == 0 ? (96 * 128) >> 4 : 0) + k * 2);
        }
        wg_commit();
    };
    zero(l);
    float mref;
    uint32_t kslot, vslot, nx = 0;
    auto tail = [&](auto first, int i) {
        constexpr bool rel_other = !decltype(first)::value;
        uint32_t ps[40];
        exp_block<0>(s, ps, sta + (3 + W) * XS, mref);
        if (rel_other) {
            wg_wait<0>();
            mbar_arrive_warp(sb + BAR_REMPTY + vslot * 8);
            if (W == 1) mbar_arrive_warp_if(sb + BAR_XEMPTY + 24, i == 3);
        }
        fence_async_smem();
        nb_arrive<NB_PFULL + W, 256>();
        TSD(W, 6 + 5 * i);
        if (W == 1) {
            mbar_arrive_warp_if<2>(sb + BAR_XEMPTY + 8, i == 3);
            mbar_arrive_warp_if<2>(sb + BAR_XEMPTY + 16, i == 3);
        }
        if (rel_other) {
            mbar_wait(sb + BAR_RFULL + r.slot * 8, r.ph, r.dl);
            sum_block(ps, l, lane);
        }
        if (W == 0 && i == 3) nx = get_item_warp(sb, it + 1, r.dl);
        TSD(W, 7 + 5 * i);
        nb_sync<NB_W + W, 128>();
        pv(first, W);
        if (!rel_other) sum_block(ps, l, lane);
        TSD(W, 8 + 5 * i);
    };
    if (W == 0) {
        nb_sync<NB_QK, 160>();
        TSD(W, 2);
        wg_fence();
        qk_steps<0, 8>(s, loRing + r.slot * (SLOT >> 4), loR);
        nb_sync<NB_Q2, 256>();
        qk_steps<8, 12>(s, loRing + r.slot * (SLOT >> 4), loR);
        wg_commit();
        nb_arrive<NB_Q01, 256>();
        TSD(W, 4);
        nb_sync<NB_REF, 160>();
        mref = __uint_as_float(lds_u(sb + OFF_GM));
        wg_wait<0>();
        reg_fence(s);
        mbar_arrive_warp<2>(sb + BAR_REMPTY + r.slot * 8);
        r.adv(2);
        TSD(W, 5);
        tail(TrueT{}, 0);
    } else {
        nb_sync<NB_Q01, 256>();
    }
#pragma unroll 1
    for (int i = (W == 0 ? 1 : 0); i < 4; i++) {
        const uint32_t pvslot = r.slot;
        r.adv(1);
        kslot = r.slot;
        mbar_wait(sb + BAR_RFULL + r.slot * 8, r.ph, r.dl);
        wg_fence();
        qk_steps<0, 4>(s, loRing + r.slot * (SLOT >> 4), loR);
        if (W == 1) wg_commit();
        qk_steps<4, 12>(s, loRing + r.slot * (SLOT >> 4), loR);
        wg_commit();
        wg_wait<1>();
        if (W == 1) mbar_arrive_warp_if(sb + BAR_XEMPTY + 0, i == 3);
        mbar_arrive_warp_if(sb + BAR_REMPTY + pvslot * 8, W == 0 || i > 0);
        r.adv(1);
        vslot = r.slot;
        TSD(W, 4 + 5 * i);
        mbar_wait(sb + BAR_RFULL + r.slot * 8, r.ph, r.dl);
        nb_sync<NB_PFULL + (W ^ 1), 256>();
        pv(FalseT{}, W ^ 1);
        if (W == 1) mref = __uint_as_float(lds_u(sb + OFF_GM));
        wg_wait<1>();
        reg_fence(s);
        mbar_arrive_warp<2>(sb + BAR_REMPTY + kslot * 8);
        if (W == 0) mbar_arrive_warp_if(sb + BAR_XEMPTY + 0, i == 3);
        r.adv(W == 1 && i == 3 ? 1 : 2);
        TSD(W, 5 + 5 * i);
        tail(FalseT{}, i);
    }
    if (W == 1) nx = get_item_warp(sb, it + 1, r.dl);
    if (W == 0) {
        Ring rn = r;
        rn.adv(2);
        q_ahead(q0, sb, rn, phm, IT_TYPE(nx) == IT_QA);
        TSD(W, 25);
    }
    const uint32_t w = (tid_now() >> 5) & 3;
    const uint32_t lxa = sb + OFF_LX + w * 640 + (((lane & 8) ? 80 : 0) + ((lane >> 1) & 8) + 2 * (lane & 3) + ((lane >> 2) & 1)) * 4;
    po.gp = ostash(IT_SLOT(e), IT_B(e)) + po.toff();
    po.sig = 1;
    if (W == 0) {
        sum_store<false>(l, lane, lxa);
        nb_arrive<NB_LX, 256>();
        wg_wait<1>();
        mbar_arrive_warp(sb + BAR_REMPTY + r.slot * 8);
        mbar_arrive_warp(sb + BAR_XEMPTY + 24);
        r.adv(1);
        mbar_wait(sb + BAR_RFULL + r.slot * 8, r.ph, r.dl);
        nb_sync<NB_PFULL + 1, 256>();
        pv(FalseT{}, 1);
    } else {
        nb_sync<NB_LX, 256>();
        sum_store<true>(l, lane, lxa);
        nb_arrive<NB_L, 160>();
    }
    TSD(W, 24);
    wg_wait<0>();
    reg_fence(oa);
    reg_fence(ob);
    mbar_arrive_warp(sb + BAR_REMPTY + r.slot * 8);
    mbar_arrive_warp(sb + BAR_XEMPTY + 32);
    r.adv(1);
    opack(ob, po.v + 40);
    opack(oa, po.v);
    return nx;
}

template <int W>
__device__ __forceinline__ uint32_t qa_run(uint32_t e, uint32_t sb, Ring& r, uint32_t phm, PendO& po, int& it) {
    float q0[80], oa[80];
    if (W == 0) {
        zero(oa);
        q_ahead(q0, sb, r, phm, true);
        wg_wait<0>();
    }
#pragma unroll 1
    do {
        TS(W, 0);
        if (W == 0) TS_ITEM(e);
        e = qa_item<W>(e, sb, r, phm, po, q0, oa, it);
        TS(W, 31);
        it++;
    } while (IT_TYPE(e) == IT_QA && !po.bad);
    if (W == 0) {
#pragma unroll
        for (int i = 56; i < 64; i++) po.v[i] = 0;
    }
    return e;
}

__device__ __forceinline__ void consumer(const Params& P, uint32_t W, uint32_t sb, uint32_t dl) {
    int it = 0;
    Ring r{0, 0, dl};
    uint32_t phm = 0;
    uint32_t e = get_item_warp(sb, 0, dl);
#pragma unroll 1
    while (true) {
        if (IT_TYPE(e) == IT_QA) {
            PendO po;
            po.clear();
            e = W == 0 ? qa_run<0>(e, sb, r, phm, po, it) : qa_run<1>(e, sb, r, phm, po, it);
#pragma unroll 1
            for (int m = po.bad ? 2 : 1; m > 0; m--) {
                if (m == 1) {
                    po.verdict(sb, W);
                    if (W == 0) po.flush<0>(sb);
                    else po.flush<1>(sb);
                }
                if (po.bad) {
                    if (W == 0) fallback_unit(P, lds_u(sb + OFF_ITEM + (it - m) * 4), tid_now() & 127);
                    __syncwarp();
                    nb_sync<NB_ODONE, 288>();
                }
            }
        }
        if (e == 0) break;
        if (IT_TYPE(e) == IT_QA) continue;
        TS(W, 0);
        if (W == 0) TS_ITEM(e);
        if (IT_TYPE(e) == IT_ON) {
            on_item(P, W, e, sb, r, phm);
            TS(W, 31);
            break;
        }
        if (W == 0) op_item<true>(e, sb, r, phm);
        else op_item<false>(e, sb, r, phm);
        TS(W, 31);
        e = get_item_warp(sb, ++it, dl);
    }
    TS_DUMP(W);
}

__global__ void __cluster_dims__(2, 1, 1) __launch_bounds__(384, 1) fused_kernel(const __grid_constant__ Params P) {
    extern __shared__ __align__(1024) unsigned char smem_raw[];
    const uint32_t sb = (uint32_t)__cvta_generic_to_shared(smem_raw);
    const uint32_t warp = __shfl_sync(0xffffffffu, threadIdx.x >> 5, 0), wgid = warp >> 2;
    const uint32_t cta = blockIdx.x;
    const uint32_t dl = deadline();

    if (threadIdx.x == 128) {
#pragma unroll
        for (int i = 0; i < NSLOT; i++) {
            mbar_init(sb + BAR_RFULL + i * 8, 1);
            mbar_init(sb + BAR_REMPTY + i * 8, 8);
            mbar_init(sb + BAR_XFULL + i * 8, 1);
            mbar_init(sb + BAR_XEMPTY + i * 8, 8);
        }
        asm volatile("fence.mbarrier_init.release.cluster;" ::: "memory");
        fence_async_smem();
    } else if (threadIdx.x == 160) {
#pragma unroll
        for (int i = 0; i < NSLOT + MAXI; i++) mbar_init(sb + BAR_PRDY + i * 8, 1);
        asm volatile("fence.mbarrier_init.release.cluster;" ::: "memory");
    } else if (threadIdx.x == 0) {
        sts_u(sb + OFF_ITEM, P.cl[cta >> 1].items[0] ? P.cl[cta >> 1].items[0] + 8 * (cta & 1) : 0);
        sts_u(sb + OFF_FB, P.cl[cta >> 1].delay);
    } else if (threadIdx.x == 64) {
        if (sb & 1023) __trap();
        asm volatile("prefetch.tensormap [%0];" ::"l"(&P.wq[0]) : "memory");
        asm volatile("prefetch.tensormap [%0];" ::"l"(&P.x[0]) : "memory");
    }
    __syncthreads();
    {
        const int it = 0;
        if (wgid == 1) TS(0, 30);
    }
    asm volatile("barrier.cluster.arrive.relaxed.aligned;" ::: "memory");
    if (warp < 3) {
        const uint32_t e = __shfl_sync(0xffffffffu, lds_u(sb + OFF_ITEM), 0), d = lds_u(sb + OFF_FB);
        const uint64_t pol = pol_shared();
        const bool isx = warp == 1, lead = (threadIdx.x & 31) == 0;
        uint32_t t0, t1;
        asm volatile("mov.u32 %0, %%clock;" : "=r"(t0));
        do {
            asm volatile("mov.u32 %0, %%clock;" : "=r"(t1));
        } while (t1 - t0 < d);
        __syncwarp();
#pragma unroll 1
        for (int n = 0; n < (e ? NSLOT : 0); n++) {
            const uint32_t bar = sb + (isx ? BAR_XFULL : BAR_RFULL) + n * 8;
            if (lead) {
                if (warp < 2) mbar_expect(bar, isx ? XS : SLOT);
                tma3(sb + (isx ? OFF_R + n * XS : OFF_RING + n * SLOT + warp * (SLOT / 4)), isx ? &P.x[0] : &P.wq[0],
                     isx ? IT_B(e) * 160 : n * 64 + warp * 16, isx ? n : IT_H0(e) * 3, bar, pol);
            }
        }
        if (threadIdx.x == 0) asm volatile("mbarrier.arrive.shared::cta.b64 _, [%0];" ::"r"(sb + BAR_ITEM) : "memory");
        __syncwarp();
    }

    if (wgid == 0) {
        asm volatile("setmaxnreg.dec.sync.aligned.u32 24;");
        if (warp == 0) {
            const bool lead = threadIdx.x == 0;
            const uint64_t pol_first = pol_stream(), pol_norm = pol_shared();
            uint32_t e = __shfl_sync(0xffffffffu, lds_u(sb + OFF_ITEM), 0);
            asm volatile("barrier.cluster.wait.aligned;" ::: "memory");
            unsigned int* const ticket = &g_ticket[next_epoch(0) & 1];
            const uint32_t rank = cta & 1;
            uint32_t peer;
            asm volatile("mapa.shared::cluster.u32 %0, %1, %2;" : "=r"(peer) : "r"(sb), "r"(rank ^ 1));
            Ring r{0, 0, dl};
            uint32_t pm = 0;
            bool told = false;
            auto load_w = [&](const CUtensorMap* m, int row, int blk, uint32_t half_bytes, bool more) {
                auto tell = [&](uint32_t slot) {
                    if (lead) {
                        mbar_expect(sb + BAR_RFULL + slot * 8, 2 * half_bytes);
                        asm volatile("mbarrier.arrive.shared::cluster.b64 _, [%0];" ::"r"(peer + BAR_PRDY + slot * 8) : "memory");
                    }
                };
                const uint32_t slot = r.slot;
                if (!told) {
                    mbar_wait(sb + BAR_REMPTY + slot * 8, r.ph, dl);
                    tell(slot);
                }
                r.adv(1);
                told = more && mbar_test(sb + BAR_REMPTY + r.slot * 8, r.ph);
                if (told) tell(r.slot);
                mbar_wait(sb + BAR_PRDY + slot * 8, (pm >> slot) & 1, dl);
                pm ^= 1u << slot;
                if (lead) tma3_mc(sb + OFF_RING + slot * SLOT + rank * half_bytes, m, row, blk, sb + BAR_RFULL + slot * 8, pol_norm);
            };
#pragma unroll 1
            for (int it = 0; e != 0; it++) {
                uint32_t nx = 0, tk = 0;
                if (rank == 0 && IT_TYPE(e) != IT_ON && it + 2 < MAXI) nx = it + 1 < NSTAT ? P.cl[cta >> 1].items[it + 1] : IT_DYN;
                const uint32_t br = IT_BR(e);
                if (IT_TYPE(e) == IT_QA) {
                    const uint32_t h = IT_H0(e);
#pragma unroll 1
                    for (int kk = it ? 0 : NSLOT; kk < 10; kk++) load_w(&P.wq[br], kk * 64 + rank * 32, h * 3, SLOT / 2, kk < 9);
                    const int grp0 = (IT_B(e) * 32 + h) * 64;
#pragma unroll 1
                    for (int n = 0; n < 16; n++) {
                        if (n == 15 && nx == IT_DYN && lead) tk = atomicAdd(ticket, 1);
                        const bool isv = n == 15 || (n > 0 && !(n & 1));
                        const int j = n == 15 ? 7 : isv ? (n - 2) >> 1 : (n + 1) >> 1;
                        mbar_wait(sb + BAR_REMPTY + r.slot * 8, r.ph, dl);
                        if (lead) {
                            mbar_expect(sb + BAR_RFULL + r.slot * 8, SLOT);
                            asm volatile(
                                "cp.async.bulk.tensor.4d.shared::cluster.global.mbarrier::complete_tx::bytes.L2::cache_hint"
                                " [%0], [%1, {%3,%3,%3,%4}], [%2], %5;" ::"r"(sb + OFF_RING + r.slot * SLOT),
                                "l"(isv ? &P.v[br] : &P.k[br]), "r"(sb + BAR_RFULL + r.slot * 8), "r"(0), "r"(grp0 + j * 8), "l"(pol_first)
                                : "memory");
                        }
                        r.adv(1);
                    }
                } else {
                    const bool wide = IT_TYPE(e) == IT_OP;
                    const int step = wide ? 32 : 64, r1 = IT_H1(e) * 192;
#pragma unroll 1
                    for (int row = IT_H0(e) * 192 + rank * (step >> 1); row < r1; row += step)
                        load_w(wide ? &P.wo[br] : &P.won[br], row, IT_HALF(e) * (wide ? 5 : 2), wide ? XS / 2 : 8192, row + step < r1);
                    if (nx == IT_DYN && lead) tk = atomicAdd(ticket, 1);
                }
                if (rank == 0) {
                    if (nx == IT_DYN) {
                        tk = __shfl_sync(0xffffffffu, tk, 0);
                        nx = tk < P.nlist ? P.list[tk] : 0;
                    }
                    e = nx;
                    if (lead) {
                        asm volatile("st.async.weak.shared::cluster.mbarrier::complete_tx::bytes.b32 [%0], %1, [%2];" ::"r"(
                                         peer + OFF_ITEM + 4 + it * 4),
                                     "r"(e ? e + 8 : 0), "r"(peer + BAR_ITEM + 8 + it * 8)
                                     : "memory");
                        sts_u(sb + OFF_ITEM + 4 + it * 4, e);
                        asm volatile("mbarrier.arrive.shared::cta.b64 _, [%0];" ::"r"(sb + BAR_ITEM + 8 + it * 8) : "memory");
                    }
                } else {
                    if (lead) mbar_expect(sb + BAR_ITEM + 8 + it * 8, 4);
                    e = get_item_warp(sb, it + 1, dl);
                }
            }
        } else if (warp == 1) {
            const uint64_t pol_norm = pol_shared(), pol_o = pol_stream();
            const bool lead = threadIdx.x == 32;
            uint32_t phm = 0, epoch = 0;
#pragma unroll 1
            for (int it = 0;; it++) {
                const uint32_t e = get_item_warp(sb, it, dl);
                if (it == 1 || (it == 0 && e == 0)) epoch = next_epoch(1);
                if (e == 0) break;
                const uint32_t br = IT_BR(e);
                uint32_t xs = 0;
                auto acquire = [&]() {
                    mbar_wait(sb + BAR_XEMPTY + xs * 8, (phm >> xs) & 1, dl);
                    phm ^= 1u << xs;
                    if (lead) mbar_expect(sb + BAR_XFULL + xs * 8, XS);
                };
                if (IT_TYPE(e) == IT_QA) {
#pragma unroll 1
                    for (int kk = it ? 0 : 5; kk < 10; kk++) {
                        acquire();
                        if (lead) tma3(sb + OFF_R + xs * XS, &P.x[br], IT_B(e) * 160, kk, sb + BAR_XFULL + xs * 8, pol_norm);
                        if (++xs == 5) xs = 0;
                    }
                } else {
                    const unsigned int* fp = g_flag + (br * 16 + IT_B(e)) * 64 + (threadIdx.x & 31) * 2;
                    uint32_t hm = 0, pm = 0;
                    auto poll = [&](uint32_t hneed, uint32_t pneed) {
                        if ((hm & hneed) == hneed && (pm & pneed) == pneed) return;
                        uint32_t n = 0;
                        do {
                            uint32_t a, b;
                            asm volatile("ld.acquire.gpu.global.v2.u32 {%0, %1}, [%2];" : "=r"(a), "=r"(b) : "l"(fp) : "memory");
                            hm = __ballot_sync(0xffffffffu, a == epoch);
                            pm = __ballot_sync(0xffffffffu, b == epoch);
                            if (++n > 0x1000000) __trap();
                        } while ((hm & hneed) != hneed || (pm & pneed) != pneed);
                        __syncwarp();
                        asm volatile("fence.proxy.async.global;" ::: "memory");
                    };
#pragma unroll 1
                    for (uint32_t h = IT_H0(e); h < IT_H1(e); h++) {
                        const unsigned char* src = ostash(P.slot[br * 32 + h], IT_B(e));
                        poll(1u << h, 0);
#pragma unroll 1
                        for (int t = 0; t < 3; t++) {
                            acquire();
                            if (lead) bulk_load(sb + OFF_R + xs * XS, src + t * XS, XS, sb + BAR_XFULL + xs * 8, pol_o);
                            if (++xs == 5) xs = 0;
                        }
                        if (IT_TYPE(e) == IT_OP && h >= 1) {
                            const uint32_t x1 = xs == 4 ? 0 : xs + 1;
                            mbar_wait(sb + BAR_XFULL + xs * 8, (phm >> xs) & 1, dl);
                            mbar_wait(sb + BAR_XFULL + x1 * 8, (phm >> x1) & 1, dl);
                            if (lead)
                                asm volatile("red.relaxed.gpu.global.max.u32 [%0], %1;" ::"l"(fp + 5 + 2 * IT_HALF(e)), "r"(epoch * 64 + h) : "memory");
                        }
                    }
                    if (IT_TYPE(e) == IT_ON) {
                        poll(0, IT_HALF(e) < 2 ? 1 : IT_HALF(e) == 2 ? 3 : 2);
#pragma unroll 1
                        for (uint32_t tile = 2 * IT_HALF(e); tile < 2 * IT_HALF(e) + 2; tile++) {
                            acquire();
                            if (lead)
                                asm volatile(
                                    "cp.async.bulk.tensor.5d.shared::cluster.global.mbarrier::complete_tx::bytes [%0], [%1, {%3,%5,%5,%5,%4}], [%2];" ::"r"(
                                        sb + OFF_R + xs * XS),
                                    "l"(&P.out), "r"(sb + BAR_XFULL + xs * 8), "r"(br * 640 + tile * 64), "r"(IT_B(e) * 5), "r"(0)
                                    : "memory");
                            if (++xs == 5) xs = 0;
                        }
                    }
                }
            }
        } else if (warp == 2) {
            asm volatile("barrier.cluster.wait.aligned;" ::: "memory");
            const uint32_t epoch = next_epoch(2);
            if (cta == 0) g_ticket[(epoch + 1) & 1] = 0;
#pragma unroll 1
            for (int it = 0;; it++) {
                const uint32_t e = get_item_warp(sb, it, dl);
                if (e == 0) break;
                if (IT_TYPE(e) != IT_QA && threadIdx.x == 64) asm volatile("prefetch.tensormap [%0];" ::"l"(&P.out) : "memory");
                if (IT_TYPE(e) == IT_ON) break;
                nb_sync<NB_ODONE, 288>();
                if (threadIdx.x == 64) {
                    const uint32_t bb = IT_BR(e) * 16 + IT_B(e);
                    if (IT_TYPE(e) != IT_QA) {
                        asm volatile("red.relaxed.gpu.global.max.u32 [%0], %1;" ::"l"(&g_flag[bb * 64 + 5 + 2 * IT_HALF(e)]),
                                     "r"(epoch * 64 + IT_H1(e))
                                     : "memory");
#pragma unroll 1
                        for (int m = 0; m < 5; m++) {
                            out_store(P, sb + OFF_R + m * XS, IT_BR(e) * 640 + IT_HALF(e) * 320 + m * 64, IT_B(e));
                            if (m >= 1) {
                                asm volatile("cp.async.bulk.wait_group.read 1;" ::: "memory");
                                asm volatile("mbarrier.arrive.shared::cta.b64 _, [%0], 8;" ::"r"(sb + BAR_XEMPTY + (m - 1) * 8) : "memory");
                            }
                        }
                        asm volatile("cp.async.bulk.wait_group.read 0;" ::: "memory");
                        asm volatile("mbarrier.arrive.shared::cta.b64 _, [%0], 8;" ::"r"(sb + BAR_XEMPTY + 32) : "memory");
                        if (IT_PART(e)) {
                            asm volatile("cp.async.bulk.wait_group 0;" ::: "memory");
                            asm volatile("fence.proxy.async.global;" ::: "memory");
                        }
                    }
                    if (IT_TYPE(e) == IT_QA || IT_PART(e)) {
                        unsigned int* f = &g_flag[bb * 64 + (IT_TYPE(e) == IT_QA ? 2 * IT_H0(e) : 1 + 2 * IT_HALF(e))];
                        asm volatile("st.release.gpu.global.u32 [%0], %1;" ::"l"(f), "r"(epoch) : "memory");
                    }
                }
                __syncwarp();
            }
            if (threadIdx.x == 64) asm volatile("cp.async.bulk.wait_group 0;" ::: "memory");
            __syncwarp();
            asm volatile("barrier.cluster.arrive.relaxed.aligned;\nbarrier.cluster.wait.aligned;" ::: "memory");
        } else {
            const uint32_t lane = threadIdx.x & 31, p = lane >> 3;
            const uint32_t epoch = next_epoch(3);
#pragma unroll 1
            for (int it = 0;; it++) {
                const uint32_t e = get_item_warp(sb, it, dl);
                if (e == 0) break;
                if (IT_TYPE(e) != IT_QA) continue;
                nb_sync<NB_QK, 160>();
                const uint32_t ka = sb + OFF_RING + lds_u(sb + OFF_GM + 4) * SLOT + p * (2 * 3072 + 256) + (lane & 7) * 16;
                const uint32_t qa = sb + OFF_R + p * 256 + (lane & 7) * 16;
                uint32_t acc = 0;
#pragma unroll 1
                for (int c = 0; c < 3; c++) {
                    const uint4 k = lds_u4(ka + c * 1024);
                    if (c == 2) nb_sync<NB_L, 160>();
                    const uint4 q = lds_u4(qa + c * XS);
                    acc = fma_bf2(k.x, q.x, fma_bf2(k.y, q.y, fma_bf2(k.z, q.z, fma_bf2(k.w, q.w, acc))));
                }
                const float d = __uint_as_float(acc << 16) + __uint_as_float(acc & 0xffff0000u);
                const int sum = __reduce_add_sync(0xffffffffu, __float2int_rn(d * 16.f));
                sts_f(sb + OFF_GM, fmaf((float)sum, SM_C / 64.f, 24.f));
                nb_arrive<NB_REF, 160>();
                if (IT_DEP(e)) {
                    const uint32_t g = IT_DEP(e) - 1, need = epoch * 64 + (g & 31) + 1;
                    const unsigned int* cp = &g_flag[((g >> 5) * 16 + IT_B(e)) * 64 + 5 + 2 * (lane & 1)];
                    for (uint32_t n = 0;; n++) {
                        uint32_t v;
                        asm volatile("ld.acquire.gpu.global.u32 %0, [%1];" : "=r"(v) : "l"(cp) : "memory");
                        if (__all_sync(0xffffffffu, v - need < 64)) break;
                        if (n > 0x800000) __trap();
                        __nanosleep(500);
                    }
                }
                nb_sync<NB_L, 160>();
                bool bad = false;
#pragma unroll
                for (int c = 0; c < 5; c++) {
                    const uint32_t la = sb + OFF_LX + (c * 32 + lane) * 4;
                    const float v = (__uint_as_float(lds_u(la)) + __uint_as_float(lds_u(la + 640))) +
                                    (__uint_as_float(lds_u(la + 1280)) + __uint_as_float(lds_u(la + 1920)));
                    const float inv = __fdividef(1.f, v);
                    const uint32_t hi = pack_bf16(inv, 0.f), lo = pack_bf16(inv - __uint_as_float(hi << 16), 0.f);
                    const uint32_t ia = sb + OFF_LINV + c * 128 + ((lane >> 1) & 3) * 32 + (lane >> 3) * 8 + (lane & 1) * 2;
                    asm volatile("st.shared.u16 [%0], %1;\nst.shared.u16 [%0+4], %2;" ::"r"(ia), "h"((unsigned short)hi), "h"((unsigned short)lo) : "memory");
                    bad |= !(v >= 5.421010862e-20f && v <= 7.9228163e28f);
                }
                sts_u(sb + OFF_FB, __any_sync(0xffffffffu, bad));
                nb_arrive<NB_VOTE, 160>();
                nb_arrive<NB_VOTE + 1, 160>();
            }
        }
    } else {
        asm volatile("setmaxnreg.inc.sync.aligned.u32 240;");
        consumer(P, wgid - 1, sb, dl);
    }
}

typedef CUresult (*EncFn)(CUtensorMap*, CUtensorMapDataType, cuuint32_t, void*, const cuuint64_t*, const cuuint64_t*,
                          const cuuint32_t*, const cuuint32_t*, CUtensorMapInterleave, CUtensorMapSwizzle,
                          CUtensorMapL2promotion, CUtensorMapFloatOOBfill);

void make_map3(EncFn enc, CUtensorMap* m, void* p, uint64_t rows, uint64_t rowbytes, uint64_t nblk, uint32_t boxrows,
               uint32_t boxblk) {
    cuuint64_t dims[3] = {64, rows, nblk};
    cuuint64_t str[2] = {rowbytes, 128};
    cuuint32_t box[3] = {64, boxrows, boxblk};
    cuuint32_t es[3] = {1, 1, 1};
    enc(m, CU_TENSOR_MAP_DATA_TYPE_BFLOAT16, 3, p, dims, str, box, es, CU_TENSOR_MAP_INTERLEAVE_NONE,
        CU_TENSOR_MAP_SWIZZLE_128B, CU_TENSOR_MAP_L2_PROMOTION_NONE, CU_TENSOR_MAP_FLOAT_OOB_FILL_NONE);
}

constexpr int tune(const char*, int def) { return def; }

void build_schedule(Params& P, int ncl) {
    const int mode = tune("MODE", 4), dmax = tune("DMAX", 22300), n0 = tune("N0", 10);
    const int H0[8] = {17, 18, 20, 21, 22, 22, 23, 25}, P0[8] = {367, 338, 337, 333, 345, 349, 340, 327};
    const int ra = tune("RA", 10), ga = tune("GA", 17), rb = tune("RB", 11), g1 = tune("G1", 58);
    const int na = ncl == NCL ? tune("NA", 4) : 0;
    const int HA[5] = {tune("A0", 29), tune("A1", 29), tune("A2", 29), tune("A3", 29), tune("A4", 30)};
    int ha = 32;
    for (int b = 0; b < na; b++) ha = HA[b] < ha ? HA[b] : ha;
    int dep[64], fifo[64];
    for (int g = 0, ns = 0, head = 0, tail = 0; g < 64; g++) {
        const bool pinned = g >= ha && g < 32;
        const bool fresh = mode < 3 || pinned || g >= g1 || tail - head < (g < ga ? ra : rb);
        dep[g] = fresh ? 0 : fifo[head] + 1;
        P.slot[g] = fresh ? ns++ : P.slot[fifo[head++]];
        if (!pinned) fifo[tail++] = g;
    }
    int H[8], pos[8], psum = 0;
    for (int b = 0; b < 8; b++) {
        const char nh[3] = {'H', (char)('0' + b), 0}, np[3] = {'P', (char)('0' + b), 0};
        H[b] = tune(nh, H0[b]);
        pos[b] = tune(np, P0[b]);
        psum += pos[b];
    }
    const int sk = tune("SK", 10), g0 = tune("G0", 20), g2 = tune("G2", 40);
    int ord[512], nxt[8] = {0, 0, 0, 0, 0, 0, 0, 0};
    for (int k = 0; k < 512; k++) {
        int best = -1;
        float bkey = 0.f;
        for (int b = 0; b < 8; b++) {
            const int g = nxt[b];
            if (g == 64) continue;
            const float w = g < g0 ? 0.f : g < 32 ? (g - g0) / (32.f - g0) : g < g2 ? 1.f : (64 - g) / (64.f - g2);
            const float key = g + w * sk * 0.1f * (pos[b] - psum / 8.f) / 8.f;
            if (best < 0 || key < bkey) best = b, bkey = key;
        }
        ord[k] = nxt[best]++ * 8 + best;
        const int d = dep[ord[k] >> 3];
        if (d > 32) {
            if (pos[best] > k) pos[best] = k;
            if (H[best] < d - 32) H[best] = d - 32;
        }
    }
    int u = 0;
    auto unit = [&]() {
        const int v = ord[u++];
        return mk_item(IT_QA, v >> 8, (v & 7) * 2, (v >> 3) & 31, P.slot[v >> 3], 0) | (dep[v >> 3] << 23);
    };
    int qa[NCL], nq = 0, op[NCL], no = 0;
    for (int c = 0; c < ncl; c++) {
        P.cl[c].delay = 0;
        for (int i = 0; i < NSTAT; i++) P.cl[c].items[i] = 0;
        if (mode >= 3 && c >= 4 && c < 20) op[((c - 4) & 7) * 2 + ((c - 4) >> 3)] = c, no++;
        else if (mode != 2 || (c & 3) == 0) qa[nq++] = c;
    }
    for (int t = 0; t < no; t++) {
        P.cl[op[t]].items[1] = t / 2 < na ? mk_item(IT_OP, 0, t & ~1, 0, HA[t / 2], t & 1, 1) : mk_item(IT_OP, 0, t & ~1, 0, 32, t & 1);
        P.cl[op[t]].items[2] = IT_DYN;
            }
    for (int k = 0; k < nq; k++) {
        const int c = qa[(k * (nq % 19 ? 19 : 17)) % nq];
        P.cl[c].items[1] = P.cl[c].items[2] = IT_DYN;
        P.cl[c].delay = k < n0 ? 0 : dmax * (k + 1 - n0) / (nq - n0);
    }
    for (int t = 0; t < no; t++) P.cl[op[(t & 7) * 2 + (t >> 3)]].items[0] = unit();
    for (int k = u; k < no + nq; k++) {
        int best = -1;
        for (int c = 0; c < ncl; c++)
            if (P.cl[c].items[1] && !P.cl[c].items[0] && (best < 0 || P.cl[c].delay < P.cl[best].delay)) best = c;
        P.cl[best].items[0] = unit();
    }
    int n = 0;
    const int uend = mode == 2 ? 8 * nq : 512;
    while (u < uend) {
        for (int b = 0; b < 8 && no; b++)
            if (pos[b] == u) {
                P.list[n++] = mk_item(IT_OP, 1, 2 * b, 0, H[b], 0, 1);
                P.list[n++] = mk_item(IT_OP, 1, 2 * b, 0, H[b], 1, 1);
            }
        P.list[n++] = unit();
    }
    for (int k = 0; no && k < 40; k++) P.list[n++] = mk_item(IT_ON, 1, k / 5 * 2, H[k / 5], 32, k % 5);
    for (int k = 0; no && k < 5 * na; k++) P.list[n++] = mk_item(IT_ON, 0, k / 5 * 2, HA[k / 5], 32, k % 5);
    P.nlist = n;
}

}

extern "C" void kernel_launch(void* const* d_in, const int* in_sizes, int n_in, void* d_out, int out_size) {
    static Params P;
    static bool init = false;
    static int ncl = NCL;
    if (!init) {
        EncFn enc = nullptr;
        cudaDriverEntryPointQueryResult qr;
        cudaGetDriverEntryPoint("cuTensorMapEncodeTiled", (void**)&enc, cudaEnableDefault, &qr);
        for (int i = 0; i < 2; i++) {
            P.px[i] = (const __nv_bfloat16*)d_in[5 * i + 0];
            P.pk[i] = (const __nv_bfloat16*)d_in[5 * i + 1];
            P.pv[i] = (const __nv_bfloat16*)d_in[5 * i + 2];
            P.pwq[i] = (const __nv_bfloat16*)d_in[5 * i + 3];
            make_map3(enc, &P.x[i], d_in[5 * i + 0], 2560, 1280, 10, 160, 1);
            for (int j = 0; j < 2; j++) {
                cuuint64_t dims[4] = {64, 8, 3, 16 * 32 * 64};
                cuuint64_t str[3] = {384, 128, 3072};
                cuuint32_t box[4] = {64, 8, 3, 8};
                cuuint32_t es[4] = {1, 1, 1, 1};
                enc(j ? &P.v[i] : &P.k[i], CU_TENSOR_MAP_DATA_TYPE_BFLOAT16, 4, d_in[5 * i + 1 + j], dims, str, box, es,
                    CU_TENSOR_MAP_INTERLEAVE_NONE, CU_TENSOR_MAP_SWIZZLE_128B, CU_TENSOR_MAP_L2_PROMOTION_NONE,
                    CU_TENSOR_MAP_FLOAT_OOB_FILL_NONE);
            }
            make_map3(enc, &P.wq[i], d_in[5 * i + 3], 640, 12288, 96, 32, 3);
            make_map3(enc, &P.wo[i], d_in[5 * i + 4], 6144, 1280, 10, 16, 5);
            make_map3(enc, &P.won[i], d_in[5 * i + 4], 6144, 1280, 10, 32, 2);
        }
        cuuint64_t dims[5] = {1280, 2, 4, 4, 80};
        cuuint64_t str[4] = {2560, 8 * 2560, 2 * 2560, 32 * 2560};
        cuuint32_t box[5] = {64, 2, 4, 4, 5};
        cuuint32_t es[5] = {1, 1, 1, 1, 1};
        enc(&P.out, CU_TENSOR_MAP_DATA_TYPE_BFLOAT16, 5, d_out, dims, str, box, es, CU_TENSOR_MAP_INTERLEAVE_NONE,
            CU_TENSOR_MAP_SWIZZLE_128B, CU_TENSOR_MAP_L2_PROMOTION_NONE, CU_TENSOR_MAP_FLOAT_OOB_FILL_NONE);
        cudaFuncSetAttribute(fused_kernel, cudaFuncAttributeMaxDynamicSharedMemorySize, SMEM_LAUNCH);
        cudaLaunchConfig_t cfg = {};
        cfg.gridDim = dim3(NCTA);
        cfg.blockDim = dim3(384);
        cfg.dynamicSmemBytes = SMEM_LAUNCH;
        int nc = 0;
        if (cudaOccupancyMaxActiveClusters(&nc, fused_kernel, &cfg) == cudaSuccess && nc >= 52 && nc < NCL) ncl = nc;
        (void)cudaGetLastError();
        ncl = tune("NCL", ncl);
        build_schedule(P, ncl);
        init = true;
    }
    fused_kernel<<<2 * ncl, 384, SMEM_LAUNCH>>>(P);
}
```

```cpp
#include <cuda_runtime.h>
#include <cuda.h>
#include <cuda_bf16.h>
#include <stdint.h>

namespace {

constexpr int NCTA = 132;
constexpr int NCL = NCTA / 2;
constexpr int MAXI = 16;
constexpr int NSTAT = 3;
constexpr uint32_t IT_DYN = 0xffffffffu;
constexpr int SLOT = 24576;
constexpr int NSLOT = 5;
constexpr int XS = 20480;
constexpr int OFF_R = 0;
constexpr int OFF_RING = 5 * XS;
constexpr int OFF_MISC = OFF_RING + NSLOT * SLOT;
constexpr int OFF_LX = OFF_MISC;
constexpr int OFF_LINV = OFF_LX + 2560;
constexpr int OFF_FB = OFF_LINV + 640;
constexpr int OFF_GM = OFF_FB + 16;
constexpr int OFF_BAR = OFF_GM + 16;
constexpr int BAR_RFULL = OFF_BAR;
constexpr int BAR_REMPTY = BAR_RFULL + 40;
constexpr int BAR_XFULL = BAR_REMPTY + 40;
constexpr int BAR_XEMPTY = BAR_XFULL + 40;
constexpr int BAR_PRDY = BAR_XEMPTY + 40;
constexpr int BAR_ITEM = BAR_PRDY + 40;
constexpr int OFF_ITEM = BAR_ITEM + MAXI * 8;
constexpr int SMEM_BYTES = OFF_ITEM + MAXI * 4;
static_assert(SMEM_BYTES <= 232448, "smem");

constexpr int NB_W = 1  , NB_PFULL = 3  , NB_VOTE = 5  , NB_Q2 = 7, NB_SDONE = 8, NB_PDONE = 9,
              NB_L = 10, NB_REF = 11, NB_ODONE = 12, NB_OPEND = 13, NB_LX = 14, NB_Q01 = 15, NB_QK = 0  ;

constexpr uint32_t IT_QA = 1, IT_OP = 2, IT_ON = 3;
__host__ __device__ constexpr uint32_t mk_item(uint32_t type, uint32_t br, uint32_t b, uint32_t h0, uint32_t h1, uint32_t half,
                                               uint32_t part = 0) {
    return type | (br << 2) | (b << 3) | (h0 << 7) | (h1 << 13) | (half << 19) | (part << 22);
}
#define IT_TYPE(e) ((e) & 3u)
#define IT_BR(e) (((e) >> 2) & 1u)
#define IT_B(e) (((e) >> 3) & 15u)
#define IT_H0(e) (((e) >> 7) & 63u)
#define IT_H1(e) (((e) >> 13) & 63u)
#define IT_HALF(e) (((e) >> 19) & 7u)
#define IT_PART(e) (((e) >> 22) & 1u)
#define IT_SLOT(e) IT_H1(e)
#define IT_DEP(e) (((e) >> 23) & 127u)

struct Params {
    CUtensorMap x[2], wq[2], k[2], v[2], wo[2], won[2], out;
    const __nv_bfloat16 *px[2], *pwq[2], *pk[2], *pv[2];
    struct alignas(16) { uint32_t delay, items[NSTAT]; } cl[NCL];
    uint32_t nlist;
    uint8_t slot[64];
    uint32_t list[568];
};

constexpr int OUNIT = 61440;
__device__ __align__(1024) unsigned char g_ostash[(size_t)1024 * OUNIT];
__device__ __align__(256) unsigned int g_flag[32 * 64];
__device__ __forceinline__ unsigned char* ostash(uint32_t slot, uint32_t b) { return g_ostash + (slot * 16 + b) * OUNIT; }
__device__ unsigned int g_epoch[NCTA * 4];
__device__ unsigned int g_ticket[2];

constexpr int SMEM_LAUNCH = SMEM_BYTES;
#define TS(role, idx)
#define TS_ITEM(e)
#define TS_DUMP(role)
#define TSD(role, idx)

__device__ __forceinline__ uint64_t pol_stream() {
    uint64_t p;
    asm volatile("createpolicy.fractional.L2::evict_first.b64 %0, 1.0;" : "=l"(p));
    return p;
}
__device__ __forceinline__ uint64_t pol_shared() {
    uint64_t p;
    asm volatile("createpolicy.fractional.L2::evict_unchanged.b64 %0, 1.0;" : "=l"(p));
    return p;
}
constexpr int NPRE = 2;
constexpr int QHOLD = 8;
constexpr float SM_C = 0.07216878364870322f * 1.4426950408889634f;

__device__ __forceinline__ uint32_t next_epoch(int warp) {
    unsigned int* p = &g_epoch[blockIdx.x * 4 + warp];
    const uint32_t e = __ldcg(p) + 1;
    *p = e;
    return e;
}

__device__ __forceinline__ uint32_t tid_now() {
    uint32_t t;
    asm volatile("mov.u32 %0, %%tid.x;" : "=r"(t));
    return t;
}
__device__ __forceinline__ void mbar_init(uint32_t a, uint32_t c) {
    asm volatile("mbarrier.init.shared::cta.b64 [%0], %1;" ::"r"(a), "r"(c) : "memory");
}
__device__ __forceinline__ void mbar_expect(uint32_t a, uint32_t b) {
    asm volatile("mbarrier.arrive.expect_tx.shared::cta.b64 _, [%0], %1;" ::"r"(a), "r"(b) : "memory");
}
template <int CNT = 1>
__device__ __forceinline__ void mbar_arrive_warp(uint32_t a) {
    if (CNT == 1)
        asm volatile("{\n.reg .pred p;\nelect.sync _|p, 0xffffffff;\n@p mbarrier.arrive.shared::cta.b64 _, [%0];\n}" ::"r"(a) : "memory");
    else
        asm volatile(
            "{\n.reg .pred p;\nelect.sync _|p, 0xffffffff;\n@p mbarrier.arrive.shared::cta.b64 _, [%0];\n"
            "@p mbarrier.arrive.shared::cta.b64 _, [%0];\n}" ::"r"(a)
            : "memory");
}
template <int CNT = 1>
__device__ __forceinline__ void mbar_arrive_warp_if(uint32_t a, bool cond) {
    if (CNT == 1)
        asm volatile(
            "{\n.reg .pred p, c;\nelect.sync _|p, 0xffffffff;\nsetp.ne.and.u32 c, %1, 0, p;\n"
            "@c mbarrier.arrive.shared::cta.b64 _, [%0];\n}" ::"r"(a), "r"((uint32_t)cond)
            : "memory");
    else
        asm volatile(
            "{\n.reg .pred p, c;\nelect.sync _|p, 0xffffffff;\nsetp.ne.and.u32 c, %1, 0, p;\n"
            "@c mbarrier.arrive.shared::cta.b64 _, [%0];\n@c mbarrier.arrive.shared::cta.b64 _, [%0];\n}" ::"r"(a), "r"((uint32_t)cond)
            : "memory");
}
__device__ __forceinline__ uint32_t deadline() {
    uint32_t c;
    asm volatile("mov.u32 %0, %%clock_hi;" : "=r"(c));
    return c + 4;
}
__device__ __forceinline__ void mbar_wait(uint32_t a, uint32_t ph, uint32_t dl) {
    asm volatile(
        "{\n.reg .pred p;\n.reg .u32 m;\n"
        "LOOP:\n"
        "mbarrier.try_wait.parity.shared::cta.b64 p, [%0], %1;\n"
        "@p bra DONE;\n"
        "mov.u32 m, %%clock_hi;\n"
        "setp.ne.u32 p, m, %2;\n"
        "@p bra LOOP;\n"
        "trap;\n"
        "DONE:\n}" ::"r"(a), "r"(ph), "r"(dl)
        : "memory");
}
__device__ __forceinline__ bool mbar_test(uint32_t a, uint32_t ph) {
    uint32_t ok;
    asm volatile("{\n.reg .pred p;\nmbarrier.test_wait.parity.shared::cta.b64 p, [%1], %2;\nselp.u32 %0, 1, 0, p;\n}"
                 : "=r"(ok) : "r"(a), "r"(ph) : "memory");
    return __all_sync(0xffffffffu, ok);
}
__device__ __forceinline__ void mbar_wait2(uint32_t a, uint32_t pa, uint32_t b, uint32_t pb, uint32_t dl) {
    asm volatile(
        "{\n.reg .pred p, q;\n.reg .u32 m;\n"
        "LOOP:\n"
        "mbarrier.try_wait.parity.shared::cta.b64 p, [%0], %1;\n"
        "mbarrier.try_wait.parity.shared::cta.b64 q, [%2], %3;\n"
        "and.pred p, p, q;\n"
        "@p bra DONE;\n"
        "mov.u32 m, %%clock_hi;\n"
        "setp.ne.u32 p, m, %4;\n"
        "@p bra LOOP;\n"
        "trap;\n"
        "DONE:\n}" ::"r"(a), "r"(pa), "r"(b), "r"(pb), "r"(dl)
        : "memory");
}
template <int ID, int CNT>
__device__ __forceinline__ void nb_sync() { asm volatile("bar.sync %0, %1;" ::"n"(ID), "n"(CNT) : "memory"); }
template <int ID, int CNT>
__device__ __forceinline__ void nb_arrive() { asm volatile("bar.arrive %0, %1;" ::"n"(ID), "n"(CNT) : "memory"); }
__device__ __forceinline__ void fence_async_smem() { asm volatile("fence.proxy.async.shared::cta;" ::: "memory"); }

__device__ __forceinline__ void tma3(uint32_t dst, const CUtensorMap* m, int c1, int c2, uint32_t bar, uint64_t pol) {
    asm volatile(
        "cp.async.bulk.tensor.3d.shared::cluster.global.mbarrier::complete_tx::bytes.L2::cache_hint [%0], [%1, {%3,%4,%5}], [%2], %6;" ::"r"(dst),
        "l"(m), "r"(bar), "r"(0), "r"(c1), "r"(c2), "l"(pol)
        : "memory");
}
__device__ __forceinline__ void tma3_mc(uint32_t dst, const CUtensorMap* m, int c1, int c2, uint32_t bar, uint64_t pol) {
    asm volatile(
        "cp.async.bulk.tensor.3d.shared::cluster.global.mbarrier::complete_tx::bytes.multicast::cluster.L2::cache_hint"
        " [%0], [%1, {%3,%4,%5}], [%2], %6, %7;" ::"r"(dst),
        "l"(m), "r"(bar), "r"(0), "r"(c1), "r"(c2), "h"((unsigned short)3), "l"(pol)
        : "memory");
}
__device__ __forceinline__ void bulk_load(uint32_t dst, const void* src, uint32_t bytes, uint32_t bar, uint64_t pol) {
    asm volatile("cp.async.bulk.shared::cluster.global.mbarrier::complete_tx::bytes.L2::cache_hint [%0], [%1], %2, [%3], %4;" ::"r"(dst),
                 "l"(src), "r"(bytes), "r"(bar), "l"(pol)
                 : "memory");
}
__device__ __forceinline__ void wg_fence() { asm volatile("wgmma.fence.sync.aligned;" ::: "memory"); }
__device__ __forceinline__ void wg_commit() { asm volatile("wgmma.commit_group.sync.aligned;" ::: "memory"); }
template <int N>
__device__ __forceinline__ void wg_wait() { asm volatile("wgmma.wait_group.sync.aligned %0;" ::"n"(N) : "memory"); }

#define RW80(c, d) c(d[0]), c(d[1]), c(d[2]), c(d[3]), c(d[4]), c(d[5]), c(d[6]), c(d[7]), c(d[8]), c(d[9]), c(d[10]), c(d[11]), c(d[12]), c(d[13]), c(d[14]), c(d[15]), c(d[16]), c(d[17]), c(d[18]), c(d[19]), c(d[20]), c(d[21]), c(d[22]), c(d[23]), c(d[24]), c(d[25]), c(d[26]), c(d[27]), c(d[28]), c(d[29]), c(d[30]), c(d[31]), c(d[32]), c(d[33]), c(d[34]), c(d[35]), c(d[36]), c(d[37]), c(d[38]), c(d[39]), c(d[40]), c(d[41]), c(d[42]), c(d[43]), c(d[44]), c(d[45]), c(d[46]), c(d[47]), c(d[48]), c(d[49]), c(d[50]), c(d[51]), c(d[52]), c(d[53]), c(d[54]), c(d[55]), c(d[56]), c(d[57]), c(d[58]), c(d[59]), c(d[60]), c(d[61]), c(d[62]), c(d[63]), c(d[64]), c(d[65]), c(d[66]), c(d[67]), c(d[68]), c(d[69]), c(d[70]), c(d[71]), c(d[72]), c(d[73]), c(d[74]), c(d[75]), c(d[76]), c(d[77]), c(d[78]), c(d[79])
#define RW48(c, d) c(d[0]), c(d[1]), c(d[2]), c(d[3]), c(d[4]), c(d[5]), c(d[6]), c(d[7]), c(d[8]), c(d[9]), c(d[10]), c(d[11]), c(d[12]), c(d[13]), c(d[14]), c(d[15]), c(d[16]), c(d[17]), c(d[18]), c(d[19]), c(d[20]), c(d[21]), c(d[22]), c(d[23]), c(d[24]), c(d[25]), c(d[26]), c(d[27]), c(d[28]), c(d[29]), c(d[30]), c(d[31]), c(d[32]), c(d[33]), c(d[34]), c(d[35]), c(d[36]), c(d[37]), c(d[38]), c(d[39]), c(d[40]), c(d[41]), c(d[42]), c(d[43]), c(d[44]), c(d[45]), c(d[46]), c(d[47])
#define RW32(c, d) c(d[0]), c(d[1]), c(d[2]), c(d[3]), c(d[4]), c(d[5]), c(d[6]), c(d[7]), c(d[8]), c(d[9]), c(d[10]), c(d[11]), c(d[12]), c(d[13]), c(d[14]), c(d[15]), c(d[16]), c(d[17]), c(d[18]), c(d[19]), c(d[20]), c(d[21]), c(d[22]), c(d[23]), c(d[24]), c(d[25]), c(d[26]), c(d[27]), c(d[28]), c(d[29]), c(d[30]), c(d[31])

__device__ __forceinline__ void reg_fence(float (&d)[80]) { asm volatile("" : RW80("+f", d)::"memory"); }
__device__ __forceinline__ void reg_fence(float (&d)[48]) { asm volatile("" : RW48("+f", d)::"memory"); }
__device__ __forceinline__ void reg_fence(float (&d)[32]) { asm volatile("" : RW32("+f", d)::"memory"); }

template <int NR>
__device__ __forceinline__ void zero(float (&d)[NR]) {
#pragma unroll
    for (int i = 0; i < NR; i++) d[i] = 0.f;
}

constexpr uint32_t HI_SW128 = (1024u >> 4) | (1u << 30);
constexpr uint32_t HI_KV = (3072u >> 4) | (1u << 30);
constexpr uint32_t HI_OST = (2560u >> 4) | (2u << 30);
constexpr uint32_t LO_LBO1 = (1u << 16);
constexpr uint32_t LO_OST = ((512u >> 4) << 16);

template <int TA, int TB, uint32_t HIB, int ACC, uint32_t HIA = HI_SW128>
__device__ __forceinline__ void wgmma(float (&d)[80], uint32_t loA, uint32_t loB) {
#define WG_ASM(SD)                                                          \
    "{\n.reg .b64 da, db;\nmov.b64 da, {%80, %82};\nmov.b64 db, {%81, %83};\n" \
    "wgmma.mma_async.sync.aligned.m64n160k16.f32.bf16.bf16 "               \
    "{%0,%1,%2,%3,%4,%5,%6,%7,%8,%9,%10,%11,%12,%13,%14,%15,%16,%17,%18,%19,%20,%21,%22,%23,%24,%25,%26,%27,%28,%29,%30,%31,%32,%33,%34,%35,%36,%37,%38,%39,%40,%41,%42,%43,%44,%45,%46,%47,%48,%49,%50,%51,%52,%53,%54,%55,%56,%57,%58,%59,%60,%61,%62,%63,%64,%65,%66,%67,%68,%69,%70,%71,%72,%73,%74,%75,%76,%77,%78,%79}, da, db, " SD ", 1, 1, %84, %85;\n}"
    if constexpr (ACC == 2)
        asm volatile(WG_ASM("0") : RW80("+f", d) : "r"(loA), "r"(loB), "n"(HIA), "n"(HIB), "n"(TA), "n"(TB));
    else if constexpr (ACC == 1)
        asm volatile(WG_ASM("1") : RW80("+f", d) : "r"(loA), "r"(loB), "n"(HIA), "n"(HIB), "n"(TA), "n"(TB));
    else
        asm volatile(WG_ASM("0") : RW80("=f", d) : "r"(loA), "r"(loB), "n"(HIA), "n"(HIB), "n"(TA), "n"(TB));
#undef WG_ASM
}
template <int TA, int TB, uint32_t HIB, int ACC, uint32_t HIA = HI_SW128>
__device__ __forceinline__ void wgmma(float (&d)[48], uint32_t loA, uint32_t loB) {
#define WG_ASM(SD)                                                          \
    "{\n.reg .b64 da, db;\nmov.b64 da, {%48, %50};\nmov.b64 db, {%49, %51};\n" \
    "wgmma.mma_async.sync.aligned.m64n96k16.f32.bf16.bf16 "               \
    "{%0,%1,%2,%3,%4,%5,%6,%7,%8,%9,%10,%11,%12,%13,%14,%15,%16,%17,%18,%19,%20,%21,%22,%23,%24,%25,%26,%27,%28,%29,%30,%31,%32,%33,%34,%35,%36,%37,%38,%39,%40,%41,%42,%43,%44,%45,%46,%47}, da, db, " SD ", 1, 1, %52, %53;\n}"
    if constexpr (ACC == 1)
        asm volatile(WG_ASM("1") : RW48("+f", d) : "r"(loA), "r"(loB), "n"(HIA), "n"(HIB), "n"(TA), "n"(TB));
    else
        asm volatile(WG_ASM("0") : RW48("=f", d) : "r"(loA), "r"(loB), "n"(HIA), "n"(HIB), "n"(TA), "n"(TB));
#undef WG_ASM
}
template <int TA, int TB, uint32_t HIB, int ACC, uint32_t HIA = HI_SW128>
__device__ __forceinline__ void wgmma(float (&d)[32], uint32_t loA, uint32_t loB) {
#define WG_ASM(SD)                                                          \
    "{\n.reg .b64 da, db;\nmov.b64 da, {%32, %34};\nmov.b64 db, {%33, %35};\n" \
    "wgmma.mma_async.sync.aligned.m64n64k16.f32.bf16.bf16 "               \
    "{%0,%1,%2,%3,%4,%5,%6,%7,%8,%9,%10,%11,%12,%13,%14,%15,%16,%17,%18,%19,%20,%21,%22,%23,%24,%25,%26,%27,%28,%29,%30,%31}, da, db, " SD ", 1, 1, %36, %37;\n}"
    if constexpr (ACC == 1)
        asm volatile(WG_ASM("1") : RW32("+f", d) : "r"(loA), "r"(loB), "n"(HIA), "n"(HIB), "n"(TA), "n"(TB));
    else
        asm volatile(WG_ASM("0") : RW32("=f", d) : "r"(loA), "r"(loB), "n"(HIA), "n"(HIB), "n"(TA), "n"(TB));
#undef WG_ASM
}

__device__ __forceinline__ uint32_t pack_bf16(float lo, float hi) {
    uint32_t r;
    asm("cvt.rn.bf16x2.f32 %0, %1, %2;" : "=r"(r) : "f"(hi), "f"(lo));
    return r;
}
__device__ __forceinline__ float ex2(float x) {
    float r;
    asm("ex2.approx.ftz.f32 %0, %1;" : "=f"(r) : "f"(x));
    return r;
}
__device__ __forceinline__ void stsm4t(uint32_t a, uint32_t r0, uint32_t r1, uint32_t r2, uint32_t r3) {
    asm volatile("stmatrix.sync.aligned.m8n8.x4.trans.shared.b16 [%0], {%1,%2,%3,%4};" ::"r"(a), "r"(r0), "r"(r1), "r"(r2), "r"(r3)
                 : "memory");
}
__device__ __forceinline__ uint32_t lds_u(uint32_t a) {
    uint32_t v;
    asm volatile("ld.shared.u32 %0, [%1];" : "=r"(v) : "r"(a) : "memory");
    return v;
}
__device__ __forceinline__ uint4 lds_u4(uint32_t a) {
    uint4 v;
    asm volatile("ld.shared.v4.u32 {%0,%1,%2,%3}, [%4];" : "=r"(v.x), "=r"(v.y), "=r"(v.z), "=r"(v.w) : "r"(a) : "memory");
    return v;
}
__device__ __forceinline__ float2 lds_f2(uint32_t a) {
    float2 v;
    asm volatile("ld.shared.v2.f32 {%0,%1}, [%2];" : "=f"(v.x), "=f"(v.y) : "r"(a) : "memory");
    return v;
}
__device__ __forceinline__ void sts_f(uint32_t a, float v) { asm volatile("st.shared.f32 [%0], %1;" ::"r"(a), "f"(v) : "memory"); }
__device__ __forceinline__ void sts_u(uint32_t a, uint32_t v) { asm volatile("st.shared.u32 [%0], %1;" ::"r"(a), "r"(v) : "memory"); }
__device__ __forceinline__ void sts_f2(uint32_t a, float x, float y) {
    asm volatile("st.shared.v2.f32 [%0], {%1,%2};" ::"r"(a), "f"(x), "f"(y) : "memory");
}

template <bool SIG = false, int NR>
__device__ __forceinline__ void store_tile_t(const float (&d)[NR], uint32_t addr) {
#pragma unroll
    for (int j = 0; j < NR / 8; j++) {
        stsm4t(addr + j * 2048, pack_bf16(d[8 * j], d[8 * j + 1]), pack_bf16(d[8 * j + 2], d[8 * j + 3]),
               pack_bf16(d[8 * j + 4], d[8 * j + 5]), pack_bf16(d[8 * j + 6], d[8 * j + 7]));
        if (SIG && j == 0) nb_arrive<NB_L, 160>();
    }
}

struct TrueT { static constexpr bool value = true; };
struct FalseT { static constexpr bool value = false; };

template <int V>
struct IntT { static constexpr int value = V; };

__device__ __forceinline__ uint32_t get_item(uint32_t sb, int it, uint32_t dl) {
    mbar_wait(sb + BAR_ITEM + it * 8, 0, dl);
    return lds_u(sb + OFF_ITEM + it * 4);
}
__device__ __forceinline__ uint32_t get_item_warp(uint32_t sb, int it, uint32_t dl) {
    return __shfl_sync(0xffffffffu, get_item(sb, it, dl), 0);
}

struct Ring {
    uint32_t slot, ph, dl;
    __device__ __forceinline__ void adv(uint32_t k) {
        slot += k;
        if (slot >= NSLOT) { slot -= NSLOT; ph ^= 1; }
    }
};

template <int K>
__device__ __forceinline__ void qk_step(float (&s)[80], uint32_t loK, uint32_t loQ) {
    wgmma<0, 0, HI_SW128, K != 0, HI_KV>(s, loK + (K >> 2) * 64 + (K & 3) * 2, loQ + (K >> 2) * (XS >> 4) + (K & 3) * 2);
}
template <int K0, int K1>
__device__ __forceinline__ void qk_steps(float (&s)[80], uint32_t loK, uint32_t loQ) {
    if constexpr (K0 < K1) {
        qk_step<K0>(s, loK, loQ);
        qk_steps<K0 + 1, K1>(s, loK, loQ);
    }
}
__device__ __forceinline__ uint32_t add_bf2(uint32_t a, uint32_t b) {
    uint32_t r;
    asm("add.rn.bf16x2 %0, %1, %2;" : "=r"(r) : "r"(a), "r"(b));
    return r;
}
__device__ __forceinline__ uint32_t fma_bf2(uint32_t a, uint32_t b, uint32_t c) {
    uint32_t r;
    asm("fma.rn.bf16x2 %0, %1, %2, %3;" : "=r"(r) : "r"(a), "r"(b), "r"(c));
    return r;
}
template <int J>
__device__ __forceinline__ void exp_block(const float (&s)[80], uint32_t (&k)[40], uint32_t pa, float mref) {
    if constexpr (J < 10) {
#pragma unroll
        for (int i = 4 * J; i < 4 * J + 4; i++)
            k[i] = pack_bf16(ex2(fmaf(s[2 * i], SM_C, -mref)), ex2(fmaf(s[2 * i + 1], SM_C, -mref)));
#pragma unroll
        for (int i = 0; i < 4; i++)
            asm volatile("stmatrix.sync.aligned.m8n8.x1.trans.shared.b16 [%0], {%1};" ::"r"(((i & 1) ? pa ^ 16 : pa) + J * 2048 + (i >> 1) * 1024),
                         "r"(k[4 * J + i])
                         : "memory");
        exp_block<J + 1>(s, k, pa, mref);
    }
}
__device__ __forceinline__ void sum_block(const uint32_t (&k)[40], float (&l)[10], uint32_t lane) {
    const bool b4 = lane & 16, b3 = lane & 8;
    uint32_t ps[20], t[10];
#pragma unroll
    for (int j = 0; j < 20; j++) ps[j] = add_bf2(k[2 * j], k[2 * j + 1]);
#pragma unroll
    for (int j = 0; j < 10; j++)
        t[j] = add_bf2(b4 ? ps[2 * j + 1] : ps[2 * j], __shfl_xor_sync(0xffffffffu, b4 ? ps[2 * j] : ps[2 * j + 1], 16));
#pragma unroll
    for (int i = 0; i < 5; i++) {
        const uint32_t a = b3 ? t[i + 5] : t[i], b = __shfl_xor_sync(0xffffffffu, b3 ? t[i] : t[i + 5], 8);
        l[2 * i] += __uint_as_float(a << 16) + __uint_as_float(b << 16);
        l[2 * i + 1] += __uint_as_float(a & 0xffff0000u) + __uint_as_float(b & 0xffff0000u);
    }
}
template <bool ADD>
__device__ __forceinline__ void sum_store(const float (&l)[10], uint32_t lane, uint32_t lxa) {
    const bool b2 = lane & 4;
    float t[5];
#pragma unroll
    for (int i = 0; i < 5; i++) t[i] = ADD ? __uint_as_float(lds_u(lxa + i * 64)) : 0.f;
#pragma unroll
    for (int i = 0; i < 5; i++)
        sts_f(lxa + i * 64, t[i] + (b2 ? l[2 * i + 1] : l[2 * i]) + __shfl_xor_sync(0xffffffffu, b2 ? l[2 * i] : l[2 * i + 1], 4));
}

__device__ __forceinline__ void fallback_unit(const Params& P, uint32_t e, uint32_t tid) {
    const uint32_t lane = tid & 31, br = IT_BR(e), b = IT_B(e), h = IT_H0(e);
    const __nv_bfloat162* wq = (const __nv_bfloat162*)(P.pwq[br] + h * 192) + lane;
    const __nv_bfloat162* kp = (const __nv_bfloat162*)(P.pk[br] + (size_t)(b * 32 + h) * 512 * 192) + lane;
    const __nv_bfloat162* vp = (const __nv_bfloat162*)(P.pv[br] + (size_t)(b * 32 + h) * 512 * 192) + lane;
#pragma unroll 1
    for (uint32_t qi = 0; qi < 40; qi++) {
        const uint32_t q = 4 * qi + (tid >> 5);
        const __nv_bfloat16* xr = P.px[br] + (size_t)(b * 160 + q) * 640;
        float a[6] = {0.f, 0.f, 0.f, 0.f, 0.f, 0.f};
#pragma unroll 2
        for (int k = 0; k < 640; k++) {
            const float xv = __bfloat162float(xr[k]);
#pragma unroll
            for (int i = 0; i < 3; i++) {
                const float2 wv = __bfloat1622float2(wq[(size_t)k * 3072 + i * 32]);
                a[2 * i] = fmaf(xv, wv.x, a[2 * i]);
                a[2 * i + 1] = fmaf(xv, wv.y, a[2 * i + 1]);
            }
        }
#pragma unroll
        for (int i = 0; i < 6; i++) a[i] = __bfloat162float(__float2bfloat16(a[i]));
        auto score = [&](int key) {
            float d = 0.f;
#pragma unroll
            for (int i = 0; i < 3; i++) {
                const float2 kv = __bfloat1622float2(kp[key * 96 + i * 32]);
                d = fmaf(a[2 * i], kv.x, fmaf(a[2 * i + 1], kv.y, d));
            }
#pragma unroll
            for (int o = 16; o > 0; o >>= 1) d += __shfl_xor_sync(0xffffffffu, d, o);
            return d;
        };
        float m = -INFINITY, o[6] = {0.f, 0.f, 0.f, 0.f, 0.f, 0.f}, sum = 0.f;
#pragma unroll 1
        for (int n = 0; n < 1024; n++) {
            const int key = n & 511;
            const float d = score(key);
            if (n < 512) {
                m = fmaxf(m, d);
            } else {
                const float p = ex2((d - m) * SM_C);
                sum += p;
#pragma unroll
                for (int i = 0; i < 3; i++) {
                    const float2 vv = __bfloat1622float2(vp[key * 96 + i * 32]);
                    o[2 * i] = fmaf(p, vv.x, o[2 * i]);
                    o[2 * i + 1] = fmaf(p, vv.y, o[2 * i + 1]);
                }
            }
        }
        const float inv = __fdividef(1.f, sum);
        __nv_bfloat16* op = (__nv_bfloat16*)ostash(IT_SLOT(e), b) + (q >> 5) * 256 + 2 * ((q & 31) >> 3) + (q & 1);
#pragma unroll
        for (int i = 0; i < 6; i++) {
            const uint32_t d = (i >> 1) * 64 + 2 * lane + (i & 1);
            op[(d >> 3) * 1280 + (d & 7) * 32 + ((((q & 7) >> 1) ^ ((d & 7) >> 1)) << 3)] = __float2bfloat16(o[i] * inv);
        }
    }
}

struct PendO {
    uint32_t v[64];
    unsigned char* gp;
    static __device__ __forceinline__ uint32_t toff() {
        const uint32_t t = tid_now();
        return ((t >> 5) & 3) * 5120 + ((t >> 2) & 7) * 64 + (((t ^ (t >> 3)) & 3) << 4);
    }
    uint32_t pend, sig, bad;
    static __device__ __forceinline__ void scale(uint32_t& x, uint32_t hi, uint32_t lo) {
        asm("{\n.reg .b32 t;\nmul.rn.bf16x2 t, %0, %2;\nfma.rn.bf16x2 %0, %0, %1, t;\n}" : "+r"(x) : "r"(hi), "r"(lo));
    }
    template <int I, int OFF>
    __device__ __forceinline__ void put() {
        asm volatile("{\n.reg .pred p;\nsetp.ne.u32 p, %6, 0;\n@p st.global.v4.b32 [%0+%5], {%1,%2,%3,%4};\n}" ::"l"(gp), "r"(v[I]),
                     "r"(v[I + 1]), "r"(v[I + 2]), "r"(v[I + 3]), "n"(OFF), "r"(pend)
                     : "memory");
    }
    __device__ __forceinline__ void verdict(uint32_t sb, uint32_t W) {
        if (sig) {
            asm volatile("bar.sync %0, 160;" ::"r"(NB_VOTE + W) : "memory");
            bad = __any_sync(0xffffffffu, lds_u(sb + OFF_FB) != 0);
            pend = !bad;
        }
    }
    template <int W, int G, int H>
    __device__ __forceinline__ void half(uint32_t sb) {
        constexpr bool T2 = W == 0 ? G >= 3 : G < 3;
        constexpr int B = T2 ? 40 + 8 * (W == 0 ? G - 3 : G) : 0;
        const uint4 a = lds_u4(sb + OFF_LINV + G * 128 + H * 16 + (threadIdx.x & 3) * 32);
#pragma unroll
        for (int i = 2 * H; i < 8; i += 4) {
            scale(v[8 * G + i], a.x, a.y);
            scale(v[8 * G + i + 1], a.z, a.w);
            if (T2) {
                scale(v[B + i], a.x, a.y);
                scale(v[B + i + 1], a.z, a.w);
            }
        }
        if (H == 1) {
            put<8 * G, W * XS + G * 512>();
            put<8 * G + 4, W * XS + G * 512 + 2560>();
            if (T2) {
                put<B, 2 * XS + G * 512>();
                put<B + 4, 2 * XS + G * 512 + 2560>();
            }
            if (G == 4 && pend) nb_arrive<NB_ODONE, 288>();
        }
    }
    template <int W, int G>
    __device__ __forceinline__ void step(uint32_t sb) {
        half<W, G, 0>(sb);
        half<W, G, 1>(sb);
    }
    template <int W>
    __device__ __forceinline__ void flush(uint32_t sb) {
        step<W, 0>(sb);
        step<W, 1>(sb);
        step<W, 2>(sb);
        step<W, 3>(sb);
        step<W, 4>(sb);
    }
    __device__ __forceinline__ void clear() {
#pragma unroll
        for (int i = 0; i < 64; i++) v[i] = 0;
        gp = nullptr;
        pend = 0;
        sig = 0;
        bad = 0;
    }
};

__device__ __forceinline__ uint32_t stsm_off() {
    const uint32_t tid = tid_now(), lane = tid & 31;
    return (lane >> 4) * 1024 + (lane & 7) * 128 + (((((tid >> 4) & 6) + ((lane >> 3) & 1)) ^ (lane & 7)) << 4);
}
__device__ __forceinline__ void q_ahead(float (&q0)[80], uint32_t sb, const Ring& rn, uint32_t phm, bool valid) {
    if (valid) mbar_wait2(sb + BAR_RFULL + rn.slot * 8, rn.ph, sb + BAR_XFULL, phm & 1, rn.dl);
    const uint32_t a = ((((sb + OFF_RING) & 0x3ffff) >> 4) | LO_LBO1) + rn.slot * (SLOT >> 4);
    const uint32_t b = (((sb + OFF_R) & 0x3ffff) >> 4) | LO_LBO1;
    wg_fence();
    wgmma<1, 0, HI_SW128, false>(q0, a, b);
#pragma unroll
    for (int k = 1; k < 4; k++) wgmma<1, 0, HI_SW128, true>(q0, a + (k >> 1) * 768 + (k & 1) * 128, b + k * 2);
    wg_commit();
}
template <int W, int KK>
__device__ __forceinline__ void qproj(float (&q0)[80], float (&q1)[80], uint32_t sb, Ring& r, uint32_t pslot, uint32_t phm,
                                      PendO& po) {
    const uint32_t loR = (((sb + OFF_R) & 0x3ffff) >> 4) | LO_LBO1;
    const uint32_t loRing = (((sb + OFF_RING) & 0x3ffff) >> 4) | LO_LBO1;
    auto ready = [&](int k) {
        mbar_wait2(sb + BAR_RFULL + r.slot * 8, r.ph, sb + BAR_XFULL + (k % 5) * 8, ((phm >> (k % 5)) ^ (k / 5)) & 1, r.dl);
    };
    auto release = [&]() {
        if (KK > 0) {
            wg_wait<1>();
            mbar_arrive_warp(sb + BAR_REMPTY + pslot * 8);
            if (KK <= 5) mbar_arrive_warp(sb + (BAR_XEMPTY + (KK - 1) * 8));
        }
    };
    if (KK == 0 && W == 1) ready(0);
    if (W == 1 && KK == QHOLD) nb_sync<NB_SDONE, 256>();
    const uint32_t a = loRing + r.slot * (SLOT >> 4) + (W == 0 ? 0 : 512), b = loR + (KK % 5) * (XS >> 4);
    wg_fence();
    constexpr bool T0 = W == 1 || KK > 0;
    if (T0) wgmma<1, 0, HI_SW128, KK != 0>(q0, a, b);
    if (W == 0) wgmma<1, 0, HI_SW128, KK != 0 ? 1 : 2>(q1, a + 256, b);
#pragma unroll
    for (int k = 1; k < 4; k++) {
        if (T0) wgmma<1, 0, HI_SW128, true>(q0, a + (k >> 1) * 768 + (k & 1) * 128, b + k * 2);
        if (W == 0) wgmma<1, 0, HI_SW128, true>(q1, a + 256 + (k >> 1) * 768 + (k & 1) * 128, b + k * 2);
    }
    wg_commit();
    const uint32_t cslot = r.slot;
    r.adv(1);
    if (W == 0 || KK < QHOLD) release();
    constexpr int QST = W == 0 ? 2 : 1;
    if (KK == QST) {
        po.verdict(sb, W);
        po.template half<W, 0, 0>(sb);
    }
    if (KK < 9) ready(KK + 1);
    if (W == 1 && KK >= QHOLD) release();
    if (W == 1 && KK == 7) nb_arrive<NB_PDONE, 256>();
    if (KK == QST) po.template half<W, 0, 1>(sb);
    if constexpr (KK > QST && KK < QST + 5) po.template step<W, KK - QST>(sb);
    if constexpr (KK < (W == 0 ? 7 : 9)) {
        qproj<W, KK + 1>(q0, q1, sb, r, cslot, phm, po);
    } else if constexpr (W == 1) {
        const uint32_t sta = sb + OFF_R + 2 * XS + stsm_off();
        wg_wait<0>();
        reg_fence(q0);
        store_tile_t<true>(q0, sta);
        mbar_arrive_warp(sb + BAR_REMPTY + cslot * 8);
    } else {
        const uint32_t s8 = r.slot, a8 = loRing + s8 * (SLOT >> 4);
        wg_fence();
#pragma unroll
        for (int k = 0; k < 4; k++) wgmma<1, 0, HI_SW128, true>(q0, a8 + (k >> 1) * 768 + (k & 1) * 128, loR + 3 * (XS >> 4) + k * 2);
        r.adv(1);
        ready(9);
        const uint32_t s9 = r.slot, a9 = loRing + s9 * (SLOT >> 4);
        r.adv(1);
        wg_fence();
#pragma unroll
        for (int k = 0; k < 4; k++) wgmma<1, 0, HI_SW128, true>(q0, a9 + (k >> 1) * 768 + (k & 1) * 128, loR + 4 * (XS >> 4) + k * 2);
        wg_commit();
        wg_wait<1>();
        mbar_arrive_warp(sb + BAR_REMPTY + cslot * 8);
        wg_fence();
#pragma unroll
        for (int k = 0; k < 8; k++)
            wgmma<1, 0, HI_SW128, true>(q1, (k < 4 ? a8 : a9) + 256 + ((k >> 1) & 1) * 768 + (k & 1) * 128,
                                        loR + (3 + (k >> 2)) * (XS >> 4) + (k & 3) * 2);
        wg_commit();
        nb_arrive<NB_SDONE, 256>();
        sts_u(sb + OFF_GM + 4, r.slot);
        nb_sync<NB_PDONE, 256>();
        wg_wait<1>();
        reg_fence(q0);
        const uint32_t sta = sb + OFF_R + stsm_off();
        store_tile_t(q0, sta);
        wg_wait<0>();
        reg_fence(q1);
        mbar_arrive_warp(sb + BAR_REMPTY + s8 * 8);
        mbar_arrive_warp(sb + BAR_REMPTY + s9 * 8);
        store_tile_t(q1, sta + XS);
        mbar_wait(sb + BAR_RFULL + r.slot * 8, r.ph, r.dl);
    }
}

template <int NR>
__device__ __forceinline__ void opack(const float (&o)[NR], uint32_t* v) {
#pragma unroll
    for (int g = 0; g < NR / 16; g++)
#pragma unroll
        for (int hh = 0; hh < 2; hh++)
#pragma unroll
            for (int t = 0; t < 4; t++) v[8 * g + 4 * hh + t] = pack_bf16(o[16 * g + 4 * t + 2 * hh], o[16 * g + 4 * t + 2 * hh + 1]);
}

__device__ __forceinline__ void out_store(const Params& P, uint32_t src, int col, int b) {
    asm volatile("cp.async.bulk.tensor.5d.global.shared::cta.bulk_group [%0, {%2,%4,%4,%4,%3}], [%1];" ::"l"(&P.out), "r"(src),
                 "r"(col), "r"(b * 5), "r"(0)
                 : "memory");
    asm volatile("cp.async.bulk.commit_group;" ::: "memory");
}

template <bool IS_S>
__device__ __forceinline__ void op_item(uint32_t e, uint32_t sb, Ring& r, uint32_t& phm) {
    constexpr int T0 = IS_S ? 0 : 2;
    constexpr uint32_t BOFF = IS_S ? (3 * 512) >> 4 : 0;
    const uint32_t loRing = (((sb + OFF_RING) & 0x3ffff) >> 4) | LO_LBO1;
    const uint32_t loO = (((sb + OFF_R) & 0x3ffff) >> 4) | LO_OST;
    float c0[80], c1[80], c2[IS_S ? 32 : 48];
    const int T = 3 * (IT_H1(e) - IT_H0(e));
    uint32_t xs = 0;
    auto step = [&](auto first, auto half) {
        constexpr bool F = decltype(first)::value;
        constexpr uint32_t hf = decltype(half)::value;
        if (hf == 0) {
            mbar_wait(sb + BAR_XFULL + xs * 8, (phm >> xs) & 1, r.dl);
            phm ^= 1u << xs;
        }
        mbar_wait(sb + BAR_RFULL + r.slot * 8, r.ph, r.dl);
        const uint32_t a = loRing + r.slot * (SLOT >> 4), b = loO + xs * (XS >> 4) + hf * 640;
        wg_fence();
        wgmma<1, 1, HI_OST, !F>(c0, a + T0 * 128, b);
        wgmma<1, 1, HI_OST, !F>(c1, a + T0 * 128 + 128, b);
        wgmma<1, 1, HI_OST, !F>(c2, a + 512, b + BOFF);
        wgmma<1, 1, HI_OST, true>(c0, a + 640 + T0 * 128, b + 320);
        wgmma<1, 1, HI_OST, true>(c1, a + 640 + T0 * 128 + 128, b + 320);
        wgmma<1, 1, HI_OST, true>(c2, a + 640 + 512, b + 320 + BOFF);
        wg_commit();
    };
    step(TrueT{}, IntT<0>{});
#pragma unroll 1
    for (int t = 1;; t++) {
        uint32_t pslot = r.slot;
        r.adv(1);
        step(FalseT{}, IntT<1>{});
        wg_wait<1>();
        mbar_arrive_warp(sb + BAR_REMPTY + pslot * 8);
        if (t == T) break;
        pslot = r.slot;
        const uint32_t pxs = xs;
        r.adv(1);
        if (++xs == 5) xs = 0;
        step(FalseT{}, IntT<0>{});
        wg_wait<1>();
        mbar_arrive_warp(sb + BAR_REMPTY + pslot * 8);
        mbar_arrive_warp_if(sb + BAR_XEMPTY + pxs * 8, t + 4 < T);
    }
    wg_wait<0>();
    reg_fence(c0);
    reg_fence(c1);
    reg_fence(c2);
    mbar_arrive_warp(sb + BAR_REMPTY + r.slot * 8);
    r.adv(1);
    nb_sync<NB_OPEND, 256>();
    const uint32_t sta = sb + OFF_R + stsm_off();
    store_tile_t(c0, sta + T0 * XS);
    store_tile_t(c1, sta + (T0 + 1) * XS);
    store_tile_t(c2, sta + 4 * XS + (IS_S ? 96 * 128 : 0));
    fence_async_smem();
    nb_arrive<NB_ODONE, 288>();
}

__device__ __forceinline__ void on_item(const Params& P, uint32_t W, uint32_t e, uint32_t sb, Ring& r, uint32_t phm) {
    const uint32_t loRing = (((sb + OFF_RING) & 0x3ffff) >> 4) | LO_LBO1;
    const uint32_t loO = (((sb + OFF_R) & 0x3ffff) >> 4) | LO_OST;
    float c[80];
    const int T = 3 * (IT_H1(e) - IT_H0(e));
    uint32_t xs = 0;
    auto step = [&](auto first) {
        constexpr bool F = decltype(first)::value;
        mbar_wait2(sb + BAR_XFULL + xs * 8, (phm >> xs) & 1, sb + BAR_RFULL + r.slot * 8, r.ph, r.dl);
        const uint32_t a = loRing + r.slot * (SLOT >> 4) + W * 256, b = loO + xs * (XS >> 4);
        wg_fence();
        wgmma<1, 1, HI_OST, !F>(c, a, b);
#pragma unroll
        for (int k = 1; k < 4; k++) wgmma<1, 1, HI_OST, true>(c, a + (k >> 1) * 512 + (k & 1) * 128, b + k * 320);
        wg_commit();
    };
    step(TrueT{});
#pragma unroll 1
    for (int t = 1; t < T; t++) {
        const uint32_t pslot = r.slot, pxs = xs;
        r.adv(1);
        if (++xs == 5) xs = 0, phm = ~phm;
        if (W == 1 && t == T - 2) nb_sync<NB_OPEND, 256>();
        step(FalseT{});
        if (W == 0 && t == T - 1) nb_arrive<NB_OPEND, 256>();
        wg_wait<1>();
        mbar_arrive_warp(sb + BAR_REMPTY + pslot * 8);
        mbar_arrive_warp_if(sb + BAR_XEMPTY + pxs * 8, t + 2 < T);
    }
    xs += 1 + W;
    if (xs >= 5) xs -= 5, phm = ~phm;
    mbar_wait(sb + BAR_XFULL + xs * 8, (phm >> xs) & 1, r.dl);
    const uint32_t sta = sb + OFF_R + xs * XS + stsm_off();
    uint32_t p[40];
#pragma unroll
    for (int j = 0; j < 10; j++)
        asm volatile("ldmatrix.sync.aligned.m8n8.x4.trans.shared.b16 {%0,%1,%2,%3}, [%4];"
                     : "=r"(p[4 * j]), "=r"(p[4 * j + 1]), "=r"(p[4 * j + 2]), "=r"(p[4 * j + 3])
                     : "r"(sta + j * 2048)
                     : "memory");
    wg_wait<0>();
    reg_fence(c);
#pragma unroll
    for (int k = 0; k < 40; k++) {
        c[2 * k] += __uint_as_float(p[k] << 16);
        c[2 * k + 1] += __uint_as_float(p[k] & 0xffff0000u);
    }
    store_tile_t(c, sta);
    fence_async_smem();
    asm volatile("bar.sync %0, 128;" ::"r"(NB_W + W) : "memory");
    if ((tid_now() & 127) == 0) {
        out_store(P, sb + OFF_R + xs * XS, IT_BR(e) * 640 + (2 * IT_HALF(e) + W) * 64, IT_B(e));
        asm volatile("cp.async.bulk.wait_group 0;" ::: "memory");
    }
    __syncwarp();
}

template <int W>
__device__ __forceinline__ uint32_t qa_item(uint32_t e, uint32_t sb, Ring& r, uint32_t phm, PendO& po, float (&q0)[80],
                                            float (&oa)[80], int it) {
    const uint32_t loR = (((sb + OFF_R) & 0x3ffff) >> 4) | LO_LBO1;
    const uint32_t loRing = (((sb + OFF_RING) & 0x3ffff) >> 4) | LO_LBO1;
    qproj<W, 0>(q0, oa, sb, r, 0, phm, po);
    fence_async_smem();
    TSD(W, 1);
    float s[80], ob[W == 0 ? 32 : 48], l[10];
    if (W == 1) {
        nb_arrive<NB_Q2, 256>();
        zero(oa);
        zero(ob);
        reg_fence(oa);
        reg_fence(ob);
    }
    const uint32_t lane = tid_now() & 31, sta = sb + OFF_R + stsm_off();
    auto pv = [&](auto first, uint32_t buf) {
        constexpr bool F = decltype(first)::value;
        if (F) mbar_wait(sb + BAR_RFULL + r.slot * 8, r.ph, r.dl);
        const uint32_t a = loRing + r.slot * (SLOT >> 4), b = loR + (3 + buf) * (XS >> 4);
        wg_fence();
        wgmma<1, 0, HI_SW128, F ? 2 : 1, HI_KV>(oa, a + W * 64, b);
        wgmma<1, 0, HI_SW128, !F, HI_KV>(ob, a + 128, b + (W == 0 ? (96 * 128) >> 4 : 0));
#pragma unroll
        for (int k = 1; k < 4; k++) {
            wgmma<1, 0, HI_SW128, true, HI_KV>(oa, a + W * 64 + k * 384, b + k * 2);
            wgmma<1, 0, HI_SW128, true, HI_KV>(ob, a + 128 + k * 384, b + (W == 0 ? (96 * 128) >> 4 : 0) + k * 2);
        }
        wg_commit();
    };
    zero(l);
    float mref;
    uint32_t kslot, vslot, nx = 0;
    auto tail = [&](auto first, int i) {
        constexpr bool rel_other = !decltype(first)::value;
        uint32_t ps[40];
        exp_block<0>(s, ps, sta + (3 + W) * XS, mref);
        if (rel_other) {
            wg_wait<0>();
            mbar_arrive_warp(sb + BAR_REMPTY + vslot * 8);
            if (W == 1) mbar_arrive_warp_if(sb + BAR_XEMPTY + 24, i == 3);
        }
        fence_async_smem();
        nb_arrive<NB_PFULL + W, 256>();
        TSD(W, 6 + 5 * i);
        if (W == 1) {
            mbar_arrive_warp_if<2>(sb + BAR_XEMPTY + 8, i == 3);
            mbar_arrive_warp_if<2>(sb + BAR_XEMPTY + 16, i == 3);
        }
        if (rel_other) {
            mbar_wait(sb + BAR_RFULL + r.slot * 8, r.ph, r.dl);
            sum_block(ps, l, lane);
        }
        if (W == 0 && i == 3) nx = get_item_warp(sb, it + 1, r.dl);
        TSD(W, 7 + 5 * i);
        nb_sync<NB_W + W, 128>();
        pv(first, W);
        if (!rel_other) sum_block(ps, l, lane);
        TSD(W, 8 + 5 * i);
    };
    if (W == 0) {
        nb_sync<NB_QK, 160>();
        TSD(W, 2);
        wg_fence();
        qk_steps<0, 8>(s, loRing + r.slot * (SLOT >> 4), loR);
        nb_sync<NB_Q2, 256>();
        qk_steps<8, 12>(s, loRing + r.slot * (SLOT >> 4), loR);
        wg_commit();
        nb_arrive<NB_Q01, 256>();
        TSD(W, 4);
        nb_sync<NB_REF, 160>();
        mref = __uint_as_float(lds_u(sb + OFF_GM));
        wg_wait<0>();
        reg_fence(s);
        mbar_arrive_warp<2>(sb + BAR_REMPTY + r.slot * 8);
        r.adv(2);
        TSD(W, 5);
        tail(TrueT{}, 0);
    } else {
        nb_sync<NB_Q01, 256>();
    }
#pragma unroll 1
    for (int i = (W == 0 ? 1 : 0); i < 4; i++) {
        const uint32_t pvslot = r.slot;
        r.adv(1);
        kslot = r.slot;
        mbar_wait(sb + BAR_RFULL + r.slot * 8, r.ph, r.dl);
        wg_fence();
        qk_steps<0, 4>(s, loRing + r.slot * (SLOT >> 4), loR);
        if (W == 1) wg_commit();
        qk_steps<4, 12>(s, loRing + r.slot * (SLOT >> 4), loR);
        wg_commit();
        wg_wait<1>();
        if (W == 1) mbar_arrive_warp_if(sb + BAR_XEMPTY + 0, i == 3);
        mbar_arrive_warp_if(sb + BAR_REMPTY + pvslot * 8, W == 0 || i > 0);
        r.adv(1);
        vslot = r.slot;
        TSD(W, 4 + 5 * i);
        mbar_wait(sb + BAR_RFULL + r.slot * 8, r.ph, r.dl);
        nb_sync<NB_PFULL + (W ^ 1), 256>();
        pv(FalseT{}, W ^ 1);
        if (W == 1) mref = __uint_as_float(lds_u(sb + OFF_GM));
        wg_wait<1>();
        reg_fence(s);
        mbar_arrive_warp<2>(sb + BAR_REMPTY + kslot * 8);
        if (W == 0) mbar_arrive_warp_if(sb + BAR_XEMPTY + 0, i == 3);
        r.adv(W == 1 && i == 3 ? 1 : 2);
        TSD(W, 5 + 5 * i);
        tail(FalseT{}, i);
    }
    if (W == 1) nx = get_item_warp(sb, it + 1, r.dl);
    if (W == 0) {
        Ring rn = r;
        rn.adv(2);
        q_ahead(q0, sb, rn, phm, IT_TYPE(nx) == IT_QA);
        TSD(W, 25);
    }
    const uint32_t w = (tid_now() >> 5) & 3;
    const uint32_t lxa = sb + OFF_LX + w * 640 + (((lane & 8) ? 80 : 0) + ((lane >> 1) & 8) + 2 * (lane & 3) + ((lane >> 2) & 1)) * 4;
    po.gp = ostash(IT_SLOT(e), IT_B(e)) + po.toff();
    po.sig = 1;
    if (W == 0) {
        sum_store<false>(l, lane, lxa);
        nb_arrive<NB_LX, 256>();
        wg_wait<1>();
        mbar_arrive_warp(sb + BAR_REMPTY + r.slot * 8);
        mbar_arrive_warp(sb + BAR_XEMPTY + 24);
        r.adv(1);
        mbar_wait(sb + BAR_RFULL + r.slot * 8, r.ph, r.dl);
        nb_sync<NB_PFULL + 1, 256>();
        pv(FalseT{}, 1);
    } else {
        nb_sync<NB_LX, 256>();
        sum_store<true>(l, lane, lxa);
        nb_arrive<NB_L, 160>();
    }
    TSD(W, 24);
    wg_wait<0>();
    reg_fence(oa);
    reg_fence(ob);
    mbar_arrive_warp(sb + BAR_REMPTY + r.slot * 8);
    mbar_arrive_warp(sb + BAR_XEMPTY + 32);
    r.adv(1);
    opack(ob, po.v + 40);
    opack(oa, po.v);
    return nx;
}

template <int W>
__device__ __forceinline__ uint32_t qa_run(uint32_t e, uint32_t sb, Ring& r, uint32_t phm, PendO& po, int& it) {
    float q0[80], oa[80];
    if (W == 0) {
        zero(oa);
        q_ahead(q0, sb, r, phm, true);
        wg_wait<0>();
    }
#pragma unroll 1
    do {
        TS(W, 0);
        if (W == 0) TS_ITEM(e);
        e = qa_item<W>(e, sb, r, phm, po, q0, oa, it);
        TS(W, 31);
        it++;
    } while (IT_TYPE(e) == IT_QA && !po.bad);
    if (W == 0) {
#pragma unroll
        for (int i = 56; i < 64; i++) po.v[i] = 0;
    }
    return e;
}

__device__ __forceinline__ void consumer(const Params& P, uint32_t W, uint32_t sb, uint32_t dl) {
    int it = 0;
    Ring r{0, 0, dl};
    uint32_t phm = 0;
    uint32_t e = get_item_warp(sb, 0, dl);
#pragma unroll 1
    while (true) {
        if (IT_TYPE(e) == IT_QA) {
            PendO po;
            po.clear();
            e = W == 0 ? qa_run<0>(e, sb, r, phm, po, it) : qa_run<1>(e, sb, r, phm, po, it);
#pragma unroll 1
            for (int m = po.bad ? 2 : 1; m > 0; m--) {
                if (m == 1) {
                    po.verdict(sb, W);
                    if (W == 0) po.flush<0>(sb);
                    else po.flush<1>(sb);
                }
                if (po.bad) {
                    if (W == 0) fallback_unit(P, lds_u(sb + OFF_ITEM + (it - m) * 4), tid_now() & 127);
                    __syncwarp();
                    nb_sync<NB_ODONE, 288>();
                }
            }
        }
        if (e == 0) break;
        if (IT_TYPE(e) == IT_QA) continue;
        TS(W, 0);
        if (W == 0) TS_ITEM(e);
        if (IT_TYPE(e) == IT_ON) {
            on_item(P, W, e, sb, r, phm);
            TS(W, 31);
            break;
        }
        if (W == 0) op_item<true>(e, sb, r, phm);
        else op_item<false>(e, sb, r, phm);
        TS(W, 31);
        e = get_item_warp(sb, ++it, dl);
    }
    TS_DUMP(W);
}

__global__ void __cluster_dims__(2, 1, 1) __launch_bounds__(384, 1) fused_kernel(const __grid_constant__ Params P) {
    extern __shared__ __align__(1024) unsigned char smem_raw[];
    const uint32_t sb = (uint32_t)__cvta_generic_to_shared(smem_raw);
    const uint32_t warp = __shfl_sync(0xffffffffu, threadIdx.x >> 5, 0), wgid = warp >> 2;
    const uint32_t cta = blockIdx.x;
    const uint32_t dl = deadline();

    if (threadIdx.x == 128) {
#pragma unroll
        for (int i = 0; i < NSLOT; i++) {
            mbar_init(sb + BAR_RFULL + i * 8, 1);
            mbar_init(sb + BAR_REMPTY + i * 8, 8);
            mbar_init(sb + BAR_XFULL + i * 8, 1);
            mbar_init(sb + BAR_XEMPTY + i * 8, 8);
        }
        asm volatile("fence.mbarrier_init.release.cluster;" ::: "memory");
        fence_async_smem();
    } else if (threadIdx.x == 160) {
#pragma unroll
        for (int i = 0; i < NSLOT + MAXI; i++) mbar_init(sb + BAR_PRDY + i * 8, 1);
        asm volatile("fence.mbarrier_init.release.cluster;" ::: "memory");
    } else if (threadIdx.x == 0) {
        sts_u(sb + OFF_ITEM, P.cl[cta >> 1].items[0] ? P.cl[cta >> 1].items[0] + 8 * (cta & 1) : 0);
        sts_u(sb + OFF_FB, P.cl[cta >> 1].delay);
    } else if (threadIdx.x == 64) {
        if (sb & 1023) __trap();
        asm volatile("prefetch.tensormap [%0];" ::"l"(&P.wq[0]) : "memory");
        asm volatile("prefetch.tensormap [%0];" ::"l"(&P.x[0]) : "memory");
    }
    __syncthreads();
    {
        const int it = 0;
        if (wgid == 1) TS(0, 30);
    }
    asm volatile("barrier.cluster.arrive.relaxed.aligned;" ::: "memory");
    if (warp < 3) {
        const uint32_t e = __shfl_sync(0xffffffffu, lds_u(sb + OFF_ITEM), 0), d = lds_u(sb + OFF_FB);
        const uint64_t pol = pol_shared();
        const bool isx = warp == 1, lead = (threadIdx.x & 31) == 0;
        uint32_t t0, t1;
        asm volatile("mov.u32 %0, %%clock;" : "=r"(t0));
        do {
            asm volatile("mov.u32 %0, %%clock;" : "=r"(t1));
        } while (t1 - t0 < d);
        __syncwarp();
#pragma unroll 1
        for (int n = 0; n < (e ? NPRE : 0); n++) {
            const uint32_t bar = sb + (isx ? BAR_XFULL : BAR_RFULL) + n * 8;
            if (lead) {
                if (warp < 2) mbar_expect(bar, isx ? XS : SLOT);
                tma3(sb + (isx ? OFF_R + n * XS : OFF_RING + n * SLOT + warp * (SLOT / 4)), isx ? &P.x[0] : &P.wq[0],
                     isx ? IT_B(e) * 160 : n * 64 + warp * 16, isx ? n : IT_H0(e) * 3, bar, pol);
            }
        }
        if (threadIdx.x == 0) asm volatile("mbarrier.arrive.shared::cta.b64 _, [%0];" ::"r"(sb + BAR_ITEM) : "memory");
        __syncwarp();
    }

    if (wgid == 0) {
        asm volatile("setmaxnreg.dec.sync.aligned.u32 24;");
        if (warp == 0) {
            const bool lead = threadIdx.x == 0;
            const uint64_t pol_first = pol_stream(), pol_norm = pol_shared();
            uint32_t e = __shfl_sync(0xffffffffu, lds_u(sb + OFF_ITEM), 0);
#pragma unroll 1
            for (int n = 2 * NPRE; n < (e ? 2 * NSLOT : 0); n++) {
                if (lead) {
                    if (!(n & 1)) mbar_expect(sb + BAR_RFULL + (n >> 1) * 8, SLOT);
                    tma3(sb + OFF_RING + n * (SLOT / 2), &P.wq[0], n * 32, IT_H0(e) * 3, sb + BAR_RFULL + (n >> 1) * 8, pol_norm);
                }
            }
            __syncwarp();
            asm volatile("barrier.cluster.wait.aligned;" ::: "memory");
            unsigned int* const ticket = &g_ticket[next_epoch(0) & 1];
            const uint32_t rank = cta & 1;
            uint32_t peer;
            asm volatile("mapa.shared::cluster.u32 %0, %1, %2;" : "=r"(peer) : "r"(sb), "r"(rank ^ 1));
            Ring r{0, 0, dl};
            uint32_t pm = 0;
            bool told = false;
            auto load_w = [&](const CUtensorMap* m, int row, int blk, uint32_t half_bytes, bool more) {
                auto tell = [&](uint32_t slot) {
                    if (lead) {
                        mbar_expect(sb + BAR_RFULL + slot * 8, 2 * half_bytes);
                        asm volatile("mbarrier.arrive.shared::cluster.b64 _, [%0];" ::"r"(peer + BAR_PRDY + slot * 8) : "memory");
                    }
                };
                const uint32_t slot = r.slot;
                if (!told) {
                    mbar_wait(sb + BAR_REMPTY + slot * 8, r.ph, dl);
                    tell(slot);
                }
                r.adv(1);
                told = more && mbar_test(sb + BAR_REMPTY + r.slot * 8, r.ph);
                if (told) tell(r.slot);
                mbar_wait(sb + BAR_PRDY + slot * 8, (pm >> slot) & 1, dl);
                pm ^= 1u << slot;
                if (lead) tma3_mc(sb + OFF_RING + slot * SLOT + rank * half_bytes, m, row, blk, sb + BAR_RFULL + slot * 8, pol_norm);
            };
#pragma unroll 1
            for (int it = 0; e != 0; it++) {
                uint32_t nx = 0, tk = 0;
                if (rank == 0 && IT_TYPE(e) != IT_ON && it + 2 < MAXI) nx = it + 1 < NSTAT ? P.cl[cta >> 1].items[it + 1] : IT_DYN;
                const uint32_t br = IT_BR(e);
                if (IT_TYPE(e) == IT_QA) {
                    const uint32_t h = IT_H0(e);
#pragma unroll 1
                    for (int kk = it ? 0 : NSLOT; kk < 10; kk++) load_w(&P.wq[br], kk * 64 + rank * 32, h * 3, SLOT / 2, kk < 9);
                    const int grp0 = (IT_B(e) * 32 + h) * 64;
#pragma unroll 1
                    for (int n = 0; n < 16; n++) {
                        if (n == 15 && nx == IT_DYN && lead) tk = atomicAdd(ticket, 1);
                        const bool isv = n == 15 || (n > 0 && !(n & 1));
                        const int j = n == 15 ? 7 : isv ? (n - 2) >> 1 : (n + 1) >> 1;
                        mbar_wait(sb + BAR_REMPTY + r.slot * 8, r.ph, dl);
                        if (lead) {
                            mbar_expect(sb + BAR_RFULL + r.slot * 8, SLOT);
                            asm volatile(
                                "cp.async.bulk.tensor.4d.shared::cluster.global.mbarrier::complete_tx::bytes.L2::cache_hint"
                                " [%0], [%1, {%3,%3,%3,%4}], [%2], %5;" ::"r"(sb + OFF_RING + r.slot * SLOT),
                                "l"(isv ? &P.v[br] : &P.k[br]), "r"(sb + BAR_RFULL + r.slot * 8), "r"(0), "r"(grp0 + j * 8), "l"(pol_first)
                                : "memory");
                        }
                        r.adv(1);
                    }
                } else {
                    const bool wide = IT_TYPE(e) == IT_OP;
                    const int step = wide ? 32 : 64, r1 = IT_H1(e) * 192;
#pragma unroll 1
                    for (int row = IT_H0(e) * 192 + rank * (step >> 1); row < r1; row += step)
                        load_w(wide ? &P.wo[br] : &P.won[br], row, IT_HALF(e) * (wide ? 5 : 2), wide ? XS / 2 : 8192, row + step < r1);
                    if (nx == IT_DYN && lead) tk = atomicAdd(ticket, 1);
                }
                if (rank == 0) {
                    if (nx == IT_DYN) {
                        tk = __shfl_sync(0xffffffffu, tk, 0);
                        nx = tk < P.nlist ? P.list[tk] : 0;
                    }
                    e = nx;
                    if (lead) {
                        asm volatile("st.async.weak.shared::cluster.mbarrier::complete_tx::bytes.b32 [%0], %1, [%2];" ::"r"(
                                         peer + OFF_ITEM + 4 + it * 4),
                                     "r"(e ? e + 8 : 0), "r"(peer + BAR_ITEM + 8 + it * 8)
                                     : "memory");
                        sts_u(sb + OFF_ITEM + 4 + it * 4, e);
                        asm volatile("mbarrier.arrive.shared::cta.b64 _, [%0];" ::"r"(sb + BAR_ITEM + 8 + it * 8) : "memory");
                    }
                } else {
                    if (lead) mbar_expect(sb + BAR_ITEM + 8 + it * 8, 4);
                    e = get_item_warp(sb, it + 1, dl);
                }
            }
        } else if (warp == 1) {
            const uint64_t pol_norm = pol_shared(), pol_o = pol_stream();
            const bool lead = threadIdx.x == 32;
            uint32_t phm = 32 - (1 << NPRE), epoch = 0;
#pragma unroll 1
            for (int it = 0;; it++) {
                const uint32_t e = get_item_warp(sb, it, dl);
                if (it == 1 || (it == 0 && e == 0)) epoch = next_epoch(1);
                if (e == 0) break;
                const uint32_t br = IT_BR(e);
                uint32_t xs = it ? 0 : NPRE;
                auto acquire = [&]() {
                    mbar_wait(sb + BAR_XEMPTY + xs * 8, (phm >> xs) & 1, dl);
                    phm ^= 1u << xs;
                    if (lead) mbar_expect(sb + BAR_XFULL + xs * 8, XS);
                };
                if (IT_TYPE(e) == IT_QA) {
#pragma unroll 1
                    for (int kk = xs; kk < 10; kk++) {
                        acquire();
                        if (lead) tma3(sb + OFF_R + xs * XS, &P.x[br], IT_B(e) * 160, kk, sb + BAR_XFULL + xs * 8, pol_norm);
                        if (++xs == 5) xs = 0;
                    }
                } else {
                    const unsigned int* fp = g_flag + (br * 16 + IT_B(e)) * 64 + (threadIdx.x & 31) * 2;
                    uint32_t hm = 0, pm = 0;
                    auto poll = [&](uint32_t hneed, uint32_t pneed) {
                        if ((hm & hneed) == hneed && (pm & pneed) == pneed) return;
                        uint32_t n = 0;
                        do {
                            uint32_t a, b;
                            asm volatile("ld.acquire.gpu.global.v2.u32 {%0, %1}, [%2];" : "=r"(a), "=r"(b) : "l"(fp) : "memory");
                            hm = __ballot_sync(0xffffffffu, a == epoch);
                            pm = __ballot_sync(0xffffffffu, b == epoch);
                            if (++n > 0x1000000) __trap();
                        } while ((hm & hneed) != hneed || (pm & pneed) != pneed);
                        __syncwarp();
                        asm volatile("fence.proxy.async.global;" ::: "memory");
                    };
#pragma unroll 1
                    for (uint32_t h = IT_H0(e); h < IT_H1(e); h++) {
                        const unsigned char* src = ostash(P.slot[br * 32 + h], IT_B(e));
                        poll(1u << h, 0);
#pragma unroll 1
                        for (int t = 0; t < 3; t++) {
                            acquire();
                            if (lead) bulk_load(sb + OFF_R + xs * XS, src + t * XS, XS, sb + BAR_XFULL + xs * 8, pol_o);
                            if (++xs == 5) xs = 0;
                        }
                        if (IT_TYPE(e) == IT_OP && h >= 1) {
                            const uint32_t x1 = xs == 4 ? 0 : xs + 1;
                            mbar_wait(sb + BAR_XFULL + xs * 8, (phm >> xs) & 1, dl);
                            mbar_wait(sb + BAR_XFULL + x1 * 8, (phm >> x1) & 1, dl);
                            if (lead)
                                asm volatile("red.relaxed.gpu.global.max.u32 [%0], %1;" ::"l"(fp + 5 + 2 * IT_HALF(e)), "r"(epoch * 64 + h) : "memory");
                        }
                    }
                    if (IT_TYPE(e) == IT_ON) {
                        poll(0, IT_HALF(e) < 2 ? 1 : IT_HALF(e) == 2 ? 3 : 2);
#pragma unroll 1
                        for (uint32_t tile = 2 * IT_HALF(e); tile < 2 * IT_HALF(e) + 2; tile++) {
                            acquire();
                            if (lead)
                                asm volatile(
                                    "cp.async.bulk.tensor.5d.shared::cluster.global.mbarrier::complete_tx::bytes [%0], [%1, {%3,%5,%5,%5,%4}], [%2];" ::"r"(
                                        sb + OFF_R + xs * XS),
                                    "l"(&P.out), "r"(sb + BAR_XFULL + xs * 8), "r"(br * 640 + tile * 64), "r"(IT_B(e) * 5), "r"(0)
                                    : "memory");
                            if (++xs == 5) xs = 0;
                        }
                    }
                }
            }
        } else if (warp == 2) {
            asm volatile("barrier.cluster.wait.aligned;" ::: "memory");
            const uint32_t epoch = next_epoch(2);
            if (cta == 0) g_ticket[(epoch + 1) & 1] = 0;
#pragma unroll 1
            for (int it = 0;; it++) {
                const uint32_t e = get_item_warp(sb, it, dl);
                if (e == 0) break;
                if (IT_TYPE(e) != IT_QA && threadIdx.x == 64) asm volatile("prefetch.tensormap [%0];" ::"l"(&P.out) : "memory");
                if (IT_TYPE(e) == IT_ON) break;
                nb_sync<NB_ODONE, 288>();
                if (threadIdx.x == 64) {
                    const uint32_t bb = IT_BR(e) * 16 + IT_B(e);
                    if (IT_TYPE(e) != IT_QA) {
                        asm volatile("red.relaxed.gpu.global.max.u32 [%0], %1;" ::"l"(&g_flag[bb * 64 + 5 + 2 * IT_HALF(e)]),
                                     "r"(epoch * 64 + IT_H1(e))
                                     : "memory");
#pragma unroll 1
                        for (int m = 0; m < 5; m++) {
                            out_store(P, sb + OFF_R + m * XS, IT_BR(e) * 640 + IT_HALF(e) * 320 + m * 64, IT_B(e));
                            if (m >= 1) {
                                asm volatile("cp.async.bulk.wait_group.read 1;" ::: "memory");
                                asm volatile("mbarrier.arrive.shared::cta.b64 _, [%0], 8;" ::"r"(sb + BAR_XEMPTY + (m - 1) * 8) : "memory");
                            }
                        }
                        asm volatile("cp.async.bulk.wait_group.read 0;" ::: "memory");
                        asm volatile("mbarrier.arrive.shared::cta.b64 _, [%0], 8;" ::"r"(sb + BAR_XEMPTY + 32) : "memory");
                        if (IT_PART(e)) {
                            asm volatile("cp.async.bulk.wait_group 0;" ::: "memory");
                            asm volatile("fence.proxy.async.global;" ::: "memory");
                        }
                    }
                    if (IT_TYPE(e) == IT_QA || IT_PART(e)) {
                        unsigned int* f = &g_flag[bb * 64 + (IT_TYPE(e) == IT_QA ? 2 * IT_H0(e) : 1 + 2 * IT_HALF(e))];
                        asm volatile("st.release.gpu.global.u32 [%0], %1;" ::"l"(f), "r"(epoch) : "memory");
                    }
                }
                __syncwarp();
            }
            if (threadIdx.x == 64) asm volatile("cp.async.bulk.wait_group 0;" ::: "memory");
            __syncwarp();
            asm volatile("barrier.cluster.arrive.relaxed.aligned;\nbarrier.cluster.wait.aligned;" ::: "memory");
        } else {
            const uint32_t lane = threadIdx.x & 31, p = lane >> 3;
            const uint32_t epoch = next_epoch(3);
            if (lane == 0) {
                asm volatile("prefetch.tensormap [%0];" ::"l"(&P.k[0]) : "memory");
                asm volatile("prefetch.tensormap [%0];" ::"l"(&P.v[0]) : "memory");
                asm volatile("prefetch.tensormap [%0];" ::"l"(&P.wo[0]) : "memory");
            }
#pragma unroll 1
            for (int it = 0;; it++) {
                const uint32_t e = get_item_warp(sb, it, dl);
                if (e == 0) break;
                if (IT_TYPE(e) != IT_QA) continue;
                nb_sync<NB_QK, 160>();
                const uint32_t ka = sb + OFF_RING + lds_u(sb + OFF_GM + 4) * SLOT + p * (2 * 3072 + 256) + (lane & 7) * 16;
                const uint32_t qa = sb + OFF_R + p * 256 + (lane & 7) * 16;
                uint32_t acc = 0;
#pragma unroll 1
                for (int c = 0; c < 3; c++) {
                    const uint4 k = lds_u4(ka + c * 1024);
                    if (c == 2) nb_sync<NB_L, 160>();
                    const uint4 q = lds_u4(qa + c * XS);
                    acc = fma_bf2(k.x, q.x, fma_bf2(k.y, q.y, fma_bf2(k.z, q.z, fma_bf2(k.w, q.w, acc))));
                }
                const float d = __uint_as_float(acc << 16) + __uint_as_float(acc & 0xffff0000u);
                const int sum = __reduce_add_sync(0xffffffffu, __float2int_rn(d * 16.f));
                sts_f(sb + OFF_GM, fmaf((float)sum, SM_C / 64.f, 24.f));
                nb_arrive<NB_REF, 160>();
                if (IT_DEP(e)) {
                    const uint32_t g = IT_DEP(e) - 1, need = epoch * 64 + (g & 31) + 1;
                    const unsigned int* cp = &g_flag[((g >> 5) * 16 + IT_B(e)) * 64 + 5 + 2 * (lane & 1)];
                    for (uint32_t n = 0;; n++) {
                        uint32_t v;
                        asm volatile("ld.acquire.gpu.global.u32 %0, [%1];" : "=r"(v) : "l"(cp) : "memory");
                        if (__all_sync(0xffffffffu, v - need < 64)) break;
                        if (n > 0x800000) __trap();
                        __nanosleep(500);
                    }
                }
                nb_sync<NB_L, 160>();
                bool bad = false;
#pragma unroll
                for (int c = 0; c < 5; c++) {
                    const uint32_t la = sb + OFF_LX + (c * 32 + lane) * 4;
                    const float v = (__uint_as_float(lds_u(la)) + __uint_as_float(lds_u(la + 640))) +
                                    (__uint_as_float(lds_u(la + 1280)) + __uint_as_float(lds_u(la + 1920)));
                    const float inv = __fdividef(1.f, v);
                    const uint32_t hi = pack_bf16(inv, 0.f), lo = pack_bf16(inv - __uint_as_float(hi << 16), 0.f);
                    const uint32_t ia = sb + OFF_LINV + c * 128 + ((lane >> 1) & 3) * 32 + (lane >> 3) * 8 + (lane & 1) * 2;
                    asm volatile("st.shared.u16 [%0], %1;\nst.shared.u16 [%0+4], %2;" ::"r"(ia), "h"((unsigned short)hi), "h"((unsigned short)lo) : "memory");
                    bad |= !(v >= 5.421010862e-20f && v <= 7.9228163e28f);
                }
                sts_u(sb + OFF_FB, __any_sync(0xffffffffu, bad));
                nb_arrive<NB_VOTE, 160>();
                nb_arrive<NB_VOTE + 1, 160>();
            }
        }
    } else {
        asm volatile("setmaxnreg.inc.sync.aligned.u32 240;");
        consumer(P, wgid - 1, sb, dl);
    }
}

typedef CUresult (*EncFn)(CUtensorMap*, CUtensorMapDataType, cuuint32_t, void*, const cuuint64_t*, const cuuint64_t*,
                          const cuuint32_t*, const cuuint32_t*, CUtensorMapInterleave, CUtensorMapSwizzle,
                          CUtensorMapL2promotion, CUtensorMapFloatOOBfill);

void make_map3(EncFn enc, CUtensorMap* m, void* p, uint64_t rows, uint64_t rowbytes, uint64_t nblk, uint32_t boxrows,
               uint32_t boxblk) {
    cuuint64_t dims[3] = {64, rows, nblk};
    cuuint64_t str[2] = {rowbytes, 128};
    cuuint32_t box[3] = {64, boxrows, boxblk};
    cuuint32_t es[3] = {1, 1, 1};
    enc(m, CU_TENSOR_MAP_DATA_TYPE_BFLOAT16, 3, p, dims, str, box, es, CU_TENSOR_MAP_INTERLEAVE_NONE,
        CU_TENSOR_MAP_SWIZZLE_128B, CU_TENSOR_MAP_L2_PROMOTION_NONE, CU_TENSOR_MAP_FLOAT_OOB_FILL_NONE);
}

constexpr int tune(const char*, int def) { return def; }

void build_schedule(Params& P, int ncl) {
    const int mode = tune("MODE", 4), dmax = tune("DMAX", 22300), n0 = tune("N0", 10);
    const int H0[8] = {17, 18, 20, 21, 22, 22, 23, 25}, P0[8] = {367, 338, 337, 333, 345, 349, 340, 327};
    const int ra = tune("RA", 10), ga = tune("GA", 17), rb = tune("RB", 11), g1 = tune("G1", 58);
    const int na = ncl == NCL ? tune("NA", 4) : 0;
    const int HA[5] = {tune("A0", 29), tune("A1", 29), tune("A2", 29), tune("A3", 29), tune("A4", 30)};
    int ha = 32;
    for (int b = 0; b < na; b++) ha = HA[b] < ha ? HA[b] : ha;
    int dep[64], fifo[64];
    for (int g = 0, ns = 0, head = 0, tail = 0; g < 64; g++) {
        const bool pinned = g >= ha && g < 32;
        const bool fresh = mode < 3 || pinned || g >= g1 || tail - head < (g < ga ? ra : rb);
        dep[g] = fresh ? 0 : fifo[head] + 1;
        P.slot[g] = fresh ? ns++ : P.slot[fifo[head++]];
        if (!pinned) fifo[tail++] = g;
    }
    int H[8], pos[8], psum = 0;
    for (int b = 0; b < 8; b++) {
        const char nh[3] = {'H', (char)('0' + b), 0}, np[3] = {'P', (char)('0' + b), 0};
        H[b] = tune(nh, H0[b]);
        pos[b] = tune(np, P0[b]);
        psum += pos[b];
    }
    const int sk = tune("SK", 10), g0 = tune("G0", 20), g2 = tune("G2", 40);
    int ord[512], nxt[8] = {0, 0, 0, 0, 0, 0, 0, 0};
    for (int k = 0; k < 512; k++) {
        int best = -1;
        float bkey = 0.f;
        for (int b = 0; b < 8; b++) {
            const int g = nxt[b];
            if (g == 64) continue;
            const float w = g < g0 ? 0.f : g < 32 ? (g - g0) / (32.f - g0) : g < g2 ? 1.f : (64 - g) / (64.f - g2);
            const float key = g + w * sk * 0.1f * (pos[b] - psum / 8.f) / 8.f;
            if (best < 0 || key < bkey) best = b, bkey = key;
        }
        ord[k] = nxt[best]++ * 8 + best;
        const int d = dep[ord[k] >> 3];
        if (d > 32) {
            if (pos[best] > k) pos[best] = k;
            if (H[best] < d - 32) H[best] = d - 32;
        }
    }
    int u = 0;
    auto unit = [&]() {
        const int v = ord[u++];
        return mk_item(IT_QA, v >> 8, (v & 7) * 2, (v >> 3) & 31, P.slot[v >> 3], 0) | (dep[v >> 3] << 23);
    };
    int qa[NCL], nq = 0, op[NCL], no = 0;
    for (int c = 0; c < ncl; c++) {
        P.cl[c].delay = 0;
        for (int i = 0; i < NSTAT; i++) P.cl[c].items[i] = 0;
        if (mode >= 3 && c >= 4 && c < 20) op[((c - 4) & 7) * 2 + ((c - 4) >> 3)] = c, no++;
        else if (mode != 2 || (c & 3) == 0) qa[nq++] = c;
    }
    for (int t = 0; t < no; t++) {
        P.cl[op[t]].items[1] = t / 2 < na ? mk_item(IT_OP, 0, t & ~1, 0, HA[t / 2], t & 1, 1) : mk_item(IT_OP, 0, t & ~1, 0, 32, t & 1);
        P.cl[op[t]].items[2] = IT_DYN;
            }
    for (int k = 0; k < nq; k++) {
        const int c = qa[(k * (nq % 19 ? 19 : 17)) % nq];
        P.cl[c].items[1] = P.cl[c].items[2] = IT_DYN;
        P.cl[c].delay = k < n0 ? 0 : dmax * (k + 1 - n0) / (nq - n0);
    }
    for (int t = 0; t < no; t++) P.cl[op[(t & 7) * 2 + (t >> 3)]].items[0] = unit();
    for (int k = u; k < no + nq; k++) {
        int best = -1;
        for (int c = 0; c < ncl; c++)
            if (P.cl[c].items[1] && !P.cl[c].items[0] && (best < 0 || P.cl[c].delay < P.cl[best].delay)) best = c;
        P.cl[best].items[0] = unit();
    }
    int n = 0;
    const int uend = mode == 2 ? 8 * nq : 512;
    while (u < uend) {
        for (int b = 0; b < 8 && no; b++)
            if (pos[b] == u) {
                P.list[n++] = mk_item(IT_OP, 1, 2 * b, 0, H[b], 0, 1);
                P.list[n++] = mk_item(IT_OP, 1, 2 * b, 0, H[b], 1, 1);
            }
        P.list[n++] = unit();
    }
    for (int k = 0; no && k < 40; k++) P.list[n++] = mk_item(IT_ON, 1, k / 5 * 2, H[k / 5], 32, k % 5);
    for (int k = 0; no && k < 5 * na; k++) P.list[n++] = mk_item(IT_ON, 0, k / 5 * 2, HA[k / 5], 32, k % 5);
    P.nlist = n;
}

}

extern "C" void kernel_launch(void* const* d_in, const int* in_sizes, int n_in, void* d_out, int out_size) {
    static Params P;
    static bool init = false;
    static int ncl = NCL;
    if (!init) {
        EncFn enc = nullptr;
        cudaDriverEntryPointQueryResult qr;
        cudaGetDriverEntryPoint("cuTensorMapEncodeTiled", (void**)&enc, cudaEnableDefault, &qr);
        for (int i = 0; i < 2; i++) {
            P.px[i] = (const __nv_bfloat16*)d_in[5 * i + 0];
            P.pk[i] = (const __nv_bfloat16*)d_in[5 * i + 1];
            P.pv[i] = (const __nv_bfloat16*)d_in[5 * i + 2];
            P.pwq[i] = (const __nv_bfloat16*)d_in[5 * i + 3];
            make_map3(enc, &P.x[i], d_in[5 * i + 0], 2560, 1280, 10, 160, 1);
            for (int j = 0; j < 2; j++) {
                cuuint64_t dims[4] = {64, 8, 3, 16 * 32 * 64};
                cuuint64_t str[3] = {384, 128, 3072};
                cuuint32_t box[4] = {64, 8, 3, 8};
                cuuint32_t es[4] = {1, 1, 1, 1};
                enc(j ? &P.v[i] : &P.k[i], CU_TENSOR_MAP_DATA_TYPE_BFLOAT16, 4, d_in[5 * i + 1 + j], dims, str, box, es,
                    CU_TENSOR_MAP_INTERLEAVE_NONE, CU_TENSOR_MAP_SWIZZLE_128B, CU_TENSOR_MAP_L2_PROMOTION_NONE,
                    CU_TENSOR_MAP_FLOAT_OOB_FILL_NONE);
            }
            make_map3(enc, &P.wq[i], d_in[5 * i + 3], 640, 12288, 96, 32, 3);
            make_map3(enc, &P.wo[i], d_in[5 * i + 4], 6144, 1280, 10, 16, 5);
            make_map3(enc, &P.won[i], d_in[5 * i + 4], 6144, 1280, 10, 32, 2);
        }
        cuuint64_t dims[5] = {1280, 2, 4, 4, 80};
        cuuint64_t str[4] = {2560, 8 * 2560, 2 * 2560, 32 * 2560};
        cuuint32_t box[5] = {64, 2, 4, 4, 5};
        cuuint32_t es[5] = {1, 1, 1, 1, 1};
        enc(&P.out, CU_TENSOR_MAP_DATA_TYPE_BFLOAT16, 5, d_out, dims, str, box, es, CU_TENSOR_MAP_INTERLEAVE_NONE,
            CU_TENSOR_MAP_SWIZZLE_128B, CU_TENSOR_MAP_L2_PROMOTION_NONE, CU_TENSOR_MAP_FLOAT_OOB_FILL_NONE);
        cudaFuncSetAttribute(fused_kernel, cudaFuncAttributeMaxDynamicSharedMemorySize, SMEM_LAUNCH);
        cudaLaunchConfig_t cfg = {};
        cfg.gridDim = dim3(NCTA);
        cfg.blockDim = dim3(384);
        cfg.dynamicSmemBytes = SMEM_LAUNCH;
        int nc = 0;
        if (cudaOccupancyMaxActiveClusters(&nc, fused_kernel, &cfg) == cudaSuccess && nc >= 52 && nc < NCL) ncl = nc;
        (void)cudaGetLastError();
        ncl = tune("NCL", ncl);
        build_schedule(P, ncl);
        init = true;
    }
    fused_kernel<<<2 * ncl, 384, SMEM_LAUNCH>>>(P);
}
```
